```python
import torch

def _softmax(x, axis=-1):
    return torch.softmax(x, dim=axis)
def _gelu(x):
    return torch.nn.functional.gelu(x, approximate="tanh")
def _silu(x):
    return torch.nn.functional.silu(x)
def _sigmoid(x):
    return torch.sigmoid(x)
def _layernorm(x, axis=-1, eps=1e-5):
    m = x.mean(dim=axis, keepdim=True)
    v = x.var(dim=axis, keepdim=True, unbiased=False)
    return (x - m) / torch.sqrt(v + eps)
def _scatter_add(tgt, idx, src, axis=0):
    return tgt.clone().index_add_(axis, idx, src)
def _segment_sum(src, seg, n):
    out = torch.zeros((n,) + src.shape[1:], dtype=src.dtype)
    return out.index_add_(0, seg, src)
def _pad(x, pw):
    flat = tuple(v for pair in reversed(pw) for v in pair)
    return torch.nn.functional.pad(x, flat)

kernel_name = 'concat_heads__gqa_block_cached__gqa_block_cached__near_ridge'

def setup_inputs():

    _w = (lambda a: (lambda t: t.to(torch.bfloat16) if t.is_floating_point() else t)(torch.as_tensor(a)))
    def _A_setup():
        B, Sq, D = 8, 256, 640
        Hq, Hkv, Sk, Dh = 32, 32, 1024, 192
        assert Hq % Hkv == 0, (Hq, Hkv)
        return {
            "x": _w((lambda *s: torch.randn(*s, dtype=torch.bfloat16) * 0.8)(B, Sq, D)),
            "k_cache": _w((lambda *s: torch.randn(*s, dtype=torch.bfloat16) * 0.8)(B, Hkv, Sk, Dh)),
            "v_cache": _w((lambda *s: torch.randn(*s, dtype=torch.bfloat16) * 0.05)(B, Hkv, Sk, Dh)),
            "wq": _w((lambda *s: torch.randn(*s, dtype=torch.bfloat16) * 0.8)(D, Hq * Dh) * (D ** -0.5)),
            "wo": _w((lambda *s: torch.randn(*s, dtype=torch.bfloat16) * 0.05)(Hq * Dh, D) * ((Hq * Dh) ** -0.5)),
        }
    _A_in = _A_setup()

    def _B_setup():
        B, Sq, D = 8, 256, 640
        Hq, Hkv, Sk, Dh = 32, 32, 1024, 192
        assert Hq % Hkv == 0, (Hq, Hkv)
        return {
            "x": _w((lambda *s: torch.randn(*s, dtype=torch.bfloat16) * 0.8)(B, Sq, D)),
            "k_cache": _w((lambda *s: torch.randn(*s, dtype=torch.bfloat16) * 0.8)(B, Hkv, Sk, Dh)),
            "v_cache": _w((lambda *s: torch.randn(*s, dtype=torch.bfloat16) * 0.05)(B, Hkv, Sk, Dh)),
            "wq": _w((lambda *s: torch.randn(*s, dtype=torch.bfloat16) * 0.8)(D, Hq * Dh) * (D ** -0.5)),
            "wo": _w((lambda *s: torch.randn(*s, dtype=torch.bfloat16) * 0.05)(Hq * Dh, D) * ((Hq * Dh) ** -0.5)),
        }
    _B_in = _B_setup()

    return {
        "A_x": _A_in["x"],
        "A_k_cache": _A_in["k_cache"],
        "A_v_cache": _A_in["v_cache"],
        "A_wq": _A_in["wq"],
        "A_wo": _A_in["wo"],
        "B_x": _B_in["x"],
        "B_k_cache": _B_in["k_cache"],
        "B_v_cache": _B_in["v_cache"],
        "B_wq": _B_in["wq"],
        "B_wo": _B_in["wo"],
    }

def reference(A_x, A_k_cache, A_v_cache, A_wq, A_wo, B_x, B_k_cache, B_v_cache, B_wq, B_wo):
    def _A_ref(x, k_cache, v_cache, wq, wo):
        B, Sq, D = x.shape
        Hq, Dh = 32, 192
        Hkv = k_cache.shape[1]
        rep = Hq // Hkv
        q = (lambda x, *d: x.permute(*d))((x @ wq).reshape(B, Sq, Hq, Dh), 0, 2, 1, 3)
        k = (lambda x, n, axis: torch.repeat_interleave(x, n, dim=axis))(k_cache, rep, axis=1)
        v = (lambda x, n, axis: torch.repeat_interleave(x, n, dim=axis))(v_cache, rep, axis=1)
        scores = torch.einsum("bhqd,bhkd->bhqk", q, k) * (Dh ** -0.5)
        p = _softmax(scores, axis=-1)
        o = torch.einsum("bhqk,bhkd->bhqd", p, v)
        return (lambda x, *d: x.permute(*d))(o, 0, 2, 1, 3).reshape(B, Sq, Hq * Dh) @ wo

    def _B_ref(x, k_cache, v_cache, wq, wo):
        B, Sq, D = x.shape
        Hq, Dh = 32, 192
        Hkv = k_cache.shape[1]
        rep = Hq // Hkv
        q = (lambda x, *d: x.permute(*d))((x @ wq).reshape(B, Sq, Hq, Dh), 0, 2, 1, 3)
        k = (lambda x, n, axis: torch.repeat_interleave(x, n, dim=axis))(k_cache, rep, axis=1)
        v = (lambda x, n, axis: torch.repeat_interleave(x, n, dim=axis))(v_cache, rep, axis=1)
        scores = torch.einsum("bhqd,bhkd->bhqk", q, k) * (Dh ** -0.5)
        p = _softmax(scores, axis=-1)
        o = torch.einsum("bhqk,bhkd->bhqd", p, v)
        return (lambda x, *d: x.permute(*d))(o, 0, 2, 1, 3).reshape(B, Sq, Hq * Dh) @ wo

    a = _A_ref(A_x, A_k_cache, A_v_cache, A_wq, A_wo)
    b = _B_ref(B_x, B_k_cache, B_v_cache, B_wq, B_wo)
    return torch.concatenate([a, b], axis=-1)
```

```cpp
#include <cuda_runtime.h>
#include <cuda_bf16.h>
#include <cuda.h>
#include <stdint.h>
#include <stdio.h>

namespace {

constexpr int kB = 8, kSq = 256, kD = 640, kH = 32, kSk = 1024, kDh = 192;
constexpr int kHD = kH * kDh;
constexpr uint32_t RING = 224 * 1024;
constexpr uint32_t SZ_KV = 24576;
constexpr uint32_t SZ_Q = 16384 + 24576;
constexpr uint32_t SZ_O = 16384 + 20480;
constexpr uint32_t SZ_W = 16384 + 40960;
constexpr uint32_t SZ_PARK = 49152;
constexpr uint32_t SZ_OL = SZ_O + 16384;
constexpr int NBAR = 10;
constexpr int EARLY = 3;
constexpr int TAIL = 2;
constexpr uint32_t KV_CH = 64, KV_SBO = 3072;
constexpr int SMEM_BYTES = RING + 1024 + 1024;
constexpr int N_TEAM = 16, N_CL = 66, MAX_OPS = 24, MAX_EV = 80, N_TILE = N_TEAM * kH, MAX_PARK = 128, ID_PART = N_TILE + MAX_PARK;
enum : uint32_t { OP_END = 0, OP_Q = 1, OP_A = 2, OP_O = 3, F_PARK = 1 << 11,
                  C_WIDE = 1 << 14, C_PEND = 1 << 26, C_SOON = 1 << 28, C_LD = 1 << 29, C_ST = 1 << 30,
                  P_GATE = 1 << 12, P_WIDE = 1 << 11, P_LD = 1 << 12, P_ST = 1 << 21, P_PRE = 1 << 22, I_NEXT = 8, E_ON = 1 << 15, E_FREE = 1 << 14, E_LAST = 1 << 13 };

#define FDRAIN 2
#define PUBNS 100
#define WATNS 100
constexpr uint32_t DBG_DEFAULT = 0x101833;

struct alignas(64) Params {
  uint16_t first[96];
  CUtensorMap x[2], wq[2], k[2], v[2], wo[2], out;
  struct {
    uint32_t c[MAX_OPS];
    uint32_t p[MAX_OPS];
    uint16_t ev[MAX_EV];
  } prog[N_CL];
  uint16_t slot[N_TILE];
  uint8_t info[ID_PART];
  uint32_t dbg;
};

__device__ uint4 g_t[N_TILE * 2 * 3072];
__device__ uint4 g_part[N_TEAM * 4 * 2 * 5120];
__device__ unsigned int g_flag[(ID_PART + N_TEAM * 4) * 2];

template <int TB, int TA = 0>
__device__ __forceinline__ void wgmma_ss_n64(float (&d)[32], uint64_t da, uint64_t db, int scale_d) {
  asm volatile("{\n.reg .pred p;\nsetp.ne.b32 p, %34, 0;\n"
    "wgmma.mma_async.sync.aligned.m64n64k16.f32.bf16.bf16 {%0, %1, %2, %3, %4, %5, %6, %7, %8, %9, %10, %11, %12, %13, %14, %15, %16, %17, %18, %19, %20, %21, %22, %23, %24, %25, %26, %27, %28, %29, %30, %31}, %32, %33, p, 1, 1, %35, %36;\n}\n"
    : "+f"(d[0]), "+f"(d[1]), "+f"(d[2]), "+f"(d[3]), "+f"(d[4]), "+f"(d[5]), "+f"(d[6]), "+f"(d[7]), "+f"(d[8]), "+f"(d[9]), "+f"(d[10]), "+f"(d[11]), "+f"(d[12]), "+f"(d[13]), "+f"(d[14]), "+f"(d[15]), "+f"(d[16]), "+f"(d[17]), "+f"(d[18]), "+f"(d[19]), "+f"(d[20]), "+f"(d[21]), "+f"(d[22]), "+f"(d[23]), "+f"(d[24]), "+f"(d[25]), "+f"(d[26]), "+f"(d[27]), "+f"(d[28]), "+f"(d[29]), "+f"(d[30]), "+f"(d[31])
    : "l"(da), "l"(db), "r"(scale_d), "n"(TA), "n"(TB));
}
template <int TB>
__device__ __forceinline__ void wgmma_rs_n64(float (&d)[32], uint32_t a0, uint32_t a1, uint32_t a2, uint32_t a3, uint64_t db, int scale_d) {
  asm volatile("{\n.reg .pred p;\nsetp.ne.b32 p, %37, 0;\n"
    "wgmma.mma_async.sync.aligned.m64n64k16.f32.bf16.bf16 {%0, %1, %2, %3, %4, %5, %6, %7, %8, %9, %10, %11, %12, %13, %14, %15, %16, %17, %18, %19, %20, %21, %22, %23, %24, %25, %26, %27, %28, %29, %30, %31}, {%32, %33, %34, %35}, %36, p, 1, 1, %38;\n}\n"
    : "+f"(d[0]), "+f"(d[1]), "+f"(d[2]), "+f"(d[3]), "+f"(d[4]), "+f"(d[5]), "+f"(d[6]), "+f"(d[7]), "+f"(d[8]), "+f"(d[9]), "+f"(d[10]), "+f"(d[11]), "+f"(d[12]), "+f"(d[13]), "+f"(d[14]), "+f"(d[15]), "+f"(d[16]), "+f"(d[17]), "+f"(d[18]), "+f"(d[19]), "+f"(d[20]), "+f"(d[21]), "+f"(d[22]), "+f"(d[23]), "+f"(d[24]), "+f"(d[25]), "+f"(d[26]), "+f"(d[27]), "+f"(d[28]), "+f"(d[29]), "+f"(d[30]), "+f"(d[31])
    : "r"(a0), "r"(a1), "r"(a2), "r"(a3), "l"(db), "r"(scale_d), "n"(TB));
}
template <int TB, int TA = 0>
__device__ __forceinline__ void wgmma_ss_n160(float (&d)[80], uint64_t da, uint64_t db, int scale_d) {
  asm volatile("{\n.reg .pred p;\nsetp.ne.b32 p, %82, 0;\n"
    "wgmma.mma_async.sync.aligned.m64n160k16.f32.bf16.bf16 {%0, %1, %2, %3, %4, %5, %6, %7, %8, %9, %10, %11, %12, %13, %14, %15, %16, %17, %18, %19, %20, %21, %22, %23, %24, %25, %26, %27, %28, %29, %30, %31, %32, %33, %34, %35, %36, %37, %38, %39, %40, %41, %42, %43, %44, %45, %46, %47, %48, %49, %50, %51, %52, %53, %54, %55, %56, %57, %58, %59, %60, %61, %62, %63, %64, %65, %66, %67, %68, %69, %70, %71, %72, %73, %74, %75, %76, %77, %78, %79}, %80, %81, p, 1, 1, %83, %84;\n}\n"
    : "+f"(d[0]), "+f"(d[1]), "+f"(d[2]), "+f"(d[3]), "+f"(d[4]), "+f"(d[5]), "+f"(d[6]), "+f"(d[7]), "+f"(d[8]), "+f"(d[9]), "+f"(d[10]), "+f"(d[11]), "+f"(d[12]), "+f"(d[13]), "+f"(d[14]), "+f"(d[15]), "+f"(d[16]), "+f"(d[17]), "+f"(d[18]), "+f"(d[19]), "+f"(d[20]), "+f"(d[21]), "+f"(d[22]), "+f"(d[23]), "+f"(d[24]), "+f"(d[25]), "+f"(d[26]), "+f"(d[27]), "+f"(d[28]), "+f"(d[29]), "+f"(d[30]), "+f"(d[31]), "+f"(d[32]), "+f"(d[33]), "+f"(d[34]), "+f"(d[35]), "+f"(d[36]), "+f"(d[37]), "+f"(d[38]), "+f"(d[39]), "+f"(d[40]), "+f"(d[41]), "+f"(d[42]), "+f"(d[43]), "+f"(d[44]), "+f"(d[45]), "+f"(d[46]), "+f"(d[47]), "+f"(d[48]), "+f"(d[49]), "+f"(d[50]), "+f"(d[51]), "+f"(d[52]), "+f"(d[53]), "+f"(d[54]), "+f"(d[55]), "+f"(d[56]), "+f"(d[57]), "+f"(d[58]), "+f"(d[59]), "+f"(d[60]), "+f"(d[61]), "+f"(d[62]), "+f"(d[63]), "+f"(d[64]), "+f"(d[65]), "+f"(d[66]), "+f"(d[67]), "+f"(d[68]), "+f"(d[69]), "+f"(d[70]), "+f"(d[71]), "+f"(d[72]), "+f"(d[73]), "+f"(d[74]), "+f"(d[75]), "+f"(d[76]), "+f"(d[77]), "+f"(d[78]), "+f"(d[79])
    : "l"(da), "l"(db), "r"(scale_d), "n"(TA), "n"(TB));
}
template <int TB>
__device__ __forceinline__ void wgmma_rs_n160(float (&d)[80], uint32_t a0, uint32_t a1, uint32_t a2, uint32_t a3, uint64_t db, int scale_d) {
  asm volatile("{\n.reg .pred p;\nsetp.ne.b32 p, %85, 0;\n"
    "wgmma.mma_async.sync.aligned.m64n160k16.f32.bf16.bf16 {%0, %1, %2, %3, %4, %5, %6, %7, %8, %9, %10, %11, %12, %13, %14, %15, %16, %17, %18, %19, %20, %21, %22, %23, %24, %25, %26, %27, %28, %29, %30, %31, %32, %33, %34, %35, %36, %37, %38, %39, %40, %41, %42, %43, %44, %45, %46, %47, %48, %49, %50, %51, %52, %53, %54, %55, %56, %57, %58, %59, %60, %61, %62, %63, %64, %65, %66, %67, %68, %69, %70, %71, %72, %73, %74, %75, %76, %77, %78, %79}, {%80, %81, %82, %83}, %84, p, 1, 1, %86;\n}\n"
    : "+f"(d[0]), "+f"(d[1]), "+f"(d[2]), "+f"(d[3]), "+f"(d[4]), "+f"(d[5]), "+f"(d[6]), "+f"(d[7]), "+f"(d[8]), "+f"(d[9]), "+f"(d[10]), "+f"(d[11]), "+f"(d[12]), "+f"(d[13]), "+f"(d[14]), "+f"(d[15]), "+f"(d[16]), "+f"(d[17]), "+f"(d[18]), "+f"(d[19]), "+f"(d[20]), "+f"(d[21]), "+f"(d[22]), "+f"(d[23]), "+f"(d[24]), "+f"(d[25]), "+f"(d[26]), "+f"(d[27]), "+f"(d[28]), "+f"(d[29]), "+f"(d[30]), "+f"(d[31]), "+f"(d[32]), "+f"(d[33]), "+f"(d[34]), "+f"(d[35]), "+f"(d[36]), "+f"(d[37]), "+f"(d[38]), "+f"(d[39]), "+f"(d[40]), "+f"(d[41]), "+f"(d[42]), "+f"(d[43]), "+f"(d[44]), "+f"(d[45]), "+f"(d[46]), "+f"(d[47]), "+f"(d[48]), "+f"(d[49]), "+f"(d[50]), "+f"(d[51]), "+f"(d[52]), "+f"(d[53]), "+f"(d[54]), "+f"(d[55]), "+f"(d[56]), "+f"(d[57]), "+f"(d[58]), "+f"(d[59]), "+f"(d[60]), "+f"(d[61]), "+f"(d[62]), "+f"(d[63]), "+f"(d[64]), "+f"(d[65]), "+f"(d[66]), "+f"(d[67]), "+f"(d[68]), "+f"(d[69]), "+f"(d[70]), "+f"(d[71]), "+f"(d[72]), "+f"(d[73]), "+f"(d[74]), "+f"(d[75]), "+f"(d[76]), "+f"(d[77]), "+f"(d[78]), "+f"(d[79])
    : "r"(a0), "r"(a1), "r"(a2), "r"(a3), "l"(db), "r"(scale_d), "n"(TB));
}
template <int TB, int TA = 0>
__device__ __forceinline__ void wgmma_ss_n192(float (&d)[96], uint64_t da, uint64_t db, int scale_d) {
  asm volatile("{\n.reg .pred p;\nsetp.ne.b32 p, %98, 0;\n"
    "wgmma.mma_async.sync.aligned.m64n192k16.f32.bf16.bf16 {%0, %1, %2, %3, %4, %5, %6, %7, %8, %9, %10, %11, %12, %13, %14, %15, %16, %17, %18, %19, %20, %21, %22, %23, %24, %25, %26, %27, %28, %29, %30, %31, %32, %33, %34, %35, %36, %37, %38, %39, %40, %41, %42, %43, %44, %45, %46, %47, %48, %49, %50, %51, %52, %53, %54, %55, %56, %57, %58, %59, %60, %61, %62, %63, %64, %65, %66, %67, %68, %69, %70, %71, %72, %73, %74, %75, %76, %77, %78, %79, %80, %81, %82, %83, %84, %85, %86, %87, %88, %89, %90, %91, %92, %93, %94, %95}, %96, %97, p, 1, 1, %99, %100;\n}\n"
    : "+f"(d[0]), "+f"(d[1]), "+f"(d[2]), "+f"(d[3]), "+f"(d[4]), "+f"(d[5]), "+f"(d[6]), "+f"(d[7]), "+f"(d[8]), "+f"(d[9]), "+f"(d[10]), "+f"(d[11]), "+f"(d[12]), "+f"(d[13]), "+f"(d[14]), "+f"(d[15]), "+f"(d[16]), "+f"(d[17]), "+f"(d[18]), "+f"(d[19]), "+f"(d[20]), "+f"(d[21]), "+f"(d[22]), "+f"(d[23]), "+f"(d[24]), "+f"(d[25]), "+f"(d[26]), "+f"(d[27]), "+f"(d[28]), "+f"(d[29]), "+f"(d[30]), "+f"(d[31]), "+f"(d[32]), "+f"(d[33]), "+f"(d[34]), "+f"(d[35]), "+f"(d[36]), "+f"(d[37]), "+f"(d[38]), "+f"(d[39]), "+f"(d[40]), "+f"(d[41]), "+f"(d[42]), "+f"(d[43]), "+f"(d[44]), "+f"(d[45]), "+f"(d[46]), "+f"(d[47]), "+f"(d[48]), "+f"(d[49]), "+f"(d[50]), "+f"(d[51]), "+f"(d[52]), "+f"(d[53]), "+f"(d[54]), "+f"(d[55]), "+f"(d[56]), "+f"(d[57]), "+f"(d[58]), "+f"(d[59]), "+f"(d[60]), "+f"(d[61]), "+f"(d[62]), "+f"(d[63]), "+f"(d[64]), "+f"(d[65]), "+f"(d[66]), "+f"(d[67]), "+f"(d[68]), "+f"(d[69]), "+f"(d[70]), "+f"(d[71]), "+f"(d[72]), "+f"(d[73]), "+f"(d[74]), "+f"(d[75]), "+f"(d[76]), "+f"(d[77]), "+f"(d[78]), "+f"(d[79]), "+f"(d[80]), "+f"(d[81]), "+f"(d[82]), "+f"(d[83]), "+f"(d[84]), "+f"(d[85]), "+f"(d[86]), "+f"(d[87]), "+f"(d[88]), "+f"(d[89]), "+f"(d[90]), "+f"(d[91]), "+f"(d[92]), "+f"(d[93]), "+f"(d[94]), "+f"(d[95])
    : "l"(da), "l"(db), "r"(scale_d), "n"(TA), "n"(TB));
}
template <int TB>
__device__ __forceinline__ void wgmma_rs_n192(float (&d)[96], uint32_t a0, uint32_t a1, uint32_t a2, uint32_t a3, uint64_t db, int scale_d) {
  asm volatile("{\n.reg .pred p;\nsetp.ne.b32 p, %101, 0;\n"
    "wgmma.mma_async.sync.aligned.m64n192k16.f32.bf16.bf16 {%0, %1, %2, %3, %4, %5, %6, %7, %8, %9, %10, %11, %12, %13, %14, %15, %16, %17, %18, %19, %20, %21, %22, %23, %24, %25, %26, %27, %28, %29, %30, %31, %32, %33, %34, %35, %36, %37, %38, %39, %40, %41, %42, %43, %44, %45, %46, %47, %48, %49, %50, %51, %52, %53, %54, %55, %56, %57, %58, %59, %60, %61, %62, %63, %64, %65, %66, %67, %68, %69, %70, %71, %72, %73, %74, %75, %76, %77, %78, %79, %80, %81, %82, %83, %84, %85, %86, %87, %88, %89, %90, %91, %92, %93, %94, %95}, {%96, %97, %98, %99}, %100, p, 1, 1, %102;\n}\n"
    : "+f"(d[0]), "+f"(d[1]), "+f"(d[2]), "+f"(d[3]), "+f"(d[4]), "+f"(d[5]), "+f"(d[6]), "+f"(d[7]), "+f"(d[8]), "+f"(d[9]), "+f"(d[10]), "+f"(d[11]), "+f"(d[12]), "+f"(d[13]), "+f"(d[14]), "+f"(d[15]), "+f"(d[16]), "+f"(d[17]), "+f"(d[18]), "+f"(d[19]), "+f"(d[20]), "+f"(d[21]), "+f"(d[22]), "+f"(d[23]), "+f"(d[24]), "+f"(d[25]), "+f"(d[26]), "+f"(d[27]), "+f"(d[28]), "+f"(d[29]), "+f"(d[30]), "+f"(d[31]), "+f"(d[32]), "+f"(d[33]), "+f"(d[34]), "+f"(d[35]), "+f"(d[36]), "+f"(d[37]), "+f"(d[38]), "+f"(d[39]), "+f"(d[40]), "+f"(d[41]), "+f"(d[42]), "+f"(d[43]), "+f"(d[44]), "+f"(d[45]), "+f"(d[46]), "+f"(d[47]), "+f"(d[48]), "+f"(d[49]), "+f"(d[50]), "+f"(d[51]), "+f"(d[52]), "+f"(d[53]), "+f"(d[54]), "+f"(d[55]), "+f"(d[56]), "+f"(d[57]), "+f"(d[58]), "+f"(d[59]), "+f"(d[60]), "+f"(d[61]), "+f"(d[62]), "+f"(d[63]), "+f"(d[64]), "+f"(d[65]), "+f"(d[66]), "+f"(d[67]), "+f"(d[68]), "+f"(d[69]), "+f"(d[70]), "+f"(d[71]), "+f"(d[72]), "+f"(d[73]), "+f"(d[74]), "+f"(d[75]), "+f"(d[76]), "+f"(d[77]), "+f"(d[78]), "+f"(d[79]), "+f"(d[80]), "+f"(d[81]), "+f"(d[82]), "+f"(d[83]), "+f"(d[84]), "+f"(d[85]), "+f"(d[86]), "+f"(d[87]), "+f"(d[88]), "+f"(d[89]), "+f"(d[90]), "+f"(d[91]), "+f"(d[92]), "+f"(d[93]), "+f"(d[94]), "+f"(d[95])
    : "r"(a0), "r"(a1), "r"(a2), "r"(a3), "l"(db), "r"(scale_d), "n"(TB));
}

__device__ __forceinline__ uint32_t smem_u32(const void* p) { return (uint32_t)__cvta_generic_to_shared(p); }
__device__ __forceinline__ void wg_fence() { asm volatile("wgmma.fence.sync.aligned;" ::: "memory"); }
__device__ __forceinline__ void wg_commit() { asm volatile("wgmma.commit_group.sync.aligned;" ::: "memory"); }
template <int N> __device__ __forceinline__ void wg_wait() { asm volatile("wgmma.wait_group.sync.aligned %0;" ::"n"(N) : "memory"); }
__device__ __forceinline__ void sched_fence(uint32_t& keep, bool never) {
  asm volatile("{\n.reg .pred p;\nsetp.ne.b32 p, %1, 0;\n@p mov.u32 %0, %%clock;\n}\n" : "+r"(keep) : "r"((int)never) : "memory");
}
template <int N> __device__ __forceinline__ void fence_regs(float (&r)[N]) {
#pragma unroll
  for (int i = 0; i < N; i++) asm volatile("" : "+f"(r[i])::"memory");
}
template <int N> __device__ __forceinline__ void undefine(float (&r)[N]) {
#pragma unroll
  for (int i = 0; i < N; i++) asm volatile("" : "=f"(r[i]));
}
template <int N> __device__ __forceinline__ void fence_regs(uint32_t (&r)[N]) {
#pragma unroll
  for (int i = 0; i < N; i++) asm volatile("" : "+r"(r[i])::"memory");
}
__device__ __forceinline__ uint64_t mk_desc(uint32_t a16, uint32_t lbo, uint32_t sbo, uint32_t swz) {
  uint64_t d;
  asm("mov.b64 %0, {%1, %2};" : "=l"(d) : "r"(a16 + ((lbo >> 4) << 16)), "r"((sbo >> 4) | (swz << 30)));
  return d;
}
__device__ __forceinline__ void mbar_init(uint32_t bar, uint32_t cnt) {
  asm volatile("mbarrier.init.shared::cta.b64 [%0], %1;" ::"r"(bar), "r"(cnt) : "memory");
}
__device__ __forceinline__ void mbar_expect(uint32_t bar, uint32_t tx) {
  asm volatile("mbarrier.arrive.expect_tx.shared::cta.b64 _, [%0], %1;" ::"r"(bar), "r"(tx) : "memory");
}
__device__ __forceinline__ bool mbar_test(uint32_t bar, uint32_t ph) {
  uint32_t ok;
  asm volatile("{\n.reg .pred p;\nmbarrier.test_wait.parity.shared::cta.b64 p, [%1], %2;\nselp.u32 %0, 1, 0, p;\n}\n"
               : "=r"(ok) : "r"(bar), "r"(ph) : "memory");
  return ok;
}
__device__ __forceinline__ void mbar_wait(uint32_t bar, uint32_t ph) {
  asm volatile("{\n.reg .pred p;\n.reg .u32 n;\n"
               "mbarrier.try_wait.parity.shared::cta.b64 p, [%0], %1;\n@p bra DONE;\n"
               "mov.u32 n, 0;\n"
               "LOOP:\nmbarrier.try_wait.parity.shared::cta.b64 p, [%0], %1;\n@p bra DONE;\n"
               "add.u32 n, n, 1;\nsetp.lt.u32 p, n, 0x1000000;\n@p bra LOOP;\ntrap;\n"
               "DONE:\n}\n" ::"r"(bar), "r"(ph) : "memory");
}
template <int NS> __device__ __forceinline__ void mbar_wait_slow(uint32_t bar, uint32_t ph) {
  asm volatile("{\n.reg .pred p;\n.reg .u32 n;\nmov.u32 n, 0;\n"
               "LOOP:\nmbarrier.test_wait.parity.shared::cta.b64 p, [%0], %1;\n@p bra DONE;\n"
               "nanosleep.u32 %2;\nadd.u32 n, n, 1;\nsetp.lt.u32 p, n, 0x400000;\n@p bra LOOP;\ntrap;\n"
               "DONE:\n}\n" ::"r"(bar), "r"(ph), "n"(NS) : "memory");
}
__device__ __forceinline__ void mbar_arrive_cluster_if(bool on, uint32_t addr) {
  asm volatile("{\n.reg .pred p;\nsetp.ne.b32 p, %1, 0;\n@p mbarrier.arrive.shared::cluster.b64 _, [%0];\n}\n" ::"r"(addr), "r"((int)on) : "memory");
}
__device__ __forceinline__ void tma2d(uint32_t dst, const CUtensorMap* m, uint32_t bar, int c0, int c1) {
  asm volatile("cp.async.bulk.tensor.2d.shared::cluster.global.mbarrier::complete_tx::bytes [%0], [%1, {%3, %4}], [%2];"
               ::"r"(dst), "l"(m), "r"(bar), "r"(c0), "r"(c1) : "memory");
}
__device__ __forceinline__ void tma3d(uint32_t dst, const CUtensorMap* m, uint32_t bar, int c0, int c1, int c2) {
  asm volatile("cp.async.bulk.tensor.3d.shared::cluster.global.mbarrier::complete_tx::bytes [%0], [%1, {%3, %4, %5}], [%2];"
               ::"r"(dst), "l"(m), "r"(bar), "r"(c0), "r"(c1), "r"(c2) : "memory");
}
__device__ __forceinline__ void tma3d_mc(uint32_t dst, const CUtensorMap* m, uint32_t bar, int c0, int c1, int c2) {
  asm volatile("cp.async.bulk.tensor.3d.shared::cluster.global.mbarrier::complete_tx::bytes.multicast::cluster"
               " [%0], [%1, {%3, %4, %5}], [%2], %6;"
               ::"r"(dst), "l"(m), "r"(bar), "r"(c0), "r"(c1), "r"(c2), "h"((uint16_t)3) : "memory");
}
__device__ __forceinline__ void tma3d_store(const CUtensorMap* m, uint32_t src, int c0, int c1, int c2) {
  asm volatile("cp.async.bulk.tensor.3d.global.shared::cta.bulk_group [%0, {%2, %3, %4}], [%1];"
               ::"l"(m), "r"(src), "r"(c0), "r"(c1), "r"(c2) : "memory");
}
__device__ __forceinline__ void bar_sync(int id, int n) { asm volatile("bar.sync %0, %1;" ::"r"(id), "r"(n) : "memory"); }
__device__ __forceinline__ uint32_t pack_bf16(float lo, float hi) {
  uint32_t r;
  asm("cvt.rn.bf16x2.f32 %0, %1, %2;" : "=r"(r) : "f"(hi), "f"(lo));
  return r;
}
__device__ __forceinline__ float ex2(float x) {
  float y;
  asm("ex2.approx.ftz.f32 %0, %1;" : "=f"(y) : "f"(x));
  return y;
}
__device__ __forceinline__ float rcp(float x) {
  float y;
  asm("rcp.approx.ftz.f32 %0, %1;" : "=f"(y) : "f"(x));
  return y;
}
__device__ __forceinline__ void stsm4(uint32_t addr, uint32_t a, uint32_t b, uint32_t c, uint32_t d) {
  asm volatile("stmatrix.sync.aligned.m8n8.x4.shared.b16 [%0], {%1, %2, %3, %4};" ::"r"(addr), "r"(a), "r"(b), "r"(c), "r"(d) : "memory");
}

__device__ __forceinline__ void tma4d_mc_hint(uint32_t dst, const CUtensorMap* m, uint32_t bar, int c3, uint64_t pol) {
  asm volatile("cp.async.bulk.tensor.4d.shared::cluster.global.mbarrier::complete_tx::bytes.multicast::cluster.L2::cache_hint"
               " [%0], [%1, {%3, %3, %3, %4}], [%2], %5, %6;"
               ::"r"(dst), "l"(m), "r"(bar), "r"(0), "r"(c3), "h"((uint16_t)3), "l"(pol) : "memory");
}
__device__ __forceinline__ void tma5d_mc(uint32_t dst, const CUtensorMap* m, uint32_t bar, int c2, int c4) {
  asm volatile("cp.async.bulk.tensor.5d.shared::cluster.global.mbarrier::complete_tx::bytes.multicast::cluster"
               " [%0], [%1, {%3, %3, %4, %3, %5}], [%2], %6;"
               ::"r"(dst), "l"(m), "r"(bar), "r"(0), "r"(c2), "r"(c4), "h"((uint16_t)3) : "memory");
}
__device__ __forceinline__ void bulk_load_hint(uint32_t dst, const void* src, uint32_t bytes, uint32_t bar, uint64_t pol) {
  asm volatile("cp.async.bulk.shared::cluster.global.mbarrier::complete_tx::bytes.L2::cache_hint [%0], [%1], %2, [%3], %4;"
               ::"r"(dst), "l"(src), "r"(bytes), "r"(bar), "l"(pol) : "memory");
}
__device__ __forceinline__ void stg128_hint(void* p, uint32_t a, uint32_t b, uint32_t c, uint32_t d, uint64_t pol) {
  asm volatile("st.global.L2::cache_hint.v4.b32 [%0], {%1, %2, %3, %4}, %5;" ::"l"(p), "r"(a), "r"(b), "r"(c), "r"(d), "l"(pol) : "memory");
}
__device__ __forceinline__ void stg2_if(bool on, void* p, uint32_t a, uint32_t b, uint32_t c, uint32_t d, uint32_t e, uint32_t f,
                                        uint32_t g, uint32_t h, uint64_t pol) {
  asm volatile("{\n.reg .pred p;\nsetp.ne.b32 p, %10, 0;\n"
               "@p st.global.L2::cache_hint.v4.b32 [%0], {%1, %2, %3, %4}, %9;\n"
               "@p st.global.L2::cache_hint.v4.b32 [%0 + 512], {%5, %6, %7, %8}, %9;\n}\n"
               ::"l"(p), "r"(a), "r"(b), "r"(c), "r"(d), "r"(e), "r"(f), "r"(g), "r"(h), "l"(pol), "r"((int)on) : "memory");
}
__device__ __forceinline__ uint64_t make_policy(bool first) {
  uint64_t pf, pn;
  asm("createpolicy.fractional.L2::evict_first.b64 %0, 1.0;" : "=l"(pf));
  asm("createpolicy.fractional.L2::evict_normal.b64 %0, 1.0;" : "=l"(pn));
  return first ? pf : pn;
}
__device__ __forceinline__ bool elect() {
  uint32_t ok;
  asm volatile("{\n.reg .pred p;\nelect.sync _|p, 0xffffffff;\nselp.u32 %0, 1, 0, p;\n}\n" : "=r"(ok));
  return ok;
}
__device__ __forceinline__ void mbar_arrive(uint32_t bar) {
  asm volatile("mbarrier.arrive.shared::cta.b64 _, [%0];" ::"r"(bar) : "memory");
}
__device__ __forceinline__ void mbar_arrive_if(bool on, uint32_t bar) {
  asm volatile("{\n.reg .pred p;\nsetp.ne.b32 p, %1, 0;\n@p mbarrier.arrive.shared::cta.b64 _, [%0];\n}\n" ::"r"(bar), "r"((int)on) : "memory");
}
__device__ __forceinline__ void stg128(void* p, uint32_t a, uint32_t b, uint32_t c, uint32_t d) {
  asm volatile("st.global.v4.b32 [%0], {%1, %2, %3, %4};" ::"l"(p), "r"(a), "r"(b), "r"(c), "r"(d) : "memory");
}
__device__ __forceinline__ void lds128(uint32_t p, uint32_t& a, uint32_t& b, uint32_t& c, uint32_t& d) {
  asm volatile("ld.shared.v4.b32 {%0, %1, %2, %3}, [%4];" : "=r"(a), "=r"(b), "=r"(c), "=r"(d) : "r"(p) : "memory");
}
template <class T> __device__ __forceinline__ T* ptr_add(T* base, uint32_t bytes) {
  T* r;
  asm("{\n.reg .u32 lo, hi;\nmov.b64 {lo, hi}, %1;\nadd.cc.u32 lo, lo, %2;\naddc.u32 hi, hi, 0;\nmov.b64 %0, {lo, hi};\n}\n" : "=l"(r) : "l"(base), "r"(bytes));
  return r;
}
__device__ __forceinline__ uint32_t flag_get(const unsigned int* p) {
  uint32_t v;
  asm volatile("ld.acquire.gpu.global.u32 %0, [%1];" : "=r"(v) : "l"(p) : "memory");
  return v;
}
__device__ __forceinline__ void wait_progress(uint32_t p, uint32_t target) {
  asm volatile("{\n.reg .pred p;\n.reg .u32 n, v;\nmov.u32 n, 0;\n"
               "LOOP:\nld.acquire.cta.shared.u32 v, [%0];\nsetp.ge.u32 p, v, %1;\n@p bra DONE;\n"
               "nanosleep.u32 %2;\nadd.u32 n, n, 1;\nsetp.lt.u32 p, n, 0x400000;\n@p bra LOOP;\ntrap;\n"
               "DONE:\n}\n" ::"r"(p), "r"(target), "n"(400) : "memory");
}
__device__ __forceinline__ void flag_set(unsigned int* p, uint32_t v) {
  asm volatile("st.release.gpu.global.u32 [%0], %1;" ::"l"(p), "r"(v) : "memory");
}
__device__ __forceinline__ void flag_dec(unsigned int* p) {
  asm volatile("red.relaxed.gpu.global.add.u32 [%0], 0xffffffff;" ::"l"(p) : "memory");
}

struct Cursor {
  int bi;
  uint32_t ph;
  __device__ __forceinline__ void next() {
    if (++bi == NBAR) { bi = 0; ph ^= 1; }
  }
};

constexpr float kScaleLog2 = 0.07216878364870322f * 1.4426950408889634f;
constexpr float kSumLimit = 1048576.0f;

__global__ void __cluster_dims__(2, 1, 1) __launch_bounds__(384, 1)
fused_kernel(const __grid_constant__ Params P) {
  extern __shared__ uint8_t smem_raw[];
  const uint32_t sbase = (smem_u32(smem_raw) + 1023) & ~1023u;
  const uint32_t full0 = sbase + RING, empty0 = full0 + 8 * NBAR, odone0 = empty0 + 8 * NBAR, ev0 = odone0 + 8 * MAX_OPS;
  const uint32_t progress = ev0 + 8 * MAX_EV;
  const uint32_t rank = blockIdx.x & 1;
  const int role = blockIdx.x >> 1;
  const int wid = __shfl_sync(0xffffffffu, (int)(threadIdx.x >> 5), 0);
  const int wg = wid >> 2;

  const uint32_t op0 = P.first[role];
  if (__builtin_expect(wid == 8, 1)) {
    if (elect()) {
#pragma unroll
      for (int k = 0; k < EARLY; k++) mbar_init(full0 + 8 * k, 1);
      asm volatile("fence.mbarrier_init.release.cluster;" ::: "memory");
      const int blk = (op0 >> 10) & 1;
      if ((op0 & 3) == OP_Q) {
#pragma unroll
        for (int k = 0; k < EARLY; k++) {
          mbar_expect(full0 + 8 * k, SZ_Q);
          tma2d(sbase + k * SZ_Q, &P.x[blk], full0 + 8 * k, 64 * k, ((op0 >> 7) & 7) * kSq + rank * 128);
          tma3d(sbase + k * SZ_Q + 16384, &P.wq[blk], full0 + 8 * k, 0, 64 * k, 3 * ((op0 >> 2) & 31));
        }
      }
      asm volatile("prefetch.tensormap [%0];" ::"l"(rank ? &P.v[blk] : &P.k[blk]) : "memory");
    }
  } else if (wg < 2 && elect()) {
#pragma unroll
    for (int j = 0; j < 16; j++) {
      const int i = EARLY + 16 * wid + j;
      if (i < 2 * NBAR + MAX_OPS + MAX_EV) mbar_init(full0 + 8 * i, i < NBAR ? 1 : i < 2 * NBAR ? 16 : i < 2 * NBAR + MAX_OPS ? 8 : 1);
    }
    if (wid == 7) asm volatile("st.shared.u32 [%0], 0;\nfence.acq_rel.cta;" ::"r"(progress) : "memory");
    asm volatile("fence.mbarrier_init.release.cluster;" ::: "memory");
  }
  __syncwarp();
  asm volatile("barrier.cluster.arrive.relaxed.aligned;\nbarrier.cluster.wait.aligned;" ::: "memory");

  if (wg == 2) {
    asm volatile("setmaxnreg.dec.sync.aligned.u32 24;");
    const uint32_t* prog = P.prog[role].p;
    unsigned int* flag = g_flag + rank;
    if (wid == 8) {
      Cursor tail{0, 0};
      int head = 0, sh = 0;
      uint32_t cur = 0, used = 0;
      uint64_t fifo = 0;
      uint32_t dst, bar, ev = ev0, done = 0;
      uint64_t pol;
      asm volatile("createpolicy.fractional.L2::evict_first.b64 %0, 1.0;" : "=l"(pol));
      auto retire = [&]() {
        mbar_wait(empty0 + 8 * tail.bi, tail.ph);
        tail.next();
        used -= (uint32_t)fifo & 31;
        fifo >>= 5;
        sh -= 5;
        asm volatile("st.volatile.shared.u32 [%0], %1;" ::"r"(progress), "r"(++done) : "memory");
      };
      auto acquire = [&](uint32_t bytes) {
        uint32_t fp = bytes >> 12;
        if (cur + fp > (RING >> 12)) { fp += (RING >> 12) - cur; cur = 0; }
        used += fp;
        while (used > (RING >> 12) || sh == 5 * NBAR) retire();
        fifo |= (uint64_t)fp << sh;
        sh += 5;
        dst = sbase + (cur << 12);
        bar = full0 + 8 * head;
        cur += bytes >> 12;
        if (++head == NBAR) head = 0;
      };
      auto gate = [&]() {
        mbar_wait(ev, 0);
        ev += 8;
        asm volatile("fence.proxy.async.global;" ::: "memory");
      };
      for (int pc = 0;; pc++) {
        const uint32_t op = prog[pc];
        const int type = op & 3, blk = (op >> 10) & 1;
        if (type == OP_END) break;
        if (type == OP_Q) {
#pragma unroll 1
          for (int k = 0; k < 10; k++) {
            if (k == 9 && (op & P_GATE)) gate();
            acquire(SZ_Q);
            if ((pc > 0 || k >= EARLY) && elect()) {
              mbar_expect(bar, SZ_Q);
              tma2d(dst, &P.x[blk], bar, 64 * k, ((op >> 7) & 7) * kSq + rank * 128);
              if ((k & 1) == rank) tma3d_mc(dst + 16384, &P.wq[blk], bar, 0, 64 * k, 3 * ((op >> 2) & 31));
            }
          }
        } else if (type == OP_A) {
          const int row0 = ((op >> 2) & 255) * kSk;
          const CUtensorMap* kv_map = rank ? &P.v[blk] : &P.k[blk];
          if (op & F_PARK) {
            gate();
            acquire(SZ_PARK);
            if (elect()) {
              mbar_expect(bar, SZ_PARK);
              bulk_load_hint(dst, &g_t[((op >> 20) * 2 + rank) * 3072], SZ_PARK, bar, make_policy(P.dbg & 4));
            }
          }
#pragma unroll 1
          for (int t = 0; t < 32; t++) {
            const int isv = t == 31 ? 1 : (t == 0 ? 0 : (~t & 1));
            const int j = isv ? (t - 1) >> 1 : (t + 1) >> 1;
            if (t == 31 && (op & P_GATE)) gate();
            acquire(SZ_KV);
            if (elect()) {
              mbar_expect(bar, SZ_KV);
              if (isv == (int)rank) tma4d_mc_hint(dst, kv_map, bar, row0 / 8 + 8 * j, pol);
            }
          }
        } else {
          const int n = (op >> 13) & 63, nw = (op & P_WIDE) ? n - TAIL : 0;
          const uint64_t pol_o = make_policy(P.dbg & (nw ? 1 : 2));
          const uint4* part = &g_part[((((op >> 5) & 60) + ((op >> 19) & 3)) * 2 + rank) * 5120];
#pragma unroll 1
          for (int i = 0; i < n + (nw ? TAIL : 0); i++) {
            const int id = ((op >> 2) & 511) + (i < n ? i : i - TAIL), col = 5 * (((op >> 19) & 3) + (i >= n));
            const uint4* src = &g_t[(P.slot[id] * 2 + rank) * 3072];
            if ((op & P_LD) && i == ((op & P_PRE) ? 0 : n - 2)) gate();
            if (i < n) gate();
#pragma unroll 1
            for (int k = 0; k < 3; k++) {
              const uint32_t j = (op & P_LD) ? 3 * (i - n) + k + 5 : 5, bytes = i < nw ? SZ_W : j < 5 ? SZ_OL : SZ_O;
              acquire(bytes);
              if (elect()) {
                mbar_expect(bar, bytes);
                tma5d_mc(dst + 16384 + rank * 10240, &P.wo[blk], bar, 24 * (id & 31) + 8 * k + 4 * rank, col);
                bulk_load_hint(dst, src + k * 1024, 16384, bar, pol_o);
                if (i < nw) tma5d_mc(dst + SZ_O + rank * 10240, &P.wo[blk], bar, 24 * (id & 31) + 8 * k + 4 * rank, col + 5);
                if (j < 5) bulk_load_hint(dst + SZ_O, part + j * 1024, 16384, bar, pol);
                if ((op & P_PRE) && 3 * i + k < 10)
                  asm volatile("cp.async.bulk.prefetch.L2.global [%0], 8192;" ::"l"(part + (3 * i + k) * 512) : "memory");
              }
            }
          }
        }
      }
      while (sh) retire();
    } else if (threadIdx.x == 288) {
      for (int pc = 0;; pc++) {
        const uint32_t op = prog[pc];
        const int type = op & 3;
        if (type == OP_END) break;
        if (type == OP_Q ? !(op & F_PARK) : type == OP_O && !(op & P_ST)) continue;
        const int id = type == OP_A ? (op >> 2) & 511 : type == OP_Q ? N_TILE + ((op >> 13) & 127) : ID_PART + ((op >> 5) & 60) + ((op >> 19) & 3);
        const uint32_t v = type == OP_O ? 1 : P.info[id] & 7;
        mbar_wait_slow<PUBNS>(odone0 + 8 * pc, 0);
        flag_set(flag + 2 * id, v);
        if (type == OP_O && (op & P_WIDE)) flag_set(flag + 2 * id + 2, v);
      }
    } else if (wid == 10) {
      int i = threadIdx.x & 31;
      uint32_t e = i < 8 ? P.prog[role].ev[i] : 0;
      for (uint32_t n = 0; __any_sync(0xffffffffu, e); n++) {
        unsigned int* f = ptr_add(flag, 8 * (e & 1023));
        const bool ok = e && flag_get(f) - 1 < ((e & E_FREE) ? 1 : 7);
        if (ok) {
          mbar_arrive(ev0 + 8 * i);
          if (e & (E_FREE | E_LAST)) flag_dec(f);
          i += 8;
          e = i < MAX_EV ? P.prog[role].ev[i] : 0;
        }
        asm volatile("{\n.reg .pred p;\nsetp.ge.u32 p, %0, 0x400000;\n@p trap;\n}\n" ::"r"(n));
        if (!__any_sync(0xffffffffu, ok)) __nanosleep(WATNS);
      }
    } else if (threadIdx.x == 352) {
      uint32_t items = 0;
      auto read = [&](int id) {
        if (!(P.info[id] & I_NEXT)) return;
        wait_progress(progress, items);
        flag_dec(flag + 2 * id);
      };
      for (int pc = 0;; pc++) {
        const uint32_t op = prog[pc];
        const int type = op & 3;
        if (type == OP_END) break;
        if (type == OP_O) {
          const int n = (op >> 13) & 63;
          for (int i = 0; i < n; i++) {
            items += (op & P_WIDE) && i == n - TAIL ? 3 * TAIL + 3 : 3;
            read(((op >> 2) & 511) + i);
          }
        } else if (type == OP_A) {
          if (op & F_PARK) { items++; read(N_TILE + ((op >> 13) & 127)); }
          items += 32;
        } else {
          items += 10;
        }
      }
    }
    __syncwarp();
    asm volatile("barrier.cluster.arrive.relaxed;\nbarrier.cluster.wait;" ::: "memory");
  } else {
    asm volatile("setmaxnreg.inc.sync.aligned.u32 240;");
    const uint32_t* prog = P.prog[role].c;
    const int lane = threadIdx.x & 31, warp = wid & 3;
    uint32_t empty_rem;
    asm volatile("mapa.shared::cluster.u32 %0, %1, %2;" : "=r"(empty_rem) : "r"(empty0), "r"(lane & 1));
    auto release = [&](int slot) { mbar_arrive_cluster_if(lane < 2, empty_rem + 8 * slot); };
    Cursor r{0, 0};
    const uint32_t ring16 = (sbase & 0x3FFFF) >> 4;
    uint32_t cur = ring16;
    bool rdy0 = false, rdy1 = false;
    auto probe1 = [&]() { rdy0 = mbar_test(full0 + 8 * r.bi, r.ph); };
    auto probe2 = [&]() {
      Cursor n = r;
      rdy0 = mbar_test(full0 + 8 * n.bi, n.ph);
      n.next();
      rdy1 = mbar_test(full0 + 8 * n.bi, n.ph);
    };
    auto take = [&](bool rdy, uint32_t bytes, uint32_t& addr) {
      const int bi = r.bi;
      if (!__all_sync(0xffffffffu, rdy)) mbar_wait(full0 + 8 * r.bi, r.ph);
      r.next();
      if (cur > ring16 + ((RING - bytes) >> 4)) cur = ring16;
      addr = cur;
      cur += bytes >> 4;
      return bi;
    };
    uint32_t keep = 0;
    const bool never = P.dbg == 0xffffffffu;
    uint32_t q[48];
#pragma unroll
    for (int i = 0; i < 48; i++) q[i] = 0;
    const int row = wg * 64 + warp * 16 + (lane >> 2);
    const int img0 = row * 4 + ((lane & 3) ^ ((row >> 1) & 3));
    uint4* pend = nullptr;
    bool pend_any = false;
    uint64_t spol;
    int pc = 0;
    auto drain = [&](int c) {
      if (!pend_any || c >= 6) return;
#pragma unroll
      for (int i = 0; i < 6; i++)
        stg2_if(c == i, pend + i * 512, q[8 * i], q[8 * i + 1], q[8 * i + 2], q[8 * i + 3],
                q[8 * i + 4], q[8 * i + 5], q[8 * i + 6], q[8 * i + 7], spol);
      if (c == 5) {
        __syncwarp();
        mbar_arrive_if(lane == 0, odone0 - 8 + 8 * pc);
      }
    };

    for (;; pc++) {
      uint32_t op = prog[pc];
      const int type = op & 3;
      auto enter = [&]() {
        r.bi = (op >> 15) & 15; r.ph = (op >> 19) & 1; cur = ring16 + (((op >> 20) & 63) << 8);
      };
      enter();
      pend_any = op & C_PEND;
      spol = make_policy(!(op & C_SOON));
      if (type == OP_END) {
        for (int c = 0; c < 6; c++) drain(c);
        asm volatile("barrier.cluster.arrive.relaxed;" ::: "memory");
        break;
      }
      if (type != OP_O) {
        float s[32], o[96];
        uint32_t ad0;
        int bi0, sk1;
        uint32_t pa[16], pb[16];
        float mc0, mc1, l0, l1;
        bool shifted;
        auto expo = [&](float (&s)[32], uint32_t (&pout)[16], float& b0, float& b1, bool shift, auto mid) {
          float c0, c1;
#pragma unroll
          for (int i = 0; i < 8; i++) {
            const float e0 = ex2(shift ? s[4 * i] - mc0 : s[4 * i]), e1 = ex2(shift ? s[4 * i + 1] - mc0 : s[4 * i + 1]);
            const float e2 = ex2(shift ? s[4 * i + 2] - mc1 : s[4 * i + 2]), e3 = ex2(shift ? s[4 * i + 3] - mc1 : s[4 * i + 3]);
            if (i) { b0 += e0; c0 += e1; b1 += e2; c1 += e3; } else { b0 = e0; c0 = e1; b1 = e2; c1 = e3; }
            pout[2 * i] = pack_bf16(e0, e1); pout[2 * i + 1] = pack_bf16(e2, e3);
            if (i & 1) mid(i >> 1);
          }
          b0 += c0; b1 += c1;
        };
        auto rowmax = [&](float (&s)[32], float& m0, float& m1) {
          m0 = fmaxf(s[0], s[1]); m1 = fmaxf(s[2], s[3]);
#pragma unroll
          for (int i = 1; i < 8; i++) { m0 = fmaxf(m0, fmaxf(s[4 * i], s[4 * i + 1])); m1 = fmaxf(m1, fmaxf(s[4 * i + 2], s[4 * i + 3])); }
          m0 = fmaxf(m0, __shfl_xor_sync(0xffffffffu, m0, 1)); m1 = fmaxf(m1, __shfl_xor_sync(0xffffffffu, m1, 1));
          m0 = fmaxf(m0, __shfl_xor_sync(0xffffffffu, m0, 2)); m1 = fmaxf(m1, __shfl_xor_sync(0xffffffffu, m1, 2));
        };
        auto first = [&](float (&s)[32], int sk0, auto mid) {
          fence_regs(s);
          release(sk0);
          mc0 = 0.f; mc1 = 0.f;
          expo(s, pa, l0, l1, false, mid);
          shifted = __any_sync(0xffffffffu, !(fmaxf(l0, l1) <= kSumLimit && fminf(l0, l1) >= 1.f / kSumLimit));
          if (shifted) {
            rowmax(s, mc0, mc1);
            expo(s, pa, l0, l1, true, [](int) {});
          }
        };
        auto qk = [&](float (&s)[32], uint32_t ak, int k0 = 0, int k1 = 12) {
#pragma unroll
          for (int kk = k0; kk < k1; kk++)
            wgmma_rs_n64<0>(s, q[4 * kk], q[4 * kk + 1], q[4 * kk + 2], q[4 * kk + 3], mk_desc(ak + (kk >> 2) * KV_CH + (kk & 3) * 2, 16, KV_SBO, 1), kk != 0);
          if (k1 == 12) wg_commit();
        };
        auto unpark = [&]() {
          uint32_t ad, ak;
          const int bi = take(rdy0, SZ_PARK, ad);
#pragma unroll
          for (int i = 0; i < 12; i++) lds128(sbase + (ad - ring16 + img0) * 16 + (i >> 1) * 8192 + (i & 1) * 512, q[4 * i], q[4 * i + 1], q[4 * i + 2], q[4 * i + 3]);
          const int sk0 = take(false, SZ_KV, ak);
          fence_regs(q);
          release(bi);
          wg_fence();
          qk(s, ak);
          probe2();
          return sk0;
        };
        auto mma4 = [&](uint32_t ad, int acc) {
#pragma unroll
          for (int kk = 0; kk < 4; kk++)
            wgmma_ss_n192<1>(o, mk_desc(ad + wg * 512 + kk * 2, 16, 1024, 1), mk_desc(ad + 1024 + kk * 128, 8192, 1024, 1), acc || kk != 0);
        };
        auto convert = [&](int i0, int i1) {
          sched_fence(keep, never);
#pragma unroll
          for (int i = i0; i < i1; i++) q[i] = pack_bf16(o[2 * i] * kScaleLog2, o[2 * i + 1] * kScaleLog2);
          sched_fence(keep, never);
        };
        auto kend = [&](int bi, int k) {
          wg_commit();
          drain(k);
          probe1();
          wg_wait<0>();
          release(bi);
        };
        bi0 = take(rdy0, SZ_Q, ad0);
        undefine(o);
        wg_fence();
        mma4(ad0, 0);
        kend(bi0, 0);
        fence_regs(o);
      next_head:
        {
#pragma unroll 1
          for (int k = 1; k < ((op & F_PARK) ? 10 : 8); k++) {
            uint32_t ad;
            const int bi = take(rdy0, SZ_Q, ad);
            wg_fence();
            mma4(ad, 1);
            kend(bi, k);
          }
          if (op & F_PARK) {
            fence_regs(o);
            convert(0, 48);
            pend = ptr_add(g_t, (((op >> 2) & 511) * 2 + rank) * SZ_PARK + img0 * 16);
            continue;
          }
          uint32_t a8, a9, ak0, ak1;
          const int b8 = take(rdy0, SZ_Q, a8), b9 = take(false, SZ_Q, a9);
          wg_fence();
          mma4(a8, 1);
          wg_commit();
          mma4(a9, 1);
          wg_commit();
          pc++;
          wg_wait<1>();
          release(b8);
          const int sk0 = take(false, SZ_KV, ak0);
          wg_wait<0>();
          fence_regs(o);
          release(b9);
          float s0[32];
          convert(0, 32);
          wg_fence();
          qk(s0, ak0, 0, 4);
          convert(32, 48);
          wg_fence();
          qk(s0, ak0, 4, 12);
          sk1 = take(false, SZ_KV, ak1);
          probe1();
          wg_wait<0>();
          first(s0, sk0, [&](int i) {
            if (i == 0) return;
            sched_fence(keep, never);
            wg_fence();
            if (i == 1) qk(s, ak1, 0, 4);
            if (i == 2) qk(s, ak1, 4, 8);
            if (i == 3) qk(s, ak1, 8, 12);
            sched_fence(keep, never);
          });
        }
        auto pv = [&](uint32_t (&pin)[16], uint32_t av, int acc) {
#pragma unroll
          for (int kk = 0; kk < 4; kk++)
            wgmma_rs_n192<1>(o, pin[4 * kk], pin[4 * kk + 1], pin[4 * kk + 2], pin[4 * kk + 3], mk_desc(av + kk * (KV_SBO / 8), KV_CH * 16, KV_SBO, 1), acc || (kk != 0));
          wg_commit();
        };
        auto soft = [&](uint32_t (&pout)[16]) {
          float b0, b1;
          expo(s, pout, b0, b1, false, [](int) {});
          if (__any_sync(0xffffffffu, shifted || !(fmaxf(b0, b1) <= kSumLimit))) {
            shifted = true;
            float m0, m1;
            rowmax(s, m0, m1);
            m0 = fmaxf(mc0, m0); m1 = fmaxf(mc1, m1);
            const float a0 = ex2(mc0 - m0), a1 = ex2(mc1 - m1);
            mc0 = m0; mc1 = m1;
            l0 *= a0; l1 *= a1;
            wg_wait<0>();
            fence_regs(o);
#pragma unroll
            for (int i = 0; i < 24; i++) { o[4 * i] *= a0; o[4 * i + 1] *= a0; o[4 * i + 2] *= a1; o[4 * i + 3] *= a1; }
            expo(s, pout, b0, b1, true, [](int) {});
          }
          l0 += b0; l1 += b1;
        };
        auto finish = [&](uint32_t (&pout)[16], int sk, int sv) {
          probe2();
          wg_wait<1>();
          fence_regs(s);
          release(sk);
          soft(pout);
          wg_wait<0>();
          fence_regs(o);
          release(sv);
        };
        auto step = [&](uint32_t (&pin)[16], uint32_t (&pout)[16]) {
          uint32_t ak, av;
          const int sk = take(rdy0, SZ_KV, ak), sv = take(rdy1, SZ_KV, av);
          wg_fence();
          qk(s, ak);
          pv(pin, av, 1);
          finish(pout, sk, sv);
        };
        for (;;) {
          {
            uint32_t av;
            const int sv = take(rdy0, SZ_KV, av);
            undefine(o);
            wg_fence();
            pv(pa, av, 0);
            finish(pb, sk1, sv);
          }
          const uint32_t nop = prog[pc + 1];
#pragma unroll 1
          for (int jj = 0; jj < 7; jj++) {
            step(pb, pa);
            step(pa, pb);
          }
          float i0, i1;
          auto last = [&]() {
            uint32_t av;
            const int sv = take(rdy0, SZ_KV, av);
            wg_fence();
            pv(pb, av, 1);
            sched_fence(keep, never);
            probe1();
            l0 += __shfl_xor_sync(0xffffffffu, l0, 1); l1 += __shfl_xor_sync(0xffffffffu, l1, 1);
            l0 += __shfl_xor_sync(0xffffffffu, l0, 2); l1 += __shfl_xor_sync(0xffffffffu, l1, 2);
            i0 = rcp(l0); i1 = rcp(l1);
            pend = ptr_add(g_t, (((op >> 2) & 511) * 2 + rank) * SZ_PARK + img0 * 16);
            return sv;
          };
          auto normalise = [&](uint32_t (&d)[48], auto mid) {
#pragma unroll
            for (int i = 0; i < 24; i++) {
              d[8 * (i >> 2) + (i & 3)] = pack_bf16(o[4 * i] * i0, o[4 * i + 1] * i0);
              d[8 * (i >> 2) + (i & 3) + 4] = pack_bf16(o[4 * i + 2] * i1, o[4 * i + 3] * i1);
              if ((i & 3) == 3 && i != 23) { sched_fence(keep, never); mid(i >> 2); }
            }
          };
          if ((nop & 3) != OP_A) {
            const int sv = last();
            op = nop;
            enter();
            pend_any = true;
            spol = make_policy(!(op & C_SOON));
            bi0 = take(rdy0 || (nop & 3) != OP_Q, SZ_Q, ad0);
            sched_fence(keep, never);
            wg_wait<0>();
            fence_regs(o);
            release(sv);
            normalise(q, [](int) {});
            if ((nop & 3) != OP_Q) break;
            sched_fence(keep, never);
            wg_fence();
            mma4(ad0, 0);
            pc++;
            kend(bi0, 0);
            fence_regs(o);
            goto next_head;
          }
          const int sv = last();
          const int sk0 = unpark();
          wg_wait<1>();
          fence_regs(o);
          release(sv);
          uint32_t t[48];
          spol = make_policy(!(nop & C_SOON));
          auto st = [&](int i) {
            stg2_if(true, pend + i * 512, t[8 * i], t[8 * i + 1], t[8 * i + 2], t[8 * i + 3], t[8 * i + 4], t[8 * i + 5], t[8 * i + 6], t[8 * i + 7], spol);
          };
          normalise(t, [&](int i) { if (!(i & 1)) st(i >> 1); });
          wg_wait<0>();
          first(s, sk0, [&](int i) { if (i < 3) { sched_fence(keep, never); st(3 + i); } });
          __syncwarp();
          mbar_arrive_if(lane == 0, odone0 + 8 * pc);
          pc++;
          op = nop;
          uint32_t ak1;
          sk1 = take(rdy0, SZ_KV, ak1);
          rdy0 = rdy1;
          wg_fence();
          qk(s, ak1);
        }
      } else {
        float c[80];
        const int nk = 3 * ((op >> 2) & 63), ro = (op >> 8) & 63;
        uint4* part = ptr_add(g_part, (ro * 2 + rank) * 81920 + img0 * 16);
        int prev = 0;
        auto mma2 = [&](float (&c)[80], uint32_t da, uint32_t db, int acc) {
          wgmma_ss_n160<1>(c, mk_desc(da, 16, 512, 2), mk_desc(db, 2048, 512, 2), acc);
          wgmma_ss_n160<1>(c, mk_desc(da + 2, 16, 512, 2), mk_desc(db + 64, 2048, 512, 2), 1);
        };
        auto kstep = [&](float (&c)[80], int acc, auto hook, uint32_t bytes = SZ_O) {
          uint32_t ad;
          const int bi = take(rdy0, bytes, ad);
          const uint32_t da = ad + wg * 256, db = ad + 1024;
          wg_fence();
          mma2(c, da, db, acc);
          wg_commit();
          if (acc) { wg_wait<1>(); release(prev); }
          mma2(c, da + 512, db + 640, 1);
          wg_commit();
          prev = bi;
          hook();
          probe1();
          wg_wait<1>();
        };
        if (op & C_WIDE) {
          float d[80];
          auto wstep = [&](int acc, auto hook) {
            uint32_t ad;
            const int bi = take(rdy0, SZ_W, ad);
            const uint32_t da = ad + wg * 256, db = ad + 1024;
            wg_fence();
            mma2(d, da, db, acc);
            mma2(d, da + 512, db + 640, 1);
            wg_commit();
            if (acc) { wg_wait<1>(); release(prev); }
            mma2(c, da, db + 1280, acc);
            mma2(c, da + 512, db + 1920, 1);
            wg_commit();
            prev = bi;
            hook();
            probe1();
            wg_wait<1>();
          };
          wstep(0, [&]() { drain(0); drain(1); });
#pragma unroll 1
          for (int k = 2; k < 6; k += 2) wstep(1, [&]() { drain(k); drain(k + 1); });
#pragma unroll 1
          for (int k = 3 + 3 * TAIL; k < nk; k++) {
            wstep(1, []() {});
          }
#pragma unroll 1
          for (int k = 0; k < 3 * TAIL; k++) kstep(d, 1, []() {});
          spol = make_policy(!(prog[pc + 1] & C_SOON));
#pragma unroll
          for (int k = 0; k < 3 * TAIL; k++)
            kstep(c, 1, [&]() {
              if (k == 0) fence_regs(d);
#pragma unroll
              for (int i = k * 10 / (3 * TAIL - 1); i < (k + 1) * 10 / (3 * TAIL - 1) && i < 10; i++)
                stg2_if(true, part - 10240 + i * 512, __float_as_uint(d[8 * i]), __float_as_uint(d[8 * i + 1]), __float_as_uint(d[8 * i + 2]),
                        __float_as_uint(d[8 * i + 3]), __float_as_uint(d[8 * i + 4]), __float_as_uint(d[8 * i + 5]),
                        __float_as_uint(d[8 * i + 6]), __float_as_uint(d[8 * i + 7]), spol);
            });
          wg_wait<0>();
          fence_regs(c);
          release(prev);
        } else {
          kstep(c, 0, [&]() { drain(0); drain(1); });
#pragma unroll 1
          for (int k = 2; k < 6; k += 2) kstep(c, 1, [&]() { drain(k); drain(k + 1); });
#pragma unroll 1
          for (int k = (op & C_LD) ? 8 : 3; k < nk; k++) kstep(c, 1, []() {});
          if (op & C_LD) {
            uint32_t t[80];
#pragma unroll
            for (int j = 0; j < 5; j++)
              kstep(c, 1, [&]() {
#pragma unroll
                for (int i = 0; i < 4; i++)
                  lds128(sbase + (cur - ring16 + img0) * 16 - 16384 + (i >> 1) * 8192 + (i & 1) * 512, t[16 * j + 4 * i], t[16 * j + 4 * i + 1], t[16 * j + 4 * i + 2], t[16 * j + 4 * i + 3]);
              }, SZ_OL);
            wg_wait<0>();
            fence_regs(c);
            release(prev);
#pragma unroll
            for (int i = 0; i < 80; i++) c[i] += __uint_as_float(t[i]);
          } else {
            wg_wait<0>();
            fence_regs(c);
            release(prev);
          }
        }
        if (op & C_ST) {
#pragma unroll
          for (int i = 0; i < 48; i++) q[i] = __float_as_uint(c[i]);
          pend = part;
#pragma unroll
          for (int i = 12; i < 20; i++)
            stg128_hint(pend + (i >> 1) * 512 + (i & 1) * 32, __float_as_uint(c[4 * i]), __float_as_uint(c[4 * i + 1]),
                        __float_as_uint(c[4 * i + 2]), __float_as_uint(c[4 * i + 3]), spol);
          continue;
        }
        {
          asm volatile("barrier.cluster.arrive.relaxed;" ::: "memory");
          bar_sync(1, 256);
          const uint32_t wstage = sbase + (wg * 4 + warp) * 5120;
          const uint32_t sa = wstage + (lane & 15) * 64;
#pragma unroll
          for (int i = 0; i < 10; i++) {
            const int u = (i & 1) * 2 + (lane >> 4);
            stsm4(sa + (i >> 1) * 1024 + ((u ^ ((lane >> 1) & 3)) << 4), pack_bf16(c[8 * i], c[8 * i + 1]), pack_bf16(c[8 * i + 2], c[8 * i + 3]),
                  pack_bf16(c[8 * i + 4], c[8 * i + 5]), pack_bf16(c[8 * i + 6], c[8 * i + 7]));
          }
          asm volatile("fence.proxy.async.shared::cta;" ::: "memory");
          __syncwarp();
          if (lane == 0) {
            tma3d_store(&P.out, wstage, 0, ((ro >> 2) & 7) * kSq + rank * 128 + wg * 64 + warp * 16, (ro >> 5) * 20 + (ro & 3) * 5);
            asm volatile("cp.async.bulk.commit_group;\ncp.async.bulk.wait_group.read 0;" ::: "memory");
          }
          __syncwarp();
          break;
        }
      }
    }
    if (never) g_flag[0] = keep;
    asm volatile("barrier.cluster.wait;" ::: "memory");
  }
}

typedef CUresult (*EncodeFn)(CUtensorMap*, CUtensorMapDataType, cuuint32_t, void*, const cuuint64_t*, const cuuint64_t*,
                             const cuuint32_t*, const cuuint32_t*, CUtensorMapInterleave, CUtensorMapSwizzle,
                             CUtensorMapL2promotion, CUtensorMapFloatOOBfill);

void encode(EncodeFn fn, CUtensorMap* m, const void* ptr, int rank, const cuuint64_t* dims, const cuuint64_t* strides,
            const cuuint32_t* box, CUtensorMapSwizzle swz) {
  const cuuint32_t es[5] = {1, 1, 1, 1, 1};
  CUresult r = fn(m, CU_TENSOR_MAP_DATA_TYPE_BFLOAT16, rank, const_cast<void*>(ptr), dims, strides, box, es,
                  CU_TENSOR_MAP_INTERLEAVE_NONE, swz, CU_TENSOR_MAP_L2_PROMOTION_L2_128B, CU_TENSOR_MAP_FLOAT_OOB_FILL_NONE);
  if (r != CUDA_SUCCESS) fprintf(stderr, "cuTensorMapEncodeTiled failed: %d\n", (int)r);
}

struct Op { int type, flags, id, n, quarter, park, item0, items; double t0, t1; };
struct Use { double ready, gate, need, freed; int readers, slot, prev; bool next; };
struct PlanStats { double end, slack, park_slack; int slots, parks; };

bool plan(const char* const* text, int n_pair, int phase, Params& P, PlanStats* stats = nullptr) {
  constexpr double T_Q = 7900, T_A = 24850, T_U = 26300, T_O = 1920, T_RUN = 800, T_WIDE = 3800, AHEAD = 3500, PUBLISH = 1500;
  const double margin = 256.0 * ((P.dbg >> 8) & 255);
  static Op op[N_CL][MAX_OPS];
  static Use use[ID_PART];
  int n_op[N_CL], covered[N_TEAM] = {}, finals[N_TEAM] = {};
  auto hex = [](char c) { return c <= '9' ? c - '0' : c - 'a' + 10; };
  for (int i = 0; i < n_pair; i++)
    for (const char* s = text[i]; *s; s++)
      if (*s == 'J') { if (covered[hex(s[1])]) return false; covered[hex(s[1])] = 10 * (s[2] - '0') + s[3] - '0'; }
  for (int c = 0; c < 2 * n_pair; c++) {
    int n = 0, items = 0;
    double t = 0;
    auto add = [&](int type, int flags, int id, int heads, int quarter, int its, double dt) {
      if (n < MAX_OPS) op[c][n] = {type, flags, id, heads, quarter, 0, items, its, t, t + dt};
      n++; items += its; t += dt;
    };
    for (const char* s = text[c >> 1]; *s; s++) {
      const int tm = hex(s[1]) & 15, nj = covered[tm];
      if (*s == 'N') { add(OP_Q, 0, 0, 0, 0, 10, T_Q); add(OP_A, 0, 0, 0, 0, 32, T_A); }
      if (*s == 'P') add(OP_Q, F_PARK, 0, 0, 0, 10, T_Q);
      if (*s == 'U') { if (n == 0 || n > MAX_OPS || op[c][n - 1].type != OP_A) return false; add(OP_A, F_PARK, 0, 0, 0, 33, T_U); }
      if (*s == 'J') { if (nj <= TAIL || nj > kH - 4) return false; add(OP_O, P_WIDE | P_ST, tm * kH, nj, 2 * (c & 1), 3 * (nj + TAIL), 2 * T_O * nj + T_WIDE); }
      if (*s == 'F') { if (s[2]) return false; add(OP_O, nj ? P_LD : 0, tm * kH + nj, kH - nj, finals[tm]++, 3 * (kH - nj), T_O * (kH - nj) + T_RUN); }
    }
    add(OP_END, 0, 0, 0, 0, 0, 0);
    if (n > MAX_OPS || op[c][0].type != OP_Q) return false;
    n_op[c] = n - 1;
  }
  for (int t = 0; t < N_TEAM; t++) if (finals[t] != 4) return false;
  for (int i = 0; i < ID_PART; i++) use[i] = {0, 0, 1e18, 0, 0, 0, 0, false};
  struct Ref { double t; Op* o; int id; };
  static Ref att[N_TILE + 1], dem[N_TILE], prk[MAX_PARK + 1], unp[MAX_PARK + 1], wr[ID_PART];
  int n_att = 0, n_prk = 0, n_unp = 0;
  auto ready = [&](const Op* o) {
    const int nt = o[1].type;
    return o->t1 + (nt == OP_Q ? 4600 : nt == OP_O ? ((o[1].flags & P_WIDE) ? 3900 : 3900 / FDRAIN) : 1500) + PUBLISH;
  };
  for (int c = 0; c < 2 * n_pair; c++)
    for (Op* o = op[c]; o->type != OP_END; o++) {
      if (o->type == OP_A) { att[n_att] = {ready(o), o, 0}; if (++n_att > N_TILE) return false; }
      if (o->type == OP_A && o->flags) { unp[n_unp] = {o->t0 - AHEAD, o, 0}; if (++n_unp > MAX_PARK) return false; }
      if (o->type == OP_Q && o->flags) { prk[n_prk] = {ready(o), o, 0}; if (++n_prk > MAX_PARK) return false; }
      for (int i = 0; o->type == OP_O && i < o->n; i++) {
        const int nw = (o->flags & P_WIDE) ? o->n - TAIL : 0;
        Use& u = use[o->id + i];
        const double t = o->t0 + T_O * (i + (i < nw ? i : nw));
        if (t - AHEAD < u.need) u.need = t - AHEAD;
        const double f = t + T_O * (i < nw ? 2 : nw ? 1 + TAIL : 1) + PUBLISH;
        if (f > u.freed) u.freed = f;
        u.readers++;
      }
    }
  if (n_att != N_TILE || n_prk != n_unp) return false;
  auto sort = [](Ref* r, int n) {
    for (int i = 1; i < n; i++)
      for (int j = i; j > 0 && r[j].t < r[j - 1].t; j--) { Ref x = r[j]; r[j] = r[j - 1]; r[j - 1] = x; }
  };
  for (int i = 0; i < N_TILE; i++) { const int id = (i & 15) * kH + (i >> 4); dem[i] = {use[id].need, nullptr, id}; }
  sort(att, n_att); sort(dem, N_TILE); sort(prk, n_prk); sort(unp, n_unp);
  PlanStats st = {0, 1e18, 1e18, 0, n_prk};
  int n_wr = 0;
  for (int i = 0; i < N_TILE; i++) {
    Op* o = att[i].o;
    o->id = dem[i].id;
    if (!o->flags) o[-1].id = o->id;
    if (dem[i].t - att[i].t < st.slack) st.slack = dem[i].t - att[i].t;
    wr[n_wr++] = {o->t1 - 2 * AHEAD, o, o->id};
  }
  for (int i = 0; i < n_prk; i++) {
    prk[i].o->id = unp[i].o->id;
    prk[i].o->park = unp[i].o->park = i;
    use[N_TILE + i].freed = unp[i].o->t0 + 2 * PUBLISH;
    use[N_TILE + i].readers = 1;
    if (unp[i].t - prk[i].t < st.park_slack) st.park_slack = unp[i].t - prk[i].t;
    wr[n_wr++] = {prk[i].o->t1 - 2 * AHEAD, prk[i].o, N_TILE + i};
  }
  for (int c = 0; c < 2 * n_pair; c++)
    for (int d = 0; d < 2 * n_pair; d++)
      for (Op *f = &op[c][n_op[c] - 1], *o = op[d]; f->type == OP_O && o->type != OP_END; o++)
        if (o->type == OP_O && (o->flags & P_ST) && o->id / kH == f->id / kH) {
          if (f->t0 - o->t1 > 4096.0 * ((P.dbg >> 16) & 255)) f->flags |= P_PRE;
          const double slack = f->t0 + ((f->flags & P_PRE) ? 0 : (f->n - 2) * T_O) - AHEAD - ready(o);
          if (slack < st.park_slack) st.park_slack = slack;
        }
  sort(wr, n_wr);
  int holder[N_TILE];
  for (int i = 0; i < n_wr; i++) {
    int best = -1;
    for (int sl = 0; sl < st.slots; sl++)
      if (use[holder[sl]].freed + margin <= wr[i].t && (best < 0 || (use[holder[sl]].freed < use[holder[best]].freed) != ((P.dbg & 32) != 0))) best = sl;
    Use& u = use[wr[i].id];
    if (best >= 0) { u.prev = holder[best]; use[u.prev].next = true; wr[i].o->flags |= P_GATE; }
    else if (st.slots == N_TILE) return false;
    else best = st.slots++;
    u.slot = best;
    holder[best] = wr[i].id;
  }
  {
    int pos[N_CL] = {}, flag[ID_PART + 4 * N_TEAM] = {}, seen[ID_PART] = {};
    for (bool moved = true; moved;) {
      moved = false;
      for (int c = 0; c < 2 * n_pair; c++) {
        const int total = op[c][n_op[c]].item0;
        for (; pos[c] < total + NBAR; pos[c]++, moved = true) {
          bool ok = true;
          for (const Op* o = op[c]; o->type != OP_END; o++) {
            const int k = pos[c] - o->item0, own = o->type == OP_A ? o->id : N_TILE + o->park;
            if (k < 0 || k >= o->items) continue;
            if (o->type == OP_O) ok = (k >= 3 * o->n || flag[o->id + k / 3]) && (k != ((o->flags & P_PRE) ? 0 : 3 * o->n - 6) || !(o->flags & P_LD) || flag[ID_PART + o->id / kH * 4 + o->quarter]);
            else if (k == o->items - 1 && (o->flags & P_GATE)) ok = seen[use[own].prev] == use[use[own].prev].readers;
            else if (k == 0 && o->type == OP_A && (o->flags & F_PARK)) ok = flag[N_TILE + o->park];
          }
          if (!ok) break;
          for (const Op* o = op[c]; o->type != OP_END; o++) {
            if (pos[c] == o->item0 + o->items + 5) {
              if (o->type == OP_A) flag[o->id] = 1;
              if (o->type == OP_Q && (o->flags & F_PARK)) flag[N_TILE + o->park] = 1;
              if (o->type == OP_O && (o->flags & P_ST)) flag[ID_PART + o->id / kH * 4 + o->quarter] = flag[ID_PART + o->id / kH * 4 + o->quarter + 1] = 1;
            }
            const int k = pos[c] - NBAR - o->item0, nw = (o->flags & P_WIDE) ? o->n - TAIL : o->n;
            if (k == 0 && o->type == OP_A && (o->flags & F_PARK)) seen[N_TILE + o->park]++;
            if (o->type == OP_O && k >= 0 && k % 3 == 2 && (k / 3 < nw || (k / 3 >= o->n && k / 3 < 2 * o->n - nw))) seen[o->id + (k / 3 < nw ? k / 3 : k / 3 - TAIL)]++;
          }
        }
      }
    }
    for (int c = 0; c < 2 * n_pair; c++) if (pos[c] < op[c][n_op[c]].item0 + NBAR) return false;
  }
  for (int c = 0; c < 2 * n_pair; c++) {
    uint32_t items = 0, cur = 0, pend = 0;
    int n = 0, ev = 0;
    auto item = [&](uint32_t bytes, int count) {
      for (int i = 0; i < count; i++) { if (cur + bytes > RING) cur = 0; cur += bytes; items++; }
    };
    auto event = [&](uint32_t e) { if (ev < MAX_EV) P.prog[c].ev[ev] = e | E_ON; ev++; };
    for (const Op* o = op[c];; o++) {
      if (o->type != OP_END && phase && (o->type == OP_O) != (phase == 2)) continue;
      uint32_t cw = o->type | (items % NBAR) << 15 | ((items / NBAR) & 1) << 19 | (cur >> 12) << 20 | pend, pw = o->type | o->id << 2 | o->flags;
      const int ps = use[N_TILE + o->park].slot;
      pend = 0;
      if (o->type == OP_O) {
        const bool wide = o->flags & P_WIDE;
        cw |= o->n << 2 | (o->id / kH * 4 + o->quarter + wide) << 8 | (wide ? C_WIDE : 0) | ((o->flags & P_LD) ? C_LD : 0) | ((o->flags & P_ST) ? C_ST : 0);
        pw |= o->n << 13 | o->quarter << 19;
        if (wide) item(SZ_W, 3 * (o->n - TAIL));
        for (int k = 0; k < (wide ? 6 * TAIL : 3 * o->n); k++) item((o->flags & P_LD) && k >= 3 * o->n - 5 ? SZ_OL : SZ_O, 1);
        if (o->flags & P_ST) pend = C_PEND | ((P.dbg & 8) ? C_SOON : 0);
        for (int i = 0; i < o->n; i++) {
          if (i == ((o->flags & P_PRE) ? 0 : o->n - 2) && (o->flags & P_LD)) event((ID_PART + o->id / kH * 4 + o->quarter) | E_LAST);
          event((o->id + i) | (use[o->id + i].next ? 0 : E_LAST));
        }
      } else if (o->type != OP_END) {
        const bool parks = o->type == OP_Q && (o->flags & F_PARK);
        cw |= (parks ? ps : use[o->id].slot) << 2 | (o->flags & F_PARK);
        if (o->flags & F_PARK) pw |= o->park << 13 | ps << 20;
        if (o->type == OP_Q) item(SZ_Q, 10);
        else { if (o->flags & F_PARK) { item(SZ_PARK, 1); event((N_TILE + o->park) | (use[N_TILE + o->park].next ? 0 : E_LAST)); } item(SZ_KV, 32); }
        if (parks || o->type == OP_A) pend = C_PEND | ((P.dbg & 16) ? 0 : C_SOON);
        if (o->flags & P_GATE) event(use[parks ? N_TILE + o->park : o->id].prev | E_FREE);
      }
      P.prog[c].c[n] = cw; P.prog[c].p[n++] = pw;
      if (o->type == OP_END) { if (o->t0 > st.end) st.end = o->t0; break; }
    }
    if (ev > MAX_EV) return false;
    while (ev < MAX_EV) P.prog[c].ev[ev++] = 0;
    while (n < MAX_OPS) { P.prog[c].c[n] = OP_END; P.prog[c].p[n++] = OP_END; }
    P.first[c] = (uint16_t)(P.prog[c].p[0] & 2047);
  }
  for (int i = 0; i < ID_PART; i++) {
    if (i < N_TILE) P.slot[i] = use[i].slot;
    P.info[i] = (use[i].readers + use[i].next) | (use[i].next ? I_NEXT : 0);
  }
  if (stats) *stats = st;
  return true;
}

const char* const kPrograms[N_CL / 2] = {
  "NNJ025NJ818NFc", "NNJ121NJ921NFa", "NNJ219NJa24NFc", "NNJ318NJb25NFa", "NNJ417NJc24NF1", "NNJ518NJd22NF2",
  "NNJ618NJe22NF2", "NNJ725NJf25Fd", "NUNNNNNNNF4", "NUNNNNNNNF4", "NUNNNNNNNF5", "NUNNNNNNNF5",
  "NUNNNNNNNF6", "NUNNNNNNNF6", "NUNNNNNNNF3", "NUNNNNNNNF3", "NUNNNNNNNF8", "NUNNNNNNNF8",
  "PNNNNNNNNNF0", "PNNNNNNNNNF7", "PNNNNNNNNNF7", "PNNNNNNNNNF0", "PNNNNNNNNNFb", "PNNNNNNNNNFb",
  "PNNNNNNNNNFf", "PNNNNNNNNNFf", "NNNNNNNNNF1", "NNNNNNNNNFd", "NNNNNNNNNFe", "NNNNNNNNNFe",
  "NNNNNNNNNF9", "NNNNNNNNNF9", "PPNNNNNNNNN",
};

const char* const* bench_programs() {
  return kPrograms;
}

}

extern "C" void kernel_launch(void* const* d_in, const int* in_sizes, int n_in, void* d_out, int out_size) {
  (void)in_sizes; (void)n_in; (void)out_size;
  static EncodeFn fn = nullptr;
  static int n_clusters = 0;
  if (!fn) {
    cudaDriverEntryPointQueryResult qr;
    void* f = nullptr;
    cudaGetDriverEntryPoint("cuTensorMapEncodeTiled", &f, cudaEnableDefault, &qr);
    fn = (EncodeFn)f;
    cudaFuncSetAttribute(fused_kernel, cudaFuncAttributeMaxDynamicSharedMemorySize, SMEM_BYTES);
    cudaLaunchConfig_t cfg = {};
    cfg.gridDim = dim3(132); cfg.blockDim = dim3(384); cfg.dynamicSmemBytes = SMEM_BYTES;
    cudaLaunchAttribute at[1];
    at[0].id = cudaLaunchAttributeClusterDimension; at[0].val.clusterDim.x = 2; at[0].val.clusterDim.y = 1; at[0].val.clusterDim.z = 1;
    cfg.attrs = at; cfg.numAttrs = 1;
    if (cudaOccupancyMaxActiveClusters(&n_clusters, fused_kernel, &cfg) != cudaSuccess || n_clusters < 1) n_clusters = 1;
    (void)cudaGetLastError();
  }
  static Params P;
  const CUtensorMapSwizzle S128 = CU_TENSOR_MAP_SWIZZLE_128B, S64 = CU_TENSOR_MAP_SWIZZLE_64B;
  for (int blk = 0; blk < 2; blk++) {
    void* const* in = d_in + 5 * blk;
    { const cuuint64_t d[] = {kD, kB * kSq}, s[] = {kD * 2}; const cuuint32_t b[] = {64, 128};
      encode(fn, &P.x[blk], in[0], 2, d, s, b, S128); }
    { const cuuint64_t d[] = {64, 8, 3, (cuuint64_t)kB * kH * kSk / 8}, s[] = {kDh * 2, 128, 8 * kDh * 2}; const cuuint32_t b[] = {64, 8, 3, 8};
      encode(fn, &P.k[blk], in[1], 4, d, s, b, S128);
      encode(fn, &P.v[blk], in[2], 4, d, s, b, S128); }
    { const cuuint64_t d[] = {64, kD, kHD / 64}, s[] = {kHD * 2, 128}; const cuuint32_t b[] = {64, 64, 3};
      encode(fn, &P.wq[blk], in[3], 3, d, s, b, S128); }
    { const cuuint64_t d[] = {32, 2, kHD / 8, 4, kD / 32}, s[] = {kD * 2, 8 * kD * 2, 2 * kD * 2, 64}; const cuuint32_t b[] = {32, 2, 4, 4, 5};
      encode(fn, &P.wo[blk], in[4], 5, d, s, b, S64); }
  }
  { const cuuint64_t d[] = {32, kB * kSq, 2 * kD / 32}, s[] = {2 * kD * 2, 64}; const cuuint32_t b[] = {32, 16, 5};
    encode(fn, &P.out, d_out, 3, d, s, b, S64); }

  P.dbg = DBG_DEFAULT;
  if (n_clusters >= N_CL && plan(bench_programs(), N_CL / 2, 0, P)) {
    fused_kernel<<<2 * N_CL, 384, SMEM_BYTES>>>(P);
  } else {
    char buf[2 * N_TEAM][16];
    const char* text[2 * N_TEAM];
    for (int i = 0; i < 2 * N_TEAM; i++) { snprintf(buf[i], sizeof(buf[i]), "NNNNNNNNF%x", i / 2); text[i] = buf[i]; }
    for (int phase = 1; phase <= 2; phase++) {
      plan(text, 2 * N_TEAM, phase, P);
      fused_kernel<<<8 * N_TEAM, 384, SMEM_BYTES>>>(P);
    }
  }
}
```

```cpp
#include <cuda_runtime.h>
#include <cuda_bf16.h>
#include <cuda.h>
#include <stdint.h>
#include <stdio.h>

namespace {

constexpr int kB = 8, kSq = 256, kD = 640, kH = 32, kSk = 1024, kDh = 192;
constexpr int kHD = kH * kDh;
constexpr uint32_t RING = 224 * 1024;
constexpr uint32_t SZ_KV = 24576;
constexpr uint32_t SZ_Q = 16384 + 24576;
constexpr uint32_t SZ_O = 16384 + 20480;
constexpr uint32_t SZ_W = 16384 + 40960;
constexpr uint32_t SZ_PARK = 49152;
constexpr uint32_t SZ_OL = SZ_O + 8192;
constexpr int NBAR = 10;
constexpr int EARLY = 3;
#define XTAIL 2
constexpr int TAIL = XTAIL;
constexpr uint32_t KV_CH = 64, KV_SBO = 3072;
constexpr int SMEM_BYTES = RING + 1024 + 1024;
constexpr int N_TEAM = 16, N_CL = 66, MAX_OPS = 24, MAX_EV = 80, N_TILE = N_TEAM * kH, MAX_PARK = 128, ID_PART = N_TILE + MAX_PARK;
enum : uint32_t { OP_END = 0, OP_Q = 1, OP_A = 2, OP_O = 3, F_PARK = 1 << 11,
                  C_WIDE = 1 << 14, C_PEND = 1 << 26, C_SOON = 1 << 28, C_LD = 1 << 29,
                  P_GATE = 1 << 12, P_WIDE = 1 << 11, P_LD = 1 << 12, P_ST = 1 << 21, P_PRE = 1 << 22, I_NEXT = 8, E_ON = 1 << 15, E_FREE = 1 << 14, E_LAST = 1 << 13 };

#define FDRAIN 1
#define PUBNS 100
#define WATNS 100
constexpr uint32_t DBG_DEFAULT = 0x101833;

struct alignas(64) Params {
  uint16_t first[96];
  CUtensorMap x[2], wq[2], k[2], v[2], wo[2], out;
  struct {
    uint32_t c[MAX_OPS];
    uint32_t p[MAX_OPS];
    uint16_t ev[MAX_EV];
  } prog[N_CL];
  uint16_t slot[N_TILE];
  uint8_t info[ID_PART];
  uint32_t dbg;
};

__device__ uint4 g_t[N_TILE * 2 * 3072];
__device__ uint4 g_part[N_TEAM * 4 * 2 * 3072];
__device__ unsigned int g_flag[(ID_PART + N_TEAM * 4) * 2];

template <int TB, int TA = 0>
__device__ __forceinline__ void wgmma_ss_n64(float (&d)[32], uint64_t da, uint64_t db, int scale_d) {
  asm volatile("{\n.reg .pred p;\nsetp.ne.b32 p, %34, 0;\n"
    "wgmma.mma_async.sync.aligned.m64n64k16.f32.bf16.bf16 {%0, %1, %2, %3, %4, %5, %6, %7, %8, %9, %10, %11, %12, %13, %14, %15, %16, %17, %18, %19, %20, %21, %22, %23, %24, %25, %26, %27, %28, %29, %30, %31}, %32, %33, p, 1, 1, %35, %36;\n}\n"
    : "+f"(d[0]), "+f"(d[1]), "+f"(d[2]), "+f"(d[3]), "+f"(d[4]), "+f"(d[5]), "+f"(d[6]), "+f"(d[7]), "+f"(d[8]), "+f"(d[9]), "+f"(d[10]), "+f"(d[11]), "+f"(d[12]), "+f"(d[13]), "+f"(d[14]), "+f"(d[15]), "+f"(d[16]), "+f"(d[17]), "+f"(d[18]), "+f"(d[19]), "+f"(d[20]), "+f"(d[21]), "+f"(d[22]), "+f"(d[23]), "+f"(d[24]), "+f"(d[25]), "+f"(d[26]), "+f"(d[27]), "+f"(d[28]), "+f"(d[29]), "+f"(d[30]), "+f"(d[31])
    : "l"(da), "l"(db), "r"(scale_d), "n"(TA), "n"(TB));
}
template <int TB>
__device__ __forceinline__ void wgmma_rs_n64(float (&d)[32], uint32_t a0, uint32_t a1, uint32_t a2, uint32_t a3, uint64_t db, int scale_d) {
  asm volatile("{\n.reg .pred p;\nsetp.ne.b32 p, %37, 0;\n"
    "wgmma.mma_async.sync.aligned.m64n64k16.f32.bf16.bf16 {%0, %1, %2, %3, %4, %5, %6, %7, %8, %9, %10, %11, %12, %13, %14, %15, %16, %17, %18, %19, %20, %21, %22, %23, %24, %25, %26, %27, %28, %29, %30, %31}, {%32, %33, %34, %35}, %36, p, 1, 1, %38;\n}\n"
    : "+f"(d[0]), "+f"(d[1]), "+f"(d[2]), "+f"(d[3]), "+f"(d[4]), "+f"(d[5]), "+f"(d[6]), "+f"(d[7]), "+f"(d[8]), "+f"(d[9]), "+f"(d[10]), "+f"(d[11]), "+f"(d[12]), "+f"(d[13]), "+f"(d[14]), "+f"(d[15]), "+f"(d[16]), "+f"(d[17]), "+f"(d[18]), "+f"(d[19]), "+f"(d[20]), "+f"(d[21]), "+f"(d[22]), "+f"(d[23]), "+f"(d[24]), "+f"(d[25]), "+f"(d[26]), "+f"(d[27]), "+f"(d[28]), "+f"(d[29]), "+f"(d[30]), "+f"(d[31])
    : "r"(a0), "r"(a1), "r"(a2), "r"(a3), "l"(db), "r"(scale_d), "n"(TB));
}
template <int TB, int TA = 0>
__device__ __forceinline__ void wgmma_ss_n160(float (&d)[80], uint64_t da, uint64_t db, int scale_d) {
  asm volatile("{\n.reg .pred p;\nsetp.ne.b32 p, %82, 0;\n"
    "wgmma.mma_async.sync.aligned.m64n160k16.f32.bf16.bf16 {%0, %1, %2, %3, %4, %5, %6, %7, %8, %9, %10, %11, %12, %13, %14, %15, %16, %17, %18, %19, %20, %21, %22, %23, %24, %25, %26, %27, %28, %29, %30, %31, %32, %33, %34, %35, %36, %37, %38, %39, %40, %41, %42, %43, %44, %45, %46, %47, %48, %49, %50, %51, %52, %53, %54, %55, %56, %57, %58, %59, %60, %61, %62, %63, %64, %65, %66, %67, %68, %69, %70, %71, %72, %73, %74, %75, %76, %77, %78, %79}, %80, %81, p, 1, 1, %83, %84;\n}\n"
    : "+f"(d[0]), "+f"(d[1]), "+f"(d[2]), "+f"(d[3]), "+f"(d[4]), "+f"(d[5]), "+f"(d[6]), "+f"(d[7]), "+f"(d[8]), "+f"(d[9]), "+f"(d[10]), "+f"(d[11]), "+f"(d[12]), "+f"(d[13]), "+f"(d[14]), "+f"(d[15]), "+f"(d[16]), "+f"(d[17]), "+f"(d[18]), "+f"(d[19]), "+f"(d[20]), "+f"(d[21]), "+f"(d[22]), "+f"(d[23]), "+f"(d[24]), "+f"(d[25]), "+f"(d[26]), "+f"(d[27]), "+f"(d[28]), "+f"(d[29]), "+f"(d[30]), "+f"(d[31]), "+f"(d[32]), "+f"(d[33]), "+f"(d[34]), "+f"(d[35]), "+f"(d[36]), "+f"(d[37]), "+f"(d[38]), "+f"(d[39]), "+f"(d[40]), "+f"(d[41]), "+f"(d[42]), "+f"(d[43]), "+f"(d[44]), "+f"(d[45]), "+f"(d[46]), "+f"(d[47]), "+f"(d[48]), "+f"(d[49]), "+f"(d[50]), "+f"(d[51]), "+f"(d[52]), "+f"(d[53]), "+f"(d[54]), "+f"(d[55]), "+f"(d[56]), "+f"(d[57]), "+f"(d[58]), "+f"(d[59]), "+f"(d[60]), "+f"(d[61]), "+f"(d[62]), "+f"(d[63]), "+f"(d[64]), "+f"(d[65]), "+f"(d[66]), "+f"(d[67]), "+f"(d[68]), "+f"(d[69]), "+f"(d[70]), "+f"(d[71]), "+f"(d[72]), "+f"(d[73]), "+f"(d[74]), "+f"(d[75]), "+f"(d[76]), "+f"(d[77]), "+f"(d[78]), "+f"(d[79])
    : "l"(da), "l"(db), "r"(scale_d), "n"(TA), "n"(TB));
}
template <int TB>
__device__ __forceinline__ void wgmma_rs_n160(float (&d)[80], uint32_t a0, uint32_t a1, uint32_t a2, uint32_t a3, uint64_t db, int scale_d) {
  asm volatile("{\n.reg .pred p;\nsetp.ne.b32 p, %85, 0;\n"
    "wgmma.mma_async.sync.aligned.m64n160k16.f32.bf16.bf16 {%0, %1, %2, %3, %4, %5, %6, %7, %8, %9, %10, %11, %12, %13, %14, %15, %16, %17, %18, %19, %20, %21, %22, %23, %24, %25, %26, %27, %28, %29, %30, %31, %32, %33, %34, %35, %36, %37, %38, %39, %40, %41, %42, %43, %44, %45, %46, %47, %48, %49, %50, %51, %52, %53, %54, %55, %56, %57, %58, %59, %60, %61, %62, %63, %64, %65, %66, %67, %68, %69, %70, %71, %72, %73, %74, %75, %76, %77, %78, %79}, {%80, %81, %82, %83}, %84, p, 1, 1, %86;\n}\n"
    : "+f"(d[0]), "+f"(d[1]), "+f"(d[2]), "+f"(d[3]), "+f"(d[4]), "+f"(d[5]), "+f"(d[6]), "+f"(d[7]), "+f"(d[8]), "+f"(d[9]), "+f"(d[10]), "+f"(d[11]), "+f"(d[12]), "+f"(d[13]), "+f"(d[14]), "+f"(d[15]), "+f"(d[16]), "+f"(d[17]), "+f"(d[18]), "+f"(d[19]), "+f"(d[20]), "+f"(d[21]), "+f"(d[22]), "+f"(d[23]), "+f"(d[24]), "+f"(d[25]), "+f"(d[26]), "+f"(d[27]), "+f"(d[28]), "+f"(d[29]), "+f"(d[30]), "+f"(d[31]), "+f"(d[32]), "+f"(d[33]), "+f"(d[34]), "+f"(d[35]), "+f"(d[36]), "+f"(d[37]), "+f"(d[38]), "+f"(d[39]), "+f"(d[40]), "+f"(d[41]), "+f"(d[42]), "+f"(d[43]), "+f"(d[44]), "+f"(d[45]), "+f"(d[46]), "+f"(d[47]), "+f"(d[48]), "+f"(d[49]), "+f"(d[50]), "+f"(d[51]), "+f"(d[52]), "+f"(d[53]), "+f"(d[54]), "+f"(d[55]), "+f"(d[56]), "+f"(d[57]), "+f"(d[58]), "+f"(d[59]), "+f"(d[60]), "+f"(d[61]), "+f"(d[62]), "+f"(d[63]), "+f"(d[64]), "+f"(d[65]), "+f"(d[66]), "+f"(d[67]), "+f"(d[68]), "+f"(d[69]), "+f"(d[70]), "+f"(d[71]), "+f"(d[72]), "+f"(d[73]), "+f"(d[74]), "+f"(d[75]), "+f"(d[76]), "+f"(d[77]), "+f"(d[78]), "+f"(d[79])
    : "r"(a0), "r"(a1), "r"(a2), "r"(a3), "l"(db), "r"(scale_d), "n"(TB));
}
template <int TB, int TA = 0>
__device__ __forceinline__ void wgmma_ss_n192(float (&d)[96], uint64_t da, uint64_t db, int scale_d) {
  asm volatile("{\n.reg .pred p;\nsetp.ne.b32 p, %98, 0;\n"
    "wgmma.mma_async.sync.aligned.m64n192k16.f32.bf16.bf16 {%0, %1, %2, %3, %4, %5, %6, %7, %8, %9, %10, %11, %12, %13, %14, %15, %16, %17, %18, %19, %20, %21, %22, %23, %24, %25, %26, %27, %28, %29, %30, %31, %32, %33, %34, %35, %36, %37, %38, %39, %40, %41, %42, %43, %44, %45, %46, %47, %48, %49, %50, %51, %52, %53, %54, %55, %56, %57, %58, %59, %60, %61, %62, %63, %64, %65, %66, %67, %68, %69, %70, %71, %72, %73, %74, %75, %76, %77, %78, %79, %80, %81, %82, %83, %84, %85, %86, %87, %88, %89, %90, %91, %92, %93, %94, %95}, %96, %97, p, 1, 1, %99, %100;\n}\n"
    : "+f"(d[0]), "+f"(d[1]), "+f"(d[2]), "+f"(d[3]), "+f"(d[4]), "+f"(d[5]), "+f"(d[6]), "+f"(d[7]), "+f"(d[8]), "+f"(d[9]), "+f"(d[10]), "+f"(d[11]), "+f"(d[12]), "+f"(d[13]), "+f"(d[14]), "+f"(d[15]), "+f"(d[16]), "+f"(d[17]), "+f"(d[18]), "+f"(d[19]), "+f"(d[20]), "+f"(d[21]), "+f"(d[22]), "+f"(d[23]), "+f"(d[24]), "+f"(d[25]), "+f"(d[26]), "+f"(d[27]), "+f"(d[28]), "+f"(d[29]), "+f"(d[30]), "+f"(d[31]), "+f"(d[32]), "+f"(d[33]), "+f"(d[34]), "+f"(d[35]), "+f"(d[36]), "+f"(d[37]), "+f"(d[38]), "+f"(d[39]), "+f"(d[40]), "+f"(d[41]), "+f"(d[42]), "+f"(d[43]), "+f"(d[44]), "+f"(d[45]), "+f"(d[46]), "+f"(d[47]), "+f"(d[48]), "+f"(d[49]), "+f"(d[50]), "+f"(d[51]), "+f"(d[52]), "+f"(d[53]), "+f"(d[54]), "+f"(d[55]), "+f"(d[56]), "+f"(d[57]), "+f"(d[58]), "+f"(d[59]), "+f"(d[60]), "+f"(d[61]), "+f"(d[62]), "+f"(d[63]), "+f"(d[64]), "+f"(d[65]), "+f"(d[66]), "+f"(d[67]), "+f"(d[68]), "+f"(d[69]), "+f"(d[70]), "+f"(d[71]), "+f"(d[72]), "+f"(d[73]), "+f"(d[74]), "+f"(d[75]), "+f"(d[76]), "+f"(d[77]), "+f"(d[78]), "+f"(d[79]), "+f"(d[80]), "+f"(d[81]), "+f"(d[82]), "+f"(d[83]), "+f"(d[84]), "+f"(d[85]), "+f"(d[86]), "+f"(d[87]), "+f"(d[88]), "+f"(d[89]), "+f"(d[90]), "+f"(d[91]), "+f"(d[92]), "+f"(d[93]), "+f"(d[94]), "+f"(d[95])
    : "l"(da), "l"(db), "r"(scale_d), "n"(TA), "n"(TB));
}
template <int TB>
__device__ __forceinline__ void wgmma_rs_n192(float (&d)[96], uint32_t a0, uint32_t a1, uint32_t a2, uint32_t a3, uint64_t db, int scale_d) {
  asm volatile("{\n.reg .pred p;\nsetp.ne.b32 p, %101, 0;\n"
    "wgmma.mma_async.sync.aligned.m64n192k16.f32.bf16.bf16 {%0, %1, %2, %3, %4, %5, %6, %7, %8, %9, %10, %11, %12, %13, %14, %15, %16, %17, %18, %19, %20, %21, %22, %23, %24, %25, %26, %27, %28, %29, %30, %31, %32, %33, %34, %35, %36, %37, %38, %39, %40, %41, %42, %43, %44, %45, %46, %47, %48, %49, %50, %51, %52, %53, %54, %55, %56, %57, %58, %59, %60, %61, %62, %63, %64, %65, %66, %67, %68, %69, %70, %71, %72, %73, %74, %75, %76, %77, %78, %79, %80, %81, %82, %83, %84, %85, %86, %87, %88, %89, %90, %91, %92, %93, %94, %95}, {%96, %97, %98, %99}, %100, p, 1, 1, %102;\n}\n"
    : "+f"(d[0]), "+f"(d[1]), "+f"(d[2]), "+f"(d[3]), "+f"(d[4]), "+f"(d[5]), "+f"(d[6]), "+f"(d[7]), "+f"(d[8]), "+f"(d[9]), "+f"(d[10]), "+f"(d[11]), "+f"(d[12]), "+f"(d[13]), "+f"(d[14]), "+f"(d[15]), "+f"(d[16]), "+f"(d[17]), "+f"(d[18]), "+f"(d[19]), "+f"(d[20]), "+f"(d[21]), "+f"(d[22]), "+f"(d[23]), "+f"(d[24]), "+f"(d[25]), "+f"(d[26]), "+f"(d[27]), "+f"(d[28]), "+f"(d[29]), "+f"(d[30]), "+f"(d[31]), "+f"(d[32]), "+f"(d[33]), "+f"(d[34]), "+f"(d[35]), "+f"(d[36]), "+f"(d[37]), "+f"(d[38]), "+f"(d[39]), "+f"(d[40]), "+f"(d[41]), "+f"(d[42]), "+f"(d[43]), "+f"(d[44]), "+f"(d[45]), "+f"(d[46]), "+f"(d[47]), "+f"(d[48]), "+f"(d[49]), "+f"(d[50]), "+f"(d[51]), "+f"(d[52]), "+f"(d[53]), "+f"(d[54]), "+f"(d[55]), "+f"(d[56]), "+f"(d[57]), "+f"(d[58]), "+f"(d[59]), "+f"(d[60]), "+f"(d[61]), "+f"(d[62]), "+f"(d[63]), "+f"(d[64]), "+f"(d[65]), "+f"(d[66]), "+f"(d[67]), "+f"(d[68]), "+f"(d[69]), "+f"(d[70]), "+f"(d[71]), "+f"(d[72]), "+f"(d[73]), "+f"(d[74]), "+f"(d[75]), "+f"(d[76]), "+f"(d[77]), "+f"(d[78]), "+f"(d[79]), "+f"(d[80]), "+f"(d[81]), "+f"(d[82]), "+f"(d[83]), "+f"(d[84]), "+f"(d[85]), "+f"(d[86]), "+f"(d[87]), "+f"(d[88]), "+f"(d[89]), "+f"(d[90]), "+f"(d[91]), "+f"(d[92]), "+f"(d[93]), "+f"(d[94]), "+f"(d[95])
    : "r"(a0), "r"(a1), "r"(a2), "r"(a3), "l"(db), "r"(scale_d), "n"(TB));
}

__device__ __forceinline__ uint32_t smem_u32(const void* p) { return (uint32_t)__cvta_generic_to_shared(p); }
__device__ __forceinline__ void wg_fence() { asm volatile("wgmma.fence.sync.aligned;" ::: "memory"); }
__device__ __forceinline__ void wg_commit() { asm volatile("wgmma.commit_group.sync.aligned;" ::: "memory"); }
template <int N> __device__ __forceinline__ void wg_wait() { asm volatile("wgmma.wait_group.sync.aligned %0;" ::"n"(N) : "memory"); }
__device__ __forceinline__ void sched_fence(uint32_t& keep, bool never) {
  asm volatile("{\n.reg .pred p;\nsetp.ne.b32 p, %1, 0;\n@p mov.u32 %0, %%clock;\n}\n" : "+r"(keep) : "r"((int)never) : "memory");
}
template <int N> __device__ __forceinline__ void fence_regs(float (&r)[N]) {
#pragma unroll
  for (int i = 0; i < N; i++) asm volatile("" : "+f"(r[i])::"memory");
}
template <int N> __device__ __forceinline__ void undefine(float (&r)[N]) {
#pragma unroll
  for (int i = 0; i < N; i++) asm volatile("" : "=f"(r[i]));
}
template <int N> __device__ __forceinline__ void fence_regs(uint32_t (&r)[N]) {
#pragma unroll
  for (int i = 0; i < N; i++) asm volatile("" : "+r"(r[i])::"memory");
}
__device__ __forceinline__ uint64_t mk_desc(uint32_t a16, uint32_t lbo, uint32_t sbo, uint32_t swz) {
  uint64_t d;
  asm("mov.b64 %0, {%1, %2};" : "=l"(d) : "r"(a16 + ((lbo >> 4) << 16)), "r"((sbo >> 4) | (swz << 30)));
  return d;
}
__device__ __forceinline__ void mbar_init(uint32_t bar, uint32_t cnt) {
  asm volatile("mbarrier.init.shared::cta.b64 [%0], %1;" ::"r"(bar), "r"(cnt) : "memory");
}
__device__ __forceinline__ void mbar_expect(uint32_t bar, uint32_t tx) {
  asm volatile("mbarrier.arrive.expect_tx.shared::cta.b64 _, [%0], %1;" ::"r"(bar), "r"(tx) : "memory");
}
__device__ __forceinline__ bool mbar_test(uint32_t bar, uint32_t ph) {
  uint32_t ok;
  asm volatile("{\n.reg .pred p;\nmbarrier.test_wait.parity.shared::cta.b64 p, [%1], %2;\nselp.u32 %0, 1, 0, p;\n}\n"
               : "=r"(ok) : "r"(bar), "r"(ph) : "memory");
  return ok;
}
__device__ __forceinline__ void mbar_wait(uint32_t bar, uint32_t ph) {
  asm volatile("{\n.reg .pred p;\n.reg .u32 n;\nmov.u32 n, 0;\n"
               "LOOP:\nmbarrier.try_wait.parity.shared::cta.b64 p, [%0], %1;\n@p bra DONE;\n"
               "add.u32 n, n, 1;\nsetp.lt.u32 p, n, 0x1000000;\n@p bra LOOP;\ntrap;\n"
               "DONE:\n}\n" ::"r"(bar), "r"(ph) : "memory");
}
template <int NS> __device__ __forceinline__ void mbar_wait_slow(uint32_t bar, uint32_t ph) {
  asm volatile("{\n.reg .pred p;\n.reg .u32 n;\nmov.u32 n, 0;\n"
               "LOOP:\nmbarrier.test_wait.parity.shared::cta.b64 p, [%0], %1;\n@p bra DONE;\n"
               "nanosleep.u32 %2;\nadd.u32 n, n, 1;\nsetp.lt.u32 p, n, 0x400000;\n@p bra LOOP;\ntrap;\n"
               "DONE:\n}\n" ::"r"(bar), "r"(ph), "n"(NS) : "memory");
}
__device__ __forceinline__ void mbar_arrive_cluster_if(bool on, uint32_t addr) {
  asm volatile("{\n.reg .pred p;\nsetp.ne.b32 p, %1, 0;\n@p mbarrier.arrive.shared::cluster.b64 _, [%0];\n}\n" ::"r"(addr), "r"((int)on) : "memory");
}
__device__ __forceinline__ void tma2d(uint32_t dst, const CUtensorMap* m, uint32_t bar, int c0, int c1) {
  asm volatile("cp.async.bulk.tensor.2d.shared::cluster.global.mbarrier::complete_tx::bytes [%0], [%1, {%3, %4}], [%2];"
               ::"r"(dst), "l"(m), "r"(bar), "r"(c0), "r"(c1) : "memory");
}
__device__ __forceinline__ void tma3d(uint32_t dst, const CUtensorMap* m, uint32_t bar, int c0, int c1, int c2) {
  asm volatile("cp.async.bulk.tensor.3d.shared::cluster.global.mbarrier::complete_tx::bytes [%0], [%1, {%3, %4, %5}], [%2];"
               ::"r"(dst), "l"(m), "r"(bar), "r"(c0), "r"(c1), "r"(c2) : "memory");
}
__device__ __forceinline__ void tma3d_mc(uint32_t dst, const CUtensorMap* m, uint32_t bar, int c0, int c1, int c2) {
  asm volatile("cp.async.bulk.tensor.3d.shared::cluster.global.mbarrier::complete_tx::bytes.multicast::cluster"
               " [%0], [%1, {%3, %4, %5}], [%2], %6;"
               ::"r"(dst), "l"(m), "r"(bar), "r"(c0), "r"(c1), "r"(c2), "h"((uint16_t)3) : "memory");
}
__device__ __forceinline__ void tma3d_store(const CUtensorMap* m, uint32_t src, int c0, int c1, int c2) {
  asm volatile("cp.async.bulk.tensor.3d.global.shared::cta.bulk_group [%0, {%2, %3, %4}], [%1];"
               ::"l"(m), "r"(src), "r"(c0), "r"(c1), "r"(c2) : "memory");
}
__device__ __forceinline__ void bar_sync(int id, int n) { asm volatile("bar.sync %0, %1;" ::"r"(id), "r"(n) : "memory"); }
__device__ __forceinline__ uint32_t pack_bf16(float lo, float hi) {
  uint32_t r;
  asm("cvt.rn.bf16x2.f32 %0, %1, %2;" : "=r"(r) : "f"(hi), "f"(lo));
  return r;
}
__device__ __forceinline__ float ex2(float x) {
  float y;
  asm("ex2.approx.ftz.f32 %0, %1;" : "=f"(y) : "f"(x));
  return y;
}
__device__ __forceinline__ float rcp(float x) {
  float y;
  asm("rcp.approx.ftz.f32 %0, %1;" : "=f"(y) : "f"(x));
  return y;
}
__device__ __forceinline__ void stsm4(uint32_t addr, uint32_t a, uint32_t b, uint32_t c, uint32_t d) {
  asm volatile("stmatrix.sync.aligned.m8n8.x4.shared.b16 [%0], {%1, %2, %3, %4};" ::"r"(addr), "r"(a), "r"(b), "r"(c), "r"(d) : "memory");
}

__device__ __forceinline__ void tma4d_mc_hint(uint32_t dst, const CUtensorMap* m, uint32_t bar, int c3, uint64_t pol) {
  asm volatile("cp.async.bulk.tensor.4d.shared::cluster.global.mbarrier::complete_tx::bytes.multicast::cluster.L2::cache_hint"
               " [%0], [%1, {%3, %3, %3, %4}], [%2], %5, %6;"
               ::"r"(dst), "l"(m), "r"(bar), "r"(0), "r"(c3), "h"((uint16_t)3), "l"(pol) : "memory");
}
__device__ __forceinline__ void tma5d_mc(uint32_t dst, const CUtensorMap* m, uint32_t bar, int c2, int c4) {
  asm volatile("cp.async.bulk.tensor.5d.shared::cluster.global.mbarrier::complete_tx::bytes.multicast::cluster"
               " [%0], [%1, {%3, %3, %4, %3, %5}], [%2], %6;"
               ::"r"(dst), "l"(m), "r"(bar), "r"(0), "r"(c2), "r"(c4), "h"((uint16_t)3) : "memory");
}
__device__ __forceinline__ void bulk_load_hint(uint32_t dst, const void* src, uint32_t bytes, uint32_t bar, uint64_t pol) {
  asm volatile("cp.async.bulk.shared::cluster.global.mbarrier::complete_tx::bytes.L2::cache_hint [%0], [%1], %2, [%3], %4;"
               ::"r"(dst), "l"(src), "r"(bytes), "r"(bar), "l"(pol) : "memory");
}
__device__ __forceinline__ void stg128_hint(void* p, uint32_t a, uint32_t b, uint32_t c, uint32_t d, uint64_t pol) {
  asm volatile("st.global.L2::cache_hint.v4.b32 [%0], {%1, %2, %3, %4}, %5;" ::"l"(p), "r"(a), "r"(b), "r"(c), "r"(d), "l"(pol) : "memory");
}
__device__ __forceinline__ void stg2_if(bool on, void* p, uint32_t a, uint32_t b, uint32_t c, uint32_t d, uint32_t e, uint32_t f,
                                        uint32_t g, uint32_t h, uint64_t pol) {
  asm volatile("{\n.reg .pred p;\nsetp.ne.b32 p, %10, 0;\n"
               "@p st.global.L2::cache_hint.v4.b32 [%0], {%1, %2, %3, %4}, %9;\n"
               "@p st.global.L2::cache_hint.v4.b32 [%0 + 512], {%5, %6, %7, %8}, %9;\n}\n"
               ::"l"(p), "r"(a), "r"(b), "r"(c), "r"(d), "r"(e), "r"(f), "r"(g), "r"(h), "l"(pol), "r"((int)on) : "memory");
}
__device__ __forceinline__ uint64_t make_policy(bool first) {
  uint64_t pf, pn;
  asm("createpolicy.fractional.L2::evict_first.b64 %0, 1.0;" : "=l"(pf));
  asm("createpolicy.fractional.L2::evict_normal.b64 %0, 1.0;" : "=l"(pn));
  return first ? pf : pn;
}
__device__ __forceinline__ bool elect() {
  uint32_t ok;
  asm volatile("{\n.reg .pred p;\nelect.sync _|p, 0xffffffff;\nselp.u32 %0, 1, 0, p;\n}\n" : "=r"(ok));
  return ok;
}
__device__ __forceinline__ void mbar_arrive(uint32_t bar) {
  asm volatile("mbarrier.arrive.shared::cta.b64 _, [%0];" ::"r"(bar) : "memory");
}
__device__ __forceinline__ void mbar_arrive_if(bool on, uint32_t bar) {
  asm volatile("{\n.reg .pred p;\nsetp.ne.b32 p, %1, 0;\n@p mbarrier.arrive.shared::cta.b64 _, [%0];\n}\n" ::"r"(bar), "r"((int)on) : "memory");
}
__device__ __forceinline__ void stg128(void* p, uint32_t a, uint32_t b, uint32_t c, uint32_t d) {
  asm volatile("st.global.v4.b32 [%0], {%1, %2, %3, %4};" ::"l"(p), "r"(a), "r"(b), "r"(c), "r"(d) : "memory");
}
__device__ __forceinline__ void lds128(uint32_t p, uint32_t& a, uint32_t& b, uint32_t& c, uint32_t& d) {
  asm volatile("ld.shared.v4.b32 {%0, %1, %2, %3}, [%4];" : "=r"(a), "=r"(b), "=r"(c), "=r"(d) : "r"(p) : "memory");
}
template <class T> __device__ __forceinline__ T* ptr_add(T* base, uint32_t bytes) {
  T* r;
  asm("{\n.reg .u32 lo, hi;\nmov.b64 {lo, hi}, %1;\nadd.cc.u32 lo, lo, %2;\naddc.u32 hi, hi, 0;\nmov.b64 %0, {lo, hi};\n}\n" : "=l"(r) : "l"(base), "r"(bytes));
  return r;
}
__device__ __forceinline__ uint32_t flag_peek(const unsigned int* p) {
  uint32_t v;
  asm volatile("ld.relaxed.gpu.global.u32 %0, [%1];" : "=r"(v) : "l"(p) : "memory");
  return v;
}
__device__ __forceinline__ uint32_t flag_get(const unsigned int* p) {
  uint32_t v;
  asm volatile("ld.acquire.gpu.global.u32 %0, [%1];" : "=r"(v) : "l"(p) : "memory");
  return v;
}
__device__ __forceinline__ void wait_progress(uint32_t p, uint32_t target) {
  asm volatile("{\n.reg .pred p;\n.reg .u32 n, v;\nmov.u32 n, 0;\n"
               "LOOP:\nld.acquire.cta.shared.u32 v, [%0];\nsetp.ge.u32 p, v, %1;\n@p bra DONE;\n"
               "nanosleep.u32 %2;\nadd.u32 n, n, 1;\nsetp.lt.u32 p, n, 0x400000;\n@p bra LOOP;\ntrap;\n"
               "DONE:\n}\n" ::"r"(p), "r"(target), "n"(400) : "memory");
}
__device__ __forceinline__ void flag_set(unsigned int* p, uint32_t v) {
  asm volatile("st.release.gpu.global.u32 [%0], %1;" ::"l"(p), "r"(v) : "memory");
}
__device__ __forceinline__ void flag_dec(unsigned int* p) {
  asm volatile("red.relaxed.gpu.global.add.u32 [%0], 0xffffffff;" ::"l"(p) : "memory");
}

struct Cursor {
  int bi;
  uint32_t ph;
  __device__ __forceinline__ void next() {
    if (++bi == NBAR) { bi = 0; ph ^= 1; }
  }
};

constexpr float kScaleLog2 = 0.07216878364870322f * 1.4426950408889634f;
constexpr float kSumLimit = 1048576.0f;

__global__ void __cluster_dims__(2, 1, 1) __launch_bounds__(384, 1)
fused_kernel(const __grid_constant__ Params P) {
  extern __shared__ uint8_t smem_raw[];
  const uint32_t sbase = (smem_u32(smem_raw) + 1023) & ~1023u;
  const uint32_t full0 = sbase + RING, empty0 = full0 + 8 * NBAR, odone0 = empty0 + 8 * NBAR, ev0 = odone0 + 8 * MAX_OPS;
  const uint32_t progress = ev0 + 8 * MAX_EV;
  const uint32_t rank = blockIdx.x & 1;
  const int role = blockIdx.x >> 1;
  const int wid = __shfl_sync(0xffffffffu, (int)(threadIdx.x >> 5), 0);
  const int wg = wid >> 2;

  const uint32_t op0 = P.first[role];
  if (__builtin_expect(wid == 8, 1)) {
    if (elect()) {
#pragma unroll
      for (int k = 0; k < EARLY; k++) mbar_init(full0 + 8 * k, 1);
      asm volatile("fence.mbarrier_init.release.cluster;" ::: "memory");
      const int blk = (op0 >> 10) & 1;
      if ((op0 & 3) == OP_Q) {
#pragma unroll
        for (int k = 0; k < EARLY; k++) {
          mbar_expect(full0 + 8 * k, SZ_Q);
          tma2d(sbase + k * SZ_Q, &P.x[blk], full0 + 8 * k, 64 * k, ((op0 >> 7) & 7) * kSq + rank * 128);
          tma3d(sbase + k * SZ_Q + 16384, &P.wq[blk], full0 + 8 * k, 0, 64 * k, 3 * ((op0 >> 2) & 31));
        }
      }
      asm volatile("prefetch.tensormap [%0];" ::"l"(rank ? &P.v[blk] : &P.k[blk]) : "memory");
    }
  } else if (wg < 2 && elect()) {
#pragma unroll
    for (int j = 0; j < 16; j++) {
      const int i = EARLY + 16 * wid + j;
      if (i < 2 * NBAR + MAX_OPS + MAX_EV) mbar_init(full0 + 8 * i, i < NBAR ? 1 : i < 2 * NBAR ? 16 : i < 2 * NBAR + MAX_OPS ? 8 : 1);
    }
    if (wid == 7) asm volatile("st.shared.u32 [%0], 0;\nfence.acq_rel.cta;" ::"r"(progress) : "memory");
    asm volatile("fence.mbarrier_init.release.cluster;" ::: "memory");
  }
  __syncwarp();
  asm volatile("barrier.cluster.arrive.relaxed.aligned;\nbarrier.cluster.wait.aligned;" ::: "memory");

  if (wg < 2) {
    asm volatile("setmaxnreg.inc.sync.aligned.u32 240;");
    const uint32_t* prog = P.prog[role].c;
    const int lane = threadIdx.x & 31, warp = wid & 3;
    uint32_t empty_rem;
    asm volatile("mapa.shared::cluster.u32 %0, %1, %2;" : "=r"(empty_rem) : "r"(empty0), "r"(lane & 1));
    auto release = [&](int slot) { mbar_arrive_cluster_if(lane < 2, empty_rem + 8 * slot); };
    Cursor r{0, 0};
    const uint32_t ring16 = (sbase & 0x3FFFF) >> 4;
    uint32_t cur = ring16;
    bool rdy0 = false, rdy1 = false;
    auto probe1 = [&]() { rdy0 = mbar_test(full0 + 8 * r.bi, r.ph); };
    auto probe2 = [&]() {
      Cursor n = r;
      rdy0 = mbar_test(full0 + 8 * n.bi, n.ph);
      n.next();
      rdy1 = mbar_test(full0 + 8 * n.bi, n.ph);
    };
    auto take = [&](bool rdy, uint32_t bytes, uint32_t& addr) {
      const int bi = r.bi;
      if (__builtin_expect(!__all_sync(0xffffffffu, rdy), 0)) mbar_wait(full0 + 8 * r.bi, r.ph);
      r.next();
      if (cur > ring16 + ((RING - bytes) >> 4)) cur = ring16;
      addr = cur;
      cur += bytes >> 4;
      return bi;
    };
    uint32_t keep = 0;
    const bool never = P.dbg == 0xffffffffu;
    uint32_t q[48];
#pragma unroll
    for (int i = 0; i < 48; i++) q[i] = 0;
    const int row = wg * 64 + warp * 16 + (lane >> 2);
    const int img0 = row * 4 + ((lane & 3) ^ ((row >> 1) & 3));
    uint4* pend = nullptr;
    bool pend_any = false;
    uint64_t spol;
    int pc = 0;
    auto slab = [&](int c, int i0) {
#pragma unroll
      for (int i = i0; i < 6; i++)
        stg2_if(c == i, pend + i * 512, q[8 * i], q[8 * i + 1], q[8 * i + 2], q[8 * i + 3],
                q[8 * i + 4], q[8 * i + 5], q[8 * i + 6], q[8 * i + 7], spol);
    };
    auto drain = [&](int c) {
      if (!pend_any || c >= 6) return;
      slab(c, 0);
      if (c == 5) {
        __syncwarp();
        mbar_arrive_if(lane == 0, odone0 - 8 + 8 * pc);
      }
    };

    for (;; pc++) {
      uint32_t op = prog[pc];
      const int type = op & 3;
      auto enter = [&]() {
        r.bi = (op >> 15) & 15; r.ph = (op >> 19) & 1; cur = ring16 + (((op >> 20) & 63) << 8);
      };
      enter();
      pend_any = op & C_PEND;
      spol = make_policy(!(op & C_SOON));
      if (type == OP_END) {
#pragma unroll 1
        for (int c = 0; c < 6; c++) drain(c);
        asm volatile("barrier.cluster.arrive.relaxed;" ::: "memory");
        break;
      }
      {
        float s[32], o[96];
        uint32_t ad0;
        int bi0, sk1;
        uint32_t pa[16], pb[16];
        float mc0, mc1, l0, l1;
        bool shifted;
        uint32_t nop;
        auto expo = [&](float (&s)[32], uint32_t (&pout)[16], float& b0, float& b1, bool shift, auto mid) {
          float c0, c1;
#pragma unroll
          for (int i = 0; i < 8; i++) {
            const float e0 = ex2(shift ? s[4 * i] - mc0 : s[4 * i]), e1 = ex2(shift ? s[4 * i + 1] - mc0 : s[4 * i + 1]);
            const float e2 = ex2(shift ? s[4 * i + 2] - mc1 : s[4 * i + 2]), e3 = ex2(shift ? s[4 * i + 3] - mc1 : s[4 * i + 3]);
            if (i) { b0 += e0; c0 += e1; b1 += e2; c1 += e3; } else { b0 = e0; c0 = e1; b1 = e2; c1 = e3; }
            pout[2 * i] = pack_bf16(e0, e1); pout[2 * i + 1] = pack_bf16(e2, e3);
            if (i & 1) mid(i >> 1);
          }
          b0 += c0; b1 += c1;
        };
        auto rowmax = [&](float (&s)[32], float& m0, float& m1) {
          m0 = fmaxf(s[0], s[1]); m1 = fmaxf(s[2], s[3]);
#pragma unroll
          for (int i = 1; i < 8; i++) { m0 = fmaxf(m0, fmaxf(s[4 * i], s[4 * i + 1])); m1 = fmaxf(m1, fmaxf(s[4 * i + 2], s[4 * i + 3])); }
          m0 = fmaxf(m0, __shfl_xor_sync(0xffffffffu, m0, 1)); m1 = fmaxf(m1, __shfl_xor_sync(0xffffffffu, m1, 1));
          m0 = fmaxf(m0, __shfl_xor_sync(0xffffffffu, m0, 2)); m1 = fmaxf(m1, __shfl_xor_sync(0xffffffffu, m1, 2));
        };
        auto first = [&](float (&s)[32], int sk0, auto mid) {
          fence_regs(s);
          release(sk0);
          mc0 = 0.f; mc1 = 0.f;
          expo(s, pa, l0, l1, false, mid);
          shifted = __any_sync(0xffffffffu, !(fmaxf(l0, l1) <= kSumLimit && fminf(l0, l1) >= 1.f / kSumLimit));
          if (shifted) {
            rowmax(s, mc0, mc1);
            expo(s, pa, l0, l1, true, [](int) {});
          }
        };
        auto qk = [&](float (&s)[32], uint32_t ak, int k0 = 0, int k1 = 12) {
#pragma unroll
          for (int kk = k0; kk < k1; kk++)
            wgmma_rs_n64<0>(s, q[4 * kk], q[4 * kk + 1], q[4 * kk + 2], q[4 * kk + 3], mk_desc(ak + (kk >> 2) * KV_CH + (kk & 3) * 2, 16, KV_SBO, 1), kk != 0);
          if (k1 == 12) wg_commit();
        };
        auto pv = [&](uint32_t (&pin)[16], uint32_t av, int acc) {
#pragma unroll
          for (int kk = 0; kk < 4; kk++)
            wgmma_rs_n192<1>(o, pin[4 * kk], pin[4 * kk + 1], pin[4 * kk + 2], pin[4 * kk + 3], mk_desc(av + kk * (KV_SBO / 8), KV_CH * 16, KV_SBO, 1), acc || (kk != 0));
          wg_commit();
        };
        auto finish = [&](uint32_t (&pout)[16], int sk, int sv) {
          probe2();
          wg_wait<1>();
          fence_regs(s);
          release(sk);
          float b0, b1;
#pragma unroll 1
          for (bool redo = false;; redo = true) {
            expo(s, pout, b0, b1, false, [](int) {});
            if (!__any_sync(0xffffffffu, !redo && (shifted || !(fmaxf(b0, b1) <= kSumLimit)))) break;
            shifted = true;
            rowmax(s, b0, b1);
            b0 = fmaxf(mc0, b0); b1 = fmaxf(mc1, b1);
            const float a0 = ex2(mc0 - b0), a1 = ex2(mc1 - b1);
            mc0 = b0; mc1 = b1;
            l0 *= a0; l1 *= a1;
            wg_wait<0>();
            fence_regs(o);
#pragma unroll
            for (int i = 0; i < 24; i++) { o[4 * i] *= a0; o[4 * i + 1] *= a0; o[4 * i + 2] *= a1; o[4 * i + 3] *= a1; }
#pragma unroll
            for (int i = 0; i < 32; i++) s[i] -= (i & 2) ? mc1 : mc0;
          }
          l0 += b0; l1 += b1;
          wg_wait<0>();
          fence_regs(o);
          release(sv);
        };
        auto step = [&](uint32_t (&pin)[16], uint32_t (&pout)[16]) {
          uint32_t ak, av;
          const int sk = take(rdy0, SZ_KV, ak), sv = take(rdy1, SZ_KV, av);
          wg_fence();
          qk(s, ak);
          pv(pin, av, 1);
          finish(pout, sk, sv);
        };
        auto unpark = [&]() {
          uint32_t ad, ak;
          const int bi = take(rdy0, SZ_PARK, ad);
#pragma unroll
          for (int i = 0; i < 12; i++) lds128(sbase + (ad - ring16 + img0) * 16 + (i >> 1) * 8192 + (i & 1) * 512, q[4 * i], q[4 * i + 1], q[4 * i + 2], q[4 * i + 3]);
          const int sk0 = take(false, SZ_KV, ak);
          fence_regs(q);
          release(bi);
          wg_fence();
          qk(s, ak);
          probe2();
          return sk0;
        };
        auto mma4 = [&](uint32_t ad, int acc) {
#pragma unroll
          for (int kk = 0; kk < 4; kk++)
            wgmma_ss_n192<1>(o, mk_desc(ad + wg * 512 + kk * 2, 16, 1024, 1), mk_desc(ad + 1024 + kk * 128, 8192, 1024, 1), acc || kk != 0);
        };
        auto convert = [&](int i0, int i1) {
          sched_fence(keep, never);
#pragma unroll
          for (int i = i0; i < i1; i++) q[i] = pack_bf16(o[2 * i] * kScaleLog2, o[2 * i + 1] * kScaleLog2);
          sched_fence(keep, never);
        };
        auto kend = [&](int bi, int k) {
          wg_commit();
          drain(k);
          probe1();
          wg_wait<0>();
          release(bi);
        };
        if (type == OP_O) {
          float c[80];
          const int nk = 3 * ((op >> 2) & 63), ro = (op >> 8) & 63;
          uint4* part = ptr_add(g_part, (ro * 2 + rank) * SZ_PARK + img0 * 16);
          int prev = 0;
          auto hand_over = [&](float (&c)[80], uint4* dst) {
            fence_regs(c);
#pragma unroll
            for (int i = 0; i < 48; i++) q[i] = i < 8 ? 0 : pack_bf16(c[2 * i - 16], c[2 * i - 15]);
            pend = dst;
          };
          auto mma2 = [&](float (&c)[80], uint32_t da, uint32_t db, int acc) {
            wgmma_ss_n160<1>(c, mk_desc(da, 16, 512, 2), mk_desc(db, 2048, 512, 2), acc);
            wgmma_ss_n160<1>(c, mk_desc(da + 2, 16, 512, 2), mk_desc(db + 64, 2048, 512, 2), 1);
          };
          auto kstep = [&](float (&c)[80], int acc, auto hook, uint32_t bytes = SZ_O) {
            uint32_t ad;
            const int bi = take(rdy0, bytes, ad);
            const uint32_t da = ad + wg * 256, db = ad + 1024;
            wg_fence();
            mma2(c, da, db, acc);
            wg_commit();
            if (acc) { wg_wait<1>(); release(prev); }
            mma2(c, da + 512, db + 640, 1);
            wg_commit();
            prev = bi;
            hook();
            probe1();
            wg_wait<1>();
          };
          if (op & C_WIDE) {
            float d[80];
            auto wstep = [&](int acc, auto hook) {
              uint32_t ad;
              const int bi = take(rdy0, SZ_W, ad);
              const uint32_t da = ad + wg * 256, db = ad + 1024;
              wg_fence();
              mma2(d, da, db, acc);
              mma2(d, da + 512, db + 640, 1);
              wg_commit();
              if (acc) { wg_wait<1>(); release(prev); }
              mma2(c, da, db + 1280, acc);
              mma2(c, da + 512, db + 1920, 1);
              wg_commit();
              prev = bi;
              hook();
              probe1();
              wg_wait<1>();
            };
            wstep(0, [&]() { drain(0); drain(1); });
#pragma unroll 1
            for (int k = 2; k < 6; k += 2) wstep(1, [&]() { drain(k); drain(k + 1); });
#pragma unroll 1
            for (int k = 3 + 3 * TAIL; k < nk; k++) {
              wstep(1, []() {});
            }
#pragma unroll 1
            for (int k = 0; k < 3 * TAIL; k++) kstep(d, 1, []() {});
            nop = prog[pc + 1];
            spol = make_policy(!(nop & C_SOON));
            kstep(c, 1, [&]() { hand_over(d, part - 6144); });
#pragma unroll 1
            for (int k = 1; k < 3 * TAIL; k++) kstep(c, 1, [&]() { slab(TAIL == 2 ? k : (0x50403201 >> (4 * k - 4)) & 7, 1); });
            if ((nop & 3) == OP_Q) {
              op = nop;
              enter();
              pc++;
              pend_any = true;
              bi0 = take(rdy0, SZ_Q, ad0);
              undefine(o);
              wg_fence();
              mma4(ad0, 0);
              wg_commit();
              wg_wait<1>();
              release(prev);
              hand_over(c, part);
              probe1();
              wg_wait<0>();
              release(bi0);
              fence_regs(o);
              goto next_head;
            }
            wg_wait<0>();
            fence_regs(c);
            release(prev);
          } else {
            kstep(c, 0, [&]() { drain(0); });
#pragma unroll 1
            for (int k = 1; k < 6; k++) kstep(c, 1, [&]() { drain(k); });
#pragma unroll 1
            for (int k = (op & C_LD) ? 11 : 6; k < nk; k++) kstep(c, 1, []() {});
            if (op & C_LD) {
              uint32_t t[40];
              float u[80];
              auto unpack = [&](int j) {
#pragma unroll
                for (int i = 8 * j; i < 8 * j + 8; i++) {
                  u[2 * i] = __uint_as_float(t[i] << 16); u[2 * i + 1] = __uint_as_float(t[i] & 0xffff0000u);
                  asm volatile("" : "+f"(u[2 * i]), "+f"(u[2 * i + 1]));
                }
              };
#pragma unroll
              for (int j = 0; j < 5; j++)
                kstep(c, 1, [&]() {
#pragma unroll
                  for (int i = 0; i < 2; i++)
                    lds128(sbase + (cur - ring16 + img0) * 16 - 8192 + i * 512, t[8 * j + 4 * i], t[8 * j + 4 * i + 1], t[8 * j + 4 * i + 2], t[8 * j + 4 * i + 3]);
                  if (j) unpack(j - 1);
                }, SZ_OL);
              unpack(4);
              sched_fence(keep, never);
              wg_wait<0>();
              fence_regs(c);
              release(prev);
#pragma unroll
              for (int i = 0; i < 80; i++) c[i] += u[i];
            } else {
              wg_wait<0>();
              fence_regs(c);
              release(prev);
            }
          }
          if (op & C_WIDE) {
            hand_over(c, part);
            continue;
          }
          {
            asm volatile("barrier.cluster.arrive.relaxed;" ::: "memory");
            bar_sync(1, 256);
            const uint32_t wstage = sbase + (wg * 4 + warp) * 5120;
            const uint32_t sa = wstage + (lane & 15) * 64;
#pragma unroll
            for (int i = 0; i < 10; i++) {
              const int u = (i & 1) * 2 + (lane >> 4);
              stsm4(sa + (i >> 1) * 1024 + ((u ^ ((lane >> 1) & 3)) << 4), pack_bf16(c[8 * i], c[8 * i + 1]), pack_bf16(c[8 * i + 2], c[8 * i + 3]),
                    pack_bf16(c[8 * i + 4], c[8 * i + 5]), pack_bf16(c[8 * i + 6], c[8 * i + 7]));
            }
            asm volatile("fence.proxy.async.shared::cta;" ::: "memory");
            __syncwarp();
            if (lane == 0) {
              tma3d_store(&P.out, wstage, 0, ((ro >> 2) & 7) * kSq + rank * 128 + wg * 64 + warp * 16, (ro >> 5) * 20 + (ro & 3) * 5);
              asm volatile("cp.async.bulk.commit_group;\ncp.async.bulk.wait_group.read 0;" ::: "memory");
            }
            __syncwarp();
            break;
          }
        }
        bi0 = take(rdy0, SZ_Q, ad0);
        undefine(o);
        wg_fence();
        mma4(ad0, 0);
        kend(bi0, 0);
        fence_regs(o);
      next_head:
        {
#pragma unroll 1
          for (int k = 1; k < ((op & F_PARK) ? 10 : 8); k++) {
            uint32_t ad;
            const int bi = take(rdy0, SZ_Q, ad);
            wg_fence();
            mma4(ad, 1);
            kend(bi, k);
          }
          if (op & F_PARK) {
            fence_regs(o);
            convert(0, 48);
            pend = ptr_add(g_t, (((op >> 2) & 511) * 2 + rank) * SZ_PARK + img0 * 16);
            continue;
          }
          uint32_t a8, a9, ak0, ak1;
          const int b8 = take(rdy0, SZ_Q, a8), b9 = take(false, SZ_Q, a9);
          wg_fence();
          mma4(a8, 1);
          wg_commit();
          mma4(a9, 1);
          wg_commit();
          pc++;
          wg_wait<1>();
          release(b8);
          const int sk0 = take(false, SZ_KV, ak0);
          wg_wait<0>();
          fence_regs(o);
          release(b9);
          float s0[32];
          convert(0, 32);
          wg_fence();
          qk(s0, ak0, 0, 4);
          convert(32, 48);
          wg_fence();
          qk(s0, ak0, 4, 12);
          sk1 = take(false, SZ_KV, ak1);
          probe1();
          wg_wait<0>();
          first(s0, sk0, [&](int i) {
            if (i == 0) return;
            sched_fence(keep, never);
            wg_fence();
            if (i == 1) qk(s, ak1, 0, 4);
            if (i == 2) qk(s, ak1, 4, 8);
            if (i == 3) qk(s, ak1, 8, 12);
            sched_fence(keep, never);
          });
        }
        for (;;) {
          {
            uint32_t av;
            const int sv = take(rdy0, SZ_KV, av);
            undefine(o);
            wg_fence();
            pv(pa, av, 0);
            finish(pb, sk1, sv);
          }
          nop = prog[pc + 1];
#pragma unroll 1
          for (int jj = 0; jj < 7; jj++) {
            step(pb, pa);
            step(pa, pb);
          }
          float i0, i1;
          auto last = [&]() {
            uint32_t av;
            const int sv = take(rdy0, SZ_KV, av);
            wg_fence();
            pv(pb, av, 1);
            sched_fence(keep, never);
            probe1();
            l0 += __shfl_xor_sync(0xffffffffu, l0, 1); l1 += __shfl_xor_sync(0xffffffffu, l1, 1);
            l0 += __shfl_xor_sync(0xffffffffu, l0, 2); l1 += __shfl_xor_sync(0xffffffffu, l1, 2);
            i0 = rcp(l0); i1 = rcp(l1);
            pend = ptr_add(g_t, (((op >> 2) & 511) * 2 + rank) * SZ_PARK + img0 * 16);
            return sv;
          };
          auto normalise = [&](uint32_t (&d)[48], auto mid) {
#pragma unroll
            for (int i = 0; i < 24; i++) {
              d[8 * (i >> 2) + (i & 3)] = pack_bf16(o[4 * i] * i0, o[4 * i + 1] * i0);
              d[8 * (i >> 2) + (i & 3) + 4] = pack_bf16(o[4 * i + 2] * i1, o[4 * i + 3] * i1);
              if ((i & 3) == 3 && i != 23) { sched_fence(keep, never); mid(i >> 2); }
            }
          };
          const int sv = last();
          if ((nop & 3) != OP_A) {
            op = nop;
            enter();
            pend_any = true;
            spol = make_policy(!(op & C_SOON));
            bi0 = take(rdy0 || (nop & 3) != OP_Q, SZ_Q, ad0);
            sched_fence(keep, never);
            wg_wait<0>();
            fence_regs(o);
            release(sv);
            normalise(q, [](int) {});
            undefine(o);
            if ((nop & 3) != OP_Q) break;
            sched_fence(keep, never);
            wg_fence();
            mma4(ad0, 0);
            pc++;
            kend(bi0, 0);
            fence_regs(o);
            goto next_head;
          }
          const int sk0 = unpark();
          wg_wait<1>();
          fence_regs(o);
          release(sv);
          uint32_t t[48];
          spol = make_policy(!(nop & C_SOON));
          auto st = [&](int i) {
            stg2_if(true, pend + i * 512, t[8 * i], t[8 * i + 1], t[8 * i + 2], t[8 * i + 3], t[8 * i + 4], t[8 * i + 5], t[8 * i + 6], t[8 * i + 7], spol);
          };
          normalise(t, [&](int i) { if (!(i & 1)) st(i >> 1); });
          wg_wait<0>();
          first(s, sk0, [&](int i) { if (i < 3) { sched_fence(keep, never); st(3 + i); } });
          __syncwarp();
          mbar_arrive_if(lane == 0, odone0 + 8 * pc);
          pc++;
          op = nop;
          uint32_t ak1;
          sk1 = take(rdy0, SZ_KV, ak1);
          rdy0 = rdy1;
          wg_fence();
          qk(s, ak1);
        }
      }
    }
    if (never) g_flag[0] = keep;
    asm volatile("barrier.cluster.wait;" ::: "memory");
  } else {
    asm volatile("setmaxnreg.dec.sync.aligned.u32 24;");
    const uint32_t* prog = P.prog[role].p;
    unsigned int* flag = g_flag + rank;
    if (wid == 8) {
      Cursor tail{0, 0};
      int head = 0, sh = 0;
      uint32_t cur = 0, used = 0;
      uint64_t fifo = 0;
      uint32_t dst, bar, ev = ev0, done = 0;
      uint64_t pol;
      asm volatile("createpolicy.fractional.L2::evict_first.b64 %0, 1.0;" : "=l"(pol));
      auto retire = [&]() {
        mbar_wait(empty0 + 8 * tail.bi, tail.ph);
        tail.next();
        used -= (uint32_t)fifo & 31;
        fifo >>= 5;
        sh -= 5;
        asm volatile("st.volatile.shared.u32 [%0], %1;" ::"r"(progress), "r"(++done) : "memory");
      };
      auto acquire = [&](uint32_t bytes) {
        uint32_t fp = bytes >> 12;
        if (cur + fp > (RING >> 12)) { fp += (RING >> 12) - cur; cur = 0; }
        used += fp;
        while (used > (RING >> 12) || sh == 5 * NBAR) retire();
        fifo |= (uint64_t)fp << sh;
        sh += 5;
        dst = sbase + (cur << 12);
        bar = full0 + 8 * head;
        cur += bytes >> 12;
        if (++head == NBAR) head = 0;
      };
      auto gate = [&]() {
        mbar_wait(ev, 0);
        ev += 8;
        asm volatile("fence.proxy.async.global;" ::: "memory");
      };
      for (int pc = 0;; pc++) {
        const uint32_t op = prog[pc];
        const int type = op & 3, blk = (op >> 10) & 1;
        if (type == OP_END) break;
        if (type == OP_Q) {
#pragma unroll 1
          for (int k = 0; k < 10; k++) {
            if (k == 9 && (op & P_GATE)) gate();
            acquire(SZ_Q);
            if ((pc > 0 || k >= EARLY) && elect()) {
              mbar_expect(bar, SZ_Q);
              tma2d(dst, &P.x[blk], bar, 64 * k, ((op >> 7) & 7) * kSq + rank * 128);
              if ((k & 1) == rank) tma3d_mc(dst + 16384, &P.wq[blk], bar, 0, 64 * k, 3 * ((op >> 2) & 31));
            }
          }
        } else if (type == OP_A) {
          const int row0 = ((op >> 2) & 255) * kSk;
          const CUtensorMap* kv_map = rank ? &P.v[blk] : &P.k[blk];
          if (op & F_PARK) {
            gate();
            acquire(SZ_PARK);
            if (elect()) {
              mbar_expect(bar, SZ_PARK);
              bulk_load_hint(dst, &g_t[((op >> 20) * 2 + rank) * 3072], SZ_PARK, bar, make_policy(P.dbg & 4));
            }
          }
#pragma unroll 1
          for (int t = 0; t < 32; t++) {
            const int isv = t == 31 ? 1 : (t == 0 ? 0 : (~t & 1));
            const int j = isv ? (t - 1) >> 1 : (t + 1) >> 1;
            if (t == 31 && (op & P_GATE)) gate();
            acquire(SZ_KV);
            if (elect()) {
              mbar_expect(bar, SZ_KV);
              if (isv == (int)rank) tma4d_mc_hint(dst, kv_map, bar, row0 / 8 + 8 * j, pol);
            }
          }
        } else {
          const int n = (op >> 13) & 63, nw = (op & P_WIDE) ? n - TAIL : 0;
          const uint64_t pol_o = make_policy(P.dbg & (nw ? 1 : 2));
          const uint4* part = &g_part[((((op >> 5) & 60) + ((op >> 19) & 3)) * 2 + rank) * 3072 + 512];
#pragma unroll 1
          for (int i = 0; i < n + (nw ? TAIL : 0); i++) {
            const int id = ((op >> 2) & 511) + (i < n ? i : i - TAIL), col = 5 * (((op >> 19) & 3) + (i >= n));
            const uint4* src = &g_t[(P.slot[id] * 2 + rank) * 3072];
            if ((op & P_LD) && i == ((op & P_PRE) ? 0 : n - 2)) gate();
            if (i < n) gate();
#pragma unroll 1
            for (int k = 0; k < 3; k++) {
              const uint32_t j = (op & P_LD) ? 3 * (i - n) + k + 5 : 5, bytes = i < nw ? SZ_W : j < 5 ? SZ_OL : SZ_O;
              acquire(bytes);
              if (elect()) {
                mbar_expect(bar, bytes);
                tma5d_mc(dst + 16384 + rank * 10240, &P.wo[blk], bar, 24 * (id & 31) + 8 * k + 4 * rank, col);
                bulk_load_hint(dst, src + k * 1024, 16384, bar, pol_o);
                if (i < nw) tma5d_mc(dst + SZ_O + rank * 10240, &P.wo[blk], bar, 24 * (id & 31) + 8 * k + 4 * rank, col + 5);
                if (j < 5) bulk_load_hint(dst + SZ_O, part + j * 512, 8192, bar, pol);
                if ((op & P_PRE) && 3 * i + k < 10)
                  asm volatile("cp.async.bulk.prefetch.L2.global [%0], 4096;" ::"l"(part + (3 * i + k) * 256) : "memory");
              }
            }
          }
        }
      }
#pragma unroll 1
      while (sh) retire();
    } else if (threadIdx.x == 288) {
      for (int pc = 0;; pc++) {
        const uint32_t op = prog[pc];
        const int type = op & 3;
        if (type == OP_END) break;
        if (type == OP_Q ? !(op & F_PARK) : type == OP_O && !(op & P_ST)) continue;
        const int id = type == OP_A ? (op >> 2) & 511 : type == OP_Q ? N_TILE + ((op >> 13) & 127) : ID_PART + ((op >> 5) & 60) + ((op >> 19) & 3);
        const uint32_t v = type == OP_O ? 1 : P.info[id] & 7;
        mbar_wait_slow<PUBNS>(odone0 + 8 * pc, 0);
        flag_set(flag + 2 * id, v);
        if (type == OP_O && (op & P_WIDE)) flag_set(flag + 2 * id + 2, v);
      }
    } else if (wid == 10) {
      int i = threadIdx.x & 31;
      uint32_t e = i < 8 ? P.prog[role].ev[i] : 0;
      for (uint32_t n = 0; __any_sync(0xffffffffu, e); n++) {
        unsigned int* f = ptr_add(flag, 8 * (e & 1023));
        const bool ok = e && flag_peek(f) - 1 < ((e & E_FREE) ? 1 : 7);
        if (ok) {
          mbar_arrive(ev0 + 8 * i);
          if (e & (E_FREE | E_LAST)) flag_dec(f);
          i += 8;
          e = i < MAX_EV ? P.prog[role].ev[i] : 0;
        }
        asm volatile("{\n.reg .pred p;\nsetp.ge.u32 p, %0, 0x400000;\n@p trap;\n}\n" ::"r"(n));
        if (!__any_sync(0xffffffffu, ok)) __nanosleep(WATNS);
      }
    } else if (threadIdx.x == 352) {
      uint32_t items = 0;
      auto read = [&](int id) {
        if (!(P.info[id] & I_NEXT)) return;
        wait_progress(progress, items);
        flag_dec(flag + 2 * id);
      };
      for (int pc = 0;; pc++) {
        const uint32_t op = prog[pc];
        const int type = op & 3;
        if (type == OP_END) break;
        if (type == OP_O) {
          const int n = (op >> 13) & 63;
#pragma unroll 1
          for (int i = 0; i < n; i++) {
            items += (op & P_WIDE) && i == n - TAIL ? 3 * TAIL + 3 : 3;
            read(((op >> 2) & 511) + i);
          }
        } else if (type == OP_A) {
          if (op & F_PARK) { items++; read(N_TILE + ((op >> 13) & 127)); }
          items += 32;
        } else {
          items += 10;
        }
      }
    }
    __syncwarp();
    asm volatile("barrier.cluster.arrive.relaxed;\nbarrier.cluster.wait;" ::: "memory");
  }
}

typedef CUresult (*EncodeFn)(CUtensorMap*, CUtensorMapDataType, cuuint32_t, void*, const cuuint64_t*, const cuuint64_t*,
                             const cuuint32_t*, const cuuint32_t*, CUtensorMapInterleave, CUtensorMapSwizzle,
                             CUtensorMapL2promotion, CUtensorMapFloatOOBfill);

void encode(EncodeFn fn, CUtensorMap* m, const void* ptr, int rank, const cuuint64_t* dims, const cuuint64_t* strides,
            const cuuint32_t* box, CUtensorMapSwizzle swz) {
  const cuuint32_t es[5] = {1, 1, 1, 1, 1};
  CUresult r = fn(m, CU_TENSOR_MAP_DATA_TYPE_BFLOAT16, rank, const_cast<void*>(ptr), dims, strides, box, es,
                  CU_TENSOR_MAP_INTERLEAVE_NONE, swz, CU_TENSOR_MAP_L2_PROMOTION_L2_128B, CU_TENSOR_MAP_FLOAT_OOB_FILL_NONE);
  if (r != CUDA_SUCCESS) fprintf(stderr, "cuTensorMapEncodeTiled failed: %d\n", (int)r);
}

struct Op { int type, flags, id, n, quarter, park, item0, items; double t0, t1; };
struct Use { double ready, gate, need, freed; int readers, slot, prev; bool next; };
struct PlanStats { double end, slack, park_slack; int slots, parks; };

bool plan(const char* const* text, int n_pair, int phase, Params& P, PlanStats* stats = nullptr) {
  constexpr double T_Q = 7900, T_A = 24850, T_U = 26300, T_O = 1920, T_RUN = 800, T_WIDE = 3800, AHEAD = 3500, PUBLISH = 1500;
  const double margin = 256.0 * ((P.dbg >> 8) & 255);
  static Op op[N_CL][MAX_OPS];
  static Use use[ID_PART];
  int n_op[N_CL], covered[N_TEAM] = {}, finals[N_TEAM] = {};
  auto hex = [](char c) { return c <= '9' ? c - '0' : c - 'a' + 10; };
  for (int i = 0; i < n_pair; i++)
    for (const char* s = text[i]; *s; s++)
      if (*s == 'J') { if (covered[hex(s[1])]) return false; covered[hex(s[1])] = 10 * (s[2] - '0') + s[3] - '0'; }
  for (int c = 0; c < 2 * n_pair; c++) {
    int n = 0, items = 0;
    double t = 0;
    auto add = [&](int type, int flags, int id, int heads, int quarter, int its, double dt) {
      if (n < MAX_OPS) op[c][n] = {type, flags, id, heads, quarter, 0, items, its, t, t + dt};
      n++; items += its; t += dt;
    };
    for (const char* s = text[c >> 1]; *s; s++) {
      const int tm = hex(s[1]) & 15, nj = covered[tm];
      if (*s == 'N') { add(OP_Q, 0, 0, 0, 0, 10, T_Q); add(OP_A, 0, 0, 0, 0, 32, T_A); }
      if (*s == 'P') add(OP_Q, F_PARK, 0, 0, 0, 10, T_Q);
      if (*s == 'U') { if (n == 0 || n > MAX_OPS || op[c][n - 1].type != OP_A) return false; add(OP_A, F_PARK, 0, 0, 0, 33, T_U); }
      if (*s == 'J') { if (nj <= TAIL || nj > kH - 4) return false; add(OP_O, P_WIDE | P_ST, tm * kH, nj, 2 * (c & 1), 3 * (nj + TAIL), 2 * T_O * nj + T_WIDE); }
      if (*s == 'F') { if (s[2]) return false; add(OP_O, nj ? P_LD : 0, tm * kH + nj, kH - nj, finals[tm]++, 3 * (kH - nj), T_O * (kH - nj) + T_RUN); }
    }
    add(OP_END, 0, 0, 0, 0, 0, 0);
    if (n > MAX_OPS || op[c][0].type != OP_Q) return false;
    n_op[c] = n - 1;
  }
  for (int t = 0; t < N_TEAM; t++) if (finals[t] != 4) return false;
  for (int i = 0; i < ID_PART; i++) use[i] = {0, 0, 1e18, 0, 0, 0, 0, false};
  struct Ref { double t; Op* o; int id; };
  static Ref att[N_TILE + 1], dem[N_TILE], prk[MAX_PARK + 1], unp[MAX_PARK + 1], wr[ID_PART];
  int n_att = 0, n_prk = 0, n_unp = 0;
  auto ready = [&](const Op* o) {
    const int nt = o[1].type;
    return o->t1 + (nt == OP_Q ? 4600 : nt == OP_O ? ((o[1].flags & P_WIDE) ? 3900 : 3900 / FDRAIN) : 1500) + PUBLISH;
  };
  for (int c = 0; c < 2 * n_pair; c++)
    for (Op* o = op[c]; o->type != OP_END; o++) {
      if (o->type == OP_A) { att[n_att] = {ready(o), o, 0}; if (++n_att > N_TILE) return false; }
      if (o->type == OP_A && o->flags) { unp[n_unp] = {o->t0 - AHEAD, o, 0}; if (++n_unp > MAX_PARK) return false; }
      if (o->type == OP_Q && o->flags) { prk[n_prk] = {ready(o), o, 0}; if (++n_prk > MAX_PARK) return false; }
      for (int i = 0; o->type == OP_O && i < o->n; i++) {
        const int nw = (o->flags & P_WIDE) ? o->n - TAIL : 0;
        Use& u = use[o->id + i];
        const double t = o->t0 + T_O * (i + (i < nw ? i : nw));
        if (t - AHEAD < u.need) u.need = t - AHEAD;
        const double f = t + T_O * (i < nw ? 2 : nw ? 1 + TAIL : 1) + PUBLISH;
        if (f > u.freed) u.freed = f;
        u.readers++;
      }
    }
  if (n_att != N_TILE || n_prk != n_unp) return false;
  auto sort = [](Ref* r, int n) {
    for (int i = 1; i < n; i++)
      for (int j = i; j > 0 && r[j].t < r[j - 1].t; j--) { Ref x = r[j]; r[j] = r[j - 1]; r[j - 1] = x; }
  };
  for (int i = 0; i < N_TILE; i++) { const int id = (i & 15) * kH + (i >> 4); dem[i] = {use[id].need, nullptr, id}; }
  sort(att, n_att); sort(dem, N_TILE); sort(prk, n_prk); sort(unp, n_unp);
  PlanStats st = {0, 1e18, 1e18, 0, n_prk};
  int n_wr = 0;
  for (int i = 0; i < N_TILE; i++) {
    Op* o = att[i].o;
    o->id = dem[i].id;
    if (!o->flags) o[-1].id = o->id;
    if (dem[i].t - att[i].t < st.slack) st.slack = dem[i].t - att[i].t;
    wr[n_wr++] = {o->t1 - 2 * AHEAD, o, o->id};
  }
  for (int i = 0; i < n_prk; i++) {
    prk[i].o->id = unp[i].o->id;
    prk[i].o->park = unp[i].o->park = i;
    use[N_TILE + i].freed = unp[i].o->t0 + 2 * PUBLISH;
    use[N_TILE + i].readers = 1;
    if (unp[i].t - prk[i].t < st.park_slack) st.park_slack = unp[i].t - prk[i].t;
    wr[n_wr++] = {prk[i].o->t1 - 2 * AHEAD, prk[i].o, N_TILE + i};
  }
  for (int c = 0; c < 2 * n_pair; c++)
    for (int d = 0; d < 2 * n_pair; d++)
      for (Op *f = &op[c][n_op[c] - 1], *o = op[d]; f->type == OP_O && o->type != OP_END; o++)
        if (o->type == OP_O && (o->flags & P_ST) && o->id / kH == f->id / kH) {
          if (f->t0 - o->t1 > 4096.0 * ((P.dbg >> 16) & 255)) f->flags |= P_PRE;
          const double slack = f->t0 + ((f->flags & P_PRE) ? 0 : (f->n - 2) * T_O) - AHEAD - ready(o);
          if (slack < st.park_slack) st.park_slack = slack;
        }
  sort(wr, n_wr);
  int holder[N_TILE];
  for (int i = 0; i < n_wr; i++) {
    int best = -1;
    for (int sl = 0; sl < st.slots; sl++)
      if (use[holder[sl]].freed + margin <= wr[i].t && (best < 0 || (use[holder[sl]].freed < use[holder[best]].freed) != ((P.dbg & 32) != 0))) best = sl;
    Use& u = use[wr[i].id];
    if (best >= 0) { u.prev = holder[best]; use[u.prev].next = true; wr[i].o->flags |= P_GATE; }
    else if (st.slots == N_TILE) return false;
    else best = st.slots++;
    u.slot = best;
    holder[best] = wr[i].id;
  }
  {
    int pos[N_CL] = {}, flag[ID_PART + 4 * N_TEAM] = {}, seen[ID_PART] = {};
    for (bool moved = true; moved;) {
      moved = false;
      for (int c = 0; c < 2 * n_pair; c++) {
        const int total = op[c][n_op[c]].item0;
        for (; pos[c] < total + NBAR; pos[c]++, moved = true) {
          bool ok = true;
          for (const Op* o = op[c]; o->type != OP_END; o++) {
            const int k = pos[c] - o->item0, own = o->type == OP_A ? o->id : N_TILE + o->park;
            if (k < 0 || k >= o->items) continue;
            if (o->type == OP_O) ok = (k >= 3 * o->n || flag[o->id + k / 3]) && (k != ((o->flags & P_PRE) ? 0 : 3 * o->n - 6) || !(o->flags & P_LD) || flag[ID_PART + o->id / kH * 4 + o->quarter]);
            else if (k == o->items - 1 && (o->flags & P_GATE)) ok = seen[use[own].prev] == use[use[own].prev].readers;
            else if (k == 0 && o->type == OP_A && (o->flags & F_PARK)) ok = flag[N_TILE + o->park];
          }
          if (!ok) break;
          for (const Op* o = op[c]; o->type != OP_END; o++) {
            if (pos[c] == o->item0 + o->items + 5) {
              if (o->type == OP_A) flag[o->id] = 1;
              if (o->type == OP_Q && (o->flags & F_PARK)) flag[N_TILE + o->park] = 1;
              if (o->type == OP_O && (o->flags & P_ST)) flag[ID_PART + o->id / kH * 4 + o->quarter] = flag[ID_PART + o->id / kH * 4 + o->quarter + 1] = 1;
            }
            const int k = pos[c] - NBAR - o->item0, nw = (o->flags & P_WIDE) ? o->n - TAIL : o->n;
            if (k == 0 && o->type == OP_A && (o->flags & F_PARK)) seen[N_TILE + o->park]++;
            if (o->type == OP_O && k >= 0 && k % 3 == 2 && (k / 3 < nw || (k / 3 >= o->n && k / 3 < 2 * o->n - nw))) seen[o->id + (k / 3 < nw ? k / 3 : k / 3 - TAIL)]++;
          }
        }
      }
    }
    for (int c = 0; c < 2 * n_pair; c++) if (pos[c] < op[c][n_op[c]].item0 + NBAR) return false;
  }
  for (int c = 0; c < 2 * n_pair; c++) {
    uint32_t items = 0, cur = 0, pend = 0;
    int n = 0, ev = 0;
    auto item = [&](uint32_t bytes, int count) {
      for (int i = 0; i < count; i++) { if (cur + bytes > RING) cur = 0; cur += bytes; items++; }
    };
    auto event = [&](uint32_t e) { if (ev < MAX_EV) P.prog[c].ev[ev] = e | E_ON; ev++; };
    for (const Op* o = op[c];; o++) {
      if (o->type != OP_END && phase && (o->type == OP_O) != (phase == 2)) continue;
      uint32_t cw = o->type | (items % NBAR) << 15 | ((items / NBAR) & 1) << 19 | (cur >> 12) << 20 | pend, pw = o->type | o->id << 2 | o->flags;
      const int ps = use[N_TILE + o->park].slot;
      pend = 0;
      if (o->type == OP_O) {
        const bool wide = o->flags & P_WIDE;
        cw |= o->n << 2 | (o->id / kH * 4 + o->quarter + wide) << 8 | (wide ? C_WIDE : 0) | ((o->flags & P_LD) ? C_LD : 0);
        pw |= o->n << 13 | o->quarter << 19;
        if (wide) item(SZ_W, 3 * (o->n - TAIL));
        for (int k = 0; k < (wide ? 6 * TAIL : 3 * o->n); k++) item((o->flags & P_LD) && k >= 3 * o->n - 5 ? SZ_OL : SZ_O, 1);
        if (wide) pend = C_PEND | ((P.dbg & 8) ? C_SOON : 0);
        for (int i = 0; i < o->n; i++) {
          if (i == ((o->flags & P_PRE) ? 0 : o->n - 2) && (o->flags & P_LD)) event((ID_PART + o->id / kH * 4 + o->quarter) | E_LAST);
          event((o->id + i) | (use[o->id + i].next ? 0 : E_LAST));
        }
      } else if (o->type != OP_END) {
        const bool parks = o->type == OP_Q && (o->flags & F_PARK);
        cw |= (parks ? ps : use[o->id].slot) << 2 | (o->flags & F_PARK);
        if (o->flags & F_PARK) pw |= o->park << 13 | ps << 20;
        if (o->type == OP_Q) item(SZ_Q, 10);
        else { if (o->flags & F_PARK) { item(SZ_PARK, 1); event((N_TILE + o->park) | (use[N_TILE + o->park].next ? 0 : E_LAST)); } item(SZ_KV, 32); }
        if (parks || o->type == OP_A) pend = C_PEND | ((P.dbg & 16) ? 0 : C_SOON);
        if (o->flags & P_GATE) event(use[parks ? N_TILE + o->park : o->id].prev | E_FREE);
      }
      P.prog[c].c[n] = cw; P.prog[c].p[n++] = pw;
      if (o->type == OP_END) { if (o->t0 > st.end) st.end = o->t0; break; }
    }
    if (ev > MAX_EV) return false;
    while (ev < MAX_EV) P.prog[c].ev[ev++] = 0;
    while (n < MAX_OPS) { P.prog[c].c[n] = OP_END; P.prog[c].p[n++] = OP_END; }
    P.first[c] = (uint16_t)(P.prog[c].p[0] & 2047);
  }
  for (int i = 0; i < ID_PART; i++) {
    if (i < N_TILE) P.slot[i] = use[i].slot;
    P.info[i] = (use[i].readers + use[i].next) | (use[i].next ? I_NEXT : 0);
  }
  if (stats) *stats = st;
  return true;
}

const char* const kPrograms[N_CL / 2] = {
  "NNJ025NJ818NFc", "NNJ121NJ921NFa", "NNJ219NJa24NFc", "NNJ318NJb25NFa", "NNJ417NJc24NF1", "NNJ518NJd22NF2",
  "NNJ618NJe22NF2", "NNJ725NJf25Fd", "NUNNNNNNNF4", "NUNNNNNNNF4", "NUNNNNNNNF5", "NUNNNNNNNF5",
  "NUNNNNNNNF6", "NUNNNNNNNF6", "NUNNNNNNNF3", "NUNNNNNNNF3", "NUNNNNNNNF8", "NUNNNNNNNF8",
  "PNNNNNNNNNF0", "PNNNNNNNNNF7", "PNNNNNNNNNF7", "PNNNNNNNNNF0", "PNNNNNNNNNFb", "PNNNNNNNNNFb",
  "PNNNNNNNNNFf", "PNNNNNNNNNFf", "NNNNNNNNNF1", "NNNNNNNNNFd", "NNNNNNNNNFe", "NNNNNNNNNFe",
  "NNNNNNNNNF9", "NNNNNNNNNF9", "PPNNNNNNNNN",
};

const char* const* bench_programs() {
  return kPrograms;
}

}

extern "C" void kernel_launch(void* const* d_in, const int* in_sizes, int n_in, void* d_out, int out_size) {
  (void)in_sizes; (void)n_in; (void)out_size;
  static EncodeFn fn = nullptr;
  static int n_clusters = 0;
  if (!fn) {
    cudaDriverEntryPointQueryResult qr;
    void* f = nullptr;
    cudaGetDriverEntryPoint("cuTensorMapEncodeTiled", &f, cudaEnableDefault, &qr);
    fn = (EncodeFn)f;
    cudaFuncSetAttribute(fused_kernel, cudaFuncAttributeMaxDynamicSharedMemorySize, SMEM_BYTES);
    cudaLaunchConfig_t cfg = {};
    cfg.gridDim = dim3(132); cfg.blockDim = dim3(384); cfg.dynamicSmemBytes = SMEM_BYTES;
    cudaLaunchAttribute at[1];
    at[0].id = cudaLaunchAttributeClusterDimension; at[0].val.clusterDim.x = 2; at[0].val.clusterDim.y = 1; at[0].val.clusterDim.z = 1;
    cfg.attrs = at; cfg.numAttrs = 1;
    if (cudaOccupancyMaxActiveClusters(&n_clusters, fused_kernel, &cfg) != cudaSuccess || n_clusters < 1) n_clusters = 1;
    (void)cudaGetLastError();
  }
  static Params P;
  const CUtensorMapSwizzle S128 = CU_TENSOR_MAP_SWIZZLE_128B, S64 = CU_TENSOR_MAP_SWIZZLE_64B;
  for (int blk = 0; blk < 2; blk++) {
    void* const* in = d_in + 5 * blk;
    { const cuuint64_t d[] = {kD, kB * kSq}, s[] = {kD * 2}; const cuuint32_t b[] = {64, 128};
      encode(fn, &P.x[blk], in[0], 2, d, s, b, S128); }
    { const cuuint64_t d[] = {64, 8, 3, (cuuint64_t)kB * kH * kSk / 8}, s[] = {kDh * 2, 128, 8 * kDh * 2}; const cuuint32_t b[] = {64, 8, 3, 8};
      encode(fn, &P.k[blk], in[1], 4, d, s, b, S128);
      encode(fn, &P.v[blk], in[2], 4, d, s, b, S128); }
    { const cuuint64_t d[] = {64, kD, kHD / 64}, s[] = {kHD * 2, 128}; const cuuint32_t b[] = {64, 64, 3};
      encode(fn, &P.wq[blk], in[3], 3, d, s, b, S128); }
    { const cuuint64_t d[] = {32, 2, kHD / 8, 4, kD / 32}, s[] = {kD * 2, 8 * kD * 2, 2 * kD * 2, 64}; const cuuint32_t b[] = {32, 2, 4, 4, 5};
      encode(fn, &P.wo[blk], in[4], 5, d, s, b, S64); }
  }
  { const cuuint64_t d[] = {32, kB * kSq, 2 * kD / 32}, s[] = {2 * kD * 2, 64}; const cuuint32_t b[] = {32, 16, 5};
    encode(fn, &P.out, d_out, 3, d, s, b, S64); }

  P.dbg = DBG_DEFAULT;
  if (n_clusters >= N_CL && plan(bench_programs(), N_CL / 2, 0, P)) {
    fused_kernel<<<2 * N_CL, 384, SMEM_BYTES>>>(P);
  } else {
    char buf[2 * N_TEAM][16];
    const char* text[2 * N_TEAM];
    for (int i = 0; i < 2 * N_TEAM; i++) { snprintf(buf[i], sizeof(buf[i]), "NNNNNNNNF%x", i / 2); text[i] = buf[i]; }
    for (int phase = 1; phase <= 2; phase++) {
      plan(text, 2 * N_TEAM, phase, P);
      fused_kernel<<<8 * N_TEAM, 384, SMEM_BYTES>>>(P);
    }
  }
}
```

```cpp
#include <cuda_runtime.h>
#include <cuda_bf16.h>
#include <cuda.h>
#include <stdint.h>
#include <stdio.h>

namespace {

constexpr int kB = 8, kSq = 256, kD = 640, kH = 32, kSk = 1024, kDh = 192;
constexpr int kHD = kH * kDh;
constexpr uint32_t RING = 224 * 1024;
constexpr uint32_t SZ_KV = 24576;
constexpr uint32_t SZ_Q = 16384 + 24576;
constexpr uint32_t SZ_O = 16384 + 20480;
constexpr uint32_t SZ_W = 16384 + 40960;
constexpr uint32_t SZ_PARK = 49152;
constexpr uint32_t SZ_OL = SZ_O + 8192;
constexpr int NBAR = 10;
constexpr int EARLY = 3;
#define XTAIL 2
constexpr int TAIL = XTAIL;
constexpr uint32_t KV_CH = 64, KV_SBO = 3072;
constexpr int SMEM_BYTES = RING + 1024 + 1024;
constexpr int N_TEAM = 16, N_CL = 66, MAX_OPS = 24, MAX_EV = 80, N_TILE = N_TEAM * kH, MAX_PARK = 128, ID_PART = N_TILE + MAX_PARK;
enum : uint32_t { OP_END = 0, OP_Q = 1, OP_A = 2, OP_O = 3, F_PARK = 1 << 11,
                  C_WIDE = 1 << 14, C_PEND = 1 << 26, C_SOON = 1 << 28, C_LD = 1 << 29,
                  P_GATE = 1 << 12, P_WIDE = 1 << 11, P_LD = 1 << 12, P_ST = 1 << 21, P_PRE = 1 << 22, I_NEXT = 8, E_ON = 1 << 15, E_FREE = 1 << 14, E_LAST = 1 << 13 };

#define QDRAIN 0x54732710u
#define FDRAIN 1
#define PUBNS 100
#define WATNS 100
constexpr uint32_t DBG_DEFAULT = 0x101833;

struct alignas(64) Params {
  uint16_t first[96];
  CUtensorMap x[2], wq[2], k[2], v[2], wo[2], out;
  struct {
    uint32_t c[MAX_OPS];
    uint32_t p[MAX_OPS];
    uint16_t ev[MAX_EV];
  } prog[N_CL];
  uint16_t slot[N_TILE];
  uint8_t info[ID_PART];
  uint32_t dbg;
};

__device__ uint4 g_t[N_TILE * 2 * 3072];
__device__ uint4 g_part[N_TEAM * 4 * 2 * 3072];
__device__ unsigned int g_flag[(ID_PART + N_TEAM * 4) * 2];

template <int TB, int TA = 0>
__device__ __forceinline__ void wgmma_ss_n64(float (&d)[32], uint64_t da, uint64_t db, int scale_d) {
  asm volatile("{\n.reg .pred p;\nsetp.ne.b32 p, %34, 0;\n"
    "wgmma.mma_async.sync.aligned.m64n64k16.f32.bf16.bf16 {%0, %1, %2, %3, %4, %5, %6, %7, %8, %9, %10, %11, %12, %13, %14, %15, %16, %17, %18, %19, %20, %21, %22, %23, %24, %25, %26, %27, %28, %29, %30, %31}, %32, %33, p, 1, 1, %35, %36;\n}\n"
    : "+f"(d[0]), "+f"(d[1]), "+f"(d[2]), "+f"(d[3]), "+f"(d[4]), "+f"(d[5]), "+f"(d[6]), "+f"(d[7]), "+f"(d[8]), "+f"(d[9]), "+f"(d[10]), "+f"(d[11]), "+f"(d[12]), "+f"(d[13]), "+f"(d[14]), "+f"(d[15]), "+f"(d[16]), "+f"(d[17]), "+f"(d[18]), "+f"(d[19]), "+f"(d[20]), "+f"(d[21]), "+f"(d[22]), "+f"(d[23]), "+f"(d[24]), "+f"(d[25]), "+f"(d[26]), "+f"(d[27]), "+f"(d[28]), "+f"(d[29]), "+f"(d[30]), "+f"(d[31])
    : "l"(da), "l"(db), "r"(scale_d), "n"(TA), "n"(TB));
}
template <int TB>
__device__ __forceinline__ void wgmma_rs_n64(float (&d)[32], uint32_t a0, uint32_t a1, uint32_t a2, uint32_t a3, uint64_t db, int scale_d) {
  asm volatile("{\n.reg .pred p;\nsetp.ne.b32 p, %37, 0;\n"
    "wgmma.mma_async.sync.aligned.m64n64k16.f32.bf16.bf16 {%0, %1, %2, %3, %4, %5, %6, %7, %8, %9, %10, %11, %12, %13, %14, %15, %16, %17, %18, %19, %20, %21, %22, %23, %24, %25, %26, %27, %28, %29, %30, %31}, {%32, %33, %34, %35}, %36, p, 1, 1, %38;\n}\n"
    : "+f"(d[0]), "+f"(d[1]), "+f"(d[2]), "+f"(d[3]), "+f"(d[4]), "+f"(d[5]), "+f"(d[6]), "+f"(d[7]), "+f"(d[8]), "+f"(d[9]), "+f"(d[10]), "+f"(d[11]), "+f"(d[12]), "+f"(d[13]), "+f"(d[14]), "+f"(d[15]), "+f"(d[16]), "+f"(d[17]), "+f"(d[18]), "+f"(d[19]), "+f"(d[20]), "+f"(d[21]), "+f"(d[22]), "+f"(d[23]), "+f"(d[24]), "+f"(d[25]), "+f"(d[26]), "+f"(d[27]), "+f"(d[28]), "+f"(d[29]), "+f"(d[30]), "+f"(d[31])
    : "r"(a0), "r"(a1), "r"(a2), "r"(a3), "l"(db), "r"(scale_d), "n"(TB));
}
template <int TB, int TA = 0>
__device__ __forceinline__ void wgmma_ss_n160(float (&d)[80], uint64_t da, uint64_t db, int scale_d) {
  asm volatile("{\n.reg .pred p;\nsetp.ne.b32 p, %82, 0;\n"
    "wgmma.mma_async.sync.aligned.m64n160k16.f32.bf16.bf16 {%0, %1, %2, %3, %4, %5, %6, %7, %8, %9, %10, %11, %12, %13, %14, %15, %16, %17, %18, %19, %20, %21, %22, %23, %24, %25, %26, %27, %28, %29, %30, %31, %32, %33, %34, %35, %36, %37, %38, %39, %40, %41, %42, %43, %44, %45, %46, %47, %48, %49, %50, %51, %52, %53, %54, %55, %56, %57, %58, %59, %60, %61, %62, %63, %64, %65, %66, %67, %68, %69, %70, %71, %72, %73, %74, %75, %76, %77, %78, %79}, %80, %81, p, 1, 1, %83, %84;\n}\n"
    : "+f"(d[0]), "+f"(d[1]), "+f"(d[2]), "+f"(d[3]), "+f"(d[4]), "+f"(d[5]), "+f"(d[6]), "+f"(d[7]), "+f"(d[8]), "+f"(d[9]), "+f"(d[10]), "+f"(d[11]), "+f"(d[12]), "+f"(d[13]), "+f"(d[14]), "+f"(d[15]), "+f"(d[16]), "+f"(d[17]), "+f"(d[18]), "+f"(d[19]), "+f"(d[20]), "+f"(d[21]), "+f"(d[22]), "+f"(d[23]), "+f"(d[24]), "+f"(d[25]), "+f"(d[26]), "+f"(d[27]), "+f"(d[28]), "+f"(d[29]), "+f"(d[30]), "+f"(d[31]), "+f"(d[32]), "+f"(d[33]), "+f"(d[34]), "+f"(d[35]), "+f"(d[36]), "+f"(d[37]), "+f"(d[38]), "+f"(d[39]), "+f"(d[40]), "+f"(d[41]), "+f"(d[42]), "+f"(d[43]), "+f"(d[44]), "+f"(d[45]), "+f"(d[46]), "+f"(d[47]), "+f"(d[48]), "+f"(d[49]), "+f"(d[50]), "+f"(d[51]), "+f"(d[52]), "+f"(d[53]), "+f"(d[54]), "+f"(d[55]), "+f"(d[56]), "+f"(d[57]), "+f"(d[58]), "+f"(d[59]), "+f"(d[60]), "+f"(d[61]), "+f"(d[62]), "+f"(d[63]), "+f"(d[64]), "+f"(d[65]), "+f"(d[66]), "+f"(d[67]), "+f"(d[68]), "+f"(d[69]), "+f"(d[70]), "+f"(d[71]), "+f"(d[72]), "+f"(d[73]), "+f"(d[74]), "+f"(d[75]), "+f"(d[76]), "+f"(d[77]), "+f"(d[78]), "+f"(d[79])
    : "l"(da), "l"(db), "r"(scale_d), "n"(TA), "n"(TB));
}
template <int TB>
__device__ __forceinline__ void wgmma_rs_n160(float (&d)[80], uint32_t a0, uint32_t a1, uint32_t a2, uint32_t a3, uint64_t db, int scale_d) {
  asm volatile("{\n.reg .pred p;\nsetp.ne.b32 p, %85, 0;\n"
    "wgmma.mma_async.sync.aligned.m64n160k16.f32.bf16.bf16 {%0, %1, %2, %3, %4, %5, %6, %7, %8, %9, %10, %11, %12, %13, %14, %15, %16, %17, %18, %19, %20, %21, %22, %23, %24, %25, %26, %27, %28, %29, %30, %31, %32, %33, %34, %35, %36, %37, %38, %39, %40, %41, %42, %43, %44, %45, %46, %47, %48, %49, %50, %51, %52, %53, %54, %55, %56, %57, %58, %59, %60, %61, %62, %63, %64, %65, %66, %67, %68, %69, %70, %71, %72, %73, %74, %75, %76, %77, %78, %79}, {%80, %81, %82, %83}, %84, p, 1, 1, %86;\n}\n"
    : "+f"(d[0]), "+f"(d[1]), "+f"(d[2]), "+f"(d[3]), "+f"(d[4]), "+f"(d[5]), "+f"(d[6]), "+f"(d[7]), "+f"(d[8]), "+f"(d[9]), "+f"(d[10]), "+f"(d[11]), "+f"(d[12]), "+f"(d[13]), "+f"(d[14]), "+f"(d[15]), "+f"(d[16]), "+f"(d[17]), "+f"(d[18]), "+f"(d[19]), "+f"(d[20]), "+f"(d[21]), "+f"(d[22]), "+f"(d[23]), "+f"(d[24]), "+f"(d[25]), "+f"(d[26]), "+f"(d[27]), "+f"(d[28]), "+f"(d[29]), "+f"(d[30]), "+f"(d[31]), "+f"(d[32]), "+f"(d[33]), "+f"(d[34]), "+f"(d[35]), "+f"(d[36]), "+f"(d[37]), "+f"(d[38]), "+f"(d[39]), "+f"(d[40]), "+f"(d[41]), "+f"(d[42]), "+f"(d[43]), "+f"(d[44]), "+f"(d[45]), "+f"(d[46]), "+f"(d[47]), "+f"(d[48]), "+f"(d[49]), "+f"(d[50]), "+f"(d[51]), "+f"(d[52]), "+f"(d[53]), "+f"(d[54]), "+f"(d[55]), "+f"(d[56]), "+f"(d[57]), "+f"(d[58]), "+f"(d[59]), "+f"(d[60]), "+f"(d[61]), "+f"(d[62]), "+f"(d[63]), "+f"(d[64]), "+f"(d[65]), "+f"(d[66]), "+f"(d[67]), "+f"(d[68]), "+f"(d[69]), "+f"(d[70]), "+f"(d[71]), "+f"(d[72]), "+f"(d[73]), "+f"(d[74]), "+f"(d[75]), "+f"(d[76]), "+f"(d[77]), "+f"(d[78]), "+f"(d[79])
    : "r"(a0), "r"(a1), "r"(a2), "r"(a3), "l"(db), "r"(scale_d), "n"(TB));
}
template <int TB, int TA = 0>
__device__ __forceinline__ void wgmma_ss_n192(float (&d)[96], uint64_t da, uint64_t db, int scale_d) {
  asm volatile("{\n.reg .pred p;\nsetp.ne.b32 p, %98, 0;\n"
    "wgmma.mma_async.sync.aligned.m64n192k16.f32.bf16.bf16 {%0, %1, %2, %3, %4, %5, %6, %7, %8, %9, %10, %11, %12, %13, %14, %15, %16, %17, %18, %19, %20, %21, %22, %23, %24, %25, %26, %27, %28, %29, %30, %31, %32, %33, %34, %35, %36, %37, %38, %39, %40, %41, %42, %43, %44, %45, %46, %47, %48, %49, %50, %51, %52, %53, %54, %55, %56, %57, %58, %59, %60, %61, %62, %63, %64, %65, %66, %67, %68, %69, %70, %71, %72, %73, %74, %75, %76, %77, %78, %79, %80, %81, %82, %83, %84, %85, %86, %87, %88, %89, %90, %91, %92, %93, %94, %95}, %96, %97, p, 1, 1, %99, %100;\n}\n"
    : "+f"(d[0]), "+f"(d[1]), "+f"(d[2]), "+f"(d[3]), "+f"(d[4]), "+f"(d[5]), "+f"(d[6]), "+f"(d[7]), "+f"(d[8]), "+f"(d[9]), "+f"(d[10]), "+f"(d[11]), "+f"(d[12]), "+f"(d[13]), "+f"(d[14]), "+f"(d[15]), "+f"(d[16]), "+f"(d[17]), "+f"(d[18]), "+f"(d[19]), "+f"(d[20]), "+f"(d[21]), "+f"(d[22]), "+f"(d[23]), "+f"(d[24]), "+f"(d[25]), "+f"(d[26]), "+f"(d[27]), "+f"(d[28]), "+f"(d[29]), "+f"(d[30]), "+f"(d[31]), "+f"(d[32]), "+f"(d[33]), "+f"(d[34]), "+f"(d[35]), "+f"(d[36]), "+f"(d[37]), "+f"(d[38]), "+f"(d[39]), "+f"(d[40]), "+f"(d[41]), "+f"(d[42]), "+f"(d[43]), "+f"(d[44]), "+f"(d[45]), "+f"(d[46]), "+f"(d[47]), "+f"(d[48]), "+f"(d[49]), "+f"(d[50]), "+f"(d[51]), "+f"(d[52]), "+f"(d[53]), "+f"(d[54]), "+f"(d[55]), "+f"(d[56]), "+f"(d[57]), "+f"(d[58]), "+f"(d[59]), "+f"(d[60]), "+f"(d[61]), "+f"(d[62]), "+f"(d[63]), "+f"(d[64]), "+f"(d[65]), "+f"(d[66]), "+f"(d[67]), "+f"(d[68]), "+f"(d[69]), "+f"(d[70]), "+f"(d[71]), "+f"(d[72]), "+f"(d[73]), "+f"(d[74]), "+f"(d[75]), "+f"(d[76]), "+f"(d[77]), "+f"(d[78]), "+f"(d[79]), "+f"(d[80]), "+f"(d[81]), "+f"(d[82]), "+f"(d[83]), "+f"(d[84]), "+f"(d[85]), "+f"(d[86]), "+f"(d[87]), "+f"(d[88]), "+f"(d[89]), "+f"(d[90]), "+f"(d[91]), "+f"(d[92]), "+f"(d[93]), "+f"(d[94]), "+f"(d[95])
    : "l"(da), "l"(db), "r"(scale_d), "n"(TA), "n"(TB));
}
template <int TB>
__device__ __forceinline__ void wgmma_rs_n192(float (&d)[96], uint32_t a0, uint32_t a1, uint32_t a2, uint32_t a3, uint64_t db, int scale_d) {
  asm volatile("{\n.reg .pred p;\nsetp.ne.b32 p, %101, 0;\n"
    "wgmma.mma_async.sync.aligned.m64n192k16.f32.bf16.bf16 {%0, %1, %2, %3, %4, %5, %6, %7, %8, %9, %10, %11, %12, %13, %14, %15, %16, %17, %18, %19, %20, %21, %22, %23, %24, %25, %26, %27, %28, %29, %30, %31, %32, %33, %34, %35, %36, %37, %38, %39, %40, %41, %42, %43, %44, %45, %46, %47, %48, %49, %50, %51, %52, %53, %54, %55, %56, %57, %58, %59, %60, %61, %62, %63, %64, %65, %66, %67, %68, %69, %70, %71, %72, %73, %74, %75, %76, %77, %78, %79, %80, %81, %82, %83, %84, %85, %86, %87, %88, %89, %90, %91, %92, %93, %94, %95}, {%96, %97, %98, %99}, %100, p, 1, 1, %102;\n}\n"
    : "+f"(d[0]), "+f"(d[1]), "+f"(d[2]), "+f"(d[3]), "+f"(d[4]), "+f"(d[5]), "+f"(d[6]), "+f"(d[7]), "+f"(d[8]), "+f"(d[9]), "+f"(d[10]), "+f"(d[11]), "+f"(d[12]), "+f"(d[13]), "+f"(d[14]), "+f"(d[15]), "+f"(d[16]), "+f"(d[17]), "+f"(d[18]), "+f"(d[19]), "+f"(d[20]), "+f"(d[21]), "+f"(d[22]), "+f"(d[23]), "+f"(d[24]), "+f"(d[25]), "+f"(d[26]), "+f"(d[27]), "+f"(d[28]), "+f"(d[29]), "+f"(d[30]), "+f"(d[31]), "+f"(d[32]), "+f"(d[33]), "+f"(d[34]), "+f"(d[35]), "+f"(d[36]), "+f"(d[37]), "+f"(d[38]), "+f"(d[39]), "+f"(d[40]), "+f"(d[41]), "+f"(d[42]), "+f"(d[43]), "+f"(d[44]), "+f"(d[45]), "+f"(d[46]), "+f"(d[47]), "+f"(d[48]), "+f"(d[49]), "+f"(d[50]), "+f"(d[51]), "+f"(d[52]), "+f"(d[53]), "+f"(d[54]), "+f"(d[55]), "+f"(d[56]), "+f"(d[57]), "+f"(d[58]), "+f"(d[59]), "+f"(d[60]), "+f"(d[61]), "+f"(d[62]), "+f"(d[63]), "+f"(d[64]), "+f"(d[65]), "+f"(d[66]), "+f"(d[67]), "+f"(d[68]), "+f"(d[69]), "+f"(d[70]), "+f"(d[71]), "+f"(d[72]), "+f"(d[73]), "+f"(d[74]), "+f"(d[75]), "+f"(d[76]), "+f"(d[77]), "+f"(d[78]), "+f"(d[79]), "+f"(d[80]), "+f"(d[81]), "+f"(d[82]), "+f"(d[83]), "+f"(d[84]), "+f"(d[85]), "+f"(d[86]), "+f"(d[87]), "+f"(d[88]), "+f"(d[89]), "+f"(d[90]), "+f"(d[91]), "+f"(d[92]), "+f"(d[93]), "+f"(d[94]), "+f"(d[95])
    : "r"(a0), "r"(a1), "r"(a2), "r"(a3), "l"(db), "r"(scale_d), "n"(TB));
}

__device__ __forceinline__ uint32_t smem_u32(const void* p) { return (uint32_t)__cvta_generic_to_shared(p); }
__device__ __forceinline__ void wg_fence() { asm volatile("wgmma.fence.sync.aligned;" ::: "memory"); }
__device__ __forceinline__ void wg_commit() { asm volatile("wgmma.commit_group.sync.aligned;" ::: "memory"); }
template <int N> __device__ __forceinline__ void wg_wait() { asm volatile("wgmma.wait_group.sync.aligned %0;" ::"n"(N) : "memory"); }
__device__ __forceinline__ void sched_fence(uint32_t& keep, bool never) {
  asm volatile("{\n.reg .pred p;\nsetp.ne.b32 p, %1, 0;\n@p mov.u32 %0, %%clock;\n}\n" : "+r"(keep) : "r"((int)never) : "memory");
}
template <int N> __device__ __forceinline__ void fence_regs(float (&r)[N]) {
#pragma unroll
  for (int i = 0; i < N; i++) asm volatile("" : "+f"(r[i])::"memory");
}
template <int N> __device__ __forceinline__ void undefine(float (&r)[N]) {
#pragma unroll
  for (int i = 0; i < N; i++) asm volatile("" : "=f"(r[i]));
}
template <int N> __device__ __forceinline__ void fence_regs(uint32_t (&r)[N]) {
#pragma unroll
  for (int i = 0; i < N; i++) asm volatile("" : "+r"(r[i])::"memory");
}
__device__ __forceinline__ uint64_t mk_desc(uint32_t a16, uint32_t lbo, uint32_t sbo, uint32_t swz) {
  uint64_t d;
  asm("mov.b64 %0, {%1, %2};" : "=l"(d) : "r"(a16 + ((lbo >> 4) << 16)), "r"((sbo >> 4) | (swz << 30)));
  return d;
}
__device__ __forceinline__ void mbar_init(uint32_t bar, uint32_t cnt) {
  asm volatile("mbarrier.init.shared::cta.b64 [%0], %1;" ::"r"(bar), "r"(cnt) : "memory");
}
__device__ __forceinline__ void mbar_expect(uint32_t bar, uint32_t tx) {
  asm volatile("mbarrier.arrive.expect_tx.shared::cta.b64 _, [%0], %1;" ::"r"(bar), "r"(tx) : "memory");
}
__device__ __forceinline__ bool mbar_test(uint32_t bar, uint32_t ph) {
  uint32_t ok;
  asm volatile("{\n.reg .pred p;\nmbarrier.test_wait.parity.shared::cta.b64 p, [%1], %2;\nselp.u32 %0, 1, 0, p;\n}\n"
               : "=r"(ok) : "r"(bar), "r"(ph) : "memory");
  return ok;
}
__device__ __forceinline__ void mbar_wait(uint32_t bar, uint32_t ph) {
  asm volatile("{\n.reg .pred p;\n.reg .u32 n;\nmov.u32 n, 0;\n"
               "LOOP:\nmbarrier.try_wait.parity.shared::cta.b64 p, [%0], %1;\n@p bra DONE;\n"
               "add.u32 n, n, 1;\nsetp.lt.u32 p, n, 0x1000000;\n@p bra LOOP;\ntrap;\n"
               "DONE:\n}\n" ::"r"(bar), "r"(ph) : "memory");
}
template <int NS> __device__ __forceinline__ void mbar_wait_slow(uint32_t bar, uint32_t ph) {
  asm volatile("{\n.reg .pred p;\n.reg .u32 n;\nmov.u32 n, 0;\n"
               "LOOP:\nmbarrier.test_wait.parity.shared::cta.b64 p, [%0], %1;\n@p bra DONE;\n"
               "nanosleep.u32 %2;\nadd.u32 n, n, 1;\nsetp.lt.u32 p, n, 0x400000;\n@p bra LOOP;\ntrap;\n"
               "DONE:\n}\n" ::"r"(bar), "r"(ph), "n"(NS) : "memory");
}
__device__ __forceinline__ void mbar_arrive_cluster_if(bool on, uint32_t addr) {
  asm volatile("{\n.reg .pred p;\nsetp.ne.b32 p, %1, 0;\n@p mbarrier.arrive.shared::cluster.b64 _, [%0];\n}\n" ::"r"(addr), "r"((int)on) : "memory");
}
__device__ __forceinline__ void tma2d(uint32_t dst, const CUtensorMap* m, uint32_t bar, int c0, int c1) {
  asm volatile("cp.async.bulk.tensor.2d.shared::cluster.global.mbarrier::complete_tx::bytes [%0], [%1, {%3, %4}], [%2];"
               ::"r"(dst), "l"(m), "r"(bar), "r"(c0), "r"(c1) : "memory");
}
__device__ __forceinline__ void tma3d(uint32_t dst, const CUtensorMap* m, uint32_t bar, int c0, int c1, int c2) {
  asm volatile("cp.async.bulk.tensor.3d.shared::cluster.global.mbarrier::complete_tx::bytes [%0], [%1, {%3, %4, %5}], [%2];"
               ::"r"(dst), "l"(m), "r"(bar), "r"(c0), "r"(c1), "r"(c2) : "memory");
}
__device__ __forceinline__ void tma3d_mc(uint32_t dst, const CUtensorMap* m, uint32_t bar, int c0, int c1, int c2) {
  asm volatile("cp.async.bulk.tensor.3d.shared::cluster.global.mbarrier::complete_tx::bytes.multicast::cluster"
               " [%0], [%1, {%3, %4, %5}], [%2], %6;"
               ::"r"(dst), "l"(m), "r"(bar), "r"(c0), "r"(c1), "r"(c2), "h"((uint16_t)3) : "memory");
}
__device__ __forceinline__ void tma3d_store(const CUtensorMap* m, uint32_t src, int c0, int c1, int c2) {
  asm volatile("cp.async.bulk.tensor.3d.global.shared::cta.bulk_group [%0, {%2, %3, %4}], [%1];"
               ::"l"(m), "r"(src), "r"(c0), "r"(c1), "r"(c2) : "memory");
}
__device__ __forceinline__ void bar_sync(int id, int n) { asm volatile("bar.sync %0, %1;" ::"r"(id), "r"(n) : "memory"); }
__device__ __forceinline__ uint32_t pack_bf16(float lo, float hi) {
  uint32_t r;
  asm("cvt.rn.bf16x2.f32 %0, %1, %2;" : "=r"(r) : "f"(hi), "f"(lo));
  return r;
}
__device__ __forceinline__ float ex2(float x) {
  float y;
  asm("ex2.approx.ftz.f32 %0, %1;" : "=f"(y) : "f"(x));
  return y;
}
__device__ __forceinline__ float rcp(float x) {
  float y;
  asm("rcp.approx.ftz.f32 %0, %1;" : "=f"(y) : "f"(x));
  return y;
}
__device__ __forceinline__ void stsm4(uint32_t addr, uint32_t a, uint32_t b, uint32_t c, uint32_t d) {
  asm volatile("stmatrix.sync.aligned.m8n8.x4.shared.b16 [%0], {%1, %2, %3, %4};" ::"r"(addr), "r"(a), "r"(b), "r"(c), "r"(d) : "memory");
}

__device__ __forceinline__ void tma4d_mc_hint(uint32_t dst, const CUtensorMap* m, uint32_t bar, int c3, uint64_t pol) {
  asm volatile("cp.async.bulk.tensor.4d.shared::cluster.global.mbarrier::complete_tx::bytes.multicast::cluster.L2::cache_hint"
               " [%0], [%1, {%3, %3, %3, %4}], [%2], %5, %6;"
               ::"r"(dst), "l"(m), "r"(bar), "r"(0), "r"(c3), "h"((uint16_t)3), "l"(pol) : "memory");
}
__device__ __forceinline__ void tma5d_mc(uint32_t dst, const CUtensorMap* m, uint32_t bar, int c2, int c4) {
  asm volatile("cp.async.bulk.tensor.5d.shared::cluster.global.mbarrier::complete_tx::bytes.multicast::cluster"
               " [%0], [%1, {%3, %3, %4, %3, %5}], [%2], %6;"
               ::"r"(dst), "l"(m), "r"(bar), "r"(0), "r"(c2), "r"(c4), "h"((uint16_t)3) : "memory");
}
__device__ __forceinline__ void bulk_load_hint(uint32_t dst, const void* src, uint32_t bytes, uint32_t bar, uint64_t pol) {
  asm volatile("cp.async.bulk.shared::cluster.global.mbarrier::complete_tx::bytes.L2::cache_hint [%0], [%1], %2, [%3], %4;"
               ::"r"(dst), "l"(src), "r"(bytes), "r"(bar), "l"(pol) : "memory");
}
__device__ __forceinline__ void stg128_hint(void* p, uint32_t a, uint32_t b, uint32_t c, uint32_t d, uint64_t pol) {
  asm volatile("st.global.L2::cache_hint.v4.b32 [%0], {%1, %2, %3, %4}, %5;" ::"l"(p), "r"(a), "r"(b), "r"(c), "r"(d), "l"(pol) : "memory");
}
__device__ __forceinline__ void stg2_if(bool on, void* p, uint32_t a, uint32_t b, uint32_t c, uint32_t d, uint32_t e, uint32_t f,
                                        uint32_t g, uint32_t h, uint64_t pol) {
  asm volatile("{\n.reg .pred p;\nsetp.ne.b32 p, %10, 0;\n"
               "@p st.global.L2::cache_hint.v4.b32 [%0], {%1, %2, %3, %4}, %9;\n"
               "@p st.global.L2::cache_hint.v4.b32 [%0 + 512], {%5, %6, %7, %8}, %9;\n}\n"
               ::"l"(p), "r"(a), "r"(b), "r"(c), "r"(d), "r"(e), "r"(f), "r"(g), "r"(h), "l"(pol), "r"((int)on) : "memory");
}
__device__ __forceinline__ uint64_t make_policy(bool first) {
  uint64_t pf, pn;
  asm("createpolicy.fractional.L2::evict_first.b64 %0, 1.0;" : "=l"(pf));
  asm("createpolicy.fractional.L2::evict_normal.b64 %0, 1.0;" : "=l"(pn));
  return first ? pf : pn;
}
__device__ __forceinline__ bool elect() {
  uint32_t ok;
  asm volatile("{\n.reg .pred p;\nelect.sync _|p, 0xffffffff;\nselp.u32 %0, 1, 0, p;\n}\n" : "=r"(ok));
  return ok;
}
__device__ __forceinline__ void mbar_arrive(uint32_t bar) {
  asm volatile("mbarrier.arrive.shared::cta.b64 _, [%0];" ::"r"(bar) : "memory");
}
__device__ __forceinline__ void mbar_arrive_if(bool on, uint32_t bar) {
  asm volatile("{\n.reg .pred p;\nsetp.ne.b32 p, %1, 0;\n@p mbarrier.arrive.shared::cta.b64 _, [%0];\n}\n" ::"r"(bar), "r"((int)on) : "memory");
}
__device__ __forceinline__ void stg128(void* p, uint32_t a, uint32_t b, uint32_t c, uint32_t d) {
  asm volatile("st.global.v4.b32 [%0], {%1, %2, %3, %4};" ::"l"(p), "r"(a), "r"(b), "r"(c), "r"(d) : "memory");
}
__device__ __forceinline__ void lds128(uint32_t p, uint32_t& a, uint32_t& b, uint32_t& c, uint32_t& d) {
  asm volatile("ld.shared.v4.b32 {%0, %1, %2, %3}, [%4];" : "=r"(a), "=r"(b), "=r"(c), "=r"(d) : "r"(p) : "memory");
}
template <class T> __device__ __forceinline__ T* ptr_add(T* base, uint32_t bytes) {
  T* r;
  asm("{\n.reg .u32 lo, hi;\nmov.b64 {lo, hi}, %1;\nadd.cc.u32 lo, lo, %2;\naddc.u32 hi, hi, 0;\nmov.b64 %0, {lo, hi};\n}\n" : "=l"(r) : "l"(base), "r"(bytes));
  return r;
}
__device__ __forceinline__ uint32_t flag_peek(const unsigned int* p) {
  uint32_t v;
  asm volatile("ld.relaxed.gpu.global.u32 %0, [%1];" : "=r"(v) : "l"(p) : "memory");
  return v;
}
__device__ __forceinline__ uint32_t flag_get(const unsigned int* p) {
  uint32_t v;
  asm volatile("ld.acquire.gpu.global.u32 %0, [%1];" : "=r"(v) : "l"(p) : "memory");
  return v;
}
__device__ __forceinline__ void wait_progress(uint32_t p, uint32_t target) {
  asm volatile("{\n.reg .pred p;\n.reg .u32 n, v;\nmov.u32 n, 0;\n"
               "LOOP:\nld.acquire.cta.shared.u32 v, [%0];\nsetp.ge.u32 p, v, %1;\n@p bra DONE;\n"
               "nanosleep.u32 %2;\nadd.u32 n, n, 1;\nsetp.lt.u32 p, n, 0x400000;\n@p bra LOOP;\ntrap;\n"
               "DONE:\n}\n" ::"r"(p), "r"(target), "n"(400) : "memory");
}
__device__ __forceinline__ void flag_set(unsigned int* p, uint32_t v) {
  asm volatile("st.release.gpu.global.u32 [%0], %1;" ::"l"(p), "r"(v) : "memory");
}
__device__ __forceinline__ void flag_dec(unsigned int* p) {
  asm volatile("red.relaxed.gpu.global.add.u32 [%0], 0xffffffff;" ::"l"(p) : "memory");
}

struct Cursor {
  int bi;
  uint32_t ph;
  __device__ __forceinline__ void next() {
    if (++bi == NBAR) { bi = 0; ph ^= 1; }
  }
};

constexpr float kScaleLog2 = 0.07216878364870322f * 1.4426950408889634f;
constexpr float kSumLimit = 1048576.0f;

__global__ void __cluster_dims__(2, 1, 1) __launch_bounds__(384, 1)
fused_kernel(const __grid_constant__ Params P) {
  extern __shared__ uint8_t smem_raw[];
  const uint32_t sbase = (smem_u32(smem_raw) + 1023) & ~1023u;
  const uint32_t full0 = sbase + RING, empty0 = full0 + 8 * NBAR, odone0 = empty0 + 8 * NBAR, ev0 = odone0 + 8 * MAX_OPS;
  const uint32_t progress = ev0 + 8 * MAX_EV;
  const uint32_t rank = blockIdx.x & 1;
  const int role = blockIdx.x >> 1;
  const int wid = __shfl_sync(0xffffffffu, (int)(threadIdx.x >> 5), 0);
  const int wg = wid >> 2;

  const uint32_t op0 = P.first[role];
  if (__builtin_expect(wid == 8, 1)) {
    if (elect()) {
#pragma unroll
      for (int k = 0; k < EARLY; k++) mbar_init(full0 + 8 * k, 1);
      asm volatile("fence.mbarrier_init.release.cluster;" ::: "memory");
      const int blk = (op0 >> 10) & 1;
      if ((op0 & 3) == OP_Q) {
#pragma unroll
        for (int k = 0; k < EARLY; k++) {
          mbar_expect(full0 + 8 * k, SZ_Q);
          tma2d(sbase + k * SZ_Q, &P.x[blk], full0 + 8 * k, 64 * k, ((op0 >> 7) & 7) * kSq + rank * 128);
          tma3d(sbase + k * SZ_Q + 16384, &P.wq[blk], full0 + 8 * k, 0, 64 * k, 3 * ((op0 >> 2) & 31));
        }
      }
      asm volatile("prefetch.tensormap [%0];" ::"l"(rank ? &P.v[blk] : &P.k[blk]) : "memory");
    }
  } else if (wg < 2 && elect()) {
#pragma unroll
    for (int j = 0; j < 16; j++) {
      const int i = EARLY + 16 * wid + j;
      if (i < 2 * NBAR + MAX_OPS + MAX_EV) mbar_init(full0 + 8 * i, i < NBAR ? 1 : i < 2 * NBAR ? 16 : i < 2 * NBAR + MAX_OPS ? 8 : 1);
    }
    if (wid == 7) asm volatile("st.shared.u32 [%0], 0;\nfence.acq_rel.cta;" ::"r"(progress) : "memory");
    asm volatile("fence.mbarrier_init.release.cluster;" ::: "memory");
  }
  __syncwarp();
  asm volatile("barrier.cluster.arrive.relaxed.aligned;\nbarrier.cluster.wait.aligned;" ::: "memory");

  if (wg < 2) {
    asm volatile("setmaxnreg.inc.sync.aligned.u32 240;");
    const uint32_t* prog = P.prog[role].c;
    const int lane = threadIdx.x & 31, warp = wid & 3;
    uint32_t empty_rem;
    asm volatile("mapa.shared::cluster.u32 %0, %1, %2;" : "=r"(empty_rem) : "r"(empty0), "r"(lane & 1));
    auto release = [&](int slot) { mbar_arrive_cluster_if(lane < 2, empty_rem + 8 * slot); };
    Cursor r{0, 0};
    const uint32_t ring16 = (sbase & 0x3FFFF) >> 4;
    uint32_t cur = ring16;
    bool rdy0 = false, rdy1 = false;
    auto probe1 = [&]() { rdy0 = mbar_test(full0 + 8 * r.bi, r.ph); };
    auto probe2 = [&]() {
      Cursor n = r;
      rdy0 = mbar_test(full0 + 8 * n.bi, n.ph);
      n.next();
      rdy1 = mbar_test(full0 + 8 * n.bi, n.ph);
    };
    auto take = [&](bool rdy, uint32_t bytes, uint32_t& addr) {
      const int bi = r.bi;
      if (__builtin_expect(!__all_sync(0xffffffffu, rdy), 0)) mbar_wait(full0 + 8 * r.bi, r.ph);
      r.next();
      if (cur > ring16 + ((RING - bytes) >> 4)) cur = ring16;
      addr = cur;
      cur += bytes >> 4;
      return bi;
    };
    uint32_t keep = 0;
    const bool never = P.dbg == 0xffffffffu;
    uint32_t q[48];
#pragma unroll
    for (int i = 0; i < 48; i++) q[i] = 0;
    const int row = wg * 64 + warp * 16 + (lane >> 2);
    const int img0 = row * 4 + ((lane & 3) ^ ((row >> 1) & 3));
    uint4* pend = nullptr;
    bool pend_any = false;
    uint64_t spol;
    int pc = 0;
    auto slab = [&](int c, int i0) {
#pragma unroll
      for (int i = i0; i < 6; i++)
        stg2_if(c == i, pend + i * 512, q[8 * i], q[8 * i + 1], q[8 * i + 2], q[8 * i + 3],
                q[8 * i + 4], q[8 * i + 5], q[8 * i + 6], q[8 * i + 7], spol);
    };
    auto drain = [&](int c) {
      if (!pend_any || c >= 6) return;
      slab(c, 0);
      if (c == 5) {
        __syncwarp();
        mbar_arrive_if(lane == 0, odone0 - 8 + 8 * pc);
      }
    };

    for (;; pc++) {
      uint32_t op = prog[pc];
      const int type = op & 3;
      auto enter = [&]() {
        r.bi = (op >> 15) & 15; r.ph = (op >> 19) & 1; cur = ring16 + (((op >> 20) & 63) << 8);
      };
      enter();
      pend_any = op & C_PEND;
      spol = make_policy(!(op & C_SOON));
      if (type == OP_END) {
#pragma unroll 1
        for (int c = 0; c < 6; c++) drain(c);
        asm volatile("barrier.cluster.arrive.relaxed;" ::: "memory");
        break;
      }
      {
        float s[32], o[96];
        uint32_t ad0;
        int bi0, sk1;
        uint32_t pa[16], pb[16];
        float mc0, mc1, l0, l1;
        bool shifted;
        uint32_t nop;
        auto expo = [&](float (&s)[32], uint32_t (&pout)[16], float& b0, float& b1, bool shift, auto mid) {
          float c0, c1;
#pragma unroll
          for (int i = 0; i < 8; i++) {
            const float e0 = ex2(shift ? s[4 * i] - mc0 : s[4 * i]), e1 = ex2(shift ? s[4 * i + 1] - mc0 : s[4 * i + 1]);
            const float e2 = ex2(shift ? s[4 * i + 2] - mc1 : s[4 * i + 2]), e3 = ex2(shift ? s[4 * i + 3] - mc1 : s[4 * i + 3]);
            if (i) { b0 += e0; c0 += e1; b1 += e2; c1 += e3; } else { b0 = e0; c0 = e1; b1 = e2; c1 = e3; }
            pout[2 * i] = pack_bf16(e0, e1); pout[2 * i + 1] = pack_bf16(e2, e3);
            if (i & 1) mid(i >> 1);
          }
          b0 += c0; b1 += c1;
        };
        auto rowmax = [&](float (&s)[32], float& m0, float& m1) {
          m0 = fmaxf(s[0], s[1]); m1 = fmaxf(s[2], s[3]);
#pragma unroll
          for (int i = 1; i < 8; i++) { m0 = fmaxf(m0, fmaxf(s[4 * i], s[4 * i + 1])); m1 = fmaxf(m1, fmaxf(s[4 * i + 2], s[4 * i + 3])); }
          m0 = fmaxf(m0, __shfl_xor_sync(0xffffffffu, m0, 1)); m1 = fmaxf(m1, __shfl_xor_sync(0xffffffffu, m1, 1));
          m0 = fmaxf(m0, __shfl_xor_sync(0xffffffffu, m0, 2)); m1 = fmaxf(m1, __shfl_xor_sync(0xffffffffu, m1, 2));
        };
        auto first = [&](float (&s)[32], int sk0, auto mid) {
          fence_regs(s);
          release(sk0);
          mc0 = 0.f; mc1 = 0.f;
          expo(s, pa, l0, l1, false, mid);
          shifted = __any_sync(0xffffffffu, !(fmaxf(l0, l1) <= kSumLimit && fminf(l0, l1) >= 1.f / kSumLimit));
          if (shifted) {
            rowmax(s, mc0, mc1);
            expo(s, pa, l0, l1, true, [](int) {});
          }
        };
        auto qk = [&](float (&s)[32], uint32_t ak, int k0 = 0, int k1 = 12) {
#pragma unroll
          for (int kk = k0; kk < k1; kk++)
            wgmma_rs_n64<0>(s, q[4 * kk], q[4 * kk + 1], q[4 * kk + 2], q[4 * kk + 3], mk_desc(ak + (kk >> 2) * KV_CH + (kk & 3) * 2, 16, KV_SBO, 1), kk != 0);
          if (k1 == 12) wg_commit();
        };
        auto pv = [&](uint32_t (&pin)[16], uint32_t av, int acc) {
#pragma unroll
          for (int kk = 0; kk < 4; kk++)
            wgmma_rs_n192<1>(o, pin[4 * kk], pin[4 * kk + 1], pin[4 * kk + 2], pin[4 * kk + 3], mk_desc(av + kk * (KV_SBO / 8), KV_CH * 16, KV_SBO, 1), acc || (kk != 0));
          wg_commit();
        };
        auto finish = [&](uint32_t (&pout)[16], int sk, int sv) {
          probe2();
          wg_wait<1>();
          fence_regs(s);
          release(sk);
          float b0, b1;
#pragma unroll 1
          for (bool redo = false;; redo = true) {
            expo(s, pout, b0, b1, false, [](int) {});
            if (!__any_sync(0xffffffffu, !redo && (shifted || !(fmaxf(b0, b1) <= kSumLimit)))) break;
            shifted = true;
            rowmax(s, b0, b1);
            b0 = fmaxf(mc0, b0); b1 = fmaxf(mc1, b1);
            const float a0 = ex2(mc0 - b0), a1 = ex2(mc1 - b1);
            mc0 = b0; mc1 = b1;
            l0 *= a0; l1 *= a1;
            wg_wait<0>();
            fence_regs(o);
#pragma unroll
            for (int i = 0; i < 24; i++) { o[4 * i] *= a0; o[4 * i + 1] *= a0; o[4 * i + 2] *= a1; o[4 * i + 3] *= a1; }
#pragma unroll
            for (int i = 0; i < 32; i++) s[i] -= (i & 2) ? mc1 : mc0;
          }
          l0 += b0; l1 += b1;
          wg_wait<0>();
          fence_regs(o);
          release(sv);
        };
        auto step = [&](uint32_t (&pin)[16], uint32_t (&pout)[16]) {
          uint32_t ak, av;
          const int sk = take(rdy0, SZ_KV, ak), sv = take(rdy1, SZ_KV, av);
          wg_fence();
          qk(s, ak);
          pv(pin, av, 1);
          finish(pout, sk, sv);
        };
        auto unpark = [&]() {
          uint32_t ad, ak;
          const int bi = take(rdy0, SZ_PARK, ad);
#pragma unroll
          for (int i = 0; i < 12; i++) lds128(sbase + (ad - ring16 + img0) * 16 + (i >> 1) * 8192 + (i & 1) * 512, q[4 * i], q[4 * i + 1], q[4 * i + 2], q[4 * i + 3]);
          const int sk0 = take(false, SZ_KV, ak);
          fence_regs(q);
          release(bi);
          wg_fence();
          qk(s, ak);
          probe2();
          return sk0;
        };
        auto mma4 = [&](uint32_t ad, int acc) {
#pragma unroll
          for (int kk = 0; kk < 4; kk++)
            wgmma_ss_n192<1>(o, mk_desc(ad + wg * 512 + kk * 2, 16, 1024, 1), mk_desc(ad + 1024 + kk * 128, 8192, 1024, 1), acc || kk != 0);
        };
        auto convert = [&](int i0, int i1) {
          sched_fence(keep, never);
#pragma unroll
          for (int i = i0; i < i1; i++) q[i] = pack_bf16(o[2 * i] * kScaleLog2, o[2 * i + 1] * kScaleLog2);
          sched_fence(keep, never);
        };
        auto kend = [&](int bi, int k) {
          wg_commit();
          drain(k < 8 ? (QDRAIN >> (4 * k)) & 7 : 7);
          probe1();
          wg_wait<0>();
          release(bi);
        };
        if (type == OP_O) {
          float c[80];
          const int nk = 3 * ((op >> 2) & 63), ro = (op >> 8) & 63;
          uint4* part = ptr_add(g_part, (ro * 2 + rank) * SZ_PARK + img0 * 16);
          int prev = 0;
          auto hand_over = [&](float (&c)[80], uint4* dst) {
            fence_regs(c);
#pragma unroll
            for (int i = 0; i < 48; i++) q[i] = i < 8 ? 0 : pack_bf16(c[2 * i - 16], c[2 * i - 15]);
            pend = dst;
          };
          auto mma2 = [&](float (&c)[80], uint32_t da, uint32_t db, int acc) {
            wgmma_ss_n160<1>(c, mk_desc(da, 16, 512, 2), mk_desc(db, 2048, 512, 2), acc);
            wgmma_ss_n160<1>(c, mk_desc(da + 2, 16, 512, 2), mk_desc(db + 64, 2048, 512, 2), 1);
          };
          auto kstep = [&](float (&c)[80], int acc, auto hook, uint32_t bytes = SZ_O) {
            uint32_t ad;
            const int bi = take(rdy0, bytes, ad);
            const uint32_t da = ad + wg * 256, db = ad + 1024;
            wg_fence();
            mma2(c, da, db, acc);
            wg_commit();
            if (acc) { wg_wait<1>(); release(prev); }
            mma2(c, da + 512, db + 640, 1);
            wg_commit();
            prev = bi;
            hook();
            probe1();
            wg_wait<1>();
          };
          if (op & C_WIDE) {
            float d[80];
            auto wstep = [&](int acc, auto hook) {
              uint32_t ad;
              const int bi = take(rdy0, SZ_W, ad);
              const uint32_t da = ad + wg * 256, db = ad + 1024;
              wg_fence();
              mma2(d, da, db, acc);
              mma2(d, da + 512, db + 640, 1);
              wg_commit();
              if (acc) { wg_wait<1>(); release(prev); }
              mma2(c, da, db + 1280, acc);
              mma2(c, da + 512, db + 1920, 1);
              wg_commit();
              prev = bi;
              hook();
              probe1();
              wg_wait<1>();
            };
            wstep(0, [&]() { drain(0); drain(1); });
#pragma unroll 1
            for (int k = 2; k < 6; k += 2) wstep(1, [&]() { drain(k); drain(k + 1); });
#pragma unroll 1
            for (int k = 3 + 3 * TAIL; k < nk; k++) {
              wstep(1, []() {});
            }
#pragma unroll 1
            for (int k = 0; k < 3 * TAIL; k++) kstep(d, 1, []() {});
            nop = prog[pc + 1];
            spol = make_policy(!(nop & C_SOON));
            kstep(c, 1, [&]() { hand_over(d, part - 6144); });
#pragma unroll 1
            for (int k = 1; k < 3 * TAIL; k++) kstep(c, 1, [&]() { slab(TAIL == 2 ? k : (0x50403201 >> (4 * k - 4)) & 7, 1); });
            if ((nop & 3) == OP_Q) {
              op = nop;
              enter();
              pc++;
              pend_any = true;
              bi0 = take(rdy0, SZ_Q, ad0);
              undefine(o);
              wg_fence();
              mma4(ad0, 0);
              wg_commit();
              wg_wait<1>();
              release(prev);
              hand_over(c, part);
              probe1();
              wg_wait<0>();
              release(bi0);
              fence_regs(o);
              goto next_head;
            }
            wg_wait<0>();
            fence_regs(c);
            release(prev);
          } else {
            kstep(c, 0, [&]() { drain(0); });
#pragma unroll 1
            for (int k = 1; k < 6; k++) kstep(c, 1, [&]() { drain(k); });
#pragma unroll 1
            for (int k = (op & C_LD) ? 11 : 6; k < nk; k++) kstep(c, 1, []() {});
            if (op & C_LD) {
              uint32_t t[40];
              float u[80];
              auto unpack = [&](int j) {
#pragma unroll
                for (int i = 8 * j; i < 8 * j + 8; i++) {
                  u[2 * i] = __uint_as_float(t[i] << 16); u[2 * i + 1] = __uint_as_float(t[i] & 0xffff0000u);
                  asm volatile("" : "+f"(u[2 * i]), "+f"(u[2 * i + 1]));
                }
              };
#pragma unroll
              for (int j = 0; j < 5; j++)
                kstep(c, 1, [&]() {
#pragma unroll
                  for (int i = 0; i < 2; i++)
                    lds128(sbase + (cur - ring16 + img0) * 16 - 8192 + i * 512, t[8 * j + 4 * i], t[8 * j + 4 * i + 1], t[8 * j + 4 * i + 2], t[8 * j + 4 * i + 3]);
                  if (j) unpack(j - 1);
                }, SZ_OL);
              unpack(4);
              sched_fence(keep, never);
              wg_wait<0>();
              fence_regs(c);
              release(prev);
#pragma unroll
              for (int i = 0; i < 80; i++) c[i] += u[i];
            } else {
              wg_wait<0>();
              fence_regs(c);
              release(prev);
            }
          }
          if (op & C_WIDE) {
            hand_over(c, part);
            continue;
          }
          {
            asm volatile("barrier.cluster.arrive.relaxed;" ::: "memory");
            bar_sync(1, 256);
            const uint32_t wstage = sbase + (wg * 4 + warp) * 5120;
            const uint32_t sa = wstage + (lane & 15) * 64;
#pragma unroll
            for (int i = 0; i < 10; i++) {
              const int u = (i & 1) * 2 + (lane >> 4);
              stsm4(sa + (i >> 1) * 1024 + ((u ^ ((lane >> 1) & 3)) << 4), pack_bf16(c[8 * i], c[8 * i + 1]), pack_bf16(c[8 * i + 2], c[8 * i + 3]),
                    pack_bf16(c[8 * i + 4], c[8 * i + 5]), pack_bf16(c[8 * i + 6], c[8 * i + 7]));
            }
            asm volatile("fence.proxy.async.shared::cta;" ::: "memory");
            __syncwarp();
            if (lane == 0) {
              tma3d_store(&P.out, wstage, 0, ((ro >> 2) & 7) * kSq + rank * 128 + wg * 64 + warp * 16, (ro >> 5) * 20 + (ro & 3) * 5);
              asm volatile("cp.async.bulk.commit_group;\ncp.async.bulk.wait_group.read 0;" ::: "memory");
            }
            __syncwarp();
            break;
          }
        }
        bi0 = take(rdy0, SZ_Q, ad0);
        undefine(o);
        wg_fence();
        mma4(ad0, 0);
        kend(bi0, 0);
        fence_regs(o);
      next_head:
        {
#pragma unroll 1
          for (int k = 1; k < ((op & F_PARK) ? 10 : 8); k++) {
            uint32_t ad;
            const int bi = take(rdy0, SZ_Q, ad);
            wg_fence();
            mma4(ad, 1);
            kend(bi, k);
          }
          if (op & F_PARK) {
            fence_regs(o);
            convert(0, 48);
            pend = ptr_add(g_t, (((op >> 2) & 511) * 2 + rank) * SZ_PARK + img0 * 16);
            continue;
          }
          uint32_t a8, a9, ak0, ak1;
          const int b8 = take(rdy0, SZ_Q, a8), b9 = take(false, SZ_Q, a9);
          wg_fence();
          mma4(a8, 1);
          wg_commit();
          mma4(a9, 1);
          wg_commit();
          pc++;
          wg_wait<1>();
          release(b8);
          const int sk0 = take(false, SZ_KV, ak0);
          wg_wait<0>();
          fence_regs(o);
          release(b9);
          float s0[32];
          convert(0, 32);
          wg_fence();
          qk(s0, ak0, 0, 4);
          convert(32, 48);
          wg_fence();
          qk(s0, ak0, 4, 12);
          sk1 = take(false, SZ_KV, ak1);
          probe1();
          wg_wait<0>();
          first(s0, sk0, [&](int i) {
            if (i == 0) return;
            sched_fence(keep, never);
            wg_fence();
            if (i == 1) qk(s, ak1, 0, 4);
            if (i == 2) qk(s, ak1, 4, 8);
            if (i == 3) qk(s, ak1, 8, 12);
            sched_fence(keep, never);
          });
        }
        for (;;) {
          {
            uint32_t av;
            const int sv = take(rdy0, SZ_KV, av);
            undefine(o);
            wg_fence();
            pv(pa, av, 0);
            finish(pb, sk1, sv);
          }
          nop = prog[pc + 1];
#pragma unroll 1
          for (int jj = 0; jj < 7; jj++) {
            step(pb, pa);
            step(pa, pb);
          }
          float i0, i1;
          auto last = [&]() {
            uint32_t av;
            const int sv = take(rdy0, SZ_KV, av);
            wg_fence();
            pv(pb, av, 1);
            sched_fence(keep, never);
            probe1();
            l0 += __shfl_xor_sync(0xffffffffu, l0, 1); l1 += __shfl_xor_sync(0xffffffffu, l1, 1);
            l0 += __shfl_xor_sync(0xffffffffu, l0, 2); l1 += __shfl_xor_sync(0xffffffffu, l1, 2);
            i0 = rcp(l0); i1 = rcp(l1);
            pend = ptr_add(g_t, (((op >> 2) & 511) * 2 + rank) * SZ_PARK + img0 * 16);
            return sv;
          };
          auto normalise = [&](uint32_t (&d)[48], auto mid) {
#pragma unroll
            for (int i = 0; i < 24; i++) {
              d[8 * (i >> 2) + (i & 3)] = pack_bf16(o[4 * i] * i0, o[4 * i + 1] * i0);
              d[8 * (i >> 2) + (i & 3) + 4] = pack_bf16(o[4 * i + 2] * i1, o[4 * i + 3] * i1);
              if ((i & 3) == 3 && i != 23) { sched_fence(keep, never); mid(i >> 2); }
            }
          };
          const int sv = last();
          if ((nop & 3) != OP_A) {
            op = nop;
            enter();
            pend_any = true;
            spol = make_policy(!(op & C_SOON));
            bi0 = take(rdy0 || (nop & 3) != OP_Q, SZ_Q, ad0);
            sched_fence(keep, never);
            wg_wait<0>();
            fence_regs(o);
            release(sv);
            normalise(q, [](int) {});
            undefine(o);
            if ((nop & 3) != OP_Q) break;
            sched_fence(keep, never);
            wg_fence();
            mma4(ad0, 0);
            pc++;
            kend(bi0, 0);
            fence_regs(o);
            goto next_head;
          }
          const int sk0 = unpark();
          wg_wait<1>();
          fence_regs(o);
          release(sv);
          uint32_t t[48];
          spol = make_policy(!(nop & C_SOON));
          auto st = [&](int i) {
            stg2_if(true, pend + i * 512, t[8 * i], t[8 * i + 1], t[8 * i + 2], t[8 * i + 3], t[8 * i + 4], t[8 * i + 5], t[8 * i + 6], t[8 * i + 7], spol);
          };
          normalise(t, [&](int i) { if (!(i & 1)) st(i >> 1); });
          wg_wait<0>();
          first(s, sk0, [&](int i) { if (i < 3) { sched_fence(keep, never); st(3 + i); } });
          __syncwarp();
          mbar_arrive_if(lane == 0, odone0 + 8 * pc);
          pc++;
          op = nop;
          uint32_t ak1;
          sk1 = take(rdy0, SZ_KV, ak1);
          rdy0 = rdy1;
          wg_fence();
          qk(s, ak1);
        }
      }
    }
    if (never) g_flag[0] = keep;
    asm volatile("barrier.cluster.wait;" ::: "memory");
  } else {
    asm volatile("setmaxnreg.dec.sync.aligned.u32 24;");
    const uint32_t* prog = P.prog[role].p;
    unsigned int* flag = g_flag + rank;
    if (wid == 8) {
      Cursor tail{0, 0};
      int head = 0, sh = 0;
      uint32_t cur = 0, used = 0;
      uint64_t fifo = 0;
      uint32_t dst, bar, ev = ev0, done = 0;
      uint64_t pol;
      asm volatile("createpolicy.fractional.L2::evict_first.b64 %0, 1.0;" : "=l"(pol));
      auto retire = [&]() {
        mbar_wait(empty0 + 8 * tail.bi, tail.ph);
        tail.next();
        used -= (uint32_t)fifo & 31;
        fifo >>= 5;
        sh -= 5;
        asm volatile("st.volatile.shared.u32 [%0], %1;" ::"r"(progress), "r"(++done) : "memory");
      };
      auto acquire = [&](uint32_t bytes) {
        uint32_t fp = bytes >> 12;
        if (cur + fp > (RING >> 12)) { fp += (RING >> 12) - cur; cur = 0; }
        used += fp;
        while (used > (RING >> 12) || sh == 5 * NBAR) retire();
        fifo |= (uint64_t)fp << sh;
        sh += 5;
        dst = sbase + (cur << 12);
        bar = full0 + 8 * head;
        cur += bytes >> 12;
        if (++head == NBAR) head = 0;
      };
      auto gate = [&]() {
        mbar_wait(ev, 0);
        ev += 8;
        asm volatile("fence.proxy.async.global;" ::: "memory");
      };
      for (int pc = 0;; pc++) {
        const uint32_t op = prog[pc];
        const int type = op & 3, blk = (op >> 10) & 1;
        if (type == OP_END) break;
        if (type == OP_Q) {
#pragma unroll 1
          for (int k = 0; k < 10; k++) {
            if (k == 9 && (op & P_GATE)) gate();
            acquire(SZ_Q);
            if ((pc > 0 || k >= EARLY) && elect()) {
              mbar_expect(bar, SZ_Q);
              tma2d(dst, &P.x[blk], bar, 64 * k, ((op >> 7) & 7) * kSq + rank * 128);
              if ((k & 1) == rank) tma3d_mc(dst + 16384, &P.wq[blk], bar, 0, 64 * k, 3 * ((op >> 2) & 31));
            }
          }
        } else if (type == OP_A) {
          const int row0 = ((op >> 2) & 255) * kSk;
          const CUtensorMap* kv_map = rank ? &P.v[blk] : &P.k[blk];
          if (op & F_PARK) {
            gate();
            acquire(SZ_PARK);
            if (elect()) {
              mbar_expect(bar, SZ_PARK);
              bulk_load_hint(dst, &g_t[((op >> 20) * 2 + rank) * 3072], SZ_PARK, bar, make_policy(P.dbg & 4));
            }
          }
#pragma unroll 1
          for (int t = 0; t < 32; t++) {
            const int isv = t == 31 ? 1 : (t == 0 ? 0 : (~t & 1));
            const int j = isv ? (t - 1) >> 1 : (t + 1) >> 1;
            if (t == 31 && (op & P_GATE)) gate();
            acquire(SZ_KV);
            if (elect()) {
              mbar_expect(bar, SZ_KV);
              if (isv == (int)rank) tma4d_mc_hint(dst, kv_map, bar, row0 / 8 + 8 * j, pol);
            }
          }
        } else {
          const int n = (op >> 13) & 63, nw = (op & P_WIDE) ? n - TAIL : 0;
          const uint64_t pol_o = make_policy(P.dbg & (nw ? 1 : 2));
          const uint4* part = &g_part[((((op >> 5) & 60) + ((op >> 19) & 3)) * 2 + rank) * 3072 + 512];
#pragma unroll 1
          for (int i = 0; i < n + (nw ? TAIL : 0); i++) {
            const int id = ((op >> 2) & 511) + (i < n ? i : i - TAIL), col = 5 * (((op >> 19) & 3) + (i >= n));
            const uint4* src = &g_t[(P.slot[id] * 2 + rank) * 3072];
            if ((op & P_LD) && i == ((op & P_PRE) ? 0 : n - 2)) gate();
            if (i < n) gate();
#pragma unroll 1
            for (int k = 0; k < 3; k++) {
              const uint32_t j = (op & P_LD) ? 3 * (i - n) + k + 5 : 5, bytes = i < nw ? SZ_W : j < 5 ? SZ_OL : SZ_O;
              acquire(bytes);
              if (elect()) {
                mbar_expect(bar, bytes);
                tma5d_mc(dst + 16384 + rank * 10240, &P.wo[blk], bar, 24 * (id & 31) + 8 * k + 4 * rank, col);
                bulk_load_hint(dst, src + k * 1024, 16384, bar, pol_o);
                if (i < nw) tma5d_mc(dst + SZ_O + rank * 10240, &P.wo[blk], bar, 24 * (id & 31) + 8 * k + 4 * rank, col + 5);
                if (j < 5) bulk_load_hint(dst + SZ_O, part + j * 512, 8192, bar, pol);
                if ((op & P_PRE) && 3 * i + k < 10)
                  asm volatile("cp.async.bulk.prefetch.L2.global [%0], 4096;" ::"l"(part + (3 * i + k) * 256) : "memory");
              }
            }
          }
        }
      }
#pragma unroll 1
      while (sh) retire();
    } else if (threadIdx.x == 288) {
      for (int pc = 0;; pc++) {
        const uint32_t op = prog[pc];
        const int type = op & 3;
        if (type == OP_END) break;
        if (type == OP_Q ? !(op & F_PARK) : type == OP_O && !(op & P_ST)) continue;
        const int id = type == OP_A ? (op >> 2) & 511 : type == OP_Q ? N_TILE + ((op >> 13) & 127) : ID_PART + ((op >> 5) & 60) + ((op >> 19) & 3);
        const uint32_t v = type == OP_O ? 1 : P.info[id] & 7;
        mbar_wait_slow<PUBNS>(odone0 + 8 * pc, 0);
        flag_set(flag + 2 * id, v);
        if (type == OP_O && (op & P_WIDE)) flag_set(flag + 2 * id + 2, v);
      }
    } else if (wid == 10) {
      int i = threadIdx.x & 31;
      uint32_t e = i < 8 ? P.prog[role].ev[i] : 0;
      for (uint32_t n = 0; __any_sync(0xffffffffu, e); n++) {
        unsigned int* f = ptr_add(flag, 8 * (e & 1023));
        const bool ok = e && flag_peek(f) - 1 < ((e & E_FREE) ? 1 : 7);
        if (ok) {
          mbar_arrive(ev0 + 8 * i);
          if (e & (E_FREE | E_LAST)) flag_dec(f);
          i += 8;
          e = i < MAX_EV ? P.prog[role].ev[i] : 0;
        }
        asm volatile("{\n.reg .pred p;\nsetp.ge.u32 p, %0, 0x400000;\n@p trap;\n}\n" ::"r"(n));
        if (!__any_sync(0xffffffffu, ok)) __nanosleep(WATNS);
      }
    } else if (threadIdx.x == 352) {
      uint32_t items = 0;
      auto read = [&](int id) {
        if (!(P.info[id] & I_NEXT)) return;
        wait_progress(progress, items);
        flag_dec(flag + 2 * id);
      };
      for (int pc = 0;; pc++) {
        const uint32_t op = prog[pc];
        const int type = op & 3;
        if (type == OP_END) break;
        if (type == OP_O) {
          const int n = (op >> 13) & 63;
#pragma unroll 1
          for (int i = 0; i < n; i++) {
            items += (op & P_WIDE) && i == n - TAIL ? 3 * TAIL + 3 : 3;
            read(((op >> 2) & 511) + i);
          }
        } else if (type == OP_A) {
          if (op & F_PARK) { items++; read(N_TILE + ((op >> 13) & 127)); }
          items += 32;
        } else {
          items += 10;
        }
      }
    }
    __syncwarp();
    asm volatile("barrier.cluster.arrive.relaxed;\nbarrier.cluster.wait;" ::: "memory");
  }
}

typedef CUresult (*EncodeFn)(CUtensorMap*, CUtensorMapDataType, cuuint32_t, void*, const cuuint64_t*, const cuuint64_t*,
                             const cuuint32_t*, const cuuint32_t*, CUtensorMapInterleave, CUtensorMapSwizzle,
                             CUtensorMapL2promotion, CUtensorMapFloatOOBfill);

void encode(EncodeFn fn, CUtensorMap* m, const void* ptr, int rank, const cuuint64_t* dims, const cuuint64_t* strides,
            const cuuint32_t* box, CUtensorMapSwizzle swz) {
  const cuuint32_t es[5] = {1, 1, 1, 1, 1};
  CUresult r = fn(m, CU_TENSOR_MAP_DATA_TYPE_BFLOAT16, rank, const_cast<void*>(ptr), dims, strides, box, es,
                  CU_TENSOR_MAP_INTERLEAVE_NONE, swz, CU_TENSOR_MAP_L2_PROMOTION_L2_128B, CU_TENSOR_MAP_FLOAT_OOB_FILL_NONE);
  if (r != CUDA_SUCCESS) fprintf(stderr, "cuTensorMapEncodeTiled failed: %d\n", (int)r);
}

struct Op { int type, flags, id, n, quarter, park, item0, items; double t0, t1; };
struct Use { double ready, gate, need, freed; int readers, slot, prev; bool next; };
struct PlanStats { double end, slack, park_slack; int slots, parks; };

bool plan(const char* const* text, int n_pair, int phase, Params& P, PlanStats* stats = nullptr) {
  constexpr double T_Q = 7900, T_A = 24850, T_U = 26300, T_O = 1920, T_RUN = 800, T_WIDE = 1900, AHEAD = 3500, PUBLISH = 1500;
  const double margin = 256.0 * ((P.dbg >> 8) & 255);
  static Op op[N_CL][MAX_OPS];
  static Use use[ID_PART];
  int n_op[N_CL], covered[N_TEAM] = {}, finals[N_TEAM] = {};
  auto hex = [](char c) { return c <= '9' ? c - '0' : c - 'a' + 10; };
  for (int i = 0; i < n_pair; i++)
    for (const char* s = text[i]; *s; s++)
      if (*s == 'J') { if (covered[hex(s[1])]) return false; covered[hex(s[1])] = 10 * (s[2] - '0') + s[3] - '0'; }
  for (int c = 0; c < 2 * n_pair; c++) {
    int n = 0, items = 0;
    double t = 0;
    auto add = [&](int type, int flags, int id, int heads, int quarter, int its, double dt) {
      if (n < MAX_OPS) op[c][n] = {type, flags, id, heads, quarter, 0, items, its, t, t + dt};
      n++; items += its; t += dt;
    };
    for (const char* s = text[c >> 1]; *s; s++) {
      const int tm = hex(s[1]) & 15, nj = covered[tm];
      if (*s == 'N') { add(OP_Q, 0, 0, 0, 0, 10, T_Q); add(OP_A, 0, 0, 0, 0, 32, T_A); }
      if (*s == 'P') add(OP_Q, F_PARK, 0, 0, 0, 10, T_Q);
      if (*s == 'U') { if (n == 0 || n > MAX_OPS || op[c][n - 1].type != OP_A) return false; add(OP_A, F_PARK, 0, 0, 0, 33, T_U); }
      if (*s == 'J') { if (nj <= TAIL || nj > kH - 4) return false; add(OP_O, P_WIDE | P_ST, tm * kH, nj, 2 * (c & 1), 3 * (nj + TAIL), 2 * T_O * nj + T_WIDE); }
      if (*s == 'F') { if (s[2]) return false; add(OP_O, nj ? P_LD : 0, tm * kH + nj, kH - nj, finals[tm]++, 3 * (kH - nj), T_O * (kH - nj) + T_RUN); }
    }
    add(OP_END, 0, 0, 0, 0, 0, 0);
    if (n > MAX_OPS || op[c][0].type != OP_Q) return false;
    n_op[c] = n - 1;
  }
  for (int t = 0; t < N_TEAM; t++) if (finals[t] != 4) return false;
  for (int i = 0; i < ID_PART; i++) use[i] = {0, 0, 1e18, 0, 0, 0, 0, false};
  struct Ref { double t; Op* o; int id; };
  static Ref att[N_TILE + 1], dem[N_TILE], prk[MAX_PARK + 1], unp[MAX_PARK + 1], wr[ID_PART];
  int n_att = 0, n_prk = 0, n_unp = 0;
  auto ready = [&](const Op* o) {
    const int nt = o[1].type;
    return o->t1 + (nt == OP_Q ? 6100 : nt == OP_O ? ((o[1].flags & P_WIDE) ? 3900 : 3900 / FDRAIN) : 1500) + PUBLISH;
  };
  for (int c = 0; c < 2 * n_pair; c++)
    for (Op* o = op[c]; o->type != OP_END; o++) {
      if (o->type == OP_A) { att[n_att] = {ready(o), o, 0}; if (++n_att > N_TILE) return false; }
      if (o->type == OP_A && o->flags) { unp[n_unp] = {o->t0 - AHEAD, o, 0}; if (++n_unp > MAX_PARK) return false; }
      if (o->type == OP_Q && o->flags) { prk[n_prk] = {ready(o), o, 0}; if (++n_prk > MAX_PARK) return false; }
      for (int i = 0; o->type == OP_O && i < o->n; i++) {
        const int nw = (o->flags & P_WIDE) ? o->n - TAIL : 0;
        Use& u = use[o->id + i];
        const double t = o->t0 + T_O * (i + (i < nw ? i : nw));
        if (t - AHEAD < u.need) u.need = t - AHEAD;
        const double f = t + T_O * (i < nw ? 2 : nw ? 1 + TAIL : 1) + PUBLISH;
        if (f > u.freed) u.freed = f;
        u.readers++;
      }
    }
  if (n_att != N_TILE || n_prk != n_unp) return false;
  auto sort = [](Ref* r, int n) {
    for (int i = 1; i < n; i++)
      for (int j = i; j > 0 && r[j].t < r[j - 1].t; j--) { Ref x = r[j]; r[j] = r[j - 1]; r[j - 1] = x; }
  };
  for (int i = 0; i < N_TILE; i++) { const int id = (i & 15) * kH + (i >> 4); dem[i] = {use[id].need, nullptr, id}; }
  sort(att, n_att); sort(dem, N_TILE); sort(prk, n_prk); sort(unp, n_unp);
  PlanStats st = {0, 1e18, 1e18, 0, n_prk};
  int n_wr = 0;
  for (int i = 0; i < N_TILE; i++) {
    Op* o = att[i].o;
    o->id = dem[i].id;
    if (!o->flags) o[-1].id = o->id;
    if (dem[i].t - att[i].t < st.slack) st.slack = dem[i].t - att[i].t;
    wr[n_wr++] = {o->t1 - 2 * AHEAD, o, o->id};
  }
  for (int i = 0; i < n_prk; i++) {
    prk[i].o->id = unp[i].o->id;
    prk[i].o->park = unp[i].o->park = i;
    use[N_TILE + i].freed = unp[i].o->t0 + 2 * PUBLISH;
    use[N_TILE + i].readers = 1;
    if (unp[i].t - prk[i].t < st.park_slack) st.park_slack = unp[i].t - prk[i].t;
    wr[n_wr++] = {prk[i].o->t1 - 2 * AHEAD, prk[i].o, N_TILE + i};
  }
  for (int c = 0; c < 2 * n_pair; c++)
    for (int d = 0; d < 2 * n_pair; d++)
      for (Op *f = &op[c][n_op[c] - 1], *o = op[d]; f->type == OP_O && o->type != OP_END; o++)
        if (o->type == OP_O && (o->flags & P_ST) && o->id / kH == f->id / kH) {
          if (f->t0 - o->t1 > 4096.0 * ((P.dbg >> 16) & 255)) f->flags |= P_PRE;
          const double slack = f->t0 + ((f->flags & P_PRE) ? 0 : (f->n - 2) * T_O) - AHEAD - ready(o);
          if (slack < st.park_slack) st.park_slack = slack;
        }
  sort(wr, n_wr);
  int holder[N_TILE];
  for (int i = 0; i < n_wr; i++) {
    int best = -1;
    for (int sl = 0; sl < st.slots; sl++)
      if (use[holder[sl]].freed + margin <= wr[i].t && (best < 0 || (use[holder[sl]].freed < use[holder[best]].freed) != ((P.dbg & 32) != 0))) best = sl;
    Use& u = use[wr[i].id];
    if (best >= 0) { u.prev = holder[best]; use[u.prev].next = true; wr[i].o->flags |= P_GATE; }
    else if (st.slots == N_TILE) return false;
    else best = st.slots++;
    u.slot = best;
    holder[best] = wr[i].id;
  }
  {
    int pos[N_CL] = {}, flag[ID_PART + 4 * N_TEAM] = {}, seen[ID_PART] = {};
    for (bool moved = true; moved;) {
      moved = false;
      for (int c = 0; c < 2 * n_pair; c++) {
        const int total = op[c][n_op[c]].item0;
        for (; pos[c] < total + NBAR; pos[c]++, moved = true) {
          bool ok = true;
          for (const Op* o = op[c]; o->type != OP_END; o++) {
            const int k = pos[c] - o->item0, own = o->type == OP_A ? o->id : N_TILE + o->park;
            if (k < 0 || k >= o->items) continue;
            if (o->type == OP_O) ok = (k >= 3 * o->n || flag[o->id + k / 3]) && (k != ((o->flags & P_PRE) ? 0 : 3 * o->n - 6) || !(o->flags & P_LD) || flag[ID_PART + o->id / kH * 4 + o->quarter]);
            else if (k == o->items - 1 && (o->flags & P_GATE)) ok = seen[use[own].prev] == use[use[own].prev].readers;
            else if (k == 0 && o->type == OP_A && (o->flags & F_PARK)) ok = flag[N_TILE + o->park];
          }
          if (!ok) break;
          for (const Op* o = op[c]; o->type != OP_END; o++) {
            if (pos[c] == o->item0 + o->items + (o[1].type == OP_Q ? 7 : 5)) {
              if (o->type == OP_A) flag[o->id] = 1;
              if (o->type == OP_Q && (o->flags & F_PARK)) flag[N_TILE + o->park] = 1;
              if (o->type == OP_O && (o->flags & P_ST)) flag[ID_PART + o->id / kH * 4 + o->quarter] = flag[ID_PART + o->id / kH * 4 + o->quarter + 1] = 1;
            }
            const int k = pos[c] - NBAR - o->item0, nw = (o->flags & P_WIDE) ? o->n - TAIL : o->n;
            if (k == 0 && o->type == OP_A && (o->flags & F_PARK)) seen[N_TILE + o->park]++;
            if (o->type == OP_O && k >= 0 && k % 3 == 2 && (k / 3 < nw || (k / 3 >= o->n && k / 3 < 2 * o->n - nw))) seen[o->id + (k / 3 < nw ? k / 3 : k / 3 - TAIL)]++;
          }
        }
      }
    }
    for (int c = 0; c < 2 * n_pair; c++) if (pos[c] < op[c][n_op[c]].item0 + NBAR) return false;
  }
  for (int c = 0; c < 2 * n_pair; c++) {
    uint32_t items = 0, cur = 0, pend = 0;
    int n = 0, ev = 0;
    auto item = [&](uint32_t bytes, int count) {
      for (int i = 0; i < count; i++) { if (cur + bytes > RING) cur = 0; cur += bytes; items++; }
    };
    auto event = [&](uint32_t e) { if (ev < MAX_EV) P.prog[c].ev[ev] = e | E_ON; ev++; };
    for (const Op* o = op[c];; o++) {
      if (o->type != OP_END && phase && (o->type == OP_O) != (phase == 2)) continue;
      uint32_t cw = o->type | (items % NBAR) << 15 | ((items / NBAR) & 1) << 19 | (cur >> 12) << 20 | pend, pw = o->type | o->id << 2 | o->flags;
      const int ps = use[N_TILE + o->park].slot;
      pend = 0;
      if (o->type == OP_O) {
        const bool wide = o->flags & P_WIDE;
        cw |= o->n << 2 | (o->id / kH * 4 + o->quarter + wide) << 8 | (wide ? C_WIDE : 0) | ((o->flags & P_LD) ? C_LD : 0);
        pw |= o->n << 13 | o->quarter << 19;
        if (wide) item(SZ_W, 3 * (o->n - TAIL));
        for (int k = 0; k < (wide ? 6 * TAIL : 3 * o->n); k++) item((o->flags & P_LD) && k >= 3 * o->n - 5 ? SZ_OL : SZ_O, 1);
        if (wide) pend = C_PEND | ((P.dbg & 8) ? C_SOON : 0);
        for (int i = 0; i < o->n; i++) {
          if (i == ((o->flags & P_PRE) ? 0 : o->n - 2) && (o->flags & P_LD)) event((ID_PART + o->id / kH * 4 + o->quarter) | E_LAST);
          event((o->id + i) | (use[o->id + i].next ? 0 : E_LAST));
        }
      } else if (o->type != OP_END) {
        const bool parks = o->type == OP_Q && (o->flags & F_PARK);
        cw |= (parks ? ps : use[o->id].slot) << 2 | (o->flags & F_PARK);
        if (o->flags & F_PARK) pw |= o->park << 13 | ps << 20;
        if (o->type == OP_Q) item(SZ_Q, 10);
        else { if (o->flags & F_PARK) { item(SZ_PARK, 1); event((N_TILE + o->park) | (use[N_TILE + o->park].next ? 0 : E_LAST)); } item(SZ_KV, 32); }
        if (parks || o->type == OP_A) pend = C_PEND | ((P.dbg & 16) ? 0 : C_SOON);
        if (o->flags & P_GATE) event(use[parks ? N_TILE + o->park : o->id].prev | E_FREE);
      }
      P.prog[c].c[n] = cw; P.prog[c].p[n++] = pw;
      if (o->type == OP_END) { if (o->t0 > st.end) st.end = o->t0; break; }
    }
    if (ev > MAX_EV) return false;
    while (ev < MAX_EV) P.prog[c].ev[ev++] = 0;
    while (n < MAX_OPS) { P.prog[c].c[n] = OP_END; P.prog[c].p[n++] = OP_END; }
    P.first[c] = (uint16_t)(P.prog[c].p[0] & 2047);
  }
  for (int i = 0; i < ID_PART; i++) {
    if (i < N_TILE) P.slot[i] = use[i].slot;
    P.info[i] = (use[i].readers + use[i].next) | (use[i].next ? I_NEXT : 0);
  }
  if (stats) *stats = st;
  return true;
}

const char* const kPrograms[N_CL / 2] = {
  "PPNNNNNNNNN", "NNJ122NJ922NFa", "PNNNNNNNNNF0", "NNJ219NJa24NFa", "NNJ026J818NNFc", "PNNNNNNNNNF0",
  "NNJ619NJe21NF4", "NNNNNNNNNFe", "NNNNNNNNNF9", "NUNNNNNNNF6", "NUNNNNNNNF8", "NNJ726Jf25NFd",
  "NUNNNNNNNF2", "NNNNNNNNNFe", "PNNNNNNNNNFf", "NNJ418NJc24NFd", "PNNNNNNNNNFb", "NPNNNNNNNNFb",
  "NNNNNNNNNF1", "PNNNNNNNNNF7", "NUUPNNNNNNF2", "NUNNNNNNNF4", "PNNNNNNNNNF7", "NNNUNNNNNF3",
  "NNNNNNUNNF6", "NNNNNNNNNF1", "NUNNNNNNNF3", "NUNNNNNNNF8", "NNNNNNNNNF9", "PNUJ318NNJd22F5",
  "PNNNNNNNNNFf", "PNUUNNNNNNF5", "NNJ518NJb25NFc",
};

const char* const* bench_programs() {
  return kPrograms;
}

}

extern "C" void kernel_launch(void* const* d_in, const int* in_sizes, int n_in, void* d_out, int out_size) {
  (void)in_sizes; (void)n_in; (void)out_size;
  static EncodeFn fn = nullptr;
  static int n_clusters = 0;
  if (!fn) {
    cudaDriverEntryPointQueryResult qr;
    void* f = nullptr;
    cudaGetDriverEntryPoint("cuTensorMapEncodeTiled", &f, cudaEnableDefault, &qr);
    fn = (EncodeFn)f;
    cudaFuncSetAttribute(fused_kernel, cudaFuncAttributeMaxDynamicSharedMemorySize, SMEM_BYTES);
    cudaLaunchConfig_t cfg = {};
    cfg.gridDim = dim3(132); cfg.blockDim = dim3(384); cfg.dynamicSmemBytes = SMEM_BYTES;
    cudaLaunchAttribute at[1];
    at[0].id = cudaLaunchAttributeClusterDimension; at[0].val.clusterDim.x = 2; at[0].val.clusterDim.y = 1; at[0].val.clusterDim.z = 1;
    cfg.attrs = at; cfg.numAttrs = 1;
    if (cudaOccupancyMaxActiveClusters(&n_clusters, fused_kernel, &cfg) != cudaSuccess || n_clusters < 1) n_clusters = 1;
    (void)cudaGetLastError();
  }
  static Params P;
  const CUtensorMapSwizzle S128 = CU_TENSOR_MAP_SWIZZLE_128B, S64 = CU_TENSOR_MAP_SWIZZLE_64B;
  for (int blk = 0; blk < 2; blk++) {
    void* const* in = d_in + 5 * blk;
    { const cuuint64_t d[] = {kD, kB * kSq}, s[] = {kD * 2}; const cuuint32_t b[] = {64, 128};
      encode(fn, &P.x[blk], in[0], 2, d, s, b, S128); }
    { const cuuint64_t d[] = {64, 8, 3, (cuuint64_t)kB * kH * kSk / 8}, s[] = {kDh * 2, 128, 8 * kDh * 2}; const cuuint32_t b[] = {64, 8, 3, 8};
      encode(fn, &P.k[blk], in[1], 4, d, s, b, S128);
      encode(fn, &P.v[blk], in[2], 4, d, s, b, S128); }
    { const cuuint64_t d[] = {64, kD, kHD / 64}, s[] = {kHD * 2, 128}; const cuuint32_t b[] = {64, 64, 3};
      encode(fn, &P.wq[blk], in[3], 3, d, s, b, S128); }
    { const cuuint64_t d[] = {32, 2, kHD / 8, 4, kD / 32}, s[] = {kD * 2, 8 * kD * 2, 2 * kD * 2, 64}; const cuuint32_t b[] = {32, 2, 4, 4, 5};
      encode(fn, &P.wo[blk], in[4], 5, d, s, b, S64); }
  }
  { const cuuint64_t d[] = {32, kB * kSq, 2 * kD / 32}, s[] = {2 * kD * 2, 64}; const cuuint32_t b[] = {32, 16, 5};
    encode(fn, &P.out, d_out, 3, d, s, b, S64); }

  P.dbg = DBG_DEFAULT;
  if (n_clusters >= N_CL && plan(bench_programs(), N_CL / 2, 0, P)) {
    fused_kernel<<<2 * N_CL, 384, SMEM_BYTES>>>(P);
  } else {
    char buf[2 * N_TEAM][16];
    const char* text[2 * N_TEAM];
    for (int i = 0; i < 2 * N_TEAM; i++) { snprintf(buf[i], sizeof(buf[i]), "NNNNNNNNF%x", i / 2); text[i] = buf[i]; }
    for (int phase = 1; phase <= 2; phase++) {
      plan(text, 2 * N_TEAM, phase, P);
      fused_kernel<<<8 * N_TEAM, 384, SMEM_BYTES>>>(P);
    }
  }
}
```

```cpp
#include <cuda_runtime.h>
#include <cuda_bf16.h>
#include <cuda.h>
#include <stdint.h>
#include <stdio.h>

namespace {

constexpr int kB = 8, kSq = 256, kD = 640, kH = 32, kSk = 1024, kDh = 192;
constexpr int kHD = kH * kDh;
constexpr uint32_t RING = 224 * 1024;
constexpr uint32_t SZ_KV = 24576;
constexpr uint32_t SZ_Q = 16384 + 24576;
constexpr uint32_t SZ_O = 16384 + 20480;
constexpr uint32_t SZ_W = 16384 + 40960;
constexpr uint32_t SZ_PARK = 49152;
constexpr uint32_t SZ_OL = SZ_O + 8192;
constexpr int NBAR = 10;
constexpr int EARLY = 3;
#define XTAIL 2
constexpr int TAIL = XTAIL;
constexpr uint32_t KV_CH = 64, KV_SBO = 3072;
constexpr int SMEM_BYTES = RING + 1024 + 1024;
constexpr int N_TEAM = 16, N_CL = 66, MAX_OPS = 24, MAX_EV = 80, N_TILE = N_TEAM * kH, MAX_PARK = 128, ID_PART = N_TILE + MAX_PARK;
enum : uint32_t { OP_END = 0, OP_Q = 1, OP_A = 2, OP_O = 3, F_PARK = 1 << 11,
                  C_WIDE = 1 << 14, C_PEND = 1 << 26, C_SOON = 1 << 28, C_LD = 1 << 29,
                  P_GATE = 1 << 12, P_WIDE = 1 << 11, P_LD = 1 << 12, P_ST = 1 << 21, P_PRE = 1 << 22, I_NEXT = 8, E_ON = 1 << 15, E_FREE = 1 << 14, E_LAST = 1 << 13 };

#define QDRAIN 0x54732710u
#define SKEW 3
#define PUBNS 100
#define WATNS 100
constexpr uint32_t DBG_DEFAULT = 0x101833;

struct alignas(64) Params {
  uint16_t first[96];
  CUtensorMap x[2], wq[2], k[2], v[2], wo[2], out;
  struct {
    uint32_t c[MAX_OPS];
    uint32_t p[MAX_OPS];
    uint16_t ev[MAX_EV];
  } prog[N_CL];
  uint16_t slot[N_TILE];
  uint8_t info[ID_PART];
  uint32_t dbg;
};

__device__ uint4 g_t[N_TILE * 2 * 3072];
__device__ uint4 g_part[N_TEAM * 4 * 2 * 3072];
__device__ unsigned int g_flag[(ID_PART + N_TEAM * 4) * 2];

template <int TB, int TA = 0>
__device__ __forceinline__ void wgmma_ss_n64(float (&d)[32], uint64_t da, uint64_t db, int scale_d) {
  asm volatile("{\n.reg .pred p;\nsetp.ne.b32 p, %34, 0;\n"
    "wgmma.mma_async.sync.aligned.m64n64k16.f32.bf16.bf16 {%0, %1, %2, %3, %4, %5, %6, %7, %8, %9, %10, %11, %12, %13, %14, %15, %16, %17, %18, %19, %20, %21, %22, %23, %24, %25, %26, %27, %28, %29, %30, %31}, %32, %33, p, 1, 1, %35, %36;\n}\n"
    : "+f"(d[0]), "+f"(d[1]), "+f"(d[2]), "+f"(d[3]), "+f"(d[4]), "+f"(d[5]), "+f"(d[6]), "+f"(d[7]), "+f"(d[8]), "+f"(d[9]), "+f"(d[10]), "+f"(d[11]), "+f"(d[12]), "+f"(d[13]), "+f"(d[14]), "+f"(d[15]), "+f"(d[16]), "+f"(d[17]), "+f"(d[18]), "+f"(d[19]), "+f"(d[20]), "+f"(d[21]), "+f"(d[22]), "+f"(d[23]), "+f"(d[24]), "+f"(d[25]), "+f"(d[26]), "+f"(d[27]), "+f"(d[28]), "+f"(d[29]), "+f"(d[30]), "+f"(d[31])
    : "l"(da), "l"(db), "r"(scale_d), "n"(TA), "n"(TB));
}
template <int TB>
__device__ __forceinline__ void wgmma_rs_n64(float (&d)[32], uint32_t a0, uint32_t a1, uint32_t a2, uint32_t a3, uint64_t db, int scale_d) {
  asm volatile("{\n.reg .pred p;\nsetp.ne.b32 p, %37, 0;\n"
    "wgmma.mma_async.sync.aligned.m64n64k16.f32.bf16.bf16 {%0, %1, %2, %3, %4, %5, %6, %7, %8, %9, %10, %11, %12, %13, %14, %15, %16, %17, %18, %19, %20, %21, %22, %23, %24, %25, %26, %27, %28, %29, %30, %31}, {%32, %33, %34, %35}, %36, p, 1, 1, %38;\n}\n"
    : "+f"(d[0]), "+f"(d[1]), "+f"(d[2]), "+f"(d[3]), "+f"(d[4]), "+f"(d[5]), "+f"(d[6]), "+f"(d[7]), "+f"(d[8]), "+f"(d[9]), "+f"(d[10]), "+f"(d[11]), "+f"(d[12]), "+f"(d[13]), "+f"(d[14]), "+f"(d[15]), "+f"(d[16]), "+f"(d[17]), "+f"(d[18]), "+f"(d[19]), "+f"(d[20]), "+f"(d[21]), "+f"(d[22]), "+f"(d[23]), "+f"(d[24]), "+f"(d[25]), "+f"(d[26]), "+f"(d[27]), "+f"(d[28]), "+f"(d[29]), "+f"(d[30]), "+f"(d[31])
    : "r"(a0), "r"(a1), "r"(a2), "r"(a3), "l"(db), "r"(scale_d), "n"(TB));
}
template <int TB, int TA = 0>
__device__ __forceinline__ void wgmma_ss_n160(float (&d)[80], uint64_t da, uint64_t db, int scale_d) {
  asm volatile("{\n.reg .pred p;\nsetp.ne.b32 p, %82, 0;\n"
    "wgmma.mma_async.sync.aligned.m64n160k16.f32.bf16.bf16 {%0, %1, %2, %3, %4, %5, %6, %7, %8, %9, %10, %11, %12, %13, %14, %15, %16, %17, %18, %19, %20, %21, %22, %23, %24, %25, %26, %27, %28, %29, %30, %31, %32, %33, %34, %35, %36, %37, %38, %39, %40, %41, %42, %43, %44, %45, %46, %47, %48, %49, %50, %51, %52, %53, %54, %55, %56, %57, %58, %59, %60, %61, %62, %63, %64, %65, %66, %67, %68, %69, %70, %71, %72, %73, %74, %75, %76, %77, %78, %79}, %80, %81, p, 1, 1, %83, %84;\n}\n"
    : "+f"(d[0]), "+f"(d[1]), "+f"(d[2]), "+f"(d[3]), "+f"(d[4]), "+f"(d[5]), "+f"(d[6]), "+f"(d[7]), "+f"(d[8]), "+f"(d[9]), "+f"(d[10]), "+f"(d[11]), "+f"(d[12]), "+f"(d[13]), "+f"(d[14]), "+f"(d[15]), "+f"(d[16]), "+f"(d[17]), "+f"(d[18]), "+f"(d[19]), "+f"(d[20]), "+f"(d[21]), "+f"(d[22]), "+f"(d[23]), "+f"(d[24]), "+f"(d[25]), "+f"(d[26]), "+f"(d[27]), "+f"(d[28]), "+f"(d[29]), "+f"(d[30]), "+f"(d[31]), "+f"(d[32]), "+f"(d[33]), "+f"(d[34]), "+f"(d[35]), "+f"(d[36]), "+f"(d[37]), "+f"(d[38]), "+f"(d[39]), "+f"(d[40]), "+f"(d[41]), "+f"(d[42]), "+f"(d[43]), "+f"(d[44]), "+f"(d[45]), "+f"(d[46]), "+f"(d[47]), "+f"(d[48]), "+f"(d[49]), "+f"(d[50]), "+f"(d[51]), "+f"(d[52]), "+f"(d[53]), "+f"(d[54]), "+f"(d[55]), "+f"(d[56]), "+f"(d[57]), "+f"(d[58]), "+f"(d[59]), "+f"(d[60]), "+f"(d[61]), "+f"(d[62]), "+f"(d[63]), "+f"(d[64]), "+f"(d[65]), "+f"(d[66]), "+f"(d[67]), "+f"(d[68]), "+f"(d[69]), "+f"(d[70]), "+f"(d[71]), "+f"(d[72]), "+f"(d[73]), "+f"(d[74]), "+f"(d[75]), "+f"(d[76]), "+f"(d[77]), "+f"(d[78]), "+f"(d[79])
    : "l"(da), "l"(db), "r"(scale_d), "n"(TA), "n"(TB));
}
template <int TB>
__device__ __forceinline__ void wgmma_rs_n160(float (&d)[80], uint32_t a0, uint32_t a1, uint32_t a2, uint32_t a3, uint64_t db, int scale_d) {
  asm volatile("{\n.reg .pred p;\nsetp.ne.b32 p, %85, 0;\n"
    "wgmma.mma_async.sync.aligned.m64n160k16.f32.bf16.bf16 {%0, %1, %2, %3, %4, %5, %6, %7, %8, %9, %10, %11, %12, %13, %14, %15, %16, %17, %18, %19, %20, %21, %22, %23, %24, %25, %26, %27, %28, %29, %30, %31, %32, %33, %34, %35, %36, %37, %38, %39, %40, %41, %42, %43, %44, %45, %46, %47, %48, %49, %50, %51, %52, %53, %54, %55, %56, %57, %58, %59, %60, %61, %62, %63, %64, %65, %66, %67, %68, %69, %70, %71, %72, %73, %74, %75, %76, %77, %78, %79}, {%80, %81, %82, %83}, %84, p, 1, 1, %86;\n}\n"
    : "+f"(d[0]), "+f"(d[1]), "+f"(d[2]), "+f"(d[3]), "+f"(d[4]), "+f"(d[5]), "+f"(d[6]), "+f"(d[7]), "+f"(d[8]), "+f"(d[9]), "+f"(d[10]), "+f"(d[11]), "+f"(d[12]), "+f"(d[13]), "+f"(d[14]), "+f"(d[15]), "+f"(d[16]), "+f"(d[17]), "+f"(d[18]), "+f"(d[19]), "+f"(d[20]), "+f"(d[21]), "+f"(d[22]), "+f"(d[23]), "+f"(d[24]), "+f"(d[25]), "+f"(d[26]), "+f"(d[27]), "+f"(d[28]), "+f"(d[29]), "+f"(d[30]), "+f"(d[31]), "+f"(d[32]), "+f"(d[33]), "+f"(d[34]), "+f"(d[35]), "+f"(d[36]), "+f"(d[37]), "+f"(d[38]), "+f"(d[39]), "+f"(d[40]), "+f"(d[41]), "+f"(d[42]), "+f"(d[43]), "+f"(d[44]), "+f"(d[45]), "+f"(d[46]), "+f"(d[47]), "+f"(d[48]), "+f"(d[49]), "+f"(d[50]), "+f"(d[51]), "+f"(d[52]), "+f"(d[53]), "+f"(d[54]), "+f"(d[55]), "+f"(d[56]), "+f"(d[57]), "+f"(d[58]), "+f"(d[59]), "+f"(d[60]), "+f"(d[61]), "+f"(d[62]), "+f"(d[63]), "+f"(d[64]), "+f"(d[65]), "+f"(d[66]), "+f"(d[67]), "+f"(d[68]), "+f"(d[69]), "+f"(d[70]), "+f"(d[71]), "+f"(d[72]), "+f"(d[73]), "+f"(d[74]), "+f"(d[75]), "+f"(d[76]), "+f"(d[77]), "+f"(d[78]), "+f"(d[79])
    : "r"(a0), "r"(a1), "r"(a2), "r"(a3), "l"(db), "r"(scale_d), "n"(TB));
}
template <int TB, int TA = 0>
__device__ __forceinline__ void wgmma_ss_n192(float (&d)[96], uint64_t da, uint64_t db, int scale_d) {
  asm volatile("{\n.reg .pred p;\nsetp.ne.b32 p, %98, 0;\n"
    "wgmma.mma_async.sync.aligned.m64n192k16.f32.bf16.bf16 {%0, %1, %2, %3, %4, %5, %6, %7, %8, %9, %10, %11, %12, %13, %14, %15, %16, %17, %18, %19, %20, %21, %22, %23, %24, %25, %26, %27, %28, %29, %30, %31, %32, %33, %34, %35, %36, %37, %38, %39, %40, %41, %42, %43, %44, %45, %46, %47, %48, %49, %50, %51, %52, %53, %54, %55, %56, %57, %58, %59, %60, %61, %62, %63, %64, %65, %66, %67, %68, %69, %70, %71, %72, %73, %74, %75, %76, %77, %78, %79, %80, %81, %82, %83, %84, %85, %86, %87, %88, %89, %90, %91, %92, %93, %94, %95}, %96, %97, p, 1, 1, %99, %100;\n}\n"
    : "+f"(d[0]), "+f"(d[1]), "+f"(d[2]), "+f"(d[3]), "+f"(d[4]), "+f"(d[5]), "+f"(d[6]), "+f"(d[7]), "+f"(d[8]), "+f"(d[9]), "+f"(d[10]), "+f"(d[11]), "+f"(d[12]), "+f"(d[13]), "+f"(d[14]), "+f"(d[15]), "+f"(d[16]), "+f"(d[17]), "+f"(d[18]), "+f"(d[19]), "+f"(d[20]), "+f"(d[21]), "+f"(d[22]), "+f"(d[23]), "+f"(d[24]), "+f"(d[25]), "+f"(d[26]), "+f"(d[27]), "+f"(d[28]), "+f"(d[29]), "+f"(d[30]), "+f"(d[31]), "+f"(d[32]), "+f"(d[33]), "+f"(d[34]), "+f"(d[35]), "+f"(d[36]), "+f"(d[37]), "+f"(d[38]), "+f"(d[39]), "+f"(d[40]), "+f"(d[41]), "+f"(d[42]), "+f"(d[43]), "+f"(d[44]), "+f"(d[45]), "+f"(d[46]), "+f"(d[47]), "+f"(d[48]), "+f"(d[49]), "+f"(d[50]), "+f"(d[51]), "+f"(d[52]), "+f"(d[53]), "+f"(d[54]), "+f"(d[55]), "+f"(d[56]), "+f"(d[57]), "+f"(d[58]), "+f"(d[59]), "+f"(d[60]), "+f"(d[61]), "+f"(d[62]), "+f"(d[63]), "+f"(d[64]), "+f"(d[65]), "+f"(d[66]), "+f"(d[67]), "+f"(d[68]), "+f"(d[69]), "+f"(d[70]), "+f"(d[71]), "+f"(d[72]), "+f"(d[73]), "+f"(d[74]), "+f"(d[75]), "+f"(d[76]), "+f"(d[77]), "+f"(d[78]), "+f"(d[79]), "+f"(d[80]), "+f"(d[81]), "+f"(d[82]), "+f"(d[83]), "+f"(d[84]), "+f"(d[85]), "+f"(d[86]), "+f"(d[87]), "+f"(d[88]), "+f"(d[89]), "+f"(d[90]), "+f"(d[91]), "+f"(d[92]), "+f"(d[93]), "+f"(d[94]), "+f"(d[95])
    : "l"(da), "l"(db), "r"(scale_d), "n"(TA), "n"(TB));
}
template <int TB>
__device__ __forceinline__ void wgmma_rs_n192(float (&d)[96], uint32_t a0, uint32_t a1, uint32_t a2, uint32_t a3, uint64_t db, int scale_d) {
  asm volatile("{\n.reg .pred p;\nsetp.ne.b32 p, %101, 0;\n"
    "wgmma.mma_async.sync.aligned.m64n192k16.f32.bf16.bf16 {%0, %1, %2, %3, %4, %5, %6, %7, %8, %9, %10, %11, %12, %13, %14, %15, %16, %17, %18, %19, %20, %21, %22, %23, %24, %25, %26, %27, %28, %29, %30, %31, %32, %33, %34, %35, %36, %37, %38, %39, %40, %41, %42, %43, %44, %45, %46, %47, %48, %49, %50, %51, %52, %53, %54, %55, %56, %57, %58, %59, %60, %61, %62, %63, %64, %65, %66, %67, %68, %69, %70, %71, %72, %73, %74, %75, %76, %77, %78, %79, %80, %81, %82, %83, %84, %85, %86, %87, %88, %89, %90, %91, %92, %93, %94, %95}, {%96, %97, %98, %99}, %100, p, 1, 1, %102;\n}\n"
    : "+f"(d[0]), "+f"(d[1]), "+f"(d[2]), "+f"(d[3]), "+f"(d[4]), "+f"(d[5]), "+f"(d[6]), "+f"(d[7]), "+f"(d[8]), "+f"(d[9]), "+f"(d[10]), "+f"(d[11]), "+f"(d[12]), "+f"(d[13]), "+f"(d[14]), "+f"(d[15]), "+f"(d[16]), "+f"(d[17]), "+f"(d[18]), "+f"(d[19]), "+f"(d[20]), "+f"(d[21]), "+f"(d[22]), "+f"(d[23]), "+f"(d[24]), "+f"(d[25]), "+f"(d[26]), "+f"(d[27]), "+f"(d[28]), "+f"(d[29]), "+f"(d[30]), "+f"(d[31]), "+f"(d[32]), "+f"(d[33]), "+f"(d[34]), "+f"(d[35]), "+f"(d[36]), "+f"(d[37]), "+f"(d[38]), "+f"(d[39]), "+f"(d[40]), "+f"(d[41]), "+f"(d[42]), "+f"(d[43]), "+f"(d[44]), "+f"(d[45]), "+f"(d[46]), "+f"(d[47]), "+f"(d[48]), "+f"(d[49]), "+f"(d[50]), "+f"(d[51]), "+f"(d[52]), "+f"(d[53]), "+f"(d[54]), "+f"(d[55]), "+f"(d[56]), "+f"(d[57]), "+f"(d[58]), "+f"(d[59]), "+f"(d[60]), "+f"(d[61]), "+f"(d[62]), "+f"(d[63]), "+f"(d[64]), "+f"(d[65]), "+f"(d[66]), "+f"(d[67]), "+f"(d[68]), "+f"(d[69]), "+f"(d[70]), "+f"(d[71]), "+f"(d[72]), "+f"(d[73]), "+f"(d[74]), "+f"(d[75]), "+f"(d[76]), "+f"(d[77]), "+f"(d[78]), "+f"(d[79]), "+f"(d[80]), "+f"(d[81]), "+f"(d[82]), "+f"(d[83]), "+f"(d[84]), "+f"(d[85]), "+f"(d[86]), "+f"(d[87]), "+f"(d[88]), "+f"(d[89]), "+f"(d[90]), "+f"(d[91]), "+f"(d[92]), "+f"(d[93]), "+f"(d[94]), "+f"(d[95])
    : "r"(a0), "r"(a1), "r"(a2), "r"(a3), "l"(db), "r"(scale_d), "n"(TB));
}

__device__ __forceinline__ uint32_t smem_u32(const void* p) { return (uint32_t)__cvta_generic_to_shared(p); }
__device__ __forceinline__ void wg_fence() { asm volatile("wgmma.fence.sync.aligned;" ::: "memory"); }
__device__ __forceinline__ void wg_commit() { asm volatile("wgmma.commit_group.sync.aligned;" ::: "memory"); }
template <int N> __device__ __forceinline__ void wg_wait() { asm volatile("wgmma.wait_group.sync.aligned %0;" ::"n"(N) : "memory"); }
__device__ __forceinline__ void sched_fence(uint32_t& keep, bool never) {
  asm volatile("{\n.reg .pred p;\nsetp.ne.b32 p, %1, 0;\n@p mov.u32 %0, %%clock;\n}\n" : "+r"(keep) : "r"((int)never) : "memory");
}
template <int N> __device__ __forceinline__ void fence_regs(float (&r)[N]) {
#pragma unroll
  for (int i = 0; i < N; i++) asm volatile("" : "+f"(r[i])::"memory");
}
template <int N> __device__ __forceinline__ void undefine(float (&r)[N]) {
#pragma unroll
  for (int i = 0; i < N; i++) asm volatile("" : "=f"(r[i]));
}
template <int N> __device__ __forceinline__ void fence_regs(uint32_t (&r)[N]) {
#pragma unroll
  for (int i = 0; i < N; i++) asm volatile("" : "+r"(r[i])::"memory");
}
__device__ __forceinline__ uint64_t mk_desc(uint32_t a16, uint32_t lbo, uint32_t sbo, uint32_t swz) {
  uint64_t d;
  asm("mov.b64 %0, {%1, %2};" : "=l"(d) : "r"(a16 + ((lbo >> 4) << 16)), "r"((sbo >> 4) | (swz << 30)));
  return d;
}
__device__ __forceinline__ void mbar_init(uint32_t bar, uint32_t cnt) {
  asm volatile("mbarrier.init.shared::cta.b64 [%0], %1;" ::"r"(bar), "r"(cnt) : "memory");
}
__device__ __forceinline__ void mbar_expect(uint32_t bar, uint32_t tx) {
  asm volatile("mbarrier.arrive.expect_tx.shared::cta.b64 _, [%0], %1;" ::"r"(bar), "r"(tx) : "memory");
}
__device__ __forceinline__ bool mbar_test(uint32_t bar, uint32_t ph) {
  uint32_t ok;
  asm volatile("{\n.reg .pred p;\nmbarrier.test_wait.parity.shared::cta.b64 p, [%1], %2;\nselp.u32 %0, 1, 0, p;\n}\n"
               : "=r"(ok) : "r"(bar), "r"(ph) : "memory");
  return ok;
}
__device__ __forceinline__ void mbar_wait(uint32_t bar, uint32_t ph) {
  asm volatile("{\n.reg .pred p;\n.reg .u32 n;\nmov.u32 n, 0;\n"
               "LOOP:\nmbarrier.try_wait.parity.shared::cta.b64 p, [%0], %1;\n@p bra DONE;\n"
               "add.u32 n, n, 1;\nsetp.lt.u32 p, n, 0x1000000;\n@p bra LOOP;\ntrap;\n"
               "DONE:\n}\n" ::"r"(bar), "r"(ph) : "memory");
}
template <int NS> __device__ __forceinline__ void mbar_wait_slow(uint32_t bar, uint32_t ph) {
  asm volatile("{\n.reg .pred p;\n.reg .u32 n;\nmov.u32 n, 0;\n"
               "LOOP:\nmbarrier.test_wait.parity.shared::cta.b64 p, [%0], %1;\n@p bra DONE;\n"
               "nanosleep.u32 %2;\nadd.u32 n, n, 1;\nsetp.lt.u32 p, n, 0x400000;\n@p bra LOOP;\ntrap;\n"
               "DONE:\n}\n" ::"r"(bar), "r"(ph), "n"(NS) : "memory");
}
__device__ __forceinline__ void mbar_arrive_cluster_if(bool on, uint32_t addr) {
  asm volatile("{\n.reg .pred p;\nsetp.ne.b32 p, %1, 0;\n@p mbarrier.arrive.shared::cluster.b64 _, [%0];\n}\n" ::"r"(addr), "r"((int)on) : "memory");
}
__device__ __forceinline__ void tma2d(uint32_t dst, const CUtensorMap* m, uint32_t bar, int c0, int c1) {
  asm volatile("cp.async.bulk.tensor.2d.shared::cluster.global.mbarrier::complete_tx::bytes [%0], [%1, {%3, %4}], [%2];"
               ::"r"(dst), "l"(m), "r"(bar), "r"(c0), "r"(c1) : "memory");
}
__device__ __forceinline__ void tma3d(uint32_t dst, const CUtensorMap* m, uint32_t bar, int c0, int c1, int c2) {
  asm volatile("cp.async.bulk.tensor.3d.shared::cluster.global.mbarrier::complete_tx::bytes [%0], [%1, {%3, %4, %5}], [%2];"
               ::"r"(dst), "l"(m), "r"(bar), "r"(c0), "r"(c1), "r"(c2) : "memory");
}
__device__ __forceinline__ void tma3d_mc(uint32_t dst, const CUtensorMap* m, uint32_t bar, int c0, int c1, int c2) {
  asm volatile("cp.async.bulk.tensor.3d.shared::cluster.global.mbarrier::complete_tx::bytes.multicast::cluster"
               " [%0], [%1, {%3, %4, %5}], [%2], %6;"
               ::"r"(dst), "l"(m), "r"(bar), "r"(c0), "r"(c1), "r"(c2), "h"((uint16_t)3) : "memory");
}
__device__ __forceinline__ void tma3d_store(const CUtensorMap* m, uint32_t src, int c0, int c1, int c2) {
  asm volatile("cp.async.bulk.tensor.3d.global.shared::cta.bulk_group [%0, {%2, %3, %4}], [%1];"
               ::"l"(m), "r"(src), "r"(c0), "r"(c1), "r"(c2) : "memory");
}
__device__ __forceinline__ void bar_sync(int id, int n) { asm volatile("bar.sync %0, %1;" ::"r"(id), "r"(n) : "memory"); }
__device__ __forceinline__ uint32_t pack_bf16(float lo, float hi) {
  uint32_t r;
  asm("cvt.rn.bf16x2.f32 %0, %1, %2;" : "=r"(r) : "f"(hi), "f"(lo));
  return r;
}
__device__ __forceinline__ float ex2(float x) {
  float y;
  asm("ex2.approx.ftz.f32 %0, %1;" : "=f"(y) : "f"(x));
  return y;
}
__device__ __forceinline__ float rcp(float x) {
  float y;
  asm("rcp.approx.ftz.f32 %0, %1;" : "=f"(y) : "f"(x));
  return y;
}
__device__ __forceinline__ void stsm4(uint32_t addr, uint32_t a, uint32_t b, uint32_t c, uint32_t d) {
  asm volatile("stmatrix.sync.aligned.m8n8.x4.shared.b16 [%0], {%1, %2, %3, %4};" ::"r"(addr), "r"(a), "r"(b), "r"(c), "r"(d) : "memory");
}

__device__ __forceinline__ void tma4d_mc_hint(uint32_t dst, const CUtensorMap* m, uint32_t bar, int c3, uint64_t pol) {
  asm volatile("cp.async.bulk.tensor.4d.shared::cluster.global.mbarrier::complete_tx::bytes.multicast::cluster.L2::cache_hint"
               " [%0], [%1, {%3, %3, %3, %4}], [%2], %5, %6;"
               ::"r"(dst), "l"(m), "r"(bar), "r"(0), "r"(c3), "h"((uint16_t)3), "l"(pol) : "memory");
}
__device__ __forceinline__ void tma5d_mc(uint32_t dst, const CUtensorMap* m, uint32_t bar, int c2, int c4) {
  asm volatile("cp.async.bulk.tensor.5d.shared::cluster.global.mbarrier::complete_tx::bytes.multicast::cluster"
               " [%0], [%1, {%3, %3, %4, %3, %5}], [%2], %6;"
               ::"r"(dst), "l"(m), "r"(bar), "r"(0), "r"(c2), "r"(c4), "h"((uint16_t)3) : "memory");
}
__device__ __forceinline__ void bulk_load_hint(uint32_t dst, const void* src, uint32_t bytes, uint32_t bar, uint64_t pol) {
  asm volatile("cp.async.bulk.shared::cluster.global.mbarrier::complete_tx::bytes.L2::cache_hint [%0], [%1], %2, [%3], %4;"
               ::"r"(dst), "l"(src), "r"(bytes), "r"(bar), "l"(pol) : "memory");
}
__device__ __forceinline__ void stg128_hint(void* p, uint32_t a, uint32_t b, uint32_t c, uint32_t d, uint64_t pol) {
  asm volatile("st.global.L2::cache_hint.v4.b32 [%0], {%1, %2, %3, %4}, %5;" ::"l"(p), "r"(a), "r"(b), "r"(c), "r"(d), "l"(pol) : "memory");
}
__device__ __forceinline__ void stg2_if(bool on, void* p, uint32_t a, uint32_t b, uint32_t c, uint32_t d, uint32_t e, uint32_t f,
                                        uint32_t g, uint32_t h, uint64_t pol) {
  asm volatile("{\n.reg .pred p;\nsetp.ne.b32 p, %10, 0;\n"
               "@p st.global.L2::cache_hint.v4.b32 [%0], {%1, %2, %3, %4}, %9;\n"
               "@p st.global.L2::cache_hint.v4.b32 [%0 + 512], {%5, %6, %7, %8}, %9;\n}\n"
               ::"l"(p), "r"(a), "r"(b), "r"(c), "r"(d), "r"(e), "r"(f), "r"(g), "r"(h), "l"(pol), "r"((int)on) : "memory");
}
__device__ __forceinline__ uint64_t make_policy(bool first) {
  uint64_t pf, pn;
  asm("createpolicy.fractional.L2::evict_first.b64 %0, 1.0;" : "=l"(pf));
  asm("createpolicy.fractional.L2::evict_normal.b64 %0, 1.0;" : "=l"(pn));
  return first ? pf : pn;
}
__device__ __forceinline__ bool elect() {
  uint32_t ok;
  asm volatile("{\n.reg .pred p;\nelect.sync _|p, 0xffffffff;\nselp.u32 %0, 1, 0, p;\n}\n" : "=r"(ok));
  return ok;
}
__device__ __forceinline__ void mbar_arrive(uint32_t bar) {
  asm volatile("mbarrier.arrive.shared::cta.b64 _, [%0];" ::"r"(bar) : "memory");
}
__device__ __forceinline__ void mbar_arrive_if(bool on, uint32_t bar) {
  asm volatile("{\n.reg .pred p;\nsetp.ne.b32 p, %1, 0;\n@p mbarrier.arrive.shared::cta.b64 _, [%0];\n}\n" ::"r"(bar), "r"((int)on) : "memory");
}
__device__ __forceinline__ void stg128(void* p, uint32_t a, uint32_t b, uint32_t c, uint32_t d) {
  asm volatile("st.global.v4.b32 [%0], {%1, %2, %3, %4};" ::"l"(p), "r"(a), "r"(b), "r"(c), "r"(d) : "memory");
}
__device__ __forceinline__ void lds2_if(bool on, uint32_t p, uint32_t (&t)[8]) {
  asm volatile("{\n.reg .pred p;\nsetp.ne.b32 p, %9, 0;\n@p ld.shared.v4.b32 {%0, %1, %2, %3}, [%8];\n@p ld.shared.v4.b32 {%4, %5, %6, %7}, [%8 + 512];\n}\n"
               : "+r"(t[0]), "+r"(t[1]), "+r"(t[2]), "+r"(t[3]), "+r"(t[4]), "+r"(t[5]), "+r"(t[6]), "+r"(t[7]) : "r"(p), "r"((int)on) : "memory");
}
__device__ __forceinline__ void lds128(uint32_t p, uint32_t& a, uint32_t& b, uint32_t& c, uint32_t& d) {
  asm volatile("ld.shared.v4.b32 {%0, %1, %2, %3}, [%4];" : "=r"(a), "=r"(b), "=r"(c), "=r"(d) : "r"(p) : "memory");
}
template <class T> __device__ __forceinline__ T* ptr_add(T* base, uint32_t bytes) {
  T* r;
  asm("{\n.reg .u32 lo, hi;\nmov.b64 {lo, hi}, %1;\nadd.cc.u32 lo, lo, %2;\naddc.u32 hi, hi, 0;\nmov.b64 %0, {lo, hi};\n}\n" : "=l"(r) : "l"(base), "r"(bytes));
  return r;
}
__device__ __forceinline__ uint32_t flag_peek(const unsigned int* p) {
  uint32_t v;
  asm volatile("ld.relaxed.gpu.global.u32 %0, [%1];" : "=r"(v) : "l"(p) : "memory");
  return v;
}
__device__ __forceinline__ uint32_t flag_get(const unsigned int* p) {
  uint32_t v;
  asm volatile("ld.acquire.gpu.global.u32 %0, [%1];" : "=r"(v) : "l"(p) : "memory");
  return v;
}
__device__ __forceinline__ void wait_progress(uint32_t p, uint32_t target) {
  asm volatile("{\n.reg .pred p;\n.reg .u32 n, v;\nmov.u32 n, 0;\n"
               "LOOP:\nld.acquire.cta.shared.u32 v, [%0];\nsetp.ge.u32 p, v, %1;\n@p bra DONE;\n"
               "nanosleep.u32 %2;\nadd.u32 n, n, 1;\nsetp.lt.u32 p, n, 0x400000;\n@p bra LOOP;\ntrap;\n"
               "DONE:\n}\n" ::"r"(p), "r"(target), "n"(400) : "memory");
}
__device__ __forceinline__ void flag_set(unsigned int* p, uint32_t v) {
  asm volatile("st.release.gpu.global.u32 [%0], %1;" ::"l"(p), "r"(v) : "memory");
}
__device__ __forceinline__ void flag_dec(unsigned int* p) {
  asm volatile("red.relaxed.gpu.global.add.u32 [%0], 0xffffffff;" ::"l"(p) : "memory");
}

struct Cursor {
  int bi;
  uint32_t ph;
  __device__ __forceinline__ void next() {
    if (++bi == NBAR) { bi = 0; ph ^= 1; }
  }
};

constexpr float kScaleLog2 = 0.07216878364870322f * 1.4426950408889634f;
constexpr float kSumLimit = 1048576.0f;

__global__ void __cluster_dims__(2, 1, 1) __launch_bounds__(384, 1)
fused_kernel(const __grid_constant__ Params P) {
  extern __shared__ uint8_t smem_raw[];
  const uint32_t sbase = (smem_u32(smem_raw) + 1023) & ~1023u;
  const uint32_t full0 = sbase + RING, empty0 = full0 + 8 * NBAR, odone0 = empty0 + 8 * NBAR, ev0 = odone0 + 8 * MAX_OPS;
  const uint32_t progress = ev0 + 8 * MAX_EV;
  const uint32_t rank = blockIdx.x & 1;
  const int role = blockIdx.x >> 1;
  const int wid = __shfl_sync(0xffffffffu, (int)(threadIdx.x >> 5), 0);
  const int wg = wid >> 2;

  const uint32_t op0 = P.first[role];
  if (__builtin_expect(wid == 8, 1)) {
    if (elect()) {
#pragma unroll
      for (int k = 0; k < EARLY; k++) mbar_init(full0 + 8 * k, 1);
      asm volatile("fence.mbarrier_init.release.cluster;" ::: "memory");
      const int blk = (op0 >> 10) & 1;
      if ((op0 & 3) == OP_Q) {
#pragma unroll
        for (int k = 0; k < EARLY; k++) {
          mbar_expect(full0 + 8 * k, SZ_Q);
          tma2d(sbase + k * SZ_Q, &P.x[blk], full0 + 8 * k, 64 * k, ((op0 >> 7) & 7) * kSq + rank * 128);
          tma3d(sbase + k * SZ_Q + 16384, &P.wq[blk], full0 + 8 * k, 0, 64 * k, 3 * ((op0 >> 2) & 31));
        }
      }
      asm volatile("prefetch.tensormap [%0];" ::"l"(rank ? &P.v[blk] : &P.k[blk]) : "memory");
    }
  } else if (wg < 2 && elect()) {
#pragma unroll
    for (int j = 0; j < 16; j++) {
      const int i = EARLY + 16 * wid + j;
      if (i < 2 * NBAR + MAX_OPS + MAX_EV) mbar_init(full0 + 8 * i, i < NBAR ? 1 : i < 2 * NBAR ? 16 : i < 2 * NBAR + MAX_OPS ? 8 : 1);
    }
    if (wid == 7) asm volatile("st.shared.u32 [%0], 0;\nfence.acq_rel.cta;" ::"r"(progress) : "memory");
    asm volatile("fence.mbarrier_init.release.cluster;" ::: "memory");
  }
  __syncwarp();
  asm volatile("barrier.cluster.arrive.relaxed.aligned;\nbarrier.cluster.wait.aligned;" ::: "memory");

  if (wg < 2) {
    asm volatile("setmaxnreg.inc.sync.aligned.u32 240;");
    const uint32_t* prog = P.prog[role].c;
    const int lane = threadIdx.x & 31, warp = wid & 3;
    uint32_t empty_rem;
    asm volatile("mapa.shared::cluster.u32 %0, %1, %2;" : "=r"(empty_rem) : "r"(empty0), "r"(lane & 1));
    auto release = [&](int slot) { mbar_arrive_cluster_if(lane < 2, empty_rem + 8 * slot); };
    Cursor r{0, 0};
    const uint32_t ring16 = (sbase & 0x3FFFF) >> 4;
    uint32_t cur = ring16;
    bool rdy0 = false, rdy1 = false;
    auto probe1 = [&]() { rdy0 = mbar_test(full0 + 8 * r.bi, r.ph); };
    auto probe2 = [&]() {
      Cursor n = r;
      rdy0 = mbar_test(full0 + 8 * n.bi, n.ph);
      n.next();
      rdy1 = mbar_test(full0 + 8 * n.bi, n.ph);
    };
    auto take = [&](bool rdy, uint32_t bytes, uint32_t& addr) {
      const int bi = r.bi;
      if (__builtin_expect(!__all_sync(0xffffffffu, rdy), 0)) mbar_wait(full0 + 8 * r.bi, r.ph);
      r.next();
      if (cur > ring16 + ((RING - bytes) >> 4)) cur = ring16;
      addr = cur;
      cur += bytes >> 4;
      return bi;
    };
    uint32_t keep = 0;
    const bool never = P.dbg == 0xffffffffu;
    uint32_t q[48];
#pragma unroll
    for (int i = 0; i < 48; i++) q[i] = 0;
    const int row = wg * 64 + warp * 16 + (lane >> 2);
    const int img0 = row * 4 + ((lane & 3) ^ ((row >> 1) & 3));
    uint4* pend = nullptr;
    bool pend_any = false;
    uint64_t spol;
    int pc = 0;
    auto slab = [&](int c, int i0) {
#pragma unroll
      for (int i = i0; i < 6; i++)
        stg2_if(c == i, pend + i * 512, q[8 * i], q[8 * i + 1], q[8 * i + 2], q[8 * i + 3],
                q[8 * i + 4], q[8 * i + 5], q[8 * i + 6], q[8 * i + 7], spol);
    };
    auto drain = [&](int c) {
      if (!pend_any || c >= 6) return;
      slab(c, 0);
      if (c == 5) {
        __syncwarp();
        mbar_arrive_if(lane == 0, odone0 - 8 + 8 * pc);
      }
    };

    for (;; pc++) {
      uint32_t op = prog[pc];
      const int type = op & 3;
      auto enter = [&]() {
        r.bi = (op >> 15) & 15; r.ph = (op >> 19) & 1; cur = ring16 + (((op >> 20) & 63) << 8);
      };
      enter();
      pend_any = op & C_PEND;
      spol = make_policy(!(op & C_SOON));
      if (type == OP_END) {
#pragma unroll 1
        for (int c = 0; c < 6; c++) drain(c);
        asm volatile("barrier.cluster.arrive.relaxed;" ::: "memory");
        break;
      }
      {
        float s[32], o[96];
        uint32_t ad0;
        int bi0, sk1;
        uint32_t pa[16], pb[16];
        float mc0, mc1, l0, l1;
        bool shifted;
        uint32_t nop;
        auto expo = [&](float (&s)[32], uint32_t (&pout)[16], float& b0, float& b1, bool shift, auto mid) {
          float c0, c1;
#pragma unroll
          for (int i = 0; i < 8; i++) {
            const float e0 = ex2(shift ? s[4 * i] - mc0 : s[4 * i]), e1 = ex2(shift ? s[4 * i + 1] - mc0 : s[4 * i + 1]);
            const float e2 = ex2(shift ? s[4 * i + 2] - mc1 : s[4 * i + 2]), e3 = ex2(shift ? s[4 * i + 3] - mc1 : s[4 * i + 3]);
            if (i) { b0 += e0; c0 += e1; b1 += e2; c1 += e3; } else { b0 = e0; c0 = e1; b1 = e2; c1 = e3; }
            pout[2 * i] = pack_bf16(e0, e1); pout[2 * i + 1] = pack_bf16(e2, e3);
            if (i & 1) mid(i >> 1);
          }
          b0 += c0; b1 += c1;
        };
        auto rowmax = [&](float (&s)[32], float& m0, float& m1) {
          m0 = fmaxf(s[0], s[1]); m1 = fmaxf(s[2], s[3]);
#pragma unroll
          for (int i = 1; i < 8; i++) { m0 = fmaxf(m0, fmaxf(s[4 * i], s[4 * i + 1])); m1 = fmaxf(m1, fmaxf(s[4 * i + 2], s[4 * i + 3])); }
          m0 = fmaxf(m0, __shfl_xor_sync(0xffffffffu, m0, 1)); m1 = fmaxf(m1, __shfl_xor_sync(0xffffffffu, m1, 1));
          m0 = fmaxf(m0, __shfl_xor_sync(0xffffffffu, m0, 2)); m1 = fmaxf(m1, __shfl_xor_sync(0xffffffffu, m1, 2));
        };
        auto first = [&](float (&s)[32], int sk0, auto mid) {
          fence_regs(s);
          release(sk0);
          mc0 = 0.f; mc1 = 0.f;
          expo(s, pa, l0, l1, false, mid);
          shifted = __any_sync(0xffffffffu, !(fmaxf(l0, l1) <= kSumLimit && fminf(l0, l1) >= 1.f / kSumLimit));
          if (shifted) {
            rowmax(s, mc0, mc1);
            expo(s, pa, l0, l1, true, [](int) {});
          }
        };
        auto qk = [&](float (&s)[32], uint32_t ak, int k0 = 0, int k1 = 12) {
#pragma unroll
          for (int kk = k0; kk < k1; kk++)
            wgmma_rs_n64<0>(s, q[4 * kk], q[4 * kk + 1], q[4 * kk + 2], q[4 * kk + 3], mk_desc(ak + (kk >> 2) * KV_CH + (kk & 3) * 2, 16, KV_SBO, 1), kk != 0);
          if (k1 == 12) wg_commit();
        };
        auto pv = [&](uint32_t (&pin)[16], uint32_t av, int acc) {
#pragma unroll
          for (int kk = 0; kk < 4; kk++)
            wgmma_rs_n192<1>(o, pin[4 * kk], pin[4 * kk + 1], pin[4 * kk + 2], pin[4 * kk + 3], mk_desc(av + kk * (KV_SBO / 8), KV_CH * 16, KV_SBO, 1), acc || (kk != 0));
          wg_commit();
        };
        auto finish = [&](uint32_t (&pout)[16], int sk, int sv) {
          probe2();
          wg_wait<1>();
          fence_regs(s);
          release(sk);
          float b0, b1;
#pragma unroll 1
          for (bool redo = false;; redo = true) {
            expo(s, pout, b0, b1, false, [](int) {});
            if (!__any_sync(0xffffffffu, !redo && (shifted || !(fmaxf(b0, b1) <= kSumLimit)))) break;
            shifted = true;
            rowmax(s, b0, b1);
            b0 = fmaxf(mc0, b0); b1 = fmaxf(mc1, b1);
            const float a0 = ex2(mc0 - b0), a1 = ex2(mc1 - b1);
            mc0 = b0; mc1 = b1;
            l0 *= a0; l1 *= a1;
            wg_wait<0>();
            fence_regs(o);
#pragma unroll
            for (int i = 0; i < 24; i++) { o[4 * i] *= a0; o[4 * i + 1] *= a0; o[4 * i + 2] *= a1; o[4 * i + 3] *= a1; }
#pragma unroll
            for (int i = 0; i < 32; i++) s[i] -= (i & 2) ? mc1 : mc0;
          }
          l0 += b0; l1 += b1;
          wg_wait<0>();
          fence_regs(o);
          release(sv);
        };
        auto step = [&](uint32_t (&pin)[16], uint32_t (&pout)[16]) {
          uint32_t ak, av;
          const int sk = take(rdy0, SZ_KV, ak), sv = take(rdy1, SZ_KV, av);
          wg_fence();
          qk(s, ak);
          pv(pin, av, 1);
          finish(pout, sk, sv);
        };
        auto unpark = [&]() {
          uint32_t ad, ak;
          const int bi = take(rdy0, SZ_PARK, ad);
#pragma unroll
          for (int i = 0; i < 12; i++) lds128(sbase + (ad - ring16 + img0) * 16 + (i >> 1) * 8192 + (i & 1) * 512, q[4 * i], q[4 * i + 1], q[4 * i + 2], q[4 * i + 3]);
          const int sk0 = take(false, SZ_KV, ak);
          fence_regs(q);
          release(bi);
          wg_fence();
          qk(s, ak);
          probe2();
          return sk0;
        };
        auto mma4 = [&](uint32_t ad, int acc) {
#pragma unroll
          for (int kk = 0; kk < 4; kk++)
            wgmma_ss_n192<1>(o, mk_desc(ad + wg * 512 + kk * 2, 16, 1024, 1), mk_desc(ad + 1024 + kk * 128, 8192, 1024, 1), acc || kk != 0);
        };
        auto convert = [&](int i0, int i1) {
          sched_fence(keep, never);
#pragma unroll
          for (int i = i0; i < i1; i++) q[i] = pack_bf16(o[2 * i] * kScaleLog2, o[2 * i + 1] * kScaleLog2);
          sched_fence(keep, never);
        };
        auto kend = [&](int bi, int k) {
          wg_commit();
          drain(k < 8 ? (QDRAIN >> (4 * k)) & 7 : 7);
          probe1();
          wg_wait<0>();
          release(bi);
        };
        if (type == OP_O) {
          float c[80];
          const int nk = 3 * ((op >> 2) & 63), ro = (op >> 8) & 63;
          uint4* part = ptr_add(g_part, (ro * 2 + rank) * SZ_PARK + img0 * 16);
          int prev = 0;
          auto hand_over = [&](float (&c)[80], uint4* dst) {
            fence_regs(c);
#pragma unroll
            for (int i = 0; i < 48; i++) q[i] = i < 8 ? 0 : pack_bf16(c[2 * i - 16], c[2 * i - 15]);
            pend = dst;
          };
          auto mma2 = [&](float (&c)[80], uint32_t da, uint32_t db, int acc) {
            wgmma_ss_n160<1>(c, mk_desc(da, 16, 512, 2), mk_desc(db, 2048, 512, 2), acc);
            wgmma_ss_n160<1>(c, mk_desc(da + 2, 16, 512, 2), mk_desc(db + 64, 2048, 512, 2), 1);
          };
          auto kstep = [&](float (&c)[80], int acc, auto hook, uint32_t bytes = SZ_O) {
            uint32_t ad;
            const int bi = take(rdy0, bytes, ad);
            const uint32_t da = ad + wg * 256, db = ad + 1024;
            wg_fence();
            mma2(c, da, db, acc);
            wg_commit();
            if (acc) { wg_wait<1>(); mbar_arrive_cluster_if(lane < 2 && (acc == 1 || wg == 0), empty_rem + 8 * prev); }
            mma2(c, da + 512, db + 640, 1);
            wg_commit();
            prev = bi;
            hook();
            probe1();
            wg_wait<1>();
          };
          if (op & C_WIDE) {
            float d[80];
            auto wstep = [&](int acc, auto hook) {
              uint32_t ad;
              const int bi = take(rdy0, SZ_W, ad);
              const uint32_t da = ad + wg * 256, db = ad + 1024;
              wg_fence();
              mma2(d, da, db, acc);
              mma2(d, da + 512, db + 640, 1);
              wg_commit();
              if (acc) { wg_wait<1>(); release(prev); }
              mma2(c, da, db + 1280, acc);
              mma2(c, da + 512, db + 1920, 1);
              wg_commit();
              prev = bi;
              hook();
              probe1();
              wg_wait<1>();
            };
            wstep(0, [&]() { drain(0); drain(1); });
#pragma unroll 1
            for (int k = 2; k < 6; k += 2) wstep(1, [&]() { drain(k); drain(k + 1); });
#pragma unroll 1
            for (int k = 3 + 3 * TAIL; k < nk; k++) {
              wstep(1, []() {});
            }
#pragma unroll 1
            for (int k = 0; k < 3 * TAIL; k++) kstep(d, 1, []() {});
            nop = prog[pc + 1];
            spol = make_policy(!(nop & C_SOON));
            kstep(c, 1, [&]() { hand_over(d, part - 6144); });
#pragma unroll 1
            for (int k = 1; k < 3 * TAIL; k++) kstep(c, 1, [&]() { slab(TAIL == 2 ? k : (0x50403201 >> (4 * k - 4)) & 7, 1); });
            if ((nop & 3) == OP_Q) {
              op = nop;
              enter();
              pc++;
              pend_any = true;
              bi0 = take(rdy0, SZ_Q, ad0);
              undefine(o);
              wg_fence();
              mma4(ad0, 0);
              wg_commit();
              wg_wait<1>();
              release(prev);
              hand_over(c, part);
              probe1();
              wg_wait<0>();
              release(bi0);
              fence_regs(o);
              goto next_head;
            }
            wg_wait<0>();
            release(prev);
            hand_over(c, part);
            continue;
          }
          kstep(c, 0, [&]() { drain(0); });
#pragma unroll 1
          for (int k = 1; k < 6; k++) kstep(c, 1, [&]() { drain(k); });
#pragma unroll 1
          for (int k = 11; k < nk; k++) kstep(c, 1, []() {});
          uint32_t t[8], stage[3];
          float u[80];
          auto unpack = [&](int j) {
#pragma unroll
            for (int i = 0; i < 8; i++) {
              u[16 * j + 2 * i] = __uint_as_float(t[i] << 16); u[16 * j + 2 * i + 1] = __uint_as_float(t[i] & 0xffff0000u);
              asm volatile("" : "+f"(u[16 * j + 2 * i]), "+f"(u[16 * j + 2 * i + 1]));
            }
          };
#pragma unroll
          for (int i = 0; i < 8; i++) t[i] = 0;
          const uint32_t bytes = (op & C_LD) ? SZ_OL : SZ_O;
#pragma unroll
          for (int j = 0; j < 5; j++) {
            if (j == 5 - SKEW && wg == 1) {
              wg_wait<0>();
              release(prev);
              bar_sync(1, 256);
            }
            kstep(c, j == 5 - SKEW ? 2 : 1, [&]() {
              if (SKEW && j == 4) asm volatile("{\n.reg .pred p;\nsetp.eq.u32 p, %0, 0;\n@p bar.arrive 1, 256;\n}\n" ::"r"(wg) : "memory");
              if (j) unpack(j - 1);
              lds2_if(op & C_LD, sbase + (cur - ring16 + img0) * 16 - 8192, t);
              if (j >= 1 && j <= 3) stage[j - 1] = sbase + (cur - ring16) * 16 - bytes + wid * 1024;
            }, bytes);
          }
          unpack(4);
          sched_fence(keep, never);
          wg_wait<0>();
          fence_regs(c);
          release(prev);
          asm volatile("barrier.cluster.arrive.relaxed;" ::: "memory");
#pragma unroll
          for (int i = 0; i < 10; i++) {
            const int v = (i & 1) * 2 + (lane >> 4);
            const uint32_t sa = stage[i >> 2] + (i & 2) * 4096;
            stsm4(sa + (lane & 15) * 64 + ((v ^ ((lane >> 1) & 3)) << 4), pack_bf16(c[8 * i] + u[8 * i], c[8 * i + 1] + u[8 * i + 1]),
                  pack_bf16(c[8 * i + 2] + u[8 * i + 2], c[8 * i + 3] + u[8 * i + 3]), pack_bf16(c[8 * i + 4] + u[8 * i + 4], c[8 * i + 5] + u[8 * i + 5]),
                  pack_bf16(c[8 * i + 6] + u[8 * i + 6], c[8 * i + 7] + u[8 * i + 7]));
          }
          asm volatile("fence.proxy.async.shared::cta;" ::: "memory");
          __syncwarp();
          if (elect()) {
#pragma unroll
            for (int i = 0; i < 5; i++)
              tma3d_store(&P.out, stage[i >> 1] + (i & 1) * 8192, 0, ((ro >> 2) & 7) * kSq + rank * 128 + wid * 16, (ro >> 5) * 20 + (ro & 3) * 5 + i);
            asm volatile("cp.async.bulk.commit_group;\ncp.async.bulk.wait_group.read 0;" ::: "memory");
          }
          __syncwarp();
          break;
        }
        bi0 = take(rdy0, SZ_Q, ad0);
        undefine(o);
        wg_fence();
        mma4(ad0, 0);
        kend(bi0, 0);
        fence_regs(o);
      next_head:
        {
#pragma unroll 1
          for (int k = 1; k < ((op & F_PARK) ? 10 : 8); k++) {
            uint32_t ad;
            const int bi = take(rdy0, SZ_Q, ad);
            wg_fence();
            mma4(ad, 1);
            kend(bi, k);
          }
          if (op & F_PARK) {
            fence_regs(o);
            convert(0, 48);
            pend = ptr_add(g_t, (((op >> 2) & 511) * 2 + rank) * SZ_PARK + img0 * 16);
            continue;
          }
          uint32_t a8, a9, ak0, ak1;
          const int b8 = take(rdy0, SZ_Q, a8), b9 = take(false, SZ_Q, a9);
          wg_fence();
          mma4(a8, 1);
          wg_commit();
          mma4(a9, 1);
          wg_commit();
          pc++;
          wg_wait<1>();
          release(b8);
          const int sk0 = take(false, SZ_KV, ak0);
          wg_wait<0>();
          fence_regs(o);
          release(b9);
          float s0[32];
          convert(0, 32);
          wg_fence();
          qk(s0, ak0, 0, 4);
          convert(32, 48);
          wg_fence();
          qk(s0, ak0, 4, 12);
          sk1 = take(false, SZ_KV, ak1);
          probe1();
          wg_wait<0>();
          first(s0, sk0, [&](int i) {
            if (i == 0) return;
            sched_fence(keep, never);
            wg_fence();
            if (i == 1) qk(s, ak1, 0, 4);
            if (i == 2) qk(s, ak1, 4, 8);
            if (i == 3) qk(s, ak1, 8, 12);
            sched_fence(keep, never);
          });
        }
        for (;;) {
          {
            uint32_t av;
            const int sv = take(rdy0, SZ_KV, av);
            undefine(o);
            wg_fence();
            pv(pa, av, 0);
            finish(pb, sk1, sv);
          }
          nop = prog[pc + 1];
#pragma unroll 1
          for (int jj = 0; jj < 7; jj++) {
            step(pb, pa);
            step(pa, pb);
          }
          float i0, i1;
          auto last = [&]() {
            uint32_t av;
            const int sv = take(rdy0, SZ_KV, av);
            wg_fence();
            pv(pb, av, 1);
            sched_fence(keep, never);
            probe1();
            l0 += __shfl_xor_sync(0xffffffffu, l0, 1); l1 += __shfl_xor_sync(0xffffffffu, l1, 1);
            l0 += __shfl_xor_sync(0xffffffffu, l0, 2); l1 += __shfl_xor_sync(0xffffffffu, l1, 2);
            i0 = rcp(l0); i1 = rcp(l1);
            pend = ptr_add(g_t, (((op >> 2) & 511) * 2 + rank) * SZ_PARK + img0 * 16);
            return sv;
          };
          auto normalise = [&](uint32_t (&d)[48], auto mid) {
#pragma unroll
            for (int i = 0; i < 24; i++) {
              d[8 * (i >> 2) + (i & 3)] = pack_bf16(o[4 * i] * i0, o[4 * i + 1] * i0);
              d[8 * (i >> 2) + (i & 3) + 4] = pack_bf16(o[4 * i + 2] * i1, o[4 * i + 3] * i1);
              if ((i & 3) == 3 && i != 23) { sched_fence(keep, never); mid(i >> 2); }
            }
          };
          const int sv = last();
          if ((nop & 3) != OP_A) {
            op = nop;
            enter();
            pend_any = true;
            spol = make_policy(!(op & C_SOON));
            bi0 = take(rdy0 || (nop & 3) != OP_Q, SZ_Q, ad0);
            sched_fence(keep, never);
            wg_wait<0>();
            fence_regs(o);
            release(sv);
            normalise(q, [](int) {});
            undefine(o);
            if ((nop & 3) != OP_Q) break;
            sched_fence(keep, never);
            wg_fence();
            mma4(ad0, 0);
            pc++;
            kend(bi0, 0);
            fence_regs(o);
            goto next_head;
          }
          const int sk0 = unpark();
          wg_wait<1>();
          fence_regs(o);
          release(sv);
          uint32_t t[48];
          spol = make_policy(!(nop & C_SOON));
          auto st = [&](int i) {
            stg2_if(true, pend + i * 512, t[8 * i], t[8 * i + 1], t[8 * i + 2], t[8 * i + 3], t[8 * i + 4], t[8 * i + 5], t[8 * i + 6], t[8 * i + 7], spol);
          };
          normalise(t, [&](int i) { if (!(i & 1)) st(i >> 1); });
          wg_wait<0>();
          first(s, sk0, [&](int i) { if (i < 3) { sched_fence(keep, never); st(3 + i); } });
          __syncwarp();
          mbar_arrive_if(lane == 0, odone0 + 8 * pc);
          pc++;
          op = nop;
          uint32_t ak1;
          sk1 = take(rdy0, SZ_KV, ak1);
          rdy0 = rdy1;
          wg_fence();
          qk(s, ak1);
        }
      }
    }
    if (never) g_flag[0] = keep;
    asm volatile("barrier.cluster.wait;" ::: "memory");
  } else {
    asm volatile("setmaxnreg.dec.sync.aligned.u32 24;");
    const uint32_t* prog = P.prog[role].p;
    unsigned int* flag = g_flag + rank;
    if (wid == 8) {
      Cursor tail{0, 0};
      int head = 0, sh = 0;
      uint32_t cur = 0, used = 0;
      uint64_t fifo = 0;
      uint32_t dst, bar, ev = ev0, done = 0;
      uint64_t pol;
      asm volatile("createpolicy.fractional.L2::evict_first.b64 %0, 1.0;" : "=l"(pol));
      auto retire = [&]() {
        mbar_wait(empty0 + 8 * tail.bi, tail.ph);
        tail.next();
        used -= (uint32_t)fifo & 31;
        fifo >>= 5;
        sh -= 5;
        asm volatile("st.volatile.shared.u32 [%0], %1;" ::"r"(progress), "r"(++done) : "memory");
      };
      auto acquire = [&](uint32_t bytes) {
        uint32_t fp = bytes >> 12;
        if (cur + fp > (RING >> 12)) { fp += (RING >> 12) - cur; cur = 0; }
        used += fp;
        while (used > (RING >> 12) || sh == 5 * NBAR) retire();
        fifo |= (uint64_t)fp << sh;
        sh += 5;
        dst = sbase + (cur << 12);
        bar = full0 + 8 * head;
        cur += bytes >> 12;
        if (++head == NBAR) head = 0;
      };
      auto gate = [&]() {
        mbar_wait(ev, 0);
        ev += 8;
        asm volatile("fence.proxy.async.global;" ::: "memory");
      };
      for (int pc = 0;; pc++) {
        const uint32_t op = prog[pc];
        const int type = op & 3, blk = (op >> 10) & 1;
        if (type == OP_END) break;
        if (type == OP_Q) {
#pragma unroll 1
          for (int k = 0; k < 10; k++) {
            if (k == 9 && (op & P_GATE)) gate();
            acquire(SZ_Q);
            if ((pc > 0 || k >= EARLY) && elect()) {
              mbar_expect(bar, SZ_Q);
              tma2d(dst, &P.x[blk], bar, 64 * k, ((op >> 7) & 7) * kSq + rank * 128);
              if ((k & 1) == rank) tma3d_mc(dst + 16384, &P.wq[blk], bar, 0, 64 * k, 3 * ((op >> 2) & 31));
            }
          }
        } else if (type == OP_A) {
          const int row0 = ((op >> 2) & 255) * kSk;
          const CUtensorMap* kv_map = rank ? &P.v[blk] : &P.k[blk];
          if (op & F_PARK) {
            gate();
            acquire(SZ_PARK);
            if (elect()) {
              mbar_expect(bar, SZ_PARK);
              bulk_load_hint(dst, &g_t[((op >> 20) * 2 + rank) * 3072], SZ_PARK, bar, make_policy(P.dbg & 4));
            }
          }
#pragma unroll 1
          for (int t = 0; t < 32; t++) {
            const int isv = t == 31 ? 1 : (t == 0 ? 0 : (~t & 1));
            const int j = isv ? (t - 1) >> 1 : (t + 1) >> 1;
            if (t == 31 && (op & P_GATE)) gate();
            acquire(SZ_KV);
            if (elect()) {
              mbar_expect(bar, SZ_KV);
              if (isv == (int)rank) tma4d_mc_hint(dst, kv_map, bar, row0 / 8 + 8 * j, pol);
            }
          }
        } else {
          const int n = (op >> 13) & 63, nw = (op & P_WIDE) ? n - TAIL : 0;
          const uint64_t pol_o = make_policy(P.dbg & (nw ? 1 : 2));
          const uint4* part = &g_part[((((op >> 5) & 60) + ((op >> 19) & 3)) * 2 + rank) * 3072 + 512];
#pragma unroll 1
          for (int i = 0; i < n + (nw ? TAIL : 0); i++) {
            const int id = ((op >> 2) & 511) + (i < n ? i : i - TAIL), col = 5 * (((op >> 19) & 3) + (i >= n));
            const uint4* src = &g_t[(P.slot[id] * 2 + rank) * 3072];
            if ((op & P_LD) && i == ((op & P_PRE) ? 0 : n - 2)) gate();
            if (i < n) gate();
#pragma unroll 1
            for (int k = 0; k < 3; k++) {
              const uint32_t j = (op & P_LD) ? 3 * (i - n) + k + 5 : 5, bytes = i < nw ? SZ_W : j < 5 ? SZ_OL : SZ_O;
              acquire(bytes);
              if (elect()) {
                mbar_expect(bar, bytes);
                tma5d_mc(dst + 16384 + rank * 10240, &P.wo[blk], bar, 24 * (id & 31) + 8 * k + 4 * rank, col);
                bulk_load_hint(dst, src + k * 1024, 16384, bar, pol_o);
                if (i < nw) tma5d_mc(dst + SZ_O + rank * 10240, &P.wo[blk], bar, 24 * (id & 31) + 8 * k + 4 * rank, col + 5);
                if (j < 5) bulk_load_hint(dst + SZ_O, part + j * 512, 8192, bar, pol);
                if ((op & P_PRE) && 3 * i + k < 10)
                  asm volatile("cp.async.bulk.prefetch.L2.global [%0], 4096;" ::"l"(part + (3 * i + k) * 256) : "memory");
              }
            }
          }
        }
      }
#pragma unroll 1
      while (sh) retire();
    } else if (threadIdx.x == 288) {
      for (int pc = 0;; pc++) {
        const uint32_t op = prog[pc];
        const int type = op & 3;
        if (type == OP_END) break;
        if (type == OP_Q ? !(op & F_PARK) : type == OP_O && !(op & P_ST)) continue;
        const int id = type == OP_A ? (op >> 2) & 511 : type == OP_Q ? N_TILE + ((op >> 13) & 127) : ID_PART + ((op >> 5) & 60) + ((op >> 19) & 3);
        const uint32_t v = type == OP_O ? 1 : P.info[id] & 7;
        mbar_wait_slow<PUBNS>(odone0 + 8 * pc, 0);
        flag_set(flag + 2 * id, v);
        if (type == OP_O && (op & P_WIDE)) flag_set(flag + 2 * id + 2, v);
      }
    } else if (wid == 10) {
      int i = threadIdx.x & 31;
      uint32_t e = i < 8 ? P.prog[role].ev[i] : 0;
      for (uint32_t n = 0; __any_sync(0xffffffffu, e); n++) {
        unsigned int* f = ptr_add(flag, 8 * (e & 1023));
        const bool ok = e && flag_peek(f) - 1 < ((e & E_FREE) ? 1 : 7);
        if (ok) {
          mbar_arrive(ev0 + 8 * i);
          if (e & (E_FREE | E_LAST)) flag_dec(f);
          i += 8;
          e = i < MAX_EV ? P.prog[role].ev[i] : 0;
        }
        asm volatile("{\n.reg .pred p;\nsetp.ge.u32 p, %0, 0x400000;\n@p trap;\n}\n" ::"r"(n));
        if (!__any_sync(0xffffffffu, ok)) __nanosleep(WATNS);
      }
    } else if (threadIdx.x == 352) {
      uint32_t items = 0;
      auto read = [&](int id) {
        if (!(P.info[id] & I_NEXT)) return;
        wait_progress(progress, items);
        flag_dec(flag + 2 * id);
      };
      for (int pc = 0;; pc++) {
        const uint32_t op = prog[pc];
        const int type = op & 3;
        if (type == OP_END) break;
        if (type == OP_O) {
          const int n = (op >> 13) & 63;
#pragma unroll 1
          for (int i = 0; i < n; i++) {
            items += (op & P_WIDE) && i == n - TAIL ? 3 * TAIL + 3 : 3;
            read(((op >> 2) & 511) + i);
          }
        } else if (type == OP_A) {
          if (op & F_PARK) { items++; read(N_TILE + ((op >> 13) & 127)); }
          items += 32;
        } else {
          items += 10;
        }
      }
    }
    __syncwarp();
    asm volatile("barrier.cluster.arrive.relaxed;\nbarrier.cluster.wait;" ::: "memory");
  }
}

typedef CUresult (*EncodeFn)(CUtensorMap*, CUtensorMapDataType, cuuint32_t, void*, const cuuint64_t*, const cuuint64_t*,
                             const cuuint32_t*, const cuuint32_t*, CUtensorMapInterleave, CUtensorMapSwizzle,
                             CUtensorMapL2promotion, CUtensorMapFloatOOBfill);

void encode(EncodeFn fn, CUtensorMap* m, const void* ptr, int rank, const cuuint64_t* dims, const cuuint64_t* strides,
            const cuuint32_t* box, CUtensorMapSwizzle swz) {
  const cuuint32_t es[5] = {1, 1, 1, 1, 1};
  CUresult r = fn(m, CU_TENSOR_MAP_DATA_TYPE_BFLOAT16, rank, const_cast<void*>(ptr), dims, strides, box, es,
                  CU_TENSOR_MAP_INTERLEAVE_NONE, swz, CU_TENSOR_MAP_L2_PROMOTION_L2_128B, CU_TENSOR_MAP_FLOAT_OOB_FILL_NONE);
  if (r != CUDA_SUCCESS) fprintf(stderr, "cuTensorMapEncodeTiled failed: %d\n", (int)r);
}

struct Op { int type, flags, id, n, quarter, park, item0, items; double t0, t1; };
struct Use { double ready, gate, need, freed; int readers, slot, prev; bool next; };
struct PlanStats { double end, slack, park_slack; int slots, parks; };

bool plan(const char* const* text, int n_pair, int phase, Params& P, PlanStats* stats = nullptr) {
  constexpr double T_Q = 7900, T_A = 24850, T_U = 26300, T_O = 1920, T_RUN = 800, T_WIDE = 1900, AHEAD = 3500, PUBLISH = 1500;
  const double margin = 256.0 * ((P.dbg >> 8) & 255);
  static Op op[N_CL][MAX_OPS];
  static Use use[ID_PART];
  int n_op[N_CL], covered[N_TEAM] = {}, finals[N_TEAM] = {};
  auto hex = [](char c) { return c <= '9' ? c - '0' : c - 'a' + 10; };
  for (int i = 0; i < n_pair; i++)
    for (const char* s = text[i]; *s; s++)
      if (*s == 'J') { if (covered[hex(s[1])]) return false; covered[hex(s[1])] = 10 * (s[2] - '0') + s[3] - '0'; }
  for (int c = 0; c < 2 * n_pair; c++) {
    int n = 0, items = 0;
    double t = 0;
    auto add = [&](int type, int flags, int id, int heads, int quarter, int its, double dt) {
      if (n < MAX_OPS) op[c][n] = {type, flags, id, heads, quarter, 0, items, its, t, t + dt};
      n++; items += its; t += dt;
    };
    for (const char* s = text[c >> 1]; *s; s++) {
      const int tm = hex(s[1]) & 15, nj = covered[tm];
      if (*s == 'N') { add(OP_Q, 0, 0, 0, 0, 10, T_Q); add(OP_A, 0, 0, 0, 0, 32, T_A); }
      if (*s == 'P') add(OP_Q, F_PARK, 0, 0, 0, 10, T_Q);
      if (*s == 'U') { if (n == 0 || n > MAX_OPS || op[c][n - 1].type != OP_A) return false; add(OP_A, F_PARK, 0, 0, 0, 33, T_U); }
      if (*s == 'J') { if (nj <= TAIL || nj > kH - 4) return false; add(OP_O, P_WIDE | P_ST, tm * kH, nj, 2 * (c & 1), 3 * (nj + TAIL), 2 * T_O * nj + T_WIDE); }
      if (*s == 'F') { if (s[2]) return false; add(OP_O, nj ? P_LD : 0, tm * kH + nj, kH - nj, finals[tm]++, 3 * (kH - nj), T_O * (kH - nj) + T_RUN); }
    }
    add(OP_END, 0, 0, 0, 0, 0, 0);
    if (n > MAX_OPS || op[c][0].type != OP_Q) return false;
    n_op[c] = n - 1;
  }
  for (int t = 0; t < N_TEAM; t++) if (finals[t] != 4) return false;
  for (int i = 0; i < ID_PART; i++) use[i] = {0, 0, 1e18, 0, 0, 0, 0, false};
  struct Ref { double t; Op* o; int id; };
  static Ref att[N_TILE + 1], dem[N_TILE], prk[MAX_PARK + 1], unp[MAX_PARK + 1], wr[ID_PART];
  int n_att = 0, n_prk = 0, n_unp = 0;
  auto ready = [&](const Op* o) {
    const int nt = o[1].type;
    return o->t1 + (nt == OP_Q ? 6100 : nt == OP_O ? 3900 : 1500) + PUBLISH;
  };
  for (int c = 0; c < 2 * n_pair; c++)
    for (Op* o = op[c]; o->type != OP_END; o++) {
      if (o->type == OP_A) { att[n_att] = {ready(o), o, 0}; if (++n_att > N_TILE) return false; }
      if (o->type == OP_A && o->flags) { unp[n_unp] = {o->t0 - AHEAD, o, 0}; if (++n_unp > MAX_PARK) return false; }
      if (o->type == OP_Q && o->flags) { prk[n_prk] = {ready(o), o, 0}; if (++n_prk > MAX_PARK) return false; }
      for (int i = 0; o->type == OP_O && i < o->n; i++) {
        const int nw = (o->flags & P_WIDE) ? o->n - TAIL : 0;
        Use& u = use[o->id + i];
        const double t = o->t0 + T_O * (i + (i < nw ? i : nw));
        if (t - AHEAD < u.need) u.need = t - AHEAD;
        const double f = t + T_O * (i < nw ? 2 : nw ? 1 + TAIL : 1) + PUBLISH;
        if (f > u.freed) u.freed = f;
        u.readers++;
      }
    }
  if (n_att != N_TILE || n_prk != n_unp) return false;
  auto sort = [](Ref* r, int n) {
    for (int i = 1; i < n; i++)
      for (int j = i; j > 0 && r[j].t < r[j - 1].t; j--) { Ref x = r[j]; r[j] = r[j - 1]; r[j - 1] = x; }
  };
  for (int i = 0; i < N_TILE; i++) { const int id = (i & 15) * kH + (i >> 4); dem[i] = {use[id].need, nullptr, id}; }
  sort(att, n_att); sort(dem, N_TILE); sort(prk, n_prk); sort(unp, n_unp);
  PlanStats st = {0, 1e18, 1e18, 0, n_prk};
  int n_wr = 0;
  for (int i = 0; i < N_TILE; i++) {
    Op* o = att[i].o;
    o->id = dem[i].id;
    if (!o->flags) o[-1].id = o->id;
    if (dem[i].t - att[i].t < st.slack) st.slack = dem[i].t - att[i].t;
    wr[n_wr++] = {o->t1 - 2 * AHEAD, o, o->id};
  }
  for (int i = 0; i < n_prk; i++) {
    prk[i].o->id = unp[i].o->id;
    prk[i].o->park = unp[i].o->park = i;
    use[N_TILE + i].freed = unp[i].o->t0 + 2 * PUBLISH;
    use[N_TILE + i].readers = 1;
    if (unp[i].t - prk[i].t < st.park_slack) st.park_slack = unp[i].t - prk[i].t;
    wr[n_wr++] = {prk[i].o->t1 - 2 * AHEAD, prk[i].o, N_TILE + i};
  }
  for (int c = 0; c < 2 * n_pair; c++)
    for (int d = 0; d < 2 * n_pair; d++)
      for (Op *f = &op[c][n_op[c] - 1], *o = op[d]; f->type == OP_O && o->type != OP_END; o++)
        if (o->type == OP_O && (o->flags & P_ST) && o->id / kH == f->id / kH) {
          if (f->t0 - o->t1 > 4096.0 * ((P.dbg >> 16) & 255)) f->flags |= P_PRE;
          const double slack = f->t0 + ((f->flags & P_PRE) ? 0 : (f->n - 2) * T_O) - AHEAD - ready(o);
          if (slack < st.park_slack) st.park_slack = slack;
        }
  sort(wr, n_wr);
  int holder[N_TILE];
  for (int i = 0; i < n_wr; i++) {
    int best = -1;
    for (int sl = 0; sl < st.slots; sl++)
      if (use[holder[sl]].freed + margin <= wr[i].t && (best < 0 || (use[holder[sl]].freed < use[holder[best]].freed) != ((P.dbg & 32) != 0))) best = sl;
    Use& u = use[wr[i].id];
    if (best >= 0) { u.prev = holder[best]; use[u.prev].next = true; wr[i].o->flags |= P_GATE; }
    else if (st.slots == N_TILE) return false;
    else best = st.slots++;
    u.slot = best;
    holder[best] = wr[i].id;
  }
  {
    int pos[N_CL] = {}, flag[ID_PART + 4 * N_TEAM] = {}, seen[ID_PART] = {};
    for (bool moved = true; moved;) {
      moved = false;
      for (int c = 0; c < 2 * n_pair; c++) {
        const int total = op[c][n_op[c]].item0;
        for (; pos[c] < total + NBAR; pos[c]++, moved = true) {
          bool ok = true;
          for (const Op* o = op[c]; o->type != OP_END; o++) {
            const int k = pos[c] - o->item0, own = o->type == OP_A ? o->id : N_TILE + o->park;
            if (k < 0 || k >= o->items) continue;
            if (o->type == OP_O) ok = (k >= 3 * o->n || flag[o->id + k / 3]) && (k != ((o->flags & P_PRE) ? 0 : 3 * o->n - 6) || !(o->flags & P_LD) || flag[ID_PART + o->id / kH * 4 + o->quarter]);
            else if (k == o->items - 1 && (o->flags & P_GATE)) ok = seen[use[own].prev] == use[use[own].prev].readers;
            else if (k == 0 && o->type == OP_A && (o->flags & F_PARK)) ok = flag[N_TILE + o->park];
          }
          if (!ok) break;
          for (const Op* o = op[c]; o->type != OP_END; o++) {
            if (pos[c] == o->item0 + o->items + (o[1].type == OP_Q ? 7 : 5)) {
              if (o->type == OP_A) flag[o->id] = 1;
              if (o->type == OP_Q && (o->flags & F_PARK)) flag[N_TILE + o->park] = 1;
              if (o->type == OP_O && (o->flags & P_ST)) flag[ID_PART + o->id / kH * 4 + o->quarter] = flag[ID_PART + o->id / kH * 4 + o->quarter + 1] = 1;
            }
            const int k = pos[c] - NBAR - o->item0, nw = (o->flags & P_WIDE) ? o->n - TAIL : o->n;
            if (k == 0 && o->type == OP_A && (o->flags & F_PARK)) seen[N_TILE + o->park]++;
            if (o->type == OP_O && k >= 0 && k % 3 == 2 && (k / 3 < nw || (k / 3 >= o->n && k / 3 < 2 * o->n - nw))) seen[o->id + (k / 3 < nw ? k / 3 : k / 3 - TAIL)]++;
          }
        }
      }
    }
    for (int c = 0; c < 2 * n_pair; c++) if (pos[c] < op[c][n_op[c]].item0 + NBAR) return false;
  }
  for (int c = 0; c < 2 * n_pair; c++) {
    uint32_t items = 0, cur = 0, pend = 0;
    int n = 0, ev = 0;
    auto item = [&](uint32_t bytes, int count) {
      for (int i = 0; i < count; i++) { if (cur + bytes > RING) cur = 0; cur += bytes; items++; }
    };
    auto event = [&](uint32_t e) { if (ev < MAX_EV) P.prog[c].ev[ev] = e | E_ON; ev++; };
    for (const Op* o = op[c];; o++) {
      if (o->type != OP_END && phase && (o->type == OP_O) != (phase == 2)) continue;
      uint32_t cw = o->type | (items % NBAR) << 15 | ((items / NBAR) & 1) << 19 | (cur >> 12) << 20 | pend, pw = o->type | o->id << 2 | o->flags;
      const int ps = use[N_TILE + o->park].slot;
      pend = 0;
      if (o->type == OP_O) {
        const bool wide = o->flags & P_WIDE;
        cw |= o->n << 2 | (o->id / kH * 4 + o->quarter + wide) << 8 | (wide ? C_WIDE : 0) | ((o->flags & P_LD) ? C_LD : 0);
        pw |= o->n << 13 | o->quarter << 19;
        if (wide) item(SZ_W, 3 * (o->n - TAIL));
        for (int k = 0; k < (wide ? 6 * TAIL : 3 * o->n); k++) item((o->flags & P_LD) && k >= 3 * o->n - 5 ? SZ_OL : SZ_O, 1);
        if (wide) pend = C_PEND | ((P.dbg & 8) ? C_SOON : 0);
        for (int i = 0; i < o->n; i++) {
          if (i == ((o->flags & P_PRE) ? 0 : o->n - 2) && (o->flags & P_LD)) event((ID_PART + o->id / kH * 4 + o->quarter) | E_LAST);
          event((o->id + i) | (use[o->id + i].next ? 0 : E_LAST));
        }
      } else if (o->type != OP_END) {
        const bool parks = o->type == OP_Q && (o->flags & F_PARK);
        cw |= (parks ? ps : use[o->id].slot) << 2 | (o->flags & F_PARK);
        if (o->flags & F_PARK) pw |= o->park << 13 | ps << 20;
        if (o->type == OP_Q) item(SZ_Q, 10);
        else { if (o->flags & F_PARK) { item(SZ_PARK, 1); event((N_TILE + o->park) | (use[N_TILE + o->park].next ? 0 : E_LAST)); } item(SZ_KV, 32); }
        if (parks || o->type == OP_A) pend = C_PEND | ((P.dbg & 16) ? 0 : C_SOON);
        if (o->flags & P_GATE) event(use[parks ? N_TILE + o->park : o->id].prev | E_FREE);
      }
      P.prog[c].c[n] = cw; P.prog[c].p[n++] = pw;
      if (o->type == OP_END) { if (o->t0 > st.end) st.end = o->t0; break; }
    }
    if (ev > MAX_EV) return false;
    while (ev < MAX_EV) P.prog[c].ev[ev++] = 0;
    while (n < MAX_OPS) { P.prog[c].c[n] = OP_END; P.prog[c].p[n++] = OP_END; }
    P.first[c] = (uint16_t)(P.prog[c].p[0] & 2047);
  }
  for (int i = 0; i < ID_PART; i++) {
    if (i < N_TILE) P.slot[i] = use[i].slot;
    P.info[i] = (use[i].readers + use[i].next) | (use[i].next ? I_NEXT : 0);
  }
  if (stats) *stats = st;
  return true;
}

const char* const kPrograms[N_CL / 2] = {
  "NNNNNNNNNF0", "NNNNNJa21NFc", "PNJ226NNNNFc", "PNNJ325NNNNF9", "PNJ421NNNNNF5", "PNJ517NNNNNNF2",
  "PNNJ617NNNNNFb", "NUNJ718NJ925F8", "NUNUNNJe26Fd", "PNNNNNNNNNF3", "PNJ121NNNNNF6", "NUNNNJb26NF8",
  "NUNNNNJc12NNFe", "NNNNNNNNNFa", "NUNNNJf18NNF1", "NUNNNJ820NNF3", "NNUNNNNNNF7", "PNNNNNNNNNFe",
  "PNNNNNNNNNFb", "PNNNNNNNNNF9", "NNNNNNNNNF0", "PNNNNNNNNNF2", "NNUNNNNNNFf", "NNUNNNNNNFf",
  "NNUNNNNNNF6", "NUNNNJd16NNFd", "NNNNNNNNNF4", "PNJ021NNNNNF5", "NNNNNNNNNFa", "NNNNNNNNNF1",
  "NNUNNNNNNF7", "NNNNNNNNNF4", "PNNNNNNNNN",
};

const char* const* bench_programs() {
  return kPrograms;
}

}

extern "C" void kernel_launch(void* const* d_in, const int* in_sizes, int n_in, void* d_out, int out_size) {
  (void)in_sizes; (void)n_in; (void)out_size;
  static EncodeFn fn = nullptr;
  static int n_clusters = 0;
  if (!fn) {
    cudaDriverEntryPointQueryResult qr;
    void* f = nullptr;
    cudaGetDriverEntryPoint("cuTensorMapEncodeTiled", &f, cudaEnableDefault, &qr);
    fn = (EncodeFn)f;
    cudaFuncSetAttribute(fused_kernel, cudaFuncAttributeMaxDynamicSharedMemorySize, SMEM_BYTES);
    cudaLaunchConfig_t cfg = {};
    cfg.gridDim = dim3(132); cfg.blockDim = dim3(384); cfg.dynamicSmemBytes = SMEM_BYTES;
    cudaLaunchAttribute at[1];
    at[0].id = cudaLaunchAttributeClusterDimension; at[0].val.clusterDim.x = 2; at[0].val.clusterDim.y = 1; at[0].val.clusterDim.z = 1;
    cfg.attrs = at; cfg.numAttrs = 1;
    if (cudaOccupancyMaxActiveClusters(&n_clusters, fused_kernel, &cfg) != cudaSuccess || n_clusters < 1) n_clusters = 1;
    (void)cudaGetLastError();
  }
  static Params P;
  const CUtensorMapSwizzle S128 = CU_TENSOR_MAP_SWIZZLE_128B, S64 = CU_TENSOR_MAP_SWIZZLE_64B;
  for (int blk = 0; blk < 2; blk++) {
    void* const* in = d_in + 5 * blk;
    { const cuuint64_t d[] = {kD, kB * kSq}, s[] = {kD * 2}; const cuuint32_t b[] = {64, 128};
      encode(fn, &P.x[blk], in[0], 2, d, s, b, S128); }
    { const cuuint64_t d[] = {64, 8, 3, (cuuint64_t)kB * kH * kSk / 8}, s[] = {kDh * 2, 128, 8 * kDh * 2}; const cuuint32_t b[] = {64, 8, 3, 8};
      encode(fn, &P.k[blk], in[1], 4, d, s, b, S128);
      encode(fn, &P.v[blk], in[2], 4, d, s, b, S128); }
    { const cuuint64_t d[] = {64, kD, kHD / 64}, s[] = {kHD * 2, 128}; const cuuint32_t b[] = {64, 64, 3};
      encode(fn, &P.wq[blk], in[3], 3, d, s, b, S128); }
    { const cuuint64_t d[] = {32, 2, kHD / 8, 4, kD / 32}, s[] = {kD * 2, 8 * kD * 2, 2 * kD * 2, 64}; const cuuint32_t b[] = {32, 2, 4, 4, 5};
      encode(fn, &P.wo[blk], in[4], 5, d, s, b, S64); }
  }
  { const cuuint64_t d[] = {32, kB * kSq, 2 * kD / 32}, s[] = {2 * kD * 2, 64}; const cuuint32_t b[] = {32, 16, 1};
    encode(fn, &P.out, d_out, 3, d, s, b, S64); }

  P.dbg = DBG_DEFAULT;
  if (n_clusters >= N_CL && plan(bench_programs(), N_CL / 2, 0, P)) {
    fused_kernel<<<2 * N_CL, 384, SMEM_BYTES>>>(P);
  } else {
    char buf[2 * N_TEAM][16];
    const char* text[2 * N_TEAM];
    for (int i = 0; i < 2 * N_TEAM; i++) { snprintf(buf[i], sizeof(buf[i]), "NNNNNNNNF%x", i / 2); text[i] = buf[i]; }
    for (int phase = 1; phase <= 2; phase++) {
      plan(text, 2 * N_TEAM, phase, P);
      fused_kernel<<<8 * N_TEAM, 384, SMEM_BYTES>>>(P);
    }
  }
}
```

```cpp
#include <cuda_runtime.h>
#include <cuda_bf16.h>
#include <cuda.h>
#include <stdint.h>
#include <stdio.h>

namespace {

constexpr int kB = 8, kSq = 256, kD = 640, kH = 32, kSk = 1024, kDh = 192;
constexpr int kHD = kH * kDh;
constexpr uint32_t RING = 224 * 1024;
constexpr uint32_t SZ_KV = 24576;
constexpr uint32_t SZ_Q = 16384 + 24576;
constexpr uint32_t SZ_O = 16384 + 20480;
constexpr uint32_t SZ_W = 16384 + 40960;
constexpr uint32_t SZ_PARK = 49152;
constexpr uint32_t SZ_OL = SZ_O + 8192;
constexpr int NBAR = 10;
constexpr int EARLY = 3;
#define XTAIL 2
constexpr int TAIL = XTAIL;
constexpr uint32_t KV_CH = 64, KV_SBO = 3072;
constexpr int SMEM_BYTES = RING + 1024 + 1024;
constexpr int N_TEAM = 16, N_CL = 66, MAX_OPS = 24, MAX_EV = 80, N_TILE = N_TEAM * kH, MAX_PARK = 128, ID_PART = N_TILE + MAX_PARK;
enum : uint32_t { OP_END = 0, OP_Q = 1, OP_A = 2, OP_O = 3, F_PARK = 1 << 11,
                  C_WIDE = 1 << 14, C_PEND = 1 << 26, C_SOON = 1 << 28, C_LD = 1 << 29,
                  P_GATE = 1 << 12, P_WIDE = 1 << 11, P_LD = 1 << 12, P_ST = 1 << 21, P_PRE = 1 << 22, I_NEXT = 8, E_ON = 1 << 15, E_FREE = 1 << 14, E_LAST = 1 << 13 };

#define QDRAIN 0x54732710u
#define SKEW 3
#define PUBNS 100
#define WATNS 100
constexpr uint32_t DBG_DEFAULT = 0x101833;

struct alignas(64) Params {
  uint16_t first[96];
  CUtensorMap x[2], wq[2], k[2], v[2], wo[2], out;
  struct {
    uint32_t c[MAX_OPS];
    uint32_t p[MAX_OPS];
    uint16_t ev[MAX_EV];
  } prog[N_CL];
  uint16_t slot[N_TILE];
  uint8_t info[ID_PART];
  uint32_t dbg;
};

__device__ uint4 g_t[N_TILE * 2 * 3072];
__device__ uint4 g_part[N_TEAM * 4 * 2 * 3072];
__device__ unsigned int g_flag[(ID_PART + N_TEAM * 4) * 2];

template <int TB, int TA = 0>
__device__ __forceinline__ void wgmma_ss_n64(float (&d)[32], uint64_t da, uint64_t db, int scale_d) {
  asm volatile("{\n.reg .pred p;\nsetp.ne.b32 p, %34, 0;\n"
    "wgmma.mma_async.sync.aligned.m64n64k16.f32.bf16.bf16 {%0, %1, %2, %3, %4, %5, %6, %7, %8, %9, %10, %11, %12, %13, %14, %15, %16, %17, %18, %19, %20, %21, %22, %23, %24, %25, %26, %27, %28, %29, %30, %31}, %32, %33, p, 1, 1, %35, %36;\n}\n"
    : "+f"(d[0]), "+f"(d[1]), "+f"(d[2]), "+f"(d[3]), "+f"(d[4]), "+f"(d[5]), "+f"(d[6]), "+f"(d[7]), "+f"(d[8]), "+f"(d[9]), "+f"(d[10]), "+f"(d[11]), "+f"(d[12]), "+f"(d[13]), "+f"(d[14]), "+f"(d[15]), "+f"(d[16]), "+f"(d[17]), "+f"(d[18]), "+f"(d[19]), "+f"(d[20]), "+f"(d[21]), "+f"(d[22]), "+f"(d[23]), "+f"(d[24]), "+f"(d[25]), "+f"(d[26]), "+f"(d[27]), "+f"(d[28]), "+f"(d[29]), "+f"(d[30]), "+f"(d[31])
    : "l"(da), "l"(db), "r"(scale_d), "n"(TA), "n"(TB));
}
template <int TB>
__device__ __forceinline__ void wgmma_rs_n64(float (&d)[32], uint32_t a0, uint32_t a1, uint32_t a2, uint32_t a3, uint64_t db, int scale_d) {
  asm volatile("{\n.reg .pred p;\nsetp.ne.b32 p, %37, 0;\n"
    "wgmma.mma_async.sync.aligned.m64n64k16.f32.bf16.bf16 {%0, %1, %2, %3, %4, %5, %6, %7, %8, %9, %10, %11, %12, %13, %14, %15, %16, %17, %18, %19, %20, %21, %22, %23, %24, %25, %26, %27, %28, %29, %30, %31}, {%32, %33, %34, %35}, %36, p, 1, 1, %38;\n}\n"
    : "+f"(d[0]), "+f"(d[1]), "+f"(d[2]), "+f"(d[3]), "+f"(d[4]), "+f"(d[5]), "+f"(d[6]), "+f"(d[7]), "+f"(d[8]), "+f"(d[9]), "+f"(d[10]), "+f"(d[11]), "+f"(d[12]), "+f"(d[13]), "+f"(d[14]), "+f"(d[15]), "+f"(d[16]), "+f"(d[17]), "+f"(d[18]), "+f"(d[19]), "+f"(d[20]), "+f"(d[21]), "+f"(d[22]), "+f"(d[23]), "+f"(d[24]), "+f"(d[25]), "+f"(d[26]), "+f"(d[27]), "+f"(d[28]), "+f"(d[29]), "+f"(d[30]), "+f"(d[31])
    : "r"(a0), "r"(a1), "r"(a2), "r"(a3), "l"(db), "r"(scale_d), "n"(TB));
}
template <int TB, int TA = 0>
__device__ __forceinline__ void wgmma_ss_n160(float (&d)[80], uint64_t da, uint64_t db, int scale_d) {
  asm volatile("{\n.reg .pred p;\nsetp.ne.b32 p, %82, 0;\n"
    "wgmma.mma_async.sync.aligned.m64n160k16.f32.bf16.bf16 {%0, %1, %2, %3, %4, %5, %6, %7, %8, %9, %10, %11, %12, %13, %14, %15, %16, %17, %18, %19, %20, %21, %22, %23, %24, %25, %26, %27, %28, %29, %30, %31, %32, %33, %34, %35, %36, %37, %38, %39, %40, %41, %42, %43, %44, %45, %46, %47, %48, %49, %50, %51, %52, %53, %54, %55, %56, %57, %58, %59, %60, %61, %62, %63, %64, %65, %66, %67, %68, %69, %70, %71, %72, %73, %74, %75, %76, %77, %78, %79}, %80, %81, p, 1, 1, %83, %84;\n}\n"
    : "+f"(d[0]), "+f"(d[1]), "+f"(d[2]), "+f"(d[3]), "+f"(d[4]), "+f"(d[5]), "+f"(d[6]), "+f"(d[7]), "+f"(d[8]), "+f"(d[9]), "+f"(d[10]), "+f"(d[11]), "+f"(d[12]), "+f"(d[13]), "+f"(d[14]), "+f"(d[15]), "+f"(d[16]), "+f"(d[17]), "+f"(d[18]), "+f"(d[19]), "+f"(d[20]), "+f"(d[21]), "+f"(d[22]), "+f"(d[23]), "+f"(d[24]), "+f"(d[25]), "+f"(d[26]), "+f"(d[27]), "+f"(d[28]), "+f"(d[29]), "+f"(d[30]), "+f"(d[31]), "+f"(d[32]), "+f"(d[33]), "+f"(d[34]), "+f"(d[35]), "+f"(d[36]), "+f"(d[37]), "+f"(d[38]), "+f"(d[39]), "+f"(d[40]), "+f"(d[41]), "+f"(d[42]), "+f"(d[43]), "+f"(d[44]), "+f"(d[45]), "+f"(d[46]), "+f"(d[47]), "+f"(d[48]), "+f"(d[49]), "+f"(d[50]), "+f"(d[51]), "+f"(d[52]), "+f"(d[53]), "+f"(d[54]), "+f"(d[55]), "+f"(d[56]), "+f"(d[57]), "+f"(d[58]), "+f"(d[59]), "+f"(d[60]), "+f"(d[61]), "+f"(d[62]), "+f"(d[63]), "+f"(d[64]), "+f"(d[65]), "+f"(d[66]), "+f"(d[67]), "+f"(d[68]), "+f"(d[69]), "+f"(d[70]), "+f"(d[71]), "+f"(d[72]), "+f"(d[73]), "+f"(d[74]), "+f"(d[75]), "+f"(d[76]), "+f"(d[77]), "+f"(d[78]), "+f"(d[79])
    : "l"(da), "l"(db), "r"(scale_d), "n"(TA), "n"(TB));
}
template <int TB>
__device__ __forceinline__ void wgmma_rs_n160(float (&d)[80], uint32_t a0, uint32_t a1, uint32_t a2, uint32_t a3, uint64_t db, int scale_d) {
  asm volatile("{\n.reg .pred p;\nsetp.ne.b32 p, %85, 0;\n"
    "wgmma.mma_async.sync.aligned.m64n160k16.f32.bf16.bf16 {%0, %1, %2, %3, %4, %5, %6, %7, %8, %9, %10, %11, %12, %13, %14, %15, %16, %17, %18, %19, %20, %21, %22, %23, %24, %25, %26, %27, %28, %29, %30, %31, %32, %33, %34, %35, %36, %37, %38, %39, %40, %41, %42, %43, %44, %45, %46, %47, %48, %49, %50, %51, %52, %53, %54, %55, %56, %57, %58, %59, %60, %61, %62, %63, %64, %65, %66, %67, %68, %69, %70, %71, %72, %73, %74, %75, %76, %77, %78, %79}, {%80, %81, %82, %83}, %84, p, 1, 1, %86;\n}\n"
    : "+f"(d[0]), "+f"(d[1]), "+f"(d[2]), "+f"(d[3]), "+f"(d[4]), "+f"(d[5]), "+f"(d[6]), "+f"(d[7]), "+f"(d[8]), "+f"(d[9]), "+f"(d[10]), "+f"(d[11]), "+f"(d[12]), "+f"(d[13]), "+f"(d[14]), "+f"(d[15]), "+f"(d[16]), "+f"(d[17]), "+f"(d[18]), "+f"(d[19]), "+f"(d[20]), "+f"(d[21]), "+f"(d[22]), "+f"(d[23]), "+f"(d[24]), "+f"(d[25]), "+f"(d[26]), "+f"(d[27]), "+f"(d[28]), "+f"(d[29]), "+f"(d[30]), "+f"(d[31]), "+f"(d[32]), "+f"(d[33]), "+f"(d[34]), "+f"(d[35]), "+f"(d[36]), "+f"(d[37]), "+f"(d[38]), "+f"(d[39]), "+f"(d[40]), "+f"(d[41]), "+f"(d[42]), "+f"(d[43]), "+f"(d[44]), "+f"(d[45]), "+f"(d[46]), "+f"(d[47]), "+f"(d[48]), "+f"(d[49]), "+f"(d[50]), "+f"(d[51]), "+f"(d[52]), "+f"(d[53]), "+f"(d[54]), "+f"(d[55]), "+f"(d[56]), "+f"(d[57]), "+f"(d[58]), "+f"(d[59]), "+f"(d[60]), "+f"(d[61]), "+f"(d[62]), "+f"(d[63]), "+f"(d[64]), "+f"(d[65]), "+f"(d[66]), "+f"(d[67]), "+f"(d[68]), "+f"(d[69]), "+f"(d[70]), "+f"(d[71]), "+f"(d[72]), "+f"(d[73]), "+f"(d[74]), "+f"(d[75]), "+f"(d[76]), "+f"(d[77]), "+f"(d[78]), "+f"(d[79])
    : "r"(a0), "r"(a1), "r"(a2), "r"(a3), "l"(db), "r"(scale_d), "n"(TB));
}
template <int TB, int TA = 0>
__device__ __forceinline__ void wgmma_ss_n192(float (&d)[96], uint64_t da, uint64_t db, int scale_d) {
  asm volatile("{\n.reg .pred p;\nsetp.ne.b32 p, %98, 0;\n"
    "wgmma.mma_async.sync.aligned.m64n192k16.f32.bf16.bf16 {%0, %1, %2, %3, %4, %5, %6, %7, %8, %9, %10, %11, %12, %13, %14, %15, %16, %17, %18, %19, %20, %21, %22, %23, %24, %25, %26, %27, %28, %29, %30, %31, %32, %33, %34, %35, %36, %37, %38, %39, %40, %41, %42, %43, %44, %45, %46, %47, %48, %49, %50, %51, %52, %53, %54, %55, %56, %57, %58, %59, %60, %61, %62, %63, %64, %65, %66, %67, %68, %69, %70, %71, %72, %73, %74, %75, %76, %77, %78, %79, %80, %81, %82, %83, %84, %85, %86, %87, %88, %89, %90, %91, %92, %93, %94, %95}, %96, %97, p, 1, 1, %99, %100;\n}\n"
    : "+f"(d[0]), "+f"(d[1]), "+f"(d[2]), "+f"(d[3]), "+f"(d[4]), "+f"(d[5]), "+f"(d[6]), "+f"(d[7]), "+f"(d[8]), "+f"(d[9]), "+f"(d[10]), "+f"(d[11]), "+f"(d[12]), "+f"(d[13]), "+f"(d[14]), "+f"(d[15]), "+f"(d[16]), "+f"(d[17]), "+f"(d[18]), "+f"(d[19]), "+f"(d[20]), "+f"(d[21]), "+f"(d[22]), "+f"(d[23]), "+f"(d[24]), "+f"(d[25]), "+f"(d[26]), "+f"(d[27]), "+f"(d[28]), "+f"(d[29]), "+f"(d[30]), "+f"(d[31]), "+f"(d[32]), "+f"(d[33]), "+f"(d[34]), "+f"(d[35]), "+f"(d[36]), "+f"(d[37]), "+f"(d[38]), "+f"(d[39]), "+f"(d[40]), "+f"(d[41]), "+f"(d[42]), "+f"(d[43]), "+f"(d[44]), "+f"(d[45]), "+f"(d[46]), "+f"(d[47]), "+f"(d[48]), "+f"(d[49]), "+f"(d[50]), "+f"(d[51]), "+f"(d[52]), "+f"(d[53]), "+f"(d[54]), "+f"(d[55]), "+f"(d[56]), "+f"(d[57]), "+f"(d[58]), "+f"(d[59]), "+f"(d[60]), "+f"(d[61]), "+f"(d[62]), "+f"(d[63]), "+f"(d[64]), "+f"(d[65]), "+f"(d[66]), "+f"(d[67]), "+f"(d[68]), "+f"(d[69]), "+f"(d[70]), "+f"(d[71]), "+f"(d[72]), "+f"(d[73]), "+f"(d[74]), "+f"(d[75]), "+f"(d[76]), "+f"(d[77]), "+f"(d[78]), "+f"(d[79]), "+f"(d[80]), "+f"(d[81]), "+f"(d[82]), "+f"(d[83]), "+f"(d[84]), "+f"(d[85]), "+f"(d[86]), "+f"(d[87]), "+f"(d[88]), "+f"(d[89]), "+f"(d[90]), "+f"(d[91]), "+f"(d[92]), "+f"(d[93]), "+f"(d[94]), "+f"(d[95])
    : "l"(da), "l"(db), "r"(scale_d), "n"(TA), "n"(TB));
}
template <int TB>
__device__ __forceinline__ void wgmma_rs_n192(float (&d)[96], uint32_t a0, uint32_t a1, uint32_t a2, uint32_t a3, uint64_t db, int scale_d) {
  asm volatile("{\n.reg .pred p;\nsetp.ne.b32 p, %101, 0;\n"
    "wgmma.mma_async.sync.aligned.m64n192k16.f32.bf16.bf16 {%0, %1, %2, %3, %4, %5, %6, %7, %8, %9, %10, %11, %12, %13, %14, %15, %16, %17, %18, %19, %20, %21, %22, %23, %24, %25, %26, %27, %28, %29, %30, %31, %32, %33, %34, %35, %36, %37, %38, %39, %40, %41, %42, %43, %44, %45, %46, %47, %48, %49, %50, %51, %52, %53, %54, %55, %56, %57, %58, %59, %60, %61, %62, %63, %64, %65, %66, %67, %68, %69, %70, %71, %72, %73, %74, %75, %76, %77, %78, %79, %80, %81, %82, %83, %84, %85, %86, %87, %88, %89, %90, %91, %92, %93, %94, %95}, {%96, %97, %98, %99}, %100, p, 1, 1, %102;\n}\n"
    : "+f"(d[0]), "+f"(d[1]), "+f"(d[2]), "+f"(d[3]), "+f"(d[4]), "+f"(d[5]), "+f"(d[6]), "+f"(d[7]), "+f"(d[8]), "+f"(d[9]), "+f"(d[10]), "+f"(d[11]), "+f"(d[12]), "+f"(d[13]), "+f"(d[14]), "+f"(d[15]), "+f"(d[16]), "+f"(d[17]), "+f"(d[18]), "+f"(d[19]), "+f"(d[20]), "+f"(d[21]), "+f"(d[22]), "+f"(d[23]), "+f"(d[24]), "+f"(d[25]), "+f"(d[26]), "+f"(d[27]), "+f"(d[28]), "+f"(d[29]), "+f"(d[30]), "+f"(d[31]), "+f"(d[32]), "+f"(d[33]), "+f"(d[34]), "+f"(d[35]), "+f"(d[36]), "+f"(d[37]), "+f"(d[38]), "+f"(d[39]), "+f"(d[40]), "+f"(d[41]), "+f"(d[42]), "+f"(d[43]), "+f"(d[44]), "+f"(d[45]), "+f"(d[46]), "+f"(d[47]), "+f"(d[48]), "+f"(d[49]), "+f"(d[50]), "+f"(d[51]), "+f"(d[52]), "+f"(d[53]), "+f"(d[54]), "+f"(d[55]), "+f"(d[56]), "+f"(d[57]), "+f"(d[58]), "+f"(d[59]), "+f"(d[60]), "+f"(d[61]), "+f"(d[62]), "+f"(d[63]), "+f"(d[64]), "+f"(d[65]), "+f"(d[66]), "+f"(d[67]), "+f"(d[68]), "+f"(d[69]), "+f"(d[70]), "+f"(d[71]), "+f"(d[72]), "+f"(d[73]), "+f"(d[74]), "+f"(d[75]), "+f"(d[76]), "+f"(d[77]), "+f"(d[78]), "+f"(d[79]), "+f"(d[80]), "+f"(d[81]), "+f"(d[82]), "+f"(d[83]), "+f"(d[84]), "+f"(d[85]), "+f"(d[86]), "+f"(d[87]), "+f"(d[88]), "+f"(d[89]), "+f"(d[90]), "+f"(d[91]), "+f"(d[92]), "+f"(d[93]), "+f"(d[94]), "+f"(d[95])
    : "r"(a0), "r"(a1), "r"(a2), "r"(a3), "l"(db), "r"(scale_d), "n"(TB));
}

__device__ __forceinline__ uint32_t smem_u32(const void* p) { return (uint32_t)__cvta_generic_to_shared(p); }
__device__ __forceinline__ void wg_fence() { asm volatile("wgmma.fence.sync.aligned;" ::: "memory"); }
__device__ __forceinline__ void wg_commit() { asm volatile("wgmma.commit_group.sync.aligned;" ::: "memory"); }
template <int N> __device__ __forceinline__ void wg_wait() { asm volatile("wgmma.wait_group.sync.aligned %0;" ::"n"(N) : "memory"); }
__device__ __forceinline__ void sched_fence(uint32_t& keep, bool never) {
  asm volatile("{\n.reg .pred p;\nsetp.ne.b32 p, %1, 0;\n@p mov.u32 %0, %%clock;\n}\n" : "+r"(keep) : "r"((int)never) : "memory");
}
template <int N> __device__ __forceinline__ void fence_regs(float (&r)[N]) {
#pragma unroll
  for (int i = 0; i < N; i++) asm volatile("" : "+f"(r[i])::"memory");
}
template <int N> __device__ __forceinline__ void undefine(float (&r)[N]) {
#pragma unroll
  for (int i = 0; i < N; i++) asm volatile("" : "=f"(r[i]));
}
template <int N> __device__ __forceinline__ void fence_regs(uint32_t (&r)[N]) {
#pragma unroll
  for (int i = 0; i < N; i++) asm volatile("" : "+r"(r[i])::"memory");
}
__device__ __forceinline__ uint64_t mk_desc(uint32_t a16, uint32_t lbo, uint32_t sbo, uint32_t swz) {
  uint64_t d;
  asm("mov.b64 %0, {%1, %2};" : "=l"(d) : "r"(a16 + ((lbo >> 4) << 16)), "r"((sbo >> 4) | (swz << 30)));
  return d;
}
__device__ __forceinline__ void mbar_init(uint32_t bar, uint32_t cnt) {
  asm volatile("mbarrier.init.shared::cta.b64 [%0], %1;" ::"r"(bar), "r"(cnt) : "memory");
}
__device__ __forceinline__ void mbar_expect(uint32_t bar, uint32_t tx) {
  asm volatile("mbarrier.arrive.expect_tx.shared::cta.b64 _, [%0], %1;" ::"r"(bar), "r"(tx) : "memory");
}
__device__ __forceinline__ bool mbar_test(uint32_t bar, uint32_t ph) {
  uint32_t ok;
  asm volatile("{\n.reg .pred p;\nmbarrier.test_wait.parity.shared::cta.b64 p, [%1], %2;\nselp.u32 %0, 1, 0, p;\n}\n"
               : "=r"(ok) : "r"(bar), "r"(ph) : "memory");
  return ok;
}
__device__ __forceinline__ void mbar_wait(uint32_t bar, uint32_t ph) {
  asm volatile("{\n.reg .pred p;\n.reg .u32 n;\nmov.u32 n, 0;\n"
               "LOOP:\nmbarrier.try_wait.parity.shared::cta.b64 p, [%0], %1;\n@p bra DONE;\n"
               "add.u32 n, n, 1;\nsetp.lt.u32 p, n, 0x1000000;\n@p bra LOOP;\ntrap;\n"
               "DONE:\n}\n" ::"r"(bar), "r"(ph) : "memory");
}
template <int NS> __device__ __forceinline__ void mbar_wait_slow(uint32_t bar, uint32_t ph) {
  asm volatile("{\n.reg .pred p;\n.reg .u32 n;\nmov.u32 n, 0;\n"
               "LOOP:\nmbarrier.test_wait.parity.shared::cta.b64 p, [%0], %1;\n@p bra DONE;\n"
               "nanosleep.u32 %2;\nadd.u32 n, n, 1;\nsetp.lt.u32 p, n, 0x400000;\n@p bra LOOP;\ntrap;\n"
               "DONE:\n}\n" ::"r"(bar), "r"(ph), "n"(NS) : "memory");
}
__device__ __forceinline__ void mbar_arrive_cluster_if(bool on, uint32_t addr) {
  asm volatile("{\n.reg .pred p;\nsetp.ne.b32 p, %1, 0;\n@p mbarrier.arrive.shared::cluster.b64 _, [%0];\n}\n" ::"r"(addr), "r"((int)on) : "memory");
}
__device__ __forceinline__ void tma2d(uint32_t dst, const CUtensorMap* m, uint32_t bar, int c0, int c1) {
  asm volatile("cp.async.bulk.tensor.2d.shared::cluster.global.mbarrier::complete_tx::bytes [%0], [%1, {%3, %4}], [%2];"
               ::"r"(dst), "l"(m), "r"(bar), "r"(c0), "r"(c1) : "memory");
}
__device__ __forceinline__ void tma3d(uint32_t dst, const CUtensorMap* m, uint32_t bar, int c0, int c1, int c2) {
  asm volatile("cp.async.bulk.tensor.3d.shared::cluster.global.mbarrier::complete_tx::bytes [%0], [%1, {%3, %4, %5}], [%2];"
               ::"r"(dst), "l"(m), "r"(bar), "r"(c0), "r"(c1), "r"(c2) : "memory");
}
__device__ __forceinline__ void tma3d_mc(uint32_t dst, const CUtensorMap* m, uint32_t bar, int c0, int c1, int c2) {
  asm volatile("cp.async.bulk.tensor.3d.shared::cluster.global.mbarrier::complete_tx::bytes.multicast::cluster"
               " [%0], [%1, {%3, %4, %5}], [%2], %6;"
               ::"r"(dst), "l"(m), "r"(bar), "r"(c0), "r"(c1), "r"(c2), "h"((uint16_t)3) : "memory");
}
__device__ __forceinline__ void tma3d_store(const CUtensorMap* m, uint32_t src, int c0, int c1, int c2) {
  asm volatile("cp.async.bulk.tensor.3d.global.shared::cta.bulk_group [%0, {%2, %3, %4}], [%1];"
               ::"l"(m), "r"(src), "r"(c0), "r"(c1), "r"(c2) : "memory");
}
__device__ __forceinline__ void bar_sync(int id, int n) { asm volatile("bar.sync %0, %1;" ::"r"(id), "r"(n) : "memory"); }
__device__ __forceinline__ uint32_t pack_bf16(float lo, float hi) {
  uint32_t r;
  asm("cvt.rn.bf16x2.f32 %0, %1, %2;" : "=r"(r) : "f"(hi), "f"(lo));
  return r;
}
__device__ __forceinline__ float ex2(float x) {
  float y;
  asm("ex2.approx.ftz.f32 %0, %1;" : "=f"(y) : "f"(x));
  return y;
}
__device__ __forceinline__ float rcp(float x) {
  float y;
  asm("rcp.approx.ftz.f32 %0, %1;" : "=f"(y) : "f"(x));
  return y;
}
__device__ __forceinline__ void stsm4(uint32_t addr, uint32_t a, uint32_t b, uint32_t c, uint32_t d) {
  asm volatile("stmatrix.sync.aligned.m8n8.x4.shared.b16 [%0], {%1, %2, %3, %4};" ::"r"(addr), "r"(a), "r"(b), "r"(c), "r"(d) : "memory");
}

__device__ __forceinline__ void tma4d_mc_hint(uint32_t dst, const CUtensorMap* m, uint32_t bar, int c3, uint64_t pol) {
  asm volatile("cp.async.bulk.tensor.4d.shared::cluster.global.mbarrier::complete_tx::bytes.multicast::cluster.L2::cache_hint"
               " [%0], [%1, {%3, %3, %3, %4}], [%2], %5, %6;"
               ::"r"(dst), "l"(m), "r"(bar), "r"(0), "r"(c3), "h"((uint16_t)3), "l"(pol) : "memory");
}
__device__ __forceinline__ void tma5d_mc(uint32_t dst, const CUtensorMap* m, uint32_t bar, int c2, int c4) {
  asm volatile("cp.async.bulk.tensor.5d.shared::cluster.global.mbarrier::complete_tx::bytes.multicast::cluster"
               " [%0], [%1, {%3, %3, %4, %3, %5}], [%2], %6;"
               ::"r"(dst), "l"(m), "r"(bar), "r"(0), "r"(c2), "r"(c4), "h"((uint16_t)3) : "memory");
}
__device__ __forceinline__ void bulk_load_hint(uint32_t dst, const void* src, uint32_t bytes, uint32_t bar, uint64_t pol) {
  asm volatile("cp.async.bulk.shared::cluster.global.mbarrier::complete_tx::bytes.L2::cache_hint [%0], [%1], %2, [%3], %4;"
               ::"r"(dst), "l"(src), "r"(bytes), "r"(bar), "l"(pol) : "memory");
}
__device__ __forceinline__ void stg128_hint(void* p, uint32_t a, uint32_t b, uint32_t c, uint32_t d, uint64_t pol) {
  asm volatile("st.global.L2::cache_hint.v4.b32 [%0], {%1, %2, %3, %4}, %5;" ::"l"(p), "r"(a), "r"(b), "r"(c), "r"(d), "l"(pol) : "memory");
}
__device__ __forceinline__ void stg2_if(bool on, void* p, uint32_t a, uint32_t b, uint32_t c, uint32_t d, uint32_t e, uint32_t f,
                                        uint32_t g, uint32_t h, uint64_t pol) {
  asm volatile("{\n.reg .pred p;\nsetp.ne.b32 p, %10, 0;\n"
               "@p st.global.L2::cache_hint.v4.b32 [%0], {%1, %2, %3, %4}, %9;\n"
               "@p st.global.L2::cache_hint.v4.b32 [%0 + 512], {%5, %6, %7, %8}, %9;\n}\n"
               ::"l"(p), "r"(a), "r"(b), "r"(c), "r"(d), "r"(e), "r"(f), "r"(g), "r"(h), "l"(pol), "r"((int)on) : "memory");
}
__device__ __forceinline__ uint64_t make_policy(bool first) {
  uint64_t pf, pn;
  asm("createpolicy.fractional.L2::evict_first.b64 %0, 1.0;" : "=l"(pf));
  asm("createpolicy.fractional.L2::evict_normal.b64 %0, 1.0;" : "=l"(pn));
  return first ? pf : pn;
}
__device__ __forceinline__ bool elect() {
  uint32_t ok;
  asm volatile("{\n.reg .pred p;\nelect.sync _|p, 0xffffffff;\nselp.u32 %0, 1, 0, p;\n}\n" : "=r"(ok));
  return ok;
}
__device__ __forceinline__ void mbar_arrive(uint32_t bar) {
  asm volatile("mbarrier.arrive.shared::cta.b64 _, [%0];" ::"r"(bar) : "memory");
}
__device__ __forceinline__ void mbar_arrive_if(bool on, uint32_t bar) {
  asm volatile("{\n.reg .pred p;\nsetp.ne.b32 p, %1, 0;\n@p mbarrier.arrive.shared::cta.b64 _, [%0];\n}\n" ::"r"(bar), "r"((int)on) : "memory");
}
__device__ __forceinline__ void stg128(void* p, uint32_t a, uint32_t b, uint32_t c, uint32_t d) {
  asm volatile("st.global.v4.b32 [%0], {%1, %2, %3, %4};" ::"l"(p), "r"(a), "r"(b), "r"(c), "r"(d) : "memory");
}
__device__ __forceinline__ void lds2_if(bool on, uint32_t p, uint32_t (&t)[8]) {
  asm volatile("{\n.reg .pred p;\nsetp.ne.b32 p, %9, 0;\n@p ld.shared.v4.b32 {%0, %1, %2, %3}, [%8];\n@p ld.shared.v4.b32 {%4, %5, %6, %7}, [%8 + 512];\n}\n"
               : "+r"(t[0]), "+r"(t[1]), "+r"(t[2]), "+r"(t[3]), "+r"(t[4]), "+r"(t[5]), "+r"(t[6]), "+r"(t[7]) : "r"(p), "r"((int)on) : "memory");
}
__device__ __forceinline__ void lds128(uint32_t p, uint32_t& a, uint32_t& b, uint32_t& c, uint32_t& d) {
  asm volatile("ld.shared.v4.b32 {%0, %1, %2, %3}, [%4];" : "=r"(a), "=r"(b), "=r"(c), "=r"(d) : "r"(p) : "memory");
}
template <class T> __device__ __forceinline__ T* ptr_add(T* base, uint32_t bytes) {
  T* r;
  asm("{\n.reg .u32 lo, hi;\nmov.b64 {lo, hi}, %1;\nadd.cc.u32 lo, lo, %2;\naddc.u32 hi, hi, 0;\nmov.b64 %0, {lo, hi};\n}\n" : "=l"(r) : "l"(base), "r"(bytes));
  return r;
}
__device__ __forceinline__ uint32_t flag_peek(const unsigned int* p) {
  uint32_t v;
  asm volatile("ld.relaxed.gpu.global.u32 %0, [%1];" : "=r"(v) : "l"(p) : "memory");
  return v;
}
__device__ __forceinline__ uint32_t flag_get(const unsigned int* p) {
  uint32_t v;
  asm volatile("ld.acquire.gpu.global.u32 %0, [%1];" : "=r"(v) : "l"(p) : "memory");
  return v;
}
__device__ __forceinline__ void wait_progress(uint32_t p, uint32_t target) {
  asm volatile("{\n.reg .pred p;\n.reg .u32 n, v;\nmov.u32 n, 0;\n"
               "LOOP:\nld.acquire.cta.shared.u32 v, [%0];\nsetp.ge.u32 p, v, %1;\n@p bra DONE;\n"
               "nanosleep.u32 %2;\nadd.u32 n, n, 1;\nsetp.lt.u32 p, n, 0x400000;\n@p bra LOOP;\ntrap;\n"
               "DONE:\n}\n" ::"r"(p), "r"(target), "n"(400) : "memory");
}
__device__ __forceinline__ void flag_set(unsigned int* p, uint32_t v) {
  asm volatile("st.release.gpu.global.u32 [%0], %1;" ::"l"(p), "r"(v) : "memory");
}
__device__ __forceinline__ void flag_dec(unsigned int* p) {
  asm volatile("red.relaxed.gpu.global.add.u32 [%0], 0xffffffff;" ::"l"(p) : "memory");
}

struct Cursor {
  int bi;
  uint32_t ph;
  __device__ __forceinline__ void next() {
    if (++bi == NBAR) { bi = 0; ph ^= 1; }
  }
};

constexpr float kScaleLog2 = 0.07216878364870322f * 1.4426950408889634f;
constexpr float kSumLimit = 1048576.0f;

__global__ void __cluster_dims__(2, 1, 1) __launch_bounds__(384, 1)
fused_kernel(const __grid_constant__ Params P) {
  extern __shared__ uint8_t smem_raw[];
  const uint32_t sbase = (smem_u32(smem_raw) + 1023) & ~1023u;
  const uint32_t full0 = sbase + RING, empty0 = full0 + 8 * NBAR, odone0 = empty0 + 8 * NBAR, ev0 = odone0 + 8 * MAX_OPS;
  const uint32_t progress = ev0 + 8 * MAX_EV;
  const uint32_t rank = blockIdx.x & 1;
  const int role = blockIdx.x >> 1;
  const int wid = __shfl_sync(0xffffffffu, (int)(threadIdx.x >> 5), 0);
  const int wg = wid >> 2;

  const uint32_t op0 = P.first[role];
  if (__builtin_expect(wid == 8, 1)) {
    if (elect()) {
#pragma unroll
      for (int k = 0; k < EARLY; k++) mbar_init(full0 + 8 * k, 1);
      asm volatile("fence.mbarrier_init.release.cluster;" ::: "memory");
      const int blk = (op0 >> 10) & 1;
      if ((op0 & 3) == OP_Q) {
#pragma unroll
        for (int k = 0; k < EARLY; k++) {
          mbar_expect(full0 + 8 * k, SZ_Q);
          tma2d(sbase + k * SZ_Q, &P.x[blk], full0 + 8 * k, 64 * k, ((op0 >> 7) & 7) * kSq + rank * 128);
          tma3d(sbase + k * SZ_Q + 16384, &P.wq[blk], full0 + 8 * k, 0, 64 * k, 3 * ((op0 >> 2) & 31));
        }
      }
      asm volatile("prefetch.tensormap [%0];" ::"l"(rank ? &P.v[blk] : &P.k[blk]) : "memory");
    }
  } else if (wg < 2 && elect()) {
#pragma unroll
    for (int j = 0; j < 16; j++) {
      const int i = EARLY + 16 * wid + j;
      if (i < 2 * NBAR + MAX_OPS + MAX_EV) mbar_init(full0 + 8 * i, i < NBAR ? 1 : i < 2 * NBAR ? 16 : i < 2 * NBAR + MAX_OPS ? 8 : 1);
    }
    if (wid == 7) asm volatile("st.shared.u32 [%0], 0;\nfence.acq_rel.cta;" ::"r"(progress) : "memory");
    asm volatile("fence.mbarrier_init.release.cluster;" ::: "memory");
  }
  __syncwarp();
  asm volatile("barrier.cluster.arrive.relaxed.aligned;\nbarrier.cluster.wait.aligned;" ::: "memory");

  if (wg < 2) {
    asm volatile("setmaxnreg.inc.sync.aligned.u32 240;");
    const uint32_t* prog = P.prog[role].c;
    const int lane = threadIdx.x & 31, warp = wid & 3;
    uint32_t empty_rem;
    asm volatile("mapa.shared::cluster.u32 %0, %1, %2;" : "=r"(empty_rem) : "r"(empty0), "r"(lane & 1));
    auto release = [&](int slot) { mbar_arrive_cluster_if(lane < 2, empty_rem + 8 * slot); };
    Cursor r{0, 0};
    const uint32_t ring16 = (sbase & 0x3FFFF) >> 4;
    uint32_t cur = ring16;
    bool rdy0 = false, rdy1 = false;
    auto probe1 = [&]() { rdy0 = mbar_test(full0 + 8 * r.bi, r.ph); };
    auto probe2 = [&]() {
      Cursor n = r;
      rdy0 = mbar_test(full0 + 8 * n.bi, n.ph);
      n.next();
      rdy1 = mbar_test(full0 + 8 * n.bi, n.ph);
    };
    auto take = [&](bool rdy, uint32_t bytes, uint32_t& addr) {
      const int bi = r.bi;
      if (__builtin_expect(!__all_sync(0xffffffffu, rdy), 0)) mbar_wait(full0 + 8 * r.bi, r.ph);
      r.next();
      if (cur > ring16 + ((RING - bytes) >> 4)) cur = ring16;
      addr = cur;
      cur += bytes >> 4;
      return bi;
    };
    uint32_t keep = 0;
    const bool never = P.dbg == 0xffffffffu;
    uint32_t q[48];
#pragma unroll
    for (int i = 0; i < 48; i++) q[i] = 0;
    const int row = wg * 64 + warp * 16 + (lane >> 2);
    const int img0 = row * 4 + ((lane & 3) ^ ((row >> 1) & 3));
    uint4* pend = nullptr;
    bool pend_any = false;
    uint64_t spol;
    int pc = 0;
    auto slab = [&](int c, int i0) {
#pragma unroll
      for (int i = i0; i < 6; i++)
        stg2_if(c == i, pend + i * 512, q[8 * i], q[8 * i + 1], q[8 * i + 2], q[8 * i + 3],
                q[8 * i + 4], q[8 * i + 5], q[8 * i + 6], q[8 * i + 7], spol);
    };
    auto drain = [&](int c) {
      if (!pend_any || c >= 6) return;
      slab(c, 0);
      if (c == 5) {
        __syncwarp();
        mbar_arrive_if(lane == 0, odone0 - 8 + 8 * pc);
      }
    };

    for (;; pc++) {
      uint32_t op = prog[pc];
      const int type = op & 3;
      auto enter = [&]() {
        r.bi = (op >> 15) & 15; r.ph = (op >> 19) & 1; cur = ring16 + (((op >> 20) & 63) << 8);
      };
      enter();
      pend_any = op & C_PEND;
      spol = make_policy(!(op & C_SOON));
      if (type == OP_END) {
#pragma unroll 1
        for (int c = 0; c < 6; c++) drain(c);
        asm volatile("barrier.cluster.arrive.relaxed;" ::: "memory");
        break;
      }
      {
        float s[32], o[96];
        uint32_t ad0;
        int bi0, sk1;
        uint32_t pa[16], pb[16];
        float mc0, mc1, l0, l1;
        bool shifted;
        uint32_t nop;
        auto expo = [&](float (&s)[32], uint32_t (&pout)[16], float& b0, float& b1, bool shift, auto mid) {
          float c0, c1;
#pragma unroll
          for (int i = 0; i < 8; i++) {
            const float e0 = ex2(shift ? s[4 * i] - mc0 : s[4 * i]), e1 = ex2(shift ? s[4 * i + 1] - mc0 : s[4 * i + 1]);
            const float e2 = ex2(shift ? s[4 * i + 2] - mc1 : s[4 * i + 2]), e3 = ex2(shift ? s[4 * i + 3] - mc1 : s[4 * i + 3]);
            if (i) { b0 += e0; c0 += e1; b1 += e2; c1 += e3; } else { b0 = e0; c0 = e1; b1 = e2; c1 = e3; }
            pout[2 * i] = pack_bf16(e0, e1); pout[2 * i + 1] = pack_bf16(e2, e3);
            if (i & 1) mid(i >> 1);
          }
          b0 += c0; b1 += c1;
        };
        auto rowmax = [&](float (&s)[32], float& m0, float& m1) {
          m0 = fmaxf(s[0], s[1]); m1 = fmaxf(s[2], s[3]);
#pragma unroll
          for (int i = 1; i < 8; i++) { m0 = fmaxf(m0, fmaxf(s[4 * i], s[4 * i + 1])); m1 = fmaxf(m1, fmaxf(s[4 * i + 2], s[4 * i + 3])); }
          m0 = fmaxf(m0, __shfl_xor_sync(0xffffffffu, m0, 1)); m1 = fmaxf(m1, __shfl_xor_sync(0xffffffffu, m1, 1));
          m0 = fmaxf(m0, __shfl_xor_sync(0xffffffffu, m0, 2)); m1 = fmaxf(m1, __shfl_xor_sync(0xffffffffu, m1, 2));
        };
        auto first = [&](float (&s)[32], int sk0, auto mid) {
          fence_regs(s);
          release(sk0);
          mc0 = 0.f; mc1 = 0.f;
          expo(s, pa, l0, l1, false, mid);
          shifted = __any_sync(0xffffffffu, !(fmaxf(l0, l1) <= kSumLimit && fminf(l0, l1) >= 1.f / kSumLimit));
          if (shifted) {
            rowmax(s, mc0, mc1);
            expo(s, pa, l0, l1, true, [](int) {});
          }
        };
        auto qk = [&](float (&s)[32], uint32_t ak, int k0 = 0, int k1 = 12) {
#pragma unroll
          for (int kk = k0; kk < k1; kk++)
            wgmma_rs_n64<0>(s, q[4 * kk], q[4 * kk + 1], q[4 * kk + 2], q[4 * kk + 3], mk_desc(ak + (kk >> 2) * KV_CH + (kk & 3) * 2, 16, KV_SBO, 1), kk != 0);
          if (k1 == 12) wg_commit();
        };
        auto pv = [&](uint32_t (&pin)[16], uint32_t av, int acc) {
#pragma unroll
          for (int kk = 0; kk < 4; kk++)
            wgmma_rs_n192<1>(o, pin[4 * kk], pin[4 * kk + 1], pin[4 * kk + 2], pin[4 * kk + 3], mk_desc(av + kk * (KV_SBO / 8), KV_CH * 16, KV_SBO, 1), acc || (kk != 0));
          wg_commit();
        };
        auto finish = [&](uint32_t (&pout)[16], int sk, int sv) {
          probe2();
          wg_wait<1>();
          fence_regs(s);
          release(sk);
          float b0, b1;
#pragma unroll 1
          for (bool redo = false;; redo = true) {
            expo(s, pout, b0, b1, false, [](int) {});
            if (!__any_sync(0xffffffffu, !redo && (shifted || !(fmaxf(b0, b1) <= kSumLimit)))) break;
            shifted = true;
            rowmax(s, b0, b1);
            b0 = fmaxf(mc0, b0); b1 = fmaxf(mc1, b1);
            const float a0 = ex2(mc0 - b0), a1 = ex2(mc1 - b1);
            mc0 = b0; mc1 = b1;
            l0 *= a0; l1 *= a1;
            wg_wait<0>();
            fence_regs(o);
#pragma unroll
            for (int i = 0; i < 24; i++) { o[4 * i] *= a0; o[4 * i + 1] *= a0; o[4 * i + 2] *= a1; o[4 * i + 3] *= a1; }
#pragma unroll
            for (int i = 0; i < 32; i++) s[i] -= (i & 2) ? mc1 : mc0;
          }
          l0 += b0; l1 += b1;
          wg_wait<0>();
          fence_regs(o);
          release(sv);
        };
        auto step = [&](uint32_t (&pin)[16], uint32_t (&pout)[16]) {
          uint32_t ak, av;
          const int sk = take(rdy0, SZ_KV, ak), sv = take(rdy1, SZ_KV, av);
          wg_fence();
          qk(s, ak);
          pv(pin, av, 1);
          finish(pout, sk, sv);
        };
        auto unpark = [&]() {
          uint32_t ad, ak;
          const int bi = take(rdy0, SZ_PARK, ad);
#pragma unroll
          for (int i = 0; i < 12; i++) lds128(sbase + (ad - ring16 + img0) * 16 + (i >> 1) * 8192 + (i & 1) * 512, q[4 * i], q[4 * i + 1], q[4 * i + 2], q[4 * i + 3]);
          const int sk0 = take(false, SZ_KV, ak);
          fence_regs(q);
          release(bi);
          wg_fence();
          qk(s, ak);
          probe2();
          return sk0;
        };
        auto mma4 = [&](uint32_t ad, int acc) {
#pragma unroll
          for (int kk = 0; kk < 4; kk++)
            wgmma_ss_n192<1>(o, mk_desc(ad + wg * 512 + kk * 2, 16, 1024, 1), mk_desc(ad + 1024 + kk * 128, 8192, 1024, 1), acc || kk != 0);
        };
        auto convert = [&](int i0, int i1) {
          sched_fence(keep, never);
#pragma unroll
          for (int i = i0; i < i1; i++) q[i] = pack_bf16(o[2 * i] * kScaleLog2, o[2 * i + 1] * kScaleLog2);
          sched_fence(keep, never);
        };
        auto kend = [&](int bi, int k) {
          wg_commit();
          drain(k < 8 ? (QDRAIN >> (4 * k)) & 7 : 7);
          probe1();
          wg_wait<0>();
          release(bi);
        };
        if (type == OP_O) {
          float c[80];
          const int nk = 3 * ((op >> 2) & 63), ro = (op >> 8) & 63;
          uint4* part = ptr_add(g_part, (ro * 2 + rank) * SZ_PARK + img0 * 16);
          int prev = 0;
          auto hand_over = [&](float (&c)[80], uint4* dst) {
            fence_regs(c);
#pragma unroll
            for (int i = 0; i < 48; i++) q[i] = i < 8 ? 0 : pack_bf16(c[2 * i - 16], c[2 * i - 15]);
            pend = dst;
          };
          auto mma2 = [&](float (&c)[80], uint32_t da, uint32_t db, int acc) {
            wgmma_ss_n160<1>(c, mk_desc(da, 16, 512, 2), mk_desc(db, 2048, 512, 2), acc);
            wgmma_ss_n160<1>(c, mk_desc(da + 2, 16, 512, 2), mk_desc(db + 64, 2048, 512, 2), 1);
          };
          auto kstep = [&](float (&c)[80], int acc, auto hook, uint32_t bytes = SZ_O) {
            uint32_t ad;
            const int bi = take(rdy0, bytes, ad);
            const uint32_t da = ad + wg * 256, db = ad + 1024;
            wg_fence();
            mma2(c, da, db, acc);
            wg_commit();
            if (acc) { wg_wait<1>(); mbar_arrive_cluster_if(lane < 2 && (acc == 1 || wg == 0), empty_rem + 8 * prev); }
            mma2(c, da + 512, db + 640, 1);
            wg_commit();
            prev = bi;
            hook();
            probe1();
            wg_wait<1>();
          };
          if (op & C_WIDE) {
            float d[80];
            auto wstep = [&](int acc, auto hook) {
              uint32_t ad;
              const int bi = take(rdy0, SZ_W, ad);
              const uint32_t da = ad + wg * 256, db = ad + 1024;
              wg_fence();
              mma2(d, da, db, acc);
              mma2(d, da + 512, db + 640, 1);
              wg_commit();
              if (acc) { wg_wait<1>(); release(prev); }
              mma2(c, da, db + 1280, acc);
              mma2(c, da + 512, db + 1920, 1);
              wg_commit();
              prev = bi;
              hook();
              probe1();
              wg_wait<1>();
            };
            wstep(0, [&]() { drain(0); drain(1); });
#pragma unroll 1
            for (int k = 2; k < 6; k += 2) wstep(1, [&]() { drain(k); drain(k + 1); });
#pragma unroll 1
            for (int k = 3 + 3 * TAIL; k < nk; k++) {
              wstep(1, []() {});
            }
#pragma unroll 1
            for (int k = 0; k < 3 * TAIL; k++) kstep(d, 1, []() {});
            nop = prog[pc + 1];
            spol = make_policy(!(nop & C_SOON));
            kstep(c, 1, [&]() { hand_over(d, part - 6144); });
#pragma unroll 1
            for (int k = 1; k < 3 * TAIL; k++) kstep(c, 1, [&]() { slab(TAIL == 2 ? k : (0x50403201 >> (4 * k - 4)) & 7, 1); });
            if ((nop & 3) == OP_Q) {
              op = nop;
              enter();
              pc++;
              pend_any = true;
              bi0 = take(rdy0, SZ_Q, ad0);
              undefine(o);
              wg_fence();
              mma4(ad0, 0);
              wg_commit();
              wg_wait<1>();
              release(prev);
              hand_over(c, part);
              probe1();
              wg_wait<0>();
              release(bi0);
              fence_regs(o);
              goto next_head;
            }
            wg_wait<0>();
            release(prev);
            hand_over(c, part);
            continue;
          }
          kstep(c, 0, [&]() { drain(0); });
#pragma unroll 1
          for (int k = 1; k < 6; k++) kstep(c, 1, [&]() { drain(k); });
#pragma unroll 1
          for (int k = 11; k < nk; k++) kstep(c, 1, []() {});
          uint32_t t[8], stage[3];
          float u[80];
          auto unpack = [&](int j) {
#pragma unroll
            for (int i = 0; i < 8; i++) {
              u[16 * j + 2 * i] = __uint_as_float(t[i] << 16); u[16 * j + 2 * i + 1] = __uint_as_float(t[i] & 0xffff0000u);
              asm volatile("" : "+f"(u[16 * j + 2 * i]), "+f"(u[16 * j + 2 * i + 1]));
            }
          };
#pragma unroll
          for (int i = 0; i < 8; i++) t[i] = 0;
          const uint32_t bytes = (op & C_LD) ? SZ_OL : SZ_O;
#pragma unroll
          for (int j = 0; j < 5; j++) {
            if (j == 5 - SKEW && wg == 1) {
              wg_wait<0>();
              release(prev);
              bar_sync(1, 256);
            }
            kstep(c, j == 5 - SKEW ? 2 : 1, [&]() {
              if (SKEW && j == 4) asm volatile("{\n.reg .pred p;\nsetp.eq.u32 p, %0, 0;\n@p bar.arrive 1, 256;\n}\n" ::"r"(wg) : "memory");
              if (j) unpack(j - 1);
              lds2_if(op & C_LD, sbase + (cur - ring16 + img0) * 16 - 8192, t);
              if (j >= 1 && j <= 3) stage[j - 1] = sbase + (cur - ring16) * 16 - bytes + wid * 1024;
            }, bytes);
          }
          unpack(4);
          sched_fence(keep, never);
          wg_wait<0>();
          fence_regs(c);
          release(prev);
          asm volatile("barrier.cluster.arrive.relaxed;" ::: "memory");
#pragma unroll
          for (int i = 0; i < 10; i++) {
            const int v = (i & 1) * 2 + (lane >> 4);
            const uint32_t sa = stage[i >> 2] + (i & 2) * 4096;
            stsm4(sa + (lane & 15) * 64 + ((v ^ ((lane >> 1) & 3)) << 4), pack_bf16(c[8 * i] + u[8 * i], c[8 * i + 1] + u[8 * i + 1]),
                  pack_bf16(c[8 * i + 2] + u[8 * i + 2], c[8 * i + 3] + u[8 * i + 3]), pack_bf16(c[8 * i + 4] + u[8 * i + 4], c[8 * i + 5] + u[8 * i + 5]),
                  pack_bf16(c[8 * i + 6] + u[8 * i + 6], c[8 * i + 7] + u[8 * i + 7]));
          }
          asm volatile("fence.proxy.async.shared::cta;" ::: "memory");
          __syncwarp();
          if (elect()) {
#pragma unroll
            for (int i = 0; i < 5; i++)
              tma3d_store(&P.out, stage[i >> 1] + (i & 1) * 8192, 0, ((ro >> 2) & 7) * kSq + rank * 128 + wid * 16, (ro >> 5) * 20 + (ro & 3) * 5 + i);
            asm volatile("cp.async.bulk.commit_group;\ncp.async.bulk.wait_group.read 0;" ::: "memory");
          }
          __syncwarp();
          break;
        }
        bi0 = take(rdy0, SZ_Q, ad0);
        undefine(o);
        wg_fence();
        mma4(ad0, 0);
        kend(bi0, 0);
        fence_regs(o);
      next_head:
        {
#pragma unroll 1
          for (int k = 1; k < ((op & F_PARK) ? 10 : 8); k++) {
            uint32_t ad;
            const int bi = take(rdy0, SZ_Q, ad);
            wg_fence();
            mma4(ad, 1);
            kend(bi, k);
          }
          if (op & F_PARK) {
            fence_regs(o);
            convert(0, 48);
            pend = ptr_add(g_t, (((op >> 2) & 511) * 2 + rank) * SZ_PARK + img0 * 16);
            continue;
          }
          uint32_t a8, a9, ak0, ak1;
          const int b8 = take(rdy0, SZ_Q, a8), b9 = take(false, SZ_Q, a9);
          wg_fence();
          mma4(a8, 1);
          wg_commit();
          mma4(a9, 1);
          wg_commit();
          pc++;
          wg_wait<1>();
          release(b8);
          const int sk0 = take(false, SZ_KV, ak0);
          wg_wait<0>();
          fence_regs(o);
          release(b9);
          float s0[32];
          convert(0, 32);
          wg_fence();
          qk(s0, ak0, 0, 4);
          convert(32, 48);
          wg_fence();
          qk(s0, ak0, 4, 12);
          sk1 = take(false, SZ_KV, ak1);
          probe1();
          wg_wait<0>();
          first(s0, sk0, [&](int i) {
            if (i == 0) return;
            sched_fence(keep, never);
            wg_fence();
            if (i == 1) qk(s, ak1, 0, 4);
            if (i == 2) qk(s, ak1, 4, 8);
            if (i == 3) qk(s, ak1, 8, 12);
            sched_fence(keep, never);
          });
        }
        for (;;) {
          {
            uint32_t av;
            const int sv = take(rdy0, SZ_KV, av);
            undefine(o);
            wg_fence();
            pv(pa, av, 0);
            finish(pb, sk1, sv);
          }
          nop = prog[pc + 1];
#pragma unroll 1
          for (int jj = 0; jj < 7; jj++) {
            step(pb, pa);
            step(pa, pb);
          }
          float i0, i1;
          auto last = [&]() {
            uint32_t av;
            const int sv = take(rdy0, SZ_KV, av);
            wg_fence();
            pv(pb, av, 1);
            sched_fence(keep, never);
            probe1();
            l0 += __shfl_xor_sync(0xffffffffu, l0, 1); l1 += __shfl_xor_sync(0xffffffffu, l1, 1);
            l0 += __shfl_xor_sync(0xffffffffu, l0, 2); l1 += __shfl_xor_sync(0xffffffffu, l1, 2);
            i0 = rcp(l0); i1 = rcp(l1);
            pend = ptr_add(g_t, (((op >> 2) & 511) * 2 + rank) * SZ_PARK + img0 * 16);
            return sv;
          };
          auto normalise = [&](uint32_t (&d)[48], auto mid) {
#pragma unroll
            for (int i = 0; i < 24; i++) {
              d[8 * (i >> 2) + (i & 3)] = pack_bf16(o[4 * i] * i0, o[4 * i + 1] * i0);
              d[8 * (i >> 2) + (i & 3) + 4] = pack_bf16(o[4 * i + 2] * i1, o[4 * i + 3] * i1);
              if ((i & 3) == 3 && i != 23) { sched_fence(keep, never); mid(i >> 2); }
            }
          };
          const int sv = last();
          if ((nop & 3) != OP_A) {
            op = nop;
            enter();
            pend_any = true;
            spol = make_policy(!(op & C_SOON));
            bi0 = take(rdy0 || (nop & 3) != OP_Q, SZ_Q, ad0);
            sched_fence(keep, never);
            wg_wait<0>();
            fence_regs(o);
            release(sv);
            normalise(q, [](int) {});
            undefine(o);
            if ((nop & 3) != OP_Q) break;
            sched_fence(keep, never);
            wg_fence();
            mma4(ad0, 0);
            pc++;
            kend(bi0, 0);
            fence_regs(o);
            goto next_head;
          }
          const int sk0 = unpark();
          wg_wait<1>();
          fence_regs(o);
          release(sv);
          uint32_t t[48];
          spol = make_policy(!(nop & C_SOON));
          auto st = [&](int i) {
            stg2_if(true, pend + i * 512, t[8 * i], t[8 * i + 1], t[8 * i + 2], t[8 * i + 3], t[8 * i + 4], t[8 * i + 5], t[8 * i + 6], t[8 * i + 7], spol);
          };
          normalise(t, [&](int i) { if (!(i & 1)) st(i >> 1); });
          wg_wait<0>();
          first(s, sk0, [&](int i) { if (i < 3) { sched_fence(keep, never); st(3 + i); } });
          __syncwarp();
          mbar_arrive_if(lane == 0, odone0 + 8 * pc);
          pc++;
          op = nop;
          uint32_t ak1;
          sk1 = take(rdy0, SZ_KV, ak1);
          rdy0 = rdy1;
          wg_fence();
          qk(s, ak1);
        }
      }
    }
    if (never) g_flag[0] = keep;
    asm volatile("barrier.cluster.wait;" ::: "memory");
  } else {
    asm volatile("setmaxnreg.dec.sync.aligned.u32 24;");
    const uint32_t* prog = P.prog[role].p;
    unsigned int* flag = g_flag + rank;
    if (wid == 8) {
      Cursor tail{0, 0};
      int head = 0, sh = 0;
      uint32_t cur = 0, used = 0;
      uint64_t fifo = 0;
      uint32_t dst, bar, ev = ev0, done = 0;
      uint64_t pol;
      asm volatile("createpolicy.fractional.L2::evict_first.b64 %0, 1.0;" : "=l"(pol));
      auto retire = [&]() {
        mbar_wait(empty0 + 8 * tail.bi, tail.ph);
        tail.next();
        used -= (uint32_t)fifo & 31;
        fifo >>= 5;
        sh -= 5;
        asm volatile("st.volatile.shared.u32 [%0], %1;" ::"r"(progress), "r"(++done) : "memory");
      };
      auto acquire = [&](uint32_t bytes) {
        uint32_t fp = bytes >> 12;
        if (cur + fp > (RING >> 12)) { fp += (RING >> 12) - cur; cur = 0; }
        used += fp;
        while (used > (RING >> 12) || sh == 5 * NBAR) retire();
        fifo |= (uint64_t)fp << sh;
        sh += 5;
        dst = sbase + (cur << 12);
        bar = full0 + 8 * head;
        cur += bytes >> 12;
        if (++head == NBAR) head = 0;
      };
      auto gate = [&]() {
        mbar_wait(ev, 0);
        ev += 8;
        asm volatile("fence.proxy.async.global;" ::: "memory");
      };
      for (int pc = 0;; pc++) {
        const uint32_t op = prog[pc];
        const int type = op & 3, blk = (op >> 10) & 1;
        if (type == OP_END) break;
        if (type == OP_Q) {
#pragma unroll 1
          for (int k = 0; k < 10; k++) {
            if (k == 9 && (op & P_GATE)) gate();
            acquire(SZ_Q);
            if ((pc > 0 || k >= EARLY) && elect()) {
              mbar_expect(bar, SZ_Q);
              tma2d(dst, &P.x[blk], bar, 64 * k, ((op >> 7) & 7) * kSq + rank * 128);
              if ((k & 1) == rank) tma3d_mc(dst + 16384, &P.wq[blk], bar, 0, 64 * k, 3 * ((op >> 2) & 31));
            }
          }
        } else if (type == OP_A) {
          const int row0 = ((op >> 2) & 255) * kSk;
          const CUtensorMap* kv_map = rank ? &P.v[blk] : &P.k[blk];
          if (op & F_PARK) {
            gate();
            acquire(SZ_PARK);
            if (elect()) {
              mbar_expect(bar, SZ_PARK);
              bulk_load_hint(dst, &g_t[((op >> 20) * 2 + rank) * 3072], SZ_PARK, bar, make_policy(P.dbg & 4));
            }
          }
#pragma unroll 1
          for (int t = 0; t < 32; t++) {
            const int isv = t == 31 ? 1 : (t == 0 ? 0 : (~t & 1));
            const int j = isv ? (t - 1) >> 1 : (t + 1) >> 1;
            if (t == 31 && (op & P_GATE)) gate();
            acquire(SZ_KV);
            if (elect()) {
              mbar_expect(bar, SZ_KV);
              if (isv == (int)rank) tma4d_mc_hint(dst, kv_map, bar, row0 / 8 + 8 * j, pol);
            }
          }
        } else {
          const int n = (op >> 13) & 63, nw = (op & P_WIDE) ? n - TAIL : 0;
          const uint64_t pol_o = make_policy(P.dbg & (nw ? 1 : 2));
          const uint4* part = &g_part[((((op >> 5) & 60) + ((op >> 19) & 3)) * 2 + rank) * 3072 + 512];
#pragma unroll 1
          for (int i = 0; i < n + (nw ? TAIL : 0); i++) {
            const int id = ((op >> 2) & 511) + (i < n ? i : i - TAIL), col = 5 * (((op >> 19) & 3) + (i >= n));
            const uint4* src = &g_t[(P.slot[id] * 2 + rank) * 3072];
            if ((op & P_LD) && i == ((op & P_PRE) ? 0 : n - 2)) gate();
            if (i < n) gate();
#pragma unroll 1
            for (int k = 0; k < 3; k++) {
              const uint32_t j = (op & P_LD) ? 3 * (i - n) + k + 5 : 5, bytes = i < nw ? SZ_W : j < 5 ? SZ_OL : SZ_O;
              acquire(bytes);
              if (elect()) {
                mbar_expect(bar, bytes);
                tma5d_mc(dst + 16384 + rank * 10240, &P.wo[blk], bar, 24 * (id & 31) + 8 * k + 4 * rank, col);
                bulk_load_hint(dst, src + k * 1024, 16384, bar, pol_o);
                if (i < nw) tma5d_mc(dst + SZ_O + rank * 10240, &P.wo[blk], bar, 24 * (id & 31) + 8 * k + 4 * rank, col + 5);
                if (j < 5) bulk_load_hint(dst + SZ_O, part + j * 512, 8192, bar, pol);
                if ((op & P_PRE) && 3 * i + k < 10)
                  asm volatile("cp.async.bulk.prefetch.L2.global [%0], 4096;" ::"l"(part + (3 * i + k) * 256) : "memory");
              }
            }
          }
        }
      }
#pragma unroll 1
      while (sh) retire();
    } else if (threadIdx.x == 288) {
      for (int pc = 0;; pc++) {
        const uint32_t op = prog[pc];
        const int type = op & 3;
        if (type == OP_END) break;
        if (type == OP_Q ? !(op & F_PARK) : type == OP_O && !(op & P_ST)) continue;
        const int id = type == OP_A ? (op >> 2) & 511 : type == OP_Q ? N_TILE + ((op >> 13) & 127) : ID_PART + ((op >> 5) & 60) + ((op >> 19) & 3);
        const uint32_t v = type == OP_O ? 1 : P.info[id] & 7;
        mbar_wait_slow<PUBNS>(odone0 + 8 * pc, 0);
        flag_set(flag + 2 * id, v);
        if (type == OP_O && (op & P_WIDE)) flag_set(flag + 2 * id + 2, v);
      }
    } else if (wid == 10) {
      int i = threadIdx.x & 31;
      uint32_t e = i < 8 ? P.prog[role].ev[i] : 0;
      for (uint32_t n = 0; __any_sync(0xffffffffu, e); n++) {
        unsigned int* f = ptr_add(flag, 8 * (e & 1023));
        const bool ok = e && flag_peek(f) - 1 < ((e & E_FREE) ? 1 : 7);
        if (ok) {
          mbar_arrive(ev0 + 8 * i);
          if (e & (E_FREE | E_LAST)) flag_dec(f);
          i += 8;
          e = i < MAX_EV ? P.prog[role].ev[i] : 0;
        }
        asm volatile("{\n.reg .pred p;\nsetp.ge.u32 p, %0, 0x400000;\n@p trap;\n}\n" ::"r"(n));
        if (!__any_sync(0xffffffffu, ok)) __nanosleep(WATNS);
      }
    } else if (threadIdx.x == 352) {
      uint32_t items = 0;
      auto read = [&](int id) {
        if (!(P.info[id] & I_NEXT)) return;
        wait_progress(progress, items);
        flag_dec(flag + 2 * id);
      };
      for (int pc = 0;; pc++) {
        const uint32_t op = prog[pc];
        const int type = op & 3;
        if (type == OP_END) break;
        if (type == OP_O) {
          const int n = (op >> 13) & 63;
#pragma unroll 1
          for (int i = 0; i < n; i++) {
            items += (op & P_WIDE) && i == n - TAIL ? 3 * TAIL + 3 : 3;
            read(((op >> 2) & 511) + i);
          }
        } else if (type == OP_A) {
          if (op & F_PARK) { items++; read(N_TILE + ((op >> 13) & 127)); }
          items += 32;
        } else {
          items += 10;
        }
      }
    }
    __syncwarp();
    asm volatile("barrier.cluster.arrive.relaxed;\nbarrier.cluster.wait;" ::: "memory");
  }
}

typedef CUresult (*EncodeFn)(CUtensorMap*, CUtensorMapDataType, cuuint32_t, void*, const cuuint64_t*, const cuuint64_t*,
                             const cuuint32_t*, const cuuint32_t*, CUtensorMapInterleave, CUtensorMapSwizzle,
                             CUtensorMapL2promotion, CUtensorMapFloatOOBfill);

void encode(EncodeFn fn, CUtensorMap* m, const void* ptr, int rank, const cuuint64_t* dims, const cuuint64_t* strides,
            const cuuint32_t* box, CUtensorMapSwizzle swz) {
  const cuuint32_t es[5] = {1, 1, 1, 1, 1};
  CUresult r = fn(m, CU_TENSOR_MAP_DATA_TYPE_BFLOAT16, rank, const_cast<void*>(ptr), dims, strides, box, es,
                  CU_TENSOR_MAP_INTERLEAVE_NONE, swz, CU_TENSOR_MAP_L2_PROMOTION_L2_128B, CU_TENSOR_MAP_FLOAT_OOB_FILL_NONE);
  if (r != CUDA_SUCCESS) fprintf(stderr, "cuTensorMapEncodeTiled failed: %d\n", (int)r);
}

struct Op { int type, flags, id, n, quarter, park, item0, items; double t0, t1; };
struct Use { double ready, gate, need, freed; int readers, slot, prev; bool next; };
struct PlanStats { double end, slack, park_slack; int slots, parks; };

bool plan(const char* const* text, int n_pair, int phase, Params& P, PlanStats* stats = nullptr) {
  constexpr double T_Q = 7900, T_A = 24850, T_U = 26300, T_O = 1920, T_RUN = 800, T_WIDE = 1900, AHEAD = 3500, PUBLISH = 1500;
  const double margin = 256.0 * ((P.dbg >> 8) & 255);
  static Op op[N_CL][MAX_OPS];
  static Use use[ID_PART];
  int n_op[N_CL], covered[N_TEAM] = {}, finals[N_TEAM] = {};
  auto hex = [](char c) { return c <= '9' ? c - '0' : c - 'a' + 10; };
  for (int i = 0; i < n_pair; i++)
    for (const char* s = text[i]; *s; s++)
      if (*s == 'J') { if (covered[hex(s[1])]) return false; covered[hex(s[1])] = 10 * (s[2] - '0') + s[3] - '0'; }
  for (int c = 0; c < 2 * n_pair; c++) {
    int n = 0, items = 0;
    double t = 0;
    auto add = [&](int type, int flags, int id, int heads, int quarter, int its, double dt) {
      if (n < MAX_OPS) op[c][n] = {type, flags, id, heads, quarter, 0, items, its, t, t + dt};
      n++; items += its; t += dt;
    };
    for (const char* s = text[c >> 1]; *s; s++) {
      const int tm = hex(s[1]) & 15, nj = covered[tm];
      if (*s == 'N') { add(OP_Q, 0, 0, 0, 0, 10, T_Q); add(OP_A, 0, 0, 0, 0, 32, T_A); }
      if (*s == 'P') add(OP_Q, F_PARK, 0, 0, 0, 10, T_Q);
      if (*s == 'U') { if (n == 0 || n > MAX_OPS || op[c][n - 1].type != OP_A) return false; add(OP_A, F_PARK, 0, 0, 0, 33, T_U); }
      if (*s == 'J') { if (nj <= TAIL || nj > kH - 4) return false; add(OP_O, P_WIDE | P_ST, tm * kH, nj, 2 * (c & 1), 3 * (nj + TAIL), 2 * T_O * nj + T_WIDE); }
      if (*s == 'F') { if (s[2]) return false; add(OP_O, nj ? P_LD : 0, tm * kH + nj, kH - nj, finals[tm]++, 3 * (kH - nj), T_O * (kH - nj) + T_RUN); }
    }
    add(OP_END, 0, 0, 0, 0, 0, 0);
    if (n > MAX_OPS || op[c][0].type != OP_Q) return false;
    n_op[c] = n - 1;
  }
  for (int t = 0; t < N_TEAM; t++) if (finals[t] != 4) return false;
  for (int i = 0; i < ID_PART; i++) use[i] = {0, 0, 1e18, 0, 0, 0, 0, false};
  struct Ref { double t; Op* o; int id; };
  static Ref att[N_TILE + 1], dem[N_TILE], prk[MAX_PARK + 1], unp[MAX_PARK + 1], wr[ID_PART];
  int n_att = 0, n_prk = 0, n_unp = 0;
  auto ready = [&](const Op* o) {
    const int nt = o[1].type;
    return o->t1 + (nt == OP_Q ? 6100 : nt == OP_O ? 3900 : 1500) + PUBLISH;
  };
  for (int c = 0; c < 2 * n_pair; c++)
    for (Op* o = op[c]; o->type != OP_END; o++) {
      if (o->type == OP_A) { att[n_att] = {ready(o), o, 0}; if (++n_att > N_TILE) return false; }
      if (o->type == OP_A && o->flags) { unp[n_unp] = {o->t0 - AHEAD, o, 0}; if (++n_unp > MAX_PARK) return false; }
      if (o->type == OP_Q && o->flags) { prk[n_prk] = {ready(o), o, 0}; if (++n_prk > MAX_PARK) return false; }
      for (int i = 0; o->type == OP_O && i < o->n; i++) {
        const int nw = (o->flags & P_WIDE) ? o->n - TAIL : 0;
        Use& u = use[o->id + i];
        const double t = o->t0 + T_O * (i + (i < nw ? i : nw));
        if (t - AHEAD < u.need) u.need = t - AHEAD;
        const double f = t + T_O * (i < nw ? 2 : nw ? 1 + TAIL : 1) + PUBLISH;
        if (f > u.freed) u.freed = f;
        u.readers++;
      }
    }
  if (n_att != N_TILE || n_prk != n_unp) return false;
  auto sort = [](Ref* r, int n) {
    for (int i = 1; i < n; i++)
      for (int j = i; j > 0 && r[j].t < r[j - 1].t; j--) { Ref x = r[j]; r[j] = r[j - 1]; r[j - 1] = x; }
  };
  for (int i = 0; i < N_TILE; i++) { const int id = (i & 15) * kH + (i >> 4); dem[i] = {use[id].need, nullptr, id}; }
  sort(att, n_att); sort(dem, N_TILE); sort(prk, n_prk); sort(unp, n_unp);
  PlanStats st = {0, 1e18, 1e18, 0, n_prk};
  int n_wr = 0;
  for (int i = 0; i < N_TILE; i++) {
    Op* o = att[i].o;
    o->id = dem[i].id;
    if (!o->flags) o[-1].id = o->id;
    if (dem[i].t - att[i].t < st.slack) st.slack = dem[i].t - att[i].t;
    wr[n_wr++] = {o->t1 - 2 * AHEAD, o, o->id};
  }
  for (int i = 0; i < n_prk; i++) {
    prk[i].o->id = unp[i].o->id;
    prk[i].o->park = unp[i].o->park = i;
    use[N_TILE + i].freed = unp[i].o->t0 + 2 * PUBLISH;
    use[N_TILE + i].readers = 1;
    if (unp[i].t - prk[i].t < st.park_slack) st.park_slack = unp[i].t - prk[i].t;
    wr[n_wr++] = {prk[i].o->t1 - 2 * AHEAD, prk[i].o, N_TILE + i};
  }
  for (int c = 0; c < 2 * n_pair; c++)
    for (int d = 0; d < 2 * n_pair; d++)
      for (Op *f = &op[c][n_op[c] - 1], *o = op[d]; f->type == OP_O && o->type != OP_END; o++)
        if (o->type == OP_O && (o->flags & P_ST) && o->id / kH == f->id / kH) {
          if (f->t0 - o->t1 > 4096.0 * ((P.dbg >> 16) & 255)) f->flags |= P_PRE;
          const double slack = f->t0 + ((f->flags & P_PRE) ? 0 : (f->n - 2) * T_O) - AHEAD - ready(o);
          if (slack < st.park_slack) st.park_slack = slack;
        }
  sort(wr, n_wr);
  int holder[N_TILE];
  for (int i = 0; i < n_wr; i++) {
    int best = -1;
    for (int sl = 0; sl < st.slots; sl++)
      if (use[holder[sl]].freed + margin <= wr[i].t && (best < 0 || (use[holder[sl]].freed < use[holder[best]].freed) != ((P.dbg & 32) != 0))) best = sl;
    Use& u = use[wr[i].id];
    if (best >= 0) { u.prev = holder[best]; use[u.prev].next = true; wr[i].o->flags |= P_GATE; }
    else if (st.slots == N_TILE) return false;
    else best = st.slots++;
    u.slot = best;
    holder[best] = wr[i].id;
  }
  {
    int pos[N_CL] = {}, flag[ID_PART + 4 * N_TEAM] = {}, seen[ID_PART] = {};
    for (bool moved = true; moved;) {
      moved = false;
      for (int c = 0; c < 2 * n_pair; c++) {
        const int total = op[c][n_op[c]].item0;
        for (; pos[c] < total + NBAR; pos[c]++, moved = true) {
          bool ok = true;
          for (const Op* o = op[c]; o->type != OP_END; o++) {
            const int k = pos[c] - o->item0, own = o->type == OP_A ? o->id : N_TILE + o->park;
            if (k < 0 || k >= o->items) continue;
            if (o->type == OP_O) ok = (k >= 3 * o->n || flag[o->id + k / 3]) && (k != ((o->flags & P_PRE) ? 0 : 3 * o->n - 6) || !(o->flags & P_LD) || flag[ID_PART + o->id / kH * 4 + o->quarter]);
            else if (k == o->items - 1 && (o->flags & P_GATE)) ok = seen[use[own].prev] == use[use[own].prev].readers;
            else if (k == 0 && o->type == OP_A && (o->flags & F_PARK)) ok = flag[N_TILE + o->park];
          }
          if (!ok) break;
          for (const Op* o = op[c]; o->type != OP_END; o++) {
            if (pos[c] == o->item0 + o->items + (o[1].type == OP_Q ? 7 : 5)) {
              if (o->type == OP_A) flag[o->id] = 1;
              if (o->type == OP_Q && (o->flags & F_PARK)) flag[N_TILE + o->park] = 1;
              if (o->type == OP_O && (o->flags & P_ST)) flag[ID_PART + o->id / kH * 4 + o->quarter] = flag[ID_PART + o->id / kH * 4 + o->quarter + 1] = 1;
            }
            const int k = pos[c] - NBAR - o->item0, nw = (o->flags & P_WIDE) ? o->n - TAIL : o->n;
            if (k == 0 && o->type == OP_A && (o->flags & F_PARK)) seen[N_TILE + o->park]++;
            if (o->type == OP_O && k >= 0 && k % 3 == 2 && (k / 3 < nw || (k / 3 >= o->n && k / 3 < 2 * o->n - nw))) seen[o->id + (k / 3 < nw ? k / 3 : k / 3 - TAIL)]++;
          }
        }
      }
    }
    for (int c = 0; c < 2 * n_pair; c++) if (pos[c] < op[c][n_op[c]].item0 + NBAR) return false;
  }
  for (int c = 0; c < 2 * n_pair; c++) {
    uint32_t items = 0, cur = 0, pend = 0;
    int n = 0, ev = 0;
    auto item = [&](uint32_t bytes, int count) {
      for (int i = 0; i < count; i++) { if (cur + bytes > RING) cur = 0; cur += bytes; items++; }
    };
    auto event = [&](uint32_t e) { if (ev < MAX_EV) P.prog[c].ev[ev] = e | E_ON; ev++; };
    for (const Op* o = op[c];; o++) {
      if (o->type != OP_END && phase && (o->type == OP_O) != (phase == 2)) continue;
      uint32_t cw = o->type | (items % NBAR) << 15 | ((items / NBAR) & 1) << 19 | (cur >> 12) << 20 | pend, pw = o->type | o->id << 2 | o->flags;
      const int ps = use[N_TILE + o->park].slot;
      pend = 0;
      if (o->type == OP_O) {
        const bool wide = o->flags & P_WIDE;
        cw |= o->n << 2 | (o->id / kH * 4 + o->quarter + wide) << 8 | (wide ? C_WIDE : 0) | ((o->flags & P_LD) ? C_LD : 0);
        pw |= o->n << 13 | o->quarter << 19;
        if (wide) item(SZ_W, 3 * (o->n - TAIL));
        for (int k = 0; k < (wide ? 6 * TAIL : 3 * o->n); k++) item((o->flags & P_LD) && k >= 3 * o->n - 5 ? SZ_OL : SZ_O, 1);
        if (wide) pend = C_PEND | ((P.dbg & 8) ? C_SOON : 0);
        for (int i = 0; i < o->n; i++) {
          if (i == ((o->flags & P_PRE) ? 0 : o->n - 2) && (o->flags & P_LD)) event((ID_PART + o->id / kH * 4 + o->quarter) | E_LAST);
          event((o->id + i) | (use[o->id + i].next ? 0 : E_LAST));
        }
      } else if (o->type != OP_END) {
        const bool parks = o->type == OP_Q && (o->flags & F_PARK);
        cw |= (parks ? ps : use[o->id].slot) << 2 | (o->flags & F_PARK);
        if (o->flags & F_PARK) pw |= o->park << 13 | ps << 20;
        if (o->type == OP_Q) item(SZ_Q, 10);
        else { if (o->flags & F_PARK) { item(SZ_PARK, 1); event((N_TILE + o->park) | (use[N_TILE + o->park].next ? 0 : E_LAST)); } item(SZ_KV, 32); }
        if (parks || o->type == OP_A) pend = C_PEND | ((P.dbg & 16) ? 0 : C_SOON);
        if (o->flags & P_GATE) event(use[parks ? N_TILE + o->park : o->id].prev | E_FREE);
      }
      P.prog[c].c[n] = cw; P.prog[c].p[n++] = pw;
      if (o->type == OP_END) { if (o->t0 > st.end) st.end = o->t0; break; }
    }
    if (ev > MAX_EV) return false;
    while (ev < MAX_EV) P.prog[c].ev[ev++] = 0;
    while (n < MAX_OPS) { P.prog[c].c[n] = OP_END; P.prog[c].p[n++] = OP_END; }
    P.first[c] = (uint16_t)(P.prog[c].p[0] & 2047);
  }
  for (int i = 0; i < ID_PART; i++) {
    if (i < N_TILE) P.slot[i] = use[i].slot;
    P.info[i] = (use[i].readers + use[i].next) | (use[i].next ? I_NEXT : 0);
  }
  if (stats) *stats = st;
  return true;
}

const char* const kPrograms[N_CL / 2] = {
  "NNNNNNNNNF4", "NNUNNNNNNF6", "NUNNJf17NNNF8", "PNNNNNNNNNFe", "PNJ121NNNNNF5", "NNNNNNNNNFa",
  "NNNNNUNNNF6", "NNNNNNNNNF1", "NNNNNNNNNF4", "NUNNNJe26NF8", "PNJ227NNNNFc", "PPNJ717NNNNUNF2",
  "NUNNJc13NNNNF2", "PNNJ325NNNNF3", "NUNUNJ926NFd", "NNNNNNNNNFa", "PNJ421NNNNNFf", "NUNNNJd16NNF7",
  "PNNNNNNNNNF3", "NNUJ618Jb23NFd", "NNNNNNNNNFb", "PNJ517NNNNNNFe", "NNNNNNNNNF0", "PNJ021NNNNNF5",
  "PNNNNNNNNN", "NUNNNJ819NNFb", "PNNNNNNNNNF9", "NNNNNNNNNF0", "PNNNNNNNNNF9", "NNNNNNNNNF1",
  "NNUNNNNNNFf", "NNNNNJa21NFc", "NUNNNNNNNF7",
};

const char* const* bench_programs() {
  return kPrograms;
}

}

extern "C" void kernel_launch(void* const* d_in, const int* in_sizes, int n_in, void* d_out, int out_size) {
  (void)in_sizes; (void)n_in; (void)out_size;
  static EncodeFn fn = nullptr;
  static int n_clusters = 0;
  if (!fn) {
    cudaDriverEntryPointQueryResult qr;
    void* f = nullptr;
    cudaGetDriverEntryPoint("cuTensorMapEncodeTiled", &f, cudaEnableDefault, &qr);
    fn = (EncodeFn)f;
    cudaFuncSetAttribute(fused_kernel, cudaFuncAttributeMaxDynamicSharedMemorySize, SMEM_BYTES);
    cudaLaunchConfig_t cfg = {};
    cfg.gridDim = dim3(132); cfg.blockDim = dim3(384); cfg.dynamicSmemBytes = SMEM_BYTES;
    cudaLaunchAttribute at[1];
    at[0].id = cudaLaunchAttributeClusterDimension; at[0].val.clusterDim.x = 2; at[0].val.clusterDim.y = 1; at[0].val.clusterDim.z = 1;
    cfg.attrs = at; cfg.numAttrs = 1;
    if (cudaOccupancyMaxActiveClusters(&n_clusters, fused_kernel, &cfg) != cudaSuccess || n_clusters < 1) n_clusters = 1;
    (void)cudaGetLastError();
  }
  static Params P;
  const CUtensorMapSwizzle S128 = CU_TENSOR_MAP_SWIZZLE_128B, S64 = CU_TENSOR_MAP_SWIZZLE_64B;
  for (int blk = 0; blk < 2; blk++) {
    void* const* in = d_in + 5 * blk;
    { const cuuint64_t d[] = {kD, kB * kSq}, s[] = {kD * 2}; const cuuint32_t b[] = {64, 128};
      encode(fn, &P.x[blk], in[0], 2, d, s, b, S128); }
    { const cuuint64_t d[] = {64, 8, 3, (cuuint64_t)kB * kH * kSk / 8}, s[] = {kDh * 2, 128, 8 * kDh * 2}; const cuuint32_t b[] = {64, 8, 3, 8};
      encode(fn, &P.k[blk], in[1], 4, d, s, b, S128);
      encode(fn, &P.v[blk], in[2], 4, d, s, b, S128); }
    { const cuuint64_t d[] = {64, kD, kHD / 64}, s[] = {kHD * 2, 128}; const cuuint32_t b[] = {64, 64, 3};
      encode(fn, &P.wq[blk], in[3], 3, d, s, b, S128); }
    { const cuuint64_t d[] = {32, 2, kHD / 8, 4, kD / 32}, s[] = {kD * 2, 8 * kD * 2, 2 * kD * 2, 64}; const cuuint32_t b[] = {32, 2, 4, 4, 5};
      encode(fn, &P.wo[blk], in[4], 5, d, s, b, S64); }
  }
  { const cuuint64_t d[] = {32, kB * kSq, 2 * kD / 32}, s[] = {2 * kD * 2, 64}; const cuuint32_t b[] = {32, 16, 1};
    encode(fn, &P.out, d_out, 3, d, s, b, S64); }

  P.dbg = DBG_DEFAULT;
  if (n_clusters >= N_CL && plan(bench_programs(), N_CL / 2, 0, P)) {
    fused_kernel<<<2 * N_CL, 384, SMEM_BYTES>>>(P);
  } else {
    char buf[2 * N_TEAM][16];
    const char* text[2 * N_TEAM];
    for (int i = 0; i < 2 * N_TEAM; i++) { snprintf(buf[i], sizeof(buf[i]), "NNNNNNNNF%x", i / 2); text[i] = buf[i]; }
    for (int phase = 1; phase <= 2; phase++) {
      plan(text, 2 * N_TEAM, phase, P);
      fused_kernel<<<8 * N_TEAM, 384, SMEM_BYTES>>>(P);
    }
  }
}
```

```cpp
#include <cuda_runtime.h>
#include <cuda_bf16.h>
#include <cuda.h>
#include <stdint.h>
#include <stdio.h>

namespace {

constexpr int kB = 8, kSq = 256, kD = 640, kH = 32, kSk = 1024, kDh = 192;
constexpr int kHD = kH * kDh;
constexpr uint32_t RING = 224 * 1024;
constexpr uint32_t SZ_KV = 24576;
constexpr uint32_t SZ_Q = 16384 + 24576;
constexpr uint32_t SZ_O = 16384 + 20480;
constexpr uint32_t SZ_W = 16384 + 40960;
constexpr uint32_t SZ_PARK = 49152;
constexpr uint32_t SZ_OL = SZ_O + 8192;
constexpr int NBAR = 10;
constexpr int EARLY = 3;
#define XTAIL 2
constexpr int TAIL = XTAIL;
constexpr uint32_t KV_CH = 64, KV_SBO = 3072;
constexpr int SMEM_BYTES = RING + 1024 + 1024;
constexpr int N_TEAM = 16, N_CL = 66, MAX_OPS = 24, MAX_EV = 80, N_TILE = N_TEAM * kH, MAX_PARK = 128, ID_PART = N_TILE + MAX_PARK;
enum : uint32_t { OP_END = 0, OP_Q = 1, OP_A = 2, OP_O = 3, F_PARK = 1 << 11,
                  C_WIDE = 1 << 14, C_PEND = 1 << 26, C_SOON = 1 << 28,
                  P_GATE = 1 << 12, P_WIDE = 1 << 11, P_LD = 1 << 12, P_ST = 1 << 21, P_PRE = 1 << 22, I_NEXT = 8, E_ON = 1 << 15, E_FREE = 1 << 14, E_LAST = 1 << 13, E_DRAW = 1 << 12, E_JOB = 1 << 11 };

#define QDRAIN 0x54732710u
#define TRYNS 1500
#define SKEW 3
#define PUBNS 100
#define WATNS 100
constexpr uint32_t DBG_DEFAULT = 0x101833;

struct alignas(64) Params {
  uint16_t first[96];
  CUtensorMap x[2], wq[2], k[2], v[2], wo[2], out;
  struct {
    uint32_t c[MAX_OPS];
    uint32_t p[MAX_OPS];
    uint16_t ev[MAX_EV];
  } prog[N_CL];
  uint32_t job[4 * N_TEAM];
  uint16_t slot[N_TILE];
  uint8_t info[ID_PART];
  uint32_t dbg;
};

__device__ uint4 g_t[N_TILE * 2 * 3072];
__device__ uint4 g_part[N_TEAM * 4 * 2 * 3072];
__device__ unsigned int g_flag[(ID_PART + N_TEAM * 4) * 2];
__device__ unsigned int g_ticket;

template <int TB, int TA = 0>
__device__ __forceinline__ void wgmma_ss_n64(float (&d)[32], uint64_t da, uint64_t db, int scale_d) {
  asm volatile("{\n.reg .pred p;\nsetp.ne.b32 p, %34, 0;\n"
    "wgmma.mma_async.sync.aligned.m64n64k16.f32.bf16.bf16 {%0, %1, %2, %3, %4, %5, %6, %7, %8, %9, %10, %11, %12, %13, %14, %15, %16, %17, %18, %19, %20, %21, %22, %23, %24, %25, %26, %27, %28, %29, %30, %31}, %32, %33, p, 1, 1, %35, %36;\n}\n"
    : "+f"(d[0]), "+f"(d[1]), "+f"(d[2]), "+f"(d[3]), "+f"(d[4]), "+f"(d[5]), "+f"(d[6]), "+f"(d[7]), "+f"(d[8]), "+f"(d[9]), "+f"(d[10]), "+f"(d[11]), "+f"(d[12]), "+f"(d[13]), "+f"(d[14]), "+f"(d[15]), "+f"(d[16]), "+f"(d[17]), "+f"(d[18]), "+f"(d[19]), "+f"(d[20]), "+f"(d[21]), "+f"(d[22]), "+f"(d[23]), "+f"(d[24]), "+f"(d[25]), "+f"(d[26]), "+f"(d[27]), "+f"(d[28]), "+f"(d[29]), "+f"(d[30]), "+f"(d[31])
    : "l"(da), "l"(db), "r"(scale_d), "n"(TA), "n"(TB));
}
template <int TB>
__device__ __forceinline__ void wgmma_rs_n64(float (&d)[32], uint32_t a0, uint32_t a1, uint32_t a2, uint32_t a3, uint64_t db, int scale_d) {
  asm volatile("{\n.reg .pred p;\nsetp.ne.b32 p, %37, 0;\n"
    "wgmma.mma_async.sync.aligned.m64n64k16.f32.bf16.bf16 {%0, %1, %2, %3, %4, %5, %6, %7, %8, %9, %10, %11, %12, %13, %14, %15, %16, %17, %18, %19, %20, %21, %22, %23, %24, %25, %26, %27, %28, %29, %30, %31}, {%32, %33, %34, %35}, %36, p, 1, 1, %38;\n}\n"
    : "+f"(d[0]), "+f"(d[1]), "+f"(d[2]), "+f"(d[3]), "+f"(d[4]), "+f"(d[5]), "+f"(d[6]), "+f"(d[7]), "+f"(d[8]), "+f"(d[9]), "+f"(d[10]), "+f"(d[11]), "+f"(d[12]), "+f"(d[13]), "+f"(d[14]), "+f"(d[15]), "+f"(d[16]), "+f"(d[17]), "+f"(d[18]), "+f"(d[19]), "+f"(d[20]), "+f"(d[21]), "+f"(d[22]), "+f"(d[23]), "+f"(d[24]), "+f"(d[25]), "+f"(d[26]), "+f"(d[27]), "+f"(d[28]), "+f"(d[29]), "+f"(d[30]), "+f"(d[31])
    : "r"(a0), "r"(a1), "r"(a2), "r"(a3), "l"(db), "r"(scale_d), "n"(TB));
}
template <int TB, int TA = 0>
__device__ __forceinline__ void wgmma_ss_n160(float (&d)[80], uint64_t da, uint64_t db, int scale_d) {
  asm volatile("{\n.reg .pred p;\nsetp.ne.b32 p, %82, 0;\n"
    "wgmma.mma_async.sync.aligned.m64n160k16.f32.bf16.bf16 {%0, %1, %2, %3, %4, %5, %6, %7, %8, %9, %10, %11, %12, %13, %14, %15, %16, %17, %18, %19, %20, %21, %22, %23, %24, %25, %26, %27, %28, %29, %30, %31, %32, %33, %34, %35, %36, %37, %38, %39, %40, %41, %42, %43, %44, %45, %46, %47, %48, %49, %50, %51, %52, %53, %54, %55, %56, %57, %58, %59, %60, %61, %62, %63, %64, %65, %66, %67, %68, %69, %70, %71, %72, %73, %74, %75, %76, %77, %78, %79}, %80, %81, p, 1, 1, %83, %84;\n}\n"
    : "+f"(d[0]), "+f"(d[1]), "+f"(d[2]), "+f"(d[3]), "+f"(d[4]), "+f"(d[5]), "+f"(d[6]), "+f"(d[7]), "+f"(d[8]), "+f"(d[9]), "+f"(d[10]), "+f"(d[11]), "+f"(d[12]), "+f"(d[13]), "+f"(d[14]), "+f"(d[15]), "+f"(d[16]), "+f"(d[17]), "+f"(d[18]), "+f"(d[19]), "+f"(d[20]), "+f"(d[21]), "+f"(d[22]), "+f"(d[23]), "+f"(d[24]), "+f"(d[25]), "+f"(d[26]), "+f"(d[27]), "+f"(d[28]), "+f"(d[29]), "+f"(d[30]), "+f"(d[31]), "+f"(d[32]), "+f"(d[33]), "+f"(d[34]), "+f"(d[35]), "+f"(d[36]), "+f"(d[37]), "+f"(d[38]), "+f"(d[39]), "+f"(d[40]), "+f"(d[41]), "+f"(d[42]), "+f"(d[43]), "+f"(d[44]), "+f"(d[45]), "+f"(d[46]), "+f"(d[47]), "+f"(d[48]), "+f"(d[49]), "+f"(d[50]), "+f"(d[51]), "+f"(d[52]), "+f"(d[53]), "+f"(d[54]), "+f"(d[55]), "+f"(d[56]), "+f"(d[57]), "+f"(d[58]), "+f"(d[59]), "+f"(d[60]), "+f"(d[61]), "+f"(d[62]), "+f"(d[63]), "+f"(d[64]), "+f"(d[65]), "+f"(d[66]), "+f"(d[67]), "+f"(d[68]), "+f"(d[69]), "+f"(d[70]), "+f"(d[71]), "+f"(d[72]), "+f"(d[73]), "+f"(d[74]), "+f"(d[75]), "+f"(d[76]), "+f"(d[77]), "+f"(d[78]), "+f"(d[79])
    : "l"(da), "l"(db), "r"(scale_d), "n"(TA), "n"(TB));
}
template <int TB>
__device__ __forceinline__ void wgmma_rs_n160(float (&d)[80], uint32_t a0, uint32_t a1, uint32_t a2, uint32_t a3, uint64_t db, int scale_d) {
  asm volatile("{\n.reg .pred p;\nsetp.ne.b32 p, %85, 0;\n"
    "wgmma.mma_async.sync.aligned.m64n160k16.f32.bf16.bf16 {%0, %1, %2, %3, %4, %5, %6, %7, %8, %9, %10, %11, %12, %13, %14, %15, %16, %17, %18, %19, %20, %21, %22, %23, %24, %25, %26, %27, %28, %29, %30, %31, %32, %33, %34, %35, %36, %37, %38, %39, %40, %41, %42, %43, %44, %45, %46, %47, %48, %49, %50, %51, %52, %53, %54, %55, %56, %57, %58, %59, %60, %61, %62, %63, %64, %65, %66, %67, %68, %69, %70, %71, %72, %73, %74, %75, %76, %77, %78, %79}, {%80, %81, %82, %83}, %84, p, 1, 1, %86;\n}\n"
    : "+f"(d[0]), "+f"(d[1]), "+f"(d[2]), "+f"(d[3]), "+f"(d[4]), "+f"(d[5]), "+f"(d[6]), "+f"(d[7]), "+f"(d[8]), "+f"(d[9]), "+f"(d[10]), "+f"(d[11]), "+f"(d[12]), "+f"(d[13]), "+f"(d[14]), "+f"(d[15]), "+f"(d[16]), "+f"(d[17]), "+f"(d[18]), "+f"(d[19]), "+f"(d[20]), "+f"(d[21]), "+f"(d[22]), "+f"(d[23]), "+f"(d[24]), "+f"(d[25]), "+f"(d[26]), "+f"(d[27]), "+f"(d[28]), "+f"(d[29]), "+f"(d[30]), "+f"(d[31]), "+f"(d[32]), "+f"(d[33]), "+f"(d[34]), "+f"(d[35]), "+f"(d[36]), "+f"(d[37]), "+f"(d[38]), "+f"(d[39]), "+f"(d[40]), "+f"(d[41]), "+f"(d[42]), "+f"(d[43]), "+f"(d[44]), "+f"(d[45]), "+f"(d[46]), "+f"(d[47]), "+f"(d[48]), "+f"(d[49]), "+f"(d[50]), "+f"(d[51]), "+f"(d[52]), "+f"(d[53]), "+f"(d[54]), "+f"(d[55]), "+f"(d[56]), "+f"(d[57]), "+f"(d[58]), "+f"(d[59]), "+f"(d[60]), "+f"(d[61]), "+f"(d[62]), "+f"(d[63]), "+f"(d[64]), "+f"(d[65]), "+f"(d[66]), "+f"(d[67]), "+f"(d[68]), "+f"(d[69]), "+f"(d[70]), "+f"(d[71]), "+f"(d[72]), "+f"(d[73]), "+f"(d[74]), "+f"(d[75]), "+f"(d[76]), "+f"(d[77]), "+f"(d[78]), "+f"(d[79])
    : "r"(a0), "r"(a1), "r"(a2), "r"(a3), "l"(db), "r"(scale_d), "n"(TB));
}
template <int TB, int TA = 0>
__device__ __forceinline__ void wgmma_ss_n192(float (&d)[96], uint64_t da, uint64_t db, int scale_d) {
  asm volatile("{\n.reg .pred p;\nsetp.ne.b32 p, %98, 0;\n"
    "wgmma.mma_async.sync.aligned.m64n192k16.f32.bf16.bf16 {%0, %1, %2, %3, %4, %5, %6, %7, %8, %9, %10, %11, %12, %13, %14, %15, %16, %17, %18, %19, %20, %21, %22, %23, %24, %25, %26, %27, %28, %29, %30, %31, %32, %33, %34, %35, %36, %37, %38, %39, %40, %41, %42, %43, %44, %45, %46, %47, %48, %49, %50, %51, %52, %53, %54, %55, %56, %57, %58, %59, %60, %61, %62, %63, %64, %65, %66, %67, %68, %69, %70, %71, %72, %73, %74, %75, %76, %77, %78, %79, %80, %81, %82, %83, %84, %85, %86, %87, %88, %89, %90, %91, %92, %93, %94, %95}, %96, %97, p, 1, 1, %99, %100;\n}\n"
    : "+f"(d[0]), "+f"(d[1]), "+f"(d[2]), "+f"(d[3]), "+f"(d[4]), "+f"(d[5]), "+f"(d[6]), "+f"(d[7]), "+f"(d[8]), "+f"(d[9]), "+f"(d[10]), "+f"(d[11]), "+f"(d[12]), "+f"(d[13]), "+f"(d[14]), "+f"(d[15]), "+f"(d[16]), "+f"(d[17]), "+f"(d[18]), "+f"(d[19]), "+f"(d[20]), "+f"(d[21]), "+f"(d[22]), "+f"(d[23]), "+f"(d[24]), "+f"(d[25]), "+f"(d[26]), "+f"(d[27]), "+f"(d[28]), "+f"(d[29]), "+f"(d[30]), "+f"(d[31]), "+f"(d[32]), "+f"(d[33]), "+f"(d[34]), "+f"(d[35]), "+f"(d[36]), "+f"(d[37]), "+f"(d[38]), "+f"(d[39]), "+f"(d[40]), "+f"(d[41]), "+f"(d[42]), "+f"(d[43]), "+f"(d[44]), "+f"(d[45]), "+f"(d[46]), "+f"(d[47]), "+f"(d[48]), "+f"(d[49]), "+f"(d[50]), "+f"(d[51]), "+f"(d[52]), "+f"(d[53]), "+f"(d[54]), "+f"(d[55]), "+f"(d[56]), "+f"(d[57]), "+f"(d[58]), "+f"(d[59]), "+f"(d[60]), "+f"(d[61]), "+f"(d[62]), "+f"(d[63]), "+f"(d[64]), "+f"(d[65]), "+f"(d[66]), "+f"(d[67]), "+f"(d[68]), "+f"(d[69]), "+f"(d[70]), "+f"(d[71]), "+f"(d[72]), "+f"(d[73]), "+f"(d[74]), "+f"(d[75]), "+f"(d[76]), "+f"(d[77]), "+f"(d[78]), "+f"(d[79]), "+f"(d[80]), "+f"(d[81]), "+f"(d[82]), "+f"(d[83]), "+f"(d[84]), "+f"(d[85]), "+f"(d[86]), "+f"(d[87]), "+f"(d[88]), "+f"(d[89]), "+f"(d[90]), "+f"(d[91]), "+f"(d[92]), "+f"(d[93]), "+f"(d[94]), "+f"(d[95])
    : "l"(da), "l"(db), "r"(scale_d), "n"(TA), "n"(TB));
}
template <int TB>
__device__ __forceinline__ void wgmma_rs_n192(float (&d)[96], uint32_t a0, uint32_t a1, uint32_t a2, uint32_t a3, uint64_t db, int scale_d) {
  asm volatile("{\n.reg .pred p;\nsetp.ne.b32 p, %101, 0;\n"
    "wgmma.mma_async.sync.aligned.m64n192k16.f32.bf16.bf16 {%0, %1, %2, %3, %4, %5, %6, %7, %8, %9, %10, %11, %12, %13, %14, %15, %16, %17, %18, %19, %20, %21, %22, %23, %24, %25, %26, %27, %28, %29, %30, %31, %32, %33, %34, %35, %36, %37, %38, %39, %40, %41, %42, %43, %44, %45, %46, %47, %48, %49, %50, %51, %52, %53, %54, %55, %56, %57, %58, %59, %60, %61, %62, %63, %64, %65, %66, %67, %68, %69, %70, %71, %72, %73, %74, %75, %76, %77, %78, %79, %80, %81, %82, %83, %84, %85, %86, %87, %88, %89, %90, %91, %92, %93, %94, %95}, {%96, %97, %98, %99}, %100, p, 1, 1, %102;\n}\n"
    : "+f"(d[0]), "+f"(d[1]), "+f"(d[2]), "+f"(d[3]), "+f"(d[4]), "+f"(d[5]), "+f"(d[6]), "+f"(d[7]), "+f"(d[8]), "+f"(d[9]), "+f"(d[10]), "+f"(d[11]), "+f"(d[12]), "+f"(d[13]), "+f"(d[14]), "+f"(d[15]), "+f"(d[16]), "+f"(d[17]), "+f"(d[18]), "+f"(d[19]), "+f"(d[20]), "+f"(d[21]), "+f"(d[22]), "+f"(d[23]), "+f"(d[24]), "+f"(d[25]), "+f"(d[26]), "+f"(d[27]), "+f"(d[28]), "+f"(d[29]), "+f"(d[30]), "+f"(d[31]), "+f"(d[32]), "+f"(d[33]), "+f"(d[34]), "+f"(d[35]), "+f"(d[36]), "+f"(d[37]), "+f"(d[38]), "+f"(d[39]), "+f"(d[40]), "+f"(d[41]), "+f"(d[42]), "+f"(d[43]), "+f"(d[44]), "+f"(d[45]), "+f"(d[46]), "+f"(d[47]), "+f"(d[48]), "+f"(d[49]), "+f"(d[50]), "+f"(d[51]), "+f"(d[52]), "+f"(d[53]), "+f"(d[54]), "+f"(d[55]), "+f"(d[56]), "+f"(d[57]), "+f"(d[58]), "+f"(d[59]), "+f"(d[60]), "+f"(d[61]), "+f"(d[62]), "+f"(d[63]), "+f"(d[64]), "+f"(d[65]), "+f"(d[66]), "+f"(d[67]), "+f"(d[68]), "+f"(d[69]), "+f"(d[70]), "+f"(d[71]), "+f"(d[72]), "+f"(d[73]), "+f"(d[74]), "+f"(d[75]), "+f"(d[76]), "+f"(d[77]), "+f"(d[78]), "+f"(d[79]), "+f"(d[80]), "+f"(d[81]), "+f"(d[82]), "+f"(d[83]), "+f"(d[84]), "+f"(d[85]), "+f"(d[86]), "+f"(d[87]), "+f"(d[88]), "+f"(d[89]), "+f"(d[90]), "+f"(d[91]), "+f"(d[92]), "+f"(d[93]), "+f"(d[94]), "+f"(d[95])
    : "r"(a0), "r"(a1), "r"(a2), "r"(a3), "l"(db), "r"(scale_d), "n"(TB));
}

__device__ __forceinline__ uint32_t smem_u32(const void* p) { return (uint32_t)__cvta_generic_to_shared(p); }
__device__ __forceinline__ void wg_fence() { asm volatile("wgmma.fence.sync.aligned;" ::: "memory"); }
__device__ __forceinline__ void wg_commit() { asm volatile("wgmma.commit_group.sync.aligned;" ::: "memory"); }
template <int N> __device__ __forceinline__ void wg_wait() { asm volatile("wgmma.wait_group.sync.aligned %0;" ::"n"(N) : "memory"); }
__device__ __forceinline__ void sched_fence(uint32_t& keep, bool never) {
  asm volatile("{\n.reg .pred p;\nsetp.ne.b32 p, %1, 0;\n@p mov.u32 %0, %%clock;\n}\n" : "+r"(keep) : "r"((int)never) : "memory");
}
template <int N> __device__ __forceinline__ void fence_regs(float (&r)[N]) {
#pragma unroll
  for (int i = 0; i < N; i++) asm volatile("" : "+f"(r[i])::"memory");
}
template <int N> __device__ __forceinline__ void undefine(float (&r)[N]) {
#pragma unroll
  for (int i = 0; i < N; i++) asm volatile("" : "=f"(r[i]));
}
template <int N> __device__ __forceinline__ void fence_regs(uint32_t (&r)[N]) {
#pragma unroll
  for (int i = 0; i < N; i++) asm volatile("" : "+r"(r[i])::"memory");
}
__device__ __forceinline__ uint64_t mk_desc(uint32_t a16, uint32_t lbo, uint32_t sbo, uint32_t swz) {
  uint64_t d;
  asm("mov.b64 %0, {%1, %2};" : "=l"(d) : "r"(a16 + ((lbo >> 4) << 16)), "r"((sbo >> 4) | (swz << 30)));
  return d;
}
__device__ __forceinline__ void mbar_init(uint32_t bar, uint32_t cnt) {
  asm volatile("mbarrier.init.shared::cta.b64 [%0], %1;" ::"r"(bar), "r"(cnt) : "memory");
}
__device__ __forceinline__ void mbar_expect(uint32_t bar, uint32_t tx) {
  asm volatile("mbarrier.arrive.expect_tx.shared::cta.b64 _, [%0], %1;" ::"r"(bar), "r"(tx) : "memory");
}
__device__ __forceinline__ bool mbar_test(uint32_t bar, uint32_t ph) {
  uint32_t ok;
  asm volatile("{\n.reg .pred p;\nmbarrier.test_wait.parity.shared::cta.b64 p, [%1], %2;\nselp.u32 %0, 1, 0, p;\n}\n"
               : "=r"(ok) : "r"(bar), "r"(ph) : "memory");
  return ok;
}
__device__ __forceinline__ bool mbar_try(uint32_t bar, uint32_t ph, uint32_t ns) {
  uint32_t ok;
  asm volatile("{\n.reg .pred p;\nmbarrier.try_wait.parity.shared::cta.b64 p, [%1], %2, %3;\nselp.u32 %0, 1, 0, p;\n}\n"
               : "=r"(ok) : "r"(bar), "r"(ph), "r"(ns) : "memory");
  return ok;
}
__device__ __forceinline__ void mbar_wait(uint32_t bar, uint32_t ph) {
  asm volatile("{\n.reg .pred p;\n.reg .u32 n;\nmov.u32 n, 0;\n"
               "LOOP:\nmbarrier.try_wait.parity.shared::cta.b64 p, [%0], %1;\n@p bra DONE;\n"
               "add.u32 n, n, 1;\nsetp.lt.u32 p, n, 0x1000000;\n@p bra LOOP;\ntrap;\n"
               "DONE:\n}\n" ::"r"(bar), "r"(ph) : "memory");
}
template <int NS> __device__ __forceinline__ void mbar_wait_slow(uint32_t bar, uint32_t ph) {
  asm volatile("{\n.reg .pred p;\n.reg .u32 n;\nmov.u32 n, 0;\n"
               "LOOP:\nmbarrier.test_wait.parity.shared::cta.b64 p, [%0], %1;\n@p bra DONE;\n"
               "nanosleep.u32 %2;\nadd.u32 n, n, 1;\nsetp.lt.u32 p, n, 0x400000;\n@p bra LOOP;\ntrap;\n"
               "DONE:\n}\n" ::"r"(bar), "r"(ph), "n"(NS) : "memory");
}
__device__ __forceinline__ void mbar_arrive_cluster_if(bool on, uint32_t addr) {
  asm volatile("{\n.reg .pred p;\nsetp.ne.b32 p, %1, 0;\n@p mbarrier.arrive.shared::cluster.b64 _, [%0];\n}\n" ::"r"(addr), "r"((int)on) : "memory");
}
__device__ __forceinline__ void tma2d(uint32_t dst, const CUtensorMap* m, uint32_t bar, int c0, int c1) {
  asm volatile("cp.async.bulk.tensor.2d.shared::cluster.global.mbarrier::complete_tx::bytes [%0], [%1, {%3, %4}], [%2];"
               ::"r"(dst), "l"(m), "r"(bar), "r"(c0), "r"(c1) : "memory");
}
__device__ __forceinline__ void tma3d(uint32_t dst, const CUtensorMap* m, uint32_t bar, int c0, int c1, int c2) {
  asm volatile("cp.async.bulk.tensor.3d.shared::cluster.global.mbarrier::complete_tx::bytes [%0], [%1, {%3, %4, %5}], [%2];"
               ::"r"(dst), "l"(m), "r"(bar), "r"(c0), "r"(c1), "r"(c2) : "memory");
}
__device__ __forceinline__ void tma3d_mc(uint32_t dst, const CUtensorMap* m, uint32_t bar, int c0, int c1, int c2) {
  asm volatile("cp.async.bulk.tensor.3d.shared::cluster.global.mbarrier::complete_tx::bytes.multicast::cluster"
               " [%0], [%1, {%3, %4, %5}], [%2], %6;"
               ::"r"(dst), "l"(m), "r"(bar), "r"(c0), "r"(c1), "r"(c2), "h"((uint16_t)3) : "memory");
}
__device__ __forceinline__ void tma3d_store(const CUtensorMap* m, uint32_t src, int c0, int c1, int c2) {
  asm volatile("cp.async.bulk.tensor.3d.global.shared::cta.bulk_group [%0, {%2, %3, %4}], [%1];"
               ::"l"(m), "r"(src), "r"(c0), "r"(c1), "r"(c2) : "memory");
}
__device__ __forceinline__ void bar_sync(int id, int n) { asm volatile("bar.sync %0, %1;" ::"r"(id), "r"(n) : "memory"); }
__device__ __forceinline__ uint32_t pack_bf16(float lo, float hi) {
  uint32_t r;
  asm("cvt.rn.bf16x2.f32 %0, %1, %2;" : "=r"(r) : "f"(hi), "f"(lo));
  return r;
}
__device__ __forceinline__ float ex2(float x) {
  float y;
  asm("ex2.approx.ftz.f32 %0, %1;" : "=f"(y) : "f"(x));
  return y;
}
__device__ __forceinline__ float rcp(float x) {
  float y;
  asm("rcp.approx.ftz.f32 %0, %1;" : "=f"(y) : "f"(x));
  return y;
}
__device__ __forceinline__ void stsm4(uint32_t addr, uint32_t a, uint32_t b, uint32_t c, uint32_t d) {
  asm volatile("stmatrix.sync.aligned.m8n8.x4.shared.b16 [%0], {%1, %2, %3, %4};" ::"r"(addr), "r"(a), "r"(b), "r"(c), "r"(d) : "memory");
}

__device__ __forceinline__ void tma4d_mc_hint(uint32_t dst, const CUtensorMap* m, uint32_t bar, int c3, uint64_t pol) {
  asm volatile("cp.async.bulk.tensor.4d.shared::cluster.global.mbarrier::complete_tx::bytes.multicast::cluster.L2::cache_hint"
               " [%0], [%1, {%3, %3, %3, %4}], [%2], %5, %6;"
               ::"r"(dst), "l"(m), "r"(bar), "r"(0), "r"(c3), "h"((uint16_t)3), "l"(pol) : "memory");
}
__device__ __forceinline__ void tma5d_mc(uint32_t dst, const CUtensorMap* m, uint32_t bar, int c2, int c4) {
  asm volatile("cp.async.bulk.tensor.5d.shared::cluster.global.mbarrier::complete_tx::bytes.multicast::cluster"
               " [%0], [%1, {%3, %3, %4, %3, %5}], [%2], %6;"
               ::"r"(dst), "l"(m), "r"(bar), "r"(0), "r"(c2), "r"(c4), "h"((uint16_t)3) : "memory");
}
__device__ __forceinline__ void bulk_load_hint(uint32_t dst, const void* src, uint32_t bytes, uint32_t bar, uint64_t pol) {
  asm volatile("cp.async.bulk.shared::cluster.global.mbarrier::complete_tx::bytes.L2::cache_hint [%0], [%1], %2, [%3], %4;"
               ::"r"(dst), "l"(src), "r"(bytes), "r"(bar), "l"(pol) : "memory");
}
__device__ __forceinline__ void stg128_hint(void* p, uint32_t a, uint32_t b, uint32_t c, uint32_t d, uint64_t pol) {
  asm volatile("st.global.L2::cache_hint.v4.b32 [%0], {%1, %2, %3, %4}, %5;" ::"l"(p), "r"(a), "r"(b), "r"(c), "r"(d), "l"(pol) : "memory");
}
__device__ __forceinline__ void stg2_if(bool on, void* p, uint32_t a, uint32_t b, uint32_t c, uint32_t d, uint32_t e, uint32_t f,
                                        uint32_t g, uint32_t h, uint64_t pol) {
  asm volatile("{\n.reg .pred p;\nsetp.ne.b32 p, %10, 0;\n"
               "@p st.global.L2::cache_hint.v4.b32 [%0], {%1, %2, %3, %4}, %9;\n"
               "@p st.global.L2::cache_hint.v4.b32 [%0 + 512], {%5, %6, %7, %8}, %9;\n}\n"
               ::"l"(p), "r"(a), "r"(b), "r"(c), "r"(d), "r"(e), "r"(f), "r"(g), "r"(h), "l"(pol), "r"((int)on) : "memory");
}
__device__ __forceinline__ uint64_t make_policy(bool first) {
  uint64_t pf, pn;
  asm("createpolicy.fractional.L2::evict_first.b64 %0, 1.0;" : "=l"(pf));
  asm("createpolicy.fractional.L2::evict_normal.b64 %0, 1.0;" : "=l"(pn));
  return first ? pf : pn;
}
__device__ __forceinline__ bool elect() {
  uint32_t ok;
  asm volatile("{\n.reg .pred p;\nelect.sync _|p, 0xffffffff;\nselp.u32 %0, 1, 0, p;\n}\n" : "=r"(ok));
  return ok;
}
__device__ __forceinline__ void mbar_arrive(uint32_t bar) {
  asm volatile("mbarrier.arrive.shared::cta.b64 _, [%0];" ::"r"(bar) : "memory");
}
__device__ __forceinline__ void mbar_arrive_if(bool on, uint32_t bar) {
  asm volatile("{\n.reg .pred p;\nsetp.ne.b32 p, %1, 0;\n@p mbarrier.arrive.shared::cta.b64 _, [%0];\n}\n" ::"r"(bar), "r"((int)on) : "memory");
}
__device__ __forceinline__ void stg128(void* p, uint32_t a, uint32_t b, uint32_t c, uint32_t d) {
  asm volatile("st.global.v4.b32 [%0], {%1, %2, %3, %4};" ::"l"(p), "r"(a), "r"(b), "r"(c), "r"(d) : "memory");
}
__device__ __forceinline__ void lds2_if(bool on, uint32_t p, uint32_t (&t)[8]) {
  asm volatile("{\n.reg .pred p;\nsetp.ne.b32 p, %9, 0;\n@p ld.shared.v4.b32 {%0, %1, %2, %3}, [%8];\n@p ld.shared.v4.b32 {%4, %5, %6, %7}, [%8 + 512];\n}\n"
               : "+r"(t[0]), "+r"(t[1]), "+r"(t[2]), "+r"(t[3]), "+r"(t[4]), "+r"(t[5]), "+r"(t[6]), "+r"(t[7]) : "r"(p), "r"((int)on) : "memory");
}
__device__ __forceinline__ void lds128(uint32_t p, uint32_t& a, uint32_t& b, uint32_t& c, uint32_t& d) {
  asm volatile("ld.shared.v4.b32 {%0, %1, %2, %3}, [%4];" : "=r"(a), "=r"(b), "=r"(c), "=r"(d) : "r"(p) : "memory");
}
template <class T> __device__ __forceinline__ T* ptr_add(T* base, uint32_t bytes) {
  T* r;
  asm("{\n.reg .u32 lo, hi;\nmov.b64 {lo, hi}, %1;\nadd.cc.u32 lo, lo, %2;\naddc.u32 hi, hi, 0;\nmov.b64 %0, {lo, hi};\n}\n" : "=l"(r) : "l"(base), "r"(bytes));
  return r;
}
__device__ __forceinline__ uint32_t lds32(uint32_t p) {
  uint32_t v;
  asm volatile("ld.volatile.shared.u32 %0, [%1];" : "=r"(v) : "r"(p) : "memory");
  return v;
}
__device__ __forceinline__ uint32_t flag_get(const unsigned int* p) {
  uint32_t v;
  asm volatile("ld.acquire.gpu.global.u32 %0, [%1];" : "=r"(v) : "l"(p) : "memory");
  return v;
}
__device__ __forceinline__ void wait_progress(uint32_t p, uint32_t target) {
  asm volatile("{\n.reg .pred p;\n.reg .u32 n, v;\nmov.u32 n, 0;\n"
               "LOOP:\nld.acquire.cta.shared.u32 v, [%0];\nsetp.ge.u32 p, v, %1;\n@p bra DONE;\n"
               "nanosleep.u32 %2;\nadd.u32 n, n, 1;\nsetp.lt.u32 p, n, 0x400000;\n@p bra LOOP;\ntrap;\n"
               "DONE:\n}\n" ::"r"(p), "r"(target), "n"(400) : "memory");
}
__device__ __forceinline__ void flag_set(unsigned int* p, uint32_t v) {
  asm volatile("st.release.gpu.global.u32 [%0], %1;" ::"l"(p), "r"(v) : "memory");
}
__device__ __forceinline__ void flag_dec(unsigned int* p) {
  asm volatile("red.relaxed.gpu.global.add.u32 [%0], 0xffffffff;" ::"l"(p) : "memory");
}

struct Cursor {
  int bi;
  uint32_t ph;
  __device__ __forceinline__ void next() {
    if (++bi == NBAR) { bi = 0; ph ^= 1; }
  }
};

constexpr float kScaleLog2 = 0.07216878364870322f * 1.4426950408889634f;
constexpr float kSumLimit = 1048576.0f;

__global__ void __cluster_dims__(2, 1, 1) __launch_bounds__(384, 1)
fused_kernel(const __grid_constant__ Params P) {
  extern __shared__ uint8_t smem_raw[];
  const uint32_t sbase = (smem_u32(smem_raw) + 1023) & ~1023u;
  const uint32_t full0 = sbase + RING, empty0 = full0 + 8 * NBAR, odone0 = empty0 + 8 * NBAR, ev0 = odone0 + 8 * MAX_OPS;
  const uint32_t progress = ev0 + 8 * MAX_EV, jobw = progress + 4;
  const uint32_t rank = blockIdx.x & 1;
  const int role = blockIdx.x >> 1;
  const int wid = __shfl_sync(0xffffffffu, (int)(threadIdx.x >> 5), 0);
  const int wg = wid >> 2;

  if (wid < 8) {
    if (elect()) {
#pragma unroll
      for (int j = 0; j < 16; j++) {
        const int i = EARLY + 16 * wid + j;
        if (i < 2 * NBAR + MAX_OPS + MAX_EV) mbar_init(full0 + 8 * i, i < NBAR ? 1 : i < 2 * NBAR ? 16 : i < 2 * NBAR + MAX_OPS ? 8 : 1);
      }
      if (wid == 7) asm volatile("st.shared.v2.u32 [%0], {0, 0};\nfence.acq_rel.cta;" ::"r"(progress) : "memory");
      asm volatile("fence.mbarrier_init.release.cluster;" ::: "memory");
    }
  } else if (wid == 8) {
    const uint32_t op0 = P.first[role];
    if (elect()) {
#pragma unroll
      for (int k = 0; k < EARLY; k++) mbar_init(full0 + 8 * k, 1);
      asm volatile("fence.mbarrier_init.release.cluster;" ::: "memory");
      const int blk = (op0 >> 10) & 1;
      if ((op0 & 3) == OP_Q) {
#pragma unroll
        for (int k = 0; k < EARLY; k++) {
          mbar_expect(full0 + 8 * k, SZ_Q);
          tma2d(sbase + k * SZ_Q, &P.x[blk], full0 + 8 * k, 64 * k, ((op0 >> 7) & 7) * kSq + rank * 128);
          tma3d(sbase + k * SZ_Q + 16384, &P.wq[blk], full0 + 8 * k, 0, 64 * k, 3 * ((op0 >> 2) & 31));
        }
      }
      asm volatile("prefetch.tensormap [%0];" ::"l"(rank ? &P.v[blk] : &P.k[blk]) : "memory");
    }
  }
  __syncwarp();
  asm volatile("barrier.cluster.arrive.relaxed.aligned;\nbarrier.cluster.wait.aligned;" ::: "memory");

  if (wg < 2) {
    asm volatile("setmaxnreg.inc.sync.aligned.u32 240;");
    const uint32_t* prog = P.prog[role].c;
    const int lane = threadIdx.x & 31, warp = wid & 3;
    uint32_t empty_rem;
    asm volatile("mapa.shared::cluster.u32 %0, %1, %2;" : "=r"(empty_rem) : "r"(empty0), "r"(lane & 1));
    auto release = [&](int slot) { mbar_arrive_cluster_if(lane < 2, empty_rem + 8 * slot); };
    Cursor r{0, 0};
    const uint32_t ring16 = (sbase & 0x3FFFF) >> 4;
    uint32_t cur = ring16;
    bool rdy0 = false, rdy1 = false;
    auto probe1 = [&]() { rdy0 = mbar_test(full0 + 8 * r.bi, r.ph); };
    auto probe2 = [&]() {
      Cursor n = r;
      rdy0 = mbar_test(full0 + 8 * n.bi, n.ph);
      n.next();
      rdy1 = mbar_test(full0 + 8 * n.bi, n.ph);
    };
    auto take = [&](bool rdy, uint32_t bytes, uint32_t& addr) {
      const int bi = r.bi;
      if (__builtin_expect(!__all_sync(0xffffffffu, rdy), 0)) mbar_wait(full0 + 8 * r.bi, r.ph);
      r.next();
      if (cur > ring16 + ((RING - bytes) >> 4)) cur = ring16;
      addr = cur;
      cur += bytes >> 4;
      return bi;
    };
    uint32_t keep = 0;
    const bool never = P.dbg == 0xffffffffu;
    uint32_t q[48];
#pragma unroll
    for (int i = 0; i < 48; i++) q[i] = 0;
    const int row = wg * 64 + warp * 16 + (lane >> 2);
    const int img0 = row * 4 + ((lane & 3) ^ ((row >> 1) & 3));
    uint4* pend = nullptr;
    bool pend_any = false;
    uint64_t spol;
    int pc = 0;
    auto slab = [&](int c, int i0) {
#pragma unroll
      for (int i = i0; i < 6; i++)
        stg2_if(c == i, pend + i * 512, q[8 * i], q[8 * i + 1], q[8 * i + 2], q[8 * i + 3],
                q[8 * i + 4], q[8 * i + 5], q[8 * i + 6], q[8 * i + 7], spol);
    };
    auto drain = [&](int c) {
      if (!pend_any || c >= 6) return;
      slab(c, 0);
      if (c == 5) {
        __syncwarp();
        mbar_arrive_if(lane == 0, odone0 - 8 + 8 * pc);
      }
    };

    for (;; pc++) {
      uint32_t op = prog[pc];
      const int type = op & 3;
      auto enter = [&]() {
        r.bi = (op >> 15) & 15; r.ph = (op >> 19) & 1; cur = ring16 + (((op >> 20) & 63) << 8);
      };
      enter();
      pend_any = op & C_PEND;
      spol = make_policy(!(op & C_SOON));
      if (type == OP_END) {
#pragma unroll 1
        for (int c = 0; c < 6; c++) drain(c);
        asm volatile("barrier.cluster.arrive.relaxed;" ::: "memory");
        break;
      }
      {
        float s[32], o[96];
        uint32_t ad0;
        int bi0, sk1;
        uint32_t pa[16], pb[16];
        float mc0, mc1, l0, l1;
        bool shifted;
        uint32_t nop;
        auto expo = [&](float (&s)[32], uint32_t (&pout)[16], float& b0, float& b1, bool shift, auto mid) {
          float c0, c1;
#pragma unroll
          for (int i = 0; i < 8; i++) {
            const float e0 = ex2(shift ? s[4 * i] - mc0 : s[4 * i]), e1 = ex2(shift ? s[4 * i + 1] - mc0 : s[4 * i + 1]);
            const float e2 = ex2(shift ? s[4 * i + 2] - mc1 : s[4 * i + 2]), e3 = ex2(shift ? s[4 * i + 3] - mc1 : s[4 * i + 3]);
            if (i) { b0 += e0; c0 += e1; b1 += e2; c1 += e3; } else { b0 = e0; c0 = e1; b1 = e2; c1 = e3; }
            pout[2 * i] = pack_bf16(e0, e1); pout[2 * i + 1] = pack_bf16(e2, e3);
            if (i & 1) mid(i >> 1);
          }
          b0 += c0; b1 += c1;
        };
        auto rowmax = [&](float (&s)[32], float& m0, float& m1) {
          m0 = fmaxf(s[0], s[1]); m1 = fmaxf(s[2], s[3]);
#pragma unroll
          for (int i = 1; i < 8; i++) { m0 = fmaxf(m0, fmaxf(s[4 * i], s[4 * i + 1])); m1 = fmaxf(m1, fmaxf(s[4 * i + 2], s[4 * i + 3])); }
          m0 = fmaxf(m0, __shfl_xor_sync(0xffffffffu, m0, 1)); m1 = fmaxf(m1, __shfl_xor_sync(0xffffffffu, m1, 1));
          m0 = fmaxf(m0, __shfl_xor_sync(0xffffffffu, m0, 2)); m1 = fmaxf(m1, __shfl_xor_sync(0xffffffffu, m1, 2));
        };
        auto first = [&](float (&s)[32], int sk0, auto mid) {
          fence_regs(s);
          release(sk0);
          mc0 = 0.f; mc1 = 0.f;
          expo(s, pa, l0, l1, false, mid);
          shifted = __any_sync(0xffffffffu, !(fmaxf(l0, l1) <= kSumLimit && fminf(l0, l1) >= 1.f / kSumLimit));
          if (shifted) {
            rowmax(s, mc0, mc1);
            expo(s, pa, l0, l1, true, [](int) {});
          }
        };
        auto qk = [&](float (&s)[32], uint32_t ak, int k0 = 0, int k1 = 12) {
#pragma unroll
          for (int kk = k0; kk < k1; kk++)
            wgmma_rs_n64<0>(s, q[4 * kk], q[4 * kk + 1], q[4 * kk + 2], q[4 * kk + 3], mk_desc(ak + (kk >> 2) * KV_CH + (kk & 3) * 2, 16, KV_SBO, 1), kk != 0);
          if (k1 == 12) wg_commit();
        };
        auto pv = [&](uint32_t (&pin)[16], uint32_t av, int acc) {
#pragma unroll
          for (int kk = 0; kk < 4; kk++)
            wgmma_rs_n192<1>(o, pin[4 * kk], pin[4 * kk + 1], pin[4 * kk + 2], pin[4 * kk + 3], mk_desc(av + kk * (KV_SBO / 8), KV_CH * 16, KV_SBO, 1), acc || (kk != 0));
          wg_commit();
        };
        auto finish = [&](uint32_t (&pout)[16], int sk, int sv) {
          probe2();
          wg_wait<1>();
          fence_regs(s);
          release(sk);
          float b0, b1;
#pragma unroll 1
          for (bool redo = false;; redo = true) {
            expo(s, pout, b0, b1, false, [](int) {});
            if (!__any_sync(0xffffffffu, !redo && (shifted || !(fmaxf(b0, b1) <= kSumLimit)))) break;
            shifted = true;
            rowmax(s, b0, b1);
            b0 = fmaxf(mc0, b0); b1 = fmaxf(mc1, b1);
            const float a0 = ex2(mc0 - b0), a1 = ex2(mc1 - b1);
            mc0 = b0; mc1 = b1;
            l0 *= a0; l1 *= a1;
            wg_wait<0>();
            fence_regs(o);
#pragma unroll
            for (int i = 0; i < 24; i++) { o[4 * i] *= a0; o[4 * i + 1] *= a0; o[4 * i + 2] *= a1; o[4 * i + 3] *= a1; }
#pragma unroll
            for (int i = 0; i < 32; i++) s[i] -= (i & 2) ? mc1 : mc0;
          }
          l0 += b0; l1 += b1;
          wg_wait<0>();
          fence_regs(o);
          release(sv);
        };
        auto step = [&](uint32_t (&pin)[16], uint32_t (&pout)[16]) {
          uint32_t ak, av;
          const int sk = take(rdy0, SZ_KV, ak), sv = take(rdy1, SZ_KV, av);
          wg_fence();
          qk(s, ak);
          pv(pin, av, 1);
          finish(pout, sk, sv);
        };
        auto unpark = [&]() {
          uint32_t ad, ak;
          const int bi = take(rdy0, SZ_PARK, ad);
#pragma unroll
          for (int i = 0; i < 12; i++) lds128(sbase + (ad - ring16 + img0) * 16 + (i >> 1) * 8192 + (i & 1) * 512, q[4 * i], q[4 * i + 1], q[4 * i + 2], q[4 * i + 3]);
          const int sk0 = take(false, SZ_KV, ak);
          fence_regs(q);
          release(bi);
          wg_fence();
          qk(s, ak);
          probe2();
          return sk0;
        };
        auto mma4 = [&](uint32_t ad, int acc) {
#pragma unroll
          for (int kk = 0; kk < 4; kk++)
            wgmma_ss_n192<1>(o, mk_desc(ad + wg * 512 + kk * 2, 16, 1024, 1), mk_desc(ad + 1024 + kk * 128, 8192, 1024, 1), acc || kk != 0);
        };
        auto convert = [&](int i0, int i1) {
          sched_fence(keep, never);
#pragma unroll
          for (int i = i0; i < i1; i++) q[i] = pack_bf16(o[2 * i] * kScaleLog2, o[2 * i + 1] * kScaleLog2);
          sched_fence(keep, never);
        };
        auto kend = [&](int bi, int k) {
          wg_commit();
          drain(k < 8 ? (QDRAIN >> (4 * k)) & 7 : 7);
          probe1();
          wg_wait<0>();
          release(bi);
        };
        if (type == OP_O) {
          float c[80];
          int prev = 0;
          auto hand_over = [&](float (&c)[80], uint4* dst) {
            fence_regs(c);
#pragma unroll
            for (int i = 0; i < 48; i++) q[i] = i < 8 ? 0 : pack_bf16(c[2 * i - 16], c[2 * i - 15]);
            pend = dst;
          };
          auto mma2 = [&](float (&c)[80], uint32_t da, uint32_t db, int acc) {
            wgmma_ss_n160<1>(c, mk_desc(da, 16, 512, 2), mk_desc(db, 2048, 512, 2), acc);
            wgmma_ss_n160<1>(c, mk_desc(da + 2, 16, 512, 2), mk_desc(db + 64, 2048, 512, 2), 1);
          };
          auto kstep = [&](float (&c)[80], int acc, auto hook, uint32_t bytes = SZ_O) {
            uint32_t ad;
            const int bi = take(rdy0, bytes, ad);
            const uint32_t da = ad + wg * 256, db = ad + 1024;
            wg_fence();
            mma2(c, da, db, acc);
            wg_commit();
            if (acc) { wg_wait<1>(); mbar_arrive_cluster_if(lane < 2 && (acc == 1 || wg == 0), empty_rem + 8 * prev); }
            mma2(c, da + 512, db + 640, 1);
            wg_commit();
            prev = bi;
            hook();
            probe1();
            wg_wait<1>();
          };
          if (op & C_WIDE) {
            float d[80];
            const int nk = 3 * ((op >> 2) & 63);
            uint4* part = ptr_add(g_part, (((op >> 8) & 63) * 2 + rank) * SZ_PARK + img0 * 16);
            auto wstep = [&](int acc, auto hook) {
              uint32_t ad;
              const int bi = take(rdy0, SZ_W, ad);
              const uint32_t da = ad + wg * 256, db = ad + 1024;
              wg_fence();
              mma2(d, da, db, acc);
              mma2(d, da + 512, db + 640, 1);
              wg_commit();
              if (acc) { wg_wait<1>(); release(prev); }
              mma2(c, da, db + 1280, acc);
              mma2(c, da + 512, db + 1920, 1);
              wg_commit();
              prev = bi;
              hook();
              probe1();
              wg_wait<1>();
            };
            wstep(0, [&]() { drain(0); drain(1); });
#pragma unroll 1
            for (int k = 2; k < 6; k += 2) wstep(1, [&]() { drain(k); drain(k + 1); });
#pragma unroll 1
            for (int k = 3 + 3 * TAIL; k < nk; k++) {
              wstep(1, []() {});
            }
#pragma unroll 1
            for (int k = 0; k < 3 * TAIL; k++) kstep(d, 1, []() {});
            nop = prog[pc + 1];
            spol = make_policy(!(nop & C_SOON));
            kstep(c, 1, [&]() { hand_over(d, part - 6144); });
#pragma unroll 1
            for (int k = 1; k < 3 * TAIL; k++) kstep(c, 1, [&]() { slab(TAIL == 2 ? k : (0x50403201 >> (4 * k - 4)) & 7, 1); });
            if ((nop & 3) == OP_Q) {
              op = nop;
              enter();
              pc++;
              pend_any = true;
              bi0 = take(rdy0, SZ_Q, ad0);
              undefine(o);
              wg_fence();
              mma4(ad0, 0);
              wg_commit();
              wg_wait<1>();
              release(prev);
              hand_over(c, part);
              probe1();
              wg_wait<0>();
              release(bi0);
              fence_regs(o);
              goto next_head;
            }
            wg_wait<0>();
            release(prev);
            hand_over(c, part);
            continue;
          }
          auto unblock = [&](int k) {
            if (__all_sync(0xffffffffu, rdy0) || __all_sync(0xffffffffu, mbar_try(full0 + 8 * r.bi, r.ph, TRYNS))) return;
#pragma unroll 1
            for (; k < 6; k++) drain(k);
            pend_any = false;
          };
          uint32_t job;
          unblock(0);
          kstep(c, 0, [&]() { job = lds32(jobw); drain(0); });
#pragma unroll 1
          for (int k = 1; k < 6; k++) {
            unblock(k);
            kstep(c, 1, [&]() { drain(k); });
          }
          job = __shfl_sync(0xffffffffu, job, 0);
#pragma unroll 1
          for (int k = 3 * ((job >> 13) & 63); k > 11; k--) kstep(c, 1, []() {});
          uint32_t t[8], stage[3];
          float u[80];
          auto unpack = [&](int j) {
#pragma unroll
            for (int i = 0; i < 8; i++) {
              u[16 * j + 2 * i] = __uint_as_float(t[i] << 16); u[16 * j + 2 * i + 1] = __uint_as_float(t[i] & 0xffff0000u);
              asm volatile("" : "+f"(u[16 * j + 2 * i]), "+f"(u[16 * j + 2 * i + 1]));
            }
          };
#pragma unroll
          for (int i = 0; i < 8; i++) t[i] = 0;
          const uint32_t bytes = (job & P_LD) ? SZ_OL : SZ_O;
#pragma unroll
          for (int j = 0; j < 5; j++) {
            if (j == 5 - SKEW && wg == 1) {
              wg_wait<0>();
              release(prev);
              bar_sync(1, 256);
            }
            kstep(c, j == 5 - SKEW ? 2 : 1, [&]() {
              if (SKEW && j == 4) asm volatile("{\n.reg .pred p;\nsetp.eq.u32 p, %0, 0;\n@p bar.arrive 1, 256;\n}\n" ::"r"(wg) : "memory");
              if (j) unpack(j - 1);
              lds2_if(job & P_LD, sbase + (cur - ring16 + img0) * 16 - 8192, t);
              if (j >= 1 && j <= 3) stage[j - 1] = sbase + (cur - ring16) * 16 - bytes + wid * 1024;
            }, bytes);
          }
          unpack(4);
          sched_fence(keep, never);
          wg_wait<0>();
          fence_regs(c);
          release(prev);
          asm volatile("barrier.cluster.arrive.relaxed;" ::: "memory");
#pragma unroll
          for (int i = 0; i < 10; i++) {
            const int v = (i & 1) * 2 + (lane >> 4);
            const uint32_t sa = stage[i >> 2] + (i & 2) * 4096;
            stsm4(sa + (lane & 15) * 64 + ((v ^ ((lane >> 1) & 3)) << 4), pack_bf16(c[8 * i] + u[8 * i], c[8 * i + 1] + u[8 * i + 1]),
                  pack_bf16(c[8 * i + 2] + u[8 * i + 2], c[8 * i + 3] + u[8 * i + 3]), pack_bf16(c[8 * i + 4] + u[8 * i + 4], c[8 * i + 5] + u[8 * i + 5]),
                  pack_bf16(c[8 * i + 6] + u[8 * i + 6], c[8 * i + 7] + u[8 * i + 7]));
          }
          asm volatile("fence.proxy.async.shared::cta;" ::: "memory");
          __syncwarp();
          if (elect()) {
#pragma unroll
            for (int i = 0; i < 5; i++)
              tma3d_store(&P.out, stage[i >> 1] + (i & 1) * 8192, 0, ((job >> 7) & 7) * kSq + rank * 128 + wid * 16, ((job >> 10) & 1) * 20 + ((job >> 19) & 3) * 5 + i);
            asm volatile("cp.async.bulk.commit_group;\ncp.async.bulk.wait_group.read 0;" ::: "memory");
          }
          __syncwarp();
          break;
        }
        bi0 = take(rdy0, SZ_Q, ad0);
        undefine(o);
        wg_fence();
        mma4(ad0, 0);
        kend(bi0, 0);
        fence_regs(o);
      next_head:
        {
#pragma unroll 1
          for (int k = 1; k < ((op & F_PARK) ? 10 : 8); k++) {
            uint32_t ad;
            const int bi = take(rdy0, SZ_Q, ad);
            wg_fence();
            mma4(ad, 1);
            kend(bi, k);
          }
          if (op & F_PARK) {
            fence_regs(o);
            convert(0, 48);
            pend = ptr_add(g_t, (((op >> 2) & 511) * 2 + rank) * SZ_PARK + img0 * 16);
            continue;
          }
          uint32_t a8, a9, ak0, ak1;
          const int b8 = take(rdy0, SZ_Q, a8), b9 = take(false, SZ_Q, a9);
          wg_fence();
          mma4(a8, 1);
          wg_commit();
          mma4(a9, 1);
          wg_commit();
          pc++;
          wg_wait<1>();
          release(b8);
          const int sk0 = take(false, SZ_KV, ak0);
          wg_wait<0>();
          fence_regs(o);
          release(b9);
          float s0[32];
          convert(0, 32);
          wg_fence();
          qk(s0, ak0, 0, 4);
          convert(32, 48);
          wg_fence();
          qk(s0, ak0, 4, 12);
          sk1 = take(false, SZ_KV, ak1);
          probe1();
          wg_wait<0>();
          first(s0, sk0, [&](int i) {
            if (i == 0) return;
            sched_fence(keep, never);
            wg_fence();
            if (i == 1) qk(s, ak1, 0, 4);
            if (i == 2) qk(s, ak1, 4, 8);
            if (i == 3) qk(s, ak1, 8, 12);
            sched_fence(keep, never);
          });
        }
        for (;;) {
          {
            uint32_t av;
            const int sv = take(rdy0, SZ_KV, av);
            undefine(o);
            wg_fence();
            pv(pa, av, 0);
            finish(pb, sk1, sv);
          }
          nop = prog[pc + 1];
#pragma unroll 1
          for (int jj = 0; jj < 7; jj++) {
            step(pb, pa);
            step(pa, pb);
          }
          float i0, i1;
          auto last = [&]() {
            uint32_t av;
            const int sv = take(rdy0, SZ_KV, av);
            wg_fence();
            pv(pb, av, 1);
            sched_fence(keep, never);
            probe1();
            l0 += __shfl_xor_sync(0xffffffffu, l0, 1); l1 += __shfl_xor_sync(0xffffffffu, l1, 1);
            l0 += __shfl_xor_sync(0xffffffffu, l0, 2); l1 += __shfl_xor_sync(0xffffffffu, l1, 2);
            i0 = rcp(l0); i1 = rcp(l1);
            pend = ptr_add(g_t, (((op >> 2) & 511) * 2 + rank) * SZ_PARK + img0 * 16);
            return sv;
          };
          auto normalise = [&](uint32_t (&d)[48], auto mid) {
#pragma unroll
            for (int i = 0; i < 24; i++) {
              d[8 * (i >> 2) + (i & 3)] = pack_bf16(o[4 * i] * i0, o[4 * i + 1] * i0);
              d[8 * (i >> 2) + (i & 3) + 4] = pack_bf16(o[4 * i + 2] * i1, o[4 * i + 3] * i1);
              if ((i & 3) == 3 && i != 23) { sched_fence(keep, never); mid(i >> 2); }
            }
          };
          const int sv = last();
          if ((nop & 3) != OP_A) {
            op = nop;
            enter();
            pend_any = true;
            spol = make_policy(!(op & C_SOON));
            bi0 = take(rdy0 || (nop & 3) != OP_Q, SZ_Q, ad0);
            sched_fence(keep, never);
            wg_wait<0>();
            fence_regs(o);
            release(sv);
            normalise(q, [](int) {});
            undefine(o);
            if ((nop & 3) != OP_Q) break;
            sched_fence(keep, never);
            wg_fence();
            mma4(ad0, 0);
            pc++;
            kend(bi0, 0);
            fence_regs(o);
            goto next_head;
          }
          const int sk0 = unpark();
          wg_wait<1>();
          fence_regs(o);
          release(sv);
          uint32_t t[48];
          spol = make_policy(!(nop & C_SOON));
          auto st = [&](int i) {
            stg2_if(true, pend + i * 512, t[8 * i], t[8 * i + 1], t[8 * i + 2], t[8 * i + 3], t[8 * i + 4], t[8 * i + 5], t[8 * i + 6], t[8 * i + 7], spol);
          };
          normalise(t, [&](int i) { if (!(i & 1)) st(i >> 1); });
          wg_wait<0>();
          first(s, sk0, [&](int i) { if (i < 3) { sched_fence(keep, never); st(3 + i); } });
          __syncwarp();
          mbar_arrive_if(lane == 0, odone0 + 8 * pc);
          pc++;
          op = nop;
          uint32_t ak1;
          sk1 = take(rdy0, SZ_KV, ak1);
          rdy0 = rdy1;
          wg_fence();
          qk(s, ak1);
        }
      }
    }
    if (never) g_flag[0] = keep;
    asm volatile("barrier.cluster.wait;" ::: "memory");
  } else {
    asm volatile("setmaxnreg.dec.sync.aligned.u32 24;");
    const uint32_t* prog = P.prog[role].p;
    unsigned int* flag = g_flag + rank;
    if (wid == 8) {
      Cursor tail{0, 0};
      int head = 0, sh = 0;
      uint32_t cur = 0, used = 0;
      uint64_t fifo = 0;
      uint32_t dst, bar, ev = ev0, done = 0;
      uint64_t pol;
      asm volatile("createpolicy.fractional.L2::evict_first.b64 %0, 1.0;" : "=l"(pol));
      auto retire = [&]() {
        mbar_wait(empty0 + 8 * tail.bi, tail.ph);
        tail.next();
        used -= (uint32_t)fifo & 31;
        fifo >>= 5;
        sh -= 5;
        asm volatile("st.volatile.shared.u32 [%0], %1;" ::"r"(progress), "r"(++done) : "memory");
      };
      auto acquire = [&](uint32_t bytes) {
        uint32_t fp = bytes >> 12;
        if (cur + fp > (RING >> 12)) { fp += (RING >> 12) - cur; cur = 0; }
        used += fp;
        while (used > (RING >> 12) || sh == 5 * NBAR) retire();
        fifo |= (uint64_t)fp << sh;
        sh += 5;
        dst = sbase + (cur << 12);
        bar = full0 + 8 * head;
        cur += bytes >> 12;
        if (++head == NBAR) head = 0;
      };
      auto gate = [&]() {
        mbar_wait(ev, 0);
        ev += 8;
        asm volatile("fence.proxy.async.global;" ::: "memory");
      };
      for (int pc = 0;; pc++) {
        uint32_t op = prog[pc];
        const int type = op & 3;
        if (type == OP_END) break;
        if (op == OP_O) {
          gate();
          op = __shfl_sync(0xffffffffu, lds32(jobw), 0);
        }
        const int blk = (op >> 10) & 1;
        if (type == OP_Q) {
#pragma unroll 1
          for (int k = 0; k < 10; k++) {
            if (k == 9 && (op & P_GATE)) gate();
            acquire(SZ_Q);
            if ((pc > 0 || k >= EARLY) && elect()) {
              mbar_expect(bar, SZ_Q);
              tma2d(dst, &P.x[blk], bar, 64 * k, ((op >> 7) & 7) * kSq + rank * 128);
              if ((k & 1) == rank) tma3d_mc(dst + 16384, &P.wq[blk], bar, 0, 64 * k, 3 * ((op >> 2) & 31));
            }
          }
        } else if (type == OP_A) {
          const int row0 = ((op >> 2) & 255) * kSk;
          const CUtensorMap* kv_map = rank ? &P.v[blk] : &P.k[blk];
          if (op & F_PARK) {
            gate();
            acquire(SZ_PARK);
            if (elect()) {
              mbar_expect(bar, SZ_PARK);
              bulk_load_hint(dst, &g_t[((op >> 20) * 2 + rank) * 3072], SZ_PARK, bar, make_policy(P.dbg & 4));
            }
          }
#pragma unroll 1
          for (int t = 0; t < 32; t++) {
            const int isv = t == 31 ? 1 : (t == 0 ? 0 : (~t & 1));
            const int j = isv ? (t - 1) >> 1 : (t + 1) >> 1;
            if (t == 31 && (op & P_GATE)) gate();
            acquire(SZ_KV);
            if (elect()) {
              mbar_expect(bar, SZ_KV);
              if (isv == (int)rank) tma4d_mc_hint(dst, kv_map, bar, row0 / 8 + 8 * j, pol);
            }
          }
        } else {
          const int n = (op >> 13) & 63, nw = (op & P_WIDE) ? n - TAIL : 0;
          const uint64_t pol_o = make_policy(P.dbg & (nw ? 1 : 2));
          const uint4* part = &g_part[((((op >> 5) & 60) + ((op >> 19) & 3)) * 2 + rank) * 3072 + 512];
#pragma unroll 1
          for (int i = 0; i < n + (nw ? TAIL : 0); i++) {
            const int id = ((op >> 2) & 511) + (i < n ? i : i - TAIL), col = 5 * (((op >> 19) & 3) + (i >= n));
            const uint4* src = &g_t[(P.slot[id] * 2 + rank) * 3072];
            if ((op & P_LD) && i == ((op & P_PRE) ? 0 : n - 2)) gate();
            if (i < n) gate();
#pragma unroll 1
            for (int k = 0; k < 3; k++) {
              const uint32_t j = (op & P_LD) ? 3 * (i - n) + k + 5 : 5, bytes = i < nw ? SZ_W : j < 5 ? SZ_OL : SZ_O;
              acquire(bytes);
              if (elect()) {
                mbar_expect(bar, bytes);
                tma5d_mc(dst + 16384 + rank * 10240, &P.wo[blk], bar, 24 * (id & 31) + 8 * k + 4 * rank, col);
                bulk_load_hint(dst, src + k * 1024, 16384, bar, pol_o);
                if (i < nw) tma5d_mc(dst + SZ_O + rank * 10240, &P.wo[blk], bar, 24 * (id & 31) + 8 * k + 4 * rank, col + 5);
                if (j < 5) bulk_load_hint(dst + SZ_O, part + j * 512, 8192, bar, pol);
                if ((op & P_PRE) && 3 * i + k < 10)
                  asm volatile("cp.async.bulk.prefetch.L2.global [%0], 4096;" ::"l"(part + (3 * i + k) * 256) : "memory");
              }
            }
          }
        }
      }
#pragma unroll 1
      while (sh) retire();
    } else if (threadIdx.x == 288) {
      for (int pc = 0;; pc++) {
        const uint32_t op = prog[pc];
        const int type = op & 3;
        if (type == OP_END) break;
        if (type == OP_Q ? !(op & F_PARK) : type == OP_O && !(op & P_ST)) continue;
        const int id = type == OP_A ? (op >> 2) & 511 : type == OP_Q ? N_TILE + ((op >> 13) & 127) : ID_PART + ((op >> 5) & 60) + ((op >> 19) & 3);
        const uint32_t v = type == OP_O ? 1 : P.info[id] & 7;
        mbar_wait_slow<PUBNS>(odone0 + 8 * pc, 0);
        flag_set(flag + 2 * id, v);
        if (type == OP_O && (op & P_WIDE)) flag_set(flag + 2 * id + 2, v);
      }
    } else if (wid == 10) {
      int i = threadIdx.x & 31;
      uint32_t e = i < 8 ? P.prog[role].ev[i] : 0;
      for (uint32_t n = 0; __any_sync(0xffffffffu, e); n++) {
        uint32_t job = lds32(jobw);
        if ((e & E_DRAW) && rank == 0 && lds32(progress) >= (e & 1023)) {
          job = P.job[atomicInc(&g_ticket, 4 * N_TEAM - 1)];
          asm volatile("{\n.reg .u32 a;\nmapa.shared::cluster.u32 a, %0, 1;\nst.volatile.shared::cluster.u32 [a], %1;\n"
                       "st.volatile.shared.u32 [%0], %1;\n}\n" ::"r"(jobw), "r"(job) : "memory");
        }
        if ((e & E_JOB) && job) {
          const uint32_t j = e & 63, heads = (job >> 13) & 63, jp = !(job & P_LD) ? 63 : (job & P_PRE) ? 0 : heads - 2, h = j - (j > jp);
          e = j == jp ? (ID_PART + ((job >> 5) & 60) + ((job >> 19) & 3)) | E_ON | E_LAST : h < heads ? (((job >> 2) & 511) + h) | E_ON | E_LAST : 0;
        }
        unsigned int* f = ptr_add(flag, 8 * (e & 1023));
        const bool ok = (e & E_ON) ? flag_get(f) - 1 < ((e & E_FREE) ? 1 : 7) : (e & E_DRAW) && job;
        if (ok) {
          mbar_arrive(ev0 + 8 * i);
          if (e & (E_FREE | E_LAST)) flag_dec(f);
          i += 8;
          e = i < MAX_EV ? P.prog[role].ev[i] : 0;
        }
        asm volatile("{\n.reg .pred p;\nsetp.ge.u32 p, %0, 0x400000;\n@p trap;\n}\n" ::"r"(n));
        if (!__any_sync(0xffffffffu, ok)) __nanosleep(WATNS);
      }
    } else if (threadIdx.x == 352) {
      uint32_t items = 0;
      auto read = [&](int id) {
        if (!(P.info[id] & I_NEXT)) return;
        wait_progress(progress, items);
        flag_dec(flag + 2 * id);
      };
      for (int pc = 0;; pc++) {
        const uint32_t op = prog[pc];
        const int type = op & 3;
        if (type == OP_END) break;
        if (type == OP_O) {
          const int n = (op >> 13) & 63;
#pragma unroll 1
          for (int i = 0; i < n; i++) {
            items += (op & P_WIDE) && i == n - TAIL ? 3 * TAIL + 3 : 3;
            read(((op >> 2) & 511) + i);
          }
        } else if (type == OP_A) {
          if (op & F_PARK) { items++; read(N_TILE + ((op >> 13) & 127)); }
          items += 32;
        } else {
          items += 10;
        }
      }
    }
    __syncwarp();
    asm volatile("barrier.cluster.arrive.relaxed;\nbarrier.cluster.wait;" ::: "memory");
  }
}

typedef CUresult (*EncodeFn)(CUtensorMap*, CUtensorMapDataType, cuuint32_t, void*, const cuuint64_t*, const cuuint64_t*,
                             const cuuint32_t*, const cuuint32_t*, CUtensorMapInterleave, CUtensorMapSwizzle,
                             CUtensorMapL2promotion, CUtensorMapFloatOOBfill);

void encode(EncodeFn fn, CUtensorMap* m, const void* ptr, int rank, const cuuint64_t* dims, const cuuint64_t* strides,
            const cuuint32_t* box, CUtensorMapSwizzle swz) {
  const cuuint32_t es[5] = {1, 1, 1, 1, 1};
  CUresult r = fn(m, CU_TENSOR_MAP_DATA_TYPE_BFLOAT16, rank, const_cast<void*>(ptr), dims, strides, box, es,
                  CU_TENSOR_MAP_INTERLEAVE_NONE, swz, CU_TENSOR_MAP_L2_PROMOTION_L2_128B, CU_TENSOR_MAP_FLOAT_OOB_FILL_NONE);
  if (r != CUDA_SUCCESS) fprintf(stderr, "cuTensorMapEncodeTiled failed: %d\n", (int)r);
}

struct Op { int type, flags, id, n, quarter, park, item0, items; double t0, t1; };
struct Use { double ready, gate, need, freed; int readers, slot, prev; bool next; };
struct PlanStats { double end, slack, park_slack; int slots, parks; uint32_t own[N_CL]; };

bool plan(const char* const* text, int n_pair, int phase, Params& P, PlanStats* stats = nullptr) {
  constexpr double T_Q = 7900, T_A = 24850, T_U = 26300, T_O = 1920, T_RUN = 800, T_WIDE = 1900, AHEAD = 3500, PUBLISH = 1500;
  const double margin = 256.0 * ((P.dbg >> 8) & 255);
  static Op op[N_CL][MAX_OPS];
  static Use use[ID_PART];
  int n_op[N_CL], covered[N_TEAM] = {}, finals[N_TEAM] = {};
  auto hex = [](char c) { return c <= '9' ? c - '0' : c - 'a' + 10; };
  for (int i = 0; i < n_pair; i++)
    for (const char* s = text[i]; *s; s++)
      if (*s == 'J') { if (covered[hex(s[1])]) return false; covered[hex(s[1])] = 10 * (s[2] - '0') + s[3] - '0'; }
  for (int c = 0; c < 2 * n_pair; c++) {
    int n = 0, items = 0;
    double t = 0;
    auto add = [&](int type, int flags, int id, int heads, int quarter, int its, double dt) {
      if (n < MAX_OPS) op[c][n] = {type, flags, id, heads, quarter, 0, items, its, t, t + dt};
      n++; items += its; t += dt;
    };
    for (const char* s = text[c >> 1]; *s; s++) {
      const int tm = hex(s[1]) & 15, nj = covered[tm];
      if (*s == 'N') { add(OP_Q, 0, 0, 0, 0, 10, T_Q); add(OP_A, 0, 0, 0, 0, 32, T_A); }
      if (*s == 'P') add(OP_Q, F_PARK, 0, 0, 0, 10, T_Q);
      if (*s == 'U') { if (n == 0 || n > MAX_OPS || op[c][n - 1].type != OP_A) return false; add(OP_A, F_PARK, 0, 0, 0, 33, T_U); }
      if (*s == 'J') { if (nj <= TAIL || nj > kH - 4) return false; add(OP_O, P_WIDE | P_ST, tm * kH, nj, 2 * (c & 1), 3 * (nj + TAIL), 2 * T_O * nj + T_WIDE); }
      if (*s == 'F') { if (s[2]) return false; add(OP_O, nj ? P_LD : 0, tm * kH + nj, kH - nj, finals[tm]++, 3 * (kH - nj), T_O * (kH - nj) + T_RUN); }
    }
    add(OP_END, 0, 0, 0, 0, 0, 0);
    if (n > MAX_OPS || op[c][0].type != OP_Q) return false;
    n_op[c] = n - 1;
  }
  for (int t = 0; t < N_TEAM; t++) if (finals[t] != 4) return false;
  for (int i = 0; i < ID_PART; i++) use[i] = {0, 0, 1e18, 0, 0, 0, 0, false};
  struct Ref { double t; Op* o; int id; };
  static Ref att[N_TILE + 1], dem[N_TILE], prk[MAX_PARK + 1], unp[MAX_PARK + 1], wr[ID_PART];
  int n_att = 0, n_prk = 0, n_unp = 0;
  auto ready = [&](const Op* o) {
    const int nt = o[1].type;
    return o->t1 + (nt == OP_Q ? 6100 : nt == OP_O ? 3900 : 1500) + PUBLISH;
  };
  for (int c = 0; c < 2 * n_pair; c++)
    for (Op* o = op[c]; o->type != OP_END; o++) {
      if (o->type == OP_A) { att[n_att] = {ready(o), o, 0}; if (++n_att > N_TILE) return false; }
      if (o->type == OP_A && o->flags) { unp[n_unp] = {o->t0 - AHEAD, o, 0}; if (++n_unp > MAX_PARK) return false; }
      if (o->type == OP_Q && o->flags) { prk[n_prk] = {ready(o), o, 0}; if (++n_prk > MAX_PARK) return false; }
      for (int i = 0; o->type == OP_O && i < o->n; i++) {
        const int nw = (o->flags & P_WIDE) ? o->n - TAIL : 0;
        Use& u = use[o->id + i];
        const double t = o->t0 + T_O * (i + (i < nw ? i : nw));
        if (t - AHEAD < u.need) u.need = t - AHEAD;
        const double f = i < nw || (nw && o[1].type != OP_O) ? t + T_O * (i < nw ? 2 : 1 + TAIL) + PUBLISH : 1e18;
        if (f > u.freed) u.freed = f;
        u.readers++;
      }
    }
  if (n_att != N_TILE || n_prk != n_unp) return false;
  auto sort = [](Ref* r, int n) {
    for (int i = 1; i < n; i++)
      for (int j = i; j > 0 && r[j].t < r[j - 1].t; j--) { Ref x = r[j]; r[j] = r[j - 1]; r[j - 1] = x; }
  };
  for (int i = 0; i < N_TILE; i++) { const int id = (i & 15) * kH + (i >> 4); dem[i] = {use[id].need, nullptr, id}; }
  sort(att, n_att); sort(dem, N_TILE); sort(prk, n_prk); sort(unp, n_unp);
  PlanStats st = {0, 1e18, 1e18, 0, n_prk};
  int n_wr = 0;
  for (int i = 0; i < N_TILE; i++) {
    Op* o = att[i].o;
    o->id = dem[i].id;
    if (!o->flags) o[-1].id = o->id;
    if (dem[i].t - att[i].t < st.slack) st.slack = dem[i].t - att[i].t;
    wr[n_wr++] = {o->t1 - 2 * AHEAD, o, o->id};
  }
  for (int i = 0; i < n_prk; i++) {
    prk[i].o->id = unp[i].o->id;
    prk[i].o->park = unp[i].o->park = i;
    use[N_TILE + i].freed = unp[i].o->t0 + 2 * PUBLISH;
    use[N_TILE + i].readers = 1;
    if (unp[i].t - prk[i].t < st.park_slack) st.park_slack = unp[i].t - prk[i].t;
    wr[n_wr++] = {prk[i].o->t1 - 2 * AHEAD, prk[i].o, N_TILE + i};
  }
  for (int c = 0; c < 2 * n_pair; c++)
    for (int d = 0; d < 2 * n_pair; d++)
      for (Op *f = &op[c][n_op[c] - 1], *o = op[d]; f->type == OP_O && o->type != OP_END; o++)
        if (o->type == OP_O && (o->flags & P_ST) && o->id / kH == f->id / kH) {
          if (f->t0 - o->t1 > 4096.0 * ((P.dbg >> 16) & 255)) f->flags |= P_PRE;
          const double slack = f->t0 + ((f->flags & P_PRE) ? 0 : (f->n - 2) * T_O) - AHEAD - ready(o);
          if (slack < st.park_slack) st.park_slack = slack;
        }
  sort(wr, n_wr);
  int holder[N_TILE];
  for (int i = 0; i < n_wr; i++) {
    int best = -1;
    for (int sl = 0; sl < st.slots; sl++)
      if (use[holder[sl]].freed + margin <= wr[i].t && (best < 0 || (use[holder[sl]].freed < use[holder[best]].freed) != ((P.dbg & 32) != 0))) best = sl;
    Use& u = use[wr[i].id];
    if (best >= 0) { u.prev = holder[best]; use[u.prev].next = true; wr[i].o->flags |= P_GATE; }
    else if (st.slots == N_TILE) return false;
    else best = st.slots++;
    u.slot = best;
    holder[best] = wr[i].id;
  }
  {
    int pos[N_CL] = {}, flag[ID_PART + 4 * N_TEAM] = {}, seen[ID_PART] = {};
    auto goal = [&](int c) { const Op& f = op[c][n_op[c] - 1]; return f.type == OP_O && !(f.flags & P_WIDE) ? f.item0 : f.item0 + f.items + NBAR; };
    for (bool moved = true; moved;) {
      moved = false;
      for (int c = 0; c < 2 * n_pair; c++) {
        for (; pos[c] < goal(c); pos[c]++, moved = true) {
          bool ok = true;
          for (const Op* o = op[c]; o->type != OP_END; o++) {
            const int k = pos[c] - o->item0, own = o->type == OP_A ? o->id : N_TILE + o->park;
            if (k < 0 || k >= o->items) continue;
            if (o->type == OP_O) ok = k >= 3 * o->n || flag[o->id + k / 3];
            else if (k == o->items - 1 && (o->flags & P_GATE)) ok = seen[use[own].prev] == use[use[own].prev].readers;
            else if (k == 0 && o->type == OP_A && (o->flags & F_PARK)) ok = flag[N_TILE + o->park];
          }
          if (!ok) break;
          for (const Op* o = op[c]; o->type != OP_END; o++) {
            if (pos[c] == o->item0 + o->items + (o[1].type == OP_Q ? 7 : o[1].item0 == goal(c) ? -1 : 5)) {
              if (o->type == OP_A) flag[o->id] = 1;
              if (o->type == OP_Q && (o->flags & F_PARK)) flag[N_TILE + o->park] = 1;
              if (o->type == OP_O) flag[ID_PART + o->id / kH * 4 + o->quarter] = flag[ID_PART + o->id / kH * 4 + o->quarter + 1] = 1;
            }
            const int k = pos[c] - NBAR - o->item0, nw = o->n - TAIL;
            if (k == 0 && o->type == OP_A && (o->flags & F_PARK)) seen[N_TILE + o->park]++;
            if (o->type == OP_O && k >= 0 && k < o->items && k % 3 == 2 && (k / 3 < nw || k / 3 >= o->n)) seen[o->id + (k / 3 < nw ? k / 3 : k / 3 - TAIL)]++;
          }
        }
      }
    }
    for (int c = 0; c < 2 * n_pair; c++) if (pos[c] < goal(c)) return false;
  }
  int n_job = 0, longest = 0;
  for (int t = 0; t < N_TEAM; t++) if (kH - covered[t] > longest) longest = kH - covered[t];
  for (int c = 0; c < 2 * n_pair; c++) {
    uint32_t items = 0, cur = 0, pend = 0;
    int n = 0, ev = 0;
    auto item = [&](uint32_t bytes, int count) {
      for (int i = 0; i < count; i++) { if (cur + bytes > RING) cur = 0; cur += bytes; items++; }
    };
    auto event = [&](uint32_t e) { if (ev < MAX_EV) P.prog[c].ev[ev] = e; ev++; };
    for (const Op* o = op[c];; o++) {
      if (o->type != OP_END && phase && (o->type == OP_O) != (phase == 2)) continue;
      uint32_t cw = o->type | (items % NBAR) << 15 | ((items / NBAR) & 1) << 19 | (cur >> 12) << 20 | pend, pw = o->type | o->id << 2 | o->flags;
      const int ps = use[N_TILE + o->park].slot;
      pend = 0;
      if (o->type == OP_O) {
        pw |= o->n << 13 | o->quarter << 19;
        if (o->flags & P_WIDE) {
          cw |= o->n << 2 | (o->id / kH * 4 + o->quarter + 1) << 8 | C_WIDE;
          item(SZ_W, 3 * (o->n - TAIL));
          item(SZ_O, 6 * TAIL);
          pend = C_PEND | ((P.dbg & 8) ? C_SOON : 0);
          for (int i = 0; i < o->n; i++) event((o->id + i) | E_ON | (use[o->id + i].next ? 0 : E_LAST));
        } else {
          dem[n_job++] = {o->t0 - 1e6 * o->n, nullptr, (int)pw};
          st.own[c] = pw;
          pw = OP_O;
          event(E_DRAW | (items < 16 ? 0 : items - 16));
          for (int i = 0; i <= longest; i++) event(E_JOB | i);
        }
      } else if (o->type != OP_END) {
        const bool parks = o->type == OP_Q && (o->flags & F_PARK);
        cw |= (parks ? ps : use[o->id].slot) << 2 | (o->flags & F_PARK);
        if (o->flags & F_PARK) pw |= o->park << 13 | ps << 20;
        if (o->type == OP_Q) item(SZ_Q, 10);
        else { if (o->flags & F_PARK) { item(SZ_PARK, 1); event((N_TILE + o->park) | E_ON | (use[N_TILE + o->park].next ? 0 : E_LAST)); } item(SZ_KV, 32); }
        if (parks || o->type == OP_A) pend = C_PEND | ((P.dbg & 16) ? 0 : C_SOON);
        if (o->flags & P_GATE) event(use[parks ? N_TILE + o->park : o->id].prev | E_ON | E_FREE);
      }
      P.prog[c].c[n] = cw; P.prog[c].p[n++] = pw;
      if (o->type == OP_END) { if (o->t0 > st.end) st.end = o->t0; break; }
    }
    if (ev > MAX_EV) return false;
    while (ev < MAX_EV) P.prog[c].ev[ev++] = 0;
    while (n < MAX_OPS) { P.prog[c].c[n] = OP_END; P.prog[c].p[n++] = OP_END; }
    P.first[c] = (uint16_t)(P.prog[c].p[0] & 2047);
  }
  sort(dem, n_job);
  for (int i = 0; i < n_job; i++) P.job[i] = dem[i].id;
  for (int i = 0; i < ID_PART; i++) {
    if (i < N_TILE) P.slot[i] = use[i].slot;
    P.info[i] = (use[i].readers + use[i].next) | (use[i].next ? I_NEXT : 0);
  }
  if (stats) *stats = st;
  return true;
}

const char* const kPrograms[N_CL / 2] = {
  "NNNNNNNNNF4", "NNUNNNNNNF6", "NUNNJf17NNNF8", "PNNNNNNNNNFe", "PNJ121NNNNNF5", "NNNNNNNNNFa",
  "NNNNNUNNNF6", "NNNNNNNNNF1", "NNNNNNNNNF4", "NUNNNJe26NF8", "PNJ227NNNNFc", "PPNJ717NNNNUNF2",
  "NUNNJc13NNNNF2", "PNNJ325NNNNF3", "NUNUNJ926NFd", "NNNNNNNNNFa", "PNJ421NNNNNFf", "NUNNNJd16NNF7",
  "PNNNNNNNNNF3", "NNUJ618Jb23NFd", "NNNNNNNNNFb", "PNJ517NNNNNNFe", "NNNNNNNNNF0", "PNJ021NNNNNF5",
  "PNNNNNNNNN", "NUNNNJ819NNFb", "PNNNNNNNNNF9", "NNNNNNNNNF0", "PNNNNNNNNNF9", "NNNNNNNNNF1",
  "NNUNNNNNNFf", "NNNNNJa21NFc", "NUNNNNNNNF7",
};

const char* const* bench_programs() {
  return kPrograms;
}

}

extern "C" void kernel_launch(void* const* d_in, const int* in_sizes, int n_in, void* d_out, int out_size) {
  (void)in_sizes; (void)n_in; (void)out_size;
  static EncodeFn fn = nullptr;
  static int n_clusters = 0;
  if (!fn) {
    cudaDriverEntryPointQueryResult qr;
    void* f = nullptr;
    cudaGetDriverEntryPoint("cuTensorMapEncodeTiled", &f, cudaEnableDefault, &qr);
    fn = (EncodeFn)f;
    cudaFuncSetAttribute(fused_kernel, cudaFuncAttributeMaxDynamicSharedMemorySize, SMEM_BYTES);
    cudaLaunchConfig_t cfg = {};
    cfg.gridDim = dim3(132); cfg.blockDim = dim3(384); cfg.dynamicSmemBytes = SMEM_BYTES;
    cudaLaunchAttribute at[1];
    at[0].id = cudaLaunchAttributeClusterDimension; at[0].val.clusterDim.x = 2; at[0].val.clusterDim.y = 1; at[0].val.clusterDim.z = 1;
    cfg.attrs = at; cfg.numAttrs = 1;
    if (cudaOccupancyMaxActiveClusters(&n_clusters, fused_kernel, &cfg) != cudaSuccess || n_clusters < 1) n_clusters = 1;
    (void)cudaGetLastError();
  }
  static Params P;
  const CUtensorMapSwizzle S128 = CU_TENSOR_MAP_SWIZZLE_128B, S64 = CU_TENSOR_MAP_SWIZZLE_64B;
  for (int blk = 0; blk < 2; blk++) {
    void* const* in = d_in + 5 * blk;
    { const cuuint64_t d[] = {kD, kB * kSq}, s[] = {kD * 2}; const cuuint32_t b[] = {64, 128};
      encode(fn, &P.x[blk], in[0], 2, d, s, b, S128); }
    { const cuuint64_t d[] = {64, 8, 3, (cuuint64_t)kB * kH * kSk / 8}, s[] = {kDh * 2, 128, 8 * kDh * 2}; const cuuint32_t b[] = {64, 8, 3, 8};
      encode(fn, &P.k[blk], in[1], 4, d, s, b, S128);
      encode(fn, &P.v[blk], in[2], 4, d, s, b, S128); }
    { const cuuint64_t d[] = {64, kD, kHD / 64}, s[] = {kHD * 2, 128}; const cuuint32_t b[] = {64, 64, 3};
      encode(fn, &P.wq[blk], in[3], 3, d, s, b, S128); }
    { const cuuint64_t d[] = {32, 2, kHD / 8, 4, kD / 32}, s[] = {kD * 2, 8 * kD * 2, 2 * kD * 2, 64}; const cuuint32_t b[] = {32, 2, 4, 4, 5};
      encode(fn, &P.wo[blk], in[4], 5, d, s, b, S64); }
  }
  { const cuuint64_t d[] = {32, kB * kSq, 2 * kD / 32}, s[] = {2 * kD * 2, 64}; const cuuint32_t b[] = {32, 16, 1};
    encode(fn, &P.out, d_out, 3, d, s, b, S64); }

  P.dbg = DBG_DEFAULT;
  if (n_clusters >= N_CL && plan(bench_programs(), N_CL / 2, 0, P)) {
    fused_kernel<<<2 * N_CL, 384, SMEM_BYTES>>>(P);
  } else {
    char buf[2 * N_TEAM][16];
    const char* text[2 * N_TEAM];
    for (int i = 0; i < 2 * N_TEAM; i++) { snprintf(buf[i], sizeof(buf[i]), "NNNNNNNNF%x", i / 2); text[i] = buf[i]; }
    for (int phase = 1; phase <= 2; phase++) {
      plan(text, 2 * N_TEAM, phase, P);
      fused_kernel<<<8 * N_TEAM, 384, SMEM_BYTES>>>(P);
    }
  }
}
```

```cpp
#include <cuda_runtime.h>
#include <cuda_bf16.h>
#include <cuda.h>
#include <stdint.h>
#include <stdio.h>

namespace {

constexpr int kB = 8, kSq = 256, kD = 640, kH = 32, kSk = 1024, kDh = 192;
constexpr int kHD = kH * kDh;
constexpr uint32_t RING = 224 * 1024;
constexpr uint32_t SZ_KV = 24576;
constexpr uint32_t SZ_Q = 16384 + 24576;
constexpr uint32_t SZ_O = 16384 + 20480;
constexpr uint32_t SZ_W = 16384 + 40960;
constexpr uint32_t SZ_PARK = 49152;
constexpr uint32_t SZ_OL = SZ_O + 8192;
constexpr int NBAR = 10;
constexpr int EARLY = 3;
#define XTAIL 2
constexpr int TAIL = XTAIL;
constexpr uint32_t KV_CH = 64, KV_SBO = 3072;
constexpr int SMEM_BYTES = RING + 1024 + 1024;
constexpr int N_TEAM = 16, N_CL = 66, MAX_OPS = 24, MAX_EV = 80, N_TILE = N_TEAM * kH, MAX_PARK = 128, ID_PART = N_TILE + MAX_PARK;
enum : uint32_t { OP_END = 0, OP_Q = 1, OP_A = 2, OP_O = 3, F_PARK = 1 << 11,
                  C_WIDE = 1 << 14, C_PEND = 1 << 26, C_SOON = 1 << 28,
                  P_GATE = 1 << 12, P_WIDE = 1 << 11, P_LD = 1 << 12, P_ST = 1 << 21, P_PRE = 1 << 22, I_NEXT = 8, E_ON = 1 << 15, E_FREE = 1 << 14, E_LAST = 1 << 13, E_DRAW = 1 << 12, E_JOB = 1 << 11 };

#define QDRAIN 0x54732710u
#define TRYNS 1500
#define PFN 10
#define SKEW 3
#define PUBNS 100
#define WATNS 100
constexpr uint32_t DBG_DEFAULT = 0x040817;

struct alignas(64) Params {
  uint16_t first[96];
  CUtensorMap x[2], wq[2], k[2], v[2], wo[2], out;
  struct {
    uint32_t c[MAX_OPS];
    uint32_t p[MAX_OPS];
    uint16_t ev[MAX_EV];
  } prog[N_CL];
  uint32_t job[4 * N_TEAM];
  uint16_t slot[N_TILE];
  uint8_t info[ID_PART];
  uint32_t dbg;
};

__device__ uint4 g_t[N_TILE * 2 * 3072];
__device__ uint4 g_part[N_TEAM * 4 * 2 * 3072];
__device__ unsigned int g_flag[(ID_PART + N_TEAM * 4) * 2];
__device__ unsigned int g_ticket;

template <int TB, int TA = 0>
__device__ __forceinline__ void wgmma_ss_n64(float (&d)[32], uint64_t da, uint64_t db, int scale_d) {
  asm volatile("{\n.reg .pred p;\nsetp.ne.b32 p, %34, 0;\n"
    "wgmma.mma_async.sync.aligned.m64n64k16.f32.bf16.bf16 {%0, %1, %2, %3, %4, %5, %6, %7, %8, %9, %10, %11, %12, %13, %14, %15, %16, %17, %18, %19, %20, %21, %22, %23, %24, %25, %26, %27, %28, %29, %30, %31}, %32, %33, p, 1, 1, %35, %36;\n}\n"
    : "+f"(d[0]), "+f"(d[1]), "+f"(d[2]), "+f"(d[3]), "+f"(d[4]), "+f"(d[5]), "+f"(d[6]), "+f"(d[7]), "+f"(d[8]), "+f"(d[9]), "+f"(d[10]), "+f"(d[11]), "+f"(d[12]), "+f"(d[13]), "+f"(d[14]), "+f"(d[15]), "+f"(d[16]), "+f"(d[17]), "+f"(d[18]), "+f"(d[19]), "+f"(d[20]), "+f"(d[21]), "+f"(d[22]), "+f"(d[23]), "+f"(d[24]), "+f"(d[25]), "+f"(d[26]), "+f"(d[27]), "+f"(d[28]), "+f"(d[29]), "+f"(d[30]), "+f"(d[31])
    : "l"(da), "l"(db), "r"(scale_d), "n"(TA), "n"(TB));
}
template <int TB>
__device__ __forceinline__ void wgmma_rs_n64(float (&d)[32], uint32_t a0, uint32_t a1, uint32_t a2, uint32_t a3, uint64_t db, int scale_d) {
  asm volatile("{\n.reg .pred p;\nsetp.ne.b32 p, %37, 0;\n"
    "wgmma.mma_async.sync.aligned.m64n64k16.f32.bf16.bf16 {%0, %1, %2, %3, %4, %5, %6, %7, %8, %9, %10, %11, %12, %13, %14, %15, %16, %17, %18, %19, %20, %21, %22, %23, %24, %25, %26, %27, %28, %29, %30, %31}, {%32, %33, %34, %35}, %36, p, 1, 1, %38;\n}\n"
    : "+f"(d[0]), "+f"(d[1]), "+f"(d[2]), "+f"(d[3]), "+f"(d[4]), "+f"(d[5]), "+f"(d[6]), "+f"(d[7]), "+f"(d[8]), "+f"(d[9]), "+f"(d[10]), "+f"(d[11]), "+f"(d[12]), "+f"(d[13]), "+f"(d[14]), "+f"(d[15]), "+f"(d[16]), "+f"(d[17]), "+f"(d[18]), "+f"(d[19]), "+f"(d[20]), "+f"(d[21]), "+f"(d[22]), "+f"(d[23]), "+f"(d[24]), "+f"(d[25]), "+f"(d[26]), "+f"(d[27]), "+f"(d[28]), "+f"(d[29]), "+f"(d[30]), "+f"(d[31])
    : "r"(a0), "r"(a1), "r"(a2), "r"(a3), "l"(db), "r"(scale_d), "n"(TB));
}
template <int TB, int TA = 0>
__device__ __forceinline__ void wgmma_ss_n160(float (&d)[80], uint64_t da, uint64_t db, int scale_d) {
  asm volatile("{\n.reg .pred p;\nsetp.ne.b32 p, %82, 0;\n"
    "wgmma.mma_async.sync.aligned.m64n160k16.f32.bf16.bf16 {%0, %1, %2, %3, %4, %5, %6, %7, %8, %9, %10, %11, %12, %13, %14, %15, %16, %17, %18, %19, %20, %21, %22, %23, %24, %25, %26, %27, %28, %29, %30, %31, %32, %33, %34, %35, %36, %37, %38, %39, %40, %41, %42, %43, %44, %45, %46, %47, %48, %49, %50, %51, %52, %53, %54, %55, %56, %57, %58, %59, %60, %61, %62, %63, %64, %65, %66, %67, %68, %69, %70, %71, %72, %73, %74, %75, %76, %77, %78, %79}, %80, %81, p, 1, 1, %83, %84;\n}\n"
    : "+f"(d[0]), "+f"(d[1]), "+f"(d[2]), "+f"(d[3]), "+f"(d[4]), "+f"(d[5]), "+f"(d[6]), "+f"(d[7]), "+f"(d[8]), "+f"(d[9]), "+f"(d[10]), "+f"(d[11]), "+f"(d[12]), "+f"(d[13]), "+f"(d[14]), "+f"(d[15]), "+f"(d[16]), "+f"(d[17]), "+f"(d[18]), "+f"(d[19]), "+f"(d[20]), "+f"(d[21]), "+f"(d[22]), "+f"(d[23]), "+f"(d[24]), "+f"(d[25]), "+f"(d[26]), "+f"(d[27]), "+f"(d[28]), "+f"(d[29]), "+f"(d[30]), "+f"(d[31]), "+f"(d[32]), "+f"(d[33]), "+f"(d[34]), "+f"(d[35]), "+f"(d[36]), "+f"(d[37]), "+f"(d[38]), "+f"(d[39]), "+f"(d[40]), "+f"(d[41]), "+f"(d[42]), "+f"(d[43]), "+f"(d[44]), "+f"(d[45]), "+f"(d[46]), "+f"(d[47]), "+f"(d[48]), "+f"(d[49]), "+f"(d[50]), "+f"(d[51]), "+f"(d[52]), "+f"(d[53]), "+f"(d[54]), "+f"(d[55]), "+f"(d[56]), "+f"(d[57]), "+f"(d[58]), "+f"(d[59]), "+f"(d[60]), "+f"(d[61]), "+f"(d[62]), "+f"(d[63]), "+f"(d[64]), "+f"(d[65]), "+f"(d[66]), "+f"(d[67]), "+f"(d[68]), "+f"(d[69]), "+f"(d[70]), "+f"(d[71]), "+f"(d[72]), "+f"(d[73]), "+f"(d[74]), "+f"(d[75]), "+f"(d[76]), "+f"(d[77]), "+f"(d[78]), "+f"(d[79])
    : "l"(da), "l"(db), "r"(scale_d), "n"(TA), "n"(TB));
}
template <int TB>
__device__ __forceinline__ void wgmma_rs_n160(float (&d)[80], uint32_t a0, uint32_t a1, uint32_t a2, uint32_t a3, uint64_t db, int scale_d) {
  asm volatile("{\n.reg .pred p;\nsetp.ne.b32 p, %85, 0;\n"
    "wgmma.mma_async.sync.aligned.m64n160k16.f32.bf16.bf16 {%0, %1, %2, %3, %4, %5, %6, %7, %8, %9, %10, %11, %12, %13, %14, %15, %16, %17, %18, %19, %20, %21, %22, %23, %24, %25, %26, %27, %28, %29, %30, %31, %32, %33, %34, %35, %36, %37, %38, %39, %40, %41, %42, %43, %44, %45, %46, %47, %48, %49, %50, %51, %52, %53, %54, %55, %56, %57, %58, %59, %60, %61, %62, %63, %64, %65, %66, %67, %68, %69, %70, %71, %72, %73, %74, %75, %76, %77, %78, %79}, {%80, %81, %82, %83}, %84, p, 1, 1, %86;\n}\n"
    : "+f"(d[0]), "+f"(d[1]), "+f"(d[2]), "+f"(d[3]), "+f"(d[4]), "+f"(d[5]), "+f"(d[6]), "+f"(d[7]), "+f"(d[8]), "+f"(d[9]), "+f"(d[10]), "+f"(d[11]), "+f"(d[12]), "+f"(d[13]), "+f"(d[14]), "+f"(d[15]), "+f"(d[16]), "+f"(d[17]), "+f"(d[18]), "+f"(d[19]), "+f"(d[20]), "+f"(d[21]), "+f"(d[22]), "+f"(d[23]), "+f"(d[24]), "+f"(d[25]), "+f"(d[26]), "+f"(d[27]), "+f"(d[28]), "+f"(d[29]), "+f"(d[30]), "+f"(d[31]), "+f"(d[32]), "+f"(d[33]), "+f"(d[34]), "+f"(d[35]), "+f"(d[36]), "+f"(d[37]), "+f"(d[38]), "+f"(d[39]), "+f"(d[40]), "+f"(d[41]), "+f"(d[42]), "+f"(d[43]), "+f"(d[44]), "+f"(d[45]), "+f"(d[46]), "+f"(d[47]), "+f"(d[48]), "+f"(d[49]), "+f"(d[50]), "+f"(d[51]), "+f"(d[52]), "+f"(d[53]), "+f"(d[54]), "+f"(d[55]), "+f"(d[56]), "+f"(d[57]), "+f"(d[58]), "+f"(d[59]), "+f"(d[60]), "+f"(d[61]), "+f"(d[62]), "+f"(d[63]), "+f"(d[64]), "+f"(d[65]), "+f"(d[66]), "+f"(d[67]), "+f"(d[68]), "+f"(d[69]), "+f"(d[70]), "+f"(d[71]), "+f"(d[72]), "+f"(d[73]), "+f"(d[74]), "+f"(d[75]), "+f"(d[76]), "+f"(d[77]), "+f"(d[78]), "+f"(d[79])
    : "r"(a0), "r"(a1), "r"(a2), "r"(a3), "l"(db), "r"(scale_d), "n"(TB));
}
template <int TB, int TA = 0>
__device__ __forceinline__ void wgmma_ss_n192(float (&d)[96], uint64_t da, uint64_t db, int scale_d) {
  asm volatile("{\n.reg .pred p;\nsetp.ne.b32 p, %98, 0;\n"
    "wgmma.mma_async.sync.aligned.m64n192k16.f32.bf16.bf16 {%0, %1, %2, %3, %4, %5, %6, %7, %8, %9, %10, %11, %12, %13, %14, %15, %16, %17, %18, %19, %20, %21, %22, %23, %24, %25, %26, %27, %28, %29, %30, %31, %32, %33, %34, %35, %36, %37, %38, %39, %40, %41, %42, %43, %44, %45, %46, %47, %48, %49, %50, %51, %52, %53, %54, %55, %56, %57, %58, %59, %60, %61, %62, %63, %64, %65, %66, %67, %68, %69, %70, %71, %72, %73, %74, %75, %76, %77, %78, %79, %80, %81, %82, %83, %84, %85, %86, %87, %88, %89, %90, %91, %92, %93, %94, %95}, %96, %97, p, 1, 1, %99, %100;\n}\n"
    : "+f"(d[0]), "+f"(d[1]), "+f"(d[2]), "+f"(d[3]), "+f"(d[4]), "+f"(d[5]), "+f"(d[6]), "+f"(d[7]), "+f"(d[8]), "+f"(d[9]), "+f"(d[10]), "+f"(d[11]), "+f"(d[12]), "+f"(d[13]), "+f"(d[14]), "+f"(d[15]), "+f"(d[16]), "+f"(d[17]), "+f"(d[18]), "+f"(d[19]), "+f"(d[20]), "+f"(d[21]), "+f"(d[22]), "+f"(d[23]), "+f"(d[24]), "+f"(d[25]), "+f"(d[26]), "+f"(d[27]), "+f"(d[28]), "+f"(d[29]), "+f"(d[30]), "+f"(d[31]), "+f"(d[32]), "+f"(d[33]), "+f"(d[34]), "+f"(d[35]), "+f"(d[36]), "+f"(d[37]), "+f"(d[38]), "+f"(d[39]), "+f"(d[40]), "+f"(d[41]), "+f"(d[42]), "+f"(d[43]), "+f"(d[44]), "+f"(d[45]), "+f"(d[46]), "+f"(d[47]), "+f"(d[48]), "+f"(d[49]), "+f"(d[50]), "+f"(d[51]), "+f"(d[52]), "+f"(d[53]), "+f"(d[54]), "+f"(d[55]), "+f"(d[56]), "+f"(d[57]), "+f"(d[58]), "+f"(d[59]), "+f"(d[60]), "+f"(d[61]), "+f"(d[62]), "+f"(d[63]), "+f"(d[64]), "+f"(d[65]), "+f"(d[66]), "+f"(d[67]), "+f"(d[68]), "+f"(d[69]), "+f"(d[70]), "+f"(d[71]), "+f"(d[72]), "+f"(d[73]), "+f"(d[74]), "+f"(d[75]), "+f"(d[76]), "+f"(d[77]), "+f"(d[78]), "+f"(d[79]), "+f"(d[80]), "+f"(d[81]), "+f"(d[82]), "+f"(d[83]), "+f"(d[84]), "+f"(d[85]), "+f"(d[86]), "+f"(d[87]), "+f"(d[88]), "+f"(d[89]), "+f"(d[90]), "+f"(d[91]), "+f"(d[92]), "+f"(d[93]), "+f"(d[94]), "+f"(d[95])
    : "l"(da), "l"(db), "r"(scale_d), "n"(TA), "n"(TB));
}
template <int TB>
__device__ __forceinline__ void wgmma_rs_n192(float (&d)[96], uint32_t a0, uint32_t a1, uint32_t a2, uint32_t a3, uint64_t db, int scale_d) {
  asm volatile("{\n.reg .pred p;\nsetp.ne.b32 p, %101, 0;\n"
    "wgmma.mma_async.sync.aligned.m64n192k16.f32.bf16.bf16 {%0, %1, %2, %3, %4, %5, %6, %7, %8, %9, %10, %11, %12, %13, %14, %15, %16, %17, %18, %19, %20, %21, %22, %23, %24, %25, %26, %27, %28, %29, %30, %31, %32, %33, %34, %35, %36, %37, %38, %39, %40, %41, %42, %43, %44, %45, %46, %47, %48, %49, %50, %51, %52, %53, %54, %55, %56, %57, %58, %59, %60, %61, %62, %63, %64, %65, %66, %67, %68, %69, %70, %71, %72, %73, %74, %75, %76, %77, %78, %79, %80, %81, %82, %83, %84, %85, %86, %87, %88, %89, %90, %91, %92, %93, %94, %95}, {%96, %97, %98, %99}, %100, p, 1, 1, %102;\n}\n"
    : "+f"(d[0]), "+f"(d[1]), "+f"(d[2]), "+f"(d[3]), "+f"(d[4]), "+f"(d[5]), "+f"(d[6]), "+f"(d[7]), "+f"(d[8]), "+f"(d[9]), "+f"(d[10]), "+f"(d[11]), "+f"(d[12]), "+f"(d[13]), "+f"(d[14]), "+f"(d[15]), "+f"(d[16]), "+f"(d[17]), "+f"(d[18]), "+f"(d[19]), "+f"(d[20]), "+f"(d[21]), "+f"(d[22]), "+f"(d[23]), "+f"(d[24]), "+f"(d[25]), "+f"(d[26]), "+f"(d[27]), "+f"(d[28]), "+f"(d[29]), "+f"(d[30]), "+f"(d[31]), "+f"(d[32]), "+f"(d[33]), "+f"(d[34]), "+f"(d[35]), "+f"(d[36]), "+f"(d[37]), "+f"(d[38]), "+f"(d[39]), "+f"(d[40]), "+f"(d[41]), "+f"(d[42]), "+f"(d[43]), "+f"(d[44]), "+f"(d[45]), "+f"(d[46]), "+f"(d[47]), "+f"(d[48]), "+f"(d[49]), "+f"(d[50]), "+f"(d[51]), "+f"(d[52]), "+f"(d[53]), "+f"(d[54]), "+f"(d[55]), "+f"(d[56]), "+f"(d[57]), "+f"(d[58]), "+f"(d[59]), "+f"(d[60]), "+f"(d[61]), "+f"(d[62]), "+f"(d[63]), "+f"(d[64]), "+f"(d[65]), "+f"(d[66]), "+f"(d[67]), "+f"(d[68]), "+f"(d[69]), "+f"(d[70]), "+f"(d[71]), "+f"(d[72]), "+f"(d[73]), "+f"(d[74]), "+f"(d[75]), "+f"(d[76]), "+f"(d[77]), "+f"(d[78]), "+f"(d[79]), "+f"(d[80]), "+f"(d[81]), "+f"(d[82]), "+f"(d[83]), "+f"(d[84]), "+f"(d[85]), "+f"(d[86]), "+f"(d[87]), "+f"(d[88]), "+f"(d[89]), "+f"(d[90]), "+f"(d[91]), "+f"(d[92]), "+f"(d[93]), "+f"(d[94]), "+f"(d[95])
    : "r"(a0), "r"(a1), "r"(a2), "r"(a3), "l"(db), "r"(scale_d), "n"(TB));
}

__device__ __forceinline__ uint32_t smem_u32(const void* p) { return (uint32_t)__cvta_generic_to_shared(p); }
__device__ __forceinline__ void wg_fence() { asm volatile("wgmma.fence.sync.aligned;" ::: "memory"); }
__device__ __forceinline__ void wg_commit() { asm volatile("wgmma.commit_group.sync.aligned;" ::: "memory"); }
template <int N> __device__ __forceinline__ void wg_wait() { asm volatile("wgmma.wait_group.sync.aligned %0;" ::"n"(N) : "memory"); }
__device__ __forceinline__ void sched_fence(uint32_t& keep, bool never) {
  asm volatile("{\n.reg .pred p;\nsetp.ne.b32 p, %1, 0;\n@p mov.u32 %0, %%clock;\n}\n" : "+r"(keep) : "r"((int)never) : "memory");
}
template <int N> __device__ __forceinline__ void fence_regs(float (&r)[N]) {
#pragma unroll
  for (int i = 0; i < N; i++) asm volatile("" : "+f"(r[i])::"memory");
}
template <int N> __device__ __forceinline__ void undefine(float (&r)[N]) {
#pragma unroll
  for (int i = 0; i < N; i++) asm volatile("" : "=f"(r[i]));
}
template <int N> __device__ __forceinline__ void fence_regs(uint32_t (&r)[N]) {
#pragma unroll
  for (int i = 0; i < N; i++) asm volatile("" : "+r"(r[i])::"memory");
}
__device__ __forceinline__ uint64_t mk_desc(uint32_t a16, uint32_t lbo, uint32_t sbo, uint32_t swz) {
  uint64_t d;
  asm("mov.b64 %0, {%1, %2};" : "=l"(d) : "r"(a16 + ((lbo >> 4) << 16)), "r"((sbo >> 4) | (swz << 30)));
  return d;
}
__device__ __forceinline__ void mbar_init(uint32_t bar, uint32_t cnt) {
  asm volatile("mbarrier.init.shared::cta.b64 [%0], %1;" ::"r"(bar), "r"(cnt) : "memory");
}
__device__ __forceinline__ void mbar_expect(uint32_t bar, uint32_t tx) {
  asm volatile("mbarrier.arrive.expect_tx.shared::cta.b64 _, [%0], %1;" ::"r"(bar), "r"(tx) : "memory");
}
__device__ __forceinline__ bool mbar_test(uint32_t bar, uint32_t ph) {
  uint32_t ok;
  asm volatile("{\n.reg .pred p;\nmbarrier.test_wait.parity.shared::cta.b64 p, [%1], %2;\nselp.u32 %0, 1, 0, p;\n}\n"
               : "=r"(ok) : "r"(bar), "r"(ph) : "memory");
  return ok;
}
__device__ __forceinline__ bool mbar_try(uint32_t bar, uint32_t ph, uint32_t ns) {
  uint32_t ok;
  asm volatile("{\n.reg .pred p;\nmbarrier.try_wait.parity.shared::cta.b64 p, [%1], %2, %3;\nselp.u32 %0, 1, 0, p;\n}\n"
               : "=r"(ok) : "r"(bar), "r"(ph), "r"(ns) : "memory");
  return ok;
}
__device__ __forceinline__ void mbar_wait(uint32_t bar, uint32_t ph) {
  asm volatile("{\n.reg .pred p;\n.reg .u32 n;\nmov.u32 n, 0;\n"
               "LOOP:\nmbarrier.try_wait.parity.shared::cta.b64 p, [%0], %1;\n@p bra DONE;\n"
               "add.u32 n, n, 1;\nsetp.lt.u32 p, n, 0x1000000;\n@p bra LOOP;\ntrap;\n"
               "DONE:\n}\n" ::"r"(bar), "r"(ph) : "memory");
}
template <int NS> __device__ __forceinline__ void mbar_wait_slow(uint32_t bar, uint32_t ph) {
  asm volatile("{\n.reg .pred p;\n.reg .u32 n;\nmov.u32 n, 0;\n"
               "LOOP:\nmbarrier.test_wait.parity.shared::cta.b64 p, [%0], %1;\n@p bra DONE;\n"
               "nanosleep.u32 %2;\nadd.u32 n, n, 1;\nsetp.lt.u32 p, n, 0x400000;\n@p bra LOOP;\ntrap;\n"
               "DONE:\n}\n" ::"r"(bar), "r"(ph), "n"(NS) : "memory");
}
__device__ __forceinline__ void mbar_arrive_cluster_if(bool on, uint32_t addr) {
  asm volatile("{\n.reg .pred p;\nsetp.ne.b32 p, %1, 0;\n@p mbarrier.arrive.shared::cluster.b64 _, [%0];\n}\n" ::"r"(addr), "r"((int)on) : "memory");
}
__device__ __forceinline__ void tma2d(uint32_t dst, const CUtensorMap* m, uint32_t bar, int c0, int c1) {
  asm volatile("cp.async.bulk.tensor.2d.shared::cluster.global.mbarrier::complete_tx::bytes [%0], [%1, {%3, %4}], [%2];"
               ::"r"(dst), "l"(m), "r"(bar), "r"(c0), "r"(c1) : "memory");
}
__device__ __forceinline__ void tma3d(uint32_t dst, const CUtensorMap* m, uint32_t bar, int c0, int c1, int c2) {
  asm volatile("cp.async.bulk.tensor.3d.shared::cluster.global.mbarrier::complete_tx::bytes [%0], [%1, {%3, %4, %5}], [%2];"
               ::"r"(dst), "l"(m), "r"(bar), "r"(c0), "r"(c1), "r"(c2) : "memory");
}
__device__ __forceinline__ void tma3d_mc(uint32_t dst, const CUtensorMap* m, uint32_t bar, int c0, int c1, int c2) {
  asm volatile("cp.async.bulk.tensor.3d.shared::cluster.global.mbarrier::complete_tx::bytes.multicast::cluster"
               " [%0], [%1, {%3, %4, %5}], [%2], %6;"
               ::"r"(dst), "l"(m), "r"(bar), "r"(c0), "r"(c1), "r"(c2), "h"((uint16_t)3) : "memory");
}
__device__ __forceinline__ void tma3d_store(const CUtensorMap* m, uint32_t src, int c0, int c1, int c2) {
  asm volatile("cp.async.bulk.tensor.3d.global.shared::cta.bulk_group [%0, {%2, %3, %4}], [%1];"
               ::"l"(m), "r"(src), "r"(c0), "r"(c1), "r"(c2) : "memory");
}
__device__ __forceinline__ void bar_sync(int id, int n) { asm volatile("bar.sync %0, %1;" ::"r"(id), "r"(n) : "memory"); }
__device__ __forceinline__ uint32_t pack_bf16(float lo, float hi) {
  uint32_t r;
  asm("cvt.rn.bf16x2.f32 %0, %1, %2;" : "=r"(r) : "f"(hi), "f"(lo));
  return r;
}
__device__ __forceinline__ float ex2(float x) {
  float y;
  asm("ex2.approx.ftz.f32 %0, %1;" : "=f"(y) : "f"(x));
  return y;
}
__device__ __forceinline__ float rcp(float x) {
  float y;
  asm("rcp.approx.ftz.f32 %0, %1;" : "=f"(y) : "f"(x));
  return y;
}
__device__ __forceinline__ void stsm4(uint32_t addr, uint32_t a, uint32_t b, uint32_t c, uint32_t d) {
  asm volatile("stmatrix.sync.aligned.m8n8.x4.shared.b16 [%0], {%1, %2, %3, %4};" ::"r"(addr), "r"(a), "r"(b), "r"(c), "r"(d) : "memory");
}

__device__ __forceinline__ void tma4d_mc_hint(uint32_t dst, const CUtensorMap* m, uint32_t bar, int c3, uint64_t pol) {
  asm volatile("cp.async.bulk.tensor.4d.shared::cluster.global.mbarrier::complete_tx::bytes.multicast::cluster.L2::cache_hint"
               " [%0], [%1, {%3, %3, %3, %4}], [%2], %5, %6;"
               ::"r"(dst), "l"(m), "r"(bar), "r"(0), "r"(c3), "h"((uint16_t)3), "l"(pol) : "memory");
}
__device__ __forceinline__ void tma5d_mc(uint32_t dst, const CUtensorMap* m, uint32_t bar, int c2, int c4) {
  asm volatile("cp.async.bulk.tensor.5d.shared::cluster.global.mbarrier::complete_tx::bytes.multicast::cluster"
               " [%0], [%1, {%3, %3, %4, %3, %5}], [%2], %6;"
               ::"r"(dst), "l"(m), "r"(bar), "r"(0), "r"(c2), "r"(c4), "h"((uint16_t)3) : "memory");
}
__device__ __forceinline__ void bulk_load_hint(uint32_t dst, const void* src, uint32_t bytes, uint32_t bar, uint64_t pol) {
  asm volatile("cp.async.bulk.shared::cluster.global.mbarrier::complete_tx::bytes.L2::cache_hint [%0], [%1], %2, [%3], %4;"
               ::"r"(dst), "l"(src), "r"(bytes), "r"(bar), "l"(pol) : "memory");
}
__device__ __forceinline__ void stg128_hint(void* p, uint32_t a, uint32_t b, uint32_t c, uint32_t d, uint64_t pol) {
  asm volatile("st.global.L2::cache_hint.v4.b32 [%0], {%1, %2, %3, %4}, %5;" ::"l"(p), "r"(a), "r"(b), "r"(c), "r"(d), "l"(pol) : "memory");
}
__device__ __forceinline__ void stg2_if(bool on, void* p, uint32_t a, uint32_t b, uint32_t c, uint32_t d, uint32_t e, uint32_t f,
                                        uint32_t g, uint32_t h, uint64_t pol) {
  asm volatile("{\n.reg .pred p;\nsetp.ne.b32 p, %10, 0;\n"
               "@p st.global.L2::cache_hint.v4.b32 [%0], {%1, %2, %3, %4}, %9;\n"
               "@p st.global.L2::cache_hint.v4.b32 [%0 + 512], {%5, %6, %7, %8}, %9;\n}\n"
               ::"l"(p), "r"(a), "r"(b), "r"(c), "r"(d), "r"(e), "r"(f), "r"(g), "r"(h), "l"(pol), "r"((int)on) : "memory");
}
__device__ __forceinline__ uint64_t make_policy(bool first) {
  uint64_t pf, pn;
  asm("createpolicy.fractional.L2::evict_first.b64 %0, 1.0;" : "=l"(pf));
  asm("createpolicy.fractional.L2::evict_normal.b64 %0, 1.0;" : "=l"(pn));
  return first ? pf : pn;
}
__device__ __forceinline__ bool elect() {
  uint32_t ok;
  asm volatile("{\n.reg .pred p;\nelect.sync _|p, 0xffffffff;\nselp.u32 %0, 1, 0, p;\n}\n" : "=r"(ok));
  return ok;
}
__device__ __forceinline__ void mbar_arrive(uint32_t bar) {
  asm volatile("mbarrier.arrive.shared::cta.b64 _, [%0];" ::"r"(bar) : "memory");
}
__device__ __forceinline__ void mbar_arrive_if(bool on, uint32_t bar) {
  asm volatile("{\n.reg .pred p;\nsetp.ne.b32 p, %1, 0;\n@p mbarrier.arrive.shared::cta.b64 _, [%0];\n}\n" ::"r"(bar), "r"((int)on) : "memory");
}
__device__ __forceinline__ void stg128(void* p, uint32_t a, uint32_t b, uint32_t c, uint32_t d) {
  asm volatile("st.global.v4.b32 [%0], {%1, %2, %3, %4};" ::"l"(p), "r"(a), "r"(b), "r"(c), "r"(d) : "memory");
}
__device__ __forceinline__ void lds2_if(bool on, uint32_t p, uint32_t (&t)[8]) {
  asm volatile("{\n.reg .pred p;\nsetp.ne.b32 p, %9, 0;\n@p ld.shared.v4.b32 {%0, %1, %2, %3}, [%8];\n@p ld.shared.v4.b32 {%4, %5, %6, %7}, [%8 + 512];\n}\n"
               : "+r"(t[0]), "+r"(t[1]), "+r"(t[2]), "+r"(t[3]), "+r"(t[4]), "+r"(t[5]), "+r"(t[6]), "+r"(t[7]) : "r"(p), "r"((int)on) : "memory");
}
__device__ __forceinline__ void lds128(uint32_t p, uint32_t& a, uint32_t& b, uint32_t& c, uint32_t& d) {
  asm volatile("ld.shared.v4.b32 {%0, %1, %2, %3}, [%4];" : "=r"(a), "=r"(b), "=r"(c), "=r"(d) : "r"(p) : "memory");
}
template <class T> __device__ __forceinline__ T* ptr_add(T* base, uint32_t bytes) {
  T* r;
  asm("{\n.reg .u32 lo, hi;\nmov.b64 {lo, hi}, %1;\nadd.cc.u32 lo, lo, %2;\naddc.u32 hi, hi, 0;\nmov.b64 %0, {lo, hi};\n}\n" : "=l"(r) : "l"(base), "r"(bytes));
  return r;
}
__device__ __forceinline__ uint32_t lds32(uint32_t p) {
  uint32_t v;
  asm volatile("ld.volatile.shared.u32 %0, [%1];" : "=r"(v) : "r"(p) : "memory");
  return v;
}
__device__ __forceinline__ uint32_t flag_get(const unsigned int* p) {
  uint32_t v;
  asm volatile("ld.acquire.gpu.global.u32 %0, [%1];" : "=r"(v) : "l"(p) : "memory");
  return v;
}
__device__ __forceinline__ void wait_progress(uint32_t p, uint32_t target) {
  asm volatile("{\n.reg .pred p;\n.reg .u32 n, v;\nmov.u32 n, 0;\n"
               "LOOP:\nld.acquire.cta.shared.u32 v, [%0];\nsetp.ge.u32 p, v, %1;\n@p bra DONE;\n"
               "nanosleep.u32 %2;\nadd.u32 n, n, 1;\nsetp.lt.u32 p, n, 0x400000;\n@p bra LOOP;\ntrap;\n"
               "DONE:\n}\n" ::"r"(p), "r"(target), "n"(400) : "memory");
}
__device__ __forceinline__ void flag_set(unsigned int* p, uint32_t v) {
  asm volatile("st.release.gpu.global.u32 [%0], %1;" ::"l"(p), "r"(v) : "memory");
}
__device__ __forceinline__ void flag_dec(unsigned int* p) {
  asm volatile("red.relaxed.gpu.global.add.u32 [%0], 0xffffffff;" ::"l"(p) : "memory");
}

struct Cursor {
  int bi;
  uint32_t ph;
  __device__ __forceinline__ void next() {
    if (++bi == NBAR) { bi = 0; ph ^= 1; }
  }
};

constexpr float kScaleLog2 = 0.07216878364870322f * 1.4426950408889634f;
constexpr float kSumLimit = 1048576.0f;

__global__ void __cluster_dims__(2, 1, 1) __launch_bounds__(384, 1)
fused_kernel(const __grid_constant__ Params P) {
  extern __shared__ uint8_t smem_raw[];
  const uint32_t sbase = (smem_u32(smem_raw) + 1023) & ~1023u;
  const uint32_t full0 = sbase + RING, empty0 = full0 + 8 * NBAR, odone0 = empty0 + 8 * NBAR, ev0 = odone0 + 8 * MAX_OPS;
  const uint32_t progress = ev0 + 8 * MAX_EV, jobw = progress + 4;
  const uint32_t rank = blockIdx.x & 1;
  const int role = blockIdx.x >> 1;
  const int wid = __shfl_sync(0xffffffffu, (int)(threadIdx.x >> 5), 0);
  const int wg = wid >> 2;

  if (wid < 8) {
    if (elect()) {
#pragma unroll
      for (int j = 0; j < 16; j++) {
        const int i = EARLY + 16 * wid + j;
        if (i < 2 * NBAR + MAX_OPS + MAX_EV) mbar_init(full0 + 8 * i, i < NBAR ? 1 : i < 2 * NBAR ? 16 : i < 2 * NBAR + MAX_OPS ? 8 : 1);
      }
      if (wid == 7) asm volatile("st.shared.v2.u32 [%0], {0, 0};\nfence.acq_rel.cta;" ::"r"(progress) : "memory");
      asm volatile("fence.mbarrier_init.release.cluster;" ::: "memory");
    }
  } else if (wid == 8) {
    const uint32_t op0 = P.first[role];
    if (elect()) {
#pragma unroll
      for (int k = 0; k < EARLY; k++) mbar_init(full0 + 8 * k, 1);
      asm volatile("fence.mbarrier_init.release.cluster;" ::: "memory");
      const int blk = (op0 >> 10) & 1;
      if ((op0 & 3) == OP_Q) {
#pragma unroll
        for (int k = 0; k < EARLY; k++) {
          mbar_expect(full0 + 8 * k, SZ_Q);
          tma2d(sbase + k * SZ_Q, &P.x[blk], full0 + 8 * k, 64 * k, ((op0 >> 7) & 7) * kSq + rank * 128);
          tma3d(sbase + k * SZ_Q + 16384, &P.wq[blk], full0 + 8 * k, 0, 64 * k, 3 * ((op0 >> 2) & 31));
        }
      }
      asm volatile("prefetch.tensormap [%0];" ::"l"(rank ? &P.v[blk] : &P.k[blk]) : "memory");
    }
  }
  __syncwarp();
  asm volatile("barrier.cluster.arrive.relaxed.aligned;\nbarrier.cluster.wait.aligned;" ::: "memory");

  if (wg < 2) {
    asm volatile("setmaxnreg.inc.sync.aligned.u32 240;");
    const uint32_t* prog = P.prog[role].c;
    const int lane = threadIdx.x & 31, warp = wid & 3;
    uint32_t empty_rem;
    asm volatile("mapa.shared::cluster.u32 %0, %1, %2;" : "=r"(empty_rem) : "r"(empty0), "r"(lane & 1));
    auto release = [&](int slot) { mbar_arrive_cluster_if(lane < 2, empty_rem + 8 * slot); };
    Cursor r{0, 0};
    const uint32_t ring16 = (sbase & 0x3FFFF) >> 4;
    uint32_t cur = ring16;
    bool rdy0 = false, rdy1 = false;
    auto probe1 = [&]() { rdy0 = mbar_test(full0 + 8 * r.bi, r.ph); };
    auto probe2 = [&]() {
      Cursor n = r;
      rdy0 = mbar_test(full0 + 8 * n.bi, n.ph);
      n.next();
      rdy1 = mbar_test(full0 + 8 * n.bi, n.ph);
    };
    auto take = [&](bool rdy, uint32_t bytes, uint32_t& addr) {
      const int bi = r.bi;
      if (__builtin_expect(!__all_sync(0xffffffffu, rdy), 0)) mbar_wait(full0 + 8 * r.bi, r.ph);
      r.next();
      if (cur > ring16 + ((RING - bytes) >> 4)) cur = ring16;
      addr = cur;
      cur += bytes >> 4;
      return bi;
    };
    uint32_t keep = 0;
    const bool never = P.dbg == 0xffffffffu;
    uint32_t q[48];
#pragma unroll
    for (int i = 0; i < 48; i++) q[i] = 0;
    const int row = wg * 64 + warp * 16 + (lane >> 2);
    const int img0 = row * 4 + ((lane & 3) ^ ((row >> 1) & 3));
    uint4* pend = nullptr;
    bool pend_any = false;
    uint64_t spol;
    int pc = 0;
    auto slab = [&](int c, int i0) {
#pragma unroll
      for (int i = i0; i < 6; i++)
        stg2_if(c == i, pend + i * 512, q[8 * i], q[8 * i + 1], q[8 * i + 2], q[8 * i + 3],
                q[8 * i + 4], q[8 * i + 5], q[8 * i + 6], q[8 * i + 7], spol);
    };
    auto drain = [&](int c) {
      if (!pend_any || c >= 6) return;
      slab(c, 0);
      if (c == 5) {
        __syncwarp();
        mbar_arrive_if(lane == 0, odone0 - 8 + 8 * pc);
      }
    };

    for (;; pc++) {
      uint32_t op = prog[pc];
      const int type = op & 3;
      auto enter = [&]() {
        r.bi = (op >> 15) & 15; r.ph = (op >> 19) & 1; cur = ring16 + (((op >> 20) & 63) << 8);
      };
      enter();
      pend_any = op & C_PEND;
      spol = make_policy(!(op & C_SOON));
      if (type == OP_END) {
#pragma unroll 1
        for (int c = 0; c < 6; c++) drain(c);
        asm volatile("barrier.cluster.arrive.relaxed;" ::: "memory");
        break;
      }
      {
        float s[32], o[96];
        uint32_t ad0;
        int bi0, sk1;
        uint32_t pa[16], pb[16];
        float mc0, mc1, l0, l1;
        bool shifted;
        uint32_t nop;
        auto expo = [&](float (&s)[32], uint32_t (&pout)[16], float& b0, float& b1, bool shift, auto mid) {
          float c0, c1;
#pragma unroll
          for (int i = 0; i < 8; i++) {
            const float e0 = ex2(shift ? s[4 * i] - mc0 : s[4 * i]), e1 = ex2(shift ? s[4 * i + 1] - mc0 : s[4 * i + 1]);
            const float e2 = ex2(shift ? s[4 * i + 2] - mc1 : s[4 * i + 2]), e3 = ex2(shift ? s[4 * i + 3] - mc1 : s[4 * i + 3]);
            if (i) { b0 += e0; c0 += e1; b1 += e2; c1 += e3; } else { b0 = e0; c0 = e1; b1 = e2; c1 = e3; }
            pout[2 * i] = pack_bf16(e0, e1); pout[2 * i + 1] = pack_bf16(e2, e3);
            if (i & 1) mid(i >> 1);
          }
          b0 += c0; b1 += c1;
        };
        auto rowmax = [&](float (&s)[32], float& m0, float& m1) {
          m0 = fmaxf(s[0], s[1]); m1 = fmaxf(s[2], s[3]);
#pragma unroll
          for (int i = 1; i < 8; i++) { m0 = fmaxf(m0, fmaxf(s[4 * i], s[4 * i + 1])); m1 = fmaxf(m1, fmaxf(s[4 * i + 2], s[4 * i + 3])); }
          m0 = fmaxf(m0, __shfl_xor_sync(0xffffffffu, m0, 1)); m1 = fmaxf(m1, __shfl_xor_sync(0xffffffffu, m1, 1));
          m0 = fmaxf(m0, __shfl_xor_sync(0xffffffffu, m0, 2)); m1 = fmaxf(m1, __shfl_xor_sync(0xffffffffu, m1, 2));
        };
        auto first = [&](float (&s)[32], int sk0, auto mid) {
          fence_regs(s);
          release(sk0);
          mc0 = 0.f; mc1 = 0.f;
          expo(s, pa, l0, l1, false, mid);
          shifted = __any_sync(0xffffffffu, !(fmaxf(l0, l1) <= kSumLimit && fminf(l0, l1) >= 1.f / kSumLimit));
          if (shifted) {
            rowmax(s, mc0, mc1);
            expo(s, pa, l0, l1, true, [](int) {});
          }
        };
        auto qk = [&](float (&s)[32], uint32_t ak, int k0 = 0, int k1 = 12) {
#pragma unroll
          for (int kk = k0; kk < k1; kk++)
            wgmma_rs_n64<0>(s, q[4 * kk], q[4 * kk + 1], q[4 * kk + 2], q[4 * kk + 3], mk_desc(ak + (kk >> 2) * KV_CH + (kk & 3) * 2, 16, KV_SBO, 1), kk != 0);
          if (k1 == 12) wg_commit();
        };
        auto pv = [&](uint32_t (&pin)[16], uint32_t av, int acc) {
#pragma unroll
          for (int kk = 0; kk < 4; kk++)
            wgmma_rs_n192<1>(o, pin[4 * kk], pin[4 * kk + 1], pin[4 * kk + 2], pin[4 * kk + 3], mk_desc(av + kk * (KV_SBO / 8), KV_CH * 16, KV_SBO, 1), acc || (kk != 0));
          wg_commit();
        };
        auto finish = [&](uint32_t (&pout)[16], int sk, int sv) {
          probe2();
          wg_wait<1>();
          fence_regs(s);
          release(sk);
          float b0, b1;
#pragma unroll 1
          for (bool redo = false;; redo = true) {
            expo(s, pout, b0, b1, false, [](int) {});
            if (!__any_sync(0xffffffffu, !redo && (shifted || !(fmaxf(b0, b1) <= kSumLimit)))) break;
            shifted = true;
            rowmax(s, b0, b1);
            b0 = fmaxf(mc0, b0); b1 = fmaxf(mc1, b1);
            const float a0 = ex2(mc0 - b0), a1 = ex2(mc1 - b1);
            mc0 = b0; mc1 = b1;
            l0 *= a0; l1 *= a1;
            wg_wait<0>();
            fence_regs(o);
#pragma unroll
            for (int i = 0; i < 24; i++) { o[4 * i] *= a0; o[4 * i + 1] *= a0; o[4 * i + 2] *= a1; o[4 * i + 3] *= a1; }
#pragma unroll
            for (int i = 0; i < 32; i++) s[i] -= (i & 2) ? mc1 : mc0;
          }
          l0 += b0; l1 += b1;
          wg_wait<0>();
          fence_regs(o);
          release(sv);
        };
        auto step = [&](uint32_t (&pin)[16], uint32_t (&pout)[16]) {
          uint32_t ak, av;
          const int sk = take(rdy0, SZ_KV, ak), sv = take(rdy1, SZ_KV, av);
          wg_fence();
          qk(s, ak);
          pv(pin, av, 1);
          finish(pout, sk, sv);
        };
        auto unpark = [&]() {
          uint32_t ad, ak;
          const int bi = take(rdy0, SZ_PARK, ad);
#pragma unroll
          for (int i = 0; i < 12; i++) lds128(sbase + (ad - ring16 + img0) * 16 + (i >> 1) * 8192 + (i & 1) * 512, q[4 * i], q[4 * i + 1], q[4 * i + 2], q[4 * i + 3]);
          const int sk0 = take(false, SZ_KV, ak);
          fence_regs(q);
          release(bi);
          wg_fence();
          qk(s, ak);
          probe2();
          return sk0;
        };
        auto mma4 = [&](uint32_t ad, int acc) {
#pragma unroll
          for (int kk = 0; kk < 4; kk++)
            wgmma_ss_n192<1>(o, mk_desc(ad + wg * 512 + kk * 2, 16, 1024, 1), mk_desc(ad + 1024 + kk * 128, 8192, 1024, 1), acc || kk != 0);
        };
        auto convert = [&](int i0, int i1) {
          sched_fence(keep, never);
#pragma unroll
          for (int i = i0; i < i1; i++) q[i] = pack_bf16(o[2 * i] * kScaleLog2, o[2 * i + 1] * kScaleLog2);
          sched_fence(keep, never);
        };
        auto kend = [&](int bi, int k) {
          wg_commit();
          drain(k < 8 ? (QDRAIN >> (4 * k)) & 7 : 7);
          probe1();
          wg_wait<0>();
          release(bi);
        };
        if (type == OP_O) {
          float c[80];
          int prev = 0;
          auto hand_over = [&](float (&c)[80], uint4* dst) {
            fence_regs(c);
#pragma unroll
            for (int i = 0; i < 48; i++) q[i] = i < 8 ? 0 : pack_bf16(c[2 * i - 16], c[2 * i - 15]);
            pend = dst;
          };
          auto mma2 = [&](float (&c)[80], uint32_t da, uint32_t db, int acc) {
            wgmma_ss_n160<1>(c, mk_desc(da, 16, 512, 2), mk_desc(db, 2048, 512, 2), acc);
            wgmma_ss_n160<1>(c, mk_desc(da + 2, 16, 512, 2), mk_desc(db + 64, 2048, 512, 2), 1);
          };
          auto kstep = [&](float (&c)[80], int acc, auto hook, uint32_t bytes = SZ_O) {
            uint32_t ad;
            const int bi = take(rdy0, bytes, ad);
            const uint32_t da = ad + wg * 256, db = ad + 1024;
            wg_fence();
            mma2(c, da, db, acc);
            wg_commit();
            if (acc) { wg_wait<1>(); mbar_arrive_cluster_if(lane < 2 && (acc == 1 || wg == 0), empty_rem + 8 * prev); }
            mma2(c, da + 512, db + 640, 1);
            wg_commit();
            prev = bi;
            hook();
            probe1();
            wg_wait<1>();
          };
          if (op & C_WIDE) {
            float d[80];
            const int nk = 3 * ((op >> 2) & 63);
            uint4* part = ptr_add(g_part, (((op >> 8) & 63) * 2 + rank) * SZ_PARK + img0 * 16);
            auto wstep = [&](int acc, auto hook) {
              uint32_t ad;
              const int bi = take(rdy0, SZ_W, ad);
              const uint32_t da = ad + wg * 256, db = ad + 1024;
              wg_fence();
              mma2(d, da, db, acc);
              mma2(d, da + 512, db + 640, 1);
              wg_commit();
              if (acc) { wg_wait<1>(); release(prev); }
              mma2(c, da, db + 1280, acc);
              mma2(c, da + 512, db + 1920, 1);
              wg_commit();
              prev = bi;
              hook();
              probe1();
              wg_wait<1>();
            };
            wstep(0, [&]() { drain(0); drain(1); });
#pragma unroll 1
            for (int k = 2; k < 6; k += 2) wstep(1, [&]() { drain(k); drain(k + 1); });
#pragma unroll 1
            for (int k = 3 + 3 * TAIL; k < nk; k++) {
              wstep(1, []() {});
            }
#pragma unroll 1
            for (int k = 0; k < 3 * TAIL; k++) kstep(d, 1, []() {});
            nop = prog[pc + 1];
            spol = make_policy(!(nop & C_SOON));
            kstep(c, 1, [&]() { hand_over(d, part - 6144); });
#pragma unroll 1
            for (int k = 1; k < 3 * TAIL; k++) kstep(c, 1, [&]() { slab(TAIL == 2 ? k : (0x50403201 >> (4 * k - 4)) & 7, 1); });
            if ((nop & 3) == OP_Q) {
              op = nop;
              enter();
              pc++;
              pend_any = true;
              bi0 = take(rdy0, SZ_Q, ad0);
              undefine(o);
              wg_fence();
              mma4(ad0, 0);
              wg_commit();
              wg_wait<1>();
              release(prev);
              hand_over(c, part);
              probe1();
              wg_wait<0>();
              release(bi0);
              fence_regs(o);
              goto next_head;
            }
            wg_wait<0>();
            release(prev);
            hand_over(c, part);
            continue;
          }
          auto unblock = [&](int k) {
            if (__all_sync(0xffffffffu, rdy0) || __all_sync(0xffffffffu, mbar_try(full0 + 8 * r.bi, r.ph, TRYNS))) return;
#pragma unroll 1
            for (; k < 6; k++) drain(k);
            pend_any = false;
          };
          uint32_t job;
          unblock(0);
          kstep(c, 0, [&]() { job = lds32(jobw); drain(0); });
#pragma unroll 1
          for (int k = 1; k < 6; k++) {
            unblock(k);
            kstep(c, 1, [&]() { drain(k); });
          }
          job = __shfl_sync(0xffffffffu, job, 0);
#pragma unroll 1
          for (int k = 3 * ((job >> 13) & 63); k > 11; k--) kstep(c, 1, []() {});
          uint32_t t[8], stage[3];
          float u[80];
          auto unpack = [&](int j) {
#pragma unroll
            for (int i = 0; i < 8; i++) {
              u[16 * j + 2 * i] = __uint_as_float(t[i] << 16); u[16 * j + 2 * i + 1] = __uint_as_float(t[i] & 0xffff0000u);
              asm volatile("" : "+f"(u[16 * j + 2 * i]), "+f"(u[16 * j + 2 * i + 1]));
            }
          };
#pragma unroll
          for (int i = 0; i < 8; i++) t[i] = 0;
          const uint32_t bytes = (job & P_LD) ? SZ_OL : SZ_O;
#pragma unroll
          for (int j = 0; j < 5; j++) {
            if (j == 5 - SKEW && wg == 1) {
              wg_wait<0>();
              release(prev);
              bar_sync(1, 256);
            }
            kstep(c, j == 5 - SKEW ? 2 : 1, [&]() {
              if (SKEW && j == 4) asm volatile("{\n.reg .pred p;\nsetp.eq.u32 p, %0, 0;\n@p bar.arrive 1, 256;\n}\n" ::"r"(wg) : "memory");
              if (j) unpack(j - 1);
              lds2_if(job & P_LD, sbase + (cur - ring16 + img0) * 16 - 8192, t);
              if (j >= 1 && j <= 3) stage[j - 1] = sbase + (cur - ring16) * 16 - bytes + wid * 1024;
            }, bytes);
          }
          unpack(4);
          sched_fence(keep, never);
          wg_wait<0>();
          fence_regs(c);
          release(prev);
          asm volatile("barrier.cluster.arrive.relaxed;" ::: "memory");
#pragma unroll
          for (int i = 0; i < 10; i++) {
            const int v = (i & 1) * 2 + (lane >> 4);
            const uint32_t sa = stage[i >> 2] + (i & 2) * 4096;
            stsm4(sa + (lane & 15) * 64 + ((v ^ ((lane >> 1) & 3)) << 4), pack_bf16(c[8 * i] + u[8 * i], c[8 * i + 1] + u[8 * i + 1]),
                  pack_bf16(c[8 * i + 2] + u[8 * i + 2], c[8 * i + 3] + u[8 * i + 3]), pack_bf16(c[8 * i + 4] + u[8 * i + 4], c[8 * i + 5] + u[8 * i + 5]),
                  pack_bf16(c[8 * i + 6] + u[8 * i + 6], c[8 * i + 7] + u[8 * i + 7]));
          }
          asm volatile("fence.proxy.async.shared::cta;" ::: "memory");
          __syncwarp();
          if (elect()) {
#pragma unroll
            for (int i = 0; i < 5; i++)
              tma3d_store(&P.out, stage[i >> 1] + (i & 1) * 8192, 0, ((job >> 7) & 7) * kSq + rank * 128 + wid * 16, ((job >> 10) & 1) * 20 + ((job >> 19) & 3) * 5 + i);
            asm volatile("cp.async.bulk.commit_group;\ncp.async.bulk.wait_group.read 0;" ::: "memory");
          }
          __syncwarp();
          break;
        }
        bi0 = take(rdy0, SZ_Q, ad0);
        undefine(o);
        wg_fence();
        mma4(ad0, 0);
        kend(bi0, 0);
        fence_regs(o);
      next_head:
        {
#pragma unroll 1
          for (int k = 1; k < ((op & F_PARK) ? 10 : 8); k++) {
            uint32_t ad;
            const int bi = take(rdy0, SZ_Q, ad);
            wg_fence();
            mma4(ad, 1);
            kend(bi, k);
          }
          if (op & F_PARK) {
            fence_regs(o);
            convert(0, 48);
            pend = ptr_add(g_t, (((op >> 2) & 511) * 2 + rank) * SZ_PARK + img0 * 16);
            continue;
          }
          uint32_t a8, a9, ak0, ak1;
          const int b8 = take(rdy0, SZ_Q, a8), b9 = take(false, SZ_Q, a9);
          wg_fence();
          mma4(a8, 1);
          wg_commit();
          mma4(a9, 1);
          wg_commit();
          pc++;
          wg_wait<1>();
          release(b8);
          const int sk0 = take(false, SZ_KV, ak0);
          wg_wait<0>();
          fence_regs(o);
          release(b9);
          float s0[32];
          convert(0, 32);
          wg_fence();
          qk(s0, ak0, 0, 4);
          convert(32, 48);
          wg_fence();
          qk(s0, ak0, 4, 12);
          sk1 = take(false, SZ_KV, ak1);
          probe1();
          wg_wait<0>();
          first(s0, sk0, [&](int i) {
            if (i == 0) return;
            sched_fence(keep, never);
            wg_fence();
            if (i == 1) qk(s, ak1, 0, 4);
            if (i == 2) qk(s, ak1, 4, 8);
            if (i == 3) qk(s, ak1, 8, 12);
            sched_fence(keep, never);
          });
        }
        for (;;) {
          {
            uint32_t av;
            const int sv = take(rdy0, SZ_KV, av);
            undefine(o);
            wg_fence();
            pv(pa, av, 0);
            finish(pb, sk1, sv);
          }
          nop = prog[pc + 1];
#pragma unroll 1
          for (int jj = 0; jj < 7; jj++) {
            step(pb, pa);
            step(pa, pb);
          }
          float i0, i1;
          auto last = [&]() {
            uint32_t av;
            const int sv = take(rdy0, SZ_KV, av);
            wg_fence();
            pv(pb, av, 1);
            sched_fence(keep, never);
            probe1();
            l0 += __shfl_xor_sync(0xffffffffu, l0, 1); l1 += __shfl_xor_sync(0xffffffffu, l1, 1);
            l0 += __shfl_xor_sync(0xffffffffu, l0, 2); l1 += __shfl_xor_sync(0xffffffffu, l1, 2);
            i0 = rcp(l0); i1 = rcp(l1);
            pend = ptr_add(g_t, (((op >> 2) & 511) * 2 + rank) * SZ_PARK + img0 * 16);
            return sv;
          };
          auto normalise = [&](uint32_t (&d)[48], auto mid) {
#pragma unroll
            for (int i = 0; i < 24; i++) {
              d[8 * (i >> 2) + (i & 3)] = pack_bf16(o[4 * i] * i0, o[4 * i + 1] * i0);
              d[8 * (i >> 2) + (i & 3) + 4] = pack_bf16(o[4 * i + 2] * i1, o[4 * i + 3] * i1);
              if ((i & 3) == 3 && i != 23) { sched_fence(keep, never); mid(i >> 2); }
            }
          };
          const int sv = last();
          if ((nop & 3) != OP_A) {
            op = nop;
            enter();
            pend_any = true;
            spol = make_policy(!(op & C_SOON));
            bi0 = take(rdy0 || (nop & 3) != OP_Q, SZ_Q, ad0);
            sched_fence(keep, never);
            wg_wait<0>();
            fence_regs(o);
            release(sv);
            normalise(q, [](int) {});
            undefine(o);
            if ((nop & 3) != OP_Q) break;
            sched_fence(keep, never);
            wg_fence();
            mma4(ad0, 0);
            pc++;
            kend(bi0, 0);
            fence_regs(o);
            goto next_head;
          }
          const int sk0 = unpark();
          wg_wait<1>();
          fence_regs(o);
          release(sv);
          uint32_t t[48];
          spol = make_policy(!(nop & C_SOON));
          auto st = [&](int i) {
            stg2_if(true, pend + i * 512, t[8 * i], t[8 * i + 1], t[8 * i + 2], t[8 * i + 3], t[8 * i + 4], t[8 * i + 5], t[8 * i + 6], t[8 * i + 7], spol);
          };
          normalise(t, [&](int i) { if (!(i & 1)) st(i >> 1); });
          wg_wait<0>();
          first(s, sk0, [&](int i) { if (i < 3) { sched_fence(keep, never); st(3 + i); } });
          __syncwarp();
          mbar_arrive_if(lane == 0, odone0 + 8 * pc);
          pc++;
          op = nop;
          uint32_t ak1;
          sk1 = take(rdy0, SZ_KV, ak1);
          rdy0 = rdy1;
          wg_fence();
          qk(s, ak1);
        }
      }
    }
    if (never) g_flag[0] = keep;
    asm volatile("barrier.cluster.wait;" ::: "memory");
  } else {
    asm volatile("setmaxnreg.dec.sync.aligned.u32 24;");
    const uint32_t* prog = P.prog[role].p;
    unsigned int* flag = g_flag + rank;
    if (wid == 8) {
      Cursor tail{0, 0};
      int head = 0, sh = 0;
      uint32_t cur = 0, used = 0;
      uint64_t fifo = 0;
      uint32_t dst, bar, ev = ev0, done = 0;
      uint64_t pol;
      asm volatile("createpolicy.fractional.L2::evict_first.b64 %0, 1.0;" : "=l"(pol));
      auto retire = [&]() {
        mbar_wait(empty0 + 8 * tail.bi, tail.ph);
        tail.next();
        used -= (uint32_t)fifo & 31;
        fifo >>= 5;
        sh -= 5;
        asm volatile("st.volatile.shared.u32 [%0], %1;" ::"r"(progress), "r"(++done) : "memory");
      };
      auto acquire = [&](uint32_t bytes) {
        uint32_t fp = bytes >> 12;
        if (cur + fp > (RING >> 12)) { fp += (RING >> 12) - cur; cur = 0; }
        used += fp;
        while (used > (RING >> 12) || sh == 5 * NBAR) retire();
        fifo |= (uint64_t)fp << sh;
        sh += 5;
        dst = sbase + (cur << 12);
        bar = full0 + 8 * head;
        cur += bytes >> 12;
        if (++head == NBAR) head = 0;
      };
      auto gate = [&]() {
        mbar_wait(ev, 0);
        ev += 8;
        asm volatile("fence.proxy.async.global;" ::: "memory");
      };
      for (int pc = 0;; pc++) {
        uint32_t op = prog[pc];
        const int type = op & 3;
        if (type == OP_END) break;
        if (op == OP_O) {
          gate();
          op = __shfl_sync(0xffffffffu, lds32(jobw), 0);
        }
        const int blk = (op >> 10) & 1;
        if (type == OP_Q) {
#pragma unroll 1
          for (int k = 0; k < 10; k++) {
            if (k == 9 && (op & P_GATE)) gate();
            acquire(SZ_Q);
            if ((pc > 0 || k >= EARLY) && elect()) {
              mbar_expect(bar, SZ_Q);
              tma2d(dst, &P.x[blk], bar, 64 * k, ((op >> 7) & 7) * kSq + rank * 128);
              if ((k & 1) == rank) tma3d_mc(dst + 16384, &P.wq[blk], bar, 0, 64 * k, 3 * ((op >> 2) & 31));
            }
          }
        } else if (type == OP_A) {
          const int row0 = ((op >> 2) & 255) * kSk;
          const CUtensorMap* kv_map = rank ? &P.v[blk] : &P.k[blk];
          if (op & F_PARK) {
            gate();
            acquire(SZ_PARK);
            if (elect()) {
              mbar_expect(bar, SZ_PARK);
              bulk_load_hint(dst, &g_t[((op >> 20) * 2 + rank) * 3072], SZ_PARK, bar, make_policy(P.dbg & 4));
            }
          }
#pragma unroll 1
          for (int t = 0; t < 32; t++) {
            const int isv = t == 31 ? 1 : (t == 0 ? 0 : (~t & 1));
            const int j = isv ? (t - 1) >> 1 : (t + 1) >> 1;
            if (t == 31 && (op & P_GATE)) gate();
            acquire(SZ_KV);
            if (elect()) {
              mbar_expect(bar, SZ_KV);
              if (isv == (int)rank) tma4d_mc_hint(dst, kv_map, bar, row0 / 8 + 8 * j, pol);
            }
          }
        } else {
          const int n = (op >> 13) & 63, nw = (op & P_WIDE) ? n - TAIL : 0;
          const uint64_t pol_o = make_policy(P.dbg & (nw ? 1 : 2));
          const uint4* part = &g_part[((((op >> 5) & 60) + ((op >> 19) & 3)) * 2 + rank) * 3072 + 512];
#pragma unroll 1
          for (int i = 0; i < n + (nw ? TAIL : 0); i++) {
            const int id = ((op >> 2) & 511) + (i < n ? i : i - TAIL), col = 5 * (((op >> 19) & 3) + (i >= n));
            const uint4* src = &g_t[(P.slot[id] * 2 + rank) * 3072];
            if ((op & P_LD) && i == ((op & P_PRE) ? 0 : n - 2)) gate();
            if (i < n) gate();
#pragma unroll 1
            for (int k = 0; k < 3; k++) {
              const uint32_t j = (op & P_LD) ? 3 * (i - n) + k + 5 : 5, bytes = i < nw ? SZ_W : j < 5 ? SZ_OL : SZ_O;
              acquire(bytes);
              if (elect()) {
                mbar_expect(bar, bytes);
                tma5d_mc(dst + 16384 + rank * 10240, &P.wo[blk], bar, 24 * (id & 31) + 8 * k + 4 * rank, col);
                bulk_load_hint(dst, src + k * 1024, 16384, bar, pol_o);
                if (i < nw) tma5d_mc(dst + SZ_O + rank * 10240, &P.wo[blk], bar, 24 * (id & 31) + 8 * k + 4 * rank, col + 5);
                if (j < 5) bulk_load_hint(dst + SZ_O, part + j * 512, 8192, bar, pol);
                if ((op & P_PRE) && (uint32_t)(3 * i + k) < PFN)
                  asm volatile("cp.async.bulk.prefetch.L2.global [%0], %1;" ::"l"(part + (3 * i + k) * (2560 / PFN)), "n"(40960 / PFN) : "memory");
              }
            }
          }
        }
      }
#pragma unroll 1
      while (sh) retire();
    } else if (threadIdx.x == 288) {
      for (int pc = 0;; pc++) {
        const uint32_t op = prog[pc];
        const int type = op & 3;
        if (type == OP_END) break;
        if (type == OP_Q ? !(op & F_PARK) : type == OP_O && !(op & P_ST)) continue;
        const int id = type == OP_A ? (op >> 2) & 511 : type == OP_Q ? N_TILE + ((op >> 13) & 127) : ID_PART + ((op >> 5) & 60) + ((op >> 19) & 3);
        const uint32_t v = type == OP_O ? 1 : P.info[id] & 7;
        mbar_wait_slow<PUBNS>(odone0 + 8 * pc, 0);
        flag_set(flag + 2 * id, v);
        if (type == OP_O && (op & P_WIDE)) flag_set(flag + 2 * id + 2, v);
      }
    } else if (wid == 10) {
      int i = threadIdx.x & 31;
      uint32_t e = i < 8 ? P.prog[role].ev[i] : 0;
      for (uint32_t n = 0; __any_sync(0xffffffffu, e); n++) {
        uint32_t job = (e & (E_DRAW | E_JOB)) ? lds32(jobw) : 0;
        if ((e & E_DRAW) && rank == 0 && lds32(progress) >= (e & 1023)) {
          job = P.job[atomicInc(&g_ticket, 4 * N_TEAM - 1)];
          asm volatile("{\n.reg .u32 a;\nmapa.shared::cluster.u32 a, %0, 1;\nst.volatile.shared::cluster.u32 [a], %1;\n"
                       "st.volatile.shared.u32 [%0], %1;\n}\n" ::"r"(jobw), "r"(job) : "memory");
        }
        if ((e & E_JOB) && job) {
          const uint32_t j = e & 63, heads = (job >> 13) & 63, jp = !(job & P_LD) ? 63 : (job & P_PRE) ? 0 : heads - 2, h = j - (j > jp);
          e = j == jp ? (ID_PART + ((job >> 5) & 60) + ((job >> 19) & 3)) | E_ON | E_LAST : h < heads ? (((job >> 2) & 511) + h) | E_ON | E_LAST : 0;
        }
        unsigned int* f = ptr_add(flag, 8 * (e & 1023));
        const bool ok = (e & E_ON) ? flag_get(f) - 1 < ((e & E_FREE) ? 1 : 7) : (e & E_DRAW) && job;
        if (ok) {
          mbar_arrive(ev0 + 8 * i);
          if (e & (E_FREE | E_LAST)) flag_dec(f);
          i += 8;
          e = i < MAX_EV ? P.prog[role].ev[i] : 0;
        }
        asm volatile("{\n.reg .pred p;\nsetp.ge.u32 p, %0, 0x400000;\n@p trap;\n}\n" ::"r"(n));
        if (!__any_sync(0xffffffffu, ok)) __nanosleep(WATNS);
      }
    } else if (threadIdx.x == 352) {
      uint32_t items = 0;
      auto read = [&](int id) {
        if (!(P.info[id] & I_NEXT)) return;
        wait_progress(progress, items);
        flag_dec(flag + 2 * id);
      };
      for (int pc = 0;; pc++) {
        const uint32_t op = prog[pc];
        const int type = op & 3;
        if (type == OP_END) break;
        if (type == OP_O) {
          const int n = (op >> 13) & 63;
#pragma unroll 1
          for (int i = 0; i < n; i++) {
            items += (op & P_WIDE) && i == n - TAIL ? 3 * TAIL + 3 : 3;
            read(((op >> 2) & 511) + i);
          }
        } else if (type == OP_A) {
          if (op & F_PARK) { items++; read(N_TILE + ((op >> 13) & 127)); }
          items += 32;
        } else {
          items += 10;
        }
      }
    }
    __syncwarp();
    asm volatile("barrier.cluster.arrive.relaxed;\nbarrier.cluster.wait;" ::: "memory");
  }
}

typedef CUresult (*EncodeFn)(CUtensorMap*, CUtensorMapDataType, cuuint32_t, void*, const cuuint64_t*, const cuuint64_t*,
                             const cuuint32_t*, const cuuint32_t*, CUtensorMapInterleave, CUtensorMapSwizzle,
                             CUtensorMapL2promotion, CUtensorMapFloatOOBfill);

void encode(EncodeFn fn, CUtensorMap* m, const void* ptr, int rank, const cuuint64_t* dims, const cuuint64_t* strides,
            const cuuint32_t* box, CUtensorMapSwizzle swz) {
  const cuuint32_t es[5] = {1, 1, 1, 1, 1};
  CUresult r = fn(m, CU_TENSOR_MAP_DATA_TYPE_BFLOAT16, rank, const_cast<void*>(ptr), dims, strides, box, es,
                  CU_TENSOR_MAP_INTERLEAVE_NONE, swz, CU_TENSOR_MAP_L2_PROMOTION_L2_128B, CU_TENSOR_MAP_FLOAT_OOB_FILL_NONE);
  if (r != CUDA_SUCCESS) fprintf(stderr, "cuTensorMapEncodeTiled failed: %d\n", (int)r);
}

struct Op { int type, flags, id, n, quarter, park, item0, items; double t0, t1; };
struct Use { double ready, gate, need, freed; int readers, slot, prev; bool next; };
struct PlanStats { double end, slack, park_slack; int slots, parks; uint32_t own[N_CL]; };

bool plan(const char* const* text, int n_pair, int phase, Params& P, PlanStats* stats = nullptr) {
  constexpr double T_Q = 7900, T_A = 24850, T_U = 26300, T_O = 1920, T_RUN = 800, T_WIDE = 1900, AHEAD = 3500, PUBLISH = 1500;
  const double margin = 256.0 * ((P.dbg >> 8) & 255);
  static Op op[N_CL][MAX_OPS];
  static Use use[ID_PART];
  int n_op[N_CL], covered[N_TEAM] = {}, finals[N_TEAM] = {};
  auto hex = [](char c) { return c <= '9' ? c - '0' : c - 'a' + 10; };
  for (int i = 0; i < n_pair; i++)
    for (const char* s = text[i]; *s; s++)
      if (*s == 'J') { if (covered[hex(s[1])]) return false; covered[hex(s[1])] = 10 * (s[2] - '0') + s[3] - '0'; }
  for (int c = 0; c < 2 * n_pair; c++) {
    int n = 0, items = 0;
    double t = 0;
    auto add = [&](int type, int flags, int id, int heads, int quarter, int its, double dt) {
      if (n < MAX_OPS) op[c][n] = {type, flags, id, heads, quarter, 0, items, its, t, t + dt};
      n++; items += its; t += dt;
    };
    for (const char* s = text[c >> 1]; *s; s++) {
      const int tm = hex(s[1]) & 15, nj = covered[tm];
      if (*s == 'N') { add(OP_Q, 0, 0, 0, 0, 10, T_Q); add(OP_A, 0, 0, 0, 0, 32, T_A); }
      if (*s == 'P') add(OP_Q, F_PARK, 0, 0, 0, 10, T_Q);
      if (*s == 'U') { if (n == 0 || n > MAX_OPS || op[c][n - 1].type != OP_A) return false; add(OP_A, F_PARK, 0, 0, 0, 33, T_U); }
      if (*s == 'J') { if (nj <= TAIL || nj > kH - 4) return false; add(OP_O, P_WIDE | P_ST, tm * kH, nj, 2 * (c & 1), 3 * (nj + TAIL), 2 * T_O * nj + T_WIDE); }
      if (*s == 'F') { if (s[2]) return false; add(OP_O, nj ? P_LD : 0, tm * kH + nj, kH - nj, finals[tm]++, 3 * (kH - nj), T_O * (kH - nj) + T_RUN); }
    }
    add(OP_END, 0, 0, 0, 0, 0, 0);
    if (n > MAX_OPS || op[c][0].type != OP_Q) return false;
    n_op[c] = n - 1;
  }
  for (int t = 0; t < N_TEAM; t++) if (finals[t] != 4) return false;
  for (int i = 0; i < ID_PART; i++) use[i] = {0, 0, 1e18, 0, 0, 0, 0, false};
  struct Ref { double t; Op* o; int id; };
  static Ref att[N_TILE + 1], dem[N_TILE], prk[MAX_PARK + 1], unp[MAX_PARK + 1], wr[ID_PART];
  int n_att = 0, n_prk = 0, n_unp = 0;
  auto ready = [&](const Op* o) {
    const int nt = o[1].type;
    return o->t1 + (nt == OP_Q ? 6100 : nt == OP_O ? 3900 : 1500) + PUBLISH;
  };
  for (int c = 0; c < 2 * n_pair; c++)
    for (Op* o = op[c]; o->type != OP_END; o++) {
      if (o->type == OP_A) { att[n_att] = {ready(o), o, 0}; if (++n_att > N_TILE) return false; }
      if (o->type == OP_A && o->flags) { unp[n_unp] = {o->t0 - AHEAD, o, 0}; if (++n_unp > MAX_PARK) return false; }
      if (o->type == OP_Q && o->flags) { prk[n_prk] = {ready(o), o, 0}; if (++n_prk > MAX_PARK) return false; }
      for (int i = 0; o->type == OP_O && i < o->n; i++) {
        const int nw = (o->flags & P_WIDE) ? o->n - TAIL : 0;
        Use& u = use[o->id + i];
        const double t = o->t0 + T_O * (i + (i < nw ? i : nw));
        if (t - AHEAD < u.need) u.need = t - AHEAD;
        const double f = i < nw || (nw && o[1].type != OP_O) ? t + T_O * (i < nw ? 2 : 1 + TAIL) + PUBLISH : 1e18;
        if (f > u.freed) u.freed = f;
        u.readers++;
      }
    }
  if (n_att != N_TILE || n_prk != n_unp) return false;
  auto sort = [](Ref* r, int n) {
    for (int i = 1; i < n; i++)
      for (int j = i; j > 0 && r[j].t < r[j - 1].t; j--) { Ref x = r[j]; r[j] = r[j - 1]; r[j - 1] = x; }
  };
  for (int i = 0; i < N_TILE; i++) { const int id = (i & 15) * kH + (i >> 4); dem[i] = {use[id].need, nullptr, id}; }
  sort(att, n_att); sort(dem, N_TILE); sort(prk, n_prk); sort(unp, n_unp);
  PlanStats st = {0, 1e18, 1e18, 0, n_prk};
  int n_wr = 0;
  for (int i = 0; i < N_TILE; i++) {
    Op* o = att[i].o;
    o->id = dem[i].id;
    if (!o->flags) o[-1].id = o->id;
    if (dem[i].t - att[i].t < st.slack) st.slack = dem[i].t - att[i].t;
    wr[n_wr++] = {o->t1 - 2 * AHEAD, o, o->id};
  }
  for (int i = 0; i < n_prk; i++) {
    prk[i].o->id = unp[i].o->id;
    prk[i].o->park = unp[i].o->park = i;
    use[N_TILE + i].freed = unp[i].o->t0 + 2 * PUBLISH;
    use[N_TILE + i].readers = 1;
    if (unp[i].t - prk[i].t < st.park_slack) st.park_slack = unp[i].t - prk[i].t;
    wr[n_wr++] = {prk[i].o->t1 - 2 * AHEAD, prk[i].o, N_TILE + i};
  }
  for (int c = 0; c < 2 * n_pair; c++)
    for (int d = 0; d < 2 * n_pair; d++)
      for (Op *f = &op[c][n_op[c] - 1], *o = op[d]; f->type == OP_O && o->type != OP_END; o++)
        if (o->type == OP_O && (o->flags & P_ST) && o->id / kH == f->id / kH) {
          if (f->t0 - o->t1 > 4096.0 * ((P.dbg >> 16) & 255)) f->flags |= P_PRE;
          const double slack = f->t0 + ((f->flags & P_PRE) ? 0 : (f->n - 2) * T_O) - AHEAD - ready(o);
          if (slack < st.park_slack) st.park_slack = slack;
        }
  sort(wr, n_wr);
  int holder[N_TILE];
  for (int i = 0; i < n_wr; i++) {
    int best = -1;
    for (int sl = 0; sl < st.slots; sl++)
      if (use[holder[sl]].freed + margin <= wr[i].t && (best < 0 || (use[holder[sl]].freed < use[holder[best]].freed) != ((P.dbg & 32) != 0))) best = sl;
    Use& u = use[wr[i].id];
    if (best >= 0) { u.prev = holder[best]; use[u.prev].next = true; wr[i].o->flags |= P_GATE; }
    else if (st.slots == N_TILE) return false;
    else best = st.slots++;
    u.slot = best;
    holder[best] = wr[i].id;
  }
  {
    int pos[N_CL] = {}, flag[ID_PART + 4 * N_TEAM] = {}, seen[ID_PART] = {};
    auto goal = [&](int c) { const Op& f = op[c][n_op[c] - 1]; return f.type == OP_O && !(f.flags & P_WIDE) ? f.item0 : f.item0 + f.items + NBAR; };
    for (bool moved = true; moved;) {
      moved = false;
      for (int c = 0; c < 2 * n_pair; c++) {
        for (; pos[c] < goal(c); pos[c]++, moved = true) {
          bool ok = true;
          for (const Op* o = op[c]; o->type != OP_END; o++) {
            const int k = pos[c] - o->item0, own = o->type == OP_A ? o->id : N_TILE + o->park;
            if (k < 0 || k >= o->items) continue;
            if (o->type == OP_O) ok = k >= 3 * o->n || flag[o->id + k / 3];
            else if (k == o->items - 1 && (o->flags & P_GATE)) ok = seen[use[own].prev] == use[use[own].prev].readers;
            else if (k == 0 && o->type == OP_A && (o->flags & F_PARK)) ok = flag[N_TILE + o->park];
          }
          if (!ok) break;
          for (const Op* o = op[c]; o->type != OP_END; o++) {
            if (pos[c] == o->item0 + o->items + (o[1].type == OP_Q ? 7 : o[1].item0 == goal(c) ? -1 : 5)) {
              if (o->type == OP_A) flag[o->id] = 1;
              if (o->type == OP_Q && (o->flags & F_PARK)) flag[N_TILE + o->park] = 1;
              if (o->type == OP_O) flag[ID_PART + o->id / kH * 4 + o->quarter] = flag[ID_PART + o->id / kH * 4 + o->quarter + 1] = 1;
            }
            const int k = pos[c] - NBAR - o->item0, nw = o->n - TAIL;
            if (k == 0 && o->type == OP_A && (o->flags & F_PARK)) seen[N_TILE + o->park]++;
            if (o->type == OP_O && k >= 0 && k < o->items && k % 3 == 2 && (k / 3 < nw || k / 3 >= o->n)) seen[o->id + (k / 3 < nw ? k / 3 : k / 3 - TAIL)]++;
          }
        }
      }
    }
    for (int c = 0; c < 2 * n_pair; c++) if (pos[c] < goal(c)) return false;
  }
  int n_job = 0, longest = 0;
  for (int t = 0; t < N_TEAM; t++) if (kH - covered[t] > longest) longest = kH - covered[t];
  for (int c = 0; c < 2 * n_pair; c++) {
    uint32_t items = 0, cur = 0, pend = 0;
    int n = 0, ev = 0;
    auto item = [&](uint32_t bytes, int count) {
      for (int i = 0; i < count; i++) { if (cur + bytes > RING) cur = 0; cur += bytes; items++; }
    };
    auto event = [&](uint32_t e) { if (ev < MAX_EV) P.prog[c].ev[ev] = e; ev++; };
    for (const Op* o = op[c];; o++) {
      if (o->type != OP_END && phase && (o->type == OP_O) != (phase == 2)) continue;
      uint32_t cw = o->type | (items % NBAR) << 15 | ((items / NBAR) & 1) << 19 | (cur >> 12) << 20 | pend, pw = o->type | o->id << 2 | o->flags;
      const int ps = use[N_TILE + o->park].slot;
      pend = 0;
      if (o->type == OP_O) {
        pw |= o->n << 13 | o->quarter << 19;
        if (o->flags & P_WIDE) {
          cw |= o->n << 2 | (o->id / kH * 4 + o->quarter + 1) << 8 | C_WIDE;
          item(SZ_W, 3 * (o->n - TAIL));
          item(SZ_O, 6 * TAIL);
          pend = C_PEND | ((P.dbg & 8) ? C_SOON : 0);
          for (int i = 0; i < o->n; i++) event((o->id + i) | E_ON | (use[o->id + i].next ? 0 : E_LAST));
        } else {
          dem[n_job++] = {o->t0 - 1e6 * o->n, nullptr, (int)pw};
          st.own[c] = pw;
          pw = OP_O;
          event(E_DRAW | (items < 16 ? 0 : items - 16));
          for (int i = 0; i <= longest; i++) event(E_JOB | i);
        }
      } else if (o->type != OP_END) {
        const bool parks = o->type == OP_Q && (o->flags & F_PARK);
        cw |= (parks ? ps : use[o->id].slot) << 2 | (o->flags & F_PARK);
        if (o->flags & F_PARK) pw |= o->park << 13 | ps << 20;
        if (o->type == OP_Q) item(SZ_Q, 10);
        else { if (o->flags & F_PARK) { item(SZ_PARK, 1); event((N_TILE + o->park) | E_ON | (use[N_TILE + o->park].next ? 0 : E_LAST)); } item(SZ_KV, 32); }
        if (parks || o->type == OP_A) pend = C_PEND | ((P.dbg & 16) ? 0 : C_SOON);
        if (o->flags & P_GATE) event(use[parks ? N_TILE + o->park : o->id].prev | E_ON | E_FREE);
      }
      P.prog[c].c[n] = cw; P.prog[c].p[n++] = pw;
      if (o->type == OP_END) { if (o->t0 > st.end) st.end = o->t0; break; }
    }
    if (ev > MAX_EV) return false;
    while (ev < MAX_EV) P.prog[c].ev[ev++] = 0;
    while (n < MAX_OPS) { P.prog[c].c[n] = OP_END; P.prog[c].p[n++] = OP_END; }
    P.first[c] = (uint16_t)(P.prog[c].p[0] & 2047);
  }
  sort(dem, n_job);
  for (int i = 0; i < n_job; i++) P.job[i] = dem[i].id;
  for (int i = 0; i < ID_PART; i++) {
    if (i < N_TILE) P.slot[i] = use[i].slot;
    P.info[i] = (use[i].readers + use[i].next) | (use[i].next ? I_NEXT : 0);
  }
  if (stats) *stats = st;
  return true;
}

const char* const kPrograms[N_CL / 2] = {
  "NNNNNNNNNF4", "NNUNNNNNNF6", "NUNNJf17NNNF8", "PNNNNNNNNNFe", "PNJ121NNNNNF5", "NNNNNNNNNFa",
  "NNNNNUNNNF6", "NNNNNNNNNF1", "NNNNNNNNNF4", "NUNNNJe26NF8", "PNJ227NNNNFc", "PPNJ717NNNNUNF2",
  "NUNNJc13NNNNF2", "PNNJ325NNNNF3", "NUNUNJ926NFd", "NNNNNNNNNFa", "PNJ421NNNNNFf", "NUNNNJd16NNF7",
  "PNNNNNNNNNF3", "NNUJ618Jb23NFd", "NNNNNNNNNFb", "PNJ517NNNNNNFe", "NNNNNNNNNF0", "PNJ021NNNNNF5",
  "PNNNNNNNNN", "NUNNNJ819NNFb", "PNNNNNNNNNF9", "NNNNNNNNNF0", "PNNNNNNNNNF9", "NNNNNNNNNF1",
  "NNUNNNNNNFf", "NNNNNJa21NFc", "NUNNNNNNNF7",
};

const char* const* bench_programs() {
  return kPrograms;
}

}

extern "C" void kernel_launch(void* const* d_in, const int* in_sizes, int n_in, void* d_out, int out_size) {
  (void)in_sizes; (void)n_in; (void)out_size;
  static EncodeFn fn = nullptr;
  static int n_clusters = 0;
  if (!fn) {
    cudaDriverEntryPointQueryResult qr;
    void* f = nullptr;
    cudaGetDriverEntryPoint("cuTensorMapEncodeTiled", &f, cudaEnableDefault, &qr);
    fn = (EncodeFn)f;
    cudaFuncSetAttribute(fused_kernel, cudaFuncAttributeMaxDynamicSharedMemorySize, SMEM_BYTES);
    cudaLaunchConfig_t cfg = {};
    cfg.gridDim = dim3(132); cfg.blockDim = dim3(384); cfg.dynamicSmemBytes = SMEM_BYTES;
    cudaLaunchAttribute at[1];
    at[0].id = cudaLaunchAttributeClusterDimension; at[0].val.clusterDim.x = 2; at[0].val.clusterDim.y = 1; at[0].val.clusterDim.z = 1;
    cfg.attrs = at; cfg.numAttrs = 1;
    if (cudaOccupancyMaxActiveClusters(&n_clusters, fused_kernel, &cfg) != cudaSuccess || n_clusters < 1) n_clusters = 1;
    (void)cudaGetLastError();
  }
  static Params P;
  const CUtensorMapSwizzle S128 = CU_TENSOR_MAP_SWIZZLE_128B, S64 = CU_TENSOR_MAP_SWIZZLE_64B;
  for (int blk = 0; blk < 2; blk++) {
    void* const* in = d_in + 5 * blk;
    { const cuuint64_t d[] = {kD, kB * kSq}, s[] = {kD * 2}; const cuuint32_t b[] = {64, 128};
      encode(fn, &P.x[blk], in[0], 2, d, s, b, S128); }
    { const cuuint64_t d[] = {64, 8, 3, (cuuint64_t)kB * kH * kSk / 8}, s[] = {kDh * 2, 128, 8 * kDh * 2}; const cuuint32_t b[] = {64, 8, 3, 8};
      encode(fn, &P.k[blk], in[1], 4, d, s, b, S128);
      encode(fn, &P.v[blk], in[2], 4, d, s, b, S128); }
    { const cuuint64_t d[] = {64, kD, kHD / 64}, s[] = {kHD * 2, 128}; const cuuint32_t b[] = {64, 64, 3};
      encode(fn, &P.wq[blk], in[3], 3, d, s, b, S128); }
    { const cuuint64_t d[] = {32, 2, kHD / 8, 4, kD / 32}, s[] = {kD * 2, 8 * kD * 2, 2 * kD * 2, 64}; const cuuint32_t b[] = {32, 2, 4, 4, 5};
      encode(fn, &P.wo[blk], in[4], 5, d, s, b, S64); }
  }
  { const cuuint64_t d[] = {32, kB * kSq, 2 * kD / 32}, s[] = {2 * kD * 2, 64}; const cuuint32_t b[] = {32, 16, 1};
    encode(fn, &P.out, d_out, 3, d, s, b, S64); }

  P.dbg = DBG_DEFAULT;
  if (n_clusters >= N_CL && plan(bench_programs(), N_CL / 2, 0, P)) {
    fused_kernel<<<2 * N_CL, 384, SMEM_BYTES>>>(P);
  } else {
    char buf[2 * N_TEAM][16];
    const char* text[2 * N_TEAM];
    for (int i = 0; i < 2 * N_TEAM; i++) { snprintf(buf[i], sizeof(buf[i]), "NNNNNNNNF%x", i / 2); text[i] = buf[i]; }
    for (int phase = 1; phase <= 2; phase++) {
      plan(text, 2 * N_TEAM, phase, P);
      fused_kernel<<<8 * N_TEAM, 384, SMEM_BYTES>>>(P);
    }
  }
}
```

```cpp
#include <cuda_runtime.h>
#include <cuda_bf16.h>
#include <cuda.h>
#include <stdint.h>
#include <stdio.h>

namespace {

constexpr int kB = 8, kSq = 256, kD = 640, kH = 32, kSk = 1024, kDh = 192;
constexpr int kHD = kH * kDh;
constexpr uint32_t RING = 224 * 1024;
constexpr uint32_t SZ_KV = 24576;
constexpr uint32_t SZ_Q = 16384 + 24576;
constexpr uint32_t SZ_O = 16384 + 20480;
constexpr uint32_t SZ_W = 16384 + 40960;
constexpr uint32_t SZ_PARK = 49152;
constexpr uint32_t SZ_OL = SZ_O + 8192;
constexpr int NBAR = 10;
constexpr int EARLY = 3;
#define XTAIL 2
constexpr int TAIL = XTAIL;
constexpr uint32_t KV_CH = 64, KV_SBO = 3072;
constexpr int SMEM_BYTES = RING + 1024 + 1024;
constexpr int N_TEAM = 16, N_CL = 66, MAX_OPS = 24, MAX_EV = 80, N_TILE = N_TEAM * kH, MAX_PARK = 128, ID_PART = N_TILE + MAX_PARK;
enum : uint32_t { OP_END = 0, OP_Q = 1, OP_A = 2, OP_O = 3, F_PARK = 1 << 11,
                  C_WIDE = 1 << 14, C_PEND = 1 << 26, C_SOON = 1 << 28,
                  P_GATE = 1 << 12, P_WIDE = 1 << 11, P_LD = 1 << 12, P_ST = 1 << 21, P_PRE = 1 << 22, I_NEXT = 8, E_ON = 1 << 15, E_FREE = 1 << 14, E_LAST = 1 << 13, E_DRAW = 1 << 12, E_JOB = 1 << 11 };

#define QDRAIN 0x54732710u
#define TRYNS 1500
#define PFN 10
#define QA 1
#define QB 2
#define QC 3
#define NORM_G 2
#define CONV_G 8
#define CONV_0 32
#define SKEW 3
#define PUBNS 100
#define WATNS 100
constexpr uint32_t DBG_DEFAULT = 0x040817;

struct alignas(1024) Scratch {
  unsigned int flag[2047];
  unsigned int ticket;
  uint4 part[N_TEAM * 4 * 2 * 3072];
  uint4 tile[N_TILE * 2 * 3072];
};

struct alignas(64) Params {
  uint16_t first[88];
  Scratch* g;
  uint32_t dbg;
  CUtensorMap x[2], wq[2], k[2], v[2], wo[2], out;
  struct {
    uint32_t c[MAX_OPS];
    uint32_t p[MAX_OPS];
    uint16_t ev[MAX_EV];
  } prog[N_CL];
  uint32_t job[4 * N_TEAM];
  uint16_t slot[N_TILE];
  uint8_t info[ID_PART];
};

__device__ Scratch g_scratch;

template <int TB, int TA = 0>
__device__ __forceinline__ void wgmma_ss_n64(float (&d)[32], uint64_t da, uint64_t db, int scale_d) {
  asm volatile("{\n.reg .pred p;\nsetp.ne.b32 p, %34, 0;\n"
    "wgmma.mma_async.sync.aligned.m64n64k16.f32.bf16.bf16 {%0, %1, %2, %3, %4, %5, %6, %7, %8, %9, %10, %11, %12, %13, %14, %15, %16, %17, %18, %19, %20, %21, %22, %23, %24, %25, %26, %27, %28, %29, %30, %31}, %32, %33, p, 1, 1, %35, %36;\n}\n"
    : "+f"(d[0]), "+f"(d[1]), "+f"(d[2]), "+f"(d[3]), "+f"(d[4]), "+f"(d[5]), "+f"(d[6]), "+f"(d[7]), "+f"(d[8]), "+f"(d[9]), "+f"(d[10]), "+f"(d[11]), "+f"(d[12]), "+f"(d[13]), "+f"(d[14]), "+f"(d[15]), "+f"(d[16]), "+f"(d[17]), "+f"(d[18]), "+f"(d[19]), "+f"(d[20]), "+f"(d[21]), "+f"(d[22]), "+f"(d[23]), "+f"(d[24]), "+f"(d[25]), "+f"(d[26]), "+f"(d[27]), "+f"(d[28]), "+f"(d[29]), "+f"(d[30]), "+f"(d[31])
    : "l"(da), "l"(db), "r"(scale_d), "n"(TA), "n"(TB));
}
template <int TB>
__device__ __forceinline__ void wgmma_rs_n64(float (&d)[32], uint32_t a0, uint32_t a1, uint32_t a2, uint32_t a3, uint64_t db, int scale_d) {
  asm volatile("{\n.reg .pred p;\nsetp.ne.b32 p, %37, 0;\n"
    "wgmma.mma_async.sync.aligned.m64n64k16.f32.bf16.bf16 {%0, %1, %2, %3, %4, %5, %6, %7, %8, %9, %10, %11, %12, %13, %14, %15, %16, %17, %18, %19, %20, %21, %22, %23, %24, %25, %26, %27, %28, %29, %30, %31}, {%32, %33, %34, %35}, %36, p, 1, 1, %38;\n}\n"
    : "+f"(d[0]), "+f"(d[1]), "+f"(d[2]), "+f"(d[3]), "+f"(d[4]), "+f"(d[5]), "+f"(d[6]), "+f"(d[7]), "+f"(d[8]), "+f"(d[9]), "+f"(d[10]), "+f"(d[11]), "+f"(d[12]), "+f"(d[13]), "+f"(d[14]), "+f"(d[15]), "+f"(d[16]), "+f"(d[17]), "+f"(d[18]), "+f"(d[19]), "+f"(d[20]), "+f"(d[21]), "+f"(d[22]), "+f"(d[23]), "+f"(d[24]), "+f"(d[25]), "+f"(d[26]), "+f"(d[27]), "+f"(d[28]), "+f"(d[29]), "+f"(d[30]), "+f"(d[31])
    : "r"(a0), "r"(a1), "r"(a2), "r"(a3), "l"(db), "r"(scale_d), "n"(TB));
}
template <int TB, int TA = 0>
__device__ __forceinline__ void wgmma_ss_n160(float (&d)[80], uint64_t da, uint64_t db, int scale_d) {
  asm volatile("{\n.reg .pred p;\nsetp.ne.b32 p, %82, 0;\n"
    "wgmma.mma_async.sync.aligned.m64n160k16.f32.bf16.bf16 {%0, %1, %2, %3, %4, %5, %6, %7, %8, %9, %10, %11, %12, %13, %14, %15, %16, %17, %18, %19, %20, %21, %22, %23, %24, %25, %26, %27, %28, %29, %30, %31, %32, %33, %34, %35, %36, %37, %38, %39, %40, %41, %42, %43, %44, %45, %46, %47, %48, %49, %50, %51, %52, %53, %54, %55, %56, %57, %58, %59, %60, %61, %62, %63, %64, %65, %66, %67, %68, %69, %70, %71, %72, %73, %74, %75, %76, %77, %78, %79}, %80, %81, p, 1, 1, %83, %84;\n}\n"
    : "+f"(d[0]), "+f"(d[1]), "+f"(d[2]), "+f"(d[3]), "+f"(d[4]), "+f"(d[5]), "+f"(d[6]), "+f"(d[7]), "+f"(d[8]), "+f"(d[9]), "+f"(d[10]), "+f"(d[11]), "+f"(d[12]), "+f"(d[13]), "+f"(d[14]), "+f"(d[15]), "+f"(d[16]), "+f"(d[17]), "+f"(d[18]), "+f"(d[19]), "+f"(d[20]), "+f"(d[21]), "+f"(d[22]), "+f"(d[23]), "+f"(d[24]), "+f"(d[25]), "+f"(d[26]), "+f"(d[27]), "+f"(d[28]), "+f"(d[29]), "+f"(d[30]), "+f"(d[31]), "+f"(d[32]), "+f"(d[33]), "+f"(d[34]), "+f"(d[35]), "+f"(d[36]), "+f"(d[37]), "+f"(d[38]), "+f"(d[39]), "+f"(d[40]), "+f"(d[41]), "+f"(d[42]), "+f"(d[43]), "+f"(d[44]), "+f"(d[45]), "+f"(d[46]), "+f"(d[47]), "+f"(d[48]), "+f"(d[49]), "+f"(d[50]), "+f"(d[51]), "+f"(d[52]), "+f"(d[53]), "+f"(d[54]), "+f"(d[55]), "+f"(d[56]), "+f"(d[57]), "+f"(d[58]), "+f"(d[59]), "+f"(d[60]), "+f"(d[61]), "+f"(d[62]), "+f"(d[63]), "+f"(d[64]), "+f"(d[65]), "+f"(d[66]), "+f"(d[67]), "+f"(d[68]), "+f"(d[69]), "+f"(d[70]), "+f"(d[71]), "+f"(d[72]), "+f"(d[73]), "+f"(d[74]), "+f"(d[75]), "+f"(d[76]), "+f"(d[77]), "+f"(d[78]), "+f"(d[79])
    : "l"(da), "l"(db), "r"(scale_d), "n"(TA), "n"(TB));
}
template <int TB>
__device__ __forceinline__ void wgmma_rs_n160(float (&d)[80], uint32_t a0, uint32_t a1, uint32_t a2, uint32_t a3, uint64_t db, int scale_d) {
  asm volatile("{\n.reg .pred p;\nsetp.ne.b32 p, %85, 0;\n"
    "wgmma.mma_async.sync.aligned.m64n160k16.f32.bf16.bf16 {%0, %1, %2, %3, %4, %5, %6, %7, %8, %9, %10, %11, %12, %13, %14, %15, %16, %17, %18, %19, %20, %21, %22, %23, %24, %25, %26, %27, %28, %29, %30, %31, %32, %33, %34, %35, %36, %37, %38, %39, %40, %41, %42, %43, %44, %45, %46, %47, %48, %49, %50, %51, %52, %53, %54, %55, %56, %57, %58, %59, %60, %61, %62, %63, %64, %65, %66, %67, %68, %69, %70, %71, %72, %73, %74, %75, %76, %77, %78, %79}, {%80, %81, %82, %83}, %84, p, 1, 1, %86;\n}\n"
    : "+f"(d[0]), "+f"(d[1]), "+f"(d[2]), "+f"(d[3]), "+f"(d[4]), "+f"(d[5]), "+f"(d[6]), "+f"(d[7]), "+f"(d[8]), "+f"(d[9]), "+f"(d[10]), "+f"(d[11]), "+f"(d[12]), "+f"(d[13]), "+f"(d[14]), "+f"(d[15]), "+f"(d[16]), "+f"(d[17]), "+f"(d[18]), "+f"(d[19]), "+f"(d[20]), "+f"(d[21]), "+f"(d[22]), "+f"(d[23]), "+f"(d[24]), "+f"(d[25]), "+f"(d[26]), "+f"(d[27]), "+f"(d[28]), "+f"(d[29]), "+f"(d[30]), "+f"(d[31]), "+f"(d[32]), "+f"(d[33]), "+f"(d[34]), "+f"(d[35]), "+f"(d[36]), "+f"(d[37]), "+f"(d[38]), "+f"(d[39]), "+f"(d[40]), "+f"(d[41]), "+f"(d[42]), "+f"(d[43]), "+f"(d[44]), "+f"(d[45]), "+f"(d[46]), "+f"(d[47]), "+f"(d[48]), "+f"(d[49]), "+f"(d[50]), "+f"(d[51]), "+f"(d[52]), "+f"(d[53]), "+f"(d[54]), "+f"(d[55]), "+f"(d[56]), "+f"(d[57]), "+f"(d[58]), "+f"(d[59]), "+f"(d[60]), "+f"(d[61]), "+f"(d[62]), "+f"(d[63]), "+f"(d[64]), "+f"(d[65]), "+f"(d[66]), "+f"(d[67]), "+f"(d[68]), "+f"(d[69]), "+f"(d[70]), "+f"(d[71]), "+f"(d[72]), "+f"(d[73]), "+f"(d[74]), "+f"(d[75]), "+f"(d[76]), "+f"(d[77]), "+f"(d[78]), "+f"(d[79])
    : "r"(a0), "r"(a1), "r"(a2), "r"(a3), "l"(db), "r"(scale_d), "n"(TB));
}
template <int TB, int TA = 0>
__device__ __forceinline__ void wgmma_ss_n192(float (&d)[96], uint64_t da, uint64_t db, int scale_d) {
  asm volatile("{\n.reg .pred p;\nsetp.ne.b32 p, %98, 0;\n"
    "wgmma.mma_async.sync.aligned.m64n192k16.f32.bf16.bf16 {%0, %1, %2, %3, %4, %5, %6, %7, %8, %9, %10, %11, %12, %13, %14, %15, %16, %17, %18, %19, %20, %21, %22, %23, %24, %25, %26, %27, %28, %29, %30, %31, %32, %33, %34, %35, %36, %37, %38, %39, %40, %41, %42, %43, %44, %45, %46, %47, %48, %49, %50, %51, %52, %53, %54, %55, %56, %57, %58, %59, %60, %61, %62, %63, %64, %65, %66, %67, %68, %69, %70, %71, %72, %73, %74, %75, %76, %77, %78, %79, %80, %81, %82, %83, %84, %85, %86, %87, %88, %89, %90, %91, %92, %93, %94, %95}, %96, %97, p, 1, 1, %99, %100;\n}\n"
    : "+f"(d[0]), "+f"(d[1]), "+f"(d[2]), "+f"(d[3]), "+f"(d[4]), "+f"(d[5]), "+f"(d[6]), "+f"(d[7]), "+f"(d[8]), "+f"(d[9]), "+f"(d[10]), "+f"(d[11]), "+f"(d[12]), "+f"(d[13]), "+f"(d[14]), "+f"(d[15]), "+f"(d[16]), "+f"(d[17]), "+f"(d[18]), "+f"(d[19]), "+f"(d[20]), "+f"(d[21]), "+f"(d[22]), "+f"(d[23]), "+f"(d[24]), "+f"(d[25]), "+f"(d[26]), "+f"(d[27]), "+f"(d[28]), "+f"(d[29]), "+f"(d[30]), "+f"(d[31]), "+f"(d[32]), "+f"(d[33]), "+f"(d[34]), "+f"(d[35]), "+f"(d[36]), "+f"(d[37]), "+f"(d[38]), "+f"(d[39]), "+f"(d[40]), "+f"(d[41]), "+f"(d[42]), "+f"(d[43]), "+f"(d[44]), "+f"(d[45]), "+f"(d[46]), "+f"(d[47]), "+f"(d[48]), "+f"(d[49]), "+f"(d[50]), "+f"(d[51]), "+f"(d[52]), "+f"(d[53]), "+f"(d[54]), "+f"(d[55]), "+f"(d[56]), "+f"(d[57]), "+f"(d[58]), "+f"(d[59]), "+f"(d[60]), "+f"(d[61]), "+f"(d[62]), "+f"(d[63]), "+f"(d[64]), "+f"(d[65]), "+f"(d[66]), "+f"(d[67]), "+f"(d[68]), "+f"(d[69]), "+f"(d[70]), "+f"(d[71]), "+f"(d[72]), "+f"(d[73]), "+f"(d[74]), "+f"(d[75]), "+f"(d[76]), "+f"(d[77]), "+f"(d[78]), "+f"(d[79]), "+f"(d[80]), "+f"(d[81]), "+f"(d[82]), "+f"(d[83]), "+f"(d[84]), "+f"(d[85]), "+f"(d[86]), "+f"(d[87]), "+f"(d[88]), "+f"(d[89]), "+f"(d[90]), "+f"(d[91]), "+f"(d[92]), "+f"(d[93]), "+f"(d[94]), "+f"(d[95])
    : "l"(da), "l"(db), "r"(scale_d), "n"(TA), "n"(TB));
}
template <int TB>
__device__ __forceinline__ void wgmma_rs_n192(float (&d)[96], uint32_t a0, uint32_t a1, uint32_t a2, uint32_t a3, uint64_t db, int scale_d) {
  asm volatile("{\n.reg .pred p;\nsetp.ne.b32 p, %101, 0;\n"
    "wgmma.mma_async.sync.aligned.m64n192k16.f32.bf16.bf16 {%0, %1, %2, %3, %4, %5, %6, %7, %8, %9, %10, %11, %12, %13, %14, %15, %16, %17, %18, %19, %20, %21, %22, %23, %24, %25, %26, %27, %28, %29, %30, %31, %32, %33, %34, %35, %36, %37, %38, %39, %40, %41, %42, %43, %44, %45, %46, %47, %48, %49, %50, %51, %52, %53, %54, %55, %56, %57, %58, %59, %60, %61, %62, %63, %64, %65, %66, %67, %68, %69, %70, %71, %72, %73, %74, %75, %76, %77, %78, %79, %80, %81, %82, %83, %84, %85, %86, %87, %88, %89, %90, %91, %92, %93, %94, %95}, {%96, %97, %98, %99}, %100, p, 1, 1, %102;\n}\n"
    : "+f"(d[0]), "+f"(d[1]), "+f"(d[2]), "+f"(d[3]), "+f"(d[4]), "+f"(d[5]), "+f"(d[6]), "+f"(d[7]), "+f"(d[8]), "+f"(d[9]), "+f"(d[10]), "+f"(d[11]), "+f"(d[12]), "+f"(d[13]), "+f"(d[14]), "+f"(d[15]), "+f"(d[16]), "+f"(d[17]), "+f"(d[18]), "+f"(d[19]), "+f"(d[20]), "+f"(d[21]), "+f"(d[22]), "+f"(d[23]), "+f"(d[24]), "+f"(d[25]), "+f"(d[26]), "+f"(d[27]), "+f"(d[28]), "+f"(d[29]), "+f"(d[30]), "+f"(d[31]), "+f"(d[32]), "+f"(d[33]), "+f"(d[34]), "+f"(d[35]), "+f"(d[36]), "+f"(d[37]), "+f"(d[38]), "+f"(d[39]), "+f"(d[40]), "+f"(d[41]), "+f"(d[42]), "+f"(d[43]), "+f"(d[44]), "+f"(d[45]), "+f"(d[46]), "+f"(d[47]), "+f"(d[48]), "+f"(d[49]), "+f"(d[50]), "+f"(d[51]), "+f"(d[52]), "+f"(d[53]), "+f"(d[54]), "+f"(d[55]), "+f"(d[56]), "+f"(d[57]), "+f"(d[58]), "+f"(d[59]), "+f"(d[60]), "+f"(d[61]), "+f"(d[62]), "+f"(d[63]), "+f"(d[64]), "+f"(d[65]), "+f"(d[66]), "+f"(d[67]), "+f"(d[68]), "+f"(d[69]), "+f"(d[70]), "+f"(d[71]), "+f"(d[72]), "+f"(d[73]), "+f"(d[74]), "+f"(d[75]), "+f"(d[76]), "+f"(d[77]), "+f"(d[78]), "+f"(d[79]), "+f"(d[80]), "+f"(d[81]), "+f"(d[82]), "+f"(d[83]), "+f"(d[84]), "+f"(d[85]), "+f"(d[86]), "+f"(d[87]), "+f"(d[88]), "+f"(d[89]), "+f"(d[90]), "+f"(d[91]), "+f"(d[92]), "+f"(d[93]), "+f"(d[94]), "+f"(d[95])
    : "r"(a0), "r"(a1), "r"(a2), "r"(a3), "l"(db), "r"(scale_d), "n"(TB));
}

__device__ __forceinline__ uint32_t smem_u32(const void* p) { return (uint32_t)__cvta_generic_to_shared(p); }
__device__ __forceinline__ void wg_fence() { asm volatile("wgmma.fence.sync.aligned;" ::: "memory"); }
__device__ __forceinline__ void wg_commit() { asm volatile("wgmma.commit_group.sync.aligned;" ::: "memory"); }
template <int N> __device__ __forceinline__ void wg_wait() { asm volatile("wgmma.wait_group.sync.aligned %0;" ::"n"(N) : "memory"); }
__device__ __forceinline__ void sched_fence(uint32_t& keep, bool never) {
  asm volatile("{\n.reg .pred p;\nsetp.ne.b32 p, %1, 0;\n@p mov.u32 %0, %%clock;\n}\n" : "+r"(keep) : "r"((int)never) : "memory");
}
template <int N> __device__ __forceinline__ void fence_regs(float (&r)[N]) {
#pragma unroll
  for (int i = 0; i < N; i++) asm volatile("" : "+f"(r[i])::"memory");
}
template <int N> __device__ __forceinline__ void undefine(float (&r)[N]) {
#pragma unroll
  for (int i = 0; i < N; i++) asm volatile("" : "=f"(r[i]));
}
template <int N> __device__ __forceinline__ void fence_regs(uint32_t (&r)[N]) {
#pragma unroll
  for (int i = 0; i < N; i++) asm volatile("" : "+r"(r[i])::"memory");
}
__device__ __forceinline__ uint64_t mk_desc(uint32_t a16, uint32_t lbo, uint32_t sbo, uint32_t swz) {
  uint64_t d;
  asm("mov.b64 %0, {%1, %2};" : "=l"(d) : "r"(a16 + ((lbo >> 4) << 16)), "r"((sbo >> 4) | (swz << 30)));
  return d;
}
__device__ __forceinline__ void mbar_init(uint32_t bar, uint32_t cnt) {
  asm volatile("mbarrier.init.shared::cta.b64 [%0], %1;" ::"r"(bar), "r"(cnt) : "memory");
}
__device__ __forceinline__ void mbar_expect(uint32_t bar, uint32_t tx) {
  asm volatile("mbarrier.arrive.expect_tx.shared::cta.b64 _, [%0], %1;" ::"r"(bar), "r"(tx) : "memory");
}
__device__ __forceinline__ bool mbar_test(uint32_t bar, uint32_t ph) {
  uint32_t ok;
  asm volatile("{\n.reg .pred p;\nmbarrier.test_wait.parity.shared::cta.b64 p, [%1], %2;\nselp.u32 %0, 1, 0, p;\n}\n"
               : "=r"(ok) : "r"(bar), "r"(ph) : "memory");
  return ok;
}
__device__ __forceinline__ bool mbar_try(uint32_t bar, uint32_t ph, uint32_t ns) {
  uint32_t ok;
  asm volatile("{\n.reg .pred p;\nmbarrier.try_wait.parity.shared::cta.b64 p, [%1], %2, %3;\nselp.u32 %0, 1, 0, p;\n}\n"
               : "=r"(ok) : "r"(bar), "r"(ph), "r"(ns) : "memory");
  return ok;
}
__device__ __forceinline__ void mbar_wait(uint32_t bar, uint32_t ph) {
  asm volatile("{\n.reg .pred p;\n.reg .u32 n;\nmov.u32 n, 0;\n"
               "LOOP:\nmbarrier.try_wait.parity.shared::cta.b64 p, [%0], %1;\n@p bra DONE;\n"
               "add.u32 n, n, 1;\nsetp.lt.u32 p, n, 0x1000000;\n@p bra LOOP;\ntrap;\n"
               "DONE:\n}\n" ::"r"(bar), "r"(ph) : "memory");
}
template <int NS> __device__ __forceinline__ void mbar_wait_slow(uint32_t bar, uint32_t ph) {
  asm volatile("{\n.reg .pred p;\n.reg .u32 n;\nmov.u32 n, 0;\n"
               "LOOP:\nmbarrier.test_wait.parity.shared::cta.b64 p, [%0], %1;\n@p bra DONE;\n"
               "nanosleep.u32 %2;\nadd.u32 n, n, 1;\nsetp.lt.u32 p, n, 0x400000;\n@p bra LOOP;\ntrap;\n"
               "DONE:\n}\n" ::"r"(bar), "r"(ph), "n"(NS) : "memory");
}
__device__ __forceinline__ void mbar_arrive_cluster_if(bool on, uint32_t addr) {
  asm volatile("{\n.reg .pred p;\nsetp.ne.b32 p, %1, 0;\n@p mbarrier.arrive.shared::cluster.b64 _, [%0];\n}\n" ::"r"(addr), "r"((int)on) : "memory");
}
__device__ __forceinline__ void tma2d(uint32_t dst, const CUtensorMap* m, uint32_t bar, int c0, int c1) {
  asm volatile("cp.async.bulk.tensor.2d.shared::cluster.global.mbarrier::complete_tx::bytes [%0], [%1, {%3, %4}], [%2];"
               ::"r"(dst), "l"(m), "r"(bar), "r"(c0), "r"(c1) : "memory");
}
__device__ __forceinline__ void tma3d(uint32_t dst, const CUtensorMap* m, uint32_t bar, int c0, int c1, int c2) {
  asm volatile("cp.async.bulk.tensor.3d.shared::cluster.global.mbarrier::complete_tx::bytes [%0], [%1, {%3, %4, %5}], [%2];"
               ::"r"(dst), "l"(m), "r"(bar), "r"(c0), "r"(c1), "r"(c2) : "memory");
}
__device__ __forceinline__ void tma3d_mc(uint32_t dst, const CUtensorMap* m, uint32_t bar, int c0, int c1, int c2) {
  asm volatile("cp.async.bulk.tensor.3d.shared::cluster.global.mbarrier::complete_tx::bytes.multicast::cluster"
               " [%0], [%1, {%3, %4, %5}], [%2], %6;"
               ::"r"(dst), "l"(m), "r"(bar), "r"(c0), "r"(c1), "r"(c2), "h"((uint16_t)3) : "memory");
}
__device__ __forceinline__ void tma3d_store(const CUtensorMap* m, uint32_t src, int c0, int c1, int c2) {
  asm volatile("cp.async.bulk.tensor.3d.global.shared::cta.bulk_group [%0, {%2, %3, %4}], [%1];"
               ::"l"(m), "r"(src), "r"(c0), "r"(c1), "r"(c2) : "memory");
}
__device__ __forceinline__ void bar_sync(int id, int n) { asm volatile("bar.sync %0, %1;" ::"r"(id), "r"(n) : "memory"); }
__device__ __forceinline__ uint32_t pack_bf16(float lo, float hi) {
  uint32_t r;
  asm("cvt.rn.bf16x2.f32 %0, %1, %2;" : "=r"(r) : "f"(hi), "f"(lo));
  return r;
}
__device__ __forceinline__ float ex2(float x) {
  float y;
  asm("ex2.approx.ftz.f32 %0, %1;" : "=f"(y) : "f"(x));
  return y;
}
__device__ __forceinline__ float rcp(float x) {
  float y;
  asm("rcp.approx.ftz.f32 %0, %1;" : "=f"(y) : "f"(x));
  return y;
}
__device__ __forceinline__ void stsm4(uint32_t addr, uint32_t a, uint32_t b, uint32_t c, uint32_t d) {
  asm volatile("stmatrix.sync.aligned.m8n8.x4.shared.b16 [%0], {%1, %2, %3, %4};" ::"r"(addr), "r"(a), "r"(b), "r"(c), "r"(d) : "memory");
}

__device__ __forceinline__ void tma4d_mc_hint(uint32_t dst, const CUtensorMap* m, uint32_t bar, int c3, uint64_t pol) {
  asm volatile("cp.async.bulk.tensor.4d.shared::cluster.global.mbarrier::complete_tx::bytes.multicast::cluster.L2::cache_hint"
               " [%0], [%1, {%3, %3, %3, %4}], [%2], %5, %6;"
               ::"r"(dst), "l"(m), "r"(bar), "r"(0), "r"(c3), "h"((uint16_t)3), "l"(pol) : "memory");
}
__device__ __forceinline__ void tma5d_mc(uint32_t dst, const CUtensorMap* m, uint32_t bar, int c2, int c4) {
  asm volatile("cp.async.bulk.tensor.5d.shared::cluster.global.mbarrier::complete_tx::bytes.multicast::cluster"
               " [%0], [%1, {%3, %3, %4, %3, %5}], [%2], %6;"
               ::"r"(dst), "l"(m), "r"(bar), "r"(0), "r"(c2), "r"(c4), "h"((uint16_t)3) : "memory");
}
__device__ __forceinline__ void bulk_load_hint(uint32_t dst, const void* src, uint32_t bytes, uint32_t bar, uint64_t pol) {
  asm volatile("cp.async.bulk.shared::cluster.global.mbarrier::complete_tx::bytes.L2::cache_hint [%0], [%1], %2, [%3], %4;"
               ::"r"(dst), "l"(src), "r"(bytes), "r"(bar), "l"(pol) : "memory");
}
__device__ __forceinline__ void stg128_hint(void* p, uint32_t a, uint32_t b, uint32_t c, uint32_t d, uint64_t pol) {
  asm volatile("st.global.L2::cache_hint.v4.b32 [%0], {%1, %2, %3, %4}, %5;" ::"l"(p), "r"(a), "r"(b), "r"(c), "r"(d), "l"(pol) : "memory");
}
__device__ __forceinline__ void stg2_if(bool on, void* p, uint32_t a, uint32_t b, uint32_t c, uint32_t d, uint32_t e, uint32_t f,
                                        uint32_t g, uint32_t h, uint64_t pol) {
  asm volatile("{\n.reg .pred p;\nsetp.ne.b32 p, %10, 0;\n"
               "@p st.global.L2::cache_hint.v4.b32 [%0], {%1, %2, %3, %4}, %9;\n"
               "@p st.global.L2::cache_hint.v4.b32 [%0 + 512], {%5, %6, %7, %8}, %9;\n}\n"
               ::"l"(p), "r"(a), "r"(b), "r"(c), "r"(d), "r"(e), "r"(f), "r"(g), "r"(h), "l"(pol), "r"((int)on) : "memory");
}
__device__ __forceinline__ uint64_t make_policy(bool first) {
  uint64_t pf, pn;
  asm("createpolicy.fractional.L2::evict_first.b64 %0, 1.0;" : "=l"(pf));
  asm("createpolicy.fractional.L2::evict_normal.b64 %0, 1.0;" : "=l"(pn));
  return first ? pf : pn;
}
__device__ __forceinline__ bool elect() {
  uint32_t ok;
  asm volatile("{\n.reg .pred p;\nelect.sync _|p, 0xffffffff;\nselp.u32 %0, 1, 0, p;\n}\n" : "=r"(ok));
  return ok;
}
__device__ __forceinline__ void mbar_arrive(uint32_t bar) {
  asm volatile("mbarrier.arrive.shared::cta.b64 _, [%0];" ::"r"(bar) : "memory");
}
__device__ __forceinline__ void mbar_arrive_if(bool on, uint32_t bar) {
  asm volatile("{\n.reg .pred p;\nsetp.ne.b32 p, %1, 0;\n@p mbarrier.arrive.shared::cta.b64 _, [%0];\n}\n" ::"r"(bar), "r"((int)on) : "memory");
}
__device__ __forceinline__ void stg128(void* p, uint32_t a, uint32_t b, uint32_t c, uint32_t d) {
  asm volatile("st.global.v4.b32 [%0], {%1, %2, %3, %4};" ::"l"(p), "r"(a), "r"(b), "r"(c), "r"(d) : "memory");
}
__device__ __forceinline__ void lds2_if(bool on, uint32_t p, uint32_t (&t)[8]) {
  asm volatile("{\n.reg .pred p;\nsetp.ne.b32 p, %9, 0;\n@p ld.shared.v4.b32 {%0, %1, %2, %3}, [%8];\n@p ld.shared.v4.b32 {%4, %5, %6, %7}, [%8 + 512];\n}\n"
               : "+r"(t[0]), "+r"(t[1]), "+r"(t[2]), "+r"(t[3]), "+r"(t[4]), "+r"(t[5]), "+r"(t[6]), "+r"(t[7]) : "r"(p), "r"((int)on) : "memory");
}
__device__ __forceinline__ void lds128(uint32_t p, uint32_t& a, uint32_t& b, uint32_t& c, uint32_t& d) {
  asm volatile("ld.shared.v4.b32 {%0, %1, %2, %3}, [%4];" : "=r"(a), "=r"(b), "=r"(c), "=r"(d) : "r"(p) : "memory");
}
template <class T> __device__ __forceinline__ T* ptr_add(T* base, uint32_t bytes) {
  T* r;
  asm("{\n.reg .u32 lo, hi;\nmov.b64 {lo, hi}, %1;\nadd.cc.u32 lo, lo, %2;\naddc.u32 hi, hi, 0;\nmov.b64 %0, {lo, hi};\n}\n" : "=l"(r) : "l"(base), "r"(bytes));
  return r;
}
__device__ __forceinline__ uint32_t lds32(uint32_t p) {
  uint32_t v;
  asm volatile("ld.volatile.shared.u32 %0, [%1];" : "=r"(v) : "r"(p) : "memory");
  return v;
}
__device__ __forceinline__ uint32_t flag_get(const unsigned int* p) {
  uint32_t v;
  asm volatile("ld.acquire.gpu.global.u32 %0, [%1];" : "=r"(v) : "l"(p) : "memory");
  return v;
}
__device__ __forceinline__ void wait_progress(uint32_t p, uint32_t target) {
  asm volatile("{\n.reg .pred p;\n.reg .u32 n, v;\nmov.u32 n, 0;\n"
               "LOOP:\nld.acquire.cta.shared.u32 v, [%0];\nsetp.ge.u32 p, v, %1;\n@p bra DONE;\n"
               "nanosleep.u32 %2;\nadd.u32 n, n, 1;\nsetp.lt.u32 p, n, 0x400000;\n@p bra LOOP;\ntrap;\n"
               "DONE:\n}\n" ::"r"(p), "r"(target), "n"(400) : "memory");
}
__device__ __forceinline__ void flag_set(unsigned int* p, uint32_t v) {
  asm volatile("st.release.gpu.global.u32 [%0], %1;" ::"l"(p), "r"(v) : "memory");
}
__device__ __forceinline__ void flag_dec(unsigned int* p) {
  asm volatile("red.relaxed.gpu.global.add.u32 [%0], 0xffffffff;" ::"l"(p) : "memory");
}

struct Cursor {
  int bi;
  uint32_t ph;
  __device__ __forceinline__ void next() {
    if (++bi == NBAR) { bi = 0; ph ^= 1; }
  }
};

constexpr float kScaleLog2 = 0.07216878364870322f * 1.4426950408889634f;
constexpr float kSumLimit = 1048576.0f;

__global__ void __cluster_dims__(2, 1, 1) __launch_bounds__(384, 1)
fused_kernel(const __grid_constant__ Params P) {
  extern __shared__ uint8_t smem_raw[];
  const uint32_t sbase = (smem_u32(smem_raw) + 1023) & ~1023u;
  const uint32_t full0 = sbase + RING, empty0 = full0 + 8 * NBAR, odone0 = empty0 + 8 * NBAR, ev0 = odone0 + 8 * MAX_OPS;
  const uint32_t progress = ev0 + 8 * MAX_EV, jobw = progress + 4;
  const uint32_t rank = blockIdx.x & 1;
  const int role = blockIdx.x >> 1;
  const int wid = __shfl_sync(0xffffffffu, (int)(threadIdx.x >> 5), 0);
  const int wg = wid >> 2;

  if (wid < 8) {
    if (elect()) {
#pragma unroll
      for (int j = 0; j < 16; j++) {
        const int i = EARLY + 16 * wid + j;
        if (i < 2 * NBAR + MAX_OPS + MAX_EV) mbar_init(full0 + 8 * i, i < NBAR ? 1 : i < 2 * NBAR ? 16 : i < 2 * NBAR + MAX_OPS ? 8 : 1);
      }
      if (wid == 7) asm volatile("st.shared.v2.u32 [%0], {0, 0};\nfence.acq_rel.cta;" ::"r"(progress) : "memory");
      asm volatile("fence.mbarrier_init.release.cluster;" ::: "memory");
    }
  } else if (wid == 8) {
    const uint32_t op0 = P.first[role];
    if (elect()) {
#pragma unroll
      for (int k = 0; k < EARLY; k++) mbar_init(full0 + 8 * k, 1);
      asm volatile("fence.mbarrier_init.release.cluster;" ::: "memory");
      const int blk = (op0 >> 10) & 1;
      if ((op0 & 3) == OP_Q) {
#pragma unroll
        for (int k = 0; k < EARLY; k++) {
          mbar_expect(full0 + 8 * k, SZ_Q);
          tma2d(sbase + k * SZ_Q, &P.x[blk], full0 + 8 * k, 64 * k, ((op0 >> 7) & 7) * kSq + rank * 128);
          tma3d(sbase + k * SZ_Q + 16384, &P.wq[blk], full0 + 8 * k, 0, 64 * k, 3 * ((op0 >> 2) & 31));
        }
      }
      asm volatile("prefetch.tensormap [%0];" ::"l"(rank ? &P.v[blk] : &P.k[blk]) : "memory");
    }
  }
  __syncwarp();
  asm volatile("barrier.cluster.arrive.relaxed.aligned;\nbarrier.cluster.wait.aligned;" ::: "memory");

  if (wg < 2) {
    asm volatile("setmaxnreg.inc.sync.aligned.u32 240;");
    const uint32_t* prog = P.prog[role].c;
    const int lane = threadIdx.x & 31, warp = wid & 3;
    uint32_t empty_rem;
    asm volatile("mapa.shared::cluster.u32 %0, %1, %2;" : "=r"(empty_rem) : "r"(empty0), "r"(lane & 1));
    auto release = [&](int slot) { mbar_arrive_cluster_if(lane < 2, empty_rem + 8 * slot); };
    Cursor r{0, 0};
    const uint32_t ring16 = (sbase & 0x3FFFF) >> 4;
    uint32_t cur = ring16;
    bool rdy0 = false, rdy1 = false;
    auto probe1 = [&]() { rdy0 = mbar_test(full0 + 8 * r.bi, r.ph); };
    auto probe2 = [&]() {
      Cursor n = r;
      rdy0 = mbar_test(full0 + 8 * n.bi, n.ph);
      n.next();
      rdy1 = mbar_test(full0 + 8 * n.bi, n.ph);
    };
    auto take = [&](bool rdy, uint32_t bytes, uint32_t& addr) {
      const int bi = r.bi;
      if (__builtin_expect(!__all_sync(0xffffffffu, rdy), 0)) mbar_wait(full0 + 8 * r.bi, r.ph);
      r.next();
      if (cur > ring16 + ((RING - bytes) >> 4)) cur = ring16;
      addr = cur;
      cur += bytes >> 4;
      return bi;
    };
    uint32_t keep = lane;
    const bool never = P.dbg == 0xffffffffu;
    uint32_t q[48];
#pragma unroll
    for (int i = 0; i < 48; i++) q[i] = 0;
    const int row = wg * 64 + warp * 16 + (lane >> 2);
    const int img0 = row * 4 + ((lane & 3) ^ ((row >> 1) & 3));
    uint4* pend = nullptr;
    bool pend_any = false;
    uint64_t spol;
    int pc = 0;
    auto slab = [&](int c, int i0) {
#pragma unroll
      for (int i = i0; i < 6; i++)
        stg2_if(c == i, pend + i * 512, q[8 * i], q[8 * i + 1], q[8 * i + 2], q[8 * i + 3],
                q[8 * i + 4], q[8 * i + 5], q[8 * i + 6], q[8 * i + 7], spol);
    };
    auto drain = [&](int c) {
      if (!pend_any || c >= 6) return;
      slab(c, 0);
      if (c == 5) {
        __syncwarp();
        mbar_arrive_if(lane == 0, odone0 - 8 + 8 * pc);
      }
    };

    for (;; pc++) {
      uint32_t op = prog[pc];
      const int type = op & 3;
      auto enter = [&]() {
        r.bi = (op >> 15) & 15; r.ph = (op >> 19) & 1; cur = ring16 + (((op >> 20) & 63) << 8);
      };
      enter();
      pend_any = op & C_PEND;
      spol = make_policy(!(op & C_SOON));
      if (type == OP_END) {
#pragma unroll 1
        for (int c = 0; c < 6; c++) drain(c);
        asm volatile("barrier.cluster.arrive.relaxed;" ::: "memory");
        break;
      }
      {
        float s[32], o[96];
        uint32_t ad0;
        int bi0, sk1;
        uint32_t pa[16], pb[16];
        float mc0, mc1, l0, l1;
        bool shifted;
        uint32_t nop;
        auto expo = [&](float (&s)[32], uint32_t (&pout)[16], float& b0, float& b1, bool shift, auto mid) {
          float c0, c1;
#pragma unroll
          for (int i = 0; i < 8; i++) {
            const float e0 = ex2(shift ? s[4 * i] - mc0 : s[4 * i]), e1 = ex2(shift ? s[4 * i + 1] - mc0 : s[4 * i + 1]);
            const float e2 = ex2(shift ? s[4 * i + 2] - mc1 : s[4 * i + 2]), e3 = ex2(shift ? s[4 * i + 3] - mc1 : s[4 * i + 3]);
            if (i) { b0 += e0; c0 += e1; b1 += e2; c1 += e3; } else { b0 = e0; c0 = e1; b1 = e2; c1 = e3; }
            pout[2 * i] = pack_bf16(e0, e1); pout[2 * i + 1] = pack_bf16(e2, e3);
            if (i & 1) mid(i >> 1);
          }
          b0 += c0; b1 += c1;
        };
        auto rowmax = [&](float (&s)[32], float& m0, float& m1) {
          m0 = fmaxf(s[0], s[1]); m1 = fmaxf(s[2], s[3]);
#pragma unroll
          for (int i = 1; i < 8; i++) { m0 = fmaxf(m0, fmaxf(s[4 * i], s[4 * i + 1])); m1 = fmaxf(m1, fmaxf(s[4 * i + 2], s[4 * i + 3])); }
          m0 = fmaxf(m0, __shfl_xor_sync(0xffffffffu, m0, 1)); m1 = fmaxf(m1, __shfl_xor_sync(0xffffffffu, m1, 1));
          m0 = fmaxf(m0, __shfl_xor_sync(0xffffffffu, m0, 2)); m1 = fmaxf(m1, __shfl_xor_sync(0xffffffffu, m1, 2));
        };
        auto first = [&](float (&s)[32], int sk0, auto mid) {
          fence_regs(s);
          release(sk0);
          mc0 = 0.f; mc1 = 0.f;
          expo(s, pa, l0, l1, false, mid);
          shifted = __any_sync(0xffffffffu, !(fmaxf(l0, l1) <= kSumLimit && fminf(l0, l1) >= 1.f / kSumLimit));
          if (shifted) {
            rowmax(s, mc0, mc1);
            expo(s, pa, l0, l1, true, [](int) {});
          }
        };
        auto qk = [&](float (&s)[32], uint32_t ak, int k0 = 0, int k1 = 12) {
#pragma unroll
          for (int kk = k0; kk < k1; kk++)
            wgmma_rs_n64<0>(s, q[4 * kk], q[4 * kk + 1], q[4 * kk + 2], q[4 * kk + 3], mk_desc(ak + (kk >> 2) * KV_CH + (kk & 3) * 2, 16, KV_SBO, 1), kk != 0);
          if (k1 == 12) wg_commit();
        };
        auto pv = [&](uint32_t (&pin)[16], uint32_t av, int acc) {
#pragma unroll
          for (int kk = 0; kk < 4; kk++)
            wgmma_rs_n192<1>(o, pin[4 * kk], pin[4 * kk + 1], pin[4 * kk + 2], pin[4 * kk + 3], mk_desc(av + kk * (KV_SBO / 8), KV_CH * 16, KV_SBO, 1), acc || (kk != 0));
          wg_commit();
        };
        auto finish = [&](uint32_t (&pout)[16], int sk, int sv) {
          probe2();
          wg_wait<1>();
          fence_regs(s);
          release(sk);
          float b0, b1;
#pragma unroll 1
          for (bool redo = false;; redo = true) {
            expo(s, pout, b0, b1, false, [](int) {});
            if (!__any_sync(0xffffffffu, !redo && (shifted || !(fmaxf(b0, b1) <= kSumLimit)))) break;
            shifted = true;
            rowmax(s, b0, b1);
            b0 = fmaxf(mc0, b0); b1 = fmaxf(mc1, b1);
            const float a0 = ex2(mc0 - b0), a1 = ex2(mc1 - b1);
            mc0 = b0; mc1 = b1;
            l0 *= a0; l1 *= a1;
            wg_wait<0>();
            fence_regs(o);
#pragma unroll
            for (int i = 0; i < 24; i++) { o[4 * i] *= a0; o[4 * i + 1] *= a0; o[4 * i + 2] *= a1; o[4 * i + 3] *= a1; }
#pragma unroll
            for (int i = 0; i < 32; i++) s[i] -= (i & 2) ? mc1 : mc0;
          }
          l0 += b0; l1 += b1;
          wg_wait<0>();
          fence_regs(o);
          release(sv);
        };
        auto step = [&](uint32_t (&pin)[16], uint32_t (&pout)[16]) {
          uint32_t ak, av;
          const int sk = take(rdy0, SZ_KV, ak), sv = take(rdy1, SZ_KV, av);
          wg_fence();
          qk(s, ak);
          pv(pin, av, 1);
          finish(pout, sk, sv);
        };
        auto unpark = [&]() {
          uint32_t ad, ak;
          const int bi = take(rdy0, SZ_PARK, ad);
#pragma unroll
          for (int i = 0; i < 12; i++) lds128(sbase + (ad - ring16 + img0) * 16 + (i >> 1) * 8192 + (i & 1) * 512, q[4 * i], q[4 * i + 1], q[4 * i + 2], q[4 * i + 3]);
          const int sk0 = take(false, SZ_KV, ak);
          fence_regs(q);
          release(bi);
          wg_fence();
          qk(s, ak);
          probe2();
          return sk0;
        };
        auto mma4 = [&](uint32_t ad, int acc) {
#pragma unroll
          for (int kk = 0; kk < 4; kk++)
            wgmma_ss_n192<1>(o, mk_desc(ad + wg * 512 + kk * 2, 16, 1024, 1), mk_desc(ad + 1024 + kk * 128, 8192, 1024, 1), acc || kk != 0);
        };
        auto convert = [&](int i0, int i1) {
          sched_fence(keep, never);
#pragma unroll
          for (int i = i0; i < i1; i++) {
            q[i] = pack_bf16(o[2 * i] * kScaleLog2, o[2 * i + 1] * kScaleLog2);
            if (i % CONV_G == CONV_G - 1 && i != i1 - 1) sched_fence(keep, never);
          }
          sched_fence(keep, never);
        };
        auto kend = [&](int bi, int k) {
          wg_commit();
          drain(k < 8 ? (QDRAIN >> (4 * k)) & 7 : 7);
          probe1();
          wg_wait<0>();
          release(bi);
        };
        if (type == OP_O) {
          float c[80];
          int prev = 0;
          auto hand_over = [&](float (&c)[80], uint4* dst) {
            fence_regs(c);
#pragma unroll
            for (int i = 0; i < 48; i++) q[i] = i < 8 ? 0 : pack_bf16(c[2 * i - 16], c[2 * i - 15]);
            pend = dst;
          };
          auto mma2 = [&](float (&c)[80], uint32_t da, uint32_t db, int acc) {
            wgmma_ss_n160<1>(c, mk_desc(da, 16, 512, 2), mk_desc(db, 2048, 512, 2), acc);
            wgmma_ss_n160<1>(c, mk_desc(da + 2, 16, 512, 2), mk_desc(db + 64, 2048, 512, 2), 1);
          };
          auto kstep = [&](float (&c)[80], int acc, auto hook, uint32_t bytes = SZ_O) {
            uint32_t ad;
            const int bi = take(rdy0, bytes, ad);
            const uint32_t da = ad + wg * 256, db = ad + 1024;
            wg_fence();
            mma2(c, da, db, acc);
            wg_commit();
            if (acc) { wg_wait<1>(); mbar_arrive_cluster_if(lane < 2 && (acc == 1 || wg == 0), empty_rem + 8 * prev); }
            mma2(c, da + 512, db + 640, 1);
            wg_commit();
            prev = bi;
            hook();
            probe1();
            wg_wait<1>();
          };
          if (op & C_WIDE) {
            float d[80];
            const int nk = 3 * ((op >> 2) & 63);
            uint4* part = ptr_add(P.g->part, (((op >> 8) & 63) * 2 + rank) * SZ_PARK + img0 * 16);
            auto wstep = [&](int acc, auto hook) {
              uint32_t ad;
              const int bi = take(rdy0, SZ_W, ad);
              const uint32_t da = ad + wg * 256, db = ad + 1024;
              wg_fence();
              mma2(d, da, db, acc);
              mma2(d, da + 512, db + 640, 1);
              wg_commit();
              if (acc) { wg_wait<1>(); release(prev); }
              mma2(c, da, db + 1280, acc);
              mma2(c, da + 512, db + 1920, 1);
              wg_commit();
              prev = bi;
              hook();
              probe1();
              wg_wait<1>();
            };
            wstep(0, [&]() { drain(0); drain(1); });
#pragma unroll 1
            for (int k = 2; k < 6; k += 2) wstep(1, [&]() { drain(k); drain(k + 1); });
#pragma unroll 1
            for (int k = 3 + 3 * TAIL; k < nk; k++) {
              wstep(1, []() {});
            }
#pragma unroll 1
            for (int k = 0; k < 3 * TAIL; k++) kstep(d, 1, []() {});
            nop = prog[pc + 1];
            spol = make_policy(!(nop & C_SOON));
            kstep(c, 1, [&]() { hand_over(d, part - 6144); });
#pragma unroll 1
            for (int k = 1; k < 3 * TAIL; k++) kstep(c, 1, [&]() { slab(TAIL == 2 ? k : (0x50403201 >> (4 * k - 4)) & 7, 1); });
            if ((nop & 3) == OP_Q) {
              op = nop;
              enter();
              pc++;
              pend_any = true;
              bi0 = take(rdy0, SZ_Q, ad0);
              undefine(o);
              wg_fence();
              mma4(ad0, 0);
              wg_commit();
              wg_wait<1>();
              release(prev);
              hand_over(c, part);
              probe1();
              wg_wait<0>();
              release(bi0);
              fence_regs(o);
              goto next_head;
            }
            wg_wait<0>();
            release(prev);
            hand_over(c, part);
            continue;
          }
          auto unblock = [&](int k) {
            if (__all_sync(0xffffffffu, rdy0) || __all_sync(0xffffffffu, mbar_try(full0 + 8 * r.bi, r.ph, TRYNS))) return;
#pragma unroll 1
            for (; k < 6; k++) drain(k);
            pend_any = false;
          };
          uint32_t job;
          unblock(0);
          kstep(c, 0, [&]() { job = lds32(jobw); drain(0); });
#pragma unroll 1
          for (int k = 1; k < 6; k++) {
            unblock(k);
            kstep(c, 1, [&]() { drain(k); });
          }
          job = __shfl_sync(0xffffffffu, job, 0);
#pragma unroll 1
          for (int k = 3 * ((job >> 13) & 63); k > 11; k--) kstep(c, 1, []() {});
          uint32_t t[8], stage[3];
          float u[80];
          auto unpack = [&](int j) {
#pragma unroll
            for (int i = 0; i < 8; i++) {
              u[16 * j + 2 * i] = __uint_as_float(t[i] << 16); u[16 * j + 2 * i + 1] = __uint_as_float(t[i] & 0xffff0000u);
              asm volatile("" : "+f"(u[16 * j + 2 * i]), "+f"(u[16 * j + 2 * i + 1]));
            }
          };
#pragma unroll
          for (int i = 0; i < 8; i++) t[i] = 0;
          const uint32_t bytes = (job & P_LD) ? SZ_OL : SZ_O;
#pragma unroll
          for (int j = 0; j < 5; j++) {
            if (j == 5 - SKEW && wg == 1) {
              wg_wait<0>();
              release(prev);
              bar_sync(1, 256);
            }
            kstep(c, j == 5 - SKEW ? 2 : 1, [&]() {
              if (SKEW && j == 4) asm volatile("{\n.reg .pred p;\nsetp.eq.u32 p, %0, 0;\n@p bar.arrive 1, 256;\n}\n" ::"r"(wg) : "memory");
              if (j) unpack(j - 1);
              lds2_if(job & P_LD, sbase + (cur - ring16 + img0) * 16 - 8192, t);
              if (j >= 1 && j <= 3) stage[j - 1] = sbase + (cur - ring16) * 16 - bytes + wid * 1024;
            }, bytes);
          }
          unpack(4);
          sched_fence(keep, never);
          wg_wait<0>();
          fence_regs(c);
          release(prev);
          asm volatile("barrier.cluster.arrive.relaxed;" ::: "memory");
#pragma unroll
          for (int i = 0; i < 10; i++) {
            const int v = (i & 1) * 2 + (lane >> 4);
            const uint32_t sa = stage[i >> 2] + (i & 2) * 4096;
            stsm4(sa + (lane & 15) * 64 + ((v ^ ((lane >> 1) & 3)) << 4), pack_bf16(c[8 * i] + u[8 * i], c[8 * i + 1] + u[8 * i + 1]),
                  pack_bf16(c[8 * i + 2] + u[8 * i + 2], c[8 * i + 3] + u[8 * i + 3]), pack_bf16(c[8 * i + 4] + u[8 * i + 4], c[8 * i + 5] + u[8 * i + 5]),
                  pack_bf16(c[8 * i + 6] + u[8 * i + 6], c[8 * i + 7] + u[8 * i + 7]));
          }
          asm volatile("fence.proxy.async.shared::cta;" ::: "memory");
          __syncwarp();
          if (elect()) {
#pragma unroll
            for (int i = 0; i < 5; i++)
              tma3d_store(&P.out, stage[i >> 1] + (i & 1) * 8192, 0, ((job >> 7) & 7) * kSq + rank * 128 + wid * 16, ((job >> 10) & 1) * 20 + ((job >> 19) & 3) * 5 + i);
            asm volatile("cp.async.bulk.commit_group;\ncp.async.bulk.wait_group.read 0;" ::: "memory");
          }
          __syncwarp();
          break;
        }
        bi0 = take(rdy0, SZ_Q, ad0);
        undefine(o);
        wg_fence();
        mma4(ad0, 0);
        kend(bi0, 0);
        fence_regs(o);
      next_head:
        {
#pragma unroll 1
          for (int k = 1; k < ((op & F_PARK) ? 10 : 8); k++) {
            uint32_t ad;
            const int bi = take(rdy0, SZ_Q, ad);
            wg_fence();
            mma4(ad, 1);
            kend(bi, k);
          }
          if (op & F_PARK) {
            fence_regs(o);
            convert(0, 48);
            pend = ptr_add(P.g->tile, (((op >> 2) & 511) * 2 + rank) * SZ_PARK + img0 * 16);
            continue;
          }
          uint32_t a8, a9, ak0, ak1;
          const int b8 = take(rdy0, SZ_Q, a8), b9 = take(false, SZ_Q, a9);
          wg_fence();
          mma4(a8, 1);
          wg_commit();
          mma4(a9, 1);
          wg_commit();
          pc++;
          wg_wait<1>();
          release(b8);
          const int sk0 = take(false, SZ_KV, ak0);
          wg_wait<0>();
          fence_regs(o);
          release(b9);
          float s0[32];
          convert(0, CONV_0);
          wg_fence();
          qk(s0, ak0, 0, 4);
          convert(CONV_0, 48);
          wg_fence();
          qk(s0, ak0, 4, 12);
          sk1 = take(false, SZ_KV, ak1);
          probe1();
          wg_wait<0>();
          first(s0, sk0, [&](int i) {
            if (i != QA && i != QB && i != QC) return;
            sched_fence(keep, never);
            wg_fence();
            if (i == QA) qk(s, ak1, 0, 4);
            if (i == QB) qk(s, ak1, 4, 8);
            if (i == QC) qk(s, ak1, 8, 12);
            sched_fence(keep, never);
          });
        }
        for (;;) {
          {
            uint32_t av;
            const int sv = take(rdy0, SZ_KV, av);
            undefine(o);
            wg_fence();
            pv(pa, av, 0);
            finish(pb, sk1, sv);
          }
          nop = prog[pc + 1];
#pragma unroll 1
          for (int jj = 0; jj < 7; jj++) {
            step(pb, pa);
            step(pa, pb);
          }
          float i0, i1;
          auto last = [&]() {
            uint32_t av;
            const int sv = take(rdy0, SZ_KV, av);
            wg_fence();
            pv(pb, av, 1);
            sched_fence(keep, never);
            probe1();
            l0 += __shfl_xor_sync(0xffffffffu, l0, 1); l1 += __shfl_xor_sync(0xffffffffu, l1, 1);
            l0 += __shfl_xor_sync(0xffffffffu, l0, 2); l1 += __shfl_xor_sync(0xffffffffu, l1, 2);
            i0 = rcp(l0); i1 = rcp(l1);
            pend = ptr_add(P.g->tile, (((op >> 2) & 511) * 2 + rank) * SZ_PARK + img0 * 16);
            return sv;
          };
          auto normalise = [&](uint32_t (&d)[48], auto mid) {
#pragma unroll
            for (int i = 0; i < 24; i++) {
              d[8 * (i >> 2) + (i & 3)] = pack_bf16(o[4 * i] * i0, o[4 * i + 1] * i0);
              d[8 * (i >> 2) + (i & 3) + 4] = pack_bf16(o[4 * i + 2] * i1, o[4 * i + 3] * i1);
              if (i % NORM_G == NORM_G - 1 && i != 23) sched_fence(keep, never);
              if ((i & 3) == 3 && i != 23) mid(i >> 2);
            }
          };
          const int sv = last();
          if ((nop & 3) != OP_A) {
            op = nop;
            enter();
            pend_any = true;
            spol = make_policy(!(op & C_SOON));
            bi0 = take(rdy0 || (nop & 3) != OP_Q, SZ_Q, ad0);
            sched_fence(keep, never);
            wg_wait<0>();
            fence_regs(o);
            release(sv);
            normalise(q, [](int) {});
            undefine(o);
            if ((nop & 3) != OP_Q) break;
            sched_fence(keep, never);
            wg_fence();
            mma4(ad0, 0);
            pc++;
            kend(bi0, 0);
            fence_regs(o);
            goto next_head;
          }
          const int sk0 = unpark();
          wg_wait<1>();
          fence_regs(o);
          release(sv);
          uint32_t t[48];
          spol = make_policy(!(nop & C_SOON));
          auto st = [&](int i) {
            stg2_if(true, pend + i * 512, t[8 * i], t[8 * i + 1], t[8 * i + 2], t[8 * i + 3], t[8 * i + 4], t[8 * i + 5], t[8 * i + 6], t[8 * i + 7], spol);
          };
          normalise(t, [&](int i) { if (!(i & 1)) st(i >> 1); });
          wg_wait<0>();
          first(s, sk0, [&](int i) { if (i < 3) { sched_fence(keep, never); st(3 + i); } });
          __syncwarp();
          mbar_arrive_if(lane == 0, odone0 + 8 * pc);
          pc++;
          op = nop;
          uint32_t ak1;
          sk1 = take(rdy0, SZ_KV, ak1);
          rdy0 = rdy1;
          wg_fence();
          qk(s, ak1);
        }
      }
    }
    if (never) P.g->flag[0] = keep;
    asm volatile("barrier.cluster.wait;" ::: "memory");
  } else {
    asm volatile("setmaxnreg.dec.sync.aligned.u32 24;");
    const uint32_t* prog = P.prog[role].p;
    unsigned int* flag = P.g->flag + rank;
    if (wid == 8) {
      Cursor tail{0, 0};
      int head = 0, sh = 0;
      uint32_t cur = 0, used = 0;
      uint64_t fifo = 0;
      uint32_t dst, bar, ev = ev0, done = 0;
      uint64_t pol;
      asm volatile("createpolicy.fractional.L2::evict_first.b64 %0, 1.0;" : "=l"(pol));
      auto retire = [&]() {
        mbar_wait(empty0 + 8 * tail.bi, tail.ph);
        tail.next();
        used -= (uint32_t)fifo & 31;
        fifo >>= 5;
        sh -= 5;
        asm volatile("st.volatile.shared.u32 [%0], %1;" ::"r"(progress), "r"(++done) : "memory");
      };
      auto acquire = [&](uint32_t bytes) {
        uint32_t fp = bytes >> 12;
        if (cur + fp > (RING >> 12)) { fp += (RING >> 12) - cur; cur = 0; }
        used += fp;
        while (used > (RING >> 12) || sh == 5 * NBAR) retire();
        fifo |= (uint64_t)fp << sh;
        sh += 5;
        dst = sbase + (cur << 12);
        bar = full0 + 8 * head;
        cur += bytes >> 12;
        if (++head == NBAR) head = 0;
      };
      auto gate = [&]() {
        mbar_wait(ev, 0);
        ev += 8;
        asm volatile("fence.proxy.async.global;" ::: "memory");
      };
      for (int pc = 0;; pc++) {
        uint32_t op = prog[pc];
        const int type = op & 3;
        if (type == OP_END) break;
        if (op == OP_O) {
          gate();
          op = __shfl_sync(0xffffffffu, lds32(jobw), 0);
        }
        const int blk = (op >> 10) & 1;
        if (type == OP_Q) {
#pragma unroll 1
          for (int k = 0; k < 10; k++) {
            if (k == 9 && (op & P_GATE)) gate();
            acquire(SZ_Q);
            if ((pc > 0 || k >= EARLY) && elect()) {
              mbar_expect(bar, SZ_Q);
              tma2d(dst, &P.x[blk], bar, 64 * k, ((op >> 7) & 7) * kSq + rank * 128);
              if ((k & 1) == rank) tma3d_mc(dst + 16384, &P.wq[blk], bar, 0, 64 * k, 3 * ((op >> 2) & 31));
            }
          }
        } else if (type == OP_A) {
          const int row0 = ((op >> 2) & 255) * kSk;
          const CUtensorMap* kv_map = rank ? &P.v[blk] : &P.k[blk];
          if (op & F_PARK) {
            gate();
            acquire(SZ_PARK);
            if (elect()) {
              mbar_expect(bar, SZ_PARK);
              bulk_load_hint(dst, &P.g->tile[((op >> 20) * 2 + rank) * 3072], SZ_PARK, bar, make_policy(P.dbg & 4));
            }
          }
#pragma unroll 1
          for (int t = 0; t < 32; t++) {
            const int isv = t == 31 ? 1 : (t == 0 ? 0 : (~t & 1));
            const int j = isv ? (t - 1) >> 1 : (t + 1) >> 1;
            if (t == 31 && (op & P_GATE)) gate();
            acquire(SZ_KV);
            if (elect()) {
              mbar_expect(bar, SZ_KV);
              if (isv == (int)rank) tma4d_mc_hint(dst, kv_map, bar, row0 / 8 + 8 * j, pol);
            }
          }
        } else {
          const int n = (op >> 13) & 63, nw = (op & P_WIDE) ? n - TAIL : 0;
          const uint64_t pol_o = make_policy(P.dbg & (nw ? 1 : 2));
          const uint4* part = &P.g->part[((((op >> 5) & 60) + ((op >> 19) & 3)) * 2 + rank) * 3072 + 512];
#pragma unroll 1
          for (int i = 0; i < n + (nw ? TAIL : 0); i++) {
            const int id = ((op >> 2) & 511) + (i < n ? i : i - TAIL), col = 5 * (((op >> 19) & 3) + (i >= n));
            const uint4* src = &P.g->tile[(P.slot[id] * 2 + rank) * 3072];
            if ((op & P_LD) && i == ((op & P_PRE) ? 0 : n - 2)) gate();
            if (i < n) gate();
#pragma unroll 1
            for (int k = 0; k < 3; k++) {
              const uint32_t j = (op & P_LD) ? 3 * (i - n) + k + 5 : 5, bytes = i < nw ? SZ_W : j < 5 ? SZ_OL : SZ_O;
              acquire(bytes);
              if (elect()) {
                mbar_expect(bar, bytes);
                tma5d_mc(dst + 16384 + rank * 10240, &P.wo[blk], bar, 24 * (id & 31) + 8 * k + 4 * rank, col);
                bulk_load_hint(dst, src + k * 1024, 16384, bar, pol_o);
                if (i < nw) tma5d_mc(dst + SZ_O + rank * 10240, &P.wo[blk], bar, 24 * (id & 31) + 8 * k + 4 * rank, col + 5);
                if (j < 5) bulk_load_hint(dst + SZ_O, part + j * 512, 8192, bar, pol);
                if ((op & P_PRE) && (uint32_t)(3 * i + k) < PFN)
                  asm volatile("cp.async.bulk.prefetch.L2.global [%0], %1;" ::"l"(part + (3 * i + k) * (2560 / PFN)), "n"(40960 / PFN) : "memory");
              }
            }
          }
        }
      }
#pragma unroll 1
      while (sh) retire();
    } else if (threadIdx.x == 288) {
      for (int pc = 0;; pc++) {
        const uint32_t op = prog[pc];
        const int type = op & 3;
        if (type == OP_END) break;
        if (type == OP_Q ? !(op & F_PARK) : type == OP_O && !(op & P_ST)) continue;
        const int id = type == OP_A ? (op >> 2) & 511 : type == OP_Q ? N_TILE + ((op >> 13) & 127) : ID_PART + ((op >> 5) & 60) + ((op >> 19) & 3);
        const uint32_t v = type == OP_O ? 1 : P.info[id] & 7;
        mbar_wait_slow<PUBNS>(odone0 + 8 * pc, 0);
        flag_set(flag + 2 * id, v);
        if (type == OP_O && (op & P_WIDE)) flag_set(flag + 2 * id + 2, v);
      }
    } else if (wid == 10) {
      int i = threadIdx.x & 31;
      uint32_t e = i < 8 ? P.prog[role].ev[i] : 0;
      for (uint32_t n = 0; __any_sync(0xffffffffu, e); n++) {
        uint32_t job = (e & (E_DRAW | E_JOB)) ? lds32(jobw) : 0;
        if ((e & E_DRAW) && rank == 0 && lds32(progress) >= (e & 1023)) {
          job = P.job[atomicInc(&P.g->ticket, 4 * N_TEAM - 1)];
          asm volatile("{\n.reg .u32 a;\nmapa.shared::cluster.u32 a, %0, 1;\nst.volatile.shared::cluster.u32 [a], %1;\n"
                       "st.volatile.shared.u32 [%0], %1;\n}\n" ::"r"(jobw), "r"(job) : "memory");
        }
        if ((e & E_JOB) && job) {
          const uint32_t j = e & 63, heads = (job >> 13) & 63, jp = !(job & P_LD) ? 63 : (job & P_PRE) ? 0 : heads - 2, h = j - (j > jp);
          e = j == jp ? (ID_PART + ((job >> 5) & 60) + ((job >> 19) & 3)) | E_ON | E_LAST : h < heads ? (((job >> 2) & 511) + h) | E_ON | E_LAST : 0;
        }
        unsigned int* f = ptr_add(flag, 8 * (e & 1023));
        const bool ok = (e & E_ON) ? flag_get(f) - 1 < ((e & E_FREE) ? 1 : 7) : (e & E_DRAW) && job;
        if (ok) {
          mbar_arrive(ev0 + 8 * i);
          if (e & (E_FREE | E_LAST)) flag_dec(f);
          i += 8;
          e = i < MAX_EV ? P.prog[role].ev[i] : 0;
        }
        asm volatile("{\n.reg .pred p;\nsetp.ge.u32 p, %0, 0x400000;\n@p trap;\n}\n" ::"r"(n));
        if (!__any_sync(0xffffffffu, ok)) __nanosleep(WATNS);
      }
    } else if (threadIdx.x == 352) {
      uint32_t items = 0;
      auto read = [&](int id) {
        if (!(P.info[id] & I_NEXT)) return;
        wait_progress(progress, items);
        flag_dec(flag + 2 * id);
      };
      for (int pc = 0;; pc++) {
        const uint32_t op = prog[pc];
        const int type = op & 3;
        if (type == OP_END) break;
        if (type == OP_O) {
          const int n = (op >> 13) & 63;
#pragma unroll 1
          for (int i = 0; i < n; i++) {
            items += (op & P_WIDE) && i == n - TAIL ? 3 * TAIL + 3 : 3;
            read(((op >> 2) & 511) + i);
          }
        } else if (type == OP_A) {
          if (op & F_PARK) { items++; read(N_TILE + ((op >> 13) & 127)); }
          items += 32;
        } else {
          items += 10;
        }
      }
    }
    __syncwarp();
    asm volatile("barrier.cluster.arrive.relaxed;\nbarrier.cluster.wait;" ::: "memory");
  }
}

typedef CUresult (*EncodeFn)(CUtensorMap*, CUtensorMapDataType, cuuint32_t, void*, const cuuint64_t*, const cuuint64_t*,
                             const cuuint32_t*, const cuuint32_t*, CUtensorMapInterleave, CUtensorMapSwizzle,
                             CUtensorMapL2promotion, CUtensorMapFloatOOBfill);

void encode(EncodeFn fn, CUtensorMap* m, const void* ptr, int rank, const cuuint64_t* dims, const cuuint64_t* strides,
            const cuuint32_t* box, CUtensorMapSwizzle swz) {
  const cuuint32_t es[5] = {1, 1, 1, 1, 1};
  CUresult r = fn(m, CU_TENSOR_MAP_DATA_TYPE_BFLOAT16, rank, const_cast<void*>(ptr), dims, strides, box, es,
                  CU_TENSOR_MAP_INTERLEAVE_NONE, swz, CU_TENSOR_MAP_L2_PROMOTION_L2_128B, CU_TENSOR_MAP_FLOAT_OOB_FILL_NONE);
  if (r != CUDA_SUCCESS) fprintf(stderr, "cuTensorMapEncodeTiled failed: %d\n", (int)r);
}

struct Op { int type, flags, id, n, quarter, park, item0, items; double t0, t1; };
struct Use { double ready, gate, need, freed; int readers, slot, prev; bool next; };
struct PlanStats { double end, slack, park_slack; int slots, parks; uint32_t own[N_CL]; };

bool plan(const char* const* text, int n_pair, int phase, Params& P, PlanStats* stats = nullptr) {
  constexpr double T_Q = 7900, T_A = 24850, T_U = 26300, T_O = 1920, T_RUN = 800, T_WIDE = 1900, AHEAD = 3500, PUBLISH = 1500;
  const double margin = 256.0 * ((P.dbg >> 8) & 255);
  static Op op[N_CL][MAX_OPS];
  static Use use[ID_PART];
  int n_op[N_CL], covered[N_TEAM] = {}, finals[N_TEAM] = {};
  auto hex = [](char c) { return c <= '9' ? c - '0' : c - 'a' + 10; };
  for (int i = 0; i < n_pair; i++)
    for (const char* s = text[i]; *s; s++)
      if (*s == 'J') { if (covered[hex(s[1])]) return false; covered[hex(s[1])] = 10 * (s[2] - '0') + s[3] - '0'; }
  for (int c = 0; c < 2 * n_pair; c++) {
    int n = 0, items = 0;
    double t = 0;
    auto add = [&](int type, int flags, int id, int heads, int quarter, int its, double dt) {
      if (n < MAX_OPS) op[c][n] = {type, flags, id, heads, quarter, 0, items, its, t, t + dt};
      n++; items += its; t += dt;
    };
    for (const char* s = text[c >> 1]; *s; s++) {
      const int tm = hex(s[1]) & 15, nj = covered[tm];
      if (*s == 'N') { add(OP_Q, 0, 0, 0, 0, 10, T_Q); add(OP_A, 0, 0, 0, 0, 32, T_A); }
      if (*s == 'P') add(OP_Q, F_PARK, 0, 0, 0, 10, T_Q);
      if (*s == 'U') { if (n == 0 || n > MAX_OPS || op[c][n - 1].type != OP_A) return false; add(OP_A, F_PARK, 0, 0, 0, 33, T_U); }
      if (*s == 'J') { if (nj <= TAIL || nj > kH - 4) return false; add(OP_O, P_WIDE | P_ST, tm * kH, nj, 2 * (c & 1), 3 * (nj + TAIL), 2 * T_O * nj + T_WIDE); }
      if (*s == 'F') { if (s[2]) return false; add(OP_O, nj ? P_LD : 0, tm * kH + nj, kH - nj, finals[tm]++, 3 * (kH - nj), T_O * (kH - nj) + T_RUN); }
    }
    add(OP_END, 0, 0, 0, 0, 0, 0);
    if (n > MAX_OPS || op[c][0].type != OP_Q) return false;
    n_op[c] = n - 1;
  }
  for (int t = 0; t < N_TEAM; t++) if (finals[t] != 4) return false;
  for (int i = 0; i < ID_PART; i++) use[i] = {0, 0, 1e18, 0, 0, 0, 0, false};
  struct Ref { double t; Op* o; int id; };
  static Ref att[N_TILE + 1], dem[N_TILE], prk[MAX_PARK + 1], unp[MAX_PARK + 1], wr[ID_PART];
  int n_att = 0, n_prk = 0, n_unp = 0;
  auto ready = [&](const Op* o) {
    const int nt = o[1].type;
    return o->t1 + (nt == OP_Q ? 6100 : nt == OP_O ? 3900 : 1500) + PUBLISH;
  };
  for (int c = 0; c < 2 * n_pair; c++)
    for (Op* o = op[c]; o->type != OP_END; o++) {
      if (o->type == OP_A) { att[n_att] = {ready(o), o, 0}; if (++n_att > N_TILE) return false; }
      if (o->type == OP_A && o->flags) { unp[n_unp] = {o->t0 - AHEAD, o, 0}; if (++n_unp > MAX_PARK) return false; }
      if (o->type == OP_Q && o->flags) { prk[n_prk] = {ready(o), o, 0}; if (++n_prk > MAX_PARK) return false; }
      for (int i = 0; o->type == OP_O && i < o->n; i++) {
        const int nw = (o->flags & P_WIDE) ? o->n - TAIL : 0;
        Use& u = use[o->id + i];
        const double t = o->t0 + T_O * (i + (i < nw ? i : nw));
        if (t - AHEAD < u.need) u.need = t - AHEAD;
        const double f = i < nw || (nw && o[1].type != OP_O) ? t + T_O * (i < nw ? 2 : 1 + TAIL) + PUBLISH : 1e18;
        if (f > u.freed) u.freed = f;
        u.readers++;
      }
    }
  if (n_att != N_TILE || n_prk != n_unp) return false;
  auto sort = [](Ref* r, int n) {
    for (int i = 1; i < n; i++)
      for (int j = i; j > 0 && r[j].t < r[j - 1].t; j--) { Ref x = r[j]; r[j] = r[j - 1]; r[j - 1] = x; }
  };
  for (int i = 0; i < N_TILE; i++) { const int id = (i & 15) * kH + (i >> 4); dem[i] = {use[id].need, nullptr, id}; }
  sort(att, n_att); sort(dem, N_TILE); sort(prk, n_prk); sort(unp, n_unp);
  PlanStats st = {0, 1e18, 1e18, 0, n_prk};
  int n_wr = 0;
  for (int i = 0; i < N_TILE; i++) {
    Op* o = att[i].o;
    o->id = dem[i].id;
    if (!o->flags) o[-1].id = o->id;
    if (dem[i].t - att[i].t < st.slack) st.slack = dem[i].t - att[i].t;
    wr[n_wr++] = {o->t1 - 2 * AHEAD, o, o->id};
  }
  for (int i = 0; i < n_prk; i++) {
    prk[i].o->id = unp[i].o->id;
    prk[i].o->park = unp[i].o->park = i;
    use[N_TILE + i].freed = unp[i].o->t0 + 2 * PUBLISH;
    use[N_TILE + i].readers = 1;
    if (unp[i].t - prk[i].t < st.park_slack) st.park_slack = unp[i].t - prk[i].t;
    wr[n_wr++] = {prk[i].o->t1 - 2 * AHEAD, prk[i].o, N_TILE + i};
  }
  for (int c = 0; c < 2 * n_pair; c++)
    for (int d = 0; d < 2 * n_pair; d++)
      for (Op *f = &op[c][n_op[c] - 1], *o = op[d]; f->type == OP_O && o->type != OP_END; o++)
        if (o->type == OP_O && (o->flags & P_ST) && o->id / kH == f->id / kH) {
          if (f->t0 - o->t1 > 4096.0 * ((P.dbg >> 16) & 255)) f->flags |= P_PRE;
          const double slack = f->t0 + ((f->flags & P_PRE) ? 0 : (f->n - 2) * T_O) - AHEAD - ready(o);
          if (slack < st.park_slack) st.park_slack = slack;
        }
  sort(wr, n_wr);
  int holder[N_TILE];
  for (int i = 0; i < n_wr; i++) {
    int best = -1;
    for (int sl = 0; sl < st.slots; sl++)
      if (use[holder[sl]].freed + margin <= wr[i].t && (best < 0 || (use[holder[sl]].freed < use[holder[best]].freed) != ((P.dbg & 32) != 0))) best = sl;
    Use& u = use[wr[i].id];
    if (best >= 0) { u.prev = holder[best]; use[u.prev].next = true; wr[i].o->flags |= P_GATE; }
    else if (st.slots == N_TILE) return false;
    else best = st.slots++;
    u.slot = best;
    holder[best] = wr[i].id;
  }
  {
    int pos[N_CL] = {}, flag[ID_PART + 4 * N_TEAM] = {}, seen[ID_PART] = {};
    auto goal = [&](int c) { const Op& f = op[c][n_op[c] - 1]; return f.type == OP_O && !(f.flags & P_WIDE) ? f.item0 : f.item0 + f.items + NBAR; };
    for (bool moved = true; moved;) {
      moved = false;
      for (int c = 0; c < 2 * n_pair; c++) {
        for (; pos[c] < goal(c); pos[c]++, moved = true) {
          bool ok = true;
          for (const Op* o = op[c]; o->type != OP_END; o++) {
            const int k = pos[c] - o->item0, own = o->type == OP_A ? o->id : N_TILE + o->park;
            if (k < 0 || k >= o->items) continue;
            if (o->type == OP_O) ok = k >= 3 * o->n || flag[o->id + k / 3];
            else if (k == o->items - 1 && (o->flags & P_GATE)) ok = seen[use[own].prev] == use[use[own].prev].readers;
            else if (k == 0 && o->type == OP_A && (o->flags & F_PARK)) ok = flag[N_TILE + o->park];
          }
          if (!ok) break;
          for (const Op* o = op[c]; o->type != OP_END; o++) {
            if (pos[c] == o->item0 + o->items + (o[1].type == OP_Q ? 7 : o[1].item0 == goal(c) ? -1 : 5)) {
              if (o->type == OP_A) flag[o->id] = 1;
              if (o->type == OP_Q && (o->flags & F_PARK)) flag[N_TILE + o->park] = 1;
              if (o->type == OP_O) flag[ID_PART + o->id / kH * 4 + o->quarter] = flag[ID_PART + o->id / kH * 4 + o->quarter + 1] = 1;
            }
            const int k = pos[c] - NBAR - o->item0, nw = o->n - TAIL;
            if (k == 0 && o->type == OP_A && (o->flags & F_PARK)) seen[N_TILE + o->park]++;
            if (o->type == OP_O && k >= 0 && k < o->items && k % 3 == 2 && (k / 3 < nw || k / 3 >= o->n)) seen[o->id + (k / 3 < nw ? k / 3 : k / 3 - TAIL)]++;
          }
        }
      }
    }
    for (int c = 0; c < 2 * n_pair; c++) if (pos[c] < goal(c)) return false;
  }
  int n_job = 0, longest = 0;
  for (int t = 0; t < N_TEAM; t++) if (kH - covered[t] > longest) longest = kH - covered[t];
  for (int c = 0; c < 2 * n_pair; c++) {
    uint32_t items = 0, cur = 0, pend = 0;
    int n = 0, ev = 0;
    auto item = [&](uint32_t bytes, int count) {
      for (int i = 0; i < count; i++) { if (cur + bytes > RING) cur = 0; cur += bytes; items++; }
    };
    auto event = [&](uint32_t e) { if (ev < MAX_EV) P.prog[c].ev[ev] = e; ev++; };
    for (const Op* o = op[c];; o++) {
      if (o->type != OP_END && phase && (o->type == OP_O) != (phase == 2)) continue;
      uint32_t cw = o->type | (items % NBAR) << 15 | ((items / NBAR) & 1) << 19 | (cur >> 12) << 20 | pend, pw = o->type | o->id << 2 | o->flags;
      const int ps = use[N_TILE + o->park].slot;
      pend = 0;
      if (o->type == OP_O) {
        pw |= o->n << 13 | o->quarter << 19;
        if (o->flags & P_WIDE) {
          cw |= o->n << 2 | (o->id / kH * 4 + o->quarter + 1) << 8 | C_WIDE;
          item(SZ_W, 3 * (o->n - TAIL));
          item(SZ_O, 6 * TAIL);
          pend = C_PEND | ((P.dbg & 8) ? C_SOON : 0);
          for (int i = 0; i < o->n; i++) event((o->id + i) | E_ON | (use[o->id + i].next ? 0 : E_LAST));
        } else {
          dem[n_job++] = {o->t0 - 1e6 * o->n, nullptr, (int)pw};
          st.own[c] = pw;
          pw = OP_O;
          event(E_DRAW | (items < 16 ? 0 : items - 16));
          for (int i = 0; i <= longest; i++) event(E_JOB | i);
        }
      } else if (o->type != OP_END) {
        const bool parks = o->type == OP_Q && (o->flags & F_PARK);
        cw |= (parks ? ps : use[o->id].slot) << 2 | (o->flags & F_PARK);
        if (o->flags & F_PARK) pw |= o->park << 13 | ps << 20;
        if (o->type == OP_Q) item(SZ_Q, 10);
        else { if (o->flags & F_PARK) { item(SZ_PARK, 1); event((N_TILE + o->park) | E_ON | (use[N_TILE + o->park].next ? 0 : E_LAST)); } item(SZ_KV, 32); }
        if (parks || o->type == OP_A) pend = C_PEND | ((P.dbg & 16) ? 0 : C_SOON);
        if (o->flags & P_GATE) event(use[parks ? N_TILE + o->park : o->id].prev | E_ON | E_FREE);
      }
      P.prog[c].c[n] = cw; P.prog[c].p[n++] = pw;
      if (o->type == OP_END) { if (o->t0 > st.end) st.end = o->t0; break; }
    }
    if (ev > MAX_EV) return false;
    while (ev < MAX_EV) P.prog[c].ev[ev++] = 0;
    while (n < MAX_OPS) { P.prog[c].c[n] = OP_END; P.prog[c].p[n++] = OP_END; }
    P.first[c] = (uint16_t)(P.prog[c].p[0] & 2047);
  }
  sort(dem, n_job);
  for (int i = 0; i < n_job; i++) P.job[i] = dem[i].id;
  for (int i = 0; i < ID_PART; i++) {
    if (i < N_TILE) P.slot[i] = use[i].slot;
    P.info[i] = (use[i].readers + use[i].next) | (use[i].next ? I_NEXT : 0);
  }
  if (stats) *stats = st;
  return true;
}

const char* const kPrograms[N_CL / 2] = {
  "NNNNNNNNNF4", "NNUNNNNNNF6", "NUNNJf17NNNF8", "PNNNNNNNNNFe", "PNJ121NNNNNF5", "NNNNNNNNNFa",
  "NNNNNUNNNF6", "NNNNNNNNNF1", "NNNNNNNNNF4", "NUNNNJe26NF8", "PNJ227NNNNFc", "PPNJ717NNNNUNF2",
  "NUNNJc13NNNNF2", "PNNJ325NNNNF3", "NUNUNJ926NFd", "NNNNNNNNNFa", "PNJ421NNNNNFf", "NUNNNJd16NNF7",
  "PNNNNNNNNNF3", "NNUJ618Jb23NFd", "NNNNNNNNNFb", "PNJ517NNNNNNFe", "NNNNNNNNNF0", "PNJ021NNNNNF5",
  "PNNNNNNNNN", "NUNNNJ819NNFb", "PNNNNNNNNNF9", "NNNNNNNNNF0", "PNNNNNNNNNF9", "NNNNNNNNNF1",
  "NNUNNNNNNFf", "NNNNNJa21NFc", "NUNNNNNNNF7",
};

const char* const* bench_programs() {
  return kPrograms;
}

}

extern "C" void kernel_launch(void* const* d_in, const int* in_sizes, int n_in, void* d_out, int out_size) {
  (void)in_sizes; (void)n_in; (void)out_size;
  static EncodeFn fn = nullptr;
  static int n_clusters = 0;
  if (!fn) {
    cudaDriverEntryPointQueryResult qr;
    void* f = nullptr;
    cudaGetDriverEntryPoint("cuTensorMapEncodeTiled", &f, cudaEnableDefault, &qr);
    fn = (EncodeFn)f;
    cudaFuncSetAttribute(fused_kernel, cudaFuncAttributeMaxDynamicSharedMemorySize, SMEM_BYTES);
    cudaLaunchConfig_t cfg = {};
    cfg.gridDim = dim3(132); cfg.blockDim = dim3(384); cfg.dynamicSmemBytes = SMEM_BYTES;
    cudaLaunchAttribute at[1];
    at[0].id = cudaLaunchAttributeClusterDimension; at[0].val.clusterDim.x = 2; at[0].val.clusterDim.y = 1; at[0].val.clusterDim.z = 1;
    cfg.attrs = at; cfg.numAttrs = 1;
    if (cudaOccupancyMaxActiveClusters(&n_clusters, fused_kernel, &cfg) != cudaSuccess || n_clusters < 1) n_clusters = 1;
    (void)cudaGetLastError();
  }
  static Params P;
  const CUtensorMapSwizzle S128 = CU_TENSOR_MAP_SWIZZLE_128B, S64 = CU_TENSOR_MAP_SWIZZLE_64B;
  for (int blk = 0; blk < 2; blk++) {
    void* const* in = d_in + 5 * blk;
    { const cuuint64_t d[] = {kD, kB * kSq}, s[] = {kD * 2}; const cuuint32_t b[] = {64, 128};
      encode(fn, &P.x[blk], in[0], 2, d, s, b, S128); }
    { const cuuint64_t d[] = {64, 8, 3, (cuuint64_t)kB * kH * kSk / 8}, s[] = {kDh * 2, 128, 8 * kDh * 2}; const cuuint32_t b[] = {64, 8, 3, 8};
      encode(fn, &P.k[blk], in[1], 4, d, s, b, S128);
      encode(fn, &P.v[blk], in[2], 4, d, s, b, S128); }
    { const cuuint64_t d[] = {64, kD, kHD / 64}, s[] = {kHD * 2, 128}; const cuuint32_t b[] = {64, 64, 3};
      encode(fn, &P.wq[blk], in[3], 3, d, s, b, S128); }
    { const cuuint64_t d[] = {32, 2, kHD / 8, 4, kD / 32}, s[] = {kD * 2, 8 * kD * 2, 2 * kD * 2, 64}; const cuuint32_t b[] = {32, 2, 4, 4, 5};
      encode(fn, &P.wo[blk], in[4], 5, d, s, b, S64); }
  }
  { const cuuint64_t d[] = {32, kB * kSq, 2 * kD / 32}, s[] = {2 * kD * 2, 64}; const cuuint32_t b[] = {32, 16, 1};
    encode(fn, &P.out, d_out, 3, d, s, b, S64); }

  cudaGetSymbolAddress((void**)&P.g, g_scratch);
  P.dbg = DBG_DEFAULT;
  if (n_clusters >= N_CL && plan(bench_programs(), N_CL / 2, 0, P)) {
    fused_kernel<<<2 * N_CL, 384, SMEM_BYTES>>>(P);
  } else {
    char buf[2 * N_TEAM][16];
    const char* text[2 * N_TEAM];
    for (int i = 0; i < 2 * N_TEAM; i++) { snprintf(buf[i], sizeof(buf[i]), "NNNNNNNNF%x", i / 2); text[i] = buf[i]; }
    for (int phase = 1; phase <= 2; phase++) {
      plan(text, 2 * N_TEAM, phase, P);
      fused_kernel<<<8 * N_TEAM, 384, SMEM_BYTES>>>(P);
    }
  }
}
```

```cpp
#include <cuda_runtime.h>
#include <cuda_bf16.h>
#include <cuda.h>
#include <stdint.h>
#include <stdio.h>

namespace {

constexpr int kB = 8, kSq = 256, kD = 640, kH = 32, kSk = 1024, kDh = 192;
constexpr int kHD = kH * kDh;
constexpr uint32_t RING = 224 * 1024;
constexpr uint32_t SZ_KV = 24576;
constexpr uint32_t SZ_Q = 16384 + 24576;
constexpr uint32_t SZ_O = 16384 + 20480;
constexpr uint32_t SZ_W = 16384 + 40960;
constexpr uint32_t SZ_PARK = 49152;
constexpr uint32_t SZ_OL = SZ_O + 8192;
constexpr int NBAR = 10;
constexpr int EARLY = 3;
#define XTAIL 2
constexpr int TAIL = XTAIL;
constexpr uint32_t KV_CH = 64, KV_SBO = 3072;
constexpr int SMEM_BYTES = RING + 1024 + 1024;
constexpr int N_TEAM = 16, N_CL = 66, MAX_OPS = 24, MAX_EV = 80, N_TILE = N_TEAM * kH, MAX_PARK = 128, ID_PART = N_TILE + MAX_PARK;
enum : uint32_t { OP_END = 0, OP_Q = 1, OP_A = 2, OP_O = 3, F_PARK = 1 << 11,
                  C_WIDE = 1 << 14, C_PEND = 1 << 26, C_SOON = 1 << 28,
                  P_GATE = 1 << 12, P_WIDE = 1 << 11, P_LD = 1 << 12, P_ST = 1 << 21, P_PRE = 1 << 22, I_NEXT = 8, E_ON = 1 << 15, E_FREE = 1 << 14, E_LAST = 1 << 13, E_DRAW = 1 << 12, E_JOB = 1 << 11 };

#define QDRAIN 0x54732710u
#define TRYNS 1500
#define PFN 10
#define QA 1
#define QB 2
#define QC 3
#define NORM_G 2
#define CONV_G 8
#define CONV_0 32
#define SKEW 3
#define PUBNS 100
#define WATNS 100
constexpr uint32_t DBG_DEFAULT = 0x040817;

struct alignas(1024) Scratch {
  unsigned int flag[2047];
  unsigned int ticket;
  uint4 part[N_TEAM * 4 * 2 * 3072];
  uint4 tile[N_TILE * 2 * 3072];
};

struct alignas(64) Params {
  uint16_t first[88];
  Scratch* g;
  uint32_t dbg;
  CUtensorMap x[2], wq[2], k[2], v[2], wo[2], out;
  struct {
    uint32_t c[MAX_OPS];
    uint32_t p[MAX_OPS];
    uint16_t ev[MAX_EV];
  } prog[N_CL];
  uint32_t job[N_CL];
  uint16_t slot[N_TILE];
  uint8_t info[ID_PART];
};

__device__ Scratch g_scratch;

template <int TB, int TA = 0>
__device__ __forceinline__ void wgmma_ss_n64(float (&d)[32], uint64_t da, uint64_t db, int scale_d) {
  asm volatile("{\n.reg .pred p;\nsetp.ne.b32 p, %34, 0;\n"
    "wgmma.mma_async.sync.aligned.m64n64k16.f32.bf16.bf16 {%0, %1, %2, %3, %4, %5, %6, %7, %8, %9, %10, %11, %12, %13, %14, %15, %16, %17, %18, %19, %20, %21, %22, %23, %24, %25, %26, %27, %28, %29, %30, %31}, %32, %33, p, 1, 1, %35, %36;\n}\n"
    : "+f"(d[0]), "+f"(d[1]), "+f"(d[2]), "+f"(d[3]), "+f"(d[4]), "+f"(d[5]), "+f"(d[6]), "+f"(d[7]), "+f"(d[8]), "+f"(d[9]), "+f"(d[10]), "+f"(d[11]), "+f"(d[12]), "+f"(d[13]), "+f"(d[14]), "+f"(d[15]), "+f"(d[16]), "+f"(d[17]), "+f"(d[18]), "+f"(d[19]), "+f"(d[20]), "+f"(d[21]), "+f"(d[22]), "+f"(d[23]), "+f"(d[24]), "+f"(d[25]), "+f"(d[26]), "+f"(d[27]), "+f"(d[28]), "+f"(d[29]), "+f"(d[30]), "+f"(d[31])
    : "l"(da), "l"(db), "r"(scale_d), "n"(TA), "n"(TB));
}
template <int TB>
__device__ __forceinline__ void wgmma_rs_n64(float (&d)[32], uint32_t a0, uint32_t a1, uint32_t a2, uint32_t a3, uint64_t db, int scale_d) {
  asm volatile("{\n.reg .pred p;\nsetp.ne.b32 p, %37, 0;\n"
    "wgmma.mma_async.sync.aligned.m64n64k16.f32.bf16.bf16 {%0, %1, %2, %3, %4, %5, %6, %7, %8, %9, %10, %11, %12, %13, %14, %15, %16, %17, %18, %19, %20, %21, %22, %23, %24, %25, %26, %27, %28, %29, %30, %31}, {%32, %33, %34, %35}, %36, p, 1, 1, %38;\n}\n"
    : "+f"(d[0]), "+f"(d[1]), "+f"(d[2]), "+f"(d[3]), "+f"(d[4]), "+f"(d[5]), "+f"(d[6]), "+f"(d[7]), "+f"(d[8]), "+f"(d[9]), "+f"(d[10]), "+f"(d[11]), "+f"(d[12]), "+f"(d[13]), "+f"(d[14]), "+f"(d[15]), "+f"(d[16]), "+f"(d[17]), "+f"(d[18]), "+f"(d[19]), "+f"(d[20]), "+f"(d[21]), "+f"(d[22]), "+f"(d[23]), "+f"(d[24]), "+f"(d[25]), "+f"(d[26]), "+f"(d[27]), "+f"(d[28]), "+f"(d[29]), "+f"(d[30]), "+f"(d[31])
    : "r"(a0), "r"(a1), "r"(a2), "r"(a3), "l"(db), "r"(scale_d), "n"(TB));
}
template <int TB, int TA = 0>
__device__ __forceinline__ void wgmma_ss_n160(float (&d)[80], uint64_t da, uint64_t db, int scale_d) {
  asm volatile("{\n.reg .pred p;\nsetp.ne.b32 p, %82, 0;\n"
    "wgmma.mma_async.sync.aligned.m64n160k16.f32.bf16.bf16 {%0, %1, %2, %3, %4, %5, %6, %7, %8, %9, %10, %11, %12, %13, %14, %15, %16, %17, %18, %19, %20, %21, %22, %23, %24, %25, %26, %27, %28, %29, %30, %31, %32, %33, %34, %35, %36, %37, %38, %39, %40, %41, %42, %43, %44, %45, %46, %47, %48, %49, %50, %51, %52, %53, %54, %55, %56, %57, %58, %59, %60, %61, %62, %63, %64, %65, %66, %67, %68, %69, %70, %71, %72, %73, %74, %75, %76, %77, %78, %79}, %80, %81, p, 1, 1, %83, %84;\n}\n"
    : "+f"(d[0]), "+f"(d[1]), "+f"(d[2]), "+f"(d[3]), "+f"(d[4]), "+f"(d[5]), "+f"(d[6]), "+f"(d[7]), "+f"(d[8]), "+f"(d[9]), "+f"(d[10]), "+f"(d[11]), "+f"(d[12]), "+f"(d[13]), "+f"(d[14]), "+f"(d[15]), "+f"(d[16]), "+f"(d[17]), "+f"(d[18]), "+f"(d[19]), "+f"(d[20]), "+f"(d[21]), "+f"(d[22]), "+f"(d[23]), "+f"(d[24]), "+f"(d[25]), "+f"(d[26]), "+f"(d[27]), "+f"(d[28]), "+f"(d[29]), "+f"(d[30]), "+f"(d[31]), "+f"(d[32]), "+f"(d[33]), "+f"(d[34]), "+f"(d[35]), "+f"(d[36]), "+f"(d[37]), "+f"(d[38]), "+f"(d[39]), "+f"(d[40]), "+f"(d[41]), "+f"(d[42]), "+f"(d[43]), "+f"(d[44]), "+f"(d[45]), "+f"(d[46]), "+f"(d[47]), "+f"(d[48]), "+f"(d[49]), "+f"(d[50]), "+f"(d[51]), "+f"(d[52]), "+f"(d[53]), "+f"(d[54]), "+f"(d[55]), "+f"(d[56]), "+f"(d[57]), "+f"(d[58]), "+f"(d[59]), "+f"(d[60]), "+f"(d[61]), "+f"(d[62]), "+f"(d[63]), "+f"(d[64]), "+f"(d[65]), "+f"(d[66]), "+f"(d[67]), "+f"(d[68]), "+f"(d[69]), "+f"(d[70]), "+f"(d[71]), "+f"(d[72]), "+f"(d[73]), "+f"(d[74]), "+f"(d[75]), "+f"(d[76]), "+f"(d[77]), "+f"(d[78]), "+f"(d[79])
    : "l"(da), "l"(db), "r"(scale_d), "n"(TA), "n"(TB));
}
template <int TB>
__device__ __forceinline__ void wgmma_rs_n160(float (&d)[80], uint32_t a0, uint32_t a1, uint32_t a2, uint32_t a3, uint64_t db, int scale_d) {
  asm volatile("{\n.reg .pred p;\nsetp.ne.b32 p, %85, 0;\n"
    "wgmma.mma_async.sync.aligned.m64n160k16.f32.bf16.bf16 {%0, %1, %2, %3, %4, %5, %6, %7, %8, %9, %10, %11, %12, %13, %14, %15, %16, %17, %18, %19, %20, %21, %22, %23, %24, %25, %26, %27, %28, %29, %30, %31, %32, %33, %34, %35, %36, %37, %38, %39, %40, %41, %42, %43, %44, %45, %46, %47, %48, %49, %50, %51, %52, %53, %54, %55, %56, %57, %58, %59, %60, %61, %62, %63, %64, %65, %66, %67, %68, %69, %70, %71, %72, %73, %74, %75, %76, %77, %78, %79}, {%80, %81, %82, %83}, %84, p, 1, 1, %86;\n}\n"
    : "+f"(d[0]), "+f"(d[1]), "+f"(d[2]), "+f"(d[3]), "+f"(d[4]), "+f"(d[5]), "+f"(d[6]), "+f"(d[7]), "+f"(d[8]), "+f"(d[9]), "+f"(d[10]), "+f"(d[11]), "+f"(d[12]), "+f"(d[13]), "+f"(d[14]), "+f"(d[15]), "+f"(d[16]), "+f"(d[17]), "+f"(d[18]), "+f"(d[19]), "+f"(d[20]), "+f"(d[21]), "+f"(d[22]), "+f"(d[23]), "+f"(d[24]), "+f"(d[25]), "+f"(d[26]), "+f"(d[27]), "+f"(d[28]), "+f"(d[29]), "+f"(d[30]), "+f"(d[31]), "+f"(d[32]), "+f"(d[33]), "+f"(d[34]), "+f"(d[35]), "+f"(d[36]), "+f"(d[37]), "+f"(d[38]), "+f"(d[39]), "+f"(d[40]), "+f"(d[41]), "+f"(d[42]), "+f"(d[43]), "+f"(d[44]), "+f"(d[45]), "+f"(d[46]), "+f"(d[47]), "+f"(d[48]), "+f"(d[49]), "+f"(d[50]), "+f"(d[51]), "+f"(d[52]), "+f"(d[53]), "+f"(d[54]), "+f"(d[55]), "+f"(d[56]), "+f"(d[57]), "+f"(d[58]), "+f"(d[59]), "+f"(d[60]), "+f"(d[61]), "+f"(d[62]), "+f"(d[63]), "+f"(d[64]), "+f"(d[65]), "+f"(d[66]), "+f"(d[67]), "+f"(d[68]), "+f"(d[69]), "+f"(d[70]), "+f"(d[71]), "+f"(d[72]), "+f"(d[73]), "+f"(d[74]), "+f"(d[75]), "+f"(d[76]), "+f"(d[77]), "+f"(d[78]), "+f"(d[79])
    : "r"(a0), "r"(a1), "r"(a2), "r"(a3), "l"(db), "r"(scale_d), "n"(TB));
}
template <int TB, int TA = 0>
__device__ __forceinline__ void wgmma_ss_n192(float (&d)[96], uint64_t da, uint64_t db, int scale_d) {
  asm volatile("{\n.reg .pred p;\nsetp.ne.b32 p, %98, 0;\n"
    "wgmma.mma_async.sync.aligned.m64n192k16.f32.bf16.bf16 {%0, %1, %2, %3, %4, %5, %6, %7, %8, %9, %10, %11, %12, %13, %14, %15, %16, %17, %18, %19, %20, %21, %22, %23, %24, %25, %26, %27, %28, %29, %30, %31, %32, %33, %34, %35, %36, %37, %38, %39, %40, %41, %42, %43, %44, %45, %46, %47, %48, %49, %50, %51, %52, %53, %54, %55, %56, %57, %58, %59, %60, %61, %62, %63, %64, %65, %66, %67, %68, %69, %70, %71, %72, %73, %74, %75, %76, %77, %78, %79, %80, %81, %82, %83, %84, %85, %86, %87, %88, %89, %90, %91, %92, %93, %94, %95}, %96, %97, p, 1, 1, %99, %100;\n}\n"
    : "+f"(d[0]), "+f"(d[1]), "+f"(d[2]), "+f"(d[3]), "+f"(d[4]), "+f"(d[5]), "+f"(d[6]), "+f"(d[7]), "+f"(d[8]), "+f"(d[9]), "+f"(d[10]), "+f"(d[11]), "+f"(d[12]), "+f"(d[13]), "+f"(d[14]), "+f"(d[15]), "+f"(d[16]), "+f"(d[17]), "+f"(d[18]), "+f"(d[19]), "+f"(d[20]), "+f"(d[21]), "+f"(d[22]), "+f"(d[23]), "+f"(d[24]), "+f"(d[25]), "+f"(d[26]), "+f"(d[27]), "+f"(d[28]), "+f"(d[29]), "+f"(d[30]), "+f"(d[31]), "+f"(d[32]), "+f"(d[33]), "+f"(d[34]), "+f"(d[35]), "+f"(d[36]), "+f"(d[37]), "+f"(d[38]), "+f"(d[39]), "+f"(d[40]), "+f"(d[41]), "+f"(d[42]), "+f"(d[43]), "+f"(d[44]), "+f"(d[45]), "+f"(d[46]), "+f"(d[47]), "+f"(d[48]), "+f"(d[49]), "+f"(d[50]), "+f"(d[51]), "+f"(d[52]), "+f"(d[53]), "+f"(d[54]), "+f"(d[55]), "+f"(d[56]), "+f"(d[57]), "+f"(d[58]), "+f"(d[59]), "+f"(d[60]), "+f"(d[61]), "+f"(d[62]), "+f"(d[63]), "+f"(d[64]), "+f"(d[65]), "+f"(d[66]), "+f"(d[67]), "+f"(d[68]), "+f"(d[69]), "+f"(d[70]), "+f"(d[71]), "+f"(d[72]), "+f"(d[73]), "+f"(d[74]), "+f"(d[75]), "+f"(d[76]), "+f"(d[77]), "+f"(d[78]), "+f"(d[79]), "+f"(d[80]), "+f"(d[81]), "+f"(d[82]), "+f"(d[83]), "+f"(d[84]), "+f"(d[85]), "+f"(d[86]), "+f"(d[87]), "+f"(d[88]), "+f"(d[89]), "+f"(d[90]), "+f"(d[91]), "+f"(d[92]), "+f"(d[93]), "+f"(d[94]), "+f"(d[95])
    : "l"(da), "l"(db), "r"(scale_d), "n"(TA), "n"(TB));
}
template <int TB>
__device__ __forceinline__ void wgmma_rs_n192(float (&d)[96], uint32_t a0, uint32_t a1, uint32_t a2, uint32_t a3, uint64_t db, int scale_d) {
  asm volatile("{\n.reg .pred p;\nsetp.ne.b32 p, %101, 0;\n"
    "wgmma.mma_async.sync.aligned.m64n192k16.f32.bf16.bf16 {%0, %1, %2, %3, %4, %5, %6, %7, %8, %9, %10, %11, %12, %13, %14, %15, %16, %17, %18, %19, %20, %21, %22, %23, %24, %25, %26, %27, %28, %29, %30, %31, %32, %33, %34, %35, %36, %37, %38, %39, %40, %41, %42, %43, %44, %45, %46, %47, %48, %49, %50, %51, %52, %53, %54, %55, %56, %57, %58, %59, %60, %61, %62, %63, %64, %65, %66, %67, %68, %69, %70, %71, %72, %73, %74, %75, %76, %77, %78, %79, %80, %81, %82, %83, %84, %85, %86, %87, %88, %89, %90, %91, %92, %93, %94, %95}, {%96, %97, %98, %99}, %100, p, 1, 1, %102;\n}\n"
    : "+f"(d[0]), "+f"(d[1]), "+f"(d[2]), "+f"(d[3]), "+f"(d[4]), "+f"(d[5]), "+f"(d[6]), "+f"(d[7]), "+f"(d[8]), "+f"(d[9]), "+f"(d[10]), "+f"(d[11]), "+f"(d[12]), "+f"(d[13]), "+f"(d[14]), "+f"(d[15]), "+f"(d[16]), "+f"(d[17]), "+f"(d[18]), "+f"(d[19]), "+f"(d[20]), "+f"(d[21]), "+f"(d[22]), "+f"(d[23]), "+f"(d[24]), "+f"(d[25]), "+f"(d[26]), "+f"(d[27]), "+f"(d[28]), "+f"(d[29]), "+f"(d[30]), "+f"(d[31]), "+f"(d[32]), "+f"(d[33]), "+f"(d[34]), "+f"(d[35]), "+f"(d[36]), "+f"(d[37]), "+f"(d[38]), "+f"(d[39]), "+f"(d[40]), "+f"(d[41]), "+f"(d[42]), "+f"(d[43]), "+f"(d[44]), "+f"(d[45]), "+f"(d[46]), "+f"(d[47]), "+f"(d[48]), "+f"(d[49]), "+f"(d[50]), "+f"(d[51]), "+f"(d[52]), "+f"(d[53]), "+f"(d[54]), "+f"(d[55]), "+f"(d[56]), "+f"(d[57]), "+f"(d[58]), "+f"(d[59]), "+f"(d[60]), "+f"(d[61]), "+f"(d[62]), "+f"(d[63]), "+f"(d[64]), "+f"(d[65]), "+f"(d[66]), "+f"(d[67]), "+f"(d[68]), "+f"(d[69]), "+f"(d[70]), "+f"(d[71]), "+f"(d[72]), "+f"(d[73]), "+f"(d[74]), "+f"(d[75]), "+f"(d[76]), "+f"(d[77]), "+f"(d[78]), "+f"(d[79]), "+f"(d[80]), "+f"(d[81]), "+f"(d[82]), "+f"(d[83]), "+f"(d[84]), "+f"(d[85]), "+f"(d[86]), "+f"(d[87]), "+f"(d[88]), "+f"(d[89]), "+f"(d[90]), "+f"(d[91]), "+f"(d[92]), "+f"(d[93]), "+f"(d[94]), "+f"(d[95])
    : "r"(a0), "r"(a1), "r"(a2), "r"(a3), "l"(db), "r"(scale_d), "n"(TB));
}

__device__ __forceinline__ uint32_t smem_u32(const void* p) { return (uint32_t)__cvta_generic_to_shared(p); }
__device__ __forceinline__ void wg_fence() { asm volatile("wgmma.fence.sync.aligned;" ::: "memory"); }
__device__ __forceinline__ void wg_commit() { asm volatile("wgmma.commit_group.sync.aligned;" ::: "memory"); }
template <int N> __device__ __forceinline__ void wg_wait() { asm volatile("wgmma.wait_group.sync.aligned %0;" ::"n"(N) : "memory"); }
__device__ __forceinline__ void sched_fence(uint32_t& keep, bool never) {
  asm volatile("{\n.reg .pred p;\nsetp.ne.b32 p, %1, 0;\n@p mov.u32 %0, %%clock;\n}\n" : "+r"(keep) : "r"((int)never) : "memory");
}
template <int N> __device__ __forceinline__ void fence_regs(float (&r)[N]) {
#pragma unroll
  for (int i = 0; i < N; i++) asm volatile("" : "+f"(r[i])::"memory");
}
template <int N> __device__ __forceinline__ void undefine(float (&r)[N]) {
#pragma unroll
  for (int i = 0; i < N; i++) asm volatile("" : "=f"(r[i]));
}
template <int N> __device__ __forceinline__ void fence_regs(uint32_t (&r)[N]) {
#pragma unroll
  for (int i = 0; i < N; i++) asm volatile("" : "+r"(r[i])::"memory");
}
__device__ __forceinline__ uint64_t mk_desc(uint32_t a16, uint32_t lbo, uint32_t sbo, uint32_t swz) {
  uint64_t d;
  asm("mov.b64 %0, {%1, %2};" : "=l"(d) : "r"(a16 + ((lbo >> 4) << 16)), "r"((sbo >> 4) | (swz << 30)));
  return d;
}
__device__ __forceinline__ void mbar_init(uint32_t bar, uint32_t cnt) {
  asm volatile("mbarrier.init.shared::cta.b64 [%0], %1;" ::"r"(bar), "r"(cnt) : "memory");
}
__device__ __forceinline__ void mbar_expect(uint32_t bar, uint32_t tx) {
  asm volatile("mbarrier.arrive.expect_tx.shared::cta.b64 _, [%0], %1;" ::"r"(bar), "r"(tx) : "memory");
}
__device__ __forceinline__ bool mbar_test(uint32_t bar, uint32_t ph) {
  uint32_t ok;
  asm volatile("{\n.reg .pred p;\nmbarrier.test_wait.parity.shared::cta.b64 p, [%1], %2;\nselp.u32 %0, 1, 0, p;\n}\n"
               : "=r"(ok) : "r"(bar), "r"(ph) : "memory");
  return ok;
}
__device__ __forceinline__ bool mbar_try(uint32_t bar, uint32_t ph, uint32_t ns) {
  uint32_t ok;
  asm volatile("{\n.reg .pred p;\nmbarrier.try_wait.parity.shared::cta.b64 p, [%1], %2, %3;\nselp.u32 %0, 1, 0, p;\n}\n"
               : "=r"(ok) : "r"(bar), "r"(ph), "r"(ns) : "memory");
  return ok;
}
__device__ __forceinline__ void mbar_wait(uint32_t bar, uint32_t ph) {
  asm volatile("{\n.reg .pred p;\n.reg .u32 n;\nmov.u32 n, 0;\n"
               "LOOP:\nmbarrier.try_wait.parity.shared::cta.b64 p, [%0], %1;\n@p bra DONE;\n"
               "add.u32 n, n, 1;\nsetp.lt.u32 p, n, 0x1000000;\n@p bra LOOP;\ntrap;\n"
               "DONE:\n}\n" ::"r"(bar), "r"(ph) : "memory");
}
template <int NS> __device__ __forceinline__ void mbar_wait_slow(uint32_t bar, uint32_t ph) {
  asm volatile("{\n.reg .pred p;\n.reg .u32 n;\nmov.u32 n, 0;\n"
               "LOOP:\nmbarrier.test_wait.parity.shared::cta.b64 p, [%0], %1;\n@p bra DONE;\n"
               "nanosleep.u32 %2;\nadd.u32 n, n, 1;\nsetp.lt.u32 p, n, 0x400000;\n@p bra LOOP;\ntrap;\n"
               "DONE:\n}\n" ::"r"(bar), "r"(ph), "n"(NS) : "memory");
}
__device__ __forceinline__ void mbar_arrive_cluster_if(bool on, uint32_t addr) {
  asm volatile("{\n.reg .pred p;\nsetp.ne.b32 p, %1, 0;\n@p mbarrier.arrive.shared::cluster.b64 _, [%0];\n}\n" ::"r"(addr), "r"((int)on) : "memory");
}
__device__ __forceinline__ void tma2d(uint32_t dst, const CUtensorMap* m, uint32_t bar, int c0, int c1) {
  asm volatile("cp.async.bulk.tensor.2d.shared::cluster.global.mbarrier::complete_tx::bytes [%0], [%1, {%3, %4}], [%2];"
               ::"r"(dst), "l"(m), "r"(bar), "r"(c0), "r"(c1) : "memory");
}
__device__ __forceinline__ void tma3d(uint32_t dst, const CUtensorMap* m, uint32_t bar, int c0, int c1, int c2) {
  asm volatile("cp.async.bulk.tensor.3d.shared::cluster.global.mbarrier::complete_tx::bytes [%0], [%1, {%3, %4, %5}], [%2];"
               ::"r"(dst), "l"(m), "r"(bar), "r"(c0), "r"(c1), "r"(c2) : "memory");
}
__device__ __forceinline__ void tma3d_mc(uint32_t dst, const CUtensorMap* m, uint32_t bar, int c0, int c1, int c2) {
  asm volatile("cp.async.bulk.tensor.3d.shared::cluster.global.mbarrier::complete_tx::bytes.multicast::cluster"
               " [%0], [%1, {%3, %4, %5}], [%2], %6;"
               ::"r"(dst), "l"(m), "r"(bar), "r"(c0), "r"(c1), "r"(c2), "h"((uint16_t)3) : "memory");
}
__device__ __forceinline__ void tma3d_store(const CUtensorMap* m, uint32_t src, int c0, int c1, int c2) {
  asm volatile("cp.async.bulk.tensor.3d.global.shared::cta.bulk_group [%0, {%2, %3, %4}], [%1];"
               ::"l"(m), "r"(src), "r"(c0), "r"(c1), "r"(c2) : "memory");
}
__device__ __forceinline__ void bar_sync(int id, int n) { asm volatile("bar.sync %0, %1;" ::"r"(id), "r"(n) : "memory"); }
__device__ __forceinline__ uint32_t pack_bf16(float lo, float hi) {
  uint32_t r;
  asm("cvt.rn.bf16x2.f32 %0, %1, %2;" : "=r"(r) : "f"(hi), "f"(lo));
  return r;
}
__device__ __forceinline__ float ex2(float x) {
  float y;
  asm("ex2.approx.ftz.f32 %0, %1;" : "=f"(y) : "f"(x));
  return y;
}
__device__ __forceinline__ float rcp(float x) {
  float y;
  asm("rcp.approx.ftz.f32 %0, %1;" : "=f"(y) : "f"(x));
  return y;
}
__device__ __forceinline__ void stsm4(uint32_t addr, uint32_t a, uint32_t b, uint32_t c, uint32_t d) {
  asm volatile("stmatrix.sync.aligned.m8n8.x4.shared.b16 [%0], {%1, %2, %3, %4};" ::"r"(addr), "r"(a), "r"(b), "r"(c), "r"(d) : "memory");
}

__device__ __forceinline__ void tma4d_mc_hint(uint32_t dst, const CUtensorMap* m, uint32_t bar, int c3, uint64_t pol) {
  asm volatile("cp.async.bulk.tensor.4d.shared::cluster.global.mbarrier::complete_tx::bytes.multicast::cluster.L2::cache_hint"
               " [%0], [%1, {%3, %3, %3, %4}], [%2], %5, %6;"
               ::"r"(dst), "l"(m), "r"(bar), "r"(0), "r"(c3), "h"((uint16_t)3), "l"(pol) : "memory");
}
__device__ __forceinline__ void tma5d_mc(uint32_t dst, const CUtensorMap* m, uint32_t bar, int c2, int c4) {
  asm volatile("cp.async.bulk.tensor.5d.shared::cluster.global.mbarrier::complete_tx::bytes.multicast::cluster"
               " [%0], [%1, {%3, %3, %4, %3, %5}], [%2], %6;"
               ::"r"(dst), "l"(m), "r"(bar), "r"(0), "r"(c2), "r"(c4), "h"((uint16_t)3) : "memory");
}
__device__ __forceinline__ void bulk_load_hint(uint32_t dst, const void* src, uint32_t bytes, uint32_t bar, uint64_t pol) {
  asm volatile("cp.async.bulk.shared::cluster.global.mbarrier::complete_tx::bytes.L2::cache_hint [%0], [%1], %2, [%3], %4;"
               ::"r"(dst), "l"(src), "r"(bytes), "r"(bar), "l"(pol) : "memory");
}
__device__ __forceinline__ void stg128_hint(void* p, uint32_t a, uint32_t b, uint32_t c, uint32_t d, uint64_t pol) {
  asm volatile("st.global.L2::cache_hint.v4.b32 [%0], {%1, %2, %3, %4}, %5;" ::"l"(p), "r"(a), "r"(b), "r"(c), "r"(d), "l"(pol) : "memory");
}
__device__ __forceinline__ void stg2_if(bool on, void* p, uint32_t a, uint32_t b, uint32_t c, uint32_t d, uint32_t e, uint32_t f,
                                        uint32_t g, uint32_t h, uint64_t pol) {
  asm volatile("{\n.reg .pred p;\nsetp.ne.b32 p, %10, 0;\n"
               "@p st.global.L2::cache_hint.v4.b32 [%0], {%1, %2, %3, %4}, %9;\n"
               "@p st.global.L2::cache_hint.v4.b32 [%0 + 512], {%5, %6, %7, %8}, %9;\n}\n"
               ::"l"(p), "r"(a), "r"(b), "r"(c), "r"(d), "r"(e), "r"(f), "r"(g), "r"(h), "l"(pol), "r"((int)on) : "memory");
}
__device__ __forceinline__ uint64_t make_policy(bool first) {
  uint64_t pf, pn;
  asm("createpolicy.fractional.L2::evict_first.b64 %0, 1.0;" : "=l"(pf));
  asm("createpolicy.fractional.L2::evict_normal.b64 %0, 1.0;" : "=l"(pn));
  return first ? pf : pn;
}
__device__ __forceinline__ bool elect() {
  uint32_t ok;
  asm volatile("{\n.reg .pred p;\nelect.sync _|p, 0xffffffff;\nselp.u32 %0, 1, 0, p;\n}\n" : "=r"(ok));
  return ok;
}
__device__ __forceinline__ void mbar_arrive(uint32_t bar) {
  asm volatile("mbarrier.arrive.shared::cta.b64 _, [%0];" ::"r"(bar) : "memory");
}
__device__ __forceinline__ void mbar_arrive_if(bool on, uint32_t bar) {
  asm volatile("{\n.reg .pred p;\nsetp.ne.b32 p, %1, 0;\n@p mbarrier.arrive.shared::cta.b64 _, [%0];\n}\n" ::"r"(bar), "r"((int)on) : "memory");
}
__device__ __forceinline__ void stg128(void* p, uint32_t a, uint32_t b, uint32_t c, uint32_t d) {
  asm volatile("st.global.v4.b32 [%0], {%1, %2, %3, %4};" ::"l"(p), "r"(a), "r"(b), "r"(c), "r"(d) : "memory");
}
__device__ __forceinline__ void lds2_if(bool on, uint32_t p, uint32_t (&t)[8]) {
  asm volatile("{\n.reg .pred p;\nsetp.ne.b32 p, %9, 0;\n@p ld.shared.v4.b32 {%0, %1, %2, %3}, [%8];\n@p ld.shared.v4.b32 {%4, %5, %6, %7}, [%8 + 512];\n}\n"
               : "+r"(t[0]), "+r"(t[1]), "+r"(t[2]), "+r"(t[3]), "+r"(t[4]), "+r"(t[5]), "+r"(t[6]), "+r"(t[7]) : "r"(p), "r"((int)on) : "memory");
}
__device__ __forceinline__ void lds128(uint32_t p, uint32_t& a, uint32_t& b, uint32_t& c, uint32_t& d) {
  asm volatile("ld.shared.v4.b32 {%0, %1, %2, %3}, [%4];" : "=r"(a), "=r"(b), "=r"(c), "=r"(d) : "r"(p) : "memory");
}
template <class T> __device__ __forceinline__ T* ptr_add(T* base, uint32_t bytes) {
  T* r;
  asm("{\n.reg .u32 lo, hi;\nmov.b64 {lo, hi}, %1;\nadd.cc.u32 lo, lo, %2;\naddc.u32 hi, hi, 0;\nmov.b64 %0, {lo, hi};\n}\n" : "=l"(r) : "l"(base), "r"(bytes));
  return r;
}
__device__ __forceinline__ uint32_t lds32(uint32_t p) {
  uint32_t v;
  asm volatile("ld.volatile.shared.u32 %0, [%1];" : "=r"(v) : "r"(p) : "memory");
  return v;
}
__device__ __forceinline__ uint32_t flag_get(const unsigned int* p) {
  uint32_t v;
  asm volatile("ld.acquire.gpu.global.u32 %0, [%1];" : "=r"(v) : "l"(p) : "memory");
  return v;
}
__device__ __forceinline__ uint32_t wait_word(uint32_t p, uint32_t target) {
  uint32_t v;
  asm volatile("{\n.reg .pred p;\n.reg .u32 n;\nmov.u32 n, 0;\n"
               "LOOP:\nld.acquire.cta.shared.u32 %0, [%1];\nsetp.ge.u32 p, %0, %2;\n@p bra DONE;\n"
               "nanosleep.u32 %3;\nadd.u32 n, n, 1;\nsetp.lt.u32 p, n, 0x400000;\n@p bra LOOP;\ntrap;\n"
               "DONE:\n}\n" : "=r"(v) : "r"(p), "r"(target), "n"(400) : "memory");
  return v;
}
__device__ __forceinline__ void flag_set(unsigned int* p, uint32_t v) {
  asm volatile("st.release.gpu.global.u32 [%0], %1;" ::"l"(p), "r"(v) : "memory");
}
__device__ __forceinline__ void flag_dec(unsigned int* p) {
  asm volatile("red.relaxed.gpu.global.add.u32 [%0], 0xffffffff;" ::"l"(p) : "memory");
}

struct Cursor {
  int bi;
  uint32_t ph;
  __device__ __forceinline__ void next() {
    if (++bi == NBAR) { bi = 0; ph ^= 1; }
  }
};

constexpr float kScaleLog2 = 0.07216878364870322f * 1.4426950408889634f;
constexpr float kSumLimit = 1048576.0f;

__global__ void __cluster_dims__(2, 1, 1) __launch_bounds__(384, 1)
fused_kernel(const __grid_constant__ Params P) {
  extern __shared__ uint8_t smem_raw[];
  const uint32_t sbase = (smem_u32(smem_raw) + 1023) & ~1023u;
  const uint32_t full0 = sbase + RING, empty0 = full0 + 8 * NBAR, odone0 = empty0 + 8 * NBAR, ev0 = odone0 + 8 * MAX_OPS;
  const uint32_t progress = ev0 + 8 * MAX_EV, jobw = progress + 4;
  const uint32_t rank = blockIdx.x & 1;
  const int role = blockIdx.x >> 1;
  const int wid = __shfl_sync(0xffffffffu, (int)(threadIdx.x >> 5), 0);
  const int wg = wid >> 2;

  if (wid < 8) {
    if (elect()) {
#pragma unroll
      for (int j = 0; j < 16; j++) {
        const int i = EARLY + 16 * wid + j;
        if (i < 2 * NBAR + MAX_OPS + MAX_EV) mbar_init(full0 + 8 * i, i < NBAR ? 1 : i < 2 * NBAR ? 16 : i < 2 * NBAR + MAX_OPS ? 8 : 1);
      }
      if (wid == 7) asm volatile("st.shared.v2.u32 [%0], {0, 0};\nfence.acq_rel.cta;" ::"r"(progress) : "memory");
      asm volatile("fence.mbarrier_init.release.cluster;" ::: "memory");
    }
  } else if (wid == 8) {
    const uint32_t op0 = P.first[role];
    if (elect()) {
#pragma unroll
      for (int k = 0; k < EARLY; k++) mbar_init(full0 + 8 * k, 1);
      asm volatile("fence.mbarrier_init.release.cluster;" ::: "memory");
      const int blk = (op0 >> 10) & 1;
      if ((op0 & 3) == OP_Q) {
#pragma unroll
        for (int k = 0; k < EARLY; k++) {
          mbar_expect(full0 + 8 * k, SZ_Q);
          tma2d(sbase + k * SZ_Q, &P.x[blk], full0 + 8 * k, 64 * k, ((op0 >> 7) & 7) * kSq + rank * 128);
          tma3d(sbase + k * SZ_Q + 16384, &P.wq[blk], full0 + 8 * k, 0, 64 * k, 3 * ((op0 >> 2) & 31));
        }
      }
      asm volatile("prefetch.tensormap [%0];" ::"l"(rank ? &P.v[blk] : &P.k[blk]) : "memory");
    }
  }
  __syncwarp();
  asm volatile("barrier.cluster.arrive.relaxed.aligned;\nbarrier.cluster.wait.aligned;" ::: "memory");

  if (wg < 2) {
    asm volatile("setmaxnreg.inc.sync.aligned.u32 240;");
    const uint32_t* prog = P.prog[role].c;
    const int lane = threadIdx.x & 31, warp = wid & 3;
    uint32_t empty_rem;
    asm volatile("mapa.shared::cluster.u32 %0, %1, %2;" : "=r"(empty_rem) : "r"(empty0), "r"(lane & 1));
    auto release = [&](int slot) { mbar_arrive_cluster_if(lane < 2, empty_rem + 8 * slot); };
    Cursor r{0, 0};
    const uint32_t ring16 = (sbase & 0x3FFFF) >> 4;
    uint32_t cur = ring16;
    bool rdy0 = false, rdy1 = false;
    auto probe1 = [&]() { rdy0 = mbar_test(full0 + 8 * r.bi, r.ph); };
    auto probe2 = [&]() {
      Cursor n = r;
      rdy0 = mbar_test(full0 + 8 * n.bi, n.ph);
      n.next();
      rdy1 = mbar_test(full0 + 8 * n.bi, n.ph);
    };
    auto take = [&](bool rdy, uint32_t bytes, uint32_t& addr) {
      const int bi = r.bi;
      if (__builtin_expect(!__all_sync(0xffffffffu, rdy), 0)) mbar_wait(full0 + 8 * r.bi, r.ph);
      r.next();
      if (cur > ring16 + ((RING - bytes) >> 4)) cur = ring16;
      addr = cur;
      cur += bytes >> 4;
      return bi;
    };
    uint32_t keep = lane;
    const bool never = P.dbg == 0xffffffffu;
    uint32_t q[48];
#pragma unroll
    for (int i = 0; i < 48; i++) q[i] = 0;
    const int row = wg * 64 + warp * 16 + (lane >> 2);
    const int img0 = row * 4 + ((lane & 3) ^ ((row >> 1) & 3));
    uint4* pend = nullptr;
    bool pend_any = false;
    uint64_t spol;
    int pc = 0;
    auto slab = [&](int c, int i0) {
#pragma unroll
      for (int i = i0; i < 6; i++)
        stg2_if(c == i, pend + i * 512, q[8 * i], q[8 * i + 1], q[8 * i + 2], q[8 * i + 3],
                q[8 * i + 4], q[8 * i + 5], q[8 * i + 6], q[8 * i + 7], spol);
    };
    auto drain = [&](int c) {
      if (!pend_any || c >= 6) return;
      slab(c, 0);
      if (c == 5) {
        __syncwarp();
        mbar_arrive_if(lane == 0, odone0 - 8 + 8 * pc);
      }
    };

    for (;; pc++) {
      uint32_t op = prog[pc];
      const int type = op & 3;
      auto enter = [&]() {
        r.bi = (op >> 15) & 15; r.ph = (op >> 19) & 1; cur = ring16 + (((op >> 20) & 63) << 8);
      };
      enter();
      pend_any = op & C_PEND;
      spol = make_policy(!(op & C_SOON));
      uint32_t job = 0;
      if ((op & (3 | C_WIDE)) == OP_O) job = __shfl_sync(0xffffffffu, wait_word(jobw, 1), 0);
      if (type == OP_END || job == OP_O) {
#pragma unroll 1
        for (int c = 0; c < 6; c++) drain(c);
        asm volatile("barrier.cluster.arrive.relaxed;" ::: "memory");
        break;
      }
      {
        float s[32], o[96];
        uint32_t ad0;
        int bi0, sk1;
        uint32_t pa[16], pb[16];
        float mc0, mc1, l0, l1;
        bool shifted;
        uint32_t nop;
        auto expo = [&](float (&s)[32], uint32_t (&pout)[16], float& b0, float& b1, bool shift, auto mid) {
          float c0, c1;
#pragma unroll
          for (int i = 0; i < 8; i++) {
            const float e0 = ex2(shift ? s[4 * i] - mc0 : s[4 * i]), e1 = ex2(shift ? s[4 * i + 1] - mc0 : s[4 * i + 1]);
            const float e2 = ex2(shift ? s[4 * i + 2] - mc1 : s[4 * i + 2]), e3 = ex2(shift ? s[4 * i + 3] - mc1 : s[4 * i + 3]);
            if (i) { b0 += e0; c0 += e1; b1 += e2; c1 += e3; } else { b0 = e0; c0 = e1; b1 = e2; c1 = e3; }
            pout[2 * i] = pack_bf16(e0, e1); pout[2 * i + 1] = pack_bf16(e2, e3);
            if (i & 1) mid(i >> 1);
          }
          b0 += c0; b1 += c1;
        };
        auto rowmax = [&](float (&s)[32], float& m0, float& m1) {
          m0 = fmaxf(s[0], s[1]); m1 = fmaxf(s[2], s[3]);
#pragma unroll
          for (int i = 1; i < 8; i++) { m0 = fmaxf(m0, fmaxf(s[4 * i], s[4 * i + 1])); m1 = fmaxf(m1, fmaxf(s[4 * i + 2], s[4 * i + 3])); }
          m0 = fmaxf(m0, __shfl_xor_sync(0xffffffffu, m0, 1)); m1 = fmaxf(m1, __shfl_xor_sync(0xffffffffu, m1, 1));
          m0 = fmaxf(m0, __shfl_xor_sync(0xffffffffu, m0, 2)); m1 = fmaxf(m1, __shfl_xor_sync(0xffffffffu, m1, 2));
        };
        auto first = [&](float (&s)[32], int sk0, auto mid) {
          fence_regs(s);
          release(sk0);
          mc0 = 0.f; mc1 = 0.f;
          expo(s, pa, l0, l1, false, mid);
          shifted = __any_sync(0xffffffffu, !(fmaxf(l0, l1) <= kSumLimit && fminf(l0, l1) >= 1.f / kSumLimit));
          if (shifted) {
            rowmax(s, mc0, mc1);
            expo(s, pa, l0, l1, true, [](int) {});
          }
        };
        auto qk = [&](float (&s)[32], uint32_t ak, int k0 = 0, int k1 = 12) {
#pragma unroll
          for (int kk = k0; kk < k1; kk++)
            wgmma_rs_n64<0>(s, q[4 * kk], q[4 * kk + 1], q[4 * kk + 2], q[4 * kk + 3], mk_desc(ak + (kk >> 2) * KV_CH + (kk & 3) * 2, 16, KV_SBO, 1), kk != 0);
          if (k1 == 12) wg_commit();
        };
        auto pv = [&](uint32_t (&pin)[16], uint32_t av, int acc) {
#pragma unroll
          for (int kk = 0; kk < 4; kk++)
            wgmma_rs_n192<1>(o, pin[4 * kk], pin[4 * kk + 1], pin[4 * kk + 2], pin[4 * kk + 3], mk_desc(av + kk * (KV_SBO / 8), KV_CH * 16, KV_SBO, 1), acc || (kk != 0));
          wg_commit();
        };
        auto finish = [&](uint32_t (&pout)[16], int sk, int sv) {
          probe2();
          wg_wait<1>();
          fence_regs(s);
          release(sk);
          float b0, b1;
#pragma unroll 1
          for (bool redo = false;; redo = true) {
            expo(s, pout, b0, b1, false, [](int) {});
            if (!__any_sync(0xffffffffu, !redo && (shifted || !(fmaxf(b0, b1) <= kSumLimit)))) break;
            shifted = true;
            rowmax(s, b0, b1);
            b0 = fmaxf(mc0, b0); b1 = fmaxf(mc1, b1);
            const float a0 = ex2(mc0 - b0), a1 = ex2(mc1 - b1);
            mc0 = b0; mc1 = b1;
            l0 *= a0; l1 *= a1;
            wg_wait<0>();
            fence_regs(o);
#pragma unroll
            for (int i = 0; i < 24; i++) { o[4 * i] *= a0; o[4 * i + 1] *= a0; o[4 * i + 2] *= a1; o[4 * i + 3] *= a1; }
#pragma unroll
            for (int i = 0; i < 32; i++) s[i] -= (i & 2) ? mc1 : mc0;
          }
          l0 += b0; l1 += b1;
          wg_wait<0>();
          fence_regs(o);
          release(sv);
        };
        auto step = [&](uint32_t (&pin)[16], uint32_t (&pout)[16]) {
          uint32_t ak, av;
          const int sk = take(rdy0, SZ_KV, ak), sv = take(rdy1, SZ_KV, av);
          wg_fence();
          qk(s, ak);
          pv(pin, av, 1);
          finish(pout, sk, sv);
        };
        auto unpark = [&]() {
          uint32_t ad, ak;
          const int bi = take(rdy0, SZ_PARK, ad);
#pragma unroll
          for (int i = 0; i < 12; i++) lds128(sbase + (ad - ring16 + img0) * 16 + (i >> 1) * 8192 + (i & 1) * 512, q[4 * i], q[4 * i + 1], q[4 * i + 2], q[4 * i + 3]);
          const int sk0 = take(false, SZ_KV, ak);
          fence_regs(q);
          release(bi);
          wg_fence();
          qk(s, ak);
          probe2();
          return sk0;
        };
        auto mma4 = [&](uint32_t ad, int acc) {
#pragma unroll
          for (int kk = 0; kk < 4; kk++)
            wgmma_ss_n192<1>(o, mk_desc(ad + wg * 512 + kk * 2, 16, 1024, 1), mk_desc(ad + 1024 + kk * 128, 8192, 1024, 1), acc || kk != 0);
        };
        auto convert = [&](int i0, int i1) {
          sched_fence(keep, never);
#pragma unroll
          for (int i = i0; i < i1; i++) {
            q[i] = pack_bf16(o[2 * i] * kScaleLog2, o[2 * i + 1] * kScaleLog2);
            if (i % CONV_G == CONV_G - 1 && i != i1 - 1) sched_fence(keep, never);
          }
          sched_fence(keep, never);
        };
        auto kend = [&](int bi, int k) {
          wg_commit();
          drain(k < 8 ? (QDRAIN >> (4 * k)) & 7 : 7);
          probe1();
          wg_wait<0>();
          release(bi);
        };
        if (type == OP_O) {
          float c[80];
          int prev = 0;
          auto hand_over = [&](float (&c)[80], uint4* dst) {
            fence_regs(c);
#pragma unroll
            for (int i = 0; i < 48; i++) q[i] = i < 8 ? 0 : pack_bf16(c[2 * i - 16], c[2 * i - 15]);
            pend = dst;
          };
          auto mma2 = [&](float (&c)[80], uint32_t da, uint32_t db, int acc) {
            wgmma_ss_n160<1>(c, mk_desc(da, 16, 512, 2), mk_desc(db, 2048, 512, 2), acc);
            wgmma_ss_n160<1>(c, mk_desc(da + 2, 16, 512, 2), mk_desc(db + 64, 2048, 512, 2), 1);
          };
          auto kstep = [&](float (&c)[80], int acc, auto hook, uint32_t bytes = SZ_O) {
            uint32_t ad;
            const int bi = take(rdy0, bytes, ad);
            const uint32_t da = ad + wg * 256, db = ad + 1024;
            wg_fence();
            mma2(c, da, db, acc);
            wg_commit();
            if (acc) { wg_wait<1>(); mbar_arrive_cluster_if(lane < 2 && (acc == 1 || wg == 0), empty_rem + 8 * prev); }
            mma2(c, da + 512, db + 640, 1);
            wg_commit();
            prev = bi;
            hook();
            probe1();
            wg_wait<1>();
          };
          if (op & C_WIDE) {
            float d[80];
            const int nk = 3 * ((op >> 2) & 63);
            uint4* part = ptr_add(P.g->part, (((op >> 8) & 63) * 2 + rank) * SZ_PARK + img0 * 16);
            auto wstep = [&](int acc, auto hook) {
              uint32_t ad;
              const int bi = take(rdy0, SZ_W, ad);
              const uint32_t da = ad + wg * 256, db = ad + 1024;
              wg_fence();
              mma2(d, da, db, acc);
              mma2(d, da + 512, db + 640, 1);
              wg_commit();
              if (acc) { wg_wait<1>(); release(prev); }
              mma2(c, da, db + 1280, acc);
              mma2(c, da + 512, db + 1920, 1);
              wg_commit();
              prev = bi;
              hook();
              probe1();
              wg_wait<1>();
            };
            wstep(0, [&]() { drain(0); drain(1); });
#pragma unroll 1
            for (int k = 2; k < 6; k += 2) wstep(1, [&]() { drain(k); drain(k + 1); });
#pragma unroll 1
            for (int k = 3 + 3 * TAIL; k < nk; k++) {
              wstep(1, []() {});
            }
#pragma unroll 1
            for (int k = 0; k < 3 * TAIL; k++) kstep(d, 1, []() {});
            nop = prog[pc + 1];
            spol = make_policy(!(nop & C_SOON));
            kstep(c, 1, [&]() { hand_over(d, part - 6144); });
#pragma unroll 1
            for (int k = 1; k < 3 * TAIL; k++) kstep(c, 1, [&]() { slab(TAIL == 2 ? k : (0x50403201 >> (4 * k - 4)) & 7, 1); });
            if ((nop & 3) == OP_Q) {
              op = nop;
              enter();
              pc++;
              pend_any = true;
              bi0 = take(rdy0, SZ_Q, ad0);
              undefine(o);
              wg_fence();
              mma4(ad0, 0);
              wg_commit();
              wg_wait<1>();
              release(prev);
              hand_over(c, part);
              probe1();
              wg_wait<0>();
              release(bi0);
              fence_regs(o);
              goto next_head;
            }
            wg_wait<0>();
            release(prev);
            hand_over(c, part);
            continue;
          }
          auto unblock = [&](int k) {
            if (__all_sync(0xffffffffu, rdy0) || __all_sync(0xffffffffu, mbar_try(full0 + 8 * r.bi, r.ph, TRYNS))) return;
#pragma unroll 1
            for (; k < 6; k++) drain(k);
            pend_any = false;
          };
          unblock(0);
          kstep(c, 0, [&]() { drain(0); });
#pragma unroll 1
          for (int k = 1; k < 6; k++) {
            unblock(k);
            kstep(c, 1, [&]() { drain(k); });
          }
#pragma unroll 1
          for (int k = 3 * ((job >> 13) & 63); k > 11; k--) kstep(c, 1, []() {});
          uint32_t t[8], stage[3];
          float u[80];
          auto unpack = [&](int j) {
#pragma unroll
            for (int i = 0; i < 8; i++) {
              u[16 * j + 2 * i] = __uint_as_float(t[i] << 16); u[16 * j + 2 * i + 1] = __uint_as_float(t[i] & 0xffff0000u);
              asm volatile("" : "+f"(u[16 * j + 2 * i]), "+f"(u[16 * j + 2 * i + 1]));
            }
          };
#pragma unroll
          for (int i = 0; i < 8; i++) t[i] = 0;
          const uint32_t bytes = (job & P_LD) ? SZ_OL : SZ_O;
#pragma unroll
          for (int j = 0; j < 5; j++) {
            if (j == 5 - SKEW && wg == 1) {
              wg_wait<0>();
              release(prev);
              bar_sync(1, 256);
            }
            kstep(c, j == 5 - SKEW ? 2 : 1, [&]() {
              if (SKEW && j == 4) asm volatile("{\n.reg .pred p;\nsetp.eq.u32 p, %0, 0;\n@p bar.arrive 1, 256;\n}\n" ::"r"(wg) : "memory");
              if (j) unpack(j - 1);
              lds2_if(job & P_LD, sbase + (cur - ring16 + img0) * 16 - 8192, t);
              if (j >= 1 && j <= 3) stage[j - 1] = sbase + (cur - ring16) * 16 - bytes + wid * 1024;
            }, bytes);
          }
          unpack(4);
          sched_fence(keep, never);
          wg_wait<0>();
          fence_regs(c);
          release(prev);
          asm volatile("barrier.cluster.arrive.relaxed;" ::: "memory");
#pragma unroll
          for (int i = 0; i < 10; i++) {
            const int v = (i & 1) * 2 + (lane >> 4);
            const uint32_t sa = stage[i >> 2] + (i & 2) * 4096;
            stsm4(sa + (lane & 15) * 64 + ((v ^ ((lane >> 1) & 3)) << 4), pack_bf16(c[8 * i] + u[8 * i], c[8 * i + 1] + u[8 * i + 1]),
                  pack_bf16(c[8 * i + 2] + u[8 * i + 2], c[8 * i + 3] + u[8 * i + 3]), pack_bf16(c[8 * i + 4] + u[8 * i + 4], c[8 * i + 5] + u[8 * i + 5]),
                  pack_bf16(c[8 * i + 6] + u[8 * i + 6], c[8 * i + 7] + u[8 * i + 7]));
          }
          asm volatile("fence.proxy.async.shared::cta;" ::: "memory");
          __syncwarp();
          if (elect()) {
#pragma unroll
            for (int i = 0; i < 5; i++)
              tma3d_store(&P.out, stage[i >> 1] + (i & 1) * 8192, 0, ((job >> 7) & 7) * kSq + rank * 128 + wid * 16, ((job >> 10) & 1) * 20 + ((job >> 19) & 3) * 5 + i);
            asm volatile("cp.async.bulk.commit_group;\ncp.async.bulk.wait_group.read 0;" ::: "memory");
          }
          __syncwarp();
          break;
        }
        bi0 = take(rdy0, SZ_Q, ad0);
        undefine(o);
        wg_fence();
        mma4(ad0, 0);
        kend(bi0, 0);
        fence_regs(o);
      next_head:
        {
#pragma unroll 1
          for (int k = 1; k < ((op & F_PARK) ? 10 : 8); k++) {
            uint32_t ad;
            const int bi = take(rdy0, SZ_Q, ad);
            wg_fence();
            mma4(ad, 1);
            kend(bi, k);
          }
          if (op & F_PARK) {
            fence_regs(o);
            convert(0, 48);
            pend = ptr_add(P.g->tile, (((op >> 2) & 511) * 2 + rank) * SZ_PARK + img0 * 16);
            continue;
          }
          uint32_t a8, a9, ak0, ak1;
          const int b8 = take(rdy0, SZ_Q, a8), b9 = take(false, SZ_Q, a9);
          wg_fence();
          mma4(a8, 1);
          wg_commit();
          mma4(a9, 1);
          wg_commit();
          pc++;
          wg_wait<1>();
          release(b8);
          const int sk0 = take(false, SZ_KV, ak0);
          wg_wait<0>();
          fence_regs(o);
          release(b9);
          float s0[32];
          convert(0, CONV_0);
          wg_fence();
          qk(s0, ak0, 0, 4);
          convert(CONV_0, 48);
          wg_fence();
          qk(s0, ak0, 4, 12);
          sk1 = take(false, SZ_KV, ak1);
          probe1();
          wg_wait<0>();
          first(s0, sk0, [&](int i) {
            if (i != QA && i != QB && i != QC) return;
            sched_fence(keep, never);
            wg_fence();
            if (i == QA) qk(s, ak1, 0, 4);
            if (i == QB) qk(s, ak1, 4, 8);
            if (i == QC) qk(s, ak1, 8, 12);
            sched_fence(keep, never);
          });
        }
        for (;;) {
          {
            uint32_t av;
            const int sv = take(rdy0, SZ_KV, av);
            undefine(o);
            wg_fence();
            pv(pa, av, 0);
            finish(pb, sk1, sv);
          }
          nop = prog[pc + 1];
#pragma unroll 1
          for (int jj = 0; jj < 7; jj++) {
            step(pb, pa);
            step(pa, pb);
          }
          float i0, i1;
          auto last = [&]() {
            uint32_t av;
            const int sv = take(rdy0, SZ_KV, av);
            wg_fence();
            pv(pb, av, 1);
            sched_fence(keep, never);
            probe1();
            l0 += __shfl_xor_sync(0xffffffffu, l0, 1); l1 += __shfl_xor_sync(0xffffffffu, l1, 1);
            l0 += __shfl_xor_sync(0xffffffffu, l0, 2); l1 += __shfl_xor_sync(0xffffffffu, l1, 2);
            i0 = rcp(l0); i1 = rcp(l1);
            pend = ptr_add(P.g->tile, (((op >> 2) & 511) * 2 + rank) * SZ_PARK + img0 * 16);
            return sv;
          };
          auto normalise = [&](uint32_t (&d)[48], auto mid) {
#pragma unroll
            for (int i = 0; i < 24; i++) {
              d[8 * (i >> 2) + (i & 3)] = pack_bf16(o[4 * i] * i0, o[4 * i + 1] * i0);
              d[8 * (i >> 2) + (i & 3) + 4] = pack_bf16(o[4 * i + 2] * i1, o[4 * i + 3] * i1);
              if (i % NORM_G == NORM_G - 1 && i != 23) sched_fence(keep, never);
              if ((i & 3) == 3 && i != 23) mid(i >> 2);
            }
          };
          const int sv = last();
          if ((nop & 3) != OP_A) {
            op = nop;
            enter();
            pend_any = true;
            spol = make_policy(!(op & C_SOON));
            bi0 = take(rdy0 || (nop & 3) != OP_Q, SZ_Q, ad0);
            sched_fence(keep, never);
            wg_wait<0>();
            fence_regs(o);
            release(sv);
            normalise(q, [](int) {});
            undefine(o);
            if ((nop & 3) != OP_Q) break;
            sched_fence(keep, never);
            wg_fence();
            mma4(ad0, 0);
            pc++;
            kend(bi0, 0);
            fence_regs(o);
            goto next_head;
          }
          const int sk0 = unpark();
          wg_wait<1>();
          fence_regs(o);
          release(sv);
          uint32_t t[48];
          spol = make_policy(!(nop & C_SOON));
          auto st = [&](int i) {
            stg2_if(true, pend + i * 512, t[8 * i], t[8 * i + 1], t[8 * i + 2], t[8 * i + 3], t[8 * i + 4], t[8 * i + 5], t[8 * i + 6], t[8 * i + 7], spol);
          };
          normalise(t, [&](int i) { if (!(i & 1)) st(i >> 1); });
          wg_wait<0>();
          first(s, sk0, [&](int i) { if (i < 3) { sched_fence(keep, never); st(3 + i); } });
          __syncwarp();
          mbar_arrive_if(lane == 0, odone0 + 8 * pc);
          pc++;
          op = nop;
          uint32_t ak1;
          sk1 = take(rdy0, SZ_KV, ak1);
          rdy0 = rdy1;
          wg_fence();
          qk(s, ak1);
        }
      }
    }
    if (never) P.g->flag[0] = keep;
    asm volatile("barrier.cluster.wait;" ::: "memory");
  } else {
    asm volatile("setmaxnreg.dec.sync.aligned.u32 24;");
    const uint32_t* prog = P.prog[role].p;
    unsigned int* flag = P.g->flag + rank;
    if (wid == 8) {
      Cursor tail{0, 0};
      int head = 0, sh = 0;
      uint32_t cur = 0, used = 0;
      uint64_t fifo = 0;
      uint32_t dst, bar, ev = ev0, done = 0;
      uint64_t pol;
      asm volatile("createpolicy.fractional.L2::evict_first.b64 %0, 1.0;" : "=l"(pol));
      auto retire = [&]() {
        mbar_wait(empty0 + 8 * tail.bi, tail.ph);
        tail.next();
        used -= (uint32_t)fifo & 31;
        fifo >>= 5;
        sh -= 5;
        asm volatile("st.volatile.shared.u32 [%0], %1;" ::"r"(progress), "r"(++done) : "memory");
      };
      auto acquire = [&](uint32_t bytes) {
        uint32_t fp = bytes >> 12;
        if (cur + fp > (RING >> 12)) { fp += (RING >> 12) - cur; cur = 0; }
        used += fp;
        while (used > (RING >> 12) || sh == 5 * NBAR) retire();
        fifo |= (uint64_t)fp << sh;
        sh += 5;
        dst = sbase + (cur << 12);
        bar = full0 + 8 * head;
        cur += bytes >> 12;
        if (++head == NBAR) head = 0;
      };
      auto gate = [&]() {
        mbar_wait(ev, 0);
        ev += 8;
        asm volatile("fence.proxy.async.global;" ::: "memory");
      };
      for (int pc = 0;; pc++) {
        uint32_t op = prog[pc];
        const int type = op & 3;
        if (type == OP_END) break;
        if (op == OP_O) {
          gate();
          op = __shfl_sync(0xffffffffu, lds32(jobw), 0);
        }
        const int blk = (op >> 10) & 1;
        if (type == OP_Q) {
#pragma unroll 1
          for (int k = 0; k < 10; k++) {
            if (k == 9 && (op & P_GATE)) gate();
            acquire(SZ_Q);
            if ((pc > 0 || k >= EARLY) && elect()) {
              mbar_expect(bar, SZ_Q);
              tma2d(dst, &P.x[blk], bar, 64 * k, ((op >> 7) & 7) * kSq + rank * 128);
              if ((k & 1) == rank) tma3d_mc(dst + 16384, &P.wq[blk], bar, 0, 64 * k, 3 * ((op >> 2) & 31));
            }
          }
        } else if (type == OP_A) {
          const int row0 = ((op >> 2) & 255) * kSk;
          const CUtensorMap* kv_map = rank ? &P.v[blk] : &P.k[blk];
          if (op & F_PARK) {
            gate();
            acquire(SZ_PARK);
            if (elect()) {
              mbar_expect(bar, SZ_PARK);
              bulk_load_hint(dst, &P.g->tile[((op >> 20) * 2 + rank) * 3072], SZ_PARK, bar, make_policy(P.dbg & 4));
            }
          }
#pragma unroll 1
          for (int t = 0; t < 32; t++) {
            const int isv = t == 31 ? 1 : (t == 0 ? 0 : (~t & 1));
            const int j = isv ? (t - 1) >> 1 : (t + 1) >> 1;
            if (t == 31 && (op & P_GATE)) gate();
            acquire(SZ_KV);
            if (elect()) {
              mbar_expect(bar, SZ_KV);
              if (isv == (int)rank) tma4d_mc_hint(dst, kv_map, bar, row0 / 8 + 8 * j, pol);
            }
          }
        } else {
          const int n = (op >> 13) & 63, nw = (op & P_WIDE) ? n - TAIL : 0;
          const uint64_t pol_o = make_policy(P.dbg & (nw ? 1 : 2));
          const uint4* part = &P.g->part[((((op >> 5) & 60) + ((op >> 19) & 3)) * 2 + rank) * 3072 + 512];
#pragma unroll 1
          for (int i = 0; i < n + (nw ? TAIL : 0); i++) {
            const int id = ((op >> 2) & 511) + (i < n ? i : i - TAIL), col = 5 * (((op >> 19) & 3) + (i >= n));
            const uint4* src = &P.g->tile[(P.slot[id] * 2 + rank) * 3072];
            if ((op & P_LD) && i == ((op & P_PRE) ? 0 : n - 2)) gate();
            if (i < n) gate();
#pragma unroll 1
            for (int k = 0; k < 3; k++) {
              const uint32_t j = (op & P_LD) ? 3 * (i - n) + k + 5 : 5, bytes = i < nw ? SZ_W : j < 5 ? SZ_OL : SZ_O;
              acquire(bytes);
              if (elect()) {
                mbar_expect(bar, bytes);
                tma5d_mc(dst + 16384 + rank * 10240, &P.wo[blk], bar, 24 * (id & 31) + 8 * k + 4 * rank, col);
                bulk_load_hint(dst, src + k * 1024, 16384, bar, pol_o);
                if (i < nw) tma5d_mc(dst + SZ_O + rank * 10240, &P.wo[blk], bar, 24 * (id & 31) + 8 * k + 4 * rank, col + 5);
                if (j < 5) bulk_load_hint(dst + SZ_O, part + j * 512, 8192, bar, pol);
                if ((op & P_PRE) && (uint32_t)(3 * i + k) < PFN)
                  asm volatile("cp.async.bulk.prefetch.L2.global [%0], %1;" ::"l"(part + (3 * i + k) * (2560 / PFN)), "n"(40960 / PFN) : "memory");
              }
            }
          }
        }
      }
#pragma unroll 1
      while (sh) retire();
    } else if (threadIdx.x == 288) {
      for (int pc = 0;; pc++) {
        const uint32_t op = prog[pc];
        const int type = op & 3;
        if (type == OP_END) break;
        if (type == OP_Q ? !(op & F_PARK) : type == OP_O && !(op & P_ST)) continue;
        const int id = type == OP_A ? (op >> 2) & 511 : type == OP_Q ? N_TILE + ((op >> 13) & 127) : ID_PART + ((op >> 5) & 60) + ((op >> 19) & 3);
        const uint32_t v = type == OP_O ? 1 : P.info[id] & 7;
        mbar_wait_slow<PUBNS>(odone0 + 8 * pc, 0);
        flag_set(flag + 2 * id, v);
        if (type == OP_O && (op & P_WIDE)) flag_set(flag + 2 * id + 2, v);
      }
    } else if (wid == 10) {
      int i = threadIdx.x & 31;
      uint32_t e = i < 8 ? P.prog[role].ev[i] : 0;
      for (uint32_t n = 0; __any_sync(0xffffffffu, e); n++) {
        uint32_t job = (e & (E_DRAW | E_JOB)) ? lds32(jobw) : 0;
        if ((e & E_DRAW) && rank == 0 && lds32(progress) >= (e & 1023)) {
          job = P.job[atomicInc(&P.g->ticket, gridDim.x / 2 - 1)];
          asm volatile("{\n.reg .u32 a;\nmapa.shared::cluster.u32 a, %0, 1;\nst.volatile.shared::cluster.u32 [a], %1;\n"
                       "st.volatile.shared.u32 [%0], %1;\n}\n" ::"r"(jobw), "r"(job) : "memory");
        }
        if ((e & E_JOB) && job) {
          const uint32_t j = e & 63, heads = (job >> 13) & 63, jp = !(job & P_LD) ? 63 : (job & P_PRE) ? 0 : heads - 2, h = j - (j > jp);
          e = j == jp ? (ID_PART + ((job >> 5) & 60) + ((job >> 19) & 3)) | E_ON | E_LAST : h < heads ? (((job >> 2) & 511) + h) | E_ON | E_LAST : 0;
        }
        unsigned int* f = ptr_add(flag, 8 * (e & 1023));
        const bool ok = (e & E_ON) ? flag_get(f) - 1 < ((e & E_FREE) ? 1 : 7) : (e & E_DRAW) && job;
        if (ok) {
          mbar_arrive(ev0 + 8 * i);
          if (e & (E_FREE | E_LAST)) flag_dec(f);
          i += 8;
          e = i < MAX_EV ? P.prog[role].ev[i] : 0;
        }
        asm volatile("{\n.reg .pred p;\nsetp.ge.u32 p, %0, 0x400000;\n@p trap;\n}\n" ::"r"(n));
        if (!__any_sync(0xffffffffu, ok)) __nanosleep(WATNS);
      }
    } else if (threadIdx.x == 352) {
      uint32_t items = 0;
      auto read = [&](int id) {
        if (!(P.info[id] & I_NEXT)) return;
        wait_word(progress, items);
        flag_dec(flag + 2 * id);
      };
      for (int pc = 0;; pc++) {
        const uint32_t op = prog[pc];
        const int type = op & 3;
        if (type == OP_END) break;
        if (type == OP_O) {
          const int n = (op >> 13) & 63;
#pragma unroll 1
          for (int i = 0; i < n; i++) {
            items += (op & P_WIDE) && i == n - TAIL ? 3 * TAIL + 3 : 3;
            read(((op >> 2) & 511) + i);
          }
        } else if (type == OP_A) {
          if (op & F_PARK) { items++; read(N_TILE + ((op >> 13) & 127)); }
          items += 32;
        } else {
          items += 10;
        }
      }
    }
    __syncwarp();
    asm volatile("barrier.cluster.arrive.relaxed;\nbarrier.cluster.wait;" ::: "memory");
  }
}

typedef CUresult (*EncodeFn)(CUtensorMap*, CUtensorMapDataType, cuuint32_t, void*, const cuuint64_t*, const cuuint64_t*,
                             const cuuint32_t*, const cuuint32_t*, CUtensorMapInterleave, CUtensorMapSwizzle,
                             CUtensorMapL2promotion, CUtensorMapFloatOOBfill);

void encode(EncodeFn fn, CUtensorMap* m, const void* ptr, int rank, const cuuint64_t* dims, const cuuint64_t* strides,
            const cuuint32_t* box, CUtensorMapSwizzle swz) {
  const cuuint32_t es[5] = {1, 1, 1, 1, 1};
  CUresult r = fn(m, CU_TENSOR_MAP_DATA_TYPE_BFLOAT16, rank, const_cast<void*>(ptr), dims, strides, box, es,
                  CU_TENSOR_MAP_INTERLEAVE_NONE, swz, CU_TENSOR_MAP_L2_PROMOTION_L2_128B, CU_TENSOR_MAP_FLOAT_OOB_FILL_NONE);
  if (r != CUDA_SUCCESS) fprintf(stderr, "cuTensorMapEncodeTiled failed: %d\n", (int)r);
}

struct Op { int type, flags, id, n, quarter, park, item0, items; double t0, t1; };
struct Use { double ready, gate, need, freed; int readers, slot, prev; bool next; };
struct PlanStats { double end, slack, park_slack; int slots, parks; uint32_t own[N_CL]; };

bool plan(const char* const* text, int n_pair, int phase, Params& P, PlanStats* stats = nullptr) {
  constexpr double T_Q = 7900, T_A = 24850, T_U = 26300, T_O = 1920, T_RUN = 800, T_WIDE = 1900, AHEAD = 3500, PUBLISH = 1500;
  const double margin = 256.0 * ((P.dbg >> 8) & 255);
  static Op op[N_CL][MAX_OPS];
  static Use use[ID_PART];
  int n_op[N_CL], covered[N_TEAM] = {}, finals[N_TEAM] = {};
  auto hex = [](char c) { return c <= '9' ? c - '0' : c - 'a' + 10; };
  for (int i = 0; i < n_pair; i++)
    for (const char* s = text[i]; *s; s++)
      if (*s == 'J') { if (covered[hex(s[1])]) return false; covered[hex(s[1])] = 10 * (s[2] - '0') + s[3] - '0'; }
  for (int c = 0; c < 2 * n_pair; c++) {
    int n = 0, items = 0;
    double t = 0;
    auto add = [&](int type, int flags, int id, int heads, int quarter, int its, double dt) {
      if (n < MAX_OPS) op[c][n] = {type, flags, id, heads, quarter, 0, items, its, t, t + dt};
      n++; items += its; t += dt;
    };
    for (const char* s = text[c >> 1]; *s; s++) {
      const int tm = hex(s[1]) & 15, nj = covered[tm];
      if (*s == 'N') { add(OP_Q, 0, 0, 0, 0, 10, T_Q); add(OP_A, 0, 0, 0, 0, 32, T_A); }
      if (*s == 'P') add(OP_Q, F_PARK, 0, 0, 0, 10, T_Q);
      if (*s == 'U') { if (n == 0 || n > MAX_OPS || op[c][n - 1].type != OP_A) return false; add(OP_A, F_PARK, 0, 0, 0, 33, T_U); }
      if (*s == 'J') { if (nj <= TAIL || nj > kH - 4) return false; add(OP_O, P_WIDE | P_ST, tm * kH, nj, 2 * (c & 1), 3 * (nj + TAIL), 2 * T_O * nj + T_WIDE); }
      if (*s == 'F') { if (s[2]) return false; add(OP_O, nj ? P_LD : 0, tm * kH + nj, kH - nj, finals[tm]++, 3 * (kH - nj), T_O * (kH - nj) + T_RUN); }
    }
    if (n && n <= MAX_OPS && (op[c][n - 1].type != OP_O || (op[c][n - 1].flags & P_WIDE))) add(OP_O, 0, 0, 0, 0, 0, 0);
    add(OP_END, 0, 0, 0, 0, 0, 0);
    if (n > MAX_OPS || op[c][0].type != OP_Q) return false;
    n_op[c] = n - 1;
  }
  for (int t = 0; t < N_TEAM; t++) if (finals[t] != 4) return false;
  for (int i = 0; i < ID_PART; i++) use[i] = {0, 0, 1e18, 0, 0, 0, 0, false};
  struct Ref { double t; Op* o; int id; };
  static Ref att[N_TILE + 1], dem[N_TILE], prk[MAX_PARK + 1], unp[MAX_PARK + 1], wr[ID_PART];
  int n_att = 0, n_prk = 0, n_unp = 0;
  auto ready = [&](const Op* o) {
    const int nt = o[1].type;
    return o->t1 + (nt == OP_Q ? 6100 : o[1].n ? 3900 : 1500) + PUBLISH;
  };
  for (int c = 0; c < 2 * n_pair; c++)
    for (Op* o = op[c]; o->type != OP_END; o++) {
      if (o->type == OP_A) { att[n_att] = {ready(o), o, 0}; if (++n_att > N_TILE) return false; }
      if (o->type == OP_A && o->flags) { unp[n_unp] = {o->t0 - AHEAD, o, 0}; if (++n_unp > MAX_PARK) return false; }
      if (o->type == OP_Q && o->flags) { prk[n_prk] = {ready(o), o, 0}; if (++n_prk > MAX_PARK) return false; }
      for (int i = 0; o->type == OP_O && i < o->n; i++) {
        const int nw = (o->flags & P_WIDE) ? o->n - TAIL : 0;
        Use& u = use[o->id + i];
        const double t = o->t0 + T_O * (i + (i < nw ? i : nw));
        if (t - AHEAD < u.need) u.need = t - AHEAD;
        const double f = i < nw || (nw && o[1].type != OP_O) ? t + T_O * (i < nw ? 2 : 1 + TAIL) + PUBLISH : 1e18;
        if (f > u.freed) u.freed = f;
        u.readers++;
      }
    }
  if (n_att != N_TILE || n_prk != n_unp) return false;
  auto sort = [](Ref* r, int n) {
    for (int i = 1; i < n; i++)
      for (int j = i; j > 0 && r[j].t < r[j - 1].t; j--) { Ref x = r[j]; r[j] = r[j - 1]; r[j - 1] = x; }
  };
  for (int i = 0; i < N_TILE; i++) { const int id = (i & 15) * kH + (i >> 4); dem[i] = {use[id].need, nullptr, id}; }
  sort(att, n_att); sort(dem, N_TILE); sort(prk, n_prk); sort(unp, n_unp);
  PlanStats st = {0, 1e18, 1e18, 0, n_prk};
  int n_wr = 0;
  for (int i = 0; i < N_TILE; i++) {
    Op* o = att[i].o;
    o->id = dem[i].id;
    if (!o->flags) o[-1].id = o->id;
    if (dem[i].t - att[i].t < st.slack) st.slack = dem[i].t - att[i].t;
    wr[n_wr++] = {o->t1 - 2 * AHEAD, o, o->id};
  }
  for (int i = 0; i < n_prk; i++) {
    prk[i].o->id = unp[i].o->id;
    prk[i].o->park = unp[i].o->park = i;
    use[N_TILE + i].freed = unp[i].o->t0 + 2 * PUBLISH;
    use[N_TILE + i].readers = 1;
    if (unp[i].t - prk[i].t < st.park_slack) st.park_slack = unp[i].t - prk[i].t;
    wr[n_wr++] = {prk[i].o->t1 - 2 * AHEAD, prk[i].o, N_TILE + i};
  }
  for (int c = 0; c < 2 * n_pair; c++)
    for (int d = 0; d < 2 * n_pair; d++)
      for (Op *f = &op[c][n_op[c] - 1], *o = op[d]; f->n && o->type != OP_END; o++)
        if (o->type == OP_O && (o->flags & P_ST) && o->id / kH == f->id / kH) {
          if (f->t0 - o->t1 > 4096.0 * ((P.dbg >> 16) & 255)) f->flags |= P_PRE;
          const double slack = f->t0 + ((f->flags & P_PRE) ? 0 : (f->n - 2) * T_O) - AHEAD - ready(o);
          if (slack < st.park_slack) st.park_slack = slack;
        }
  sort(wr, n_wr);
  int holder[N_TILE];
  for (int i = 0; i < n_wr; i++) {
    int best = -1;
    for (int sl = 0; sl < st.slots; sl++)
      if (use[holder[sl]].freed + margin <= wr[i].t && (best < 0 || (use[holder[sl]].freed < use[holder[best]].freed) != ((P.dbg & 32) != 0))) best = sl;
    Use& u = use[wr[i].id];
    if (best >= 0) { u.prev = holder[best]; use[u.prev].next = true; wr[i].o->flags |= P_GATE; }
    else if (st.slots == N_TILE) return false;
    else best = st.slots++;
    u.slot = best;
    holder[best] = wr[i].id;
  }
  {
    int pos[N_CL] = {}, flag[ID_PART + 4 * N_TEAM] = {}, seen[ID_PART] = {};
    auto goal = [&](int c) { return op[c][n_op[c] - 1].item0; };
    for (bool moved = true; moved;) {
      moved = false;
      for (int c = 0; c < 2 * n_pair; c++) {
        for (; pos[c] < goal(c); pos[c]++, moved = true) {
          bool ok = true;
          for (const Op* o = op[c]; o->type != OP_END; o++) {
            const int k = pos[c] - o->item0, own = o->type == OP_A ? o->id : N_TILE + o->park;
            if (k < 0 || k >= o->items) continue;
            if (o->type == OP_O) ok = k >= 3 * o->n || flag[o->id + k / 3];
            else if (k == o->items - 1 && (o->flags & P_GATE)) ok = seen[use[own].prev] == use[use[own].prev].readers;
            else if (k == 0 && o->type == OP_A && (o->flags & F_PARK)) ok = flag[N_TILE + o->park];
          }
          if (!ok) break;
          for (const Op* o = op[c]; o->type != OP_END; o++) {
            if (pos[c] == o->item0 + o->items + (o[1].type == OP_Q ? 7 : o[1].item0 == goal(c) ? -1 : 5)) {
              if (o->type == OP_A) flag[o->id] = 1;
              if (o->type == OP_Q && (o->flags & F_PARK)) flag[N_TILE + o->park] = 1;
              if (o->type == OP_O) flag[ID_PART + o->id / kH * 4 + o->quarter] = flag[ID_PART + o->id / kH * 4 + o->quarter + 1] = 1;
            }
            const int k = pos[c] - NBAR - o->item0, nw = o->n - TAIL;
            if (k == 0 && o->type == OP_A && (o->flags & F_PARK)) seen[N_TILE + o->park]++;
            if (o->type == OP_O && k >= 0 && k < o->items && k % 3 == 2 && (k / 3 < nw || k / 3 >= o->n)) seen[o->id + (k / 3 < nw ? k / 3 : k / 3 - TAIL)]++;
          }
        }
      }
    }
    for (int c = 0; c < 2 * n_pair; c++) if (pos[c] < goal(c)) return false;
  }
  int n_job = 0, longest = 0;
  for (int t = 0; t < N_TEAM; t++) if (kH - covered[t] > longest) longest = kH - covered[t];
  for (int c = 0; c < 2 * n_pair; c++) {
    uint32_t items = 0, cur = 0, pend = 0;
    int n = 0, ev = 0;
    auto item = [&](uint32_t bytes, int count) {
      for (int i = 0; i < count; i++) { if (cur + bytes > RING) cur = 0; cur += bytes; items++; }
    };
    auto event = [&](uint32_t e) { if (ev < MAX_EV) P.prog[c].ev[ev] = e; ev++; };
    for (const Op* o = op[c];; o++) {
      if (o->type != OP_END && phase && (o->type == OP_O) != (phase == 2)) continue;
      uint32_t cw = o->type | (items % NBAR) << 15 | ((items / NBAR) & 1) << 19 | (cur >> 12) << 20 | pend, pw = o->type | o->id << 2 | o->flags;
      const int ps = use[N_TILE + o->park].slot;
      pend = 0;
      if (o->type == OP_O) {
        pw |= o->n << 13 | o->quarter << 19;
        if (o->flags & P_WIDE) {
          cw |= o->n << 2 | (o->id / kH * 4 + o->quarter + 1) << 8 | C_WIDE;
          item(SZ_W, 3 * (o->n - TAIL));
          item(SZ_O, 6 * TAIL);
          pend = C_PEND | ((P.dbg & 8) ? C_SOON : 0);
          for (int i = 0; i < o->n; i++) event((o->id + i) | E_ON | (use[o->id + i].next ? 0 : E_LAST));
        } else {
          dem[n_job++] = {o->t0 - 1e6 * o->n, nullptr, (int)pw};
          st.own[c] = pw;
          pw = OP_O;
          event(E_DRAW | (items < 16 ? 0 : items - 16));
          for (int i = 0; i <= longest; i++) event(E_JOB | i);
        }
      } else if (o->type != OP_END) {
        const bool parks = o->type == OP_Q && (o->flags & F_PARK);
        cw |= (parks ? ps : use[o->id].slot) << 2 | (o->flags & F_PARK);
        if (o->flags & F_PARK) pw |= o->park << 13 | ps << 20;
        if (o->type == OP_Q) item(SZ_Q, 10);
        else { if (o->flags & F_PARK) { item(SZ_PARK, 1); event((N_TILE + o->park) | E_ON | (use[N_TILE + o->park].next ? 0 : E_LAST)); } item(SZ_KV, 32); }
        if (parks || o->type == OP_A) pend = C_PEND | ((P.dbg & 16) ? 0 : C_SOON);
        if (o->flags & P_GATE) event(use[parks ? N_TILE + o->park : o->id].prev | E_ON | E_FREE);
      }
      P.prog[c].c[n] = cw; P.prog[c].p[n++] = pw;
      if (o->type == OP_END) { if (o->t0 > st.end) st.end = o->t0; break; }
    }
    if (ev > MAX_EV) return false;
    while (ev < MAX_EV) P.prog[c].ev[ev++] = 0;
    while (n < MAX_OPS) { P.prog[c].c[n] = OP_END; P.prog[c].p[n++] = OP_END; }
    P.first[c] = (uint16_t)(P.prog[c].p[0] & 2047);
  }
  sort(dem, n_job);
  for (int i = 0; i < n_job; i++) P.job[i] = dem[i].id;
  for (int i = 0; i < ID_PART; i++) {
    if (i < N_TILE) P.slot[i] = use[i].slot;
    P.info[i] = (use[i].readers + use[i].next) | (use[i].next ? I_NEXT : 0);
  }
  if (stats) *stats = st;
  return true;
}

const char* const kPrograms[N_CL / 2] = {
  "NNNNNNNNNF0", "NNNNNNNNNFe", "NUNNJf16NNNFf", "PNNNNNNNNNF3", "PNJ421NNNNNFf", "NNNNNNNNNF1",
  "NNUNNNNNNF7", "NNNNNNNNNF4", "NNNNNNNNNF1", "NUNNNJa26NFe", "PNJ227NNNNFc", "PPNJ517NNNNUNF2",
  "NUNNJc13NPNNUF2", "NNJ326NNNNF8", "NUNUNJ926NFd", "PNUNNNNNNNFb", "PNJ021NNNNNF7", "NUNNNJd15NNFd",
  "PNNNNNNNNNFa", "NNUJ618Jb22NFc", "NNNNNNNNNF4", "PNJ717NNNNNNF3", "NNNNNNNNNFb", "PNJ121NNNNNF5",
  "PNNNNNNNNN", "NUNNNJe20NNFa", "PNNNNNNNNNF9", "NNNNNNNNNF0", "PNNNNNNNNNF9", "PPNUNNNNNNUF8",
  "NNUNNNNNNF6", "NNNNNJ824NF6", "NUNNNNNNNF5",
};

const char* const* bench_programs() {
  return kPrograms;
}

}

extern "C" void kernel_launch(void* const* d_in, const int* in_sizes, int n_in, void* d_out, int out_size) {
  (void)in_sizes; (void)n_in; (void)out_size;
  static EncodeFn fn = nullptr;
  static int n_clusters = 0;
  if (!fn) {
    cudaDriverEntryPointQueryResult qr;
    void* f = nullptr;
    cudaGetDriverEntryPoint("cuTensorMapEncodeTiled", &f, cudaEnableDefault, &qr);
    fn = (EncodeFn)f;
    cudaFuncSetAttribute(fused_kernel, cudaFuncAttributeMaxDynamicSharedMemorySize, SMEM_BYTES);
    cudaLaunchConfig_t cfg = {};
    cfg.gridDim = dim3(132); cfg.blockDim = dim3(384); cfg.dynamicSmemBytes = SMEM_BYTES;
    cudaLaunchAttribute at[1];
    at[0].id = cudaLaunchAttributeClusterDimension; at[0].val.clusterDim.x = 2; at[0].val.clusterDim.y = 1; at[0].val.clusterDim.z = 1;
    cfg.attrs = at; cfg.numAttrs = 1;
    if (cudaOccupancyMaxActiveClusters(&n_clusters, fused_kernel, &cfg) != cudaSuccess || n_clusters < 1) n_clusters = 1;
    (void)cudaGetLastError();
  }
  static Params P;
  const CUtensorMapSwizzle S128 = CU_TENSOR_MAP_SWIZZLE_128B, S64 = CU_TENSOR_MAP_SWIZZLE_64B;
  for (int blk = 0; blk < 2; blk++) {
    void* const* in = d_in + 5 * blk;
    { const cuuint64_t d[] = {kD, kB * kSq}, s[] = {kD * 2}; const cuuint32_t b[] = {64, 128};
      encode(fn, &P.x[blk], in[0], 2, d, s, b, S128); }
    { const cuuint64_t d[] = {64, 8, 3, (cuuint64_t)kB * kH * kSk / 8}, s[] = {kDh * 2, 128, 8 * kDh * 2}; const cuuint32_t b[] = {64, 8, 3, 8};
      encode(fn, &P.k[blk], in[1], 4, d, s, b, S128);
      encode(fn, &P.v[blk], in[2], 4, d, s, b, S128); }
    { const cuuint64_t d[] = {64, kD, kHD / 64}, s[] = {kHD * 2, 128}; const cuuint32_t b[] = {64, 64, 3};
      encode(fn, &P.wq[blk], in[3], 3, d, s, b, S128); }
    { const cuuint64_t d[] = {32, 2, kHD / 8, 4, kD / 32}, s[] = {kD * 2, 8 * kD * 2, 2 * kD * 2, 64}; const cuuint32_t b[] = {32, 2, 4, 4, 5};
      encode(fn, &P.wo[blk], in[4], 5, d, s, b, S64); }
  }
  { const cuuint64_t d[] = {32, kB * kSq, 2 * kD / 32}, s[] = {2 * kD * 2, 64}; const cuuint32_t b[] = {32, 16, 1};
    encode(fn, &P.out, d_out, 3, d, s, b, S64); }

  cudaGetSymbolAddress((void**)&P.g, g_scratch);
  P.dbg = DBG_DEFAULT;
  if (n_clusters >= N_CL && plan(bench_programs(), N_CL / 2, 0, P)) {
    fused_kernel<<<2 * N_CL, 384, SMEM_BYTES>>>(P);
  } else {
    char buf[2 * N_TEAM][16];
    const char* text[2 * N_TEAM];
    for (int i = 0; i < 2 * N_TEAM; i++) { snprintf(buf[i], sizeof(buf[i]), "NNNNNNNNF%x", i / 2); text[i] = buf[i]; }
    for (int phase = 1; phase <= 2; phase++) {
      plan(text, 2 * N_TEAM, phase, P);
      fused_kernel<<<8 * N_TEAM, 384, SMEM_BYTES>>>(P);
    }
  }
}
```

```cpp
#include <cuda_runtime.h>
#include <cuda_bf16.h>
#include <cuda.h>
#include <stdint.h>
#include <stdio.h>

namespace {

constexpr int kB = 8, kSq = 256, kD = 640, kH = 32, kSk = 1024, kDh = 192;
constexpr int kHD = kH * kDh;
constexpr uint32_t RING = 224 * 1024;
constexpr uint32_t SZ_KV = 24576;
constexpr uint32_t SZ_Q = 16384 + 24576;
constexpr uint32_t SZ_O = 16384 + 20480;
constexpr uint32_t SZ_W = 16384 + 40960;
constexpr uint32_t SZ_PARK = 49152;
constexpr uint32_t SZ_OL = SZ_O + 8192;
constexpr int NBAR = 10;
constexpr int EARLY = 3;
#define XTAIL 2
constexpr int TAIL = XTAIL;
constexpr uint32_t KV_CH = 64, KV_SBO = 3072;
constexpr int SMEM_BYTES = RING + 1024 + 1024;
constexpr int N_TEAM = 16, N_CL = 66, MAX_OPS = 24, MAX_EV = 80, N_TILE = N_TEAM * kH, MAX_PARK = 128, ID_PART = N_TILE + MAX_PARK;
enum : uint32_t { OP_END = 0, OP_Q = 1, OP_A = 2, OP_O = 3, F_PARK = 1 << 11,
                  C_WIDE = 1 << 14, C_PEND = 1 << 26, C_SOON = 1 << 28,
                  P_GATE = 1 << 12, P_WIDE = 1 << 11, P_LD = 1 << 12, P_ST = 1 << 21, P_PRE = 1 << 22, I_NEXT = 8, E_ON = 1 << 15, E_FREE = 1 << 14, E_LAST = 1 << 13, E_DRAW = 1 << 12, E_JOB = 1 << 11 };

#define QDRAIN 0x54732710u
#define TRYNS 1500
#define PFN 10
#define QA 1
#define QB 2
#define QC 3
#define NORM_G 2
#define CONV_G 8
#define CONV_0 32
#define SLOWF 12
#define SLOWP 0x4511
#define FASTF 7
#define FASTP 0x1a
#define WATNS2 100
#define NEAR 2
#define TICK 16
#define SKEW 3
#define PUBNS 0
#define WATNS 600
constexpr uint32_t DBG_DEFAULT = 0x040817;

struct alignas(1024) Scratch {
  unsigned int flag[2047];
  unsigned int ticket;
  uint4 part[N_TEAM * 4 * 2 * 3072];
  uint4 tile[N_TILE * 2 * 3072];
};

struct alignas(64) Params {
  uint16_t first[88];
  Scratch* g;
  uint32_t dbg;
  CUtensorMap x[2], wq[2], k[2], v[2], wo[2], out;
  struct {
    uint32_t c[MAX_OPS];
    uint32_t p[MAX_OPS];
    uint16_t ev[MAX_EV];
  } prog[N_CL];
  uint32_t job[N_CL];
  uint16_t slot[N_TILE];
  uint8_t info[ID_PART];
};

__device__ Scratch g_scratch;

template <int TB, int TA = 0>
__device__ __forceinline__ void wgmma_ss_n64(float (&d)[32], uint64_t da, uint64_t db, int scale_d) {
  asm volatile("{\n.reg .pred p;\nsetp.ne.b32 p, %34, 0;\n"
    "wgmma.mma_async.sync.aligned.m64n64k16.f32.bf16.bf16 {%0, %1, %2, %3, %4, %5, %6, %7, %8, %9, %10, %11, %12, %13, %14, %15, %16, %17, %18, %19, %20, %21, %22, %23, %24, %25, %26, %27, %28, %29, %30, %31}, %32, %33, p, 1, 1, %35, %36;\n}\n"
    : "+f"(d[0]), "+f"(d[1]), "+f"(d[2]), "+f"(d[3]), "+f"(d[4]), "+f"(d[5]), "+f"(d[6]), "+f"(d[7]), "+f"(d[8]), "+f"(d[9]), "+f"(d[10]), "+f"(d[11]), "+f"(d[12]), "+f"(d[13]), "+f"(d[14]), "+f"(d[15]), "+f"(d[16]), "+f"(d[17]), "+f"(d[18]), "+f"(d[19]), "+f"(d[20]), "+f"(d[21]), "+f"(d[22]), "+f"(d[23]), "+f"(d[24]), "+f"(d[25]), "+f"(d[26]), "+f"(d[27]), "+f"(d[28]), "+f"(d[29]), "+f"(d[30]), "+f"(d[31])
    : "l"(da), "l"(db), "r"(scale_d), "n"(TA), "n"(TB));
}
template <int TB>
__device__ __forceinline__ void wgmma_rs_n64(float (&d)[32], uint32_t a0, uint32_t a1, uint32_t a2, uint32_t a3, uint64_t db, int scale_d) {
  asm volatile("{\n.reg .pred p;\nsetp.ne.b32 p, %37, 0;\n"
    "wgmma.mma_async.sync.aligned.m64n64k16.f32.bf16.bf16 {%0, %1, %2, %3, %4, %5, %6, %7, %8, %9, %10, %11, %12, %13, %14, %15, %16, %17, %18, %19, %20, %21, %22, %23, %24, %25, %26, %27, %28, %29, %30, %31}, {%32, %33, %34, %35}, %36, p, 1, 1, %38;\n}\n"
    : "+f"(d[0]), "+f"(d[1]), "+f"(d[2]), "+f"(d[3]), "+f"(d[4]), "+f"(d[5]), "+f"(d[6]), "+f"(d[7]), "+f"(d[8]), "+f"(d[9]), "+f"(d[10]), "+f"(d[11]), "+f"(d[12]), "+f"(d[13]), "+f"(d[14]), "+f"(d[15]), "+f"(d[16]), "+f"(d[17]), "+f"(d[18]), "+f"(d[19]), "+f"(d[20]), "+f"(d[21]), "+f"(d[22]), "+f"(d[23]), "+f"(d[24]), "+f"(d[25]), "+f"(d[26]), "+f"(d[27]), "+f"(d[28]), "+f"(d[29]), "+f"(d[30]), "+f"(d[31])
    : "r"(a0), "r"(a1), "r"(a2), "r"(a3), "l"(db), "r"(scale_d), "n"(TB));
}
template <int TB, int TA = 0>
__device__ __forceinline__ void wgmma_ss_n160(float (&d)[80], uint64_t da, uint64_t db, int scale_d) {
  asm volatile("{\n.reg .pred p;\nsetp.ne.b32 p, %82, 0;\n"
    "wgmma.mma_async.sync.aligned.m64n160k16.f32.bf16.bf16 {%0, %1, %2, %3, %4, %5, %6, %7, %8, %9, %10, %11, %12, %13, %14, %15, %16, %17, %18, %19, %20, %21, %22, %23, %24, %25, %26, %27, %28, %29, %30, %31, %32, %33, %34, %35, %36, %37, %38, %39, %40, %41, %42, %43, %44, %45, %46, %47, %48, %49, %50, %51, %52, %53, %54, %55, %56, %57, %58, %59, %60, %61, %62, %63, %64, %65, %66, %67, %68, %69, %70, %71, %72, %73, %74, %75, %76, %77, %78, %79}, %80, %81, p, 1, 1, %83, %84;\n}\n"
    : "+f"(d[0]), "+f"(d[1]), "+f"(d[2]), "+f"(d[3]), "+f"(d[4]), "+f"(d[5]), "+f"(d[6]), "+f"(d[7]), "+f"(d[8]), "+f"(d[9]), "+f"(d[10]), "+f"(d[11]), "+f"(d[12]), "+f"(d[13]), "+f"(d[14]), "+f"(d[15]), "+f"(d[16]), "+f"(d[17]), "+f"(d[18]), "+f"(d[19]), "+f"(d[20]), "+f"(d[21]), "+f"(d[22]), "+f"(d[23]), "+f"(d[24]), "+f"(d[25]), "+f"(d[26]), "+f"(d[27]), "+f"(d[28]), "+f"(d[29]), "+f"(d[30]), "+f"(d[31]), "+f"(d[32]), "+f"(d[33]), "+f"(d[34]), "+f"(d[35]), "+f"(d[36]), "+f"(d[37]), "+f"(d[38]), "+f"(d[39]), "+f"(d[40]), "+f"(d[41]), "+f"(d[42]), "+f"(d[43]), "+f"(d[44]), "+f"(d[45]), "+f"(d[46]), "+f"(d[47]), "+f"(d[48]), "+f"(d[49]), "+f"(d[50]), "+f"(d[51]), "+f"(d[52]), "+f"(d[53]), "+f"(d[54]), "+f"(d[55]), "+f"(d[56]), "+f"(d[57]), "+f"(d[58]), "+f"(d[59]), "+f"(d[60]), "+f"(d[61]), "+f"(d[62]), "+f"(d[63]), "+f"(d[64]), "+f"(d[65]), "+f"(d[66]), "+f"(d[67]), "+f"(d[68]), "+f"(d[69]), "+f"(d[70]), "+f"(d[71]), "+f"(d[72]), "+f"(d[73]), "+f"(d[74]), "+f"(d[75]), "+f"(d[76]), "+f"(d[77]), "+f"(d[78]), "+f"(d[79])
    : "l"(da), "l"(db), "r"(scale_d), "n"(TA), "n"(TB));
}
template <int TB>
__device__ __forceinline__ void wgmma_rs_n160(float (&d)[80], uint32_t a0, uint32_t a1, uint32_t a2, uint32_t a3, uint64_t db, int scale_d) {
  asm volatile("{\n.reg .pred p;\nsetp.ne.b32 p, %85, 0;\n"
    "wgmma.mma_async.sync.aligned.m64n160k16.f32.bf16.bf16 {%0, %1, %2, %3, %4, %5, %6, %7, %8, %9, %10, %11, %12, %13, %14, %15, %16, %17, %18, %19, %20, %21, %22, %23, %24, %25, %26, %27, %28, %29, %30, %31, %32, %33, %34, %35, %36, %37, %38, %39, %40, %41, %42, %43, %44, %45, %46, %47, %48, %49, %50, %51, %52, %53, %54, %55, %56, %57, %58, %59, %60, %61, %62, %63, %64, %65, %66, %67, %68, %69, %70, %71, %72, %73, %74, %75, %76, %77, %78, %79}, {%80, %81, %82, %83}, %84, p, 1, 1, %86;\n}\n"
    : "+f"(d[0]), "+f"(d[1]), "+f"(d[2]), "+f"(d[3]), "+f"(d[4]), "+f"(d[5]), "+f"(d[6]), "+f"(d[7]), "+f"(d[8]), "+f"(d[9]), "+f"(d[10]), "+f"(d[11]), "+f"(d[12]), "+f"(d[13]), "+f"(d[14]), "+f"(d[15]), "+f"(d[16]), "+f"(d[17]), "+f"(d[18]), "+f"(d[19]), "+f"(d[20]), "+f"(d[21]), "+f"(d[22]), "+f"(d[23]), "+f"(d[24]), "+f"(d[25]), "+f"(d[26]), "+f"(d[27]), "+f"(d[28]), "+f"(d[29]), "+f"(d[30]), "+f"(d[31]), "+f"(d[32]), "+f"(d[33]), "+f"(d[34]), "+f"(d[35]), "+f"(d[36]), "+f"(d[37]), "+f"(d[38]), "+f"(d[39]), "+f"(d[40]), "+f"(d[41]), "+f"(d[42]), "+f"(d[43]), "+f"(d[44]), "+f"(d[45]), "+f"(d[46]), "+f"(d[47]), "+f"(d[48]), "+f"(d[49]), "+f"(d[50]), "+f"(d[51]), "+f"(d[52]), "+f"(d[53]), "+f"(d[54]), "+f"(d[55]), "+f"(d[56]), "+f"(d[57]), "+f"(d[58]), "+f"(d[59]), "+f"(d[60]), "+f"(d[61]), "+f"(d[62]), "+f"(d[63]), "+f"(d[64]), "+f"(d[65]), "+f"(d[66]), "+f"(d[67]), "+f"(d[68]), "+f"(d[69]), "+f"(d[70]), "+f"(d[71]), "+f"(d[72]), "+f"(d[73]), "+f"(d[74]), "+f"(d[75]), "+f"(d[76]), "+f"(d[77]), "+f"(d[78]), "+f"(d[79])
    : "r"(a0), "r"(a1), "r"(a2), "r"(a3), "l"(db), "r"(scale_d), "n"(TB));
}
template <int TB, int TA = 0>
__device__ __forceinline__ void wgmma_ss_n192(float (&d)[96], uint64_t da, uint64_t db, int scale_d) {
  asm volatile("{\n.reg .pred p;\nsetp.ne.b32 p, %98, 0;\n"
    "wgmma.mma_async.sync.aligned.m64n192k16.f32.bf16.bf16 {%0, %1, %2, %3, %4, %5, %6, %7, %8, %9, %10, %11, %12, %13, %14, %15, %16, %17, %18, %19, %20, %21, %22, %23, %24, %25, %26, %27, %28, %29, %30, %31, %32, %33, %34, %35, %36, %37, %38, %39, %40, %41, %42, %43, %44, %45, %46, %47, %48, %49, %50, %51, %52, %53, %54, %55, %56, %57, %58, %59, %60, %61, %62, %63, %64, %65, %66, %67, %68, %69, %70, %71, %72, %73, %74, %75, %76, %77, %78, %79, %80, %81, %82, %83, %84, %85, %86, %87, %88, %89, %90, %91, %92, %93, %94, %95}, %96, %97, p, 1, 1, %99, %100;\n}\n"
    : "+f"(d[0]), "+f"(d[1]), "+f"(d[2]), "+f"(d[3]), "+f"(d[4]), "+f"(d[5]), "+f"(d[6]), "+f"(d[7]), "+f"(d[8]), "+f"(d[9]), "+f"(d[10]), "+f"(d[11]), "+f"(d[12]), "+f"(d[13]), "+f"(d[14]), "+f"(d[15]), "+f"(d[16]), "+f"(d[17]), "+f"(d[18]), "+f"(d[19]), "+f"(d[20]), "+f"(d[21]), "+f"(d[22]), "+f"(d[23]), "+f"(d[24]), "+f"(d[25]), "+f"(d[26]), "+f"(d[27]), "+f"(d[28]), "+f"(d[29]), "+f"(d[30]), "+f"(d[31]), "+f"(d[32]), "+f"(d[33]), "+f"(d[34]), "+f"(d[35]), "+f"(d[36]), "+f"(d[37]), "+f"(d[38]), "+f"(d[39]), "+f"(d[40]), "+f"(d[41]), "+f"(d[42]), "+f"(d[43]), "+f"(d[44]), "+f"(d[45]), "+f"(d[46]), "+f"(d[47]), "+f"(d[48]), "+f"(d[49]), "+f"(d[50]), "+f"(d[51]), "+f"(d[52]), "+f"(d[53]), "+f"(d[54]), "+f"(d[55]), "+f"(d[56]), "+f"(d[57]), "+f"(d[58]), "+f"(d[59]), "+f"(d[60]), "+f"(d[61]), "+f"(d[62]), "+f"(d[63]), "+f"(d[64]), "+f"(d[65]), "+f"(d[66]), "+f"(d[67]), "+f"(d[68]), "+f"(d[69]), "+f"(d[70]), "+f"(d[71]), "+f"(d[72]), "+f"(d[73]), "+f"(d[74]), "+f"(d[75]), "+f"(d[76]), "+f"(d[77]), "+f"(d[78]), "+f"(d[79]), "+f"(d[80]), "+f"(d[81]), "+f"(d[82]), "+f"(d[83]), "+f"(d[84]), "+f"(d[85]), "+f"(d[86]), "+f"(d[87]), "+f"(d[88]), "+f"(d[89]), "+f"(d[90]), "+f"(d[91]), "+f"(d[92]), "+f"(d[93]), "+f"(d[94]), "+f"(d[95])
    : "l"(da), "l"(db), "r"(scale_d), "n"(TA), "n"(TB));
}
template <int TB>
__device__ __forceinline__ void wgmma_rs_n192(float (&d)[96], uint32_t a0, uint32_t a1, uint32_t a2, uint32_t a3, uint64_t db, int scale_d) {
  asm volatile("{\n.reg .pred p;\nsetp.ne.b32 p, %101, 0;\n"
    "wgmma.mma_async.sync.aligned.m64n192k16.f32.bf16.bf16 {%0, %1, %2, %3, %4, %5, %6, %7, %8, %9, %10, %11, %12, %13, %14, %15, %16, %17, %18, %19, %20, %21, %22, %23, %24, %25, %26, %27, %28, %29, %30, %31, %32, %33, %34, %35, %36, %37, %38, %39, %40, %41, %42, %43, %44, %45, %46, %47, %48, %49, %50, %51, %52, %53, %54, %55, %56, %57, %58, %59, %60, %61, %62, %63, %64, %65, %66, %67, %68, %69, %70, %71, %72, %73, %74, %75, %76, %77, %78, %79, %80, %81, %82, %83, %84, %85, %86, %87, %88, %89, %90, %91, %92, %93, %94, %95}, {%96, %97, %98, %99}, %100, p, 1, 1, %102;\n}\n"
    : "+f"(d[0]), "+f"(d[1]), "+f"(d[2]), "+f"(d[3]), "+f"(d[4]), "+f"(d[5]), "+f"(d[6]), "+f"(d[7]), "+f"(d[8]), "+f"(d[9]), "+f"(d[10]), "+f"(d[11]), "+f"(d[12]), "+f"(d[13]), "+f"(d[14]), "+f"(d[15]), "+f"(d[16]), "+f"(d[17]), "+f"(d[18]), "+f"(d[19]), "+f"(d[20]), "+f"(d[21]), "+f"(d[22]), "+f"(d[23]), "+f"(d[24]), "+f"(d[25]), "+f"(d[26]), "+f"(d[27]), "+f"(d[28]), "+f"(d[29]), "+f"(d[30]), "+f"(d[31]), "+f"(d[32]), "+f"(d[33]), "+f"(d[34]), "+f"(d[35]), "+f"(d[36]), "+f"(d[37]), "+f"(d[38]), "+f"(d[39]), "+f"(d[40]), "+f"(d[41]), "+f"(d[42]), "+f"(d[43]), "+f"(d[44]), "+f"(d[45]), "+f"(d[46]), "+f"(d[47]), "+f"(d[48]), "+f"(d[49]), "+f"(d[50]), "+f"(d[51]), "+f"(d[52]), "+f"(d[53]), "+f"(d[54]), "+f"(d[55]), "+f"(d[56]), "+f"(d[57]), "+f"(d[58]), "+f"(d[59]), "+f"(d[60]), "+f"(d[61]), "+f"(d[62]), "+f"(d[63]), "+f"(d[64]), "+f"(d[65]), "+f"(d[66]), "+f"(d[67]), "+f"(d[68]), "+f"(d[69]), "+f"(d[70]), "+f"(d[71]), "+f"(d[72]), "+f"(d[73]), "+f"(d[74]), "+f"(d[75]), "+f"(d[76]), "+f"(d[77]), "+f"(d[78]), "+f"(d[79]), "+f"(d[80]), "+f"(d[81]), "+f"(d[82]), "+f"(d[83]), "+f"(d[84]), "+f"(d[85]), "+f"(d[86]), "+f"(d[87]), "+f"(d[88]), "+f"(d[89]), "+f"(d[90]), "+f"(d[91]), "+f"(d[92]), "+f"(d[93]), "+f"(d[94]), "+f"(d[95])
    : "r"(a0), "r"(a1), "r"(a2), "r"(a3), "l"(db), "r"(scale_d), "n"(TB));
}

__device__ __forceinline__ uint32_t smem_u32(const void* p) { return (uint32_t)__cvta_generic_to_shared(p); }
__device__ __forceinline__ void wg_fence() { asm volatile("wgmma.fence.sync.aligned;" ::: "memory"); }
__device__ __forceinline__ void wg_commit() { asm volatile("wgmma.commit_group.sync.aligned;" ::: "memory"); }
template <int N> __device__ __forceinline__ void wg_wait() { asm volatile("wgmma.wait_group.sync.aligned %0;" ::"n"(N) : "memory"); }
__device__ __forceinline__ void sched_fence(uint32_t& keep, bool never) {
  asm volatile("{\n.reg .pred p;\nsetp.ne.b32 p, %1, 0;\n@p mov.u32 %0, %%clock;\n}\n" : "+r"(keep) : "r"((int)never) : "memory");
}
template <int N> __device__ __forceinline__ void fence_regs(float (&r)[N]) {
#pragma unroll
  for (int i = 0; i < N; i++) asm volatile("" : "+f"(r[i])::"memory");
}
template <int N> __device__ __forceinline__ void undefine(float (&r)[N]) {
#pragma unroll
  for (int i = 0; i < N; i++) asm volatile("" : "=f"(r[i]));
}
template <int N> __device__ __forceinline__ void fence_regs(uint32_t (&r)[N]) {
#pragma unroll
  for (int i = 0; i < N; i++) asm volatile("" : "+r"(r[i])::"memory");
}
__device__ __forceinline__ uint64_t mk_desc(uint32_t a16, uint32_t lbo, uint32_t sbo, uint32_t swz) {
  uint64_t d;
  asm("mov.b64 %0, {%1, %2};" : "=l"(d) : "r"(a16 + ((lbo >> 4) << 16)), "r"((sbo >> 4) | (swz << 30)));
  return d;
}
__device__ __forceinline__ void mbar_init(uint32_t bar, uint32_t cnt) {
  asm volatile("mbarrier.init.shared::cta.b64 [%0], %1;" ::"r"(bar), "r"(cnt) : "memory");
}
__device__ __forceinline__ void mbar_expect(uint32_t bar, uint32_t tx) {
  asm volatile("mbarrier.arrive.expect_tx.shared::cta.b64 _, [%0], %1;" ::"r"(bar), "r"(tx) : "memory");
}
__device__ __forceinline__ bool mbar_test(uint32_t bar, uint32_t ph) {
  uint32_t ok;
  asm volatile("{\n.reg .pred p;\nmbarrier.test_wait.parity.shared::cta.b64 p, [%1], %2;\nselp.u32 %0, 1, 0, p;\n}\n"
               : "=r"(ok) : "r"(bar), "r"(ph) : "memory");
  return ok;
}
__device__ __forceinline__ bool mbar_try(uint32_t bar, uint32_t ph, uint32_t ns) {
  uint32_t ok;
  asm volatile("{\n.reg .pred p;\nmbarrier.try_wait.parity.shared::cta.b64 p, [%1], %2, %3;\nselp.u32 %0, 1, 0, p;\n}\n"
               : "=r"(ok) : "r"(bar), "r"(ph), "r"(ns) : "memory");
  return ok;
}
__device__ __forceinline__ void mbar_wait(uint32_t bar, uint32_t ph) {
  asm volatile("{\n.reg .pred p;\n.reg .u32 n;\nmov.u32 n, 0;\n"
               "LOOP:\nmbarrier.try_wait.parity.shared::cta.b64 p, [%0], %1;\n@p bra DONE;\n"
               "add.u32 n, n, 1;\nsetp.lt.u32 p, n, 0x1000000;\n@p bra LOOP;\ntrap;\n"
               "DONE:\n}\n" ::"r"(bar), "r"(ph) : "memory");
}
template <int NS> __device__ __forceinline__ void mbar_wait_slow(uint32_t bar, uint32_t ph) {
  asm volatile("{\n.reg .pred p;\n.reg .u32 n;\nmov.u32 n, 0;\n"
               "LOOP:\nmbarrier.test_wait.parity.shared::cta.b64 p, [%0], %1;\n@p bra DONE;\n"
               "nanosleep.u32 %2;\nadd.u32 n, n, 1;\nsetp.lt.u32 p, n, 0x400000;\n@p bra LOOP;\ntrap;\n"
               "DONE:\n}\n" ::"r"(bar), "r"(ph), "n"(NS) : "memory");
}
__device__ __forceinline__ void mbar_arrive_cluster_if(bool on, uint32_t addr) {
  asm volatile("{\n.reg .pred p;\nsetp.ne.b32 p, %1, 0;\n@p mbarrier.arrive.shared::cluster.b64 _, [%0];\n}\n" ::"r"(addr), "r"((int)on) : "memory");
}
__device__ __forceinline__ void tma2d(uint32_t dst, const CUtensorMap* m, uint32_t bar, int c0, int c1) {
  asm volatile("cp.async.bulk.tensor.2d.shared::cluster.global.mbarrier::complete_tx::bytes [%0], [%1, {%3, %4}], [%2];"
               ::"r"(dst), "l"(m), "r"(bar), "r"(c0), "r"(c1) : "memory");
}
__device__ __forceinline__ void tma3d(uint32_t dst, const CUtensorMap* m, uint32_t bar, int c0, int c1, int c2) {
  asm volatile("cp.async.bulk.tensor.3d.shared::cluster.global.mbarrier::complete_tx::bytes [%0], [%1, {%3, %4, %5}], [%2];"
               ::"r"(dst), "l"(m), "r"(bar), "r"(c0), "r"(c1), "r"(c2) : "memory");
}
__device__ __forceinline__ void tma3d_mc(uint32_t dst, const CUtensorMap* m, uint32_t bar, int c0, int c1, int c2) {
  asm volatile("cp.async.bulk.tensor.3d.shared::cluster.global.mbarrier::complete_tx::bytes.multicast::cluster"
               " [%0], [%1, {%3, %4, %5}], [%2], %6;"
               ::"r"(dst), "l"(m), "r"(bar), "r"(c0), "r"(c1), "r"(c2), "h"((uint16_t)3) : "memory");
}
__device__ __forceinline__ void tma3d_store(const CUtensorMap* m, uint32_t src, int c0, int c1, int c2) {
  asm volatile("cp.async.bulk.tensor.3d.global.shared::cta.bulk_group [%0, {%2, %3, %4}], [%1];"
               ::"l"(m), "r"(src), "r"(c0), "r"(c1), "r"(c2) : "memory");
}
__device__ __forceinline__ void bar_sync(int id, int n) { asm volatile("bar.sync %0, %1;" ::"r"(id), "r"(n) : "memory"); }
__device__ __forceinline__ uint32_t pack_bf16(float lo, float hi) {
  uint32_t r;
  asm("cvt.rn.bf16x2.f32 %0, %1, %2;" : "=r"(r) : "f"(hi), "f"(lo));
  return r;
}
__device__ __forceinline__ float ex2(float x) {
  float y;
  asm("ex2.approx.ftz.f32 %0, %1;" : "=f"(y) : "f"(x));
  return y;
}
__device__ __forceinline__ float rcp(float x) {
  float y;
  asm("rcp.approx.ftz.f32 %0, %1;" : "=f"(y) : "f"(x));
  return y;
}
__device__ __forceinline__ void stsm4(uint32_t addr, uint32_t a, uint32_t b, uint32_t c, uint32_t d) {
  asm volatile("stmatrix.sync.aligned.m8n8.x4.shared.b16 [%0], {%1, %2, %3, %4};" ::"r"(addr), "r"(a), "r"(b), "r"(c), "r"(d) : "memory");
}

__device__ __forceinline__ void tma4d_mc_hint(uint32_t dst, const CUtensorMap* m, uint32_t bar, int c3, uint64_t pol) {
  asm volatile("cp.async.bulk.tensor.4d.shared::cluster.global.mbarrier::complete_tx::bytes.multicast::cluster.L2::cache_hint"
               " [%0], [%1, {%3, %3, %3, %4}], [%2], %5, %6;"
               ::"r"(dst), "l"(m), "r"(bar), "r"(0), "r"(c3), "h"((uint16_t)3), "l"(pol) : "memory");
}
__device__ __forceinline__ void tma5d_mc(uint32_t dst, const CUtensorMap* m, uint32_t bar, int c2, int c4) {
  asm volatile("cp.async.bulk.tensor.5d.shared::cluster.global.mbarrier::complete_tx::bytes.multicast::cluster"
               " [%0], [%1, {%3, %3, %4, %3, %5}], [%2], %6;"
               ::"r"(dst), "l"(m), "r"(bar), "r"(0), "r"(c2), "r"(c4), "h"((uint16_t)3) : "memory");
}
__device__ __forceinline__ void bulk_load_hint(uint32_t dst, const void* src, uint32_t bytes, uint32_t bar, uint64_t pol) {
  asm volatile("cp.async.bulk.shared::cluster.global.mbarrier::complete_tx::bytes.L2::cache_hint [%0], [%1], %2, [%3], %4;"
               ::"r"(dst), "l"(src), "r"(bytes), "r"(bar), "l"(pol) : "memory");
}
__device__ __forceinline__ void stg128_hint(void* p, uint32_t a, uint32_t b, uint32_t c, uint32_t d, uint64_t pol) {
  asm volatile("st.global.L2::cache_hint.v4.b32 [%0], {%1, %2, %3, %4}, %5;" ::"l"(p), "r"(a), "r"(b), "r"(c), "r"(d), "l"(pol) : "memory");
}
__device__ __forceinline__ void stg2_if(bool on, void* p, uint32_t a, uint32_t b, uint32_t c, uint32_t d, uint32_t e, uint32_t f,
                                        uint32_t g, uint32_t h, uint64_t pol) {
  asm volatile("{\n.reg .pred p;\nsetp.ne.b32 p, %10, 0;\n"
               "@p st.global.L2::cache_hint.v4.b32 [%0], {%1, %2, %3, %4}, %9;\n"
               "@p st.global.L2::cache_hint.v4.b32 [%0 + 512], {%5, %6, %7, %8}, %9;\n}\n"
               ::"l"(p), "r"(a), "r"(b), "r"(c), "r"(d), "r"(e), "r"(f), "r"(g), "r"(h), "l"(pol), "r"((int)on) : "memory");
}
__device__ __forceinline__ uint64_t make_policy(bool first) {
  uint64_t pf, pn;
  asm("createpolicy.fractional.L2::evict_first.b64 %0, 1.0;" : "=l"(pf));
  asm("createpolicy.fractional.L2::evict_normal.b64 %0, 1.0;" : "=l"(pn));
  return first ? pf : pn;
}
__device__ __forceinline__ bool elect() {
  uint32_t ok;
  asm volatile("{\n.reg .pred p;\nelect.sync _|p, 0xffffffff;\nselp.u32 %0, 1, 0, p;\n}\n" : "=r"(ok));
  return ok;
}
__device__ __forceinline__ void mbar_arrive(uint32_t bar) {
  asm volatile("mbarrier.arrive.shared::cta.b64 _, [%0];" ::"r"(bar) : "memory");
}
__device__ __forceinline__ void mbar_arrive_if(bool on, uint32_t bar) {
  asm volatile("{\n.reg .pred p;\nsetp.ne.b32 p, %1, 0;\n@p mbarrier.arrive.shared::cta.b64 _, [%0];\n}\n" ::"r"(bar), "r"((int)on) : "memory");
}
__device__ __forceinline__ void stg128(void* p, uint32_t a, uint32_t b, uint32_t c, uint32_t d) {
  asm volatile("st.global.v4.b32 [%0], {%1, %2, %3, %4};" ::"l"(p), "r"(a), "r"(b), "r"(c), "r"(d) : "memory");
}
__device__ __forceinline__ void lds2_if(bool on, uint32_t p, uint32_t (&t)[8]) {
  asm volatile("{\n.reg .pred p;\nsetp.ne.b32 p, %9, 0;\n@p ld.shared.v4.b32 {%0, %1, %2, %3}, [%8];\n@p ld.shared.v4.b32 {%4, %5, %6, %7}, [%8 + 512];\n}\n"
               : "+r"(t[0]), "+r"(t[1]), "+r"(t[2]), "+r"(t[3]), "+r"(t[4]), "+r"(t[5]), "+r"(t[6]), "+r"(t[7]) : "r"(p), "r"((int)on) : "memory");
}
__device__ __forceinline__ void lds128(uint32_t p, uint32_t& a, uint32_t& b, uint32_t& c, uint32_t& d) {
  asm volatile("ld.shared.v4.b32 {%0, %1, %2, %3}, [%4];" : "=r"(a), "=r"(b), "=r"(c), "=r"(d) : "r"(p) : "memory");
}
template <class T> __device__ __forceinline__ T* ptr_add(T* base, uint32_t bytes) {
  T* r;
  asm("{\n.reg .u32 lo, hi;\nmov.b64 {lo, hi}, %1;\nadd.cc.u32 lo, lo, %2;\naddc.u32 hi, hi, 0;\nmov.b64 %0, {lo, hi};\n}\n" : "=l"(r) : "l"(base), "r"(bytes));
  return r;
}
__device__ __forceinline__ uint32_t lds32(uint32_t p) {
  uint32_t v;
  asm volatile("ld.volatile.shared.u32 %0, [%1];" : "=r"(v) : "r"(p) : "memory");
  return v;
}
__device__ __forceinline__ uint32_t flag_get(const unsigned int* p) {
  uint32_t v;
  asm volatile("ld.acquire.gpu.global.u32 %0, [%1];" : "=r"(v) : "l"(p) : "memory");
  return v;
}
__device__ __forceinline__ uint32_t wait_word(uint32_t p, uint32_t target) {
  uint32_t v;
  asm volatile("{\n.reg .pred p;\n.reg .u32 n;\nmov.u32 n, 0;\n"
               "LOOP:\nld.acquire.cta.shared.u32 %0, [%1];\nsetp.ge.u32 p, %0, %2;\n@p bra DONE;\n"
               "nanosleep.u32 %3;\nadd.u32 n, n, 1;\nsetp.lt.u32 p, n, 0x400000;\n@p bra LOOP;\ntrap;\n"
               "DONE:\n}\n" : "=r"(v) : "r"(p), "r"(target), "n"(400) : "memory");
  return v;
}
__device__ __forceinline__ void flag_set(unsigned int* p, uint32_t v) {
  asm volatile("st.release.gpu.global.u32 [%0], %1;" ::"l"(p), "r"(v) : "memory");
}
__device__ __forceinline__ void flag_dec(unsigned int* p) {
  asm volatile("red.relaxed.gpu.global.add.u32 [%0], 0xffffffff;" ::"l"(p) : "memory");
}

struct Cursor {
  int bi;
  uint32_t ph;
  __device__ __forceinline__ void next() {
    if (++bi == NBAR) { bi = 0; ph ^= 1; }
  }
};

constexpr float kScaleLog2 = 0.07216878364870322f * 1.4426950408889634f;
constexpr float kSumLimit = 1048576.0f;

__global__ void __cluster_dims__(2, 1, 1) __launch_bounds__(384, 1)
fused_kernel(const __grid_constant__ Params P) {
  extern __shared__ uint8_t smem_raw[];
  const uint32_t sbase = (smem_u32(smem_raw) + 1023) & ~1023u;
  const uint32_t full0 = sbase + RING, empty0 = full0 + 8 * NBAR, odone0 = empty0 + 8 * NBAR, ev0 = odone0 + 8 * MAX_OPS;
  const uint32_t progress = ev0 + 8 * MAX_EV, jobw = progress + 4;
  const uint32_t rank = blockIdx.x & 1;
  const int role = blockIdx.x >> 1;
  const int wid = __shfl_sync(0xffffffffu, (int)(threadIdx.x >> 5), 0);
  const int wg = wid >> 2;

  if (wid < 8) {
    if (elect()) {
#pragma unroll
      for (int j = 0; j < 16; j++) {
        const int i = EARLY + 16 * wid + j;
        if (i < 2 * NBAR + MAX_OPS + MAX_EV) mbar_init(full0 + 8 * i, i < NBAR ? 1 : i < 2 * NBAR ? 16 : i < 2 * NBAR + MAX_OPS ? 8 : 1);
      }
      if (wid == 7) asm volatile("st.shared.v2.u32 [%0], {0, 0};\nfence.acq_rel.cta;" ::"r"(progress) : "memory");
      asm volatile("fence.mbarrier_init.release.cluster;" ::: "memory");
    }
  } else if (wid == 8) {
    const uint32_t op0 = P.first[role];
    if (elect()) {
#pragma unroll
      for (int k = 0; k < EARLY; k++) mbar_init(full0 + 8 * k, 1);
      asm volatile("fence.mbarrier_init.release.cluster;" ::: "memory");
      const int blk = (op0 >> 10) & 1;
      if ((op0 & 3) == OP_Q) {
#pragma unroll
        for (int k = 0; k < EARLY; k++) {
          mbar_expect(full0 + 8 * k, SZ_Q);
          tma2d(sbase + k * SZ_Q, &P.x[blk], full0 + 8 * k, 64 * k, ((op0 >> 7) & 7) * kSq + rank * 128);
          tma3d(sbase + k * SZ_Q + 16384, &P.wq[blk], full0 + 8 * k, 0, 64 * k, 3 * ((op0 >> 2) & 31));
        }
      }
      asm volatile("prefetch.tensormap [%0];" ::"l"(rank ? &P.v[blk] : &P.k[blk]) : "memory");
    }
  }
  __syncwarp();
  asm volatile("barrier.cluster.arrive.relaxed.aligned;\nbarrier.cluster.wait.aligned;" ::: "memory");

  if (wg < 2) {
    asm volatile("setmaxnreg.inc.sync.aligned.u32 240;");
    const uint32_t* prog = P.prog[role].c;
    const int lane = threadIdx.x & 31, warp = wid & 3;
    uint32_t empty_rem;
    asm volatile("mapa.shared::cluster.u32 %0, %1, %2;" : "=r"(empty_rem) : "r"(empty0), "r"(lane & 1));
    auto release = [&](int slot) { mbar_arrive_cluster_if(lane < 2, empty_rem + 8 * slot); };
    Cursor r{0, 0};
    const uint32_t ring16 = (sbase & 0x3FFFF) >> 4;
    uint32_t cur = ring16;
    bool rdy0 = false, rdy1 = false;
    auto probe1 = [&]() { rdy0 = mbar_test(full0 + 8 * r.bi, r.ph); };
    auto probe2 = [&]() {
      Cursor n = r;
      rdy0 = mbar_test(full0 + 8 * n.bi, n.ph);
      n.next();
      rdy1 = mbar_test(full0 + 8 * n.bi, n.ph);
    };
    auto take = [&](bool rdy, uint32_t bytes, uint32_t& addr) {
      const int bi = r.bi;
      if (__builtin_expect(!__all_sync(0xffffffffu, rdy), 0)) mbar_wait(full0 + 8 * r.bi, r.ph);
      r.next();
      if (cur > ring16 + ((RING - bytes) >> 4)) cur = ring16;
      addr = cur;
      cur += bytes >> 4;
      return bi;
    };
    uint32_t keep = lane;
    const bool never = P.dbg == 0xffffffffu;
    uint32_t q[48];
#pragma unroll
    for (int i = 0; i < 48; i++) q[i] = 0;
    const int row = wg * 64 + warp * 16 + (lane >> 2);
    const int img0 = row * 4 + ((lane & 3) ^ ((row >> 1) & 3));
    uint4* pend = nullptr;
    bool pend_any = false;
    uint64_t spol;
    int pc = 0;
    auto slab = [&](int c, int i0) {
#pragma unroll
      for (int i = i0; i < 6; i++)
        stg2_if(c == i, pend + i * 512, q[8 * i], q[8 * i + 1], q[8 * i + 2], q[8 * i + 3],
                q[8 * i + 4], q[8 * i + 5], q[8 * i + 6], q[8 * i + 7], spol);
    };
    auto drain = [&](int c) {
      if (!pend_any || c >= 6) return;
      slab(c, 0);
      if (c == 5) {
        __syncwarp();
        mbar_arrive_if(lane == 0, odone0 - 8 + 8 * pc);
      }
    };

    for (;; pc++) {
      uint32_t op = prog[pc];
      const int type = op & 3;
      auto enter = [&]() {
        r.bi = (op >> 15) & 15; r.ph = (op >> 19) & 1; cur = ring16 + (((op >> 20) & 63) << 8);
      };
      enter();
      pend_any = op & C_PEND;
      spol = make_policy(!(op & C_SOON));
      uint32_t job = 0;
      if ((op & (3 | C_WIDE)) == OP_O) job = __shfl_sync(0xffffffffu, wait_word(jobw, 1), 0);
      if (type == OP_END || job == OP_O) {
#pragma unroll 1
        for (int c = 0; c < 6; c++) drain(c);
        asm volatile("barrier.cluster.arrive.relaxed;" ::: "memory");
        break;
      }
      {
        float s[32], o[96];
        uint32_t ad0;
        int bi0, sk1;
        uint32_t pa[16], pb[16];
        float mc0, mc1, l0, l1;
        bool shifted;
        uint32_t nop;
        auto expo = [&](float (&s)[32], uint32_t (&pout)[16], float& b0, float& b1, bool shift, auto mid) {
          float c0, c1;
#pragma unroll
          for (int i = 0; i < 8; i++) {
            const float e0 = ex2(shift ? s[4 * i] - mc0 : s[4 * i]), e1 = ex2(shift ? s[4 * i + 1] - mc0 : s[4 * i + 1]);
            const float e2 = ex2(shift ? s[4 * i + 2] - mc1 : s[4 * i + 2]), e3 = ex2(shift ? s[4 * i + 3] - mc1 : s[4 * i + 3]);
            if (i) { b0 += e0; c0 += e1; b1 += e2; c1 += e3; } else { b0 = e0; c0 = e1; b1 = e2; c1 = e3; }
            pout[2 * i] = pack_bf16(e0, e1); pout[2 * i + 1] = pack_bf16(e2, e3);
            if (i & 1) mid(i >> 1);
          }
          b0 += c0; b1 += c1;
        };
        auto rowmax = [&](float (&s)[32], float& m0, float& m1) {
          m0 = fmaxf(s[0], s[1]); m1 = fmaxf(s[2], s[3]);
#pragma unroll
          for (int i = 1; i < 8; i++) { m0 = fmaxf(m0, fmaxf(s[4 * i], s[4 * i + 1])); m1 = fmaxf(m1, fmaxf(s[4 * i + 2], s[4 * i + 3])); }
          m0 = fmaxf(m0, __shfl_xor_sync(0xffffffffu, m0, 1)); m1 = fmaxf(m1, __shfl_xor_sync(0xffffffffu, m1, 1));
          m0 = fmaxf(m0, __shfl_xor_sync(0xffffffffu, m0, 2)); m1 = fmaxf(m1, __shfl_xor_sync(0xffffffffu, m1, 2));
        };
        auto first = [&](float (&s)[32], int sk0, auto mid) {
          fence_regs(s);
          release(sk0);
          mc0 = 0.f; mc1 = 0.f;
          expo(s, pa, l0, l1, false, mid);
          shifted = __any_sync(0xffffffffu, !(fmaxf(l0, l1) <= kSumLimit && fminf(l0, l1) >= 1.f / kSumLimit));
          if (shifted) {
            rowmax(s, mc0, mc1);
            expo(s, pa, l0, l1, true, [](int) {});
          }
        };
        auto qk = [&](float (&s)[32], uint32_t ak, int k0 = 0, int k1 = 12) {
#pragma unroll
          for (int kk = k0; kk < k1; kk++)
            wgmma_rs_n64<0>(s, q[4 * kk], q[4 * kk + 1], q[4 * kk + 2], q[4 * kk + 3], mk_desc(ak, 16, KV_SBO, 1) + ((kk >> 2) * KV_CH + (kk & 3) * 2), kk != 0);
          if (k1 == 12) wg_commit();
        };
        auto pv = [&](uint32_t (&pin)[16], uint32_t av, int acc) {
#pragma unroll
          for (int kk = 0; kk < 4; kk++)
            wgmma_rs_n192<1>(o, pin[4 * kk], pin[4 * kk + 1], pin[4 * kk + 2], pin[4 * kk + 3], mk_desc(av, KV_CH * 16, KV_SBO, 1) + (kk * (KV_SBO / 8)), acc || (kk != 0));
          wg_commit();
        };
        auto finish = [&](uint32_t (&pout)[16], int sk, int sv) {
          probe2();
          wg_wait<1>();
          fence_regs(s);
          release(sk);
          float b0, b1;
#pragma unroll 1
          for (bool redo = false;; redo = true) {
            expo(s, pout, b0, b1, false, [](int) {});
            if (!__any_sync(0xffffffffu, !redo && (shifted || !(fmaxf(b0, b1) <= kSumLimit)))) break;
            shifted = true;
            rowmax(s, b0, b1);
            b0 = fmaxf(mc0, b0); b1 = fmaxf(mc1, b1);
            const float a0 = ex2(mc0 - b0), a1 = ex2(mc1 - b1);
            mc0 = b0; mc1 = b1;
            l0 *= a0; l1 *= a1;
            wg_wait<0>();
            fence_regs(o);
#pragma unroll
            for (int i = 0; i < 24; i++) { o[4 * i] *= a0; o[4 * i + 1] *= a0; o[4 * i + 2] *= a1; o[4 * i + 3] *= a1; }
#pragma unroll
            for (int i = 0; i < 32; i++) s[i] -= (i & 2) ? mc1 : mc0;
          }
          l0 += b0; l1 += b1;
          wg_wait<0>();
          fence_regs(o);
          release(sv);
        };
        auto step = [&](uint32_t (&pin)[16], uint32_t (&pout)[16]) {
          uint32_t ak, av;
          const int sk = take(rdy0, SZ_KV, ak), sv = take(rdy1, SZ_KV, av);
          wg_fence();
          qk(s, ak);
          pv(pin, av, 1);
          finish(pout, sk, sv);
        };
        auto unpark = [&]() {
          uint32_t ad, ak;
          const int bi = take(rdy0, SZ_PARK, ad);
#pragma unroll
          for (int i = 0; i < 12; i++) lds128(sbase + (ad - ring16 + img0) * 16 + (i >> 1) * 8192 + (i & 1) * 512, q[4 * i], q[4 * i + 1], q[4 * i + 2], q[4 * i + 3]);
          const int sk0 = take(false, SZ_KV, ak);
          fence_regs(q);
          release(bi);
          wg_fence();
          qk(s, ak);
          probe2();
          return sk0;
        };
        auto mma4 = [&](uint32_t ad, int acc) {
#pragma unroll
          for (int kk = 0; kk < 4; kk++)
            wgmma_ss_n192<1>(o, mk_desc(ad + wg * 512, 16, 1024, 1) + (kk * 2), mk_desc(ad, 8192, 1024, 1) + (1024 + kk * 128), acc || kk != 0);
        };
        auto convert = [&](int i0, int i1) {
          sched_fence(keep, never);
#pragma unroll
          for (int i = i0; i < i1; i++) {
            q[i] = pack_bf16(o[2 * i] * kScaleLog2, o[2 * i + 1] * kScaleLog2);
            if (i % CONV_G == CONV_G - 1 && i != i1 - 1) sched_fence(keep, never);
          }
          sched_fence(keep, never);
        };
        auto kend = [&](int bi, int k) {
          wg_commit();
          drain(k < 8 ? (QDRAIN >> (4 * k)) & 7 : 7);
          probe1();
          wg_wait<0>();
          release(bi);
        };
        if (type == OP_O) {
          float c[80];
          int prev = 0;
          auto hand_over = [&](float (&c)[80], uint4* dst) {
            fence_regs(c);
#pragma unroll
            for (int i = 0; i < 48; i++) q[i] = i < 8 ? 0 : pack_bf16(c[2 * i - 16], c[2 * i - 15]);
            pend = dst;
          };
          auto mma2 = [&](float (&c)[80], uint32_t ad, uint32_t oa, uint32_t ob, int acc) {
            wgmma_ss_n160<1>(c, mk_desc(ad + wg * 256, 16, 512, 2) + (oa), mk_desc(ad, 2048, 512, 2) + (1024 + ob), acc);
            wgmma_ss_n160<1>(c, mk_desc(ad + wg * 256, 16, 512, 2) + (oa + 2), mk_desc(ad, 2048, 512, 2) + (1024 + ob + 64), 1);
          };
          auto kstep = [&](float (&c)[80], int acc, auto hook, uint32_t bytes = SZ_O) {
            uint32_t ad;
            const int bi = take(rdy0, bytes, ad);
            wg_fence();
            mma2(c, ad, 0, 0, acc);
            wg_commit();
            if (acc) { wg_wait<1>(); mbar_arrive_cluster_if(lane < 2 && (acc == 1 || wg == 0), empty_rem + 8 * prev); }
            mma2(c, ad, 512, 640, 1);
            wg_commit();
            prev = bi;
            hook();
            probe1();
            wg_wait<1>();
          };
          if (op & C_WIDE) {
            float d[80];
            const int nk = 3 * ((op >> 2) & 63);
            uint4* part = ptr_add(P.g->part, (((op >> 8) & 63) * 2 + rank) * SZ_PARK + img0 * 16);
            auto wstep = [&](int acc, auto hook) {
              uint32_t ad;
              const int bi = take(rdy0, SZ_W, ad);
              wg_fence();
              mma2(d, ad, 0, 0, acc);
              mma2(d, ad, 512, 640, 1);
              wg_commit();
              if (acc) { wg_wait<1>(); release(prev); }
              mma2(c, ad, 0, 1280, acc);
              mma2(c, ad, 512, 1920, 1);
              wg_commit();
              prev = bi;
              hook();
              probe1();
              wg_wait<1>();
            };
            wstep(0, [&]() { drain(0); drain(1); });
#pragma unroll 1
            for (int k = 2; k < 6; k += 2) wstep(1, [&]() { drain(k); drain(k + 1); });
#pragma unroll 1
            for (int k = 3 + 3 * TAIL; k < nk; k++) {
              wstep(1, []() {});
            }
#pragma unroll 1
            for (int k = 0; k < 3 * TAIL; k++) kstep(d, 1, []() {});
            nop = prog[pc + 1];
            spol = make_policy(!(nop & C_SOON));
            kstep(c, 1, [&]() { hand_over(d, part - 6144); });
#pragma unroll 1
            for (int k = 1; k < 3 * TAIL; k++) kstep(c, 1, [&]() { slab(TAIL == 2 ? k : (0x50403201 >> (4 * k - 4)) & 7, 1); });
            if ((nop & 3) == OP_Q) {
              op = nop;
              enter();
              pc++;
              pend_any = true;
              bi0 = take(rdy0, SZ_Q, ad0);
              undefine(o);
              wg_fence();
              mma4(ad0, 0);
              wg_commit();
              wg_wait<1>();
              release(prev);
              hand_over(c, part);
              probe1();
              wg_wait<0>();
              release(bi0);
              fence_regs(o);
              goto next_head;
            }
            wg_wait<0>();
            release(prev);
            hand_over(c, part);
            continue;
          }
          auto unblock = [&](int k) {
            if (__all_sync(0xffffffffu, rdy0) || __all_sync(0xffffffffu, mbar_try(full0 + 8 * r.bi, r.ph, TRYNS))) return;
#pragma unroll 1
            for (; k < 6; k++) drain(k);
            pend_any = false;
          };
          unblock(0);
          kstep(c, 0, [&]() { drain(0); });
          int left = 3 * ((job >> 13) & 63) - 6;
#pragma unroll 1
          for (uint32_t k = 1, pace = left >= 3 * SLOWF - 6 ? SLOWP : left <= 3 * FASTF - 6 ? FASTP : 0x155; k < 6; pace >>= 2, left--) {
            unblock(k);
            kstep(c, 1, [&]() {
#pragma unroll 1
              for (int i = pace & 3; i > 0; i--) drain(k++);
            });
          }
#pragma unroll 1
          for (; left > 0; left--) kstep(c, 1, []() {});
          uint32_t t[8], stage[3];
          float u[80];
          auto unpack = [&](int j) {
#pragma unroll
            for (int i = 0; i < 8; i++) {
              u[16 * j + 2 * i] = __uint_as_float(t[i] << 16); u[16 * j + 2 * i + 1] = __uint_as_float(t[i] & 0xffff0000u);
              asm volatile("" : "+f"(u[16 * j + 2 * i]), "+f"(u[16 * j + 2 * i + 1]));
            }
          };
#pragma unroll
          for (int i = 0; i < 8; i++) t[i] = 0;
          const uint32_t bytes = (job & P_LD) ? SZ_OL : SZ_O;
#pragma unroll
          for (int j = 0; j < 5; j++) {
            if (j == 5 - SKEW && wg == 1) {
              wg_wait<0>();
              release(prev);
              bar_sync(1, 256);
            }
            kstep(c, j == 5 - SKEW ? 2 : 1, [&]() {
              if (SKEW && j == 4) asm volatile("{\n.reg .pred p;\nsetp.eq.u32 p, %0, 0;\n@p bar.arrive 1, 256;\n}\n" ::"r"(wg) : "memory");
              if (j) unpack(j - 1);
              lds2_if(job & P_LD, sbase + (cur - ring16 + img0) * 16 - 8192, t);
              if (j >= 1 && j <= 3) stage[j - 1] = sbase + (cur - ring16) * 16 - bytes + wid * 1024;
            }, bytes);
          }
          unpack(4);
          sched_fence(keep, never);
          wg_wait<0>();
          fence_regs(c);
          release(prev);
          asm volatile("barrier.cluster.arrive.relaxed;" ::: "memory");
#pragma unroll
          for (int i = 0; i < 10; i++) {
            const int v = (i & 1) * 2 + (lane >> 4);
            const uint32_t sa = stage[i >> 2] + (i & 2) * 4096;
            stsm4(sa + (lane & 15) * 64 + ((v ^ ((lane >> 1) & 3)) << 4), pack_bf16(c[8 * i] + u[8 * i], c[8 * i + 1] + u[8 * i + 1]),
                  pack_bf16(c[8 * i + 2] + u[8 * i + 2], c[8 * i + 3] + u[8 * i + 3]), pack_bf16(c[8 * i + 4] + u[8 * i + 4], c[8 * i + 5] + u[8 * i + 5]),
                  pack_bf16(c[8 * i + 6] + u[8 * i + 6], c[8 * i + 7] + u[8 * i + 7]));
          }
          asm volatile("fence.proxy.async.shared::cta;" ::: "memory");
          __syncwarp();
          if (elect()) {
#pragma unroll
            for (int i = 0; i < 5; i++)
              tma3d_store(&P.out, stage[i >> 1] + (i & 1) * 8192, 0, ((job >> 7) & 7) * kSq + rank * 128 + wid * 16, ((job >> 10) & 1) * 20 + ((job >> 19) & 3) * 5 + i);
            asm volatile("cp.async.bulk.commit_group;\ncp.async.bulk.wait_group.read 0;" ::: "memory");
          }
          __syncwarp();
          break;
        }
        bi0 = take(rdy0, SZ_Q, ad0);
        undefine(o);
        wg_fence();
        mma4(ad0, 0);
        kend(bi0, 0);
        fence_regs(o);
      next_head:
        {
#pragma unroll 1
          for (int k = 1; k < ((op & F_PARK) ? 10 : 8); k++) {
            uint32_t ad;
            const int bi = take(rdy0, SZ_Q, ad);
            wg_fence();
            mma4(ad, 1);
            kend(bi, k);
          }
          if (op & F_PARK) {
            fence_regs(o);
            convert(0, 48);
            pend = ptr_add(P.g->tile, (((op >> 2) & 511) * 2 + rank) * SZ_PARK + img0 * 16);
            continue;
          }
          uint32_t a8, a9, ak0, ak1;
          const int b8 = take(rdy0, SZ_Q, a8), b9 = take(false, SZ_Q, a9);
          wg_fence();
          mma4(a8, 1);
          wg_commit();
          mma4(a9, 1);
          wg_commit();
          pc++;
          wg_wait<1>();
          release(b8);
          const int sk0 = take(false, SZ_KV, ak0);
          wg_wait<0>();
          fence_regs(o);
          release(b9);
          float s0[32];
          convert(0, CONV_0);
          wg_fence();
          qk(s0, ak0, 0, 4);
          convert(CONV_0, 48);
          wg_fence();
          qk(s0, ak0, 4, 12);
          sk1 = take(false, SZ_KV, ak1);
          probe1();
          wg_wait<0>();
          first(s0, sk0, [&](int i) {
            if (i != QA && i != QB && i != QC) return;
            sched_fence(keep, never);
            wg_fence();
            if (i == QA) qk(s, ak1, 0, 4);
            if (i == QB) qk(s, ak1, 4, 8);
            if (i == QC) qk(s, ak1, 8, 12);
            sched_fence(keep, never);
          });
        }
        for (;;) {
          {
            uint32_t av;
            const int sv = take(rdy0, SZ_KV, av);
            undefine(o);
            wg_fence();
            pv(pa, av, 0);
            finish(pb, sk1, sv);
          }
          nop = prog[pc + 1];
#pragma unroll 1
          for (int jj = 0; jj < 7; jj++) {
            step(pb, pa);
            step(pa, pb);
          }
          float i0, i1;
          auto last = [&]() {
            uint32_t av;
            const int sv = take(rdy0, SZ_KV, av);
            wg_fence();
            pv(pb, av, 1);
            sched_fence(keep, never);
            probe1();
            l0 += __shfl_xor_sync(0xffffffffu, l0, 1); l1 += __shfl_xor_sync(0xffffffffu, l1, 1);
            l0 += __shfl_xor_sync(0xffffffffu, l0, 2); l1 += __shfl_xor_sync(0xffffffffu, l1, 2);
            i0 = rcp(l0); i1 = rcp(l1);
            pend = ptr_add(P.g->tile, (((op >> 2) & 511) * 2 + rank) * SZ_PARK + img0 * 16);
            return sv;
          };
          auto normalise = [&](uint32_t (&d)[48], auto mid) {
#pragma unroll
            for (int i = 0; i < 24; i++) {
              d[8 * (i >> 2) + (i & 3)] = pack_bf16(o[4 * i] * i0, o[4 * i + 1] * i0);
              d[8 * (i >> 2) + (i & 3) + 4] = pack_bf16(o[4 * i + 2] * i1, o[4 * i + 3] * i1);
              if (i % NORM_G == NORM_G - 1 && i != 23) sched_fence(keep, never);
              if ((i & 3) == 3 && i != 23) mid(i >> 2);
            }
          };
          const int sv = last();
          if ((nop & 3) != OP_A) {
            op = nop;
            enter();
            pend_any = true;
            spol = make_policy(!(op & C_SOON));
            bi0 = take(rdy0 || (nop & 3) != OP_Q, SZ_Q, ad0);
            sched_fence(keep, never);
            wg_wait<0>();
            fence_regs(o);
            release(sv);
            normalise(q, [](int) {});
            undefine(o);
            if ((nop & 3) != OP_Q) break;
            sched_fence(keep, never);
            wg_fence();
            mma4(ad0, 0);
            pc++;
            kend(bi0, 0);
            fence_regs(o);
            goto next_head;
          }
          const int sk0 = unpark();
          wg_wait<1>();
          fence_regs(o);
          release(sv);
          uint32_t t[48];
          spol = make_policy(!(nop & C_SOON));
          auto st = [&](int i) {
            stg2_if(true, pend + i * 512, t[8 * i], t[8 * i + 1], t[8 * i + 2], t[8 * i + 3], t[8 * i + 4], t[8 * i + 5], t[8 * i + 6], t[8 * i + 7], spol);
          };
          normalise(t, [&](int i) { if (!(i & 1)) st(i >> 1); });
          wg_wait<0>();
          first(s, sk0, [&](int i) { if (i < 3) { sched_fence(keep, never); st(3 + i); } });
          __syncwarp();
          mbar_arrive_if(lane == 0, odone0 + 8 * pc);
          pc++;
          op = nop;
          uint32_t ak1;
          sk1 = take(rdy0, SZ_KV, ak1);
          rdy0 = rdy1;
          wg_fence();
          qk(s, ak1);
        }
      }
    }
    if (never) P.g->flag[0] = keep;
    asm volatile("barrier.cluster.wait;" ::: "memory");
  } else {
    asm volatile("setmaxnreg.dec.sync.aligned.u32 24;");
    const uint32_t* prog = P.prog[role].p;
    unsigned int* flag = P.g->flag + rank;
    if (wid == 8) {
      Cursor tail{0, 0};
      int head = 0, sh = 0;
      uint32_t cur = 0, used = 0;
      uint64_t fifo = 0;
      uint32_t dst, bar, ev = ev0, done = 0;
      uint64_t pol;
      asm volatile("createpolicy.fractional.L2::evict_first.b64 %0, 1.0;" : "=l"(pol));
      auto retire = [&]() {
        mbar_wait(empty0 + 8 * tail.bi, tail.ph);
        tail.next();
        used -= (uint32_t)fifo & 31;
        fifo >>= 5;
        sh -= 5;
        asm volatile("st.volatile.shared.u32 [%0], %1;" ::"r"(progress), "r"(++done) : "memory");
      };
      auto acquire = [&](uint32_t bytes) {
        uint32_t fp = bytes >> 12;
        if (cur + fp > (RING >> 12)) { fp += (RING >> 12) - cur; cur = 0; }
        used += fp;
        while (used > (RING >> 12) || sh == 5 * NBAR) retire();
        fifo |= (uint64_t)fp << sh;
        sh += 5;
        dst = sbase + (cur << 12);
        bar = full0 + 8 * head;
        cur += bytes >> 12;
        if (++head == NBAR) head = 0;
      };
      auto gate = [&]() {
        mbar_wait(ev, 0);
        ev += 8;
        asm volatile("fence.proxy.async.global;" ::: "memory");
      };
      for (int pc = 0;; pc++) {
        uint32_t op = prog[pc];
        const int type = op & 3;
        if (type == OP_END) break;
        if (op == OP_O) {
          gate();
          op = __shfl_sync(0xffffffffu, lds32(jobw), 0);
        }
        const int blk = (op >> 10) & 1;
        if (type == OP_Q) {
#pragma unroll 1
          for (int k = 0; k < 10; k++) {
            if (k == 9 && (op & P_GATE)) gate();
            acquire(SZ_Q);
            if ((pc > 0 || k >= EARLY) && elect()) {
              mbar_expect(bar, SZ_Q);
              tma2d(dst, &P.x[blk], bar, 64 * k, ((op >> 7) & 7) * kSq + rank * 128);
              if ((k & 1) == rank) tma3d_mc(dst + 16384, &P.wq[blk], bar, 0, 64 * k, 3 * ((op >> 2) & 31));
            }
          }
        } else if (type == OP_A) {
          const int row0 = ((op >> 2) & 255) * kSk;
          const CUtensorMap* kv_map = rank ? &P.v[blk] : &P.k[blk];
          if (op & F_PARK) {
            gate();
            acquire(SZ_PARK);
            if (elect()) {
              mbar_expect(bar, SZ_PARK);
              bulk_load_hint(dst, &P.g->tile[((op >> 20) * 2 + rank) * 3072], SZ_PARK, bar, make_policy(P.dbg & 4));
            }
          }
#pragma unroll 1
          for (int t = 0; t < 32; t++) {
            const int isv = t == 31 ? 1 : (t == 0 ? 0 : (~t & 1));
            const int j = isv ? (t - 1) >> 1 : (t + 1) >> 1;
            if (t == 31 && (op & P_GATE)) gate();
            acquire(SZ_KV);
            if (elect()) {
              mbar_expect(bar, SZ_KV);
              if (isv == (int)rank) tma4d_mc_hint(dst, kv_map, bar, row0 / 8 + 8 * j, pol);
            }
          }
        } else {
          const int n = (op >> 13) & 63, nw = (op & P_WIDE) ? n - TAIL : 0;
          const uint64_t pol_o = make_policy(P.dbg & (nw ? 1 : 2));
          const uint4* part = &P.g->part[((((op >> 5) & 60) + ((op >> 19) & 3)) * 2 + rank) * 3072 + 512];
#pragma unroll 1
          for (int i = 0; i < n + (nw ? TAIL : 0); i++) {
            const int id = ((op >> 2) & 511) + (i < n ? i : i - TAIL), col = 5 * (((op >> 19) & 3) + (i >= n));
            const uint4* src = &P.g->tile[(P.slot[id] * 2 + rank) * 3072];
            if ((op & P_LD) && i == ((op & P_PRE) ? 0 : n - 2)) gate();
            if (i < n) gate();
#pragma unroll 1
            for (int k = 0; k < 3; k++) {
              const uint32_t j = (op & P_LD) ? 3 * (i - n) + k + 5 : 5, bytes = i < nw ? SZ_W : j < 5 ? SZ_OL : SZ_O;
              acquire(bytes);
              if (elect()) {
                mbar_expect(bar, bytes);
                tma5d_mc(dst + 16384 + rank * 10240, &P.wo[blk], bar, 24 * (id & 31) + 8 * k + 4 * rank, col);
                bulk_load_hint(dst, src + k * 1024, 16384, bar, pol_o);
                if (i < nw) tma5d_mc(dst + SZ_O + rank * 10240, &P.wo[blk], bar, 24 * (id & 31) + 8 * k + 4 * rank, col + 5);
                if (j < 5) bulk_load_hint(dst + SZ_O, part + j * 512, 8192, bar, pol);
                if ((op & P_PRE) && (uint32_t)(3 * i + k) < PFN)
                  asm volatile("cp.async.bulk.prefetch.L2.global [%0], %1;" ::"l"(part + (3 * i + k) * (2560 / PFN)), "n"(40960 / PFN) : "memory");
              }
            }
          }
        }
      }
#pragma unroll 1
      while (sh) retire();
    } else if (threadIdx.x == 288) {
      for (int pc = 0;; pc++) {
        const uint32_t op = prog[pc];
        const int type = op & 3;
        if (type == OP_END) break;
        if (type == OP_Q ? !(op & F_PARK) : type == OP_O && !(op & P_ST)) continue;
        const int id = type == OP_A ? (op >> 2) & 511 : type == OP_Q ? N_TILE + ((op >> 13) & 127) : ID_PART + ((op >> 5) & 60) + ((op >> 19) & 3);
        const uint32_t v = type == OP_O ? 1 : P.info[id] & 7;
        asm volatile("{\n.reg .pred p;\n.reg .u32 n;\nmov.u32 n, 0;\n"
                     "LOOP:\nmbarrier.try_wait.parity.shared::cta.b64 p, [%0], 0, 20000;\n@p bra DONE;\n"
                     "add.u32 n, n, 1;\nsetp.lt.u32 p, n, 0x1000000;\n@p bra LOOP;\ntrap;\n"
                     "DONE:\n}\n" ::"r"(odone0 + 8 * pc) : "memory");
        flag_set(flag + 2 * id, v);
        if (type == OP_O && (op & P_WIDE)) flag_set(flag + 2 * id + 2, v);
      }
    } else if (wid == 10) {
      int i = threadIdx.x & 31;
      uint32_t e = i < 8 ? P.prog[role].ev[i] : 0;
      for (uint32_t n = 0; __any_sync(0xffffffffu, e); n++) {
        uint32_t job = lds32(jobw);
        const int togo = (e & E_DRAW) ? (e & 1023) - lds32(progress) : 99;
        if (togo <= 0 && rank == 0) {
          job = P.job[atomicInc(&P.g->ticket, gridDim.x / 2 - 1)];
          asm volatile("{\n.reg .u32 a;\nmapa.shared::cluster.u32 a, %0, 1;\nst.volatile.shared::cluster.u32 [a], %1;\n"
                       "st.volatile.shared.u32 [%0], %1;\n}\n" ::"r"(jobw), "r"(job) : "memory");
        }
        if ((e & E_JOB) && job) {
          const uint32_t j = e & 63, heads = (job >> 13) & 63, jp = !(job & P_LD) ? 63 : (job & P_PRE) ? 0 : heads - 2, h = j - (j > jp);
          e = j == jp ? (ID_PART + ((job >> 5) & 60) + ((job >> 19) & 3)) | E_ON | E_LAST : h < heads ? (((job >> 2) & 511) + h) | E_ON | E_LAST : 0;
        }
        unsigned int* f = ptr_add(flag, 8 * (e & 1023));
        const bool ok = (e & E_ON) ? flag_get(f) - 1 < ((e & E_FREE) ? 1 : 7) : (e & E_DRAW) && job;
        if (ok) {
          mbar_arrive(ev0 + 8 * i);
          if (e & (E_FREE | E_LAST)) flag_dec(f);
          i += 8;
          e = i < MAX_EV ? P.prog[role].ev[i] : 0;
        }
        asm volatile("{\n.reg .pred p;\nsetp.ge.u32 p, %0, 0x400000;\n@p trap;\n}\n" ::"r"(n));
        if (!__any_sync(0xffffffffu, ok)) __nanosleep(__any_sync(0xffffffffu, job || togo <= NEAR) ? WATNS2 : WATNS);
      }
    } else if (threadIdx.x == 352) {
      uint32_t items = 0;
      auto read = [&](int id) {
        if (!(P.info[id] & I_NEXT)) return;
        wait_word(progress, items);
        flag_dec(flag + 2 * id);
      };
      for (int pc = 0;; pc++) {
        const uint32_t op = prog[pc];
        const int type = op & 3;
        if (type == OP_END) break;
        if (type == OP_O) {
          const int n = (op >> 13) & 63;
#pragma unroll 1
          for (int i = 0; i < n; i++) {
            items += (op & P_WIDE) && i == n - TAIL ? 3 * TAIL + 3 : 3;
            read(((op >> 2) & 511) + i);
          }
        } else if (type == OP_A) {
          if (op & F_PARK) { items++; read(N_TILE + ((op >> 13) & 127)); }
          items += 32;
        } else {
          items += 10;
        }
      }
    }
    __syncwarp();
    asm volatile("barrier.cluster.arrive.relaxed;\nbarrier.cluster.wait;" ::: "memory");
  }
}

typedef CUresult (*EncodeFn)(CUtensorMap*, CUtensorMapDataType, cuuint32_t, void*, const cuuint64_t*, const cuuint64_t*,
                             const cuuint32_t*, const cuuint32_t*, CUtensorMapInterleave, CUtensorMapSwizzle,
                             CUtensorMapL2promotion, CUtensorMapFloatOOBfill);

void encode(EncodeFn fn, CUtensorMap* m, const void* ptr, int rank, const cuuint64_t* dims, const cuuint64_t* strides,
            const cuuint32_t* box, CUtensorMapSwizzle swz) {
  const cuuint32_t es[5] = {1, 1, 1, 1, 1};
  CUresult r = fn(m, CU_TENSOR_MAP_DATA_TYPE_BFLOAT16, rank, const_cast<void*>(ptr), dims, strides, box, es,
                  CU_TENSOR_MAP_INTERLEAVE_NONE, swz, CU_TENSOR_MAP_L2_PROMOTION_L2_128B, CU_TENSOR_MAP_FLOAT_OOB_FILL_NONE);
  if (r != CUDA_SUCCESS) fprintf(stderr, "cuTensorMapEncodeTiled failed: %d\n", (int)r);
}

struct Op { int type, flags, id, n, quarter, park, item0, items; double t0, t1; };
struct Use { double ready, gate, need, freed; int readers, slot, prev; bool next; };
struct PlanStats { double end, slack, park_slack; int slots, parks; uint32_t own[N_CL]; };

bool plan(const char* const* text, int n_pair, int phase, Params& P, PlanStats* stats = nullptr) {
  constexpr double T_Q = 7900, T_A = 24850, T_U = 26300, T_O = 1920, T_RUN = 800, T_WIDE = 1900, AHEAD = 3500, PUBLISH = 1500;
  const double margin = 256.0 * ((P.dbg >> 8) & 255);
  static Op op[N_CL][MAX_OPS];
  static Use use[ID_PART];
  int n_op[N_CL], covered[N_TEAM] = {}, finals[N_TEAM] = {};
  auto hex = [](char c) { return c <= '9' ? c - '0' : c - 'a' + 10; };
  for (int i = 0; i < n_pair; i++)
    for (const char* s = text[i]; *s; s++)
      if (*s == 'J') { if (covered[hex(s[1])]) return false; covered[hex(s[1])] = 10 * (s[2] - '0') + s[3] - '0'; }
  for (int c = 0; c < 2 * n_pair; c++) {
    int n = 0, items = 0;
    double t = 0;
    auto add = [&](int type, int flags, int id, int heads, int quarter, int its, double dt) {
      if (n < MAX_OPS) op[c][n] = {type, flags, id, heads, quarter, 0, items, its, t, t + dt};
      n++; items += its; t += dt;
    };
    for (const char* s = text[c >> 1]; *s; s++) {
      const int tm = hex(s[1]) & 15, nj = covered[tm];
      if (*s == 'N') { add(OP_Q, 0, 0, 0, 0, 10, T_Q); add(OP_A, 0, 0, 0, 0, 32, T_A); }
      if (*s == 'P') add(OP_Q, F_PARK, 0, 0, 0, 10, T_Q);
      if (*s == 'U') { if (n == 0 || n > MAX_OPS || op[c][n - 1].type != OP_A) return false; add(OP_A, F_PARK, 0, 0, 0, 33, T_U); }
      if (*s == 'J') { if (nj <= TAIL || nj > kH - 4) return false; add(OP_O, P_WIDE | P_ST, tm * kH, nj, 2 * (c & 1), 3 * (nj + TAIL), 2 * T_O * nj + T_WIDE); }
      if (*s == 'F') { if (s[2]) return false; add(OP_O, nj ? P_LD : 0, tm * kH + nj, kH - nj, finals[tm]++, 3 * (kH - nj), T_O * (kH - nj) + T_RUN); }
    }
    if (n && n <= MAX_OPS && (op[c][n - 1].type != OP_O || (op[c][n - 1].flags & P_WIDE))) add(OP_O, 0, 0, 0, 0, 0, 0);
    add(OP_END, 0, 0, 0, 0, 0, 0);
    if (n > MAX_OPS || op[c][0].type != OP_Q) return false;
    n_op[c] = n - 1;
  }
  for (int t = 0; t < N_TEAM; t++) if (finals[t] != 4) return false;
  for (int i = 0; i < ID_PART; i++) use[i] = {0, 0, 1e18, 0, 0, 0, 0, false};
  struct Ref { double t; Op* o; int id; };
  static Ref att[N_TILE + 1], dem[N_TILE], prk[MAX_PARK + 1], unp[MAX_PARK + 1], wr[ID_PART];
  int n_att = 0, n_prk = 0, n_unp = 0;
  auto ready = [&](const Op* o) {
    const int nt = o[1].type;
    return o->t1 + (nt == OP_Q ? 6100 : o[1].n ? 3900 : 1500) + PUBLISH;
  };
  for (int c = 0; c < 2 * n_pair; c++)
    for (Op* o = op[c]; o->type != OP_END; o++) {
      if (o->type == OP_A) { att[n_att] = {ready(o), o, 0}; if (++n_att > N_TILE) return false; }
      if (o->type == OP_A && o->flags) { unp[n_unp] = {o->t0 - AHEAD, o, 0}; if (++n_unp > MAX_PARK) return false; }
      if (o->type == OP_Q && o->flags) { prk[n_prk] = {ready(o), o, 0}; if (++n_prk > MAX_PARK) return false; }
      for (int i = 0; o->type == OP_O && i < o->n; i++) {
        const int nw = (o->flags & P_WIDE) ? o->n - TAIL : 0;
        Use& u = use[o->id + i];
        const double t = o->t0 + T_O * (i + (i < nw ? i : nw));
        if (t - AHEAD < u.need) u.need = t - AHEAD;
        const double f = i < nw || (nw && o[1].type != OP_O) ? t + T_O * (i < nw ? 2 : 1 + TAIL) + PUBLISH : 1e18;
        if (f > u.freed) u.freed = f;
        u.readers++;
      }
    }
  if (n_att != N_TILE || n_prk != n_unp) return false;
  auto sort = [](Ref* r, int n) {
    for (int i = 1; i < n; i++)
      for (int j = i; j > 0 && r[j].t < r[j - 1].t; j--) { Ref x = r[j]; r[j] = r[j - 1]; r[j - 1] = x; }
  };
  for (int i = 0; i < N_TILE; i++) { const int id = (i & 15) * kH + (i >> 4); dem[i] = {use[id].need, nullptr, id}; }
  sort(att, n_att); sort(dem, N_TILE); sort(prk, n_prk); sort(unp, n_unp);
  PlanStats st = {0, 1e18, 1e18, 0, n_prk};
  int n_wr = 0;
  for (int i = 0; i < N_TILE; i++) {
    Op* o = att[i].o;
    o->id = dem[i].id;
    if (!o->flags) o[-1].id = o->id;
    if (dem[i].t - att[i].t < st.slack) st.slack = dem[i].t - att[i].t;
    wr[n_wr++] = {o->t1 - 2 * AHEAD, o, o->id};
  }
  for (int i = 0; i < n_prk; i++) {
    prk[i].o->id = unp[i].o->id;
    prk[i].o->park = unp[i].o->park = i;
    use[N_TILE + i].freed = unp[i].o->t0 + 2 * PUBLISH;
    use[N_TILE + i].readers = 1;
    if (unp[i].t - prk[i].t < st.park_slack) st.park_slack = unp[i].t - prk[i].t;
    wr[n_wr++] = {prk[i].o->t1 - 2 * AHEAD, prk[i].o, N_TILE + i};
  }
  for (int c = 0; c < 2 * n_pair; c++)
    for (int d = 0; d < 2 * n_pair; d++)
      for (Op *f = &op[c][n_op[c] - 1], *o = op[d]; f->n && o->type != OP_END; o++)
        if (o->type == OP_O && (o->flags & P_ST) && o->id / kH == f->id / kH) {
          if (f->t0 - o->t1 > 4096.0 * ((P.dbg >> 16) & 255)) f->flags |= P_PRE;
          const double slack = f->t0 + ((f->flags & P_PRE) ? 0 : (f->n - 2) * T_O) - AHEAD - ready(o);
          if (slack < st.park_slack) st.park_slack = slack;
        }
  sort(wr, n_wr);
  int holder[N_TILE];
  for (int i = 0; i < n_wr; i++) {
    int best = -1;
    for (int sl = 0; sl < st.slots; sl++)
      if (use[holder[sl]].freed + margin <= wr[i].t && (best < 0 || (use[holder[sl]].freed < use[holder[best]].freed) != ((P.dbg & 32) != 0))) best = sl;
    Use& u = use[wr[i].id];
    if (best >= 0) { u.prev = holder[best]; use[u.prev].next = true; wr[i].o->flags |= P_GATE; }
    else if (st.slots == N_TILE) return false;
    else best = st.slots++;
    u.slot = best;
    holder[best] = wr[i].id;
  }
  {
    int pos[N_CL] = {}, flag[ID_PART + 4 * N_TEAM] = {}, seen[ID_PART] = {};
    auto goal = [&](int c) { return op[c][n_op[c] - 1].item0; };
    for (bool moved = true; moved;) {
      moved = false;
      for (int c = 0; c < 2 * n_pair; c++) {
        for (; pos[c] < goal(c); pos[c]++, moved = true) {
          bool ok = true;
          for (const Op* o = op[c]; o->type != OP_END; o++) {
            const int k = pos[c] - o->item0, own = o->type == OP_A ? o->id : N_TILE + o->park;
            if (k < 0 || k >= o->items) continue;
            if (o->type == OP_O) ok = k >= 3 * o->n || flag[o->id + k / 3];
            else if (k == o->items - 1 && (o->flags & P_GATE)) ok = seen[use[own].prev] == use[use[own].prev].readers;
            else if (k == 0 && o->type == OP_A && (o->flags & F_PARK)) ok = flag[N_TILE + o->park];
          }
          if (!ok) break;
          for (const Op* o = op[c]; o->type != OP_END; o++) {
            if (pos[c] == o->item0 + o->items + (o[1].type == OP_Q ? 7 : o[1].item0 == goal(c) ? -1 : 5)) {
              if (o->type == OP_A) flag[o->id] = 1;
              if (o->type == OP_Q && (o->flags & F_PARK)) flag[N_TILE + o->park] = 1;
              if (o->type == OP_O) flag[ID_PART + o->id / kH * 4 + o->quarter] = flag[ID_PART + o->id / kH * 4 + o->quarter + 1] = 1;
            }
            const int k = pos[c] - NBAR - o->item0, nw = o->n - TAIL;
            if (k == 0 && o->type == OP_A && (o->flags & F_PARK)) seen[N_TILE + o->park]++;
            if (o->type == OP_O && k >= 0 && k < o->items && k % 3 == 2 && (k / 3 < nw || k / 3 >= o->n)) seen[o->id + (k / 3 < nw ? k / 3 : k / 3 - TAIL)]++;
          }
        }
      }
    }
    for (int c = 0; c < 2 * n_pair; c++) if (pos[c] < goal(c)) return false;
  }
  int n_job = 0, longest = 0;
  for (int t = 0; t < N_TEAM; t++) if (kH - covered[t] > longest) longest = kH - covered[t];
  for (int c = 0; c < 2 * n_pair; c++) {
    uint32_t items = 0, cur = 0, pend = 0;
    int n = 0, ev = 0;
    auto item = [&](uint32_t bytes, int count) {
      for (int i = 0; i < count; i++) { if (cur + bytes > RING) cur = 0; cur += bytes; items++; }
    };
    auto event = [&](uint32_t e) { if (ev < MAX_EV) P.prog[c].ev[ev] = e; ev++; };
    for (const Op* o = op[c];; o++) {
      if (o->type != OP_END && phase && (o->type == OP_O) != (phase == 2)) continue;
      uint32_t cw = o->type | (items % NBAR) << 15 | ((items / NBAR) & 1) << 19 | (cur >> 12) << 20 | pend, pw = o->type | o->id << 2 | o->flags;
      const int ps = use[N_TILE + o->park].slot;
      pend = 0;
      if (o->type == OP_O) {
        pw |= o->n << 13 | o->quarter << 19;
        if (o->flags & P_WIDE) {
          cw |= o->n << 2 | (o->id / kH * 4 + o->quarter + 1) << 8 | C_WIDE;
          item(SZ_W, 3 * (o->n - TAIL));
          item(SZ_O, 6 * TAIL);
          pend = C_PEND | ((P.dbg & 8) ? C_SOON : 0);
          for (int i = 0; i < o->n; i++) event((o->id + i) | E_ON | (use[o->id + i].next ? 0 : E_LAST));
        } else {
          dem[n_job++] = {o->t0 - 1e6 * o->n, nullptr, (int)pw};
          st.own[c] = pw;
          pw = OP_O;
          event(E_DRAW | (items < TICK ? 0 : items - TICK));
          for (int i = 0; i <= longest; i++) event(E_JOB | i);
        }
      } else if (o->type != OP_END) {
        const bool parks = o->type == OP_Q && (o->flags & F_PARK);
        cw |= (parks ? ps : use[o->id].slot) << 2 | (o->flags & F_PARK);
        if (o->flags & F_PARK) pw |= o->park << 13 | ps << 20;
        if (o->type == OP_Q) item(SZ_Q, 10);
        else { if (o->flags & F_PARK) { item(SZ_PARK, 1); event((N_TILE + o->park) | E_ON | (use[N_TILE + o->park].next ? 0 : E_LAST)); } item(SZ_KV, 32); }
        if (parks || o->type == OP_A) pend = C_PEND | ((P.dbg & 16) ? 0 : C_SOON);
        if (o->flags & P_GATE) event(use[parks ? N_TILE + o->park : o->id].prev | E_ON | E_FREE);
      }
      P.prog[c].c[n] = cw; P.prog[c].p[n++] = pw;
      if (o->type == OP_END) { if (o->t0 > st.end) st.end = o->t0; break; }
    }
    if (ev > MAX_EV) return false;
    while (ev < MAX_EV) P.prog[c].ev[ev++] = 0;
    while (n < MAX_OPS) { P.prog[c].c[n] = OP_END; P.prog[c].p[n++] = OP_END; }
    P.first[c] = (uint16_t)(P.prog[c].p[0] & 2047);
  }
  sort(dem, n_job);
  for (int i = 0; i < n_job; i++) P.job[i] = dem[i].id;
  for (int i = 0; i < ID_PART; i++) {
    if (i < N_TILE) P.slot[i] = use[i].slot;
    P.info[i] = (use[i].readers + use[i].next) | (use[i].next ? I_NEXT : 0);
  }
  if (stats) *stats = st;
  return true;
}

const char* const kPrograms[N_CL / 2] = {
  "NNNNNNNNNF6", "NNNNNNNNNF0", "NNNNJf15NNNF7", "PNNNNNNNNNF8", "PNJ621NNNNNF5", "NNNNNNNNNFe",
  "NUNNNNNNNF5", "NNNNNNNNNF6", "NNNNNNNNNFe", "NUNNNJa26NFb", "PNJ227NNNNFc", "PPNJ517NNNNUNF2",
  "NNNNNJc13NNUF2", "NNJ327NNNNF8", "NUNUNJ925NFc", "PNUNNNNNNNF1", "PNJ021NNNNNFf", "NUNNNJd15NNFd",
  "PNNNNNNNNNF9", "NNUJ420Jb20NFd", "NNNNNNNNNFb", "PNJ717NNNNNNF3", "NNNNNNNNNF4", "PNJ125NNNNN",
  "PNNNNNNNNNFa", "NUNNNJe21NNFa", "PNNNNNNNNNF9", "NNNNNNNNNF0", "PNNNNNNNNNF3", "PPNUNNNNNNUF1",
  "NNUNNNNNNF7", "NNNNNJ825NF4", "NUNUNNNNNFf",
};

const char* const* bench_programs() {
  return kPrograms;
}

}

extern "C" void kernel_launch(void* const* d_in, const int* in_sizes, int n_in, void* d_out, int out_size) {
  (void)in_sizes; (void)n_in; (void)out_size;
  static EncodeFn fn = nullptr;
  static int n_clusters = 0;
  if (!fn) {
    cudaDriverEntryPointQueryResult qr;
    void* f = nullptr;
    cudaGetDriverEntryPoint("cuTensorMapEncodeTiled", &f, cudaEnableDefault, &qr);
    fn = (EncodeFn)f;
    cudaFuncSetAttribute(fused_kernel, cudaFuncAttributeMaxDynamicSharedMemorySize, SMEM_BYTES);
    cudaLaunchConfig_t cfg = {};
    cfg.gridDim = dim3(132); cfg.blockDim = dim3(384); cfg.dynamicSmemBytes = SMEM_BYTES;
    cudaLaunchAttribute at[1];
    at[0].id = cudaLaunchAttributeClusterDimension; at[0].val.clusterDim.x = 2; at[0].val.clusterDim.y = 1; at[0].val.clusterDim.z = 1;
    cfg.attrs = at; cfg.numAttrs = 1;
    if (cudaOccupancyMaxActiveClusters(&n_clusters, fused_kernel, &cfg) != cudaSuccess || n_clusters < 1) n_clusters = 1;
    (void)cudaGetLastError();
  }
  static Params P;
  const CUtensorMapSwizzle S128 = CU_TENSOR_MAP_SWIZZLE_128B, S64 = CU_TENSOR_MAP_SWIZZLE_64B;
  for (int blk = 0; blk < 2; blk++) {
    void* const* in = d_in + 5 * blk;
    { const cuuint64_t d[] = {kD, kB * kSq}, s[] = {kD * 2}; const cuuint32_t b[] = {64, 128};
      encode(fn, &P.x[blk], in[0], 2, d, s, b, S128); }
    { const cuuint64_t d[] = {64, 8, 3, (cuuint64_t)kB * kH * kSk / 8}, s[] = {kDh * 2, 128, 8 * kDh * 2}; const cuuint32_t b[] = {64, 8, 3, 8};
      encode(fn, &P.k[blk], in[1], 4, d, s, b, S128);
      encode(fn, &P.v[blk], in[2], 4, d, s, b, S128); }
    { const cuuint64_t d[] = {64, kD, kHD / 64}, s[] = {kHD * 2, 128}; const cuuint32_t b[] = {64, 64, 3};
      encode(fn, &P.wq[blk], in[3], 3, d, s, b, S128); }
    { const cuuint64_t d[] = {32, 2, kHD / 8, 4, kD / 32}, s[] = {kD * 2, 8 * kD * 2, 2 * kD * 2, 64}; const cuuint32_t b[] = {32, 2, 4, 4, 5};
      encode(fn, &P.wo[blk], in[4], 5, d, s, b, S64); }
  }
  { const cuuint64_t d[] = {32, kB * kSq, 2 * kD / 32}, s[] = {2 * kD * 2, 64}; const cuuint32_t b[] = {32, 16, 1};
    encode(fn, &P.out, d_out, 3, d, s, b, S64); }

  cudaGetSymbolAddress((void**)&P.g, g_scratch);
  P.dbg = DBG_DEFAULT;
  if (n_clusters >= N_CL && plan(bench_programs(), N_CL / 2, 0, P)) {
    fused_kernel<<<2 * N_CL, 384, SMEM_BYTES>>>(P);
  } else {
    char buf[2 * N_TEAM][16];
    const char* text[2 * N_TEAM];
    for (int i = 0; i < 2 * N_TEAM; i++) { snprintf(buf[i], sizeof(buf[i]), "NNNNNNNNF%x", i / 2); text[i] = buf[i]; }
    for (int phase = 1; phase <= 2; phase++) {
      plan(text, 2 * N_TEAM, phase, P);
      fused_kernel<<<8 * N_TEAM, 384, SMEM_BYTES>>>(P);
    }
  }
}
```

```cpp
#include <cuda_runtime.h>
#include <cuda_bf16.h>
#include <cuda.h>
#include <stdint.h>
#include <stdio.h>

namespace {

constexpr int kB = 8, kSq = 256, kD = 640, kH = 32, kSk = 1024, kDh = 192;
constexpr int kHD = kH * kDh;
constexpr uint32_t RING = 224 * 1024;
constexpr uint32_t SZ_KV = 24576;
constexpr uint32_t SZ_Q = 16384 + 24576;
constexpr uint32_t SZ_O = 16384 + 20480;
constexpr uint32_t SZ_W = 16384 + 40960;
constexpr uint32_t SZ_PARK = 49152;
constexpr uint32_t SZ_OL = SZ_O + 8192;
constexpr int NBAR = 10;
constexpr int EARLY = 3;
constexpr int kSteps = kHD / 64;
constexpr int TAIL = 6;
constexpr uint32_t KV_CH = 64, KV_SBO = 3072;
constexpr int SMEM_BYTES = RING + 1024 + 1024;
constexpr int N_TEAM = 16, N_CL = 66, MAX_OPS = 24, MAX_EV = 80, N_TILE = N_TEAM * kH, MAX_PARK = 128, ID_PART = N_TILE + MAX_PARK;
enum : uint32_t { OP_END = 0, OP_Q = 1, OP_A = 2, OP_O = 3, F_PARK = 1 << 11,
                  C_WIDE = 1 << 27, C_PEND = 1 << 26, C_SOON = 1 << 28,
                  P_GATE = 1 << 12, P_WIDE = 1 << 11, P_LD = 1 << 12, P_PRE = 1 << 22, I_NEXT = 8, E_ON = 1 << 15, E_FREE = 1 << 14, E_LAST = 1 << 13, E_DRAW = 1 << 12, E_JOB = 1 << 11 };

#define QDRAIN 0x54732710u
#define TRYNS 1500
#define QA 1
#define QB 2
#define QC 3
#define NORM_G 2
#define CONV_G 8
#define CONV_0 32
#define SLOWF 35
#define SLOWP 0x4511
#define FASTF 23
#define FASTP 0x1a
#define WATNS2 100
#define NEAR 2
#define TICK 16
#define SKEW 3
#define PUBNS 0
#define WATNS 600
constexpr uint32_t DBG_DEFAULT = 0x040817;

struct alignas(1024) Scratch {
  unsigned int flag[2047];
  unsigned int ticket;
  uint4 part[N_TEAM * 4 * 2 * 3072];
  uint4 tile[N_TILE * 2 * 3072];
};

struct alignas(64) Params {
  uint16_t first[88];
  Scratch* g;
  uint32_t dbg;
  CUtensorMap x[2], wq[2], k[2], v[2], wo[2], out;
  struct {
    uint32_t c[MAX_OPS];
    uint32_t p[MAX_OPS];
    uint16_t ev[MAX_EV];
  } prog[N_CL];
  uint32_t job[N_CL];
  uint16_t slot[N_TILE];
  uint8_t info[ID_PART];
};

__device__ Scratch g_scratch;

template <int TB, int TA = 0>
__device__ __forceinline__ void wgmma_ss_n64(float (&d)[32], uint64_t da, uint64_t db, int scale_d) {
  asm volatile("{\n.reg .pred p;\nsetp.ne.b32 p, %34, 0;\n"
    "wgmma.mma_async.sync.aligned.m64n64k16.f32.bf16.bf16 {%0, %1, %2, %3, %4, %5, %6, %7, %8, %9, %10, %11, %12, %13, %14, %15, %16, %17, %18, %19, %20, %21, %22, %23, %24, %25, %26, %27, %28, %29, %30, %31}, %32, %33, p, 1, 1, %35, %36;\n}\n"
    : "+f"(d[0]), "+f"(d[1]), "+f"(d[2]), "+f"(d[3]), "+f"(d[4]), "+f"(d[5]), "+f"(d[6]), "+f"(d[7]), "+f"(d[8]), "+f"(d[9]), "+f"(d[10]), "+f"(d[11]), "+f"(d[12]), "+f"(d[13]), "+f"(d[14]), "+f"(d[15]), "+f"(d[16]), "+f"(d[17]), "+f"(d[18]), "+f"(d[19]), "+f"(d[20]), "+f"(d[21]), "+f"(d[22]), "+f"(d[23]), "+f"(d[24]), "+f"(d[25]), "+f"(d[26]), "+f"(d[27]), "+f"(d[28]), "+f"(d[29]), "+f"(d[30]), "+f"(d[31])
    : "l"(da), "l"(db), "r"(scale_d), "n"(TA), "n"(TB));
}
template <int TB>
__device__ __forceinline__ void wgmma_rs_n64(float (&d)[32], uint32_t a0, uint32_t a1, uint32_t a2, uint32_t a3, uint64_t db, int scale_d) {
  asm volatile("{\n.reg .pred p;\nsetp.ne.b32 p, %37, 0;\n"
    "wgmma.mma_async.sync.aligned.m64n64k16.f32.bf16.bf16 {%0, %1, %2, %3, %4, %5, %6, %7, %8, %9, %10, %11, %12, %13, %14, %15, %16, %17, %18, %19, %20, %21, %22, %23, %24, %25, %26, %27, %28, %29, %30, %31}, {%32, %33, %34, %35}, %36, p, 1, 1, %38;\n}\n"
    : "+f"(d[0]), "+f"(d[1]), "+f"(d[2]), "+f"(d[3]), "+f"(d[4]), "+f"(d[5]), "+f"(d[6]), "+f"(d[7]), "+f"(d[8]), "+f"(d[9]), "+f"(d[10]), "+f"(d[11]), "+f"(d[12]), "+f"(d[13]), "+f"(d[14]), "+f"(d[15]), "+f"(d[16]), "+f"(d[17]), "+f"(d[18]), "+f"(d[19]), "+f"(d[20]), "+f"(d[21]), "+f"(d[22]), "+f"(d[23]), "+f"(d[24]), "+f"(d[25]), "+f"(d[26]), "+f"(d[27]), "+f"(d[28]), "+f"(d[29]), "+f"(d[30]), "+f"(d[31])
    : "r"(a0), "r"(a1), "r"(a2), "r"(a3), "l"(db), "r"(scale_d), "n"(TB));
}
template <int TB, int TA = 0>
__device__ __forceinline__ void wgmma_ss_n160(float (&d)[80], uint64_t da, uint64_t db, int scale_d) {
  asm volatile("{\n.reg .pred p;\nsetp.ne.b32 p, %82, 0;\n"
    "wgmma.mma_async.sync.aligned.m64n160k16.f32.bf16.bf16 {%0, %1, %2, %3, %4, %5, %6, %7, %8, %9, %10, %11, %12, %13, %14, %15, %16, %17, %18, %19, %20, %21, %22, %23, %24, %25, %26, %27, %28, %29, %30, %31, %32, %33, %34, %35, %36, %37, %38, %39, %40, %41, %42, %43, %44, %45, %46, %47, %48, %49, %50, %51, %52, %53, %54, %55, %56, %57, %58, %59, %60, %61, %62, %63, %64, %65, %66, %67, %68, %69, %70, %71, %72, %73, %74, %75, %76, %77, %78, %79}, %80, %81, p, 1, 1, %83, %84;\n}\n"
    : "+f"(d[0]), "+f"(d[1]), "+f"(d[2]), "+f"(d[3]), "+f"(d[4]), "+f"(d[5]), "+f"(d[6]), "+f"(d[7]), "+f"(d[8]), "+f"(d[9]), "+f"(d[10]), "+f"(d[11]), "+f"(d[12]), "+f"(d[13]), "+f"(d[14]), "+f"(d[15]), "+f"(d[16]), "+f"(d[17]), "+f"(d[18]), "+f"(d[19]), "+f"(d[20]), "+f"(d[21]), "+f"(d[22]), "+f"(d[23]), "+f"(d[24]), "+f"(d[25]), "+f"(d[26]), "+f"(d[27]), "+f"(d[28]), "+f"(d[29]), "+f"(d[30]), "+f"(d[31]), "+f"(d[32]), "+f"(d[33]), "+f"(d[34]), "+f"(d[35]), "+f"(d[36]), "+f"(d[37]), "+f"(d[38]), "+f"(d[39]), "+f"(d[40]), "+f"(d[41]), "+f"(d[42]), "+f"(d[43]), "+f"(d[44]), "+f"(d[45]), "+f"(d[46]), "+f"(d[47]), "+f"(d[48]), "+f"(d[49]), "+f"(d[50]), "+f"(d[51]), "+f"(d[52]), "+f"(d[53]), "+f"(d[54]), "+f"(d[55]), "+f"(d[56]), "+f"(d[57]), "+f"(d[58]), "+f"(d[59]), "+f"(d[60]), "+f"(d[61]), "+f"(d[62]), "+f"(d[63]), "+f"(d[64]), "+f"(d[65]), "+f"(d[66]), "+f"(d[67]), "+f"(d[68]), "+f"(d[69]), "+f"(d[70]), "+f"(d[71]), "+f"(d[72]), "+f"(d[73]), "+f"(d[74]), "+f"(d[75]), "+f"(d[76]), "+f"(d[77]), "+f"(d[78]), "+f"(d[79])
    : "l"(da), "l"(db), "r"(scale_d), "n"(TA), "n"(TB));
}
template <int TB>
__device__ __forceinline__ void wgmma_rs_n160(float (&d)[80], uint32_t a0, uint32_t a1, uint32_t a2, uint32_t a3, uint64_t db, int scale_d) {
  asm volatile("{\n.reg .pred p;\nsetp.ne.b32 p, %85, 0;\n"
    "wgmma.mma_async.sync.aligned.m64n160k16.f32.bf16.bf16 {%0, %1, %2, %3, %4, %5, %6, %7, %8, %9, %10, %11, %12, %13, %14, %15, %16, %17, %18, %19, %20, %21, %22, %23, %24, %25, %26, %27, %28, %29, %30, %31, %32, %33, %34, %35, %36, %37, %38, %39, %40, %41, %42, %43, %44, %45, %46, %47, %48, %49, %50, %51, %52, %53, %54, %55, %56, %57, %58, %59, %60, %61, %62, %63, %64, %65, %66, %67, %68, %69, %70, %71, %72, %73, %74, %75, %76, %77, %78, %79}, {%80, %81, %82, %83}, %84, p, 1, 1, %86;\n}\n"
    : "+f"(d[0]), "+f"(d[1]), "+f"(d[2]), "+f"(d[3]), "+f"(d[4]), "+f"(d[5]), "+f"(d[6]), "+f"(d[7]), "+f"(d[8]), "+f"(d[9]), "+f"(d[10]), "+f"(d[11]), "+f"(d[12]), "+f"(d[13]), "+f"(d[14]), "+f"(d[15]), "+f"(d[16]), "+f"(d[17]), "+f"(d[18]), "+f"(d[19]), "+f"(d[20]), "+f"(d[21]), "+f"(d[22]), "+f"(d[23]), "+f"(d[24]), "+f"(d[25]), "+f"(d[26]), "+f"(d[27]), "+f"(d[28]), "+f"(d[29]), "+f"(d[30]), "+f"(d[31]), "+f"(d[32]), "+f"(d[33]), "+f"(d[34]), "+f"(d[35]), "+f"(d[36]), "+f"(d[37]), "+f"(d[38]), "+f"(d[39]), "+f"(d[40]), "+f"(d[41]), "+f"(d[42]), "+f"(d[43]), "+f"(d[44]), "+f"(d[45]), "+f"(d[46]), "+f"(d[47]), "+f"(d[48]), "+f"(d[49]), "+f"(d[50]), "+f"(d[51]), "+f"(d[52]), "+f"(d[53]), "+f"(d[54]), "+f"(d[55]), "+f"(d[56]), "+f"(d[57]), "+f"(d[58]), "+f"(d[59]), "+f"(d[60]), "+f"(d[61]), "+f"(d[62]), "+f"(d[63]), "+f"(d[64]), "+f"(d[65]), "+f"(d[66]), "+f"(d[67]), "+f"(d[68]), "+f"(d[69]), "+f"(d[70]), "+f"(d[71]), "+f"(d[72]), "+f"(d[73]), "+f"(d[74]), "+f"(d[75]), "+f"(d[76]), "+f"(d[77]), "+f"(d[78]), "+f"(d[79])
    : "r"(a0), "r"(a1), "r"(a2), "r"(a3), "l"(db), "r"(scale_d), "n"(TB));
}
template <int TB, int TA = 0>
__device__ __forceinline__ void wgmma_ss_n192(float (&d)[96], uint64_t da, uint64_t db, int scale_d) {
  asm volatile("{\n.reg .pred p;\nsetp.ne.b32 p, %98, 0;\n"
    "wgmma.mma_async.sync.aligned.m64n192k16.f32.bf16.bf16 {%0, %1, %2, %3, %4, %5, %6, %7, %8, %9, %10, %11, %12, %13, %14, %15, %16, %17, %18, %19, %20, %21, %22, %23, %24, %25, %26, %27, %28, %29, %30, %31, %32, %33, %34, %35, %36, %37, %38, %39, %40, %41, %42, %43, %44, %45, %46, %47, %48, %49, %50, %51, %52, %53, %54, %55, %56, %57, %58, %59, %60, %61, %62, %63, %64, %65, %66, %67, %68, %69, %70, %71, %72, %73, %74, %75, %76, %77, %78, %79, %80, %81, %82, %83, %84, %85, %86, %87, %88, %89, %90, %91, %92, %93, %94, %95}, %96, %97, p, 1, 1, %99, %100;\n}\n"
    : "+f"(d[0]), "+f"(d[1]), "+f"(d[2]), "+f"(d[3]), "+f"(d[4]), "+f"(d[5]), "+f"(d[6]), "+f"(d[7]), "+f"(d[8]), "+f"(d[9]), "+f"(d[10]), "+f"(d[11]), "+f"(d[12]), "+f"(d[13]), "+f"(d[14]), "+f"(d[15]), "+f"(d[16]), "+f"(d[17]), "+f"(d[18]), "+f"(d[19]), "+f"(d[20]), "+f"(d[21]), "+f"(d[22]), "+f"(d[23]), "+f"(d[24]), "+f"(d[25]), "+f"(d[26]), "+f"(d[27]), "+f"(d[28]), "+f"(d[29]), "+f"(d[30]), "+f"(d[31]), "+f"(d[32]), "+f"(d[33]), "+f"(d[34]), "+f"(d[35]), "+f"(d[36]), "+f"(d[37]), "+f"(d[38]), "+f"(d[39]), "+f"(d[40]), "+f"(d[41]), "+f"(d[42]), "+f"(d[43]), "+f"(d[44]), "+f"(d[45]), "+f"(d[46]), "+f"(d[47]), "+f"(d[48]), "+f"(d[49]), "+f"(d[50]), "+f"(d[51]), "+f"(d[52]), "+f"(d[53]), "+f"(d[54]), "+f"(d[55]), "+f"(d[56]), "+f"(d[57]), "+f"(d[58]), "+f"(d[59]), "+f"(d[60]), "+f"(d[61]), "+f"(d[62]), "+f"(d[63]), "+f"(d[64]), "+f"(d[65]), "+f"(d[66]), "+f"(d[67]), "+f"(d[68]), "+f"(d[69]), "+f"(d[70]), "+f"(d[71]), "+f"(d[72]), "+f"(d[73]), "+f"(d[74]), "+f"(d[75]), "+f"(d[76]), "+f"(d[77]), "+f"(d[78]), "+f"(d[79]), "+f"(d[80]), "+f"(d[81]), "+f"(d[82]), "+f"(d[83]), "+f"(d[84]), "+f"(d[85]), "+f"(d[86]), "+f"(d[87]), "+f"(d[88]), "+f"(d[89]), "+f"(d[90]), "+f"(d[91]), "+f"(d[92]), "+f"(d[93]), "+f"(d[94]), "+f"(d[95])
    : "l"(da), "l"(db), "r"(scale_d), "n"(TA), "n"(TB));
}
template <int TB>
__device__ __forceinline__ void wgmma_rs_n192(float (&d)[96], uint32_t a0, uint32_t a1, uint32_t a2, uint32_t a3, uint64_t db, int scale_d) {
  asm volatile("{\n.reg .pred p;\nsetp.ne.b32 p, %101, 0;\n"
    "wgmma.mma_async.sync.aligned.m64n192k16.f32.bf16.bf16 {%0, %1, %2, %3, %4, %5, %6, %7, %8, %9, %10, %11, %12, %13, %14, %15, %16, %17, %18, %19, %20, %21, %22, %23, %24, %25, %26, %27, %28, %29, %30, %31, %32, %33, %34, %35, %36, %37, %38, %39, %40, %41, %42, %43, %44, %45, %46, %47, %48, %49, %50, %51, %52, %53, %54, %55, %56, %57, %58, %59, %60, %61, %62, %63, %64, %65, %66, %67, %68, %69, %70, %71, %72, %73, %74, %75, %76, %77, %78, %79, %80, %81, %82, %83, %84, %85, %86, %87, %88, %89, %90, %91, %92, %93, %94, %95}, {%96, %97, %98, %99}, %100, p, 1, 1, %102;\n}\n"
    : "+f"(d[0]), "+f"(d[1]), "+f"(d[2]), "+f"(d[3]), "+f"(d[4]), "+f"(d[5]), "+f"(d[6]), "+f"(d[7]), "+f"(d[8]), "+f"(d[9]), "+f"(d[10]), "+f"(d[11]), "+f"(d[12]), "+f"(d[13]), "+f"(d[14]), "+f"(d[15]), "+f"(d[16]), "+f"(d[17]), "+f"(d[18]), "+f"(d[19]), "+f"(d[20]), "+f"(d[21]), "+f"(d[22]), "+f"(d[23]), "+f"(d[24]), "+f"(d[25]), "+f"(d[26]), "+f"(d[27]), "+f"(d[28]), "+f"(d[29]), "+f"(d[30]), "+f"(d[31]), "+f"(d[32]), "+f"(d[33]), "+f"(d[34]), "+f"(d[35]), "+f"(d[36]), "+f"(d[37]), "+f"(d[38]), "+f"(d[39]), "+f"(d[40]), "+f"(d[41]), "+f"(d[42]), "+f"(d[43]), "+f"(d[44]), "+f"(d[45]), "+f"(d[46]), "+f"(d[47]), "+f"(d[48]), "+f"(d[49]), "+f"(d[50]), "+f"(d[51]), "+f"(d[52]), "+f"(d[53]), "+f"(d[54]), "+f"(d[55]), "+f"(d[56]), "+f"(d[57]), "+f"(d[58]), "+f"(d[59]), "+f"(d[60]), "+f"(d[61]), "+f"(d[62]), "+f"(d[63]), "+f"(d[64]), "+f"(d[65]), "+f"(d[66]), "+f"(d[67]), "+f"(d[68]), "+f"(d[69]), "+f"(d[70]), "+f"(d[71]), "+f"(d[72]), "+f"(d[73]), "+f"(d[74]), "+f"(d[75]), "+f"(d[76]), "+f"(d[77]), "+f"(d[78]), "+f"(d[79]), "+f"(d[80]), "+f"(d[81]), "+f"(d[82]), "+f"(d[83]), "+f"(d[84]), "+f"(d[85]), "+f"(d[86]), "+f"(d[87]), "+f"(d[88]), "+f"(d[89]), "+f"(d[90]), "+f"(d[91]), "+f"(d[92]), "+f"(d[93]), "+f"(d[94]), "+f"(d[95])
    : "r"(a0), "r"(a1), "r"(a2), "r"(a3), "l"(db), "r"(scale_d), "n"(TB));
}

__device__ __forceinline__ uint32_t smem_u32(const void* p) { return (uint32_t)__cvta_generic_to_shared(p); }
__device__ __forceinline__ void wg_fence() { asm volatile("wgmma.fence.sync.aligned;" ::: "memory"); }
__device__ __forceinline__ void wg_commit() { asm volatile("wgmma.commit_group.sync.aligned;" ::: "memory"); }
template <int N> __device__ __forceinline__ void wg_wait() { asm volatile("wgmma.wait_group.sync.aligned %0;" ::"n"(N) : "memory"); }
__device__ __forceinline__ void sched_fence(uint32_t& keep, bool never) {
  asm volatile("{\n.reg .pred p;\nsetp.ne.b32 p, %1, 0;\n@p mov.u32 %0, %%clock;\n}\n" : "+r"(keep) : "r"((int)never) : "memory");
}
template <int N> __device__ __forceinline__ void fence_regs(float (&r)[N]) {
#pragma unroll
  for (int i = 0; i < N; i++) asm volatile("" : "+f"(r[i])::"memory");
}
template <int N> __device__ __forceinline__ void undefine(float (&r)[N]) {
#pragma unroll
  for (int i = 0; i < N; i++) asm volatile("" : "=f"(r[i]));
}
template <int N> __device__ __forceinline__ void fence_regs(uint32_t (&r)[N]) {
#pragma unroll
  for (int i = 0; i < N; i++) asm volatile("" : "+r"(r[i])::"memory");
}
__device__ __forceinline__ uint64_t mk_desc(uint32_t a16, uint32_t lbo, uint32_t sbo, uint32_t swz) {
  uint64_t d;
  asm("mov.b64 %0, {%1, %2};" : "=l"(d) : "r"(a16 + ((lbo >> 4) << 16)), "r"((sbo >> 4) | (swz << 30)));
  return d;
}
__device__ __forceinline__ void mbar_init(uint32_t bar, uint32_t cnt) {
  asm volatile("mbarrier.init.shared::cta.b64 [%0], %1;" ::"r"(bar), "r"(cnt) : "memory");
}
__device__ __forceinline__ void mbar_expect(uint32_t bar, uint32_t tx) {
  asm volatile("mbarrier.arrive.expect_tx.shared::cta.b64 _, [%0], %1;" ::"r"(bar), "r"(tx) : "memory");
}
__device__ __forceinline__ bool mbar_test(uint32_t bar, uint32_t ph) {
  uint32_t ok;
  asm volatile("{\n.reg .pred p;\nmbarrier.test_wait.parity.shared::cta.b64 p, [%1], %2;\nselp.u32 %0, 1, 0, p;\n}\n"
               : "=r"(ok) : "r"(bar), "r"(ph) : "memory");
  return ok;
}
__device__ __forceinline__ bool mbar_try(uint32_t bar, uint32_t ph, uint32_t ns) {
  uint32_t ok;
  asm volatile("{\n.reg .pred p;\nmbarrier.try_wait.parity.shared::cta.b64 p, [%1], %2, %3;\nselp.u32 %0, 1, 0, p;\n}\n"
               : "=r"(ok) : "r"(bar), "r"(ph), "r"(ns) : "memory");
  return ok;
}
__device__ __forceinline__ void mbar_wait(uint32_t bar, uint32_t ph) {
  asm volatile("{\n.reg .pred p;\n.reg .u32 n;\nmov.u32 n, 0;\n"
               "LOOP:\nmbarrier.try_wait.parity.shared::cta.b64 p, [%0], %1;\n@p bra DONE;\n"
               "add.u32 n, n, 1;\nsetp.lt.u32 p, n, 0x1000000;\n@p bra LOOP;\ntrap;\n"
               "DONE:\n}\n" ::"r"(bar), "r"(ph) : "memory");
}
template <int NS> __device__ __forceinline__ void mbar_wait_slow(uint32_t bar, uint32_t ph) {
  asm volatile("{\n.reg .pred p;\n.reg .u32 n;\nmov.u32 n, 0;\n"
               "LOOP:\nmbarrier.test_wait.parity.shared::cta.b64 p, [%0], %1;\n@p bra DONE;\n"
               "nanosleep.u32 %2;\nadd.u32 n, n, 1;\nsetp.lt.u32 p, n, 0x400000;\n@p bra LOOP;\ntrap;\n"
               "DONE:\n}\n" ::"r"(bar), "r"(ph), "n"(NS) : "memory");
}
__device__ __forceinline__ void mbar_arrive_cluster_if(bool on, uint32_t addr) {
  asm volatile("{\n.reg .pred p;\nsetp.ne.b32 p, %1, 0;\n@p mbarrier.arrive.shared::cluster.b64 _, [%0];\n}\n" ::"r"(addr), "r"((int)on) : "memory");
}
__device__ __forceinline__ void tma2d(uint32_t dst, const CUtensorMap* m, uint32_t bar, int c0, int c1) {
  asm volatile("cp.async.bulk.tensor.2d.shared::cluster.global.mbarrier::complete_tx::bytes [%0], [%1, {%3, %4}], [%2];"
               ::"r"(dst), "l"(m), "r"(bar), "r"(c0), "r"(c1) : "memory");
}
__device__ __forceinline__ void tma3d(uint32_t dst, const CUtensorMap* m, uint32_t bar, int c0, int c1, int c2) {
  asm volatile("cp.async.bulk.tensor.3d.shared::cluster.global.mbarrier::complete_tx::bytes [%0], [%1, {%3, %4, %5}], [%2];"
               ::"r"(dst), "l"(m), "r"(bar), "r"(c0), "r"(c1), "r"(c2) : "memory");
}
__device__ __forceinline__ void tma3d_mc(uint32_t dst, const CUtensorMap* m, uint32_t bar, int c0, int c1, int c2) {
  asm volatile("cp.async.bulk.tensor.3d.shared::cluster.global.mbarrier::complete_tx::bytes.multicast::cluster"
               " [%0], [%1, {%3, %4, %5}], [%2], %6;"
               ::"r"(dst), "l"(m), "r"(bar), "r"(c0), "r"(c1), "r"(c2), "h"((uint16_t)3) : "memory");
}
__device__ __forceinline__ void tma3d_store(const CUtensorMap* m, uint32_t src, int c0, int c1, int c2) {
  asm volatile("cp.async.bulk.tensor.3d.global.shared::cta.bulk_group [%0, {%2, %3, %4}], [%1];"
               ::"l"(m), "r"(src), "r"(c0), "r"(c1), "r"(c2) : "memory");
}
__device__ __forceinline__ void bar_sync(int id, int n) { asm volatile("bar.sync %0, %1;" ::"r"(id), "r"(n) : "memory"); }
__device__ __forceinline__ uint32_t pack_bf16(float lo, float hi) {
  uint32_t r;
  asm("cvt.rn.bf16x2.f32 %0, %1, %2;" : "=r"(r) : "f"(hi), "f"(lo));
  return r;
}
__device__ __forceinline__ float ex2(float x) {
  float y;
  asm("ex2.approx.ftz.f32 %0, %1;" : "=f"(y) : "f"(x));
  return y;
}
__device__ __forceinline__ float rcp(float x) {
  float y;
  asm("rcp.approx.ftz.f32 %0, %1;" : "=f"(y) : "f"(x));
  return y;
}
__device__ __forceinline__ void stsm4(uint32_t addr, uint32_t a, uint32_t b, uint32_t c, uint32_t d) {
  asm volatile("stmatrix.sync.aligned.m8n8.x4.shared.b16 [%0], {%1, %2, %3, %4};" ::"r"(addr), "r"(a), "r"(b), "r"(c), "r"(d) : "memory");
}

__device__ __forceinline__ void tma4d_mc_hint(uint32_t dst, const CUtensorMap* m, uint32_t bar, int c3, uint64_t pol) {
  asm volatile("cp.async.bulk.tensor.4d.shared::cluster.global.mbarrier::complete_tx::bytes.multicast::cluster.L2::cache_hint"
               " [%0], [%1, {%3, %3, %3, %4}], [%2], %5, %6;"
               ::"r"(dst), "l"(m), "r"(bar), "r"(0), "r"(c3), "h"((uint16_t)3), "l"(pol) : "memory");
}
__device__ __forceinline__ void tma5d_mc(uint32_t dst, const CUtensorMap* m, uint32_t bar, int c2, int c4) {
  asm volatile("cp.async.bulk.tensor.5d.shared::cluster.global.mbarrier::complete_tx::bytes.multicast::cluster"
               " [%0], [%1, {%3, %3, %4, %3, %5}], [%2], %6;"
               ::"r"(dst), "l"(m), "r"(bar), "r"(0), "r"(c2), "r"(c4), "h"((uint16_t)3) : "memory");
}
__device__ __forceinline__ void bulk_load_hint(uint32_t dst, const void* src, uint32_t bytes, uint32_t bar, uint64_t pol) {
  asm volatile("cp.async.bulk.shared::cluster.global.mbarrier::complete_tx::bytes.L2::cache_hint [%0], [%1], %2, [%3], %4;"
               ::"r"(dst), "l"(src), "r"(bytes), "r"(bar), "l"(pol) : "memory");
}
__device__ __forceinline__ void stg128_hint(void* p, uint32_t a, uint32_t b, uint32_t c, uint32_t d, uint64_t pol) {
  asm volatile("st.global.L2::cache_hint.v4.b32 [%0], {%1, %2, %3, %4}, %5;" ::"l"(p), "r"(a), "r"(b), "r"(c), "r"(d), "l"(pol) : "memory");
}
__device__ __forceinline__ void stg2_if(bool on, void* p, uint32_t a, uint32_t b, uint32_t c, uint32_t d, uint32_t e, uint32_t f,
                                        uint32_t g, uint32_t h, uint64_t pol) {
  asm volatile("{\n.reg .pred p;\nsetp.ne.b32 p, %10, 0;\n"
               "@p st.global.L2::cache_hint.v4.b32 [%0], {%1, %2, %3, %4}, %9;\n"
               "@p st.global.L2::cache_hint.v4.b32 [%0 + 512], {%5, %6, %7, %8}, %9;\n}\n"
               ::"l"(p), "r"(a), "r"(b), "r"(c), "r"(d), "r"(e), "r"(f), "r"(g), "r"(h), "l"(pol), "r"((int)on) : "memory");
}
__device__ __forceinline__ uint64_t make_policy(bool first) {
  uint64_t pf, pn;
  asm("createpolicy.fractional.L2::evict_first.b64 %0, 1.0;" : "=l"(pf));
  asm("createpolicy.fractional.L2::evict_normal.b64 %0, 1.0;" : "=l"(pn));
  return first ? pf : pn;
}
__device__ __forceinline__ bool elect() {
  uint32_t ok;
  asm volatile("{\n.reg .pred p;\nelect.sync _|p, 0xffffffff;\nselp.u32 %0, 1, 0, p;\n}\n" : "=r"(ok));
  return ok;
}
__device__ __forceinline__ void mbar_arrive(uint32_t bar) {
  asm volatile("mbarrier.arrive.shared::cta.b64 _, [%0];" ::"r"(bar) : "memory");
}
__device__ __forceinline__ void mbar_arrive_if(bool on, uint32_t bar) {
  asm volatile("{\n.reg .pred p;\nsetp.ne.b32 p, %1, 0;\n@p mbarrier.arrive.shared::cta.b64 _, [%0];\n}\n" ::"r"(bar), "r"((int)on) : "memory");
}
__device__ __forceinline__ void stg128(void* p, uint32_t a, uint32_t b, uint32_t c, uint32_t d) {
  asm volatile("st.global.v4.b32 [%0], {%1, %2, %3, %4};" ::"l"(p), "r"(a), "r"(b), "r"(c), "r"(d) : "memory");
}
__device__ __forceinline__ void lds2_if(bool on, uint32_t p, uint32_t (&t)[8]) {
  asm volatile("{\n.reg .pred p;\nsetp.ne.b32 p, %9, 0;\n@p ld.shared.v4.b32 {%0, %1, %2, %3}, [%8];\n@p ld.shared.v4.b32 {%4, %5, %6, %7}, [%8 + 512];\n}\n"
               : "+r"(t[0]), "+r"(t[1]), "+r"(t[2]), "+r"(t[3]), "+r"(t[4]), "+r"(t[5]), "+r"(t[6]), "+r"(t[7]) : "r"(p), "r"((int)on) : "memory");
}
__device__ __forceinline__ void lds128(uint32_t p, uint32_t& a, uint32_t& b, uint32_t& c, uint32_t& d) {
  asm volatile("ld.shared.v4.b32 {%0, %1, %2, %3}, [%4];" : "=r"(a), "=r"(b), "=r"(c), "=r"(d) : "r"(p) : "memory");
}
template <class T> __device__ __forceinline__ T* ptr_add(T* base, uint32_t bytes) {
  T* r;
  asm("{\n.reg .u32 lo, hi;\nmov.b64 {lo, hi}, %1;\nadd.cc.u32 lo, lo, %2;\naddc.u32 hi, hi, 0;\nmov.b64 %0, {lo, hi};\n}\n" : "=l"(r) : "l"(base), "r"(bytes));
  return r;
}
__device__ __forceinline__ uint32_t lds32(uint32_t p) {
  uint32_t v;
  asm volatile("ld.volatile.shared.u32 %0, [%1];" : "=r"(v) : "r"(p) : "memory");
  return v;
}
__device__ __forceinline__ uint32_t flag_get(const unsigned int* p) {
  uint32_t v;
  asm volatile("ld.acquire.gpu.global.u32 %0, [%1];" : "=r"(v) : "l"(p) : "memory");
  return v;
}
__device__ __forceinline__ uint32_t wait_word(uint32_t p, uint32_t target) {
  uint32_t v;
  asm volatile("{\n.reg .pred p;\n.reg .u32 n;\nmov.u32 n, 0;\n"
               "LOOP:\nld.acquire.cta.shared.u32 %0, [%1];\nsetp.ge.u32 p, %0, %2;\n@p bra DONE;\n"
               "nanosleep.u32 %3;\nadd.u32 n, n, 1;\nsetp.lt.u32 p, n, 0x400000;\n@p bra LOOP;\ntrap;\n"
               "DONE:\n}\n" : "=r"(v) : "r"(p), "r"(target), "n"(400) : "memory");
  return v;
}
__device__ __forceinline__ void flag_set(unsigned int* p, uint32_t v) {
  asm volatile("st.release.gpu.global.u32 [%0], %1;" ::"l"(p), "r"(v) : "memory");
}
__device__ __forceinline__ void flag_dec(unsigned int* p) {
  asm volatile("red.relaxed.gpu.global.add.u32 [%0], 0xffffffff;" ::"l"(p) : "memory");
}

struct Cursor {
  int bi;
  uint32_t ph;
  __device__ __forceinline__ void next() {
    if (++bi == NBAR) { bi = 0; ph ^= 1; }
  }
};

constexpr float kScaleLog2 = 0.07216878364870322f * 1.4426950408889634f;
constexpr float kSumLimit = 1048576.0f;

__global__ void __cluster_dims__(2, 1, 1) __launch_bounds__(384, 1)
fused_kernel(const __grid_constant__ Params P) {
  extern __shared__ uint8_t smem_raw[];
  const uint32_t sbase = (smem_u32(smem_raw) + 1023) & ~1023u;
  const uint32_t full0 = sbase + RING, empty0 = full0 + 8 * NBAR, odone0 = empty0 + 8 * NBAR, ev0 = odone0 + 8 * MAX_OPS;
  const uint32_t progress = ev0 + 8 * MAX_EV, jobw = progress + 4;
  const uint32_t rank = blockIdx.x & 1;
  const int role = blockIdx.x >> 1;
  const int wid = __shfl_sync(0xffffffffu, (int)(threadIdx.x >> 5), 0);
  const int wg = wid >> 2;

  if (wid < 8) {
    if (elect()) {
#pragma unroll
      for (int j = 0; j < 16; j++) {
        const int i = EARLY + 16 * wid + j;
        if (i < 2 * NBAR + MAX_OPS + MAX_EV) mbar_init(full0 + 8 * i, i < NBAR ? 1 : i < 2 * NBAR ? 16 : i < 2 * NBAR + MAX_OPS ? 8 : 1);
      }
      if (wid == 7) asm volatile("st.shared.v2.u32 [%0], {0, 0};\nfence.acq_rel.cta;" ::"r"(progress) : "memory");
      asm volatile("fence.mbarrier_init.release.cluster;" ::: "memory");
    }
  } else if (wid == 8) {
    const uint32_t op0 = P.first[role];
    if (elect()) {
#pragma unroll
      for (int k = 0; k < EARLY; k++) mbar_init(full0 + 8 * k, 1);
      asm volatile("fence.mbarrier_init.release.cluster;" ::: "memory");
      const int blk = (op0 >> 10) & 1;
      if ((op0 & 3) == OP_Q) {
#pragma unroll
        for (int k = 0; k < EARLY; k++) {
          mbar_expect(full0 + 8 * k, SZ_Q);
          tma2d(sbase + k * SZ_Q, &P.x[blk], full0 + 8 * k, 64 * k, ((op0 >> 7) & 7) * kSq + rank * 128);
          tma3d(sbase + k * SZ_Q + 16384, &P.wq[blk], full0 + 8 * k, 0, 64 * k, 3 * ((op0 >> 2) & 31));
        }
      }
      asm volatile("prefetch.tensormap [%0];" ::"l"(rank ? &P.v[blk] : &P.k[blk]) : "memory");
    }
  }
  __syncwarp();
  asm volatile("barrier.cluster.arrive.relaxed.aligned;\nbarrier.cluster.wait.aligned;" ::: "memory");

  if (wg < 2) {
    asm volatile("setmaxnreg.inc.sync.aligned.u32 240;");
    const uint32_t* prog = P.prog[role].c;
    const int lane = threadIdx.x & 31, warp = wid & 3;
    uint32_t empty_rem;
    asm volatile("mapa.shared::cluster.u32 %0, %1, %2;" : "=r"(empty_rem) : "r"(empty0), "r"(lane & 1));
    auto release = [&](int slot) { mbar_arrive_cluster_if(lane < 2, empty_rem + 8 * slot); };
    Cursor r{0, 0};
    const uint32_t ring16 = (sbase & 0x3FFFF) >> 4;
    uint32_t cur = ring16;
    bool rdy0 = false, rdy1 = false;
    auto probe1 = [&]() { rdy0 = mbar_test(full0 + 8 * r.bi, r.ph); };
    auto probe2 = [&]() {
      Cursor n = r;
      rdy0 = mbar_test(full0 + 8 * n.bi, n.ph);
      n.next();
      rdy1 = mbar_test(full0 + 8 * n.bi, n.ph);
    };
    auto take = [&](bool rdy, uint32_t bytes, uint32_t& addr) {
      const int bi = r.bi;
      if (__builtin_expect(!__all_sync(0xffffffffu, rdy), 0)) mbar_wait(full0 + 8 * r.bi, r.ph);
      r.next();
      if (cur > ring16 + ((RING - bytes) >> 4)) cur = ring16;
      addr = cur;
      cur += bytes >> 4;
      return bi;
    };
    uint32_t keep = lane;
    const bool never = P.dbg == 0xffffffffu;
    uint32_t q[48];
#pragma unroll
    for (int i = 0; i < 48; i++) q[i] = 0;
    const int row = wg * 64 + warp * 16 + (lane >> 2);
    const int img0 = row * 4 + ((lane & 3) ^ ((row >> 1) & 3));
    uint4* pend = nullptr;
    bool pend_any = false;
    uint64_t spol;
    int pc = 0;
    auto slab = [&](int c, int i0) {
#pragma unroll
      for (int i = i0; i < 6; i++)
        stg2_if(c == i, pend + i * 512, q[8 * i], q[8 * i + 1], q[8 * i + 2], q[8 * i + 3],
                q[8 * i + 4], q[8 * i + 5], q[8 * i + 6], q[8 * i + 7], spol);
    };
    auto drain = [&](int c) {
      if (!pend_any || c >= 6) return;
      slab(c, 0);
      if (c == 5) {
        __syncwarp();
        mbar_arrive_if(lane == 0, odone0 - 8 + 8 * pc);
      }
    };

    for (;; pc++) {
      uint32_t op = prog[pc];
      const int type = op & 3;
      auto enter = [&]() {
        r.bi = (op >> 15) & 15; r.ph = (op >> 19) & 1; cur = ring16 + (((op >> 20) & 63) << 8);
      };
      enter();
      pend_any = op & C_PEND;
      spol = make_policy(!(op & C_SOON));
      uint32_t job = 0;
      if ((op & (3 | C_WIDE)) == OP_O) job = __shfl_sync(0xffffffffu, wait_word(jobw, 1), 0);
      if (type == OP_END || job == OP_O) {
#pragma unroll 1
        for (int c = 0; c < 6; c++) drain(c);
        asm volatile("barrier.cluster.arrive.relaxed;" ::: "memory");
        break;
      }
      {
        float s[32], o[96];
        uint32_t ad0;
        int bi0, sk1;
        uint32_t pa[16], pb[16];
        float mc0, mc1, l0, l1;
        bool shifted;
        uint32_t nop;
        auto expo = [&](float (&s)[32], uint32_t (&pout)[16], float& b0, float& b1, bool shift, auto mid) {
          float c0, c1;
#pragma unroll
          for (int i = 0; i < 8; i++) {
            const float e0 = ex2(shift ? s[4 * i] - mc0 : s[4 * i]), e1 = ex2(shift ? s[4 * i + 1] - mc0 : s[4 * i + 1]);
            const float e2 = ex2(shift ? s[4 * i + 2] - mc1 : s[4 * i + 2]), e3 = ex2(shift ? s[4 * i + 3] - mc1 : s[4 * i + 3]);
            if (i) { b0 += e0; c0 += e1; b1 += e2; c1 += e3; } else { b0 = e0; c0 = e1; b1 = e2; c1 = e3; }
            pout[2 * i] = pack_bf16(e0, e1); pout[2 * i + 1] = pack_bf16(e2, e3);
            if (i & 1) mid(i >> 1);
          }
          b0 += c0; b1 += c1;
        };
        auto rowmax = [&](float (&s)[32], float& m0, float& m1) {
          m0 = fmaxf(s[0], s[1]); m1 = fmaxf(s[2], s[3]);
#pragma unroll
          for (int i = 1; i < 8; i++) { m0 = fmaxf(m0, fmaxf(s[4 * i], s[4 * i + 1])); m1 = fmaxf(m1, fmaxf(s[4 * i + 2], s[4 * i + 3])); }
          m0 = fmaxf(m0, __shfl_xor_sync(0xffffffffu, m0, 1)); m1 = fmaxf(m1, __shfl_xor_sync(0xffffffffu, m1, 1));
          m0 = fmaxf(m0, __shfl_xor_sync(0xffffffffu, m0, 2)); m1 = fmaxf(m1, __shfl_xor_sync(0xffffffffu, m1, 2));
        };
        auto first = [&](float (&s)[32], int sk0, auto mid) {
          fence_regs(s);
          release(sk0);
          mc0 = 0.f; mc1 = 0.f;
          expo(s, pa, l0, l1, false, mid);
          shifted = __any_sync(0xffffffffu, !(fmaxf(l0, l1) <= kSumLimit && fminf(l0, l1) >= 1.f / kSumLimit));
          if (shifted) {
            rowmax(s, mc0, mc1);
            expo(s, pa, l0, l1, true, [](int) {});
          }
        };
        auto qk = [&](float (&s)[32], uint32_t ak, int k0 = 0, int k1 = 12) {
#pragma unroll
          for (int kk = k0; kk < k1; kk++)
            wgmma_rs_n64<0>(s, q[4 * kk], q[4 * kk + 1], q[4 * kk + 2], q[4 * kk + 3], mk_desc(ak, 16, KV_SBO, 1) + ((kk >> 2) * KV_CH + (kk & 3) * 2), kk != 0);
          if (k1 == 12) wg_commit();
        };
        auto pv = [&](uint32_t (&pin)[16], uint32_t av, int acc) {
#pragma unroll
          for (int kk = 0; kk < 4; kk++)
            wgmma_rs_n192<1>(o, pin[4 * kk], pin[4 * kk + 1], pin[4 * kk + 2], pin[4 * kk + 3], mk_desc(av, KV_CH * 16, KV_SBO, 1) + (kk * (KV_SBO / 8)), acc || (kk != 0));
          wg_commit();
        };
        auto finish = [&](uint32_t (&pout)[16], int sk, int sv) {
          probe2();
          wg_wait<1>();
          fence_regs(s);
          release(sk);
          float b0, b1;
#pragma unroll 1
          for (bool redo = false;; redo = true) {
            expo(s, pout, b0, b1, false, [](int) {});
            if (!__any_sync(0xffffffffu, !redo && (shifted || !(fmaxf(b0, b1) <= kSumLimit)))) break;
            shifted = true;
            rowmax(s, b0, b1);
            b0 = fmaxf(mc0, b0); b1 = fmaxf(mc1, b1);
            const float a0 = ex2(mc0 - b0), a1 = ex2(mc1 - b1);
            mc0 = b0; mc1 = b1;
            l0 *= a0; l1 *= a1;
            wg_wait<0>();
            fence_regs(o);
#pragma unroll
            for (int i = 0; i < 24; i++) { o[4 * i] *= a0; o[4 * i + 1] *= a0; o[4 * i + 2] *= a1; o[4 * i + 3] *= a1; }
#pragma unroll
            for (int i = 0; i < 32; i++) s[i] -= (i & 2) ? mc1 : mc0;
          }
          l0 += b0; l1 += b1;
          wg_wait<0>();
          fence_regs(o);
          release(sv);
        };
        auto step = [&](uint32_t (&pin)[16], uint32_t (&pout)[16]) {
          uint32_t ak, av;
          const int sk = take(rdy0, SZ_KV, ak), sv = take(rdy1, SZ_KV, av);
          wg_fence();
          qk(s, ak);
          pv(pin, av, 1);
          finish(pout, sk, sv);
        };
        auto unpark = [&]() {
          uint32_t ad, ak;
          const int bi = take(rdy0, SZ_PARK, ad);
#pragma unroll
          for (int i = 0; i < 12; i++) lds128(sbase + (ad - ring16 + img0) * 16 + (i >> 1) * 8192 + (i & 1) * 512, q[4 * i], q[4 * i + 1], q[4 * i + 2], q[4 * i + 3]);
          const int sk0 = take(false, SZ_KV, ak);
          fence_regs(q);
          release(bi);
          wg_fence();
          qk(s, ak);
          probe2();
          return sk0;
        };
        auto mma4 = [&](uint32_t ad, int acc) {
#pragma unroll
          for (int kk = 0; kk < 4; kk++)
            wgmma_ss_n192<1>(o, mk_desc(ad + wg * 512, 16, 1024, 1) + (kk * 2), mk_desc(ad, 8192, 1024, 1) + (1024 + kk * 128), acc || kk != 0);
        };
        auto convert = [&](int i0, int i1) {
          sched_fence(keep, never);
#pragma unroll
          for (int i = i0; i < i1; i++) {
            q[i] = pack_bf16(o[2 * i] * kScaleLog2, o[2 * i + 1] * kScaleLog2);
            if (i % CONV_G == CONV_G - 1 && i != i1 - 1) sched_fence(keep, never);
          }
          sched_fence(keep, never);
        };
        auto kend = [&](int bi, int k) {
          wg_commit();
          drain(k < 8 ? (QDRAIN >> (4 * k)) & 7 : 7);
          probe1();
          wg_wait<0>();
          release(bi);
        };
        if (type == OP_O) {
          float c[80];
          int prev = 0;
          auto hand_over = [&](float (&c)[80], uint4* dst) {
            fence_regs(c);
#pragma unroll
            for (int i = 0; i < 48; i++) q[i] = i < 8 ? 0 : pack_bf16(c[2 * i - 16], c[2 * i - 15]);
            pend = dst;
          };
          auto mma2 = [&](float (&c)[80], uint32_t ad, uint32_t oa, uint32_t ob, int acc) {
            wgmma_ss_n160<1>(c, mk_desc(ad + wg * 256, 16, 512, 2) + (oa), mk_desc(ad, 2048, 512, 2) + (1024 + ob), acc);
            wgmma_ss_n160<1>(c, mk_desc(ad + wg * 256, 16, 512, 2) + (oa + 2), mk_desc(ad, 2048, 512, 2) + (1024 + ob + 64), 1);
          };
          auto kstep = [&](float (&c)[80], int acc, auto hook, uint32_t bytes = SZ_O) {
            uint32_t ad;
            const int bi = take(rdy0, bytes, ad);
            wg_fence();
            mma2(c, ad, 0, 0, acc);
            wg_commit();
            if (acc) { wg_wait<1>(); mbar_arrive_cluster_if(lane < 2 && (acc == 1 || wg == 0), empty_rem + 8 * prev); }
            mma2(c, ad, 512, 640, 1);
            wg_commit();
            prev = bi;
            hook();
            probe1();
            wg_wait<1>();
          };
          if (op & C_WIDE) {
            float d[80];
            const int nk = (op >> 2) & 127;
            uint4* part = ptr_add(P.g->part, (((op >> 9) & 63) * 2 + rank) * SZ_PARK + img0 * 16);
            auto wstep = [&](int acc, auto hook) {
              uint32_t ad;
              const int bi = take(rdy0, SZ_W, ad);
              wg_fence();
              mma2(d, ad, 0, 0, acc);
              mma2(d, ad, 512, 640, 1);
              wg_commit();
              if (acc) { wg_wait<1>(); release(prev); }
              mma2(c, ad, 0, 1280, acc);
              mma2(c, ad, 512, 1920, 1);
              wg_commit();
              prev = bi;
              hook();
              probe1();
              wg_wait<1>();
            };
            wstep(0, [&]() { drain(0); drain(1); });
#pragma unroll 1
            for (int k = 2; k < 6; k += 2) wstep(1, [&]() { drain(k); drain(k + 1); });
#pragma unroll 1
            for (int k = 3 + TAIL; k < nk; k++) {
              wstep(1, []() {});
            }
#pragma unroll 1
            for (int k = 0; k < TAIL; k++) kstep(d, 1, []() {});
            nop = prog[pc + 1];
            spol = make_policy(!(nop & C_SOON));
            kstep(c, 1, [&]() { hand_over(d, part - 6144); });
#pragma unroll 1
            for (int k = 1; k < TAIL; k++) kstep(c, 1, [&]() { slab(k, 1); });
            if ((nop & 3) == OP_Q) {
              op = nop;
              enter();
              pc++;
              pend_any = true;
              bi0 = take(rdy0, SZ_Q, ad0);
              undefine(o);
              wg_fence();
              mma4(ad0, 0);
              wg_commit();
              wg_wait<1>();
              release(prev);
              hand_over(c, part);
              probe1();
              wg_wait<0>();
              release(bi0);
              fence_regs(o);
              goto next_head;
            }
            wg_wait<0>();
            release(prev);
            hand_over(c, part);
            continue;
          }
          auto unblock = [&](int k) {
            if (__all_sync(0xffffffffu, rdy0) || __all_sync(0xffffffffu, mbar_try(full0 + 8 * r.bi, r.ph, TRYNS))) return;
#pragma unroll 1
            for (; k < 6; k++) drain(k);
            pend_any = false;
          };
          unblock(0);
          kstep(c, 0, [&]() { drain(0); });
          int left = ((job >> 13) & 127) - 6;
#pragma unroll 1
          for (uint32_t k = 1, pace = left >= SLOWF - 6 ? SLOWP : left <= FASTF - 6 ? FASTP : 0x155; k < 6; pace >>= 2, left--) {
            unblock(k);
            kstep(c, 1, [&]() {
#pragma unroll 1
              for (int i = pace & 3; i > 0; i--) drain(k++);
            });
          }
#pragma unroll 1
          for (; left > 0; left--) kstep(c, 1, []() {});
          uint32_t t[8], stage[3];
          float u[80];
          auto unpack = [&](int j) {
#pragma unroll
            for (int i = 0; i < 8; i++) {
              u[16 * j + 2 * i] = __uint_as_float(t[i] << 16); u[16 * j + 2 * i + 1] = __uint_as_float(t[i] & 0xffff0000u);
              asm volatile("" : "+f"(u[16 * j + 2 * i]), "+f"(u[16 * j + 2 * i + 1]));
            }
          };
#pragma unroll
          for (int i = 0; i < 8; i++) t[i] = 0;
          const uint32_t bytes = (job & P_LD) ? SZ_OL : SZ_O;
#pragma unroll
          for (int j = 0; j < 5; j++) {
            if (j == 5 - SKEW && wg == 1) {
              wg_wait<0>();
              release(prev);
              bar_sync(1, 256);
            }
            kstep(c, j == 5 - SKEW ? 2 : 1, [&]() {
              if (SKEW && j == 4) asm volatile("{\n.reg .pred p;\nsetp.eq.u32 p, %0, 0;\n@p bar.arrive 1, 256;\n}\n" ::"r"(wg) : "memory");
              if (j) unpack(j - 1);
              lds2_if(job & P_LD, sbase + (cur - ring16 + img0) * 16 - 8192, t);
              if (j >= 1 && j <= 3) stage[j - 1] = sbase + (cur - ring16) * 16 - bytes + wid * 1024;
            }, bytes);
          }
          unpack(4);
          sched_fence(keep, never);
          wg_wait<0>();
          fence_regs(c);
          release(prev);
          asm volatile("barrier.cluster.arrive.relaxed;" ::: "memory");
#pragma unroll
          for (int i = 0; i < 10; i++) {
            const int v = (i & 1) * 2 + (lane >> 4);
            const uint32_t sa = stage[i >> 2] + (i & 2) * 4096;
            stsm4(sa + (lane & 15) * 64 + ((v ^ ((lane >> 1) & 3)) << 4), pack_bf16(c[8 * i] + u[8 * i], c[8 * i + 1] + u[8 * i + 1]),
                  pack_bf16(c[8 * i + 2] + u[8 * i + 2], c[8 * i + 3] + u[8 * i + 3]), pack_bf16(c[8 * i + 4] + u[8 * i + 4], c[8 * i + 5] + u[8 * i + 5]),
                  pack_bf16(c[8 * i + 6] + u[8 * i + 6], c[8 * i + 7] + u[8 * i + 7]));
          }
          asm volatile("fence.proxy.async.shared::cta;" ::: "memory");
          __syncwarp();
          if (elect()) {
#pragma unroll
            for (int i = 0; i < 5; i++)
              tma3d_store(&P.out, stage[i >> 1] + (i & 1) * 8192, 0, ((job >> 7) & 7) * kSq + rank * 128 + wid * 16, ((job >> 10) & 1) * 20 + ((job >> 20) & 3) * 5 + i);
            asm volatile("cp.async.bulk.commit_group;\ncp.async.bulk.wait_group.read 0;" ::: "memory");
          }
          __syncwarp();
          break;
        }
        bi0 = take(rdy0, SZ_Q, ad0);
        undefine(o);
        wg_fence();
        mma4(ad0, 0);
        kend(bi0, 0);
        fence_regs(o);
      next_head:
        {
#pragma unroll 1
          for (int k = 1; k < ((op & F_PARK) ? 10 : 8); k++) {
            uint32_t ad;
            const int bi = take(rdy0, SZ_Q, ad);
            wg_fence();
            mma4(ad, 1);
            kend(bi, k);
          }
          if (op & F_PARK) {
            fence_regs(o);
            convert(0, 48);
            pend = ptr_add(P.g->tile, (((op >> 2) & 511) * 2 + rank) * SZ_PARK + img0 * 16);
            continue;
          }
          uint32_t a8, a9, ak0, ak1;
          const int b8 = take(rdy0, SZ_Q, a8), b9 = take(false, SZ_Q, a9);
          wg_fence();
          mma4(a8, 1);
          wg_commit();
          mma4(a9, 1);
          wg_commit();
          pc++;
          wg_wait<1>();
          release(b8);
          const int sk0 = take(false, SZ_KV, ak0);
          wg_wait<0>();
          fence_regs(o);
          release(b9);
          float s0[32];
          convert(0, CONV_0);
          wg_fence();
          qk(s0, ak0, 0, 4);
          convert(CONV_0, 48);
          wg_fence();
          qk(s0, ak0, 4, 12);
          sk1 = take(false, SZ_KV, ak1);
          probe1();
          wg_wait<0>();
          first(s0, sk0, [&](int i) {
            if (i != QA && i != QB && i != QC) return;
            sched_fence(keep, never);
            wg_fence();
            if (i == QA) qk(s, ak1, 0, 4);
            if (i == QB) qk(s, ak1, 4, 8);
            if (i == QC) qk(s, ak1, 8, 12);
            sched_fence(keep, never);
          });
        }
        for (;;) {
          {
            uint32_t av;
            const int sv = take(rdy0, SZ_KV, av);
            undefine(o);
            wg_fence();
            pv(pa, av, 0);
            finish(pb, sk1, sv);
          }
          nop = prog[pc + 1];
#pragma unroll 1
          for (int jj = 0; jj < 7; jj++) {
            step(pb, pa);
            step(pa, pb);
          }
          float i0, i1;
          auto last = [&]() {
            uint32_t av;
            const int sv = take(rdy0, SZ_KV, av);
            wg_fence();
            pv(pb, av, 1);
            sched_fence(keep, never);
            probe1();
            l0 += __shfl_xor_sync(0xffffffffu, l0, 1); l1 += __shfl_xor_sync(0xffffffffu, l1, 1);
            l0 += __shfl_xor_sync(0xffffffffu, l0, 2); l1 += __shfl_xor_sync(0xffffffffu, l1, 2);
            i0 = rcp(l0); i1 = rcp(l1);
            pend = ptr_add(P.g->tile, (((op >> 2) & 511) * 2 + rank) * SZ_PARK + img0 * 16);
            return sv;
          };
          auto normalise = [&](uint32_t (&d)[48], auto mid) {
#pragma unroll
            for (int i = 0; i < 24; i++) {
              d[8 * (i >> 2) + (i & 3)] = pack_bf16(o[4 * i] * i0, o[4 * i + 1] * i0);
              d[8 * (i >> 2) + (i & 3) + 4] = pack_bf16(o[4 * i + 2] * i1, o[4 * i + 3] * i1);
              if (i % NORM_G == NORM_G - 1 && i != 23) sched_fence(keep, never);
              if ((i & 3) == 3 && i != 23) mid(i >> 2);
            }
          };
          const int sv = last();
          if ((nop & 3) != OP_A) {
            op = nop;
            enter();
            pend_any = true;
            spol = make_policy(!(op & C_SOON));
            bi0 = take(rdy0 || (nop & 3) != OP_Q, SZ_Q, ad0);
            sched_fence(keep, never);
            wg_wait<0>();
            fence_regs(o);
            release(sv);
            normalise(q, [](int) {});
            undefine(o);
            if ((nop & 3) != OP_Q) break;
            sched_fence(keep, never);
            wg_fence();
            mma4(ad0, 0);
            pc++;
            kend(bi0, 0);
            fence_regs(o);
            goto next_head;
          }
          const int sk0 = unpark();
          wg_wait<1>();
          fence_regs(o);
          release(sv);
          uint32_t t[48];
          spol = make_policy(!(nop & C_SOON));
          auto st = [&](int i) {
            stg2_if(true, pend + i * 512, t[8 * i], t[8 * i + 1], t[8 * i + 2], t[8 * i + 3], t[8 * i + 4], t[8 * i + 5], t[8 * i + 6], t[8 * i + 7], spol);
          };
          normalise(t, [&](int i) { if (!(i & 1)) st(i >> 1); });
          wg_wait<0>();
          first(s, sk0, [&](int i) { if (i < 3) { sched_fence(keep, never); st(3 + i); } });
          __syncwarp();
          mbar_arrive_if(lane == 0, odone0 + 8 * pc);
          pc++;
          op = nop;
          uint32_t ak1;
          sk1 = take(rdy0, SZ_KV, ak1);
          rdy0 = rdy1;
          wg_fence();
          qk(s, ak1);
        }
      }
    }
    if (never) P.g->flag[0] = keep;
    asm volatile("barrier.cluster.wait;" ::: "memory");
  } else {
    asm volatile("setmaxnreg.dec.sync.aligned.u32 24;");
    const uint32_t* prog = P.prog[role].p;
    unsigned int* flag = P.g->flag + rank;
    if (wid == 8) {
      Cursor tail{0, 0};
      int head = 0, sh = 0;
      uint32_t cur = 0, used = 0;
      uint64_t fifo = 0;
      uint32_t dst, bar, ev = ev0, done = 0;
      uint64_t pol;
      asm volatile("createpolicy.fractional.L2::evict_first.b64 %0, 1.0;" : "=l"(pol));
      auto retire = [&]() {
        mbar_wait(empty0 + 8 * tail.bi, tail.ph);
        tail.next();
        used -= (uint32_t)fifo & 31;
        fifo >>= 5;
        sh -= 5;
        asm volatile("st.volatile.shared.u32 [%0], %1;" ::"r"(progress), "r"(++done) : "memory");
      };
      auto acquire = [&](uint32_t bytes) {
        uint32_t fp = bytes >> 12;
        if (cur + fp > (RING >> 12)) { fp += (RING >> 12) - cur; cur = 0; }
        used += fp;
        while (used > (RING >> 12) || sh == 5 * NBAR) retire();
        fifo |= (uint64_t)fp << sh;
        sh += 5;
        dst = sbase + (cur << 12);
        bar = full0 + 8 * head;
        cur += bytes >> 12;
        if (++head == NBAR) head = 0;
      };
      auto gate = [&]() {
        mbar_wait(ev, 0);
        ev += 8;
        asm volatile("fence.proxy.async.global;" ::: "memory");
      };
      for (int pc = 0;; pc++) {
        uint32_t op = prog[pc];
        const int type = op & 3;
        if (type == OP_END) break;
        if (op == OP_O) {
          gate();
          op = __shfl_sync(0xffffffffu, lds32(jobw), 0);
        }
        const int blk = (op >> 10) & 1;
        if (type == OP_Q) {
#pragma unroll 1
          for (int k = 0; k < 10; k++) {
            if (k == 9 && (op & P_GATE)) gate();
            acquire(SZ_Q);
            if ((pc > 0 || k >= EARLY) && elect()) {
              mbar_expect(bar, SZ_Q);
              tma2d(dst, &P.x[blk], bar, 64 * k, ((op >> 7) & 7) * kSq + rank * 128);
              if ((k & 1) == rank) tma3d_mc(dst + 16384, &P.wq[blk], bar, 0, 64 * k, 3 * ((op >> 2) & 31));
            }
          }
        } else if (type == OP_A) {
          const int row0 = ((op >> 2) & 255) * kSk;
          const CUtensorMap* kv_map = rank ? &P.v[blk] : &P.k[blk];
          if (op & F_PARK) {
            gate();
            acquire(SZ_PARK);
            if (elect()) {
              mbar_expect(bar, SZ_PARK);
              bulk_load_hint(dst, &P.g->tile[((op >> 20) * 2 + rank) * 3072], SZ_PARK, bar, make_policy(P.dbg & 4));
            }
          }
#pragma unroll 1
          for (int t = 0; t < 32; t++) {
            const int isv = t == 31 ? 1 : (t == 0 ? 0 : (~t & 1));
            const int j = isv ? (t - 1) >> 1 : (t + 1) >> 1;
            if (t == 31 && (op & P_GATE)) gate();
            acquire(SZ_KV);
            if (elect()) {
              mbar_expect(bar, SZ_KV);
              if (isv == (int)rank) tma4d_mc_hint(dst, kv_map, bar, row0 / 8 + 8 * j, pol);
            }
          }
        } else {
          const int n = (op >> 13) & 127, nw = (op & P_WIDE) ? n - TAIL : 0;
          const uint64_t pol_o = make_policy(P.dbg & (nw ? 1 : 2));
          const uint4* part = &P.g->part[((((op >> 5) & 60) + ((op >> 20) & 3)) * 2 + rank) * 3072 + 512];
#pragma unroll 1
          for (int i = 0; i < n + (nw ? TAIL : 0); i++) {
            const int k = nw ? (i < n ? i : i - TAIL) : kSteps - n + i, h = (k * 43) >> 7, col = 5 * (((op >> 20) & 3) + (i >= n));
            const uint4* src = &P.g->tile[(P.slot[((op >> 2) & 480) + h] * 2 + rank) * 3072 + (k - 3 * h) * 1024];
            const uint32_t j = (op & P_LD) ? i - n + 5 : 5, bytes = i < nw ? SZ_W : j < 5 ? SZ_OL : SZ_O;
            if ((op & P_PRE) ? i == 0 : j == 0) gate();
            if (i < n && (i == 0 || k == 3 * h)) gate();
            acquire(bytes);
            if (elect()) {
              mbar_expect(bar, bytes);
              tma5d_mc(dst + 16384 + rank * 10240, &P.wo[blk], bar, 8 * k + 4 * rank, col);
              bulk_load_hint(dst, src, 16384, bar, pol_o);
              if (i < nw) tma5d_mc(dst + SZ_O + rank * 10240, &P.wo[blk], bar, 8 * k + 4 * rank, col + 5);
              if (j < 5) bulk_load_hint(dst + SZ_O, part + j * 512, 8192, bar, pol);
              if ((op & P_PRE) && i < 10) asm volatile("cp.async.bulk.prefetch.L2.global [%0], 4096;" ::"l"(part + i * 256) : "memory");
            }
          }
        }
      }
#pragma unroll 1
      while (sh) retire();
    } else if (threadIdx.x == 288) {
      for (int pc = 0;; pc++) {
        const uint32_t op = prog[pc];
        const int type = op & 3;
        if (type == OP_END) break;
        if (type == OP_Q ? !(op & F_PARK) : type == OP_O && !(op & P_WIDE)) continue;
        const int id = type == OP_A ? (op >> 2) & 511 : type == OP_Q ? N_TILE + ((op >> 13) & 127) : ID_PART + ((op >> 5) & 60) + ((op >> 20) & 3);
        const uint32_t v = type == OP_O ? 1 : P.info[id] & 7;
        asm volatile("{\n.reg .pred p;\n.reg .u32 n;\nmov.u32 n, 0;\n"
                     "LOOP:\nmbarrier.try_wait.parity.shared::cta.b64 p, [%0], 0, 20000;\n@p bra DONE;\n"
                     "add.u32 n, n, 1;\nsetp.lt.u32 p, n, 0x1000000;\n@p bra LOOP;\ntrap;\n"
                     "DONE:\n}\n" ::"r"(odone0 + 8 * pc) : "memory");
        flag_set(flag + 2 * id, v);
        if (type == OP_O && (op & P_WIDE)) flag_set(flag + 2 * id + 2, v);
      }
    } else if (wid == 10) {
      int i = threadIdx.x & 31;
      uint32_t e = i < 8 ? P.prog[role].ev[i] : 0;
      for (uint32_t n = 0; __any_sync(0xffffffffu, e); n++) {
        uint32_t job = lds32(jobw);
        const int togo = (e & E_DRAW) ? (e & 1023) - lds32(progress) : 99;
        if (togo <= 0 && rank == 0) {
          job = P.job[atomicInc(&P.g->ticket, gridDim.x / 2 - 1)];
          asm volatile("{\n.reg .u32 a;\nmapa.shared::cluster.u32 a, %0, 1;\nst.volatile.shared::cluster.u32 [a], %1;\n"
                       "st.volatile.shared.u32 [%0], %1;\n}\n" ::"r"(jobw), "r"(job) : "memory");
        }
        if ((e & E_JOB) && job) {
          const uint32_t j = e & 63, heads = job == OP_O ? 0 : kH - ((job >> 2) & 31), jp = !(job & P_LD) ? 63 : (job & P_PRE) ? 0 : heads - 1, h = j - (j > jp);
          e = j == jp ? (ID_PART + ((job >> 5) & 60) + ((job >> 20) & 3)) | E_ON | E_LAST : h < heads ? (((job >> 2) & 511) + h) | E_ON | E_LAST : 0;
        }
        unsigned int* f = ptr_add(flag, 8 * (e & 1023));
        const bool ok = (e & E_ON) ? flag_get(f) - 1 < ((e & E_FREE) ? 1 : 7) : (e & E_DRAW) && job;
        if (ok) {
          mbar_arrive(ev0 + 8 * i);
          if (e & (E_FREE | E_LAST)) flag_dec(f);
          i += 8;
          e = i < MAX_EV ? P.prog[role].ev[i] : 0;
        }
        asm volatile("{\n.reg .pred p;\nsetp.ge.u32 p, %0, 0x400000;\n@p trap;\n}\n" ::"r"(n));
        if (!__any_sync(0xffffffffu, ok)) __nanosleep(__any_sync(0xffffffffu, job || togo <= NEAR) ? WATNS2 : WATNS);
      }
    } else if (threadIdx.x == 352) {
      uint32_t items = 0;
      auto read = [&](int id) {
        if (!(P.info[id] & I_NEXT)) return;
        wait_word(progress, items);
        flag_dec(flag + 2 * id);
      };
      for (int pc = 0;; pc++) {
        const uint32_t op = prog[pc];
        const int type = op & 3;
        if (type == OP_END) break;
        if (type == OP_O) {
          const uint32_t n = (op >> 13) & 127, base = items;
#pragma unroll 1
          for (uint32_t k = 3, id = (op >> 2) & 511; k <= n; k += 3, id++) {
            items = base + k + (k + TAIL > n ? TAIL : 0);
            read(id);
          }
          items = base + n + TAIL;
        } else if (type == OP_A) {
          if (op & F_PARK) { items++; read(N_TILE + ((op >> 13) & 127)); }
          items += 32;
        } else {
          items += 10;
        }
      }
    }
    __syncwarp();
    asm volatile("barrier.cluster.arrive.relaxed;\nbarrier.cluster.wait;" ::: "memory");
  }
}

typedef CUresult (*EncodeFn)(CUtensorMap*, CUtensorMapDataType, cuuint32_t, void*, const cuuint64_t*, const cuuint64_t*,
                             const cuuint32_t*, const cuuint32_t*, CUtensorMapInterleave, CUtensorMapSwizzle,
                             CUtensorMapL2promotion, CUtensorMapFloatOOBfill);

void encode(EncodeFn fn, CUtensorMap* m, const void* ptr, int rank, const cuuint64_t* dims, const cuuint64_t* strides,
            const cuuint32_t* box, CUtensorMapSwizzle swz) {
  const cuuint32_t es[5] = {1, 1, 1, 1, 1};
  CUresult r = fn(m, CU_TENSOR_MAP_DATA_TYPE_BFLOAT16, rank, const_cast<void*>(ptr), dims, strides, box, es,
                  CU_TENSOR_MAP_INTERLEAVE_NONE, swz, CU_TENSOR_MAP_L2_PROMOTION_L2_128B, CU_TENSOR_MAP_FLOAT_OOB_FILL_NONE);
  if (r != CUDA_SUCCESS) fprintf(stderr, "cuTensorMapEncodeTiled failed: %d\n", (int)r);
}

struct Op { int type, flags, id, n, quarter, park, item0, items; double t0, t1; };
struct Use { double ready, gate, need, freed; int readers, slot, prev; bool next; };
struct PlanStats { double end, slack, park_slack; int slots, parks; uint32_t own[N_CL]; };

bool plan(const char* const* text, int n_pair, int phase, Params& P, PlanStats* stats = nullptr) {
  constexpr double T_Q = 7900, T_A = 24850, T_U = 26300, T_O = 640, T_RUN = 800, T_WIDE = 1900, AHEAD = 3500, PUBLISH = 1500;
  const double margin = 256.0 * ((P.dbg >> 8) & 255);
  static Op op[N_CL][MAX_OPS];
  static Use use[ID_PART];
  int n_op[N_CL], covered[N_TEAM] = {}, finals[N_TEAM] = {};
  auto hex = [](char c) { return c <= '9' ? c - '0' : c - 'a' + 10; };
  for (int i = 0; i < n_pair; i++)
    for (const char* s = text[i]; *s; s++)
      if (*s == 'J') { if (covered[hex(s[1])]) return false; covered[hex(s[1])] = 10 * (s[2] - '0') + s[3] - '0'; }
  for (int c = 0; c < 2 * n_pair; c++) {
    int n = 0, items = 0;
    double t = 0;
    auto add = [&](int type, int flags, int id, int heads, int quarter, int its, double dt) {
      if (n < MAX_OPS) op[c][n] = {type, flags, id, heads, quarter, 0, items, its, t, t + dt};
      n++; items += its; t += dt;
    };
    for (const char* s = text[c >> 1]; *s; s++) {
      const int tm = hex(s[1]) & 15, nj = covered[tm];
      if (*s == 'N') { add(OP_Q, 0, 0, 0, 0, 10, T_Q); add(OP_A, 0, 0, 0, 0, 32, T_A); }
      if (*s == 'P') add(OP_Q, F_PARK, 0, 0, 0, 10, T_Q);
      if (*s == 'U') { if (n == 0 || n > MAX_OPS || op[c][n - 1].type != OP_A) return false; add(OP_A, F_PARK, 0, 0, 0, 33, T_U); }
      if (*s == 'J') { if (nj < TAIL + 3 || nj > kSteps - 11) return false; add(OP_O, P_WIDE, tm * kH, nj, 2 * (c & 1), nj + TAIL, 2 * T_O * nj + T_WIDE); }
      if (*s == 'F') { if (s[2]) return false; add(OP_O, nj ? P_LD : 0, tm * kH + nj / 3, kSteps - nj, finals[tm]++, kSteps - nj, T_O * (kSteps - nj) + T_RUN); }
    }
    if (n && n <= MAX_OPS && (op[c][n - 1].type != OP_O || (op[c][n - 1].flags & P_WIDE))) add(OP_O, 0, 0, 0, 0, 0, 0);
    add(OP_END, 0, 0, 0, 0, 0, 0);
    if (n > MAX_OPS || op[c][0].type != OP_Q) return false;
    n_op[c] = n - 1;
  }
  for (int t = 0; t < N_TEAM; t++) if (finals[t] != 4) return false;
  for (int i = 0; i < ID_PART; i++) use[i] = {0, 0, 1e18, 0, 0, 0, 0, false};
  struct Ref { double t; Op* o; int id; };
  static Ref att[N_TILE + 1], dem[N_TILE], prk[MAX_PARK + 1], unp[MAX_PARK + 1], wr[ID_PART];
  int n_att = 0, n_prk = 0, n_unp = 0;
  auto ready = [&](const Op* o) {
    const int nt = o[1].type;
    return o->t1 + (nt == OP_Q ? 6100 : o[1].n ? 3900 : 1500) + PUBLISH;
  };
  for (int c = 0; c < 2 * n_pair; c++)
    for (Op* o = op[c]; o->type != OP_END; o++) {
      if (o->type == OP_A) { att[n_att] = {ready(o), o, 0}; if (++n_att > N_TILE) return false; }
      if (o->type == OP_A && o->flags) { unp[n_unp] = {o->t0 - AHEAD, o, 0}; if (++n_unp > MAX_PARK) return false; }
      if (o->type == OP_Q && o->flags) { prk[n_prk] = {ready(o), o, 0}; if (++n_prk > MAX_PARK) return false; }
      for (int i = 0; o->type == OP_O && i < o->n; i++) {
        const int nw = (o->flags & P_WIDE) ? o->n - TAIL : 0, k = nw ? i : kSteps - o->n + i;
        Use& u = use[o->id / kH * kH + k / 3];
        const double t = o->t0 + T_O * (i + (i < nw ? i : nw));
        if (t - AHEAD < u.need) u.need = t - AHEAD;
        const double f = i < nw || (nw && o[1].type != OP_O) ? t + T_O * (i < nw ? 2 : 1 + TAIL) + PUBLISH : 1e18;
        if (f > u.freed) u.freed = f;
        if (i == 0 || k % 3 == 0) u.readers++;
      }
    }
  if (n_att != N_TILE || n_prk != n_unp) return false;
  auto sort = [](Ref* r, int n) {
    for (int i = 1; i < n; i++)
      for (int j = i; j > 0 && r[j].t < r[j - 1].t; j--) { Ref x = r[j]; r[j] = r[j - 1]; r[j - 1] = x; }
  };
  for (int i = 0; i < N_TILE; i++) { const int id = (i & 15) * kH + (i >> 4); dem[i] = {use[id].need, nullptr, id}; }
  sort(att, n_att); sort(dem, N_TILE); sort(prk, n_prk); sort(unp, n_unp);
  PlanStats st = {0, 1e18, 1e18, 0, n_prk};
  int n_wr = 0;
  for (int i = 0; i < N_TILE; i++) {
    Op* o = att[i].o;
    o->id = dem[i].id;
    if (!o->flags) o[-1].id = o->id;
    if (dem[i].t - att[i].t < st.slack) st.slack = dem[i].t - att[i].t;
    wr[n_wr++] = {o->t1 - 2 * AHEAD, o, o->id};
  }
  for (int i = 0; i < n_prk; i++) {
    prk[i].o->id = unp[i].o->id;
    prk[i].o->park = unp[i].o->park = i;
    use[N_TILE + i].freed = unp[i].o->t0 + 2 * PUBLISH;
    use[N_TILE + i].readers = 1;
    if (unp[i].t - prk[i].t < st.park_slack) st.park_slack = unp[i].t - prk[i].t;
    wr[n_wr++] = {prk[i].o->t1 - 2 * AHEAD, prk[i].o, N_TILE + i};
  }
  for (int c = 0; c < 2 * n_pair; c++)
    for (int d = 0; d < 2 * n_pair; d++)
      for (Op *f = &op[c][n_op[c] - 1], *o = op[d]; f->n && o->type != OP_END; o++)
        if (o->type == OP_O && (o->flags & P_WIDE) && o->id / kH == f->id / kH) {
          if (f->t0 - o->t1 > 4096.0 * ((P.dbg >> 16) & 255)) f->flags |= P_PRE;
          const double slack = f->t0 + ((f->flags & P_PRE) ? 0 : (f->n - 5) * T_O) - AHEAD - ready(o);
          if (slack < st.park_slack) st.park_slack = slack;
        }
  sort(wr, n_wr);
  int holder[N_TILE];
  for (int i = 0; i < n_wr; i++) {
    int best = -1;
    for (int sl = 0; sl < st.slots; sl++)
      if (use[holder[sl]].freed + margin <= wr[i].t && (best < 0 || (use[holder[sl]].freed < use[holder[best]].freed) != ((P.dbg & 32) != 0))) best = sl;
    Use& u = use[wr[i].id];
    if (best >= 0) { u.prev = holder[best]; use[u.prev].next = true; wr[i].o->flags |= P_GATE; }
    else if (st.slots == N_TILE) return false;
    else best = st.slots++;
    u.slot = best;
    holder[best] = wr[i].id;
  }
  {
    int pos[N_CL] = {}, flag[ID_PART + 4 * N_TEAM] = {}, seen[ID_PART] = {};
    auto goal = [&](int c) { return op[c][n_op[c] - 1].item0; };
    for (bool moved = true; moved;) {
      moved = false;
      for (int c = 0; c < 2 * n_pair; c++) {
        for (; pos[c] < goal(c); pos[c]++, moved = true) {
          bool ok = true;
          for (const Op* o = op[c]; o->type != OP_END; o++) {
            const int k = pos[c] - o->item0, own = o->type == OP_A ? o->id : N_TILE + o->park;
            if (k < 0 || k >= o->items) continue;
            if (o->type == OP_O) ok = k >= o->n || flag[o->id + k / 3];
            else if (k == o->items - 1 && (o->flags & P_GATE)) ok = seen[use[own].prev] == use[use[own].prev].readers;
            else if (k == 0 && o->type == OP_A && (o->flags & F_PARK)) ok = flag[N_TILE + o->park];
          }
          if (!ok) break;
          for (const Op* o = op[c]; o->type != OP_END; o++) {
            if (pos[c] == o->item0 + o->items + (o[1].type == OP_Q ? 7 : o[1].item0 == goal(c) ? -1 : 5)) {
              if (o->type == OP_A) flag[o->id] = 1;
              if (o->type == OP_Q && (o->flags & F_PARK)) flag[N_TILE + o->park] = 1;
              if (o->type == OP_O) flag[ID_PART + o->id / kH * 4 + o->quarter] = flag[ID_PART + o->id / kH * 4 + o->quarter + 1] = 1;
            }
            const int k = pos[c] - NBAR - o->item0, nw = o->n - TAIL;
            if (k == 0 && o->type == OP_A && (o->flags & F_PARK)) seen[N_TILE + o->park]++;
            if (o->type == OP_O && k >= 0 && k < o->items && k % 3 == 2 && (k < nw || k >= o->n)) seen[o->id + (k < nw ? k : k - TAIL) / 3]++;
          }
        }
      }
    }
    for (int c = 0; c < 2 * n_pair; c++) if (pos[c] < goal(c)) return false;
  }
  int n_job = 0, longest = 0;
  for (int t = 0; t < N_TEAM; t++) if (kH - covered[t] / 3 > longest) longest = kH - covered[t] / 3;
  for (int c = 0; c < 2 * n_pair; c++) {
    uint32_t items = 0, cur = 0, pend = 0;
    int n = 0, ev = 0;
    auto item = [&](uint32_t bytes, int count) {
      for (int i = 0; i < count; i++) { if (cur + bytes > RING) cur = 0; cur += bytes; items++; }
    };
    auto event = [&](uint32_t e) { if (ev < MAX_EV) P.prog[c].ev[ev] = e; ev++; };
    for (const Op* o = op[c];; o++) {
      if (o->type != OP_END && phase && (o->type == OP_O) != (phase == 2)) continue;
      uint32_t cw = o->type | (items % NBAR) << 15 | ((items / NBAR) & 1) << 19 | (cur >> 12) << 20 | pend, pw = o->type | o->id << 2 | o->flags;
      const int ps = use[N_TILE + o->park].slot;
      pend = 0;
      if (o->type == OP_O) {
        pw |= o->n << 13 | o->quarter << 20;
        if (o->flags & P_WIDE) {
          cw |= o->n << 2 | (o->id / kH * 4 + o->quarter + 1) << 9 | C_WIDE;
          item(SZ_W, o->n - TAIL);
          item(SZ_O, 2 * TAIL);
          pend = C_PEND | ((P.dbg & 8) ? C_SOON : 0);
          for (int i = 0; 3 * i < o->n; i++) event((o->id + i) | E_ON | (use[o->id + i].next ? 0 : E_LAST));
        } else {
          dem[n_job++] = {o->t0 - 1e6 * o->n, nullptr, (int)pw};
          st.own[c] = pw;
          pw = OP_O;
          event(E_DRAW | (items < TICK ? 0 : items - TICK));
          for (int i = 0; i <= longest; i++) event(E_JOB | i);
        }
      } else if (o->type != OP_END) {
        const bool parks = o->type == OP_Q && (o->flags & F_PARK);
        cw |= (parks ? ps : use[o->id].slot) << 2 | (o->flags & F_PARK);
        if (o->flags & F_PARK) pw |= o->park << 13 | ps << 20;
        if (o->type == OP_Q) item(SZ_Q, 10);
        else { if (o->flags & F_PARK) { item(SZ_PARK, 1); event((N_TILE + o->park) | E_ON | (use[N_TILE + o->park].next ? 0 : E_LAST)); } item(SZ_KV, 32); }
        if (parks || o->type == OP_A) pend = C_PEND | ((P.dbg & 16) ? 0 : C_SOON);
        if (o->flags & P_GATE) event(use[parks ? N_TILE + o->park : o->id].prev | E_ON | E_FREE);
      }
      P.prog[c].c[n] = cw; P.prog[c].p[n++] = pw;
      if (o->type == OP_END) { if (o->t0 > st.end) st.end = o->t0; break; }
    }
    if (ev > MAX_EV) return false;
    while (ev < MAX_EV) P.prog[c].ev[ev++] = 0;
    while (n < MAX_OPS) { P.prog[c].c[n] = OP_END; P.prog[c].p[n++] = OP_END; }
    P.first[c] = (uint16_t)(P.prog[c].p[0] & 2047);
  }
  sort(dem, n_job);
  for (int i = 0; i < n_job; i++) P.job[i] = dem[i].id;
  for (int i = 0; i < ID_PART; i++) {
    if (i < N_TILE) P.slot[i] = use[i].slot;
    P.info[i] = (use[i].readers + use[i].next) | (use[i].next ? I_NEXT : 0);
  }
  if (stats) *stats = st;
  return true;
}

const char* const kPrograms[N_CL / 2] = {
  "NNNNNNNNNF6", "NNNNNNNNNF0", "NNNNJf45NNNF7", "PNNNNNNNNNF8", "PNJ663NNNNNF5", "NNNNNNNNNFe",
  "NUNNNNNNNF5", "NNNNNNNNNF6", "NNNNNNNNNFe", "NUNNNJa78NFb", "PNJ281NNNNFc", "PPNJ551NNNNUNF2",
  "NNNNNJc39NNUF2", "NNJ381NNNNF8", "NUNUNJ975NFc", "PNUNNNNNNNF1", "PNJ063NNNNNFf", "NUNNNJd45NNFd",
  "PNNNNNNNNNF9", "NNUJ460Jb60NFd", "NNNNNNNNNFb", "PNJ751NNNNNNF3", "NNNNNNNNNF4", "PNJ175NNNNN",
  "PNNNNNNNNNFa", "NUNNNJe63NNFa", "PNNNNNNNNNF9", "NNNNNNNNNF0", "PNNNNNNNNNF3", "PPNUNNNNNNUF1",
  "NNUNNNNNNF7", "NNNNNJ875NF4", "NUNUNNNNNFf",
};

const char* const* bench_programs() {
  return kPrograms;
}

}

extern "C" void kernel_launch(void* const* d_in, const int* in_sizes, int n_in, void* d_out, int out_size) {
  (void)in_sizes; (void)n_in; (void)out_size;
  static EncodeFn fn = nullptr;
  static int n_clusters = 0;
  if (!fn) {
    cudaDriverEntryPointQueryResult qr;
    void* f = nullptr;
    cudaGetDriverEntryPoint("cuTensorMapEncodeTiled", &f, cudaEnableDefault, &qr);
    fn = (EncodeFn)f;
    cudaFuncSetAttribute(fused_kernel, cudaFuncAttributeMaxDynamicSharedMemorySize, SMEM_BYTES);
    cudaLaunchConfig_t cfg = {};
    cfg.gridDim = dim3(132); cfg.blockDim = dim3(384); cfg.dynamicSmemBytes = SMEM_BYTES;
    cudaLaunchAttribute at[1];
    at[0].id = cudaLaunchAttributeClusterDimension; at[0].val.clusterDim.x = 2; at[0].val.clusterDim.y = 1; at[0].val.clusterDim.z = 1;
    cfg.attrs = at; cfg.numAttrs = 1;
    if (cudaOccupancyMaxActiveClusters(&n_clusters, fused_kernel, &cfg) != cudaSuccess || n_clusters < 1) n_clusters = 1;
    (void)cudaGetLastError();
  }
  static Params P;
  const CUtensorMapSwizzle S128 = CU_TENSOR_MAP_SWIZZLE_128B, S64 = CU_TENSOR_MAP_SWIZZLE_64B;
  for (int blk = 0; blk < 2; blk++) {
    void* const* in = d_in + 5 * blk;
    { const cuuint64_t d[] = {kD, kB * kSq}, s[] = {kD * 2}; const cuuint32_t b[] = {64, 128};
      encode(fn, &P.x[blk], in[0], 2, d, s, b, S128); }
    { const cuuint64_t d[] = {64, 8, 3, (cuuint64_t)kB * kH * kSk / 8}, s[] = {kDh * 2, 128, 8 * kDh * 2}; const cuuint32_t b[] = {64, 8, 3, 8};
      encode(fn, &P.k[blk], in[1], 4, d, s, b, S128);
      encode(fn, &P.v[blk], in[2], 4, d, s, b, S128); }
    { const cuuint64_t d[] = {64, kD, kHD / 64}, s[] = {kHD * 2, 128}; const cuuint32_t b[] = {64, 64, 3};
      encode(fn, &P.wq[blk], in[3], 3, d, s, b, S128); }
    { const cuuint64_t d[] = {32, 2, kHD / 8, 4, kD / 32}, s[] = {kD * 2, 8 * kD * 2, 2 * kD * 2, 64}; const cuuint32_t b[] = {32, 2, 4, 4, 5};
      encode(fn, &P.wo[blk], in[4], 5, d, s, b, S64); }
  }
  { const cuuint64_t d[] = {32, kB * kSq, 2 * kD / 32}, s[] = {2 * kD * 2, 64}; const cuuint32_t b[] = {32, 16, 1};
    encode(fn, &P.out, d_out, 3, d, s, b, S64); }

  cudaGetSymbolAddress((void**)&P.g, g_scratch);
  P.dbg = DBG_DEFAULT;
  if (n_clusters >= N_CL && plan(bench_programs(), N_CL / 2, 0, P)) {
    fused_kernel<<<2 * N_CL, 384, SMEM_BYTES>>>(P);
  } else {
    char buf[2 * N_TEAM][16];
    const char* text[2 * N_TEAM];
    for (int i = 0; i < 2 * N_TEAM; i++) { snprintf(buf[i], sizeof(buf[i]), "NNNNNNNNF%x", i / 2); text[i] = buf[i]; }
    for (int phase = 1; phase <= 2; phase++) {
      plan(text, 2 * N_TEAM, phase, P);
      fused_kernel<<<8 * N_TEAM, 384, SMEM_BYTES>>>(P);
    }
  }
}
```

```cpp
#include <cuda_runtime.h>
#include <cuda_bf16.h>
#include <cuda.h>
#include <stdint.h>
#include <stdio.h>

namespace {

constexpr int kB = 8, kSq = 256, kD = 640, kH = 32, kSk = 1024, kDh = 192;
constexpr int kHD = kH * kDh;
constexpr uint32_t RING = 224 * 1024;
constexpr uint32_t SZ_KV = 24576;
constexpr uint32_t SZ_Q = 16384 + 24576;
constexpr uint32_t SZ_O = 16384 + 20480;
constexpr uint32_t SZ_W = 16384 + 40960;
constexpr uint32_t SZ_PARK = 49152;
constexpr uint32_t SZ_OL = SZ_O + 8192;
constexpr int NBAR = 10;
constexpr int EARLY = 3;
constexpr int kSteps = kHD / 64;
constexpr int TAIL = 6;
constexpr uint32_t KV_CH = 64, KV_SBO = 3072;
constexpr int SMEM_BYTES = RING + 1024 + 1024;
constexpr int N_TEAM = 16, N_CL = 66, MAX_OPS = 24, MAX_EV = 80, N_TILE = N_TEAM * kH, MAX_PARK = 128, ID_PART = N_TILE + MAX_PARK;
enum : uint32_t { OP_END = 0, OP_Q = 1, OP_A = 2, OP_O = 3, F_PARK = 1 << 11,
                  C_WIDE = 1 << 27, C_PEND = 1 << 26, C_SOON = 1 << 28,
                  P_GATE = 1 << 12, P_WIDE = 1 << 11, P_LD = 1 << 12, P_PRE = 1 << 22, I_NEXT = 8, E_ON = 1 << 15, E_FREE = 1 << 14, E_LAST = 1 << 13, E_DRAW = 1 << 12, E_JOB = 1 << 11 };

#define QDRAIN 0x54732710u
#define TRYNS 1500
#define QA 1
#define QB 2
#define QC 3
#define NORM_G 2
#define CONV_G 8
#define CONV_0 32
#define SLOWF 35
#define SLOWP 0x4511
#define FASTF 23
#define FASTP 0x1a
#define WATNS2 100
#define NEAR 2
#define TICK 16
#define SKEW 3
#define PUBNS 0
#define WATNS 600
constexpr uint32_t DBG_DEFAULT = 0x040817;

struct alignas(1024) Scratch {
  unsigned int flag[2047];
  unsigned int ticket;
  uint4 part[N_TEAM * 4 * 2 * 3072];
  uint4 tile[N_TILE * 2 * 3072];
};

struct alignas(64) Params {
  const char* xw[2];
  uint16_t first[80];
  Scratch* g;
  uint32_t dbg;
  CUtensorMap x[2], wq[2], k[2], v[2], wo[2], out;
  struct {
    uint32_t c[MAX_OPS];
    uint32_t p[MAX_OPS];
    uint16_t ev[MAX_EV];
  } prog[N_CL];
  uint32_t job[N_CL];
  uint16_t slot[N_TILE];
  uint8_t info[ID_PART];
};

__device__ Scratch g_scratch;

template <int TB, int TA = 0>
__device__ __forceinline__ void wgmma_ss_n64(float (&d)[32], uint64_t da, uint64_t db, int scale_d) {
  asm volatile("{\n.reg .pred p;\nsetp.ne.b32 p, %34, 0;\n"
    "wgmma.mma_async.sync.aligned.m64n64k16.f32.bf16.bf16 {%0, %1, %2, %3, %4, %5, %6, %7, %8, %9, %10, %11, %12, %13, %14, %15, %16, %17, %18, %19, %20, %21, %22, %23, %24, %25, %26, %27, %28, %29, %30, %31}, %32, %33, p, 1, 1, %35, %36;\n}\n"
    : "+f"(d[0]), "+f"(d[1]), "+f"(d[2]), "+f"(d[3]), "+f"(d[4]), "+f"(d[5]), "+f"(d[6]), "+f"(d[7]), "+f"(d[8]), "+f"(d[9]), "+f"(d[10]), "+f"(d[11]), "+f"(d[12]), "+f"(d[13]), "+f"(d[14]), "+f"(d[15]), "+f"(d[16]), "+f"(d[17]), "+f"(d[18]), "+f"(d[19]), "+f"(d[20]), "+f"(d[21]), "+f"(d[22]), "+f"(d[23]), "+f"(d[24]), "+f"(d[25]), "+f"(d[26]), "+f"(d[27]), "+f"(d[28]), "+f"(d[29]), "+f"(d[30]), "+f"(d[31])
    : "l"(da), "l"(db), "r"(scale_d), "n"(TA), "n"(TB));
}
template <int TB>
__device__ __forceinline__ void wgmma_rs_n64(float (&d)[32], uint32_t a0, uint32_t a1, uint32_t a2, uint32_t a3, uint64_t db, int scale_d) {
  asm volatile("{\n.reg .pred p;\nsetp.ne.b32 p, %37, 0;\n"
    "wgmma.mma_async.sync.aligned.m64n64k16.f32.bf16.bf16 {%0, %1, %2, %3, %4, %5, %6, %7, %8, %9, %10, %11, %12, %13, %14, %15, %16, %17, %18, %19, %20, %21, %22, %23, %24, %25, %26, %27, %28, %29, %30, %31}, {%32, %33, %34, %35}, %36, p, 1, 1, %38;\n}\n"
    : "+f"(d[0]), "+f"(d[1]), "+f"(d[2]), "+f"(d[3]), "+f"(d[4]), "+f"(d[5]), "+f"(d[6]), "+f"(d[7]), "+f"(d[8]), "+f"(d[9]), "+f"(d[10]), "+f"(d[11]), "+f"(d[12]), "+f"(d[13]), "+f"(d[14]), "+f"(d[15]), "+f"(d[16]), "+f"(d[17]), "+f"(d[18]), "+f"(d[19]), "+f"(d[20]), "+f"(d[21]), "+f"(d[22]), "+f"(d[23]), "+f"(d[24]), "+f"(d[25]), "+f"(d[26]), "+f"(d[27]), "+f"(d[28]), "+f"(d[29]), "+f"(d[30]), "+f"(d[31])
    : "r"(a0), "r"(a1), "r"(a2), "r"(a3), "l"(db), "r"(scale_d), "n"(TB));
}
template <int TB, int TA = 0>
__device__ __forceinline__ void wgmma_ss_n160(float (&d)[80], uint64_t da, uint64_t db, int scale_d) {
  asm volatile("{\n.reg .pred p;\nsetp.ne.b32 p, %82, 0;\n"
    "wgmma.mma_async.sync.aligned.m64n160k16.f32.bf16.bf16 {%0, %1, %2, %3, %4, %5, %6, %7, %8, %9, %10, %11, %12, %13, %14, %15, %16, %17, %18, %19, %20, %21, %22, %23, %24, %25, %26, %27, %28, %29, %30, %31, %32, %33, %34, %35, %36, %37, %38, %39, %40, %41, %42, %43, %44, %45, %46, %47, %48, %49, %50, %51, %52, %53, %54, %55, %56, %57, %58, %59, %60, %61, %62, %63, %64, %65, %66, %67, %68, %69, %70, %71, %72, %73, %74, %75, %76, %77, %78, %79}, %80, %81, p, 1, 1, %83, %84;\n}\n"
    : "+f"(d[0]), "+f"(d[1]), "+f"(d[2]), "+f"(d[3]), "+f"(d[4]), "+f"(d[5]), "+f"(d[6]), "+f"(d[7]), "+f"(d[8]), "+f"(d[9]), "+f"(d[10]), "+f"(d[11]), "+f"(d[12]), "+f"(d[13]), "+f"(d[14]), "+f"(d[15]), "+f"(d[16]), "+f"(d[17]), "+f"(d[18]), "+f"(d[19]), "+f"(d[20]), "+f"(d[21]), "+f"(d[22]), "+f"(d[23]), "+f"(d[24]), "+f"(d[25]), "+f"(d[26]), "+f"(d[27]), "+f"(d[28]), "+f"(d[29]), "+f"(d[30]), "+f"(d[31]), "+f"(d[32]), "+f"(d[33]), "+f"(d[34]), "+f"(d[35]), "+f"(d[36]), "+f"(d[37]), "+f"(d[38]), "+f"(d[39]), "+f"(d[40]), "+f"(d[41]), "+f"(d[42]), "+f"(d[43]), "+f"(d[44]), "+f"(d[45]), "+f"(d[46]), "+f"(d[47]), "+f"(d[48]), "+f"(d[49]), "+f"(d[50]), "+f"(d[51]), "+f"(d[52]), "+f"(d[53]), "+f"(d[54]), "+f"(d[55]), "+f"(d[56]), "+f"(d[57]), "+f"(d[58]), "+f"(d[59]), "+f"(d[60]), "+f"(d[61]), "+f"(d[62]), "+f"(d[63]), "+f"(d[64]), "+f"(d[65]), "+f"(d[66]), "+f"(d[67]), "+f"(d[68]), "+f"(d[69]), "+f"(d[70]), "+f"(d[71]), "+f"(d[72]), "+f"(d[73]), "+f"(d[74]), "+f"(d[75]), "+f"(d[76]), "+f"(d[77]), "+f"(d[78]), "+f"(d[79])
    : "l"(da), "l"(db), "r"(scale_d), "n"(TA), "n"(TB));
}
template <int TB>
__device__ __forceinline__ void wgmma_rs_n160(float (&d)[80], uint32_t a0, uint32_t a1, uint32_t a2, uint32_t a3, uint64_t db, int scale_d) {
  asm volatile("{\n.reg .pred p;\nsetp.ne.b32 p, %85, 0;\n"
    "wgmma.mma_async.sync.aligned.m64n160k16.f32.bf16.bf16 {%0, %1, %2, %3, %4, %5, %6, %7, %8, %9, %10, %11, %12, %13, %14, %15, %16, %17, %18, %19, %20, %21, %22, %23, %24, %25, %26, %27, %28, %29, %30, %31, %32, %33, %34, %35, %36, %37, %38, %39, %40, %41, %42, %43, %44, %45, %46, %47, %48, %49, %50, %51, %52, %53, %54, %55, %56, %57, %58, %59, %60, %61, %62, %63, %64, %65, %66, %67, %68, %69, %70, %71, %72, %73, %74, %75, %76, %77, %78, %79}, {%80, %81, %82, %83}, %84, p, 1, 1, %86;\n}\n"
    : "+f"(d[0]), "+f"(d[1]), "+f"(d[2]), "+f"(d[3]), "+f"(d[4]), "+f"(d[5]), "+f"(d[6]), "+f"(d[7]), "+f"(d[8]), "+f"(d[9]), "+f"(d[10]), "+f"(d[11]), "+f"(d[12]), "+f"(d[13]), "+f"(d[14]), "+f"(d[15]), "+f"(d[16]), "+f"(d[17]), "+f"(d[18]), "+f"(d[19]), "+f"(d[20]), "+f"(d[21]), "+f"(d[22]), "+f"(d[23]), "+f"(d[24]), "+f"(d[25]), "+f"(d[26]), "+f"(d[27]), "+f"(d[28]), "+f"(d[29]), "+f"(d[30]), "+f"(d[31]), "+f"(d[32]), "+f"(d[33]), "+f"(d[34]), "+f"(d[35]), "+f"(d[36]), "+f"(d[37]), "+f"(d[38]), "+f"(d[39]), "+f"(d[40]), "+f"(d[41]), "+f"(d[42]), "+f"(d[43]), "+f"(d[44]), "+f"(d[45]), "+f"(d[46]), "+f"(d[47]), "+f"(d[48]), "+f"(d[49]), "+f"(d[50]), "+f"(d[51]), "+f"(d[52]), "+f"(d[53]), "+f"(d[54]), "+f"(d[55]), "+f"(d[56]), "+f"(d[57]), "+f"(d[58]), "+f"(d[59]), "+f"(d[60]), "+f"(d[61]), "+f"(d[62]), "+f"(d[63]), "+f"(d[64]), "+f"(d[65]), "+f"(d[66]), "+f"(d[67]), "+f"(d[68]), "+f"(d[69]), "+f"(d[70]), "+f"(d[71]), "+f"(d[72]), "+f"(d[73]), "+f"(d[74]), "+f"(d[75]), "+f"(d[76]), "+f"(d[77]), "+f"(d[78]), "+f"(d[79])
    : "r"(a0), "r"(a1), "r"(a2), "r"(a3), "l"(db), "r"(scale_d), "n"(TB));
}
template <int TB, int TA = 0>
__device__ __forceinline__ void wgmma_ss_n192(float (&d)[96], uint64_t da, uint64_t db, int scale_d) {
  asm volatile("{\n.reg .pred p;\nsetp.ne.b32 p, %98, 0;\n"
    "wgmma.mma_async.sync.aligned.m64n192k16.f32.bf16.bf16 {%0, %1, %2, %3, %4, %5, %6, %7, %8, %9, %10, %11, %12, %13, %14, %15, %16, %17, %18, %19, %20, %21, %22, %23, %24, %25, %26, %27, %28, %29, %30, %31, %32, %33, %34, %35, %36, %37, %38, %39, %40, %41, %42, %43, %44, %45, %46, %47, %48, %49, %50, %51, %52, %53, %54, %55, %56, %57, %58, %59, %60, %61, %62, %63, %64, %65, %66, %67, %68, %69, %70, %71, %72, %73, %74, %75, %76, %77, %78, %79, %80, %81, %82, %83, %84, %85, %86, %87, %88, %89, %90, %91, %92, %93, %94, %95}, %96, %97, p, 1, 1, %99, %100;\n}\n"
    : "+f"(d[0]), "+f"(d[1]), "+f"(d[2]), "+f"(d[3]), "+f"(d[4]), "+f"(d[5]), "+f"(d[6]), "+f"(d[7]), "+f"(d[8]), "+f"(d[9]), "+f"(d[10]), "+f"(d[11]), "+f"(d[12]), "+f"(d[13]), "+f"(d[14]), "+f"(d[15]), "+f"(d[16]), "+f"(d[17]), "+f"(d[18]), "+f"(d[19]), "+f"(d[20]), "+f"(d[21]), "+f"(d[22]), "+f"(d[23]), "+f"(d[24]), "+f"(d[25]), "+f"(d[26]), "+f"(d[27]), "+f"(d[28]), "+f"(d[29]), "+f"(d[30]), "+f"(d[31]), "+f"(d[32]), "+f"(d[33]), "+f"(d[34]), "+f"(d[35]), "+f"(d[36]), "+f"(d[37]), "+f"(d[38]), "+f"(d[39]), "+f"(d[40]), "+f"(d[41]), "+f"(d[42]), "+f"(d[43]), "+f"(d[44]), "+f"(d[45]), "+f"(d[46]), "+f"(d[47]), "+f"(d[48]), "+f"(d[49]), "+f"(d[50]), "+f"(d[51]), "+f"(d[52]), "+f"(d[53]), "+f"(d[54]), "+f"(d[55]), "+f"(d[56]), "+f"(d[57]), "+f"(d[58]), "+f"(d[59]), "+f"(d[60]), "+f"(d[61]), "+f"(d[62]), "+f"(d[63]), "+f"(d[64]), "+f"(d[65]), "+f"(d[66]), "+f"(d[67]), "+f"(d[68]), "+f"(d[69]), "+f"(d[70]), "+f"(d[71]), "+f"(d[72]), "+f"(d[73]), "+f"(d[74]), "+f"(d[75]), "+f"(d[76]), "+f"(d[77]), "+f"(d[78]), "+f"(d[79]), "+f"(d[80]), "+f"(d[81]), "+f"(d[82]), "+f"(d[83]), "+f"(d[84]), "+f"(d[85]), "+f"(d[86]), "+f"(d[87]), "+f"(d[88]), "+f"(d[89]), "+f"(d[90]), "+f"(d[91]), "+f"(d[92]), "+f"(d[93]), "+f"(d[94]), "+f"(d[95])
    : "l"(da), "l"(db), "r"(scale_d), "n"(TA), "n"(TB));
}
template <int TB>
__device__ __forceinline__ void wgmma_rs_n192(float (&d)[96], uint32_t a0, uint32_t a1, uint32_t a2, uint32_t a3, uint64_t db, int scale_d) {
  asm volatile("{\n.reg .pred p;\nsetp.ne.b32 p, %101, 0;\n"
    "wgmma.mma_async.sync.aligned.m64n192k16.f32.bf16.bf16 {%0, %1, %2, %3, %4, %5, %6, %7, %8, %9, %10, %11, %12, %13, %14, %15, %16, %17, %18, %19, %20, %21, %22, %23, %24, %25, %26, %27, %28, %29, %30, %31, %32, %33, %34, %35, %36, %37, %38, %39, %40, %41, %42, %43, %44, %45, %46, %47, %48, %49, %50, %51, %52, %53, %54, %55, %56, %57, %58, %59, %60, %61, %62, %63, %64, %65, %66, %67, %68, %69, %70, %71, %72, %73, %74, %75, %76, %77, %78, %79, %80, %81, %82, %83, %84, %85, %86, %87, %88, %89, %90, %91, %92, %93, %94, %95}, {%96, %97, %98, %99}, %100, p, 1, 1, %102;\n}\n"
    : "+f"(d[0]), "+f"(d[1]), "+f"(d[2]), "+f"(d[3]), "+f"(d[4]), "+f"(d[5]), "+f"(d[6]), "+f"(d[7]), "+f"(d[8]), "+f"(d[9]), "+f"(d[10]), "+f"(d[11]), "+f"(d[12]), "+f"(d[13]), "+f"(d[14]), "+f"(d[15]), "+f"(d[16]), "+f"(d[17]), "+f"(d[18]), "+f"(d[19]), "+f"(d[20]), "+f"(d[21]), "+f"(d[22]), "+f"(d[23]), "+f"(d[24]), "+f"(d[25]), "+f"(d[26]), "+f"(d[27]), "+f"(d[28]), "+f"(d[29]), "+f"(d[30]), "+f"(d[31]), "+f"(d[32]), "+f"(d[33]), "+f"(d[34]), "+f"(d[35]), "+f"(d[36]), "+f"(d[37]), "+f"(d[38]), "+f"(d[39]), "+f"(d[40]), "+f"(d[41]), "+f"(d[42]), "+f"(d[43]), "+f"(d[44]), "+f"(d[45]), "+f"(d[46]), "+f"(d[47]), "+f"(d[48]), "+f"(d[49]), "+f"(d[50]), "+f"(d[51]), "+f"(d[52]), "+f"(d[53]), "+f"(d[54]), "+f"(d[55]), "+f"(d[56]), "+f"(d[57]), "+f"(d[58]), "+f"(d[59]), "+f"(d[60]), "+f"(d[61]), "+f"(d[62]), "+f"(d[63]), "+f"(d[64]), "+f"(d[65]), "+f"(d[66]), "+f"(d[67]), "+f"(d[68]), "+f"(d[69]), "+f"(d[70]), "+f"(d[71]), "+f"(d[72]), "+f"(d[73]), "+f"(d[74]), "+f"(d[75]), "+f"(d[76]), "+f"(d[77]), "+f"(d[78]), "+f"(d[79]), "+f"(d[80]), "+f"(d[81]), "+f"(d[82]), "+f"(d[83]), "+f"(d[84]), "+f"(d[85]), "+f"(d[86]), "+f"(d[87]), "+f"(d[88]), "+f"(d[89]), "+f"(d[90]), "+f"(d[91]), "+f"(d[92]), "+f"(d[93]), "+f"(d[94]), "+f"(d[95])
    : "r"(a0), "r"(a1), "r"(a2), "r"(a3), "l"(db), "r"(scale_d), "n"(TB));
}

__device__ __forceinline__ uint32_t smem_u32(const void* p) { return (uint32_t)__cvta_generic_to_shared(p); }
__device__ __forceinline__ void wg_fence() { asm volatile("wgmma.fence.sync.aligned;" ::: "memory"); }
__device__ __forceinline__ void wg_commit() { asm volatile("wgmma.commit_group.sync.aligned;" ::: "memory"); }
template <int N> __device__ __forceinline__ void wg_wait() { asm volatile("wgmma.wait_group.sync.aligned %0;" ::"n"(N) : "memory"); }
__device__ __forceinline__ void sched_fence(uint32_t& keep, bool never) {
  asm volatile("{\n.reg .pred p;\nsetp.ne.b32 p, %1, 0;\n@p mov.u32 %0, %%clock;\n}\n" : "+r"(keep) : "r"((int)never) : "memory");
}
template <int N> __device__ __forceinline__ void fence_regs(float (&r)[N]) {
#pragma unroll
  for (int i = 0; i < N; i++) asm volatile("" : "+f"(r[i])::"memory");
}
template <int N> __device__ __forceinline__ void undefine(float (&r)[N]) {
#pragma unroll
  for (int i = 0; i < N; i++) asm volatile("" : "=f"(r[i]));
}
template <int N> __device__ __forceinline__ void fence_regs(uint32_t (&r)[N]) {
#pragma unroll
  for (int i = 0; i < N; i++) asm volatile("" : "+r"(r[i])::"memory");
}
__device__ __forceinline__ uint64_t mk_desc(uint32_t a16, uint32_t lbo, uint32_t sbo, uint32_t swz) {
  uint64_t d;
  asm("mov.b64 %0, {%1, %2};" : "=l"(d) : "r"(a16 + ((lbo >> 4) << 16)), "r"((sbo >> 4) | (swz << 30)));
  return d;
}
__device__ __forceinline__ void mbar_init(uint32_t bar, uint32_t cnt) {
  asm volatile("mbarrier.init.shared::cta.b64 [%0], %1;" ::"r"(bar), "r"(cnt) : "memory");
}
__device__ __forceinline__ void mbar_expect(uint32_t bar, uint32_t tx) {
  asm volatile("mbarrier.arrive.expect_tx.shared::cta.b64 _, [%0], %1;" ::"r"(bar), "r"(tx) : "memory");
}
__device__ __forceinline__ bool mbar_test(uint32_t bar, uint32_t ph) {
  uint32_t ok;
  asm volatile("{\n.reg .pred p;\nmbarrier.test_wait.parity.shared::cta.b64 p, [%1], %2;\nselp.u32 %0, 1, 0, p;\n}\n"
               : "=r"(ok) : "r"(bar), "r"(ph) : "memory");
  return ok;
}
__device__ __forceinline__ bool mbar_try(uint32_t bar, uint32_t ph, uint32_t ns) {
  uint32_t ok;
  asm volatile("{\n.reg .pred p;\nmbarrier.try_wait.parity.shared::cta.b64 p, [%1], %2, %3;\nselp.u32 %0, 1, 0, p;\n}\n"
               : "=r"(ok) : "r"(bar), "r"(ph), "r"(ns) : "memory");
  return ok;
}
__device__ __forceinline__ void mbar_wait(uint32_t bar, uint32_t ph) {
  asm volatile("{\n.reg .pred p;\n.reg .u32 n;\nmov.u32 n, 0;\n"
               "LOOP:\nmbarrier.try_wait.parity.shared::cta.b64 p, [%0], %1;\n@p bra DONE;\n"
               "add.u32 n, n, 1;\nsetp.lt.u32 p, n, 0x1000000;\n@p bra LOOP;\ntrap;\n"
               "DONE:\n}\n" ::"r"(bar), "r"(ph) : "memory");
}
template <int NS> __device__ __forceinline__ void mbar_wait_slow(uint32_t bar, uint32_t ph) {
  asm volatile("{\n.reg .pred p;\n.reg .u32 n;\nmov.u32 n, 0;\n"
               "LOOP:\nmbarrier.test_wait.parity.shared::cta.b64 p, [%0], %1;\n@p bra DONE;\n"
               "nanosleep.u32 %2;\nadd.u32 n, n, 1;\nsetp.lt.u32 p, n, 0x400000;\n@p bra LOOP;\ntrap;\n"
               "DONE:\n}\n" ::"r"(bar), "r"(ph), "n"(NS) : "memory");
}
__device__ __forceinline__ void mbar_arrive_cluster_if(bool on, uint32_t addr) {
  asm volatile("{\n.reg .pred p;\nsetp.ne.b32 p, %1, 0;\n@p mbarrier.arrive.shared::cluster.b64 _, [%0];\n}\n" ::"r"(addr), "r"((int)on) : "memory");
}
__device__ __forceinline__ void mbar_arrive_cluster_n(uint32_t n, uint32_t addr) {
  asm volatile("{\n.reg .pred p;\nsetp.ne.b32 p, %1, 0;\n@p mbarrier.arrive.shared::cluster.b64 _, [%0], %1;\n}\n" ::"r"(addr), "r"(n) : "memory");
}
__device__ __forceinline__ void tma2d(uint32_t dst, const CUtensorMap* m, uint32_t bar, int c0, int c1) {
  asm volatile("cp.async.bulk.tensor.2d.shared::cluster.global.mbarrier::complete_tx::bytes [%0], [%1, {%3, %4}], [%2];"
               ::"r"(dst), "l"(m), "r"(bar), "r"(c0), "r"(c1) : "memory");
}
__device__ __forceinline__ void tma3d(uint32_t dst, const CUtensorMap* m, uint32_t bar, int c0, int c1, int c2) {
  asm volatile("cp.async.bulk.tensor.3d.shared::cluster.global.mbarrier::complete_tx::bytes [%0], [%1, {%3, %4, %5}], [%2];"
               ::"r"(dst), "l"(m), "r"(bar), "r"(c0), "r"(c1), "r"(c2) : "memory");
}
__device__ __forceinline__ void tma3d_mc(uint32_t dst, const CUtensorMap* m, uint32_t bar, int c0, int c1, int c2) {
  asm volatile("cp.async.bulk.tensor.3d.shared::cluster.global.mbarrier::complete_tx::bytes.multicast::cluster"
               " [%0], [%1, {%3, %4, %5}], [%2], %6;"
               ::"r"(dst), "l"(m), "r"(bar), "r"(c0), "r"(c1), "r"(c2), "h"((uint16_t)3) : "memory");
}
__device__ __forceinline__ void tma3d_store(const CUtensorMap* m, uint32_t src, int c0, int c1, int c2) {
  asm volatile("cp.async.bulk.tensor.3d.global.shared::cta.bulk_group [%0, {%2, %3, %4}], [%1];"
               ::"l"(m), "r"(src), "r"(c0), "r"(c1), "r"(c2) : "memory");
}
__device__ __forceinline__ void bar_sync(int id, int n) { asm volatile("bar.sync %0, %1;" ::"r"(id), "r"(n) : "memory"); }
__device__ __forceinline__ uint32_t pack_bf16(float lo, float hi) {
  uint32_t r;
  asm("cvt.rn.bf16x2.f32 %0, %1, %2;" : "=r"(r) : "f"(hi), "f"(lo));
  return r;
}
__device__ __forceinline__ float ex2(float x) {
  float y;
  asm("ex2.approx.ftz.f32 %0, %1;" : "=f"(y) : "f"(x));
  return y;
}
__device__ __forceinline__ float rcp(float x) {
  float y;
  asm("rcp.approx.ftz.f32 %0, %1;" : "=f"(y) : "f"(x));
  return y;
}
__device__ __forceinline__ void stsm4(uint32_t addr, uint32_t a, uint32_t b, uint32_t c, uint32_t d) {
  asm volatile("stmatrix.sync.aligned.m8n8.x4.shared.b16 [%0], {%1, %2, %3, %4};" ::"r"(addr), "r"(a), "r"(b), "r"(c), "r"(d) : "memory");
}

__device__ __forceinline__ void tma4d_mc_hint(uint32_t dst, const CUtensorMap* m, uint32_t bar, int c3, uint64_t pol) {
  asm volatile("cp.async.bulk.tensor.4d.shared::cluster.global.mbarrier::complete_tx::bytes.multicast::cluster.L2::cache_hint"
               " [%0], [%1, {%3, %3, %3, %4}], [%2], %5, %6;"
               ::"r"(dst), "l"(m), "r"(bar), "r"(0), "r"(c3), "h"((uint16_t)3), "l"(pol) : "memory");
}
__device__ __forceinline__ void tma5d_mc(uint32_t dst, const CUtensorMap* m, uint32_t bar, int c2, int c4) {
  asm volatile("cp.async.bulk.tensor.5d.shared::cluster.global.mbarrier::complete_tx::bytes.multicast::cluster"
               " [%0], [%1, {%3, %3, %4, %3, %5}], [%2], %6;"
               ::"r"(dst), "l"(m), "r"(bar), "r"(0), "r"(c2), "r"(c4), "h"((uint16_t)3) : "memory");
}
__device__ __forceinline__ void bulk_load_hint(uint32_t dst, const void* src, uint32_t bytes, uint32_t bar, uint64_t pol) {
  asm volatile("cp.async.bulk.shared::cluster.global.mbarrier::complete_tx::bytes.L2::cache_hint [%0], [%1], %2, [%3], %4;"
               ::"r"(dst), "l"(src), "r"(bytes), "r"(bar), "l"(pol) : "memory");
}
__device__ __forceinline__ void stg128_hint(void* p, uint32_t a, uint32_t b, uint32_t c, uint32_t d, uint64_t pol) {
  asm volatile("st.global.L2::cache_hint.v4.b32 [%0], {%1, %2, %3, %4}, %5;" ::"l"(p), "r"(a), "r"(b), "r"(c), "r"(d), "l"(pol) : "memory");
}
__device__ __forceinline__ void stg2_if(bool on, void* p, uint32_t a, uint32_t b, uint32_t c, uint32_t d, uint32_t e, uint32_t f,
                                        uint32_t g, uint32_t h, uint64_t pol) {
  asm volatile("{\n.reg .pred p;\nsetp.ne.b32 p, %10, 0;\n"
               "@p st.global.L2::cache_hint.v4.b32 [%0], {%1, %2, %3, %4}, %9;\n"
               "@p st.global.L2::cache_hint.v4.b32 [%0 + 512], {%5, %6, %7, %8}, %9;\n}\n"
               ::"l"(p), "r"(a), "r"(b), "r"(c), "r"(d), "r"(e), "r"(f), "r"(g), "r"(h), "l"(pol), "r"((int)on) : "memory");
}
__device__ __forceinline__ uint64_t make_policy(bool first) {
  uint64_t pf, pn;
  asm("createpolicy.fractional.L2::evict_first.b64 %0, 1.0;" : "=l"(pf));
  asm("createpolicy.fractional.L2::evict_normal.b64 %0, 1.0;" : "=l"(pn));
  return first ? pf : pn;
}
__device__ __forceinline__ bool elect() {
  uint32_t ok;
  asm volatile("{\n.reg .pred p;\nelect.sync _|p, 0xffffffff;\nselp.u32 %0, 1, 0, p;\n}\n" : "=r"(ok));
  return ok;
}
__device__ __forceinline__ void mbar_arrive(uint32_t bar) {
  asm volatile("mbarrier.arrive.shared::cta.b64 _, [%0];" ::"r"(bar) : "memory");
}
__device__ __forceinline__ void mbar_arrive_if(bool on, uint32_t bar) {
  asm volatile("{\n.reg .pred p;\nsetp.ne.b32 p, %1, 0;\n@p mbarrier.arrive.shared::cta.b64 _, [%0];\n}\n" ::"r"(bar), "r"((int)on) : "memory");
}
__device__ __forceinline__ void stg128(void* p, uint32_t a, uint32_t b, uint32_t c, uint32_t d) {
  asm volatile("st.global.v4.b32 [%0], {%1, %2, %3, %4};" ::"l"(p), "r"(a), "r"(b), "r"(c), "r"(d) : "memory");
}
__device__ __forceinline__ void lds2_if(bool on, uint32_t p, uint32_t (&t)[8]) {
  asm volatile("{\n.reg .pred p;\nsetp.ne.b32 p, %9, 0;\n@p ld.shared.v4.b32 {%0, %1, %2, %3}, [%8];\n@p ld.shared.v4.b32 {%4, %5, %6, %7}, [%8 + 512];\n}\n"
               : "+r"(t[0]), "+r"(t[1]), "+r"(t[2]), "+r"(t[3]), "+r"(t[4]), "+r"(t[5]), "+r"(t[6]), "+r"(t[7]) : "r"(p), "r"((int)on) : "memory");
}
__device__ __forceinline__ void lds128(uint32_t p, uint32_t& a, uint32_t& b, uint32_t& c, uint32_t& d) {
  asm volatile("ld.shared.v4.b32 {%0, %1, %2, %3}, [%4];" : "=r"(a), "=r"(b), "=r"(c), "=r"(d) : "r"(p) : "memory");
}
template <class T> __device__ __forceinline__ T* ptr_add(T* base, uint32_t bytes) {
  T* r;
  asm("{\n.reg .u32 lo, hi;\nmov.b64 {lo, hi}, %1;\nadd.cc.u32 lo, lo, %2;\naddc.u32 hi, hi, 0;\nmov.b64 %0, {lo, hi};\n}\n" : "=l"(r) : "l"(base), "r"(bytes));
  return r;
}
__device__ __forceinline__ uint32_t lds32(uint32_t p) {
  uint32_t v;
  asm volatile("ld.volatile.shared.u32 %0, [%1];" : "=r"(v) : "r"(p) : "memory");
  return v;
}
__device__ __forceinline__ uint32_t flag_get(const unsigned int* p) {
  uint32_t v;
  asm volatile("ld.acquire.gpu.global.u32 %0, [%1];" : "=r"(v) : "l"(p) : "memory");
  return v;
}
__device__ __forceinline__ uint32_t wait_word(uint32_t p, uint32_t target) {
  uint32_t v;
  asm volatile("{\n.reg .pred p;\n.reg .u32 n;\nmov.u32 n, 0;\n"
               "LOOP:\nld.acquire.cta.shared.u32 %0, [%1];\nsetp.ge.u32 p, %0, %2;\n@p bra DONE;\n"
               "nanosleep.u32 %3;\nadd.u32 n, n, 1;\nsetp.lt.u32 p, n, 0x400000;\n@p bra LOOP;\ntrap;\n"
               "DONE:\n}\n" : "=r"(v) : "r"(p), "r"(target), "n"(400) : "memory");
  return v;
}
__device__ __forceinline__ void flag_set(unsigned int* p, uint32_t v) {
  asm volatile("st.release.gpu.global.u32 [%0], %1;" ::"l"(p), "r"(v) : "memory");
}
__device__ __forceinline__ void flag_dec(unsigned int* p) {
  asm volatile("red.relaxed.gpu.global.add.u32 [%0], 0xffffffff;" ::"l"(p) : "memory");
}

struct Cursor {
  int bi;
  uint32_t ph;
  __device__ __forceinline__ void next() {
    if (++bi == NBAR) { bi = 0; ph ^= 1; }
  }
};

constexpr float kScaleLog2 = 0.07216878364870322f * 1.4426950408889634f;
constexpr float kSumLimit = 1048576.0f;

__global__ void __cluster_dims__(2, 1, 1) __launch_bounds__(384, 1)
fused_kernel(const __grid_constant__ Params P) {
  extern __shared__ uint8_t smem_raw[];
  const uint32_t sbase = (smem_u32(smem_raw) + 1023) & ~1023u;
  const uint32_t full0 = sbase + RING, empty0 = full0 + 8 * NBAR, odone0 = empty0 + 8 * NBAR, ev0 = odone0 + 8 * MAX_OPS;
  const uint32_t progress = ev0 + 8 * MAX_EV, jobw = progress + 4;
  const uint32_t rank = blockIdx.x & 1;
  const int role = blockIdx.x >> 1;
  const int wid = __shfl_sync(0xffffffffu, (int)(threadIdx.x >> 5), 0);
  const int wg = wid >> 2;

  if (wid < 8) {
    if (elect()) {
#pragma unroll
      for (int j = 0; j < 16; j++) {
        const int i = EARLY + 16 * wid + j;
        if (i < 2 * NBAR + MAX_OPS + MAX_EV) mbar_init(full0 + 8 * i, i < NBAR ? 1 : i < 2 * NBAR ? 16 : i < 2 * NBAR + MAX_OPS ? 8 : 1);
      }
      if (wid == 7) asm volatile("st.shared.v2.u32 [%0], {0, 0};\nfence.acq_rel.cta;" ::"r"(progress) : "memory");
      asm volatile("fence.mbarrier_init.release.cluster;" ::: "memory");
    }
  } else if (wid > 8) {
    const uint32_t g = blockIdx.x * 96 + threadIdx.x - 288, w = g - 2048;
    if (g < 4096) asm volatile("prefetch.global.L2 [%0];" ::"l"(g < 2048 ? P.xw[0] + g * (kD * 2) : P.xw[1] + (w >> 5) * (kHD * 2) + (w & 31) * 128));
  } else {
    const uint32_t op0 = P.first[role];
    if (elect()) {
#pragma unroll
      for (int k = 0; k < EARLY; k++) mbar_init(full0 + 8 * k, 1);
      asm volatile("fence.mbarrier_init.release.cluster;" ::: "memory");
      const int blk = (op0 >> 10) & 1;
      if ((op0 & 3) == OP_Q) {
#pragma unroll
        for (int k = 0; k < EARLY; k++) {
          mbar_expect(full0 + 8 * k, SZ_Q);
          tma2d(sbase + k * SZ_Q, &P.x[blk], full0 + 8 * k, 64 * k, ((op0 >> 7) & 7) * kSq + rank * 128);
          tma3d(sbase + k * SZ_Q + 16384, &P.wq[blk], full0 + 8 * k, 0, 64 * k, 3 * ((op0 >> 2) & 31));
        }
      }
      asm volatile("prefetch.tensormap [%0];" ::"l"(rank ? &P.v[blk] : &P.k[blk]) : "memory");
    }
  }
  __syncwarp();
  asm volatile("barrier.cluster.arrive.relaxed.aligned;\nbarrier.cluster.wait.aligned;" ::: "memory");

  if (wg < 2) {
    asm volatile("setmaxnreg.inc.sync.aligned.u32 240;");
    const uint32_t* prog = P.prog[role].c;
    const int lane = threadIdx.x & 31, warp = wid & 3;
    uint32_t empty_rem;
    asm volatile("mapa.shared::cluster.u32 %0, %1, %2;" : "=r"(empty_rem) : "r"(empty0), "r"(lane & 1));
    uint32_t keep = (threadIdx.x & 127) < 2 ? 4 : 0;
    auto release = [&](int slot) { mbar_arrive_cluster_n(keep, empty_rem + 8 * slot); };
    auto release_warp = [&](int slot, bool on = true) { mbar_arrive_cluster_if(lane < 2 && on, empty_rem + 8 * slot); };
    Cursor r{0, 0};
    const uint32_t ring16 = (sbase & 0x3FFFF) >> 4;
    uint32_t cur = ring16;
    bool rdy0 = false, rdy1 = false;
    auto probe1 = [&]() { rdy0 = mbar_test(full0 + 8 * r.bi, r.ph); };
    auto probe2 = [&]() {
      Cursor n = r;
      rdy0 = mbar_test(full0 + 8 * n.bi, n.ph);
      n.next();
      rdy1 = mbar_test(full0 + 8 * n.bi, n.ph);
    };
    auto take = [&](bool rdy, uint32_t bytes, uint32_t& addr) {
      const int bi = r.bi;
      if (__builtin_expect(!__all_sync(0xffffffffu, rdy), 0)) mbar_wait(full0 + 8 * r.bi, r.ph);
      r.next();
      if (cur > ring16 + ((RING - bytes) >> 4)) cur = ring16;
      addr = cur;
      cur += bytes >> 4;
      return bi;
    };
    const bool never = P.dbg == 0xffffffffu;
    uint32_t q[48];
#pragma unroll
    for (int i = 0; i < 48; i++) q[i] = 0;
    const int row = wg * 64 + warp * 16 + (lane >> 2);
    const int img0 = row * 4 + ((lane & 3) ^ ((row >> 1) & 3));
    uint4* pend = nullptr;
    bool pend_any = false;
    uint64_t spol;
    int pc = 0;
    auto slab = [&](int c, int i0) {
#pragma unroll
      for (int i = i0; i < 6; i++)
        stg2_if(c == i, pend + i * 512, q[8 * i], q[8 * i + 1], q[8 * i + 2], q[8 * i + 3],
                q[8 * i + 4], q[8 * i + 5], q[8 * i + 6], q[8 * i + 7], spol);
    };
    auto drain = [&](int c) {
      if (!pend_any || c >= 6) return;
      slab(c, 0);
      if (c == 5) {
        __syncwarp();
        mbar_arrive_if(lane == 0, odone0 - 8 + 8 * pc);
      }
    };

    for (;; pc++) {
      uint32_t op = prog[pc];
      const int type = op & 3;
      auto enter = [&]() {
        r.bi = (op >> 15) & 15; r.ph = (op >> 19) & 1; cur = ring16 + (((op >> 20) & 63) << 8);
      };
      enter();
      pend_any = op & C_PEND;
      spol = make_policy(!(op & C_SOON));
      uint32_t job = 0;
      if ((op & (3 | C_WIDE)) == OP_O) job = __shfl_sync(0xffffffffu, wait_word(jobw, 1), 0);
      if (type == OP_END || job == OP_O) {
#pragma unroll 1
        for (int c = 0; c < 6; c++) drain(c);
        asm volatile("barrier.cluster.arrive.relaxed;" ::: "memory");
        break;
      }
      {
        float s[32], o[96];
        uint32_t ad0;
        int bi0, sk1;
        uint32_t pa[16], pb[16];
        float mc0, mc1, l0, l1;
        bool shifted;
        uint32_t nop;
        auto expo = [&](float (&s)[32], uint32_t (&pout)[16], float& b0, float& b1, bool shift, auto mid) {
          float c0, c1;
#pragma unroll
          for (int i = 0; i < 8; i++) {
            const float e0 = ex2(shift ? s[4 * i] - mc0 : s[4 * i]), e1 = ex2(shift ? s[4 * i + 1] - mc0 : s[4 * i + 1]);
            const float e2 = ex2(shift ? s[4 * i + 2] - mc1 : s[4 * i + 2]), e3 = ex2(shift ? s[4 * i + 3] - mc1 : s[4 * i + 3]);
            if (i) { b0 += e0; c0 += e1; b1 += e2; c1 += e3; } else { b0 = e0; c0 = e1; b1 = e2; c1 = e3; }
            pout[2 * i] = pack_bf16(e0, e1); pout[2 * i + 1] = pack_bf16(e2, e3);
            if (i & 1) mid(i >> 1);
          }
          b0 += c0; b1 += c1;
        };
        auto rowmax = [&](float (&s)[32], float& m0, float& m1) {
          m0 = fmaxf(s[0], s[1]); m1 = fmaxf(s[2], s[3]);
#pragma unroll
          for (int i = 1; i < 8; i++) { m0 = fmaxf(m0, fmaxf(s[4 * i], s[4 * i + 1])); m1 = fmaxf(m1, fmaxf(s[4 * i + 2], s[4 * i + 3])); }
          m0 = fmaxf(m0, __shfl_xor_sync(0xffffffffu, m0, 1)); m1 = fmaxf(m1, __shfl_xor_sync(0xffffffffu, m1, 1));
          m0 = fmaxf(m0, __shfl_xor_sync(0xffffffffu, m0, 2)); m1 = fmaxf(m1, __shfl_xor_sync(0xffffffffu, m1, 2));
        };
        auto first = [&](float (&s)[32], int sk0, auto mid) {
          fence_regs(s);
          release(sk0);
          mc0 = 0.f; mc1 = 0.f;
          expo(s, pa, l0, l1, false, mid);
          shifted = __any_sync(0xffffffffu, !(fmaxf(l0, l1) <= kSumLimit && fminf(l0, l1) >= 1.f / kSumLimit));
          if (shifted) {
            rowmax(s, mc0, mc1);
            expo(s, pa, l0, l1, true, [](int) {});
          }
        };
        auto qk = [&](float (&s)[32], uint32_t ak, int k0 = 0, int k1 = 12) {
#pragma unroll
          for (int kk = k0; kk < k1; kk++)
            wgmma_rs_n64<0>(s, q[4 * kk], q[4 * kk + 1], q[4 * kk + 2], q[4 * kk + 3], mk_desc(ak, 16, KV_SBO, 1) + ((kk >> 2) * KV_CH + (kk & 3) * 2), kk != 0);
          if (k1 == 12) wg_commit();
        };
        auto pv = [&](uint32_t (&pin)[16], uint32_t av, int acc) {
#pragma unroll
          for (int kk = 0; kk < 4; kk++)
            wgmma_rs_n192<1>(o, pin[4 * kk], pin[4 * kk + 1], pin[4 * kk + 2], pin[4 * kk + 3], mk_desc(av, KV_CH * 16, KV_SBO, 1) + (kk * (KV_SBO / 8)), acc || (kk != 0));
          wg_commit();
        };
        auto finish = [&](uint32_t (&pout)[16], int sk, int sv) {
          probe2();
          wg_wait<1>();
          fence_regs(s);
          release(sk);
          float b0, b1;
#pragma unroll 1
          for (bool redo = false;; redo = true) {
            expo(s, pout, b0, b1, false, [](int) {});
            if (!__any_sync(0xffffffffu, !redo && (shifted || !(fmaxf(b0, b1) <= kSumLimit)))) break;
            shifted = true;
            rowmax(s, b0, b1);
            b0 = fmaxf(mc0, b0); b1 = fmaxf(mc1, b1);
            const float a0 = ex2(mc0 - b0), a1 = ex2(mc1 - b1);
            mc0 = b0; mc1 = b1;
            l0 *= a0; l1 *= a1;
            wg_wait<0>();
            fence_regs(o);
#pragma unroll
            for (int i = 0; i < 24; i++) { o[4 * i] *= a0; o[4 * i + 1] *= a0; o[4 * i + 2] *= a1; o[4 * i + 3] *= a1; }
#pragma unroll
            for (int i = 0; i < 32; i++) s[i] -= (i & 2) ? mc1 : mc0;
          }
          l0 += b0; l1 += b1;
          wg_wait<0>();
          fence_regs(o);
          release(sv);
        };
        auto step = [&](uint32_t (&pin)[16], uint32_t (&pout)[16]) {
          uint32_t ak, av;
          const int sk = take(rdy0, SZ_KV, ak), sv = take(rdy1, SZ_KV, av);
          wg_fence();
          qk(s, ak);
          pv(pin, av, 1);
          finish(pout, sk, sv);
        };
        auto unpark = [&]() {
          uint32_t ad, ak;
          const int bi = take(rdy0, SZ_PARK, ad);
#pragma unroll
          for (int i = 0; i < 12; i++) lds128(sbase + (ad - ring16 + img0) * 16 + (i >> 1) * 8192 + (i & 1) * 512, q[4 * i], q[4 * i + 1], q[4 * i + 2], q[4 * i + 3]);
          const int sk0 = take(false, SZ_KV, ak);
          fence_regs(q);
          release_warp(bi);
          wg_fence();
          qk(s, ak);
          probe2();
          return sk0;
        };
        auto mma4 = [&](uint32_t ad, int acc) {
#pragma unroll
          for (int kk = 0; kk < 4; kk++)
            wgmma_ss_n192<1>(o, mk_desc(ad + wg * 512, 16, 1024, 1) + (kk * 2), mk_desc(ad, 8192, 1024, 1) + (1024 + kk * 128), acc || kk != 0);
        };
        auto convert = [&](int i0, int i1) {
          sched_fence(keep, never);
#pragma unroll
          for (int i = i0; i < i1; i++) {
            q[i] = pack_bf16(o[2 * i] * kScaleLog2, o[2 * i + 1] * kScaleLog2);
            if (i % CONV_G == CONV_G - 1 && i != i1 - 1) sched_fence(keep, never);
          }
          sched_fence(keep, never);
        };
        auto kend = [&](int bi, int k) {
          wg_commit();
          drain(k < 8 ? (QDRAIN >> (4 * k)) & 7 : 7);
          probe1();
          wg_wait<0>();
          release(bi);
        };
        if (type == OP_O) {
          float c[80];
          int prev = 0;
          auto hand_over = [&](float (&c)[80], uint4* dst) {
            fence_regs(c);
#pragma unroll
            for (int i = 0; i < 48; i++) q[i] = i < 8 ? 0 : pack_bf16(c[2 * i - 16], c[2 * i - 15]);
            pend = dst;
          };
          auto mma2 = [&](float (&c)[80], uint32_t ad, uint32_t oa, uint32_t ob, int acc) {
            wgmma_ss_n160<1>(c, mk_desc(ad + wg * 256, 16, 512, 2) + (oa), mk_desc(ad, 2048, 512, 2) + (1024 + ob), acc);
            wgmma_ss_n160<1>(c, mk_desc(ad + wg * 256, 16, 512, 2) + (oa + 2), mk_desc(ad, 2048, 512, 2) + (1024 + ob + 64), 1);
          };
          auto kstep = [&](float (&c)[80], int acc, auto hook, uint32_t bytes = SZ_O) {
            uint32_t ad;
            const int bi = take(rdy0, bytes, ad);
            wg_fence();
            mma2(c, ad, 0, 0, acc);
            wg_commit();
            if (acc) wg_wait<1>();
            if (acc == 1) release(prev);
            if (acc > 1) release_warp(prev, acc == 2 || wg == 0);
            mma2(c, ad, 512, 640, 1);
            wg_commit();
            prev = bi;
            hook();
            probe1();
            wg_wait<1>();
          };
          if (op & C_WIDE) {
            float d[80];
            const int nk = (op >> 2) & 127;
            uint4* part = ptr_add(P.g->part, (((op >> 9) & 63) * 2 + rank) * SZ_PARK + img0 * 16);
            auto wstep = [&](int acc, auto hook) {
              uint32_t ad;
              const int bi = take(rdy0, SZ_W, ad);
              wg_fence();
              mma2(d, ad, 0, 0, acc);
              mma2(d, ad, 512, 640, 1);
              wg_commit();
              if (acc) { wg_wait<1>(); release(prev); }
              mma2(c, ad, 0, 1280, acc);
              mma2(c, ad, 512, 1920, 1);
              wg_commit();
              prev = bi;
              hook();
              probe1();
              wg_wait<1>();
            };
            wstep(0, [&]() { drain(0); drain(1); });
#pragma unroll 1
            for (int k = 2; k < 6; k += 2) wstep(1, [&]() { drain(k); drain(k + 1); });
#pragma unroll 1
            for (int k = 3 + TAIL; k < nk; k++) {
              wstep(1, []() {});
            }
#pragma unroll 1
            for (int k = 0; k < TAIL; k++) kstep(d, 1, []() {});
            nop = prog[pc + 1];
            spol = make_policy(!(nop & C_SOON));
            kstep(c, 1, [&]() { hand_over(d, part - 6144); });
#pragma unroll 1
            for (int k = 1; k < TAIL; k++) kstep(c, 1, [&]() { slab(k, 1); });
            if ((nop & 3) == OP_Q) {
              op = nop;
              enter();
              pc++;
              pend_any = true;
              bi0 = take(rdy0, SZ_Q, ad0);
              undefine(o);
              wg_fence();
              mma4(ad0, 0);
              wg_commit();
              wg_wait<1>();
              release(prev);
              hand_over(c, part);
              probe1();
              wg_wait<0>();
              release(bi0);
              fence_regs(o);
              goto next_head;
            }
            wg_wait<0>();
            release(prev);
            hand_over(c, part);
            continue;
          }
          auto unblock = [&](int k) {
            if (__all_sync(0xffffffffu, rdy0) || __all_sync(0xffffffffu, mbar_try(full0 + 8 * r.bi, r.ph, TRYNS))) return;
#pragma unroll 1
            for (; k < 6; k++) drain(k);
            pend_any = false;
          };
          unblock(0);
          kstep(c, 0, [&]() { drain(0); });
          int left = ((job >> 13) & 127) - 6;
#pragma unroll 1
          for (uint32_t k = 1, pace = left >= SLOWF - 6 ? SLOWP : left <= FASTF - 6 ? FASTP : 0x155; k < 6; pace >>= 2, left--) {
            unblock(k);
            kstep(c, 1, [&]() {
#pragma unroll 1
              for (int i = pace & 3; i > 0; i--) drain(k++);
            });
          }
#pragma unroll 1
          for (; left > 0; left--) kstep(c, 1, []() {});
          uint32_t t[8], stage[3];
          float u[80];
          auto unpack = [&](int j) {
#pragma unroll
            for (int i = 0; i < 8; i++) {
              u[16 * j + 2 * i] = __uint_as_float(t[i] << 16); u[16 * j + 2 * i + 1] = __uint_as_float(t[i] & 0xffff0000u);
              asm volatile("" : "+f"(u[16 * j + 2 * i]), "+f"(u[16 * j + 2 * i + 1]));
            }
          };
#pragma unroll
          for (int i = 0; i < 8; i++) t[i] = 0;
          const uint32_t bytes = (job & P_LD) ? SZ_OL : SZ_O;
#pragma unroll
          for (int j = 0; j < 5; j++) {
            if (j == 5 - SKEW && wg == 1) {
              wg_wait<0>();
              release_warp(prev);
              bar_sync(1, 256);
            }
            kstep(c, j == 5 - SKEW ? 3 : 2, [&]() {
              if (SKEW && j == 4) asm volatile("{\n.reg .pred p;\nsetp.eq.u32 p, %0, 0;\n@p bar.arrive 1, 256;\n}\n" ::"r"(wg) : "memory");
              if (j) unpack(j - 1);
              lds2_if(job & P_LD, sbase + (cur - ring16 + img0) * 16 - 8192, t);
              if (j >= 1 && j <= 3) stage[j - 1] = sbase + (cur - ring16) * 16 - bytes + wid * 1024;
            }, bytes);
          }
          unpack(4);
          sched_fence(keep, never);
          wg_wait<0>();
          fence_regs(c);
          release_warp(prev);
          asm volatile("barrier.cluster.arrive.relaxed;" ::: "memory");
#pragma unroll
          for (int i = 0; i < 10; i++) {
            const int v = (i & 1) * 2 + (lane >> 4);
            const uint32_t sa = stage[i >> 2] + (i & 2) * 4096;
            stsm4(sa + (lane & 15) * 64 + ((v ^ ((lane >> 1) & 3)) << 4), pack_bf16(c[8 * i] + u[8 * i], c[8 * i + 1] + u[8 * i + 1]),
                  pack_bf16(c[8 * i + 2] + u[8 * i + 2], c[8 * i + 3] + u[8 * i + 3]), pack_bf16(c[8 * i + 4] + u[8 * i + 4], c[8 * i + 5] + u[8 * i + 5]),
                  pack_bf16(c[8 * i + 6] + u[8 * i + 6], c[8 * i + 7] + u[8 * i + 7]));
          }
          asm volatile("fence.proxy.async.shared::cta;" ::: "memory");
          __syncwarp();
          if (elect()) {
#pragma unroll
            for (int i = 0; i < 5; i++)
              tma3d_store(&P.out, stage[i >> 1] + (i & 1) * 8192, 0, ((job >> 7) & 7) * kSq + rank * 128 + wid * 16, ((job >> 10) & 1) * 20 + ((job >> 20) & 3) * 5 + i);
            asm volatile("cp.async.bulk.commit_group;\ncp.async.bulk.wait_group.read 0;" ::: "memory");
          }
          __syncwarp();
          break;
        }
        bi0 = take(rdy0, SZ_Q, ad0);
        undefine(o);
        wg_fence();
        mma4(ad0, 0);
        kend(bi0, 0);
        fence_regs(o);
      next_head:
        {
#pragma unroll 1
          for (int k = 1; k < ((op & F_PARK) ? 10 : 8); k++) {
            uint32_t ad;
            const int bi = take(rdy0, SZ_Q, ad);
            wg_fence();
            mma4(ad, 1);
            kend(bi, k);
          }
          if (op & F_PARK) {
            fence_regs(o);
            convert(0, 48);
            pend = ptr_add(P.g->tile, (((op >> 2) & 511) * 2 + rank) * SZ_PARK + img0 * 16);
            continue;
          }
          uint32_t a8, a9, ak0, ak1;
          const int b8 = take(rdy0, SZ_Q, a8), b9 = take(false, SZ_Q, a9);
          wg_fence();
          mma4(a8, 1);
          wg_commit();
          mma4(a9, 1);
          wg_commit();
          pc++;
          wg_wait<1>();
          release(b8);
          const int sk0 = take(false, SZ_KV, ak0);
          wg_wait<0>();
          fence_regs(o);
          release(b9);
          float s0[32];
          convert(0, CONV_0);
          wg_fence();
          qk(s0, ak0, 0, 4);
          convert(CONV_0, 48);
          wg_fence();
          qk(s0, ak0, 4, 12);
          sk1 = take(false, SZ_KV, ak1);
          probe1();
          wg_wait<0>();
          first(s0, sk0, [&](int i) {
            if (i != QA && i != QB && i != QC) return;
            sched_fence(keep, never);
            wg_fence();
            if (i == QA) qk(s, ak1, 0, 4);
            if (i == QB) qk(s, ak1, 4, 8);
            if (i == QC) qk(s, ak1, 8, 12);
            sched_fence(keep, never);
          });
        }
        for (;;) {
          {
            uint32_t av;
            const int sv = take(rdy0, SZ_KV, av);
            undefine(o);
            wg_fence();
            pv(pa, av, 0);
            finish(pb, sk1, sv);
          }
          nop = prog[pc + 1];
#pragma unroll 1
          for (int jj = 0; jj < 7; jj++) {
            step(pb, pa);
            step(pa, pb);
          }
          float i0, i1;
          auto last = [&]() {
            uint32_t av;
            const int sv = take(rdy0, SZ_KV, av);
            wg_fence();
            pv(pb, av, 1);
            sched_fence(keep, never);
            probe1();
            l0 += __shfl_xor_sync(0xffffffffu, l0, 1); l1 += __shfl_xor_sync(0xffffffffu, l1, 1);
            l0 += __shfl_xor_sync(0xffffffffu, l0, 2); l1 += __shfl_xor_sync(0xffffffffu, l1, 2);
            i0 = rcp(l0); i1 = rcp(l1);
            pend = ptr_add(P.g->tile, (((op >> 2) & 511) * 2 + rank) * SZ_PARK + img0 * 16);
            return sv;
          };
          auto normalise = [&](uint32_t (&d)[48], auto mid) {
#pragma unroll
            for (int i = 0; i < 24; i++) {
              d[8 * (i >> 2) + (i & 3)] = pack_bf16(o[4 * i] * i0, o[4 * i + 1] * i0);
              d[8 * (i >> 2) + (i & 3) + 4] = pack_bf16(o[4 * i + 2] * i1, o[4 * i + 3] * i1);
              if (i % NORM_G == NORM_G - 1 && i != 23) sched_fence(keep, never);
              if ((i & 3) == 3 && i != 23) mid(i >> 2);
            }
          };
          const int sv = last();
          if ((nop & 3) != OP_A) {
            op = nop;
            enter();
            pend_any = true;
            spol = make_policy(!(op & C_SOON));
            bi0 = take(rdy0 || (nop & 3) != OP_Q, SZ_Q, ad0);
            sched_fence(keep, never);
            wg_wait<0>();
            fence_regs(o);
            release(sv);
            normalise(q, [](int) {});
            undefine(o);
            if ((nop & 3) != OP_Q) break;
            sched_fence(keep, never);
            wg_fence();
            mma4(ad0, 0);
            pc++;
            kend(bi0, 0);
            fence_regs(o);
            goto next_head;
          }
          const int sk0 = unpark();
          wg_wait<1>();
          fence_regs(o);
          release(sv);
          uint32_t t[48];
          spol = make_policy(!(nop & C_SOON));
          auto st = [&](int i) {
            stg2_if(true, pend + i * 512, t[8 * i], t[8 * i + 1], t[8 * i + 2], t[8 * i + 3], t[8 * i + 4], t[8 * i + 5], t[8 * i + 6], t[8 * i + 7], spol);
          };
          normalise(t, [&](int i) { if (!(i & 1)) st(i >> 1); });
          wg_wait<0>();
          first(s, sk0, [&](int i) { if (i < 3) { sched_fence(keep, never); st(3 + i); } });
          __syncwarp();
          mbar_arrive_if(lane == 0, odone0 + 8 * pc);
          pc++;
          op = nop;
          uint32_t ak1;
          sk1 = take(rdy0, SZ_KV, ak1);
          rdy0 = rdy1;
          wg_fence();
          qk(s, ak1);
        }
      }
    }
    asm volatile("barrier.cluster.wait;" ::: "memory");
  } else {
    asm volatile("setmaxnreg.dec.sync.aligned.u32 24;");
    const uint32_t* prog = P.prog[role].p;
    unsigned int* flag = P.g->flag + rank;
    if (wid == 8) {
      Cursor tail{0, 0};
      int head = 0, sh = 0;
      uint32_t cur = 0, used = 0;
      uint64_t fifo = 0;
      uint32_t dst, bar, ev = ev0, done = 0;
      uint64_t pol;
      asm volatile("createpolicy.fractional.L2::evict_first.b64 %0, 1.0;" : "=l"(pol));
      auto retire = [&]() {
        mbar_wait(empty0 + 8 * tail.bi, tail.ph);
        tail.next();
        used -= (uint32_t)fifo & 31;
        fifo >>= 5;
        sh -= 5;
        asm volatile("st.volatile.shared.u32 [%0], %1;" ::"r"(progress), "r"(++done) : "memory");
      };
      auto acquire = [&](uint32_t bytes) {
        uint32_t fp = bytes >> 12;
        if (cur + fp > (RING >> 12)) { fp += (RING >> 12) - cur; cur = 0; }
        used += fp;
        while (used > (RING >> 12) || sh == 5 * NBAR) retire();
        fifo |= (uint64_t)fp << sh;
        sh += 5;
        dst = sbase + (cur << 12);
        bar = full0 + 8 * head;
        cur += bytes >> 12;
        if (++head == NBAR) head = 0;
      };
      auto gate = [&]() {
        mbar_wait(ev, 0);
        ev += 8;
        asm volatile("fence.proxy.async.global;" ::: "memory");
      };
      for (int pc = 0;; pc++) {
        uint32_t op = prog[pc];
        const int type = op & 3;
        if (type == OP_END) break;
        if (op == OP_O) {
          gate();
          op = __shfl_sync(0xffffffffu, lds32(jobw), 0);
        }
        const int blk = (op >> 10) & 1;
        if (type == OP_Q) {
#pragma unroll 1
          for (int k = 0; k < 10; k++) {
            if (k == 9 && (op & P_GATE)) gate();
            acquire(SZ_Q);
            if ((pc > 0 || k >= EARLY) && elect()) {
              mbar_expect(bar, SZ_Q);
              tma2d(dst, &P.x[blk], bar, 64 * k, ((op >> 7) & 7) * kSq + rank * 128);
              if ((k & 1) == rank) tma3d_mc(dst + 16384, &P.wq[blk], bar, 0, 64 * k, 3 * ((op >> 2) & 31));
            }
          }
        } else if (type == OP_A) {
          const int row0 = ((op >> 2) & 255) * kSk;
          const CUtensorMap* kv_map = rank ? &P.v[blk] : &P.k[blk];
          if (op & F_PARK) {
            gate();
            acquire(SZ_PARK);
            if (elect()) {
              mbar_expect(bar, SZ_PARK);
              bulk_load_hint(dst, &P.g->tile[((op >> 20) * 2 + rank) * 3072], SZ_PARK, bar, make_policy(P.dbg & 4));
            }
          }
#pragma unroll 1
          for (int t = 0; t < 32; t++) {
            const int isv = t == 31 ? 1 : (t == 0 ? 0 : (~t & 1));
            const int j = isv ? (t - 1) >> 1 : (t + 1) >> 1;
            if (t == 31 && (op & P_GATE)) gate();
            acquire(SZ_KV);
            if (elect()) {
              mbar_expect(bar, SZ_KV);
              if (isv == (int)rank) tma4d_mc_hint(dst, kv_map, bar, row0 / 8 + 8 * j, pol);
            }
          }
        } else {
          const int n = (op >> 13) & 127, nw = (op & P_WIDE) ? n - TAIL : 0;
          const uint64_t pol_o = make_policy(P.dbg & (nw ? 1 : 2));
          const uint4* part = &P.g->part[((((op >> 5) & 60) + ((op >> 20) & 3)) * 2 + rank) * 3072 + 512];
#pragma unroll 1
          for (int i = 0; i < n + (nw ? TAIL : 0); i++) {
            const int k = nw ? (i < n ? i : i - TAIL) : kSteps - n + i, h = (k * 43) >> 7, col = 5 * (((op >> 20) & 3) + (i >= n));
            const uint4* src = &P.g->tile[(P.slot[((op >> 2) & 480) + h] * 2 + rank) * 3072 + (k - 3 * h) * 1024];
            const uint32_t j = (op & P_LD) ? i - n + 5 : 5, bytes = i < nw ? SZ_W : j < 5 ? SZ_OL : SZ_O;
            if ((op & P_PRE) ? i == 0 : j == 0) gate();
            if (i < n && (i == 0 || k == 3 * h)) gate();
            acquire(bytes);
            if (elect()) {
              mbar_expect(bar, bytes);
              tma5d_mc(dst + 16384 + rank * 10240, &P.wo[blk], bar, 8 * k + 4 * rank, col);
              bulk_load_hint(dst, src, 16384, bar, pol_o);
              if (i < nw) tma5d_mc(dst + SZ_O + rank * 10240, &P.wo[blk], bar, 8 * k + 4 * rank, col + 5);
              if (j < 5) bulk_load_hint(dst + SZ_O, part + j * 512, 8192, bar, pol);
              if ((op & P_PRE) && i < 10) asm volatile("cp.async.bulk.prefetch.L2.global [%0], 4096;" ::"l"(part + i * 256) : "memory");
            }
          }
        }
      }
#pragma unroll 1
      while (sh) retire();
    } else if (threadIdx.x == 288) {
      for (int pc = 0;; pc++) {
        const uint32_t op = prog[pc];
        const int type = op & 3;
        if (type == OP_END) break;
        if (type == OP_Q ? !(op & F_PARK) : type == OP_O && !(op & P_WIDE)) continue;
        const int id = type == OP_A ? (op >> 2) & 511 : type == OP_Q ? N_TILE + ((op >> 13) & 127) : ID_PART + ((op >> 5) & 60) + ((op >> 20) & 3);
        const uint32_t v = type == OP_O ? 1 : P.info[id] & 7;
        asm volatile("{\n.reg .pred p;\n.reg .u32 n;\nmov.u32 n, 0;\n"
                     "LOOP:\nmbarrier.try_wait.parity.shared::cta.b64 p, [%0], 0, 20000;\n@p bra DONE;\n"
                     "add.u32 n, n, 1;\nsetp.lt.u32 p, n, 0x1000000;\n@p bra LOOP;\ntrap;\n"
                     "DONE:\n}\n" ::"r"(odone0 + 8 * pc) : "memory");
        flag_set(flag + 2 * id, v);
        if (type == OP_O && (op & P_WIDE)) flag_set(flag + 2 * id + 2, v);
      }
    } else if (wid == 10) {
      int i = threadIdx.x & 31;
      uint32_t e = i < 8 ? P.prog[role].ev[i] : 0;
      for (uint32_t n = 0; __any_sync(0xffffffffu, e); n++) {
        uint32_t job = lds32(jobw);
        const int togo = (e & E_DRAW) ? (e & 1023) - lds32(progress) : 99;
        if (togo <= 0 && rank == 0) {
          job = P.job[atomicInc(&P.g->ticket, gridDim.x / 2 - 1)];
          asm volatile("{\n.reg .u32 a;\nmapa.shared::cluster.u32 a, %0, 1;\nst.volatile.shared::cluster.u32 [a], %1;\n"
                       "st.volatile.shared.u32 [%0], %1;\n}\n" ::"r"(jobw), "r"(job) : "memory");
        }
        if ((e & E_JOB) && job) {
          const uint32_t j = e & 63, heads = job == OP_O ? 0 : kH - ((job >> 2) & 31), jp = !(job & P_LD) ? 63 : (job & P_PRE) ? 0 : heads - 1, h = j - (j > jp);
          e = j == jp ? (ID_PART + ((job >> 5) & 60) + ((job >> 20) & 3)) | E_ON | E_LAST : h < heads ? (((job >> 2) & 511) + h) | E_ON | E_LAST : 0;
        }
        unsigned int* f = ptr_add(flag, 8 * (e & 1023));
        const bool ok = (e & E_ON) ? flag_get(f) - 1 < ((e & E_FREE) ? 1 : 7) : (e & E_DRAW) && job;
        if (ok) {
          mbar_arrive(ev0 + 8 * i);
          if (e & (E_FREE | E_LAST)) flag_dec(f);
          i += 8;
          e = i < MAX_EV ? P.prog[role].ev[i] : 0;
        }
        asm volatile("{\n.reg .pred p;\nsetp.ge.u32 p, %0, 0x400000;\n@p trap;\n}\n" ::"r"(n));
        if (!__any_sync(0xffffffffu, ok)) __nanosleep(__any_sync(0xffffffffu, job || togo <= NEAR) ? WATNS2 : WATNS);
      }
    } else if (threadIdx.x == 352) {
      uint32_t items = 0;
      auto read = [&](int id) {
        if (!(P.info[id] & I_NEXT)) return;
        wait_word(progress, items);
        flag_dec(flag + 2 * id);
      };
      for (int pc = 0;; pc++) {
        const uint32_t op = prog[pc];
        const int type = op & 3;
        if (type == OP_END) break;
        if (type == OP_O) {
          const uint32_t n = (op >> 13) & 127, base = items;
#pragma unroll 1
          for (uint32_t k = 3, id = (op >> 2) & 511; k <= n; k += 3, id++) {
            items = base + k + (k + TAIL > n ? TAIL : 0);
            read(id);
          }
          items = base + n + TAIL;
        } else if (type == OP_A) {
          if (op & F_PARK) { items++; read(N_TILE + ((op >> 13) & 127)); }
          items += 32;
        } else {
          items += 10;
        }
      }
    }
    __syncwarp();
    asm volatile("barrier.cluster.arrive.relaxed;\nbarrier.cluster.wait;" ::: "memory");
  }
}

typedef CUresult (*EncodeFn)(CUtensorMap*, CUtensorMapDataType, cuuint32_t, void*, const cuuint64_t*, const cuuint64_t*,
                             const cuuint32_t*, const cuuint32_t*, CUtensorMapInterleave, CUtensorMapSwizzle,
                             CUtensorMapL2promotion, CUtensorMapFloatOOBfill);

void encode(EncodeFn fn, CUtensorMap* m, const void* ptr, int rank, const cuuint64_t* dims, const cuuint64_t* strides,
            const cuuint32_t* box, CUtensorMapSwizzle swz) {
  const cuuint32_t es[5] = {1, 1, 1, 1, 1};
  CUresult r = fn(m, CU_TENSOR_MAP_DATA_TYPE_BFLOAT16, rank, const_cast<void*>(ptr), dims, strides, box, es,
                  CU_TENSOR_MAP_INTERLEAVE_NONE, swz, CU_TENSOR_MAP_L2_PROMOTION_L2_128B, CU_TENSOR_MAP_FLOAT_OOB_FILL_NONE);
  if (r != CUDA_SUCCESS) fprintf(stderr, "cuTensorMapEncodeTiled failed: %d\n", (int)r);
}

struct Op { int type, flags, id, n, quarter, park, item0, items; double t0, t1; };
struct Use { double ready, gate, need, freed; int readers, slot, prev; bool next; };
struct PlanStats { double end, slack, park_slack; int slots, parks; uint32_t own[N_CL]; };

bool plan(const char* const* text, int n_pair, int phase, Params& P, PlanStats* stats = nullptr) {
  constexpr double T_Q = 7900, T_A = 24850, T_U = 26300, T_O = 640, T_RUN = 800, T_WIDE = 1900, AHEAD = 3500, PUBLISH = 1500;
  const double margin = 256.0 * ((P.dbg >> 8) & 255);
  static Op op[N_CL][MAX_OPS];
  static Use use[ID_PART];
  int n_op[N_CL], covered[N_TEAM] = {}, finals[N_TEAM] = {};
  auto hex = [](char c) { return c <= '9' ? c - '0' : c - 'a' + 10; };
  for (int i = 0; i < n_pair; i++)
    for (const char* s = text[i]; *s; s++)
      if (*s == 'J') { if (covered[hex(s[1])]) return false; covered[hex(s[1])] = 10 * (s[2] - '0') + s[3] - '0'; }
  for (int c = 0; c < 2 * n_pair; c++) {
    int n = 0, items = 0;
    double t = 0;
    auto add = [&](int type, int flags, int id, int heads, int quarter, int its, double dt) {
      if (n < MAX_OPS) op[c][n] = {type, flags, id, heads, quarter, 0, items, its, t, t + dt};
      n++; items += its; t += dt;
    };
    for (const char* s = text[c >> 1]; *s; s++) {
      const int tm = hex(s[1]) & 15, nj = covered[tm];
      if (*s == 'N') { add(OP_Q, 0, 0, 0, 0, 10, T_Q); add(OP_A, 0, 0, 0, 0, 32, T_A); }
      if (*s == 'P') add(OP_Q, F_PARK, 0, 0, 0, 10, T_Q);
      if (*s == 'U') { if (n == 0 || n > MAX_OPS || op[c][n - 1].type != OP_A) return false; add(OP_A, F_PARK, 0, 0, 0, 33, T_U); }
      if (*s == 'J') { if (nj < TAIL + 3 || nj > kSteps - 11) return false; add(OP_O, P_WIDE, tm * kH, nj, 2 * (c & 1), nj + TAIL, 2 * T_O * nj + T_WIDE); }
      if (*s == 'F') { if (s[2]) return false; add(OP_O, nj ? P_LD : 0, tm * kH + nj / 3, kSteps - nj, finals[tm]++, kSteps - nj, T_O * (kSteps - nj) + T_RUN); }
    }
    if (n && n <= MAX_OPS && (op[c][n - 1].type != OP_O || (op[c][n - 1].flags & P_WIDE))) add(OP_O, 0, 0, 0, 0, 0, 0);
    add(OP_END, 0, 0, 0, 0, 0, 0);
    if (n > MAX_OPS || op[c][0].type != OP_Q) return false;
    n_op[c] = n - 1;
  }
  for (int t = 0; t < N_TEAM; t++) if (finals[t] != 4) return false;
  for (int i = 0; i < ID_PART; i++) use[i] = {0, 0, 1e18, 0, 0, 0, 0, false};
  struct Ref { double t; Op* o; int id; };
  static Ref att[N_TILE + 1], dem[N_TILE], prk[MAX_PARK + 1], unp[MAX_PARK + 1], wr[ID_PART];
  int n_att = 0, n_prk = 0, n_unp = 0;
  auto ready = [&](const Op* o) {
    const int nt = o[1].type;
    return o->t1 + (nt == OP_Q ? 6100 : o[1].n ? 3900 : 1500) + PUBLISH;
  };
  for (int c = 0; c < 2 * n_pair; c++)
    for (Op* o = op[c]; o->type != OP_END; o++) {
      if (o->type == OP_A) { att[n_att] = {ready(o), o, 0}; if (++n_att > N_TILE) return false; }
      if (o->type == OP_A && o->flags) { unp[n_unp] = {o->t0 - AHEAD, o, 0}; if (++n_unp > MAX_PARK) return false; }
      if (o->type == OP_Q && o->flags) { prk[n_prk] = {ready(o), o, 0}; if (++n_prk > MAX_PARK) return false; }
      for (int i = 0; o->type == OP_O && i < o->n; i++) {
        const int nw = (o->flags & P_WIDE) ? o->n - TAIL : 0, k = nw ? i : kSteps - o->n + i;
        Use& u = use[o->id / kH * kH + k / 3];
        const double t = o->t0 + T_O * (i + (i < nw ? i : nw));
        if (t - AHEAD < u.need) u.need = t - AHEAD;
        const double f = i < nw || (nw && o[1].type != OP_O) ? t + T_O * (i < nw ? 2 : 1 + TAIL) + PUBLISH : 1e18;
        if (f > u.freed) u.freed = f;
        if (i == 0 || k % 3 == 0) u.readers++;
      }
    }
  if (n_att != N_TILE || n_prk != n_unp) return false;
  auto sort = [](Ref* r, int n) {
    for (int i = 1; i < n; i++)
      for (int j = i; j > 0 && r[j].t < r[j - 1].t; j--) { Ref x = r[j]; r[j] = r[j - 1]; r[j - 1] = x; }
  };
  for (int i = 0; i < N_TILE; i++) { const int id = (i & 15) * kH + (i >> 4); dem[i] = {use[id].need, nullptr, id}; }
  sort(att, n_att); sort(dem, N_TILE); sort(prk, n_prk); sort(unp, n_unp);
  PlanStats st = {0, 1e18, 1e18, 0, n_prk};
  int n_wr = 0;
  for (int i = 0; i < N_TILE; i++) {
    Op* o = att[i].o;
    o->id = dem[i].id;
    if (!o->flags) o[-1].id = o->id;
    if (dem[i].t - att[i].t < st.slack) st.slack = dem[i].t - att[i].t;
    wr[n_wr++] = {o->t1 - 2 * AHEAD, o, o->id};
  }
  for (int i = 0; i < n_prk; i++) {
    prk[i].o->id = unp[i].o->id;
    prk[i].o->park = unp[i].o->park = i;
    use[N_TILE + i].freed = unp[i].o->t0 + 2 * PUBLISH;
    use[N_TILE + i].readers = 1;
    if (unp[i].t - prk[i].t < st.park_slack) st.park_slack = unp[i].t - prk[i].t;
    wr[n_wr++] = {prk[i].o->t1 - 2 * AHEAD, prk[i].o, N_TILE + i};
  }
  for (int c = 0; c < 2 * n_pair; c++)
    for (int d = 0; d < 2 * n_pair; d++)
      for (Op *f = &op[c][n_op[c] - 1], *o = op[d]; f->n && o->type != OP_END; o++)
        if (o->type == OP_O && (o->flags & P_WIDE) && o->id / kH == f->id / kH) {
          if (f->t0 - o->t1 > 4096.0 * ((P.dbg >> 16) & 255)) f->flags |= P_PRE;
          const double slack = f->t0 + ((f->flags & P_PRE) ? 0 : (f->n - 5) * T_O) - AHEAD - ready(o);
          if (slack < st.park_slack) st.park_slack = slack;
        }
  sort(wr, n_wr);
  int holder[N_TILE];
  for (int i = 0; i < n_wr; i++) {
    int best = -1;
    for (int sl = 0; sl < st.slots; sl++)
      if (use[holder[sl]].freed + margin <= wr[i].t && (best < 0 || (use[holder[sl]].freed < use[holder[best]].freed) != ((P.dbg & 32) != 0))) best = sl;
    Use& u = use[wr[i].id];
    if (best >= 0) { u.prev = holder[best]; use[u.prev].next = true; wr[i].o->flags |= P_GATE; }
    else if (st.slots == N_TILE) return false;
    else best = st.slots++;
    u.slot = best;
    holder[best] = wr[i].id;
  }
  {
    int pos[N_CL] = {}, flag[ID_PART + 4 * N_TEAM] = {}, seen[ID_PART] = {};
    auto goal = [&](int c) { return op[c][n_op[c] - 1].item0; };
    for (bool moved = true; moved;) {
      moved = false;
      for (int c = 0; c < 2 * n_pair; c++) {
        for (; pos[c] < goal(c); pos[c]++, moved = true) {
          bool ok = true;
          for (const Op* o = op[c]; o->type != OP_END; o++) {
            const int k = pos[c] - o->item0, own = o->type == OP_A ? o->id : N_TILE + o->park;
            if (k < 0 || k >= o->items) continue;
            if (o->type == OP_O) ok = k >= o->n || flag[o->id + k / 3];
            else if (k == o->items - 1 && (o->flags & P_GATE)) ok = seen[use[own].prev] == use[use[own].prev].readers;
            else if (k == 0 && o->type == OP_A && (o->flags & F_PARK)) ok = flag[N_TILE + o->park];
          }
          if (!ok) break;
          for (const Op* o = op[c]; o->type != OP_END; o++) {
            if (pos[c] == o->item0 + o->items + (o[1].type == OP_Q ? 7 : o[1].item0 == goal(c) ? -1 : 5)) {
              if (o->type == OP_A) flag[o->id] = 1;
              if (o->type == OP_Q && (o->flags & F_PARK)) flag[N_TILE + o->park] = 1;
              if (o->type == OP_O) flag[ID_PART + o->id / kH * 4 + o->quarter] = flag[ID_PART + o->id / kH * 4 + o->quarter + 1] = 1;
            }
            const int k = pos[c] - NBAR - o->item0, nw = o->n - TAIL;
            if (k == 0 && o->type == OP_A && (o->flags & F_PARK)) seen[N_TILE + o->park]++;
            if (o->type == OP_O && k >= 0 && k < o->items && k % 3 == 2 && (k < nw || k >= o->n)) seen[o->id + (k < nw ? k : k - TAIL) / 3]++;
          }
        }
      }
    }
    for (int c = 0; c < 2 * n_pair; c++) if (pos[c] < goal(c)) return false;
  }
  int n_job = 0, longest = 0;
  for (int t = 0; t < N_TEAM; t++) if (kH - covered[t] / 3 > longest) longest = kH - covered[t] / 3;
  for (int c = 0; c < 2 * n_pair; c++) {
    uint32_t items = 0, cur = 0, pend = 0;
    int n = 0, ev = 0;
    auto item = [&](uint32_t bytes, int count) {
      for (int i = 0; i < count; i++) { if (cur + bytes > RING) cur = 0; cur += bytes; items++; }
    };
    auto event = [&](uint32_t e) { if (ev < MAX_EV) P.prog[c].ev[ev] = e; ev++; };
    for (const Op* o = op[c];; o++) {
      if (o->type != OP_END && phase && (o->type == OP_O) != (phase == 2)) continue;
      uint32_t cw = o->type | (items % NBAR) << 15 | ((items / NBAR) & 1) << 19 | (cur >> 12) << 20 | pend, pw = o->type | o->id << 2 | o->flags;
      const int ps = use[N_TILE + o->park].slot;
      pend = 0;
      if (o->type == OP_O) {
        pw |= o->n << 13 | o->quarter << 20;
        if (o->flags & P_WIDE) {
          cw |= o->n << 2 | (o->id / kH * 4 + o->quarter + 1) << 9 | C_WIDE;
          item(SZ_W, o->n - TAIL);
          item(SZ_O, 2 * TAIL);
          pend = C_PEND | ((P.dbg & 8) ? C_SOON : 0);
          for (int i = 0; 3 * i < o->n; i++) event((o->id + i) | E_ON | (use[o->id + i].next ? 0 : E_LAST));
        } else {
          dem[n_job++] = {o->t0 - 1e6 * o->n, nullptr, (int)pw};
          st.own[c] = pw;
          pw = OP_O;
          event(E_DRAW | (items < TICK ? 0 : items - TICK));
          for (int i = 0; i <= longest; i++) event(E_JOB | i);
        }
      } else if (o->type != OP_END) {
        const bool parks = o->type == OP_Q && (o->flags & F_PARK);
        cw |= (parks ? ps : use[o->id].slot) << 2 | (o->flags & F_PARK);
        if (o->flags & F_PARK) pw |= o->park << 13 | ps << 20;
        if (o->type == OP_Q) item(SZ_Q, 10);
        else { if (o->flags & F_PARK) { item(SZ_PARK, 1); event((N_TILE + o->park) | E_ON | (use[N_TILE + o->park].next ? 0 : E_LAST)); } item(SZ_KV, 32); }
        if (parks || o->type == OP_A) pend = C_PEND | ((P.dbg & 16) ? 0 : C_SOON);
        if (o->flags & P_GATE) event(use[parks ? N_TILE + o->park : o->id].prev | E_ON | E_FREE);
      }
      P.prog[c].c[n] = cw; P.prog[c].p[n++] = pw;
      if (o->type == OP_END) { if (o->t0 > st.end) st.end = o->t0; break; }
    }
    if (ev > MAX_EV) return false;
    while (ev < MAX_EV) P.prog[c].ev[ev++] = 0;
    while (n < MAX_OPS) { P.prog[c].c[n] = OP_END; P.prog[c].p[n++] = OP_END; }
    P.first[c] = (uint16_t)(P.prog[c].p[0] & 2047);
  }
  sort(dem, n_job);
  for (int i = 0; i < n_job; i++) P.job[i] = dem[i].id;
  for (int i = 0; i < ID_PART; i++) {
    if (i < N_TILE) P.slot[i] = use[i].slot;
    P.info[i] = (use[i].readers + use[i].next) | (use[i].next ? I_NEXT : 0);
  }
  if (stats) *stats = st;
  return true;
}

const char* const kPrograms[N_CL / 2] = {
  "NNNNNNNNNF4", "NNNNNNNNNF0", "NNNNJf44NNNF7", "PNNNNNNNNNF8", "PNJ664NNNNNF5", "NNNNNNNNNFe",
  "NUNNNNNNNF5", "NNNNNNNNNF6", "NNNNNNNNNFe", "NUNNNJa78NFb", "PNJ281NNNNFc", "PPNJ551NNNNUNF2",
  "NNNNNJc39NNUF2", "NNJ379NNNNF9", "NUNUNJ974NFc", "PNUNNNNNNNF6", "PNJ062NNNNNFd", "NUNNNJd45NNFd",
  "PNNNNNNNNNF8", "NNUJ460Jb60NFf", "NNNNNNNNNFb", "PNJ751NNNNNNF3", "NNNNNNNNNF4", "PNJ172NNNNN",
  "PNNNNNNNNNFa", "NUNNNJe63NNF3", "PNNNNNNNNNF9", "NNNNNNNNNF0", "PNNNNNNNNNFa", "PPNUNNNNNNUF1",
  "NNUNNNNNNF7", "NNNNNJ878NF1", "NUNUNNNNNFf",
};

const char* const* bench_programs() {
  return kPrograms;
}

}

extern "C" void kernel_launch(void* const* d_in, const int* in_sizes, int n_in, void* d_out, int out_size) {
  (void)in_sizes; (void)n_in; (void)out_size;
  static EncodeFn fn = nullptr;
  static int n_clusters = 0;
  if (!fn) {
    cudaDriverEntryPointQueryResult qr;
    void* f = nullptr;
    cudaGetDriverEntryPoint("cuTensorMapEncodeTiled", &f, cudaEnableDefault, &qr);
    fn = (EncodeFn)f;
    cudaFuncSetAttribute(fused_kernel, cudaFuncAttributeMaxDynamicSharedMemorySize, SMEM_BYTES);
    cudaLaunchConfig_t cfg = {};
    cfg.gridDim = dim3(132); cfg.blockDim = dim3(384); cfg.dynamicSmemBytes = SMEM_BYTES;
    cudaLaunchAttribute at[1];
    at[0].id = cudaLaunchAttributeClusterDimension; at[0].val.clusterDim.x = 2; at[0].val.clusterDim.y = 1; at[0].val.clusterDim.z = 1;
    cfg.attrs = at; cfg.numAttrs = 1;
    if (cudaOccupancyMaxActiveClusters(&n_clusters, fused_kernel, &cfg) != cudaSuccess || n_clusters < 1) n_clusters = 1;
    (void)cudaGetLastError();
  }
  static Params P;
  const CUtensorMapSwizzle S128 = CU_TENSOR_MAP_SWIZZLE_128B, S64 = CU_TENSOR_MAP_SWIZZLE_64B;
  for (int blk = 0; blk < 2; blk++) {
    void* const* in = d_in + 5 * blk;
    { const cuuint64_t d[] = {kD, kB * kSq}, s[] = {kD * 2}; const cuuint32_t b[] = {64, 128};
      encode(fn, &P.x[blk], in[0], 2, d, s, b, S128); }
    { const cuuint64_t d[] = {64, 8, 3, (cuuint64_t)kB * kH * kSk / 8}, s[] = {kDh * 2, 128, 8 * kDh * 2}; const cuuint32_t b[] = {64, 8, 3, 8};
      encode(fn, &P.k[blk], in[1], 4, d, s, b, S128);
      encode(fn, &P.v[blk], in[2], 4, d, s, b, S128); }
    { const cuuint64_t d[] = {64, kD, kHD / 64}, s[] = {kHD * 2, 128}; const cuuint32_t b[] = {64, 64, 3};
      encode(fn, &P.wq[blk], in[3], 3, d, s, b, S128); }
    { const cuuint64_t d[] = {32, 2, kHD / 8, 4, kD / 32}, s[] = {kD * 2, 8 * kD * 2, 2 * kD * 2, 64}; const cuuint32_t b[] = {32, 2, 4, 4, 5};
      encode(fn, &P.wo[blk], in[4], 5, d, s, b, S64); }
  }
  { const cuuint64_t d[] = {32, kB * kSq, 2 * kD / 32}, s[] = {2 * kD * 2, 64}; const cuuint32_t b[] = {32, 16, 1};
    encode(fn, &P.out, d_out, 3, d, s, b, S64); }

  P.xw[0] = (const char*)d_in[0]; P.xw[1] = (const char*)d_in[3];
  cudaGetSymbolAddress((void**)&P.g, g_scratch);
  P.dbg = DBG_DEFAULT;
  if (n_clusters >= N_CL && plan(bench_programs(), N_CL / 2, 0, P)) {
    fused_kernel<<<2 * N_CL, 384, SMEM_BYTES>>>(P);
  } else {
    char buf[2 * N_TEAM][16];
    const char* text[2 * N_TEAM];
    for (int i = 0; i < 2 * N_TEAM; i++) { snprintf(buf[i], sizeof(buf[i]), "NNNNNNNNF%x", i / 2); text[i] = buf[i]; }
    for (int phase = 1; phase <= 2; phase++) {
      plan(text, 2 * N_TEAM, phase, P);
      fused_kernel<<<8 * N_TEAM, 384, SMEM_BYTES>>>(P);
    }
  }
}
```

```cpp
#include <cuda_runtime.h>
#include <cuda_bf16.h>
#include <cuda.h>
#include <stdint.h>
#include <stdio.h>

namespace {

constexpr int kB = 8, kSq = 256, kD = 640, kH = 32, kSk = 1024, kDh = 192;
constexpr int kHD = kH * kDh;
constexpr uint32_t RING = 224 * 1024;
constexpr uint32_t SZ_KV = 24576;
constexpr uint32_t SZ_Q = 16384 + 24576;
constexpr uint32_t SZ_O = 16384 + 20480;
constexpr uint32_t SZ_W = 16384 + 40960;
constexpr uint32_t SZ_PARK = 49152;
constexpr uint32_t SZ_OL = SZ_O + 8192;
constexpr int NBAR = 10;
constexpr int EARLY = 3;
constexpr int kSteps = kHD / 64;
constexpr int TAIL = 6;
constexpr uint32_t KV_CH = 64, KV_SBO = 3072;
constexpr int SMEM_BYTES = RING + 1024 + 1024;
constexpr int N_TEAM = 16, N_CL = 66, MAX_OPS = 24, MAX_EV = 80, N_TILE = N_TEAM * kH, MAX_PARK = 128, ID_PART = N_TILE + MAX_PARK;
enum : uint32_t { OP_END = 0, OP_Q = 1, OP_A = 2, OP_O = 3, F_PARK = 1 << 11,
                  C_WIDE = 1 << 27, C_PEND = 1 << 26, P_GATE = 1 << 12, P_WIDE = 1 << 11, P_LD = 1 << 12, P_PRE = 1 << 22,
                  I_NEXT = 8, E_ON = 1 << 15, E_FREE = 1 << 14, E_LAST = 1 << 13, E_DRAW = 1 << 12, E_JOB = 1 << 11 };

constexpr uint32_t DBG_DEFAULT = 0x040800;

struct alignas(1024) Scratch {
  unsigned int flag[2047];
  unsigned int ticket;
  uint4 part[N_TEAM * 4 * 2 * 3072];
  uint4 tile[N_TILE * 2 * 3072];
};

struct alignas(64) Params {
  const char* xw[2];
  uint16_t first[80];
  Scratch* g;
  uint32_t dbg;
  CUtensorMap x[2], wq[2], k[2], v[2], wo[2], out;
  struct {
    uint32_t c[MAX_OPS];
    uint32_t p[MAX_OPS];
    uint16_t ev[MAX_EV];
  } prog[N_CL];
  uint32_t job[N_CL];
  uint16_t slot[N_TILE];
  uint8_t info[ID_PART];
};

__device__ Scratch g_scratch;

template <int TB, int TA = 0>
__device__ __forceinline__ void wgmma_ss_n64(float (&d)[32], uint64_t da, uint64_t db, int scale_d) {
  asm volatile("{\n.reg .pred p;\nsetp.ne.b32 p, %34, 0;\n"
    "wgmma.mma_async.sync.aligned.m64n64k16.f32.bf16.bf16 {%0, %1, %2, %3, %4, %5, %6, %7, %8, %9, %10, %11, %12, %13, %14, %15, %16, %17, %18, %19, %20, %21, %22, %23, %24, %25, %26, %27, %28, %29, %30, %31}, %32, %33, p, 1, 1, %35, %36;\n}\n"
    : "+f"(d[0]), "+f"(d[1]), "+f"(d[2]), "+f"(d[3]), "+f"(d[4]), "+f"(d[5]), "+f"(d[6]), "+f"(d[7]), "+f"(d[8]), "+f"(d[9]), "+f"(d[10]), "+f"(d[11]), "+f"(d[12]), "+f"(d[13]), "+f"(d[14]), "+f"(d[15]), "+f"(d[16]), "+f"(d[17]), "+f"(d[18]), "+f"(d[19]), "+f"(d[20]), "+f"(d[21]), "+f"(d[22]), "+f"(d[23]), "+f"(d[24]), "+f"(d[25]), "+f"(d[26]), "+f"(d[27]), "+f"(d[28]), "+f"(d[29]), "+f"(d[30]), "+f"(d[31])
    : "l"(da), "l"(db), "r"(scale_d), "n"(TA), "n"(TB));
}
template <int TB>
__device__ __forceinline__ void wgmma_rs_n64(float (&d)[32], uint32_t a0, uint32_t a1, uint32_t a2, uint32_t a3, uint64_t db, int scale_d) {
  asm volatile("{\n.reg .pred p;\nsetp.ne.b32 p, %37, 0;\n"
    "wgmma.mma_async.sync.aligned.m64n64k16.f32.bf16.bf16 {%0, %1, %2, %3, %4, %5, %6, %7, %8, %9, %10, %11, %12, %13, %14, %15, %16, %17, %18, %19, %20, %21, %22, %23, %24, %25, %26, %27, %28, %29, %30, %31}, {%32, %33, %34, %35}, %36, p, 1, 1, %38;\n}\n"
    : "+f"(d[0]), "+f"(d[1]), "+f"(d[2]), "+f"(d[3]), "+f"(d[4]), "+f"(d[5]), "+f"(d[6]), "+f"(d[7]), "+f"(d[8]), "+f"(d[9]), "+f"(d[10]), "+f"(d[11]), "+f"(d[12]), "+f"(d[13]), "+f"(d[14]), "+f"(d[15]), "+f"(d[16]), "+f"(d[17]), "+f"(d[18]), "+f"(d[19]), "+f"(d[20]), "+f"(d[21]), "+f"(d[22]), "+f"(d[23]), "+f"(d[24]), "+f"(d[25]), "+f"(d[26]), "+f"(d[27]), "+f"(d[28]), "+f"(d[29]), "+f"(d[30]), "+f"(d[31])
    : "r"(a0), "r"(a1), "r"(a2), "r"(a3), "l"(db), "r"(scale_d), "n"(TB));
}
template <int TB, int TA = 0>
__device__ __forceinline__ void wgmma_ss_n160(float (&d)[80], uint64_t da, uint64_t db, int scale_d) {
  asm volatile("{\n.reg .pred p;\nsetp.ne.b32 p, %82, 0;\n"
    "wgmma.mma_async.sync.aligned.m64n160k16.f32.bf16.bf16 {%0, %1, %2, %3, %4, %5, %6, %7, %8, %9, %10, %11, %12, %13, %14, %15, %16, %17, %18, %19, %20, %21, %22, %23, %24, %25, %26, %27, %28, %29, %30, %31, %32, %33, %34, %35, %36, %37, %38, %39, %40, %41, %42, %43, %44, %45, %46, %47, %48, %49, %50, %51, %52, %53, %54, %55, %56, %57, %58, %59, %60, %61, %62, %63, %64, %65, %66, %67, %68, %69, %70, %71, %72, %73, %74, %75, %76, %77, %78, %79}, %80, %81, p, 1, 1, %83, %84;\n}\n"
    : "+f"(d[0]), "+f"(d[1]), "+f"(d[2]), "+f"(d[3]), "+f"(d[4]), "+f"(d[5]), "+f"(d[6]), "+f"(d[7]), "+f"(d[8]), "+f"(d[9]), "+f"(d[10]), "+f"(d[11]), "+f"(d[12]), "+f"(d[13]), "+f"(d[14]), "+f"(d[15]), "+f"(d[16]), "+f"(d[17]), "+f"(d[18]), "+f"(d[19]), "+f"(d[20]), "+f"(d[21]), "+f"(d[22]), "+f"(d[23]), "+f"(d[24]), "+f"(d[25]), "+f"(d[26]), "+f"(d[27]), "+f"(d[28]), "+f"(d[29]), "+f"(d[30]), "+f"(d[31]), "+f"(d[32]), "+f"(d[33]), "+f"(d[34]), "+f"(d[35]), "+f"(d[36]), "+f"(d[37]), "+f"(d[38]), "+f"(d[39]), "+f"(d[40]), "+f"(d[41]), "+f"(d[42]), "+f"(d[43]), "+f"(d[44]), "+f"(d[45]), "+f"(d[46]), "+f"(d[47]), "+f"(d[48]), "+f"(d[49]), "+f"(d[50]), "+f"(d[51]), "+f"(d[52]), "+f"(d[53]), "+f"(d[54]), "+f"(d[55]), "+f"(d[56]), "+f"(d[57]), "+f"(d[58]), "+f"(d[59]), "+f"(d[60]), "+f"(d[61]), "+f"(d[62]), "+f"(d[63]), "+f"(d[64]), "+f"(d[65]), "+f"(d[66]), "+f"(d[67]), "+f"(d[68]), "+f"(d[69]), "+f"(d[70]), "+f"(d[71]), "+f"(d[72]), "+f"(d[73]), "+f"(d[74]), "+f"(d[75]), "+f"(d[76]), "+f"(d[77]), "+f"(d[78]), "+f"(d[79])
    : "l"(da), "l"(db), "r"(scale_d), "n"(TA), "n"(TB));
}
template <int TB>
__device__ __forceinline__ void wgmma_rs_n160(float (&d)[80], uint32_t a0, uint32_t a1, uint32_t a2, uint32_t a3, uint64_t db, int scale_d) {
  asm volatile("{\n.reg .pred p;\nsetp.ne.b32 p, %85, 0;\n"
    "wgmma.mma_async.sync.aligned.m64n160k16.f32.bf16.bf16 {%0, %1, %2, %3, %4, %5, %6, %7, %8, %9, %10, %11, %12, %13, %14, %15, %16, %17, %18, %19, %20, %21, %22, %23, %24, %25, %26, %27, %28, %29, %30, %31, %32, %33, %34, %35, %36, %37, %38, %39, %40, %41, %42, %43, %44, %45, %46, %47, %48, %49, %50, %51, %52, %53, %54, %55, %56, %57, %58, %59, %60, %61, %62, %63, %64, %65, %66, %67, %68, %69, %70, %71, %72, %73, %74, %75, %76, %77, %78, %79}, {%80, %81, %82, %83}, %84, p, 1, 1, %86;\n}\n"
    : "+f"(d[0]), "+f"(d[1]), "+f"(d[2]), "+f"(d[3]), "+f"(d[4]), "+f"(d[5]), "+f"(d[6]), "+f"(d[7]), "+f"(d[8]), "+f"(d[9]), "+f"(d[10]), "+f"(d[11]), "+f"(d[12]), "+f"(d[13]), "+f"(d[14]), "+f"(d[15]), "+f"(d[16]), "+f"(d[17]), "+f"(d[18]), "+f"(d[19]), "+f"(d[20]), "+f"(d[21]), "+f"(d[22]), "+f"(d[23]), "+f"(d[24]), "+f"(d[25]), "+f"(d[26]), "+f"(d[27]), "+f"(d[28]), "+f"(d[29]), "+f"(d[30]), "+f"(d[31]), "+f"(d[32]), "+f"(d[33]), "+f"(d[34]), "+f"(d[35]), "+f"(d[36]), "+f"(d[37]), "+f"(d[38]), "+f"(d[39]), "+f"(d[40]), "+f"(d[41]), "+f"(d[42]), "+f"(d[43]), "+f"(d[44]), "+f"(d[45]), "+f"(d[46]), "+f"(d[47]), "+f"(d[48]), "+f"(d[49]), "+f"(d[50]), "+f"(d[51]), "+f"(d[52]), "+f"(d[53]), "+f"(d[54]), "+f"(d[55]), "+f"(d[56]), "+f"(d[57]), "+f"(d[58]), "+f"(d[59]), "+f"(d[60]), "+f"(d[61]), "+f"(d[62]), "+f"(d[63]), "+f"(d[64]), "+f"(d[65]), "+f"(d[66]), "+f"(d[67]), "+f"(d[68]), "+f"(d[69]), "+f"(d[70]), "+f"(d[71]), "+f"(d[72]), "+f"(d[73]), "+f"(d[74]), "+f"(d[75]), "+f"(d[76]), "+f"(d[77]), "+f"(d[78]), "+f"(d[79])
    : "r"(a0), "r"(a1), "r"(a2), "r"(a3), "l"(db), "r"(scale_d), "n"(TB));
}
template <int TB, int TA = 0>
__device__ __forceinline__ void wgmma_ss_n192(float (&d)[96], uint64_t da, uint64_t db, int scale_d) {
  asm volatile("{\n.reg .pred p;\nsetp.ne.b32 p, %98, 0;\n"
    "wgmma.mma_async.sync.aligned.m64n192k16.f32.bf16.bf16 {%0, %1, %2, %3, %4, %5, %6, %7, %8, %9, %10, %11, %12, %13, %14, %15, %16, %17, %18, %19, %20, %21, %22, %23, %24, %25, %26, %27, %28, %29, %30, %31, %32, %33, %34, %35, %36, %37, %38, %39, %40, %41, %42, %43, %44, %45, %46, %47, %48, %49, %50, %51, %52, %53, %54, %55, %56, %57, %58, %59, %60, %61, %62, %63, %64, %65, %66, %67, %68, %69, %70, %71, %72, %73, %74, %75, %76, %77, %78, %79, %80, %81, %82, %83, %84, %85, %86, %87, %88, %89, %90, %91, %92, %93, %94, %95}, %96, %97, p, 1, 1, %99, %100;\n}\n"
    : "+f"(d[0]), "+f"(d[1]), "+f"(d[2]), "+f"(d[3]), "+f"(d[4]), "+f"(d[5]), "+f"(d[6]), "+f"(d[7]), "+f"(d[8]), "+f"(d[9]), "+f"(d[10]), "+f"(d[11]), "+f"(d[12]), "+f"(d[13]), "+f"(d[14]), "+f"(d[15]), "+f"(d[16]), "+f"(d[17]), "+f"(d[18]), "+f"(d[19]), "+f"(d[20]), "+f"(d[21]), "+f"(d[22]), "+f"(d[23]), "+f"(d[24]), "+f"(d[25]), "+f"(d[26]), "+f"(d[27]), "+f"(d[28]), "+f"(d[29]), "+f"(d[30]), "+f"(d[31]), "+f"(d[32]), "+f"(d[33]), "+f"(d[34]), "+f"(d[35]), "+f"(d[36]), "+f"(d[37]), "+f"(d[38]), "+f"(d[39]), "+f"(d[40]), "+f"(d[41]), "+f"(d[42]), "+f"(d[43]), "+f"(d[44]), "+f"(d[45]), "+f"(d[46]), "+f"(d[47]), "+f"(d[48]), "+f"(d[49]), "+f"(d[50]), "+f"(d[51]), "+f"(d[52]), "+f"(d[53]), "+f"(d[54]), "+f"(d[55]), "+f"(d[56]), "+f"(d[57]), "+f"(d[58]), "+f"(d[59]), "+f"(d[60]), "+f"(d[61]), "+f"(d[62]), "+f"(d[63]), "+f"(d[64]), "+f"(d[65]), "+f"(d[66]), "+f"(d[67]), "+f"(d[68]), "+f"(d[69]), "+f"(d[70]), "+f"(d[71]), "+f"(d[72]), "+f"(d[73]), "+f"(d[74]), "+f"(d[75]), "+f"(d[76]), "+f"(d[77]), "+f"(d[78]), "+f"(d[79]), "+f"(d[80]), "+f"(d[81]), "+f"(d[82]), "+f"(d[83]), "+f"(d[84]), "+f"(d[85]), "+f"(d[86]), "+f"(d[87]), "+f"(d[88]), "+f"(d[89]), "+f"(d[90]), "+f"(d[91]), "+f"(d[92]), "+f"(d[93]), "+f"(d[94]), "+f"(d[95])
    : "l"(da), "l"(db), "r"(scale_d), "n"(TA), "n"(TB));
}
template <int TB>
__device__ __forceinline__ void wgmma_rs_n192(float (&d)[96], uint32_t a0, uint32_t a1, uint32_t a2, uint32_t a3, uint64_t db, int scale_d) {
  asm volatile("{\n.reg .pred p;\nsetp.ne.b32 p, %101, 0;\n"
    "wgmma.mma_async.sync.aligned.m64n192k16.f32.bf16.bf16 {%0, %1, %2, %3, %4, %5, %6, %7, %8, %9, %10, %11, %12, %13, %14, %15, %16, %17, %18, %19, %20, %21, %22, %23, %24, %25, %26, %27, %28, %29, %30, %31, %32, %33, %34, %35, %36, %37, %38, %39, %40, %41, %42, %43, %44, %45, %46, %47, %48, %49, %50, %51, %52, %53, %54, %55, %56, %57, %58, %59, %60, %61, %62, %63, %64, %65, %66, %67, %68, %69, %70, %71, %72, %73, %74, %75, %76, %77, %78, %79, %80, %81, %82, %83, %84, %85, %86, %87, %88, %89, %90, %91, %92, %93, %94, %95}, {%96, %97, %98, %99}, %100, p, 1, 1, %102;\n}\n"
    : "+f"(d[0]), "+f"(d[1]), "+f"(d[2]), "+f"(d[3]), "+f"(d[4]), "+f"(d[5]), "+f"(d[6]), "+f"(d[7]), "+f"(d[8]), "+f"(d[9]), "+f"(d[10]), "+f"(d[11]), "+f"(d[12]), "+f"(d[13]), "+f"(d[14]), "+f"(d[15]), "+f"(d[16]), "+f"(d[17]), "+f"(d[18]), "+f"(d[19]), "+f"(d[20]), "+f"(d[21]), "+f"(d[22]), "+f"(d[23]), "+f"(d[24]), "+f"(d[25]), "+f"(d[26]), "+f"(d[27]), "+f"(d[28]), "+f"(d[29]), "+f"(d[30]), "+f"(d[31]), "+f"(d[32]), "+f"(d[33]), "+f"(d[34]), "+f"(d[35]), "+f"(d[36]), "+f"(d[37]), "+f"(d[38]), "+f"(d[39]), "+f"(d[40]), "+f"(d[41]), "+f"(d[42]), "+f"(d[43]), "+f"(d[44]), "+f"(d[45]), "+f"(d[46]), "+f"(d[47]), "+f"(d[48]), "+f"(d[49]), "+f"(d[50]), "+f"(d[51]), "+f"(d[52]), "+f"(d[53]), "+f"(d[54]), "+f"(d[55]), "+f"(d[56]), "+f"(d[57]), "+f"(d[58]), "+f"(d[59]), "+f"(d[60]), "+f"(d[61]), "+f"(d[62]), "+f"(d[63]), "+f"(d[64]), "+f"(d[65]), "+f"(d[66]), "+f"(d[67]), "+f"(d[68]), "+f"(d[69]), "+f"(d[70]), "+f"(d[71]), "+f"(d[72]), "+f"(d[73]), "+f"(d[74]), "+f"(d[75]), "+f"(d[76]), "+f"(d[77]), "+f"(d[78]), "+f"(d[79]), "+f"(d[80]), "+f"(d[81]), "+f"(d[82]), "+f"(d[83]), "+f"(d[84]), "+f"(d[85]), "+f"(d[86]), "+f"(d[87]), "+f"(d[88]), "+f"(d[89]), "+f"(d[90]), "+f"(d[91]), "+f"(d[92]), "+f"(d[93]), "+f"(d[94]), "+f"(d[95])
    : "r"(a0), "r"(a1), "r"(a2), "r"(a3), "l"(db), "r"(scale_d), "n"(TB));
}

__device__ __forceinline__ uint32_t smem_u32(const void* p) { return (uint32_t)__cvta_generic_to_shared(p); }
__device__ __forceinline__ void wg_fence() { asm volatile("wgmma.fence.sync.aligned;" ::: "memory"); }
__device__ __forceinline__ void wg_commit() { asm volatile("wgmma.commit_group.sync.aligned;" ::: "memory"); }
template <int N> __device__ __forceinline__ void wg_wait() { asm volatile("wgmma.wait_group.sync.aligned %0;" ::"n"(N) : "memory"); }
__device__ __forceinline__ void sched_fence(uint32_t& keep, bool never) {
  asm volatile("{\n.reg .pred p;\nsetp.ne.b32 p, %1, 0;\n@p mov.u32 %0, %%clock;\n}\n" : "+r"(keep) : "r"((int)never) : "memory");
}
template <int N> __device__ __forceinline__ void fence_regs(float (&r)[N]) {
#pragma unroll
  for (int i = 0; i < N; i++) asm volatile("" : "+f"(r[i])::"memory");
}
template <int N> __device__ __forceinline__ void undefine(float (&r)[N]) {
#pragma unroll
  for (int i = 0; i < N; i++) asm volatile("" : "=f"(r[i]));
}
template <int N> __device__ __forceinline__ void fence_regs(uint32_t (&r)[N]) {
#pragma unroll
  for (int i = 0; i < N; i++) asm volatile("" : "+r"(r[i])::"memory");
}
__device__ __forceinline__ uint64_t mk_desc(uint32_t a16, uint32_t lbo, uint32_t sbo, uint32_t swz) {
  uint64_t d;
  asm("mov.b64 %0, {%1, %2};" : "=l"(d) : "r"(a16 + ((lbo >> 4) << 16)), "r"((sbo >> 4) | (swz << 30)));
  return d;
}
__device__ __forceinline__ void mbar_init(uint32_t bar, uint32_t cnt) {
  asm volatile("mbarrier.init.shared::cta.b64 [%0], %1;" ::"r"(bar), "r"(cnt) : "memory");
}
__device__ __forceinline__ void mbar_expect(uint32_t bar, uint32_t tx) {
  asm volatile("mbarrier.arrive.expect_tx.shared::cta.b64 _, [%0], %1;" ::"r"(bar), "r"(tx) : "memory");
}
__device__ __forceinline__ bool mbar_test(uint32_t bar, uint32_t ph) {
  uint32_t ok;
  asm volatile("{\n.reg .pred p;\nmbarrier.test_wait.parity.shared::cta.b64 p, [%1], %2;\nselp.u32 %0, 1, 0, p;\n}\n"
               : "=r"(ok) : "r"(bar), "r"(ph) : "memory");
  return ok;
}
__device__ __forceinline__ bool mbar_try(uint32_t bar, uint32_t ph, uint32_t ns) {
  uint32_t ok;
  asm volatile("{\n.reg .pred p;\nmbarrier.try_wait.parity.shared::cta.b64 p, [%1], %2, %3;\nselp.u32 %0, 1, 0, p;\n}\n"
               : "=r"(ok) : "r"(bar), "r"(ph), "r"(ns) : "memory");
  return ok;
}
__device__ __forceinline__ void mbar_wait(uint32_t bar, uint32_t ph) {
  asm volatile("{\n.reg .pred p;\n.reg .u32 n;\nmov.u32 n, 0;\n"
               "LOOP:\nmbarrier.try_wait.parity.shared::cta.b64 p, [%0], %1;\n@p bra DONE;\n"
               "add.u32 n, n, 1;\nsetp.lt.u32 p, n, 0x1000000;\n@p bra LOOP;\ntrap;\n"
               "DONE:\n}\n" ::"r"(bar), "r"(ph) : "memory");
}
__device__ __forceinline__ void mbar_wait_long(uint32_t bar) {
  asm volatile("{\n.reg .pred p;\n.reg .u32 n;\nmov.u32 n, 0;\n"
               "LOOP:\nmbarrier.try_wait.parity.shared::cta.b64 p, [%0], 0, 20000;\n@p bra DONE;\n"
               "add.u32 n, n, 1;\nsetp.lt.u32 p, n, 0x100000;\n@p bra LOOP;\ntrap;\n"
               "DONE:\n}\n" ::"r"(bar) : "memory");
}
__device__ __forceinline__ void mbar_arrive_cluster_if(bool on, uint32_t addr) {
  asm volatile("{\n.reg .pred p;\nsetp.ne.b32 p, %1, 0;\n@p mbarrier.arrive.shared::cluster.b64 _, [%0];\n}\n" ::"r"(addr), "r"((int)on) : "memory");
}
__device__ __forceinline__ void mbar_arrive_cluster_n(uint32_t n, uint32_t addr) {
  asm volatile("{\n.reg .pred p;\nsetp.ne.b32 p, %1, 0;\n@p mbarrier.arrive.shared::cluster.b64 _, [%0], %1;\n}\n" ::"r"(addr), "r"(n) : "memory");
}
__device__ __forceinline__ void tma2d(uint32_t dst, const CUtensorMap* m, uint32_t bar, int c0, int c1) {
  asm volatile("cp.async.bulk.tensor.2d.shared::cluster.global.mbarrier::complete_tx::bytes [%0], [%1, {%3, %4}], [%2];"
               ::"r"(dst), "l"(m), "r"(bar), "r"(c0), "r"(c1) : "memory");
}
__device__ __forceinline__ void tma3d(uint32_t dst, const CUtensorMap* m, uint32_t bar, int c0, int c1, int c2) {
  asm volatile("cp.async.bulk.tensor.3d.shared::cluster.global.mbarrier::complete_tx::bytes [%0], [%1, {%3, %4, %5}], [%2];"
               ::"r"(dst), "l"(m), "r"(bar), "r"(c0), "r"(c1), "r"(c2) : "memory");
}
__device__ __forceinline__ void tma3d_mc(uint32_t dst, const CUtensorMap* m, uint32_t bar, int c0, int c1, int c2) {
  asm volatile("cp.async.bulk.tensor.3d.shared::cluster.global.mbarrier::complete_tx::bytes.multicast::cluster"
               " [%0], [%1, {%3, %4, %5}], [%2], %6;"
               ::"r"(dst), "l"(m), "r"(bar), "r"(c0), "r"(c1), "r"(c2), "h"((uint16_t)3) : "memory");
}
__device__ __forceinline__ void tma3d_store(const CUtensorMap* m, uint32_t src, int c0, int c1, int c2) {
  asm volatile("cp.async.bulk.tensor.3d.global.shared::cta.bulk_group [%0, {%2, %3, %4}], [%1];"
               ::"l"(m), "r"(src), "r"(c0), "r"(c1), "r"(c2) : "memory");
}
__device__ __forceinline__ void bar_sync(int id, int n) { asm volatile("bar.sync %0, %1;" ::"r"(id), "r"(n) : "memory"); }
__device__ __forceinline__ uint32_t pack_bf16(float lo, float hi) {
  uint32_t r;
  asm("cvt.rn.bf16x2.f32 %0, %1, %2;" : "=r"(r) : "f"(hi), "f"(lo));
  return r;
}
__device__ __forceinline__ float ex2(float x) {
  float y;
  asm("ex2.approx.ftz.f32 %0, %1;" : "=f"(y) : "f"(x));
  return y;
}
__device__ __forceinline__ float rcp(float x) {
  float y;
  asm("rcp.approx.ftz.f32 %0, %1;" : "=f"(y) : "f"(x));
  return y;
}
__device__ __forceinline__ void stsm4(uint32_t addr, uint32_t a, uint32_t b, uint32_t c, uint32_t d) {
  asm volatile("stmatrix.sync.aligned.m8n8.x4.shared.b16 [%0], {%1, %2, %3, %4};" ::"r"(addr), "r"(a), "r"(b), "r"(c), "r"(d) : "memory");
}

__device__ __forceinline__ void tma4d_mc_hint(uint32_t dst, const CUtensorMap* m, uint32_t bar, int c3, uint64_t pol) {
  asm volatile("cp.async.bulk.tensor.4d.shared::cluster.global.mbarrier::complete_tx::bytes.multicast::cluster.L2::cache_hint"
               " [%0], [%1, {%3, %3, %3, %4}], [%2], %5, %6;"
               ::"r"(dst), "l"(m), "r"(bar), "r"(0), "r"(c3), "h"((uint16_t)3), "l"(pol) : "memory");
}
__device__ __forceinline__ void tma5d_mc(uint32_t dst, const CUtensorMap* m, uint32_t bar, int c2, int c4) {
  asm volatile("cp.async.bulk.tensor.5d.shared::cluster.global.mbarrier::complete_tx::bytes.multicast::cluster"
               " [%0], [%1, {%3, %3, %4, %3, %5}], [%2], %6;"
               ::"r"(dst), "l"(m), "r"(bar), "r"(0), "r"(c2), "r"(c4), "h"((uint16_t)3) : "memory");
}
__device__ __forceinline__ void bulk_load_hint(uint32_t dst, const void* src, uint32_t bytes, uint32_t bar, uint64_t pol) {
  asm volatile("cp.async.bulk.shared::cluster.global.mbarrier::complete_tx::bytes.L2::cache_hint [%0], [%1], %2, [%3], %4;"
               ::"r"(dst), "l"(src), "r"(bytes), "r"(bar), "l"(pol) : "memory");
}
__device__ __forceinline__ void stg2_if(bool on, void* p, uint32_t a, uint32_t b, uint32_t c, uint32_t d, uint32_t e, uint32_t f,
                                        uint32_t g, uint32_t h, uint64_t pol) {
  asm volatile("{\n.reg .pred p;\nsetp.ne.b32 p, %10, 0;\n"
               "@p st.global.L2::cache_hint.v4.b32 [%0], {%1, %2, %3, %4}, %9;\n"
               "@p st.global.L2::cache_hint.v4.b32 [%0 + 512], {%5, %6, %7, %8}, %9;\n}\n"
               ::"l"(p), "r"(a), "r"(b), "r"(c), "r"(d), "r"(e), "r"(f), "r"(g), "r"(h), "l"(pol), "r"((int)on) : "memory");
}
__device__ __forceinline__ uint64_t evict_first() {
  uint64_t p;
  asm("createpolicy.fractional.L2::evict_first.b64 %0, 1.0;" : "=l"(p));
  return p;
}
__device__ __forceinline__ bool elect() {
  uint32_t ok;
  asm volatile("{\n.reg .pred p;\nelect.sync _|p, 0xffffffff;\nselp.u32 %0, 1, 0, p;\n}\n" : "=r"(ok));
  return ok;
}
__device__ __forceinline__ void mbar_arrive(uint32_t bar) {
  asm volatile("mbarrier.arrive.shared::cta.b64 _, [%0];" ::"r"(bar) : "memory");
}
__device__ __forceinline__ void mbar_arrive_if(bool on, uint32_t bar) {
  asm volatile("{\n.reg .pred p;\nsetp.ne.b32 p, %1, 0;\n@p mbarrier.arrive.shared::cta.b64 _, [%0];\n}\n" ::"r"(bar), "r"((int)on) : "memory");
}
__device__ __forceinline__ void lds2_if(bool on, uint32_t p, uint32_t (&t)[8]) {
  asm volatile("{\n.reg .pred p;\nsetp.ne.b32 p, %9, 0;\n@p ld.shared.v4.b32 {%0, %1, %2, %3}, [%8];\n@p ld.shared.v4.b32 {%4, %5, %6, %7}, [%8 + 512];\n}\n"
               : "+r"(t[0]), "+r"(t[1]), "+r"(t[2]), "+r"(t[3]), "+r"(t[4]), "+r"(t[5]), "+r"(t[6]), "+r"(t[7]) : "r"(p), "r"((int)on) : "memory");
}
__device__ __forceinline__ void lds128(uint32_t p, uint32_t& a, uint32_t& b, uint32_t& c, uint32_t& d) {
  asm volatile("ld.shared.v4.b32 {%0, %1, %2, %3}, [%4];" : "=r"(a), "=r"(b), "=r"(c), "=r"(d) : "r"(p) : "memory");
}
template <class T> __device__ __forceinline__ T* ptr_add(T* base, uint32_t bytes) {
  T* r;
  asm("{\n.reg .u32 lo, hi;\nmov.b64 {lo, hi}, %1;\nadd.cc.u32 lo, lo, %2;\naddc.u32 hi, hi, 0;\nmov.b64 %0, {lo, hi};\n}\n" : "=l"(r) : "l"(base), "r"(bytes));
  return r;
}
__device__ __forceinline__ uint32_t lds32(uint32_t p) {
  uint32_t v;
  asm volatile("ld.volatile.shared.u32 %0, [%1];" : "=r"(v) : "r"(p) : "memory");
  return v;
}
__device__ __forceinline__ uint32_t flag_get(const unsigned int* p) {
  uint32_t v;
  asm volatile("ld.acquire.gpu.global.u32 %0, [%1];" : "=r"(v) : "l"(p) : "memory");
  return v;
}
__device__ __forceinline__ uint32_t wait_word(uint32_t p, uint32_t target) {
  uint32_t v;
  asm volatile("{\n.reg .pred p;\n.reg .u32 n;\nmov.u32 n, 0;\n"
               "LOOP:\nld.acquire.cta.shared.u32 %0, [%1];\nsetp.ge.u32 p, %0, %2;\n@p bra DONE;\n"
               "nanosleep.u32 %3;\nadd.u32 n, n, 1;\nsetp.lt.u32 p, n, 0x400000;\n@p bra LOOP;\ntrap;\n"
               "DONE:\n}\n" : "=r"(v) : "r"(p), "r"(target), "n"(400) : "memory");
  return v;
}
__device__ __forceinline__ void flag_set(unsigned int* p, uint32_t v) {
  asm volatile("st.release.gpu.global.u32 [%0], %1;" ::"l"(p), "r"(v) : "memory");
}
__device__ __forceinline__ void flag_dec(unsigned int* p) {
  asm volatile("red.relaxed.gpu.global.add.u32 [%0], 0xffffffff;" ::"l"(p) : "memory");
}

struct Cursor {
  int bi;
  uint32_t ph;
  __device__ __forceinline__ void next() {
    if (++bi == NBAR) { bi = 0; ph ^= 1; }
  }
};

constexpr float kScaleLog2 = 0.07216878364870322f * 1.4426950408889634f;
constexpr float kSumLimit = 1048576.0f;

__global__ void __cluster_dims__(2, 1, 1) __launch_bounds__(384, 1)
fused_kernel(const __grid_constant__ Params P) {
  extern __shared__ uint8_t smem_raw[];
  const uint32_t sbase = (smem_u32(smem_raw) + 1023) & ~1023u;
  const uint32_t full0 = sbase + RING, empty0 = full0 + 8 * NBAR, odone0 = empty0 + 8 * NBAR, ev0 = odone0 + 8 * MAX_OPS;
  const uint32_t progress = ev0 + 8 * MAX_EV, jobw = progress + 4;
  const uint32_t rank = blockIdx.x & 1;
  const int role = blockIdx.x >> 1;
  const int wid = __shfl_sync(0xffffffffu, (int)(threadIdx.x >> 5), 0);
  const int wg = wid >> 2;

  if (wid < 8) {
    if (elect()) {
#pragma unroll
      for (int j = 0; j < 16; j++) {
        const int i = EARLY + 16 * wid + j;
        if (i < 2 * NBAR + MAX_OPS + MAX_EV) mbar_init(full0 + 8 * i, i < NBAR ? 1 : i < 2 * NBAR ? 16 : i < 2 * NBAR + MAX_OPS ? 8 : 1);
      }
      if (wid == 7) asm volatile("st.shared.v2.u32 [%0], {0, 0};\nfence.acq_rel.cta;" ::"r"(progress) : "memory");
      asm volatile("fence.mbarrier_init.release.cluster;" ::: "memory");
    }
  } else if (wid > 8) {
    const uint32_t g = blockIdx.x * 96 + threadIdx.x - 288, w = g - 2048;
    if (g < 4096) asm volatile("prefetch.global.L2 [%0];" ::"l"(g < 2048 ? P.xw[0] + g * (kD * 2) : P.xw[1] + (w >> 5) * (kHD * 2) + (w & 31) * 128));
  } else {
    const uint32_t op0 = P.first[role];
    if (elect()) {
#pragma unroll
      for (int k = 0; k < EARLY; k++) mbar_init(full0 + 8 * k, 1);
      asm volatile("fence.mbarrier_init.release.cluster;" ::: "memory");
      const int blk = (op0 >> 10) & 1;
      if ((op0 & 3) == OP_Q) {
#pragma unroll
        for (int k = 0; k < EARLY; k++) {
          mbar_expect(full0 + 8 * k, SZ_Q);
          tma2d(sbase + k * SZ_Q, &P.x[blk], full0 + 8 * k, 64 * k, ((op0 >> 7) & 7) * kSq + rank * 128);
          tma3d(sbase + k * SZ_Q + 16384, &P.wq[blk], full0 + 8 * k, 0, 64 * k, 3 * ((op0 >> 2) & 31));
        }
      }
      asm volatile("prefetch.tensormap [%0];" ::"l"(rank ? &P.v[blk] : &P.k[blk]) : "memory");
    }
  }
  __syncwarp();
  asm volatile("barrier.cluster.arrive.relaxed.aligned;\nbarrier.cluster.wait.aligned;" ::: "memory");

  if (wg < 2) {
    asm volatile("setmaxnreg.inc.sync.aligned.u32 240;");
    const uint32_t* prog = P.prog[role].c;
    const int lane = threadIdx.x & 31, warp = wid & 3;
    uint32_t empty_rem;
    asm volatile("mapa.shared::cluster.u32 %0, %1, %2;" : "=r"(empty_rem) : "r"(empty0), "r"(lane & 1));
    uint32_t keep = (threadIdx.x & 127) < 2 ? 4 : 0;
    auto release = [&](int slot) { mbar_arrive_cluster_n(keep, empty_rem + 8 * slot); };
    auto release_warp = [&](int slot, bool on = true) { mbar_arrive_cluster_if(lane < 2 && on, empty_rem + 8 * slot); };
    Cursor r{0, 0};
    const uint32_t ring16 = (sbase & 0x3FFFF) >> 4;
    uint32_t cur = ring16;
    bool rdy0 = false, rdy1 = false;
    auto probe1 = [&]() { rdy0 = mbar_test(full0 + 8 * r.bi, r.ph); };
    auto probe2 = [&]() {
      Cursor n = r;
      rdy0 = mbar_test(full0 + 8 * n.bi, n.ph);
      n.next();
      rdy1 = mbar_test(full0 + 8 * n.bi, n.ph);
    };
    auto take = [&](bool rdy, uint32_t bytes, uint32_t& addr) {
      const int bi = r.bi;
      if (__builtin_expect(!__all_sync(0xffffffffu, rdy), 0)) mbar_wait(full0 + 8 * r.bi, r.ph);
      r.next();
      if (cur > ring16 + ((RING - bytes) >> 4)) cur = ring16;
      addr = cur;
      cur += bytes >> 4;
      return bi;
    };
    const bool never = P.dbg == 0xffffffffu;
    uint32_t q[48];
#pragma unroll
    for (int i = 0; i < 48; i++) q[i] = 0;
    const int row = wg * 64 + warp * 16 + (lane >> 2);
    const int img0 = row * 4 + ((lane & 3) ^ ((row >> 1) & 3));
    uint4* pend = nullptr;
    bool pend_any = false;
    const uint64_t spol = evict_first();
    int pc = 0;
    auto slab = [&](int c, int i0) {
#pragma unroll
      for (int i = i0; i < 6; i++)
        stg2_if(c == i, pend + i * 512, q[8 * i], q[8 * i + 1], q[8 * i + 2], q[8 * i + 3],
                q[8 * i + 4], q[8 * i + 5], q[8 * i + 6], q[8 * i + 7], spol);
    };
    auto drain = [&](int c) {
      if (!pend_any || c >= 6) return;
      slab(c, 0);
      if (c == 5) {
        __syncwarp();
        mbar_arrive_if(lane == 0, odone0 - 8 + 8 * pc);
      }
    };

    for (;; pc++) {
      uint32_t op = prog[pc];
      const int type = op & 3;
      auto enter = [&]() {
        r.bi = (op >> 15) & 15; r.ph = (op >> 19) & 1; cur = ring16 + (((op >> 20) & 63) << 8);
      };
      enter();
      pend_any = op & C_PEND;
      uint32_t job = 0;
      if ((op & (3 | C_WIDE)) == OP_O) job = __shfl_sync(0xffffffffu, wait_word(jobw, 1), 0);
      if (type == OP_END || job == OP_O) {
#pragma unroll 1
        for (int c = 0; c < 6; c++) drain(c);
        asm volatile("barrier.cluster.arrive.relaxed;" ::: "memory");
        break;
      }
      {
        float s[32], o[96];
        uint32_t ad0;
        int bi0, sk1;
        uint32_t pa[16], pb[16];
        float mc0, mc1, l0, l1;
        bool shifted;
        uint32_t nop;
        auto expo = [&](float (&s)[32], uint32_t (&pout)[16], float& b0, float& b1, bool shift, auto mid) {
          float c0, c1;
#pragma unroll
          for (int i = 0; i < 8; i++) {
            const float e0 = ex2(shift ? s[4 * i] - mc0 : s[4 * i]), e1 = ex2(shift ? s[4 * i + 1] - mc0 : s[4 * i + 1]);
            const float e2 = ex2(shift ? s[4 * i + 2] - mc1 : s[4 * i + 2]), e3 = ex2(shift ? s[4 * i + 3] - mc1 : s[4 * i + 3]);
            if (i) { b0 += e0; c0 += e1; b1 += e2; c1 += e3; } else { b0 = e0; c0 = e1; b1 = e2; c1 = e3; }
            pout[2 * i] = pack_bf16(e0, e1); pout[2 * i + 1] = pack_bf16(e2, e3);
            if (i & 1) mid(i >> 1);
          }
          b0 += c0; b1 += c1;
        };
        auto rowmax = [&](float (&s)[32], float& m0, float& m1) {
          m0 = fmaxf(s[0], s[1]); m1 = fmaxf(s[2], s[3]);
#pragma unroll
          for (int i = 1; i < 8; i++) { m0 = fmaxf(m0, fmaxf(s[4 * i], s[4 * i + 1])); m1 = fmaxf(m1, fmaxf(s[4 * i + 2], s[4 * i + 3])); }
          m0 = fmaxf(m0, __shfl_xor_sync(0xffffffffu, m0, 1)); m1 = fmaxf(m1, __shfl_xor_sync(0xffffffffu, m1, 1));
          m0 = fmaxf(m0, __shfl_xor_sync(0xffffffffu, m0, 2)); m1 = fmaxf(m1, __shfl_xor_sync(0xffffffffu, m1, 2));
        };
        auto first = [&](float (&s)[32], int sk0, auto mid) {
          fence_regs(s);
          release(sk0);
          mc0 = 0.f; mc1 = 0.f;
          expo(s, pa, l0, l1, false, mid);
          shifted = __any_sync(0xffffffffu, !(fmaxf(l0, l1) <= kSumLimit && fminf(l0, l1) >= 1.f / kSumLimit));
          if (shifted) {
            rowmax(s, mc0, mc1);
            expo(s, pa, l0, l1, true, [](int) {});
          }
        };
        auto qk = [&](float (&s)[32], uint32_t ak, int k0 = 0, int k1 = 12) {
#pragma unroll
          for (int kk = k0; kk < k1; kk++)
            wgmma_rs_n64<0>(s, q[4 * kk], q[4 * kk + 1], q[4 * kk + 2], q[4 * kk + 3], mk_desc(ak, 16, KV_SBO, 1) + ((kk >> 2) * KV_CH + (kk & 3) * 2), kk != 0);
          if (k1 == 12) wg_commit();
        };
        auto pv = [&](uint32_t (&pin)[16], uint32_t av, int acc) {
#pragma unroll
          for (int kk = 0; kk < 4; kk++)
            wgmma_rs_n192<1>(o, pin[4 * kk], pin[4 * kk + 1], pin[4 * kk + 2], pin[4 * kk + 3], mk_desc(av, KV_CH * 16, KV_SBO, 1) + (kk * (KV_SBO / 8)), acc || (kk != 0));
          wg_commit();
        };
        auto finish = [&](uint32_t (&pout)[16], int sk, int sv) {
          probe2();
          wg_wait<1>();
          fence_regs(s);
          release(sk);
          float b0, b1;
#pragma unroll 1
          for (bool redo = false;; redo = true) {
            expo(s, pout, b0, b1, false, [](int) {});
            if (!__any_sync(0xffffffffu, !redo && (shifted || !(fmaxf(b0, b1) <= kSumLimit)))) break;
            shifted = true;
            rowmax(s, b0, b1);
            b0 = fmaxf(mc0, b0); b1 = fmaxf(mc1, b1);
            const float a0 = ex2(mc0 - b0), a1 = ex2(mc1 - b1);
            mc0 = b0; mc1 = b1;
            l0 *= a0; l1 *= a1;
            wg_wait<0>();
            fence_regs(o);
#pragma unroll
            for (int i = 0; i < 24; i++) { o[4 * i] *= a0; o[4 * i + 1] *= a0; o[4 * i + 2] *= a1; o[4 * i + 3] *= a1; }
#pragma unroll
            for (int i = 0; i < 32; i++) s[i] -= (i & 2) ? mc1 : mc0;
          }
          l0 += b0; l1 += b1;
          wg_wait<0>();
          fence_regs(o);
          release(sv);
        };
        auto step = [&](uint32_t (&pin)[16], uint32_t (&pout)[16]) {
          uint32_t ak, av;
          const int sk = take(rdy0, SZ_KV, ak), sv = take(rdy1, SZ_KV, av);
          wg_fence();
          qk(s, ak);
          pv(pin, av, 1);
          finish(pout, sk, sv);
        };
        auto unpark = [&]() {
          uint32_t ad, ak;
          const int bi = take(rdy0, SZ_PARK, ad);
#pragma unroll
          for (int i = 0; i < 12; i++) lds128(sbase + (ad - ring16 + img0) * 16 + (i >> 1) * 8192 + (i & 1) * 512, q[4 * i], q[4 * i + 1], q[4 * i + 2], q[4 * i + 3]);
          const int sk0 = take(false, SZ_KV, ak);
          fence_regs(q);
          release_warp(bi);
          wg_fence();
          qk(s, ak);
          probe2();
          return sk0;
        };
        auto mma4 = [&](uint32_t ad, int acc) {
#pragma unroll
          for (int kk = 0; kk < 4; kk++)
            wgmma_ss_n192<1>(o, mk_desc(ad + wg * 512, 16, 1024, 1) + (kk * 2), mk_desc(ad, 8192, 1024, 1) + (1024 + kk * 128), acc || kk != 0);
        };
        auto convert = [&](int i0, int i1) {
          sched_fence(keep, never);
#pragma unroll
          for (int i = i0; i < i1; i++) {
            q[i] = pack_bf16(o[2 * i] * kScaleLog2, o[2 * i + 1] * kScaleLog2);
            if ((i & 7) == 7 && i != i1 - 1) sched_fence(keep, never);
          }
          sched_fence(keep, never);
        };
        auto kend = [&](int bi, int k) {
          wg_commit();
          drain(k < 8 ? (0x54732710u >> (4 * k)) & 7 : 7);
          probe1();
          wg_wait<0>();
          release(bi);
        };
        if (type == OP_O) {
          float c[80];
          int prev = 0;
          auto hand_over = [&](float (&c)[80], uint4* dst) {
            fence_regs(c);
#pragma unroll
            for (int i = 0; i < 48; i++) q[i] = i < 8 ? 0 : pack_bf16(c[2 * i - 16], c[2 * i - 15]);
            pend = dst;
          };
          auto mma2 = [&](float (&c)[80], uint32_t ad, uint32_t oa, uint32_t ob, int acc) {
            wgmma_ss_n160<1>(c, mk_desc(ad + wg * 256, 16, 512, 2) + (oa), mk_desc(ad, 2048, 512, 2) + (1024 + ob), acc);
            wgmma_ss_n160<1>(c, mk_desc(ad + wg * 256, 16, 512, 2) + (oa + 2), mk_desc(ad, 2048, 512, 2) + (1024 + ob + 64), 1);
          };
          auto kstep = [&](float (&c)[80], int acc, auto hook, uint32_t bytes = SZ_O) {
            uint32_t ad;
            const int bi = take(rdy0, bytes, ad);
            wg_fence();
            mma2(c, ad, 0, 0, acc);
            wg_commit();
            if (acc) wg_wait<1>();
            if (acc == 1) release(prev);
            if (acc > 1) release_warp(prev, acc == 2 || wg == 0);
            mma2(c, ad, 512, 640, 1);
            wg_commit();
            prev = bi;
            hook();
            probe1();
            wg_wait<1>();
          };
          if (op & C_WIDE) {
            float d[80];
            const int nk = (op >> 2) & 127;
            uint4* part = ptr_add(P.g->part, (((op >> 9) & 63) * 2 + rank) * SZ_PARK + img0 * 16);
            auto wstep = [&](int acc, auto hook) {
              uint32_t ad;
              const int bi = take(rdy0, SZ_W, ad);
              wg_fence();
              mma2(d, ad, 0, 0, acc);
              mma2(d, ad, 512, 640, 1);
              wg_commit();
              if (acc) { wg_wait<1>(); release(prev); }
              mma2(c, ad, 0, 1280, acc);
              mma2(c, ad, 512, 1920, 1);
              wg_commit();
              prev = bi;
              hook();
              probe1();
              wg_wait<1>();
            };
            wstep(0, [&]() { drain(0); drain(1); });
#pragma unroll 1
            for (int k = 2; k < 6; k += 2) wstep(1, [&]() { drain(k); drain(k + 1); });
#pragma unroll 1
            for (int k = 3 + TAIL; k < nk; k++) {
              wstep(1, []() {});
            }
#pragma unroll 1
            for (int k = 0; k < TAIL; k++) kstep(d, 1, []() {});
            nop = prog[pc + 1];
            kstep(c, 1, [&]() { hand_over(d, part - 6144); });
#pragma unroll 1
            for (int k = 1; k < TAIL; k++) kstep(c, 1, [&]() { slab(k, 1); });
            if ((nop & 3) == OP_Q) {
              op = nop;
              enter();
              pc++;
              pend_any = true;
              bi0 = take(rdy0, SZ_Q, ad0);
              undefine(o);
              wg_fence();
              mma4(ad0, 0);
              wg_commit();
              wg_wait<1>();
              release(prev);
              hand_over(c, part);
              probe1();
              wg_wait<0>();
              release(bi0);
              fence_regs(o);
              goto next_head;
            }
            wg_wait<0>();
            release(prev);
            hand_over(c, part);
            continue;
          }
          auto unblock = [&](int k) {
            if (__all_sync(0xffffffffu, rdy0) || __all_sync(0xffffffffu, mbar_try(full0 + 8 * r.bi, r.ph, 1500))) return;
#pragma unroll 1
            for (; k < 6; k++) drain(k);
            pend_any = false;
          };
          unblock(0);
          kstep(c, 0, [&]() { drain(0); });
          int left = ((job >> 13) & 127) - 6;
#pragma unroll 1
          for (uint32_t k = 1, pace = left >= 29 ? 0x4511 : left <= 17 ? 0x1a : 0x155; k < 6; pace >>= 2, left--) {
            unblock(k);
            kstep(c, 1, [&]() {
#pragma unroll 1
              for (int i = pace & 3; i > 0; i--) drain(k++);
            });
          }
#pragma unroll 1
          for (; left > 0; left--) kstep(c, 1, []() {});
          uint32_t t[8], stage[3];
          float u[80];
          auto unpack = [&](int j) {
#pragma unroll
            for (int i = 0; i < 8; i++) {
              u[16 * j + 2 * i] = __uint_as_float(t[i] << 16); u[16 * j + 2 * i + 1] = __uint_as_float(t[i] & 0xffff0000u);
              asm volatile("" : "+f"(u[16 * j + 2 * i]), "+f"(u[16 * j + 2 * i + 1]));
            }
          };
#pragma unroll
          for (int i = 0; i < 8; i++) t[i] = 0;
          const uint32_t bytes = (job & P_LD) ? SZ_OL : SZ_O;
#pragma unroll
          for (int j = 0; j < 5; j++) {
            if (j == 2 && wg == 1) {
              wg_wait<0>();
              release_warp(prev);
              bar_sync(1, 256);
            }
            kstep(c, j == 2 ? 3 : 2, [&]() {
              if (j == 4) asm volatile("{\n.reg .pred p;\nsetp.eq.u32 p, %0, 0;\n@p bar.arrive 1, 256;\n}\n" ::"r"(wg) : "memory");
              if (j) unpack(j - 1);
              lds2_if(job & P_LD, sbase + (cur - ring16 + img0) * 16 - 8192, t);
              if (j >= 1 && j <= 3) stage[j - 1] = sbase + (cur - ring16) * 16 - bytes + wid * 1024;
            }, bytes);
          }
          unpack(4);
          sched_fence(keep, never);
          wg_wait<0>();
          fence_regs(c);
          release_warp(prev);
          asm volatile("barrier.cluster.arrive.relaxed;" ::: "memory");
#pragma unroll
          for (int i = 0; i < 10; i++) {
            const int v = (i & 1) * 2 + (lane >> 4);
            const uint32_t sa = stage[i >> 2] + (i & 2) * 4096;
            stsm4(sa + (lane & 15) * 64 + ((v ^ ((lane >> 1) & 3)) << 4), pack_bf16(c[8 * i] + u[8 * i], c[8 * i + 1] + u[8 * i + 1]),
                  pack_bf16(c[8 * i + 2] + u[8 * i + 2], c[8 * i + 3] + u[8 * i + 3]), pack_bf16(c[8 * i + 4] + u[8 * i + 4], c[8 * i + 5] + u[8 * i + 5]),
                  pack_bf16(c[8 * i + 6] + u[8 * i + 6], c[8 * i + 7] + u[8 * i + 7]));
          }
          asm volatile("fence.proxy.async.shared::cta;" ::: "memory");
          __syncwarp();
          if (elect()) {
#pragma unroll
            for (int i = 0; i < 5; i++)
              tma3d_store(&P.out, stage[i >> 1] + (i & 1) * 8192, 0, ((job >> 7) & 7) * kSq + rank * 128 + wid * 16, ((job >> 10) & 1) * 20 + ((job >> 20) & 3) * 5 + i);
            asm volatile("cp.async.bulk.commit_group;\ncp.async.bulk.wait_group.read 0;" ::: "memory");
          }
          __syncwarp();
          break;
        }
        bi0 = take(rdy0, SZ_Q, ad0);
        undefine(o);
        wg_fence();
        mma4(ad0, 0);
        kend(bi0, 0);
        fence_regs(o);
      next_head:
        {
#pragma unroll 1
          for (int k = 1; k < ((op & F_PARK) ? 10 : 8); k++) {
            uint32_t ad;
            const int bi = take(rdy0, SZ_Q, ad);
            wg_fence();
            mma4(ad, 1);
            kend(bi, k);
          }
          if (op & F_PARK) {
            fence_regs(o);
            convert(0, 48);
            pend = ptr_add(P.g->tile, (((op >> 2) & 511) * 2 + rank) * SZ_PARK + img0 * 16);
            continue;
          }
          uint32_t a8, a9, ak0, ak1;
          const int b8 = take(rdy0, SZ_Q, a8), b9 = take(false, SZ_Q, a9);
          wg_fence();
          mma4(a8, 1);
          wg_commit();
          mma4(a9, 1);
          wg_commit();
          pc++;
          wg_wait<1>();
          release(b8);
          const int sk0 = take(false, SZ_KV, ak0);
          wg_wait<0>();
          fence_regs(o);
          release(b9);
          float s0[32];
          convert(0, 32);
          wg_fence();
          qk(s0, ak0, 0, 4);
          convert(32, 48);
          wg_fence();
          qk(s0, ak0, 4, 12);
          sk1 = take(false, SZ_KV, ak1);
          probe1();
          wg_wait<0>();
          first(s0, sk0, [&](int i) {
            if (i == 0) return;
            sched_fence(keep, never);
            wg_fence();
            if (i == 1) qk(s, ak1, 0, 4);
            if (i == 2) qk(s, ak1, 4, 8);
            if (i == 3) qk(s, ak1, 8, 12);
            sched_fence(keep, never);
          });
        }
        for (;;) {
          {
            uint32_t av;
            const int sv = take(rdy0, SZ_KV, av);
            undefine(o);
            wg_fence();
            pv(pa, av, 0);
            finish(pb, sk1, sv);
          }
          nop = prog[pc + 1];
#pragma unroll 1
          for (int jj = 0; jj < 7; jj++) {
            step(pb, pa);
            step(pa, pb);
          }
          float i0, i1;
          auto last = [&]() {
            uint32_t av;
            const int sv = take(rdy0, SZ_KV, av);
            wg_fence();
            pv(pb, av, 1);
            sched_fence(keep, never);
            probe1();
            l0 += __shfl_xor_sync(0xffffffffu, l0, 1); l1 += __shfl_xor_sync(0xffffffffu, l1, 1);
            l0 += __shfl_xor_sync(0xffffffffu, l0, 2); l1 += __shfl_xor_sync(0xffffffffu, l1, 2);
            i0 = rcp(l0); i1 = rcp(l1);
            pend = ptr_add(P.g->tile, (((op >> 2) & 511) * 2 + rank) * SZ_PARK + img0 * 16);
            return sv;
          };
          auto normalise = [&](uint32_t (&d)[48], auto mid) {
#pragma unroll
            for (int i = 0; i < 24; i++) {
              d[8 * (i >> 2) + (i & 3)] = pack_bf16(o[4 * i] * i0, o[4 * i + 1] * i0);
              d[8 * (i >> 2) + (i & 3) + 4] = pack_bf16(o[4 * i + 2] * i1, o[4 * i + 3] * i1);
              if ((i & 1) && i != 23) sched_fence(keep, never);
              if ((i & 3) == 3 && i != 23) mid(i >> 2);
            }
          };
          const int sv = last();
          if ((nop & 3) != OP_A) {
            op = nop;
            enter();
            pend_any = true;
            bi0 = take(rdy0 || (nop & 3) != OP_Q, SZ_Q, ad0);
            sched_fence(keep, never);
            wg_wait<0>();
            fence_regs(o);
            release(sv);
            normalise(q, [](int) {});
            undefine(o);
            if ((nop & 3) != OP_Q) break;
            sched_fence(keep, never);
            wg_fence();
            mma4(ad0, 0);
            pc++;
            kend(bi0, 0);
            fence_regs(o);
            goto next_head;
          }
          const int sk0 = unpark();
          wg_wait<1>();
          fence_regs(o);
          release(sv);
          uint32_t t[48];
          auto st = [&](int i) {
            stg2_if(true, pend + i * 512, t[8 * i], t[8 * i + 1], t[8 * i + 2], t[8 * i + 3], t[8 * i + 4], t[8 * i + 5], t[8 * i + 6], t[8 * i + 7], spol);
          };
          normalise(t, [&](int i) { if (!(i & 1)) st(i >> 1); });
          wg_wait<0>();
          first(s, sk0, [&](int i) { if (i < 3) { sched_fence(keep, never); st(3 + i); } });
          __syncwarp();
          mbar_arrive_if(lane == 0, odone0 + 8 * pc);
          pc++;
          op = nop;
          uint32_t ak1;
          sk1 = take(rdy0, SZ_KV, ak1);
          rdy0 = rdy1;
          wg_fence();
          qk(s, ak1);
        }
      }
    }
    asm volatile("barrier.cluster.wait;" ::: "memory");
  } else {
    asm volatile("setmaxnreg.dec.sync.aligned.u32 24;");
    const uint32_t* prog = P.prog[role].p;
    unsigned int* flag = P.g->flag + rank;
    if (wid == 8) {
      Cursor tail{0, 0};
      int head = 0, sh = 0;
      uint32_t cur = 0, used = 0;
      uint64_t fifo = 0;
      uint32_t dst, bar, ev = ev0, done = 0;
      const uint64_t pol = evict_first();
      auto retire = [&]() {
        mbar_wait(empty0 + 8 * tail.bi, tail.ph);
        tail.next();
        used -= (uint32_t)fifo & 31;
        fifo >>= 5;
        sh -= 5;
        asm volatile("st.volatile.shared.u32 [%0], %1;" ::"r"(progress), "r"(++done) : "memory");
      };
      auto acquire = [&](uint32_t bytes) {
        uint32_t fp = bytes >> 12;
        if (cur + fp > (RING >> 12)) { fp += (RING >> 12) - cur; cur = 0; }
        used += fp;
        while (used > (RING >> 12) || sh == 5 * NBAR) retire();
        fifo |= (uint64_t)fp << sh;
        sh += 5;
        dst = sbase + (cur << 12);
        bar = full0 + 8 * head;
        cur += bytes >> 12;
        if (++head == NBAR) head = 0;
      };
      auto gate = [&]() {
        mbar_wait(ev, 0);
        ev += 8;
        asm volatile("fence.proxy.async.global;" ::: "memory");
      };
      for (int pc = 0;; pc++) {
        uint32_t op = prog[pc];
        const int type = op & 3;
        if (type == OP_END) break;
        if (op == OP_O) {
          gate();
          op = __shfl_sync(0xffffffffu, lds32(jobw), 0);
        }
        const int blk = (op >> 10) & 1;
        if (type == OP_Q) {
#pragma unroll 1
          for (int k = 0; k < 10; k++) {
            if (k == 9 && (op & P_GATE)) gate();
            acquire(SZ_Q);
            if ((pc > 0 || k >= EARLY) && elect()) {
              mbar_expect(bar, SZ_Q);
              tma2d(dst, &P.x[blk], bar, 64 * k, ((op >> 7) & 7) * kSq + rank * 128);
              if ((k & 1) == rank) tma3d_mc(dst + 16384, &P.wq[blk], bar, 0, 64 * k, 3 * ((op >> 2) & 31));
            }
          }
        } else if (type == OP_A) {
          const int row0 = ((op >> 2) & 255) * kSk;
          const CUtensorMap* kv_map = rank ? &P.v[blk] : &P.k[blk];
          if (op & F_PARK) {
            gate();
            acquire(SZ_PARK);
            if (elect()) {
              mbar_expect(bar, SZ_PARK);
              bulk_load_hint(dst, &P.g->tile[((op >> 20) * 2 + rank) * 3072], SZ_PARK, bar, pol);
            }
          }
#pragma unroll 1
          for (int t = 0; t < 32; t++) {
            const int isv = t == 31 ? 1 : (t == 0 ? 0 : (~t & 1));
            const int j = isv ? (t - 1) >> 1 : (t + 1) >> 1;
            if (t == 31 && (op & P_GATE)) gate();
            acquire(SZ_KV);
            if (elect()) {
              mbar_expect(bar, SZ_KV);
              if (isv == (int)rank) tma4d_mc_hint(dst, kv_map, bar, row0 / 8 + 8 * j, pol);
            }
          }
        } else {
          const int n = (op >> 13) & 127, nw = (op & P_WIDE) ? n - TAIL : 0;
          const uint4* part = &P.g->part[((((op >> 5) & 60) + ((op >> 20) & 3)) * 2 + rank) * 3072 + 512];
#pragma unroll 1
          for (int i = 0; i < n + (nw ? TAIL : 0); i++) {
            const int k = nw ? (i < n ? i : i - TAIL) : kSteps - n + i, h = (k * 43) >> 7, col = 5 * (((op >> 20) & 3) + (i >= n));
            const uint4* src = &P.g->tile[(P.slot[((op >> 2) & 480) + h] * 2 + rank) * 3072 + (k - 3 * h) * 1024];
            const uint32_t j = (op & P_LD) ? i - n + 5 : 5, bytes = i < nw ? SZ_W : j < 5 ? SZ_OL : SZ_O;
            if ((op & P_PRE) ? i == 0 : j == 0) gate();
            if (i < n && (i == 0 || k == 3 * h)) gate();
            acquire(bytes);
            if (elect()) {
              mbar_expect(bar, bytes);
              tma5d_mc(dst + 16384 + rank * 10240, &P.wo[blk], bar, 8 * k + 4 * rank, col);
              bulk_load_hint(dst, src, 16384, bar, pol);
              if (i < nw) tma5d_mc(dst + SZ_O + rank * 10240, &P.wo[blk], bar, 8 * k + 4 * rank, col + 5);
              if (j < 5) bulk_load_hint(dst + SZ_O, part + j * 512, 8192, bar, pol);
              if ((op & P_PRE) && i < 10) asm volatile("cp.async.bulk.prefetch.L2.global [%0], 4096;" ::"l"(part + i * 256) : "memory");
            }
          }
        }
      }
#pragma unroll 1
      while (sh) retire();
    } else if (threadIdx.x == 288) {
      for (int pc = 0;; pc++) {
        const uint32_t op = prog[pc];
        const int type = op & 3;
        if (type == OP_END) break;
        if (type == OP_Q ? !(op & F_PARK) : type == OP_O && !(op & P_WIDE)) continue;
        const int id = type == OP_A ? (op >> 2) & 511 : type == OP_Q ? N_TILE + ((op >> 13) & 127) : ID_PART + ((op >> 5) & 60) + ((op >> 20) & 3);
        const uint32_t v = type == OP_O ? 1 : P.info[id] & 7;
        mbar_wait_long(odone0 + 8 * pc);
        flag_set(flag + 2 * id, v);
        if (type == OP_O && (op & P_WIDE)) flag_set(flag + 2 * id + 2, v);
      }
    } else if (wid == 10) {
      int i = threadIdx.x & 31;
      uint32_t e = i < 8 ? P.prog[role].ev[i] : 0;
      for (uint32_t n = 0; __any_sync(0xffffffffu, e); n++) {
        uint32_t job = lds32(jobw);
        const int togo = (e & E_DRAW) ? (e & 1023) - lds32(progress) : 99;
        if (togo <= 0 && rank == 0) {
          job = P.job[atomicInc(&P.g->ticket, gridDim.x / 2 - 1)];
          asm volatile("{\n.reg .u32 a;\nmapa.shared::cluster.u32 a, %0, 1;\nst.volatile.shared::cluster.u32 [a], %1;\n"
                       "st.volatile.shared.u32 [%0], %1;\n}\n" ::"r"(jobw), "r"(job) : "memory");
        }
        if ((e & E_JOB) && job) {
          const uint32_t j = e & 63, heads = job == OP_O ? 0 : kH - ((job >> 2) & 31), jp = !(job & P_LD) ? 63 : (job & P_PRE) ? 0 : heads - 1, h = j - (j > jp);
          e = j == jp ? (ID_PART + ((job >> 5) & 60) + ((job >> 20) & 3)) | E_ON | E_LAST : h < heads ? (((job >> 2) & 511) + h) | E_ON | E_LAST : 0;
        }
        unsigned int* f = ptr_add(flag, 8 * (e & 1023));
        const bool ok = (e & E_ON) ? flag_get(f) - 1 < ((e & E_FREE) ? 1 : 7) : (e & E_DRAW) && job;
        if (ok) {
          mbar_arrive(ev0 + 8 * i);
          if (e & (E_FREE | E_LAST)) flag_dec(f);
          i += 8;
          e = i < MAX_EV ? P.prog[role].ev[i] : 0;
        }
        asm volatile("{\n.reg .pred p;\nsetp.ge.u32 p, %0, 0x400000;\n@p trap;\n}\n" ::"r"(n));
        if (!__any_sync(0xffffffffu, ok)) __nanosleep(__any_sync(0xffffffffu, job || togo <= 2) ? 100 : 600);
      }
    } else if (threadIdx.x == 352) {
      uint32_t items = 0;
      auto read = [&](int id) {
        if (!(P.info[id] & I_NEXT)) return;
        wait_word(progress, items);
        flag_dec(flag + 2 * id);
      };
      for (int pc = 0;; pc++) {
        const uint32_t op = prog[pc];
        const int type = op & 3;
        if (type == OP_END) break;
        if (type == OP_O) {
          const uint32_t n = (op >> 13) & 127, base = items;
#pragma unroll 1
          for (uint32_t k = 3, id = (op >> 2) & 511; k <= n; k += 3, id++) {
            items = base + k + (k + TAIL > n ? TAIL : 0);
            read(id);
          }
          items = base + n + TAIL;
        } else if (type == OP_A) {
          if (op & F_PARK) { items++; read(N_TILE + ((op >> 13) & 127)); }
          items += 32;
        } else {
          items += 10;
        }
      }
    }
    __syncwarp();
    asm volatile("barrier.cluster.arrive.relaxed;\nbarrier.cluster.wait;" ::: "memory");
  }
}

typedef CUresult (*EncodeFn)(CUtensorMap*, CUtensorMapDataType, cuuint32_t, void*, const cuuint64_t*, const cuuint64_t*,
                             const cuuint32_t*, const cuuint32_t*, CUtensorMapInterleave, CUtensorMapSwizzle,
                             CUtensorMapL2promotion, CUtensorMapFloatOOBfill);

void encode(EncodeFn fn, CUtensorMap* m, const void* ptr, int rank, const cuuint64_t* dims, const cuuint64_t* strides,
            const cuuint32_t* box, CUtensorMapSwizzle swz) {
  const cuuint32_t es[5] = {1, 1, 1, 1, 1};
  CUresult r = fn(m, CU_TENSOR_MAP_DATA_TYPE_BFLOAT16, rank, const_cast<void*>(ptr), dims, strides, box, es,
                  CU_TENSOR_MAP_INTERLEAVE_NONE, swz, CU_TENSOR_MAP_L2_PROMOTION_L2_128B, CU_TENSOR_MAP_FLOAT_OOB_FILL_NONE);
  if (r != CUDA_SUCCESS) fprintf(stderr, "cuTensorMapEncodeTiled failed: %d\n", (int)r);
}

struct Op { int type, flags, id, n, quarter, park, item0, items; double t0, t1; };
struct Use { double ready, gate, need, freed; int readers, slot, prev; bool next; };
struct PlanStats { double end, slack, park_slack; int slots, parks; uint32_t own[N_CL]; };

bool plan(const char* const* text, int n_pair, int phase, Params& P, PlanStats* stats = nullptr) {
  constexpr double T_Q = 7900, T_A = 24850, T_U = 26300, T_O = 640, T_RUN = 800, T_WIDE = 1900, AHEAD = 3500, PUBLISH = 1500;
  const double margin = 256.0 * ((P.dbg >> 8) & 255);
  static Op op[N_CL][MAX_OPS];
  static Use use[ID_PART];
  int n_op[N_CL], covered[N_TEAM] = {}, finals[N_TEAM] = {};
  auto hex = [](char c) { return c <= '9' ? c - '0' : c - 'a' + 10; };
  for (int i = 0; i < n_pair; i++)
    for (const char* s = text[i]; *s; s++)
      if (*s == 'J') { if (covered[hex(s[1])]) return false; covered[hex(s[1])] = 10 * (s[2] - '0') + s[3] - '0'; }
  for (int c = 0; c < 2 * n_pair; c++) {
    int n = 0, items = 0;
    double t = 0;
    auto add = [&](int type, int flags, int id, int heads, int quarter, int its, double dt) {
      if (n < MAX_OPS) op[c][n] = {type, flags, id, heads, quarter, 0, items, its, t, t + dt};
      n++; items += its; t += dt;
    };
    for (const char* s = text[c >> 1]; *s; s++) {
      const int tm = hex(s[1]) & 15, nj = covered[tm];
      if (*s == 'N') { add(OP_Q, 0, 0, 0, 0, 10, T_Q); add(OP_A, 0, 0, 0, 0, 32, T_A); }
      if (*s == 'P') add(OP_Q, F_PARK, 0, 0, 0, 10, T_Q);
      if (*s == 'U') { if (n == 0 || n > MAX_OPS || op[c][n - 1].type != OP_A) return false; add(OP_A, F_PARK, 0, 0, 0, 33, T_U); }
      if (*s == 'J') { if (nj < TAIL + 3 || nj > kSteps - 11) return false; add(OP_O, P_WIDE, tm * kH, nj, 2 * (c & 1), nj + TAIL, 2 * T_O * nj + T_WIDE); }
      if (*s == 'F') { if (s[2]) return false; add(OP_O, nj ? P_LD : 0, tm * kH + nj / 3, kSteps - nj, finals[tm]++, kSteps - nj, T_O * (kSteps - nj) + T_RUN); }
    }
    if (n && n <= MAX_OPS && (op[c][n - 1].type != OP_O || (op[c][n - 1].flags & P_WIDE))) add(OP_O, 0, 0, 0, 0, 0, 0);
    add(OP_END, 0, 0, 0, 0, 0, 0);
    if (n > MAX_OPS || op[c][0].type != OP_Q) return false;
    n_op[c] = n - 1;
  }
  for (int t = 0; t < N_TEAM; t++) if (finals[t] != 4) return false;
  for (int i = 0; i < ID_PART; i++) use[i] = {0, 0, 1e18, 0, 0, 0, 0, false};
  struct Ref { double t; Op* o; int id; };
  static Ref att[N_TILE + 1], dem[N_TILE], prk[MAX_PARK + 1], unp[MAX_PARK + 1], wr[ID_PART];
  int n_att = 0, n_prk = 0, n_unp = 0;
  auto ready = [&](const Op* o) {
    const int nt = o[1].type;
    return o->t1 + (nt == OP_Q ? 6100 : o[1].n ? 3900 : 1500) + PUBLISH;
  };
  for (int c = 0; c < 2 * n_pair; c++)
    for (Op* o = op[c]; o->type != OP_END; o++) {
      if (o->type == OP_A) { att[n_att] = {ready(o), o, 0}; if (++n_att > N_TILE) return false; }
      if (o->type == OP_A && o->flags) { unp[n_unp] = {o->t0 - AHEAD, o, 0}; if (++n_unp > MAX_PARK) return false; }
      if (o->type == OP_Q && o->flags) { prk[n_prk] = {ready(o), o, 0}; if (++n_prk > MAX_PARK) return false; }
      for (int i = 0; o->type == OP_O && i < o->n; i++) {
        const int nw = (o->flags & P_WIDE) ? o->n - TAIL : 0, k = nw ? i : kSteps - o->n + i;
        Use& u = use[o->id / kH * kH + k / 3];
        const double t = o->t0 + T_O * (i + (i < nw ? i : nw));
        if (t - AHEAD < u.need) u.need = t - AHEAD;
        const double f = i < nw || (nw && o[1].type != OP_O) ? t + T_O * (i < nw ? 2 : 1 + TAIL) + PUBLISH : 1e18;
        if (f > u.freed) u.freed = f;
        if (i == 0 || k % 3 == 0) u.readers++;
      }
    }
  if (n_att != N_TILE || n_prk != n_unp) return false;
  auto sort = [](Ref* r, int n) {
    for (int i = 1; i < n; i++)
      for (int j = i; j > 0 && r[j].t < r[j - 1].t; j--) { Ref x = r[j]; r[j] = r[j - 1]; r[j - 1] = x; }
  };
  for (int i = 0; i < N_TILE; i++) { const int id = (i & 15) * kH + (i >> 4); dem[i] = {use[id].need, nullptr, id}; }
  sort(att, n_att); sort(dem, N_TILE); sort(prk, n_prk); sort(unp, n_unp);
  PlanStats st = {0, 1e18, 1e18, 0, n_prk};
  int n_wr = 0;
  for (int i = 0; i < N_TILE; i++) {
    Op* o = att[i].o;
    o->id = dem[i].id;
    if (!o->flags) o[-1].id = o->id;
    if (dem[i].t - att[i].t < st.slack) st.slack = dem[i].t - att[i].t;
    wr[n_wr++] = {o->t1 - 2 * AHEAD, o, o->id};
  }
  for (int i = 0; i < n_prk; i++) {
    prk[i].o->id = unp[i].o->id;
    prk[i].o->park = unp[i].o->park = i;
    use[N_TILE + i].freed = unp[i].o->t0 + 2 * PUBLISH;
    use[N_TILE + i].readers = 1;
    if (unp[i].t - prk[i].t < st.park_slack) st.park_slack = unp[i].t - prk[i].t;
    wr[n_wr++] = {prk[i].o->t1 - 2 * AHEAD, prk[i].o, N_TILE + i};
  }
  for (int c = 0; c < 2 * n_pair; c++)
    for (int d = 0; d < 2 * n_pair; d++)
      for (Op *f = &op[c][n_op[c] - 1], *o = op[d]; f->n && o->type != OP_END; o++)
        if (o->type == OP_O && (o->flags & P_WIDE) && o->id / kH == f->id / kH) {
          if (f->t0 - o->t1 > 4096.0 * ((P.dbg >> 16) & 255)) f->flags |= P_PRE;
          const double slack = f->t0 + ((f->flags & P_PRE) ? 0 : (f->n - 5) * T_O) - AHEAD - ready(o);
          if (slack < st.park_slack) st.park_slack = slack;
        }
  sort(wr, n_wr);
  int holder[N_TILE];
  for (int i = 0; i < n_wr; i++) {
    int best = -1;
    for (int sl = 0; sl < st.slots; sl++)
      if (use[holder[sl]].freed + margin <= wr[i].t && (best < 0 || use[holder[sl]].freed < use[holder[best]].freed)) best = sl;
    Use& u = use[wr[i].id];
    if (best >= 0) { u.prev = holder[best]; use[u.prev].next = true; wr[i].o->flags |= P_GATE; }
    else if (st.slots == N_TILE) return false;
    else best = st.slots++;
    u.slot = best;
    holder[best] = wr[i].id;
  }
  {
    int pos[N_CL] = {}, flag[ID_PART + 4 * N_TEAM] = {}, seen[ID_PART] = {};
    auto goal = [&](int c) { return op[c][n_op[c] - 1].item0; };
    for (bool moved = true; moved;) {
      moved = false;
      for (int c = 0; c < 2 * n_pair; c++) {
        for (; pos[c] < goal(c); pos[c]++, moved = true) {
          bool ok = true;
          for (const Op* o = op[c]; o->type != OP_END; o++) {
            const int k = pos[c] - o->item0, own = o->type == OP_A ? o->id : N_TILE + o->park;
            if (k < 0 || k >= o->items) continue;
            if (o->type == OP_O) ok = k >= o->n || flag[o->id + k / 3];
            else if (k == o->items - 1 && (o->flags & P_GATE)) ok = seen[use[own].prev] == use[use[own].prev].readers;
            else if (k == 0 && o->type == OP_A && (o->flags & F_PARK)) ok = flag[N_TILE + o->park];
          }
          if (!ok) break;
          for (const Op* o = op[c]; o->type != OP_END; o++) {
            if (pos[c] == o->item0 + o->items + (o[1].type == OP_Q ? 7 : o[1].item0 == goal(c) ? -1 : 5)) {
              if (o->type == OP_A) flag[o->id] = 1;
              if (o->type == OP_Q && (o->flags & F_PARK)) flag[N_TILE + o->park] = 1;
              if (o->type == OP_O) flag[ID_PART + o->id / kH * 4 + o->quarter] = flag[ID_PART + o->id / kH * 4 + o->quarter + 1] = 1;
            }
            const int k = pos[c] - NBAR - o->item0, nw = o->n - TAIL;
            if (k == 0 && o->type == OP_A && (o->flags & F_PARK)) seen[N_TILE + o->park]++;
            if (o->type == OP_O && k >= 0 && k < o->items && k % 3 == 2 && (k < nw || k >= o->n)) seen[o->id + (k < nw ? k : k - TAIL) / 3]++;
          }
        }
      }
    }
    for (int c = 0; c < 2 * n_pair; c++) if (pos[c] < goal(c)) return false;
  }
  int n_job = 0, longest = 0;
  for (int t = 0; t < N_TEAM; t++) if (kH - covered[t] / 3 > longest) longest = kH - covered[t] / 3;
  for (int c = 0; c < 2 * n_pair; c++) {
    uint32_t items = 0, cur = 0, pend = 0;
    int n = 0, ev = 0;
    auto item = [&](uint32_t bytes, int count) {
      for (int i = 0; i < count; i++) { if (cur + bytes > RING) cur = 0; cur += bytes; items++; }
    };
    auto event = [&](uint32_t e) { if (ev < MAX_EV) P.prog[c].ev[ev] = e; ev++; };
    for (const Op* o = op[c];; o++) {
      if (o->type != OP_END && phase && (o->type == OP_O) != (phase == 2)) continue;
      uint32_t cw = o->type | (items % NBAR) << 15 | ((items / NBAR) & 1) << 19 | (cur >> 12) << 20 | pend, pw = o->type | o->id << 2 | o->flags;
      const int ps = use[N_TILE + o->park].slot;
      pend = 0;
      if (o->type == OP_O) {
        pw |= o->n << 13 | o->quarter << 20;
        if (o->flags & P_WIDE) {
          cw |= o->n << 2 | (o->id / kH * 4 + o->quarter + 1) << 9 | C_WIDE;
          item(SZ_W, o->n - TAIL);
          item(SZ_O, 2 * TAIL);
          pend = C_PEND;
          for (int i = 0; 3 * i < o->n; i++) event((o->id + i) | E_ON | (use[o->id + i].next ? 0 : E_LAST));
        } else {
          dem[n_job++] = {o->t0 - 1e6 * o->n, nullptr, (int)pw};
          st.own[c] = pw;
          pw = OP_O;
          event(E_DRAW | (items < 16 ? 0 : items - 16));
          for (int i = 0; i <= longest; i++) event(E_JOB | i);
        }
      } else if (o->type != OP_END) {
        const bool parks = o->type == OP_Q && (o->flags & F_PARK);
        cw |= (parks ? ps : use[o->id].slot) << 2 | (o->flags & F_PARK);
        if (o->flags & F_PARK) pw |= o->park << 13 | ps << 20;
        if (o->type == OP_Q) item(SZ_Q, 10);
        else { if (o->flags & F_PARK) { item(SZ_PARK, 1); event((N_TILE + o->park) | E_ON | (use[N_TILE + o->park].next ? 0 : E_LAST)); } item(SZ_KV, 32); }
        if (parks || o->type == OP_A) pend = C_PEND;
        if (o->flags & P_GATE) event(use[parks ? N_TILE + o->park : o->id].prev | E_ON | E_FREE);
      }
      P.prog[c].c[n] = cw; P.prog[c].p[n++] = pw;
      if (o->type == OP_END) { if (o->t0 > st.end) st.end = o->t0; break; }
    }
    if (ev > MAX_EV) return false;
    while (ev < MAX_EV) P.prog[c].ev[ev++] = 0;
    while (n < MAX_OPS) { P.prog[c].c[n] = OP_END; P.prog[c].p[n++] = OP_END; }
    P.first[c] = (uint16_t)(P.prog[c].p[0] & 2047);
  }
  sort(dem, n_job);
  for (int i = 0; i < n_job; i++) P.job[i] = dem[i].id;
  for (int i = 0; i < ID_PART; i++) {
    if (i < N_TILE) P.slot[i] = use[i].slot;
    P.info[i] = (use[i].readers + use[i].next) | (use[i].next ? I_NEXT : 0);
  }
  if (stats) *stats = st;
  return true;
}

const char* const kPrograms[N_CL / 2] = {
  "NNNNNNNNNF4", "NNNNNNNNNF0", "NNNNJf44NNNF7", "PNNNNNNNNNF8", "PNJ664NNNNNF5", "NNNNNNNNNFe",
  "NUNNNNNNNF5", "NNNNNNNNNF6", "NNNNNNNNNFe", "NUNNNJa78NFb", "PNJ281NNNNFc", "PPNJ551NNNNUNF2",
  "NNNNNJc39NNUF2", "NNJ379NNNNF9", "NUNUNJ974NFc", "PNUNNNNNNNF6", "PNJ062NNNNNFd", "NUNNNJd45NNFd",
  "PNNNNNNNNNF8", "NNUJ460Jb60NFf", "NNNNNNNNNFb", "PNJ751NNNNNNF3", "NNNNNNNNNF4", "PNJ172NNNNN",
  "PNNNNNNNNNFa", "NUNNNJe63NNF3", "PNNNNNNNNNF9", "NNNNNNNNNF0", "PNNNNNNNNNFa", "PPNUNNNNNNUF1",
  "NNUNNNNNNF7", "NNNNNJ878NF1", "NUNUNNNNNFf",
};

const char* const* bench_programs() {
  return kPrograms;
}

}

extern "C" void kernel_launch(void* const* d_in, const int* in_sizes, int n_in, void* d_out, int out_size) {
  (void)in_sizes; (void)n_in; (void)out_size;
  static EncodeFn fn = nullptr;
  static int n_clusters = 0;
  if (!fn) {
    cudaDriverEntryPointQueryResult qr;
    void* f = nullptr;
    cudaGetDriverEntryPoint("cuTensorMapEncodeTiled", &f, cudaEnableDefault, &qr);
    fn = (EncodeFn)f;
    cudaFuncSetAttribute(fused_kernel, cudaFuncAttributeMaxDynamicSharedMemorySize, SMEM_BYTES);
    cudaLaunchConfig_t cfg = {};
    cfg.gridDim = dim3(132); cfg.blockDim = dim3(384); cfg.dynamicSmemBytes = SMEM_BYTES;
    cudaLaunchAttribute at[1];
    at[0].id = cudaLaunchAttributeClusterDimension; at[0].val.clusterDim.x = 2; at[0].val.clusterDim.y = 1; at[0].val.clusterDim.z = 1;
    cfg.attrs = at; cfg.numAttrs = 1;
    if (cudaOccupancyMaxActiveClusters(&n_clusters, fused_kernel, &cfg) != cudaSuccess || n_clusters < 1) n_clusters = 1;
    (void)cudaGetLastError();
  }
  static Params P;
  const CUtensorMapSwizzle S128 = CU_TENSOR_MAP_SWIZZLE_128B, S64 = CU_TENSOR_MAP_SWIZZLE_64B;
  for (int blk = 0; blk < 2; blk++) {
    void* const* in = d_in + 5 * blk;
    { const cuuint64_t d[] = {kD, kB * kSq}, s[] = {kD * 2}; const cuuint32_t b[] = {64, 128};
      encode(fn, &P.x[blk], in[0], 2, d, s, b, S128); }
    { const cuuint64_t d[] = {64, 8, 3, (cuuint64_t)kB * kH * kSk / 8}, s[] = {kDh * 2, 128, 8 * kDh * 2}; const cuuint32_t b[] = {64, 8, 3, 8};
      encode(fn, &P.k[blk], in[1], 4, d, s, b, S128);
      encode(fn, &P.v[blk], in[2], 4, d, s, b, S128); }
    { const cuuint64_t d[] = {64, kD, kHD / 64}, s[] = {kHD * 2, 128}; const cuuint32_t b[] = {64, 64, 3};
      encode(fn, &P.wq[blk], in[3], 3, d, s, b, S128); }
    { const cuuint64_t d[] = {32, 2, kHD / 8, 4, kD / 32}, s[] = {kD * 2, 8 * kD * 2, 2 * kD * 2, 64}; const cuuint32_t b[] = {32, 2, 4, 4, 5};
      encode(fn, &P.wo[blk], in[4], 5, d, s, b, S64); }
  }
  { const cuuint64_t d[] = {32, kB * kSq, 2 * kD / 32}, s[] = {2 * kD * 2, 64}; const cuuint32_t b[] = {32, 16, 1};
    encode(fn, &P.out, d_out, 3, d, s, b, S64); }

  P.xw[0] = (const char*)d_in[0]; P.xw[1] = (const char*)d_in[3];
  cudaGetSymbolAddress((void**)&P.g, g_scratch);
  P.dbg = DBG_DEFAULT;
  if (n_clusters >= N_CL && plan(bench_programs(), N_CL / 2, 0, P)) {
    fused_kernel<<<2 * N_CL, 384, SMEM_BYTES>>>(P);
  } else {
    char buf[2 * N_TEAM][16];
    const char* text[2 * N_TEAM];
    for (int i = 0; i < 2 * N_TEAM; i++) { snprintf(buf[i], sizeof(buf[i]), "NNNNNNNNF%x", i / 2); text[i] = buf[i]; }
    for (int phase = 1; phase <= 2; phase++) {
      plan(text, 2 * N_TEAM, phase, P);
      fused_kernel<<<8 * N_TEAM, 384, SMEM_BYTES>>>(P);
    }
  }
}
```

```cpp
#include <cuda_runtime.h>
#include <cuda_bf16.h>
#include <cuda.h>
#include <stdint.h>
#include <stdio.h>

namespace {

constexpr int kB = 8, kSq = 256, kD = 640, kH = 32, kSk = 1024, kDh = 192;
constexpr int kHD = kH * kDh;
constexpr uint32_t RING = 224 * 1024;
constexpr uint32_t SZ_KV = 24576;
constexpr uint32_t SZ_Q = 16384 + 24576;
constexpr uint32_t SZ_O = 16384 + 20480;
constexpr uint32_t SZ_W = 16384 + 40960;
constexpr uint32_t SZ_PARK = 49152;
constexpr uint32_t SZ_OL = SZ_O + 8192;
constexpr int NBAR = 10;
constexpr int EARLY = 3;
constexpr int kSteps = kHD / 64;
constexpr int TAIL = 6;
constexpr uint32_t KV_CH = 64, KV_SBO = 3072;
constexpr int SMEM_BYTES = RING + 1024 + 1024;
constexpr int N_TEAM = 16, N_CL = 66, MAX_OPS = 24, MAX_EV = 80, N_TILE = N_TEAM * kH, MAX_PARK = 128, ID_PART = N_TILE + MAX_PARK;
enum : uint32_t { OP_END = 0, OP_Q = 1, OP_A = 2, OP_O = 3, F_PARK = 1 << 11,
                  C_WIDE = 1 << 27, C_PEND = 1 << 26, P_GATE = 1 << 12, P_WIDE = 1 << 11, P_LD = 1 << 12, P_PRE = 1 << 22,
                  I_NEXT = 8, E_ON = 1 << 15, E_FREE = 1 << 14, E_LAST = 1 << 13, E_DRAW = 1 << 12, E_JOB = 1 << 11 };

constexpr uint32_t DBG_DEFAULT = 0x040800;

struct alignas(1024) Scratch {
  unsigned int flag[2047];
  unsigned int ticket;
  uint4 part[N_TEAM * 4 * 2 * 3072];
  uint4 tile[N_TILE * 2 * 3072];
};

struct alignas(64) Params {
  const char* xw[2];
  uint16_t first[80];
  Scratch* g;
  uint32_t dbg;
  CUtensorMap x[2], wq[2], k[2], v[2], wo[2], out;
  struct {
    uint32_t c[MAX_OPS];
    uint32_t p[MAX_OPS];
    uint16_t ev[MAX_EV];
  } prog[N_CL];
  uint32_t job[N_CL];
  uint16_t slot[N_TILE];
  uint8_t info[ID_PART];
};

__device__ Scratch g_scratch;

template <int TB, int TA = 0>
__device__ __forceinline__ void wgmma_ss_n64(float (&d)[32], uint64_t da, uint64_t db, int scale_d) {
  asm volatile("{\n.reg .pred p;\nsetp.ne.b32 p, %34, 0;\n"
    "wgmma.mma_async.sync.aligned.m64n64k16.f32.bf16.bf16 {%0, %1, %2, %3, %4, %5, %6, %7, %8, %9, %10, %11, %12, %13, %14, %15, %16, %17, %18, %19, %20, %21, %22, %23, %24, %25, %26, %27, %28, %29, %30, %31}, %32, %33, p, 1, 1, %35, %36;\n}\n"
    : "+f"(d[0]), "+f"(d[1]), "+f"(d[2]), "+f"(d[3]), "+f"(d[4]), "+f"(d[5]), "+f"(d[6]), "+f"(d[7]), "+f"(d[8]), "+f"(d[9]), "+f"(d[10]), "+f"(d[11]), "+f"(d[12]), "+f"(d[13]), "+f"(d[14]), "+f"(d[15]), "+f"(d[16]), "+f"(d[17]), "+f"(d[18]), "+f"(d[19]), "+f"(d[20]), "+f"(d[21]), "+f"(d[22]), "+f"(d[23]), "+f"(d[24]), "+f"(d[25]), "+f"(d[26]), "+f"(d[27]), "+f"(d[28]), "+f"(d[29]), "+f"(d[30]), "+f"(d[31])
    : "l"(da), "l"(db), "r"(scale_d), "n"(TA), "n"(TB));
}
template <int TB>
__device__ __forceinline__ void wgmma_rs_n64(float (&d)[32], uint32_t a0, uint32_t a1, uint32_t a2, uint32_t a3, uint64_t db, int scale_d) {
  asm volatile("{\n.reg .pred p;\nsetp.ne.b32 p, %37, 0;\n"
    "wgmma.mma_async.sync.aligned.m64n64k16.f32.bf16.bf16 {%0, %1, %2, %3, %4, %5, %6, %7, %8, %9, %10, %11, %12, %13, %14, %15, %16, %17, %18, %19, %20, %21, %22, %23, %24, %25, %26, %27, %28, %29, %30, %31}, {%32, %33, %34, %35}, %36, p, 1, 1, %38;\n}\n"
    : "+f"(d[0]), "+f"(d[1]), "+f"(d[2]), "+f"(d[3]), "+f"(d[4]), "+f"(d[5]), "+f"(d[6]), "+f"(d[7]), "+f"(d[8]), "+f"(d[9]), "+f"(d[10]), "+f"(d[11]), "+f"(d[12]), "+f"(d[13]), "+f"(d[14]), "+f"(d[15]), "+f"(d[16]), "+f"(d[17]), "+f"(d[18]), "+f"(d[19]), "+f"(d[20]), "+f"(d[21]), "+f"(d[22]), "+f"(d[23]), "+f"(d[24]), "+f"(d[25]), "+f"(d[26]), "+f"(d[27]), "+f"(d[28]), "+f"(d[29]), "+f"(d[30]), "+f"(d[31])
    : "r"(a0), "r"(a1), "r"(a2), "r"(a3), "l"(db), "r"(scale_d), "n"(TB));
}
template <int TB, int TA = 0>
__device__ __forceinline__ void wgmma_ss_n160(float (&d)[80], uint64_t da, uint64_t db, int scale_d) {
  asm volatile("{\n.reg .pred p;\nsetp.ne.b32 p, %82, 0;\n"
    "wgmma.mma_async.sync.aligned.m64n160k16.f32.bf16.bf16 {%0, %1, %2, %3, %4, %5, %6, %7, %8, %9, %10, %11, %12, %13, %14, %15, %16, %17, %18, %19, %20, %21, %22, %23, %24, %25, %26, %27, %28, %29, %30, %31, %32, %33, %34, %35, %36, %37, %38, %39, %40, %41, %42, %43, %44, %45, %46, %47, %48, %49, %50, %51, %52, %53, %54, %55, %56, %57, %58, %59, %60, %61, %62, %63, %64, %65, %66, %67, %68, %69, %70, %71, %72, %73, %74, %75, %76, %77, %78, %79}, %80, %81, p, 1, 1, %83, %84;\n}\n"
    : "+f"(d[0]), "+f"(d[1]), "+f"(d[2]), "+f"(d[3]), "+f"(d[4]), "+f"(d[5]), "+f"(d[6]), "+f"(d[7]), "+f"(d[8]), "+f"(d[9]), "+f"(d[10]), "+f"(d[11]), "+f"(d[12]), "+f"(d[13]), "+f"(d[14]), "+f"(d[15]), "+f"(d[16]), "+f"(d[17]), "+f"(d[18]), "+f"(d[19]), "+f"(d[20]), "+f"(d[21]), "+f"(d[22]), "+f"(d[23]), "+f"(d[24]), "+f"(d[25]), "+f"(d[26]), "+f"(d[27]), "+f"(d[28]), "+f"(d[29]), "+f"(d[30]), "+f"(d[31]), "+f"(d[32]), "+f"(d[33]), "+f"(d[34]), "+f"(d[35]), "+f"(d[36]), "+f"(d[37]), "+f"(d[38]), "+f"(d[39]), "+f"(d[40]), "+f"(d[41]), "+f"(d[42]), "+f"(d[43]), "+f"(d[44]), "+f"(d[45]), "+f"(d[46]), "+f"(d[47]), "+f"(d[48]), "+f"(d[49]), "+f"(d[50]), "+f"(d[51]), "+f"(d[52]), "+f"(d[53]), "+f"(d[54]), "+f"(d[55]), "+f"(d[56]), "+f"(d[57]), "+f"(d[58]), "+f"(d[59]), "+f"(d[60]), "+f"(d[61]), "+f"(d[62]), "+f"(d[63]), "+f"(d[64]), "+f"(d[65]), "+f"(d[66]), "+f"(d[67]), "+f"(d[68]), "+f"(d[69]), "+f"(d[70]), "+f"(d[71]), "+f"(d[72]), "+f"(d[73]), "+f"(d[74]), "+f"(d[75]), "+f"(d[76]), "+f"(d[77]), "+f"(d[78]), "+f"(d[79])
    : "l"(da), "l"(db), "r"(scale_d), "n"(TA), "n"(TB));
}
template <int TB>
__device__ __forceinline__ void wgmma_rs_n160(float (&d)[80], uint32_t a0, uint32_t a1, uint32_t a2, uint32_t a3, uint64_t db, int scale_d) {
  asm volatile("{\n.reg .pred p;\nsetp.ne.b32 p, %85, 0;\n"
    "wgmma.mma_async.sync.aligned.m64n160k16.f32.bf16.bf16 {%0, %1, %2, %3, %4, %5, %6, %7, %8, %9, %10, %11, %12, %13, %14, %15, %16, %17, %18, %19, %20, %21, %22, %23, %24, %25, %26, %27, %28, %29, %30, %31, %32, %33, %34, %35, %36, %37, %38, %39, %40, %41, %42, %43, %44, %45, %46, %47, %48, %49, %50, %51, %52, %53, %54, %55, %56, %57, %58, %59, %60, %61, %62, %63, %64, %65, %66, %67, %68, %69, %70, %71, %72, %73, %74, %75, %76, %77, %78, %79}, {%80, %81, %82, %83}, %84, p, 1, 1, %86;\n}\n"
    : "+f"(d[0]), "+f"(d[1]), "+f"(d[2]), "+f"(d[3]), "+f"(d[4]), "+f"(d[5]), "+f"(d[6]), "+f"(d[7]), "+f"(d[8]), "+f"(d[9]), "+f"(d[10]), "+f"(d[11]), "+f"(d[12]), "+f"(d[13]), "+f"(d[14]), "+f"(d[15]), "+f"(d[16]), "+f"(d[17]), "+f"(d[18]), "+f"(d[19]), "+f"(d[20]), "+f"(d[21]), "+f"(d[22]), "+f"(d[23]), "+f"(d[24]), "+f"(d[25]), "+f"(d[26]), "+f"(d[27]), "+f"(d[28]), "+f"(d[29]), "+f"(d[30]), "+f"(d[31]), "+f"(d[32]), "+f"(d[33]), "+f"(d[34]), "+f"(d[35]), "+f"(d[36]), "+f"(d[37]), "+f"(d[38]), "+f"(d[39]), "+f"(d[40]), "+f"(d[41]), "+f"(d[42]), "+f"(d[43]), "+f"(d[44]), "+f"(d[45]), "+f"(d[46]), "+f"(d[47]), "+f"(d[48]), "+f"(d[49]), "+f"(d[50]), "+f"(d[51]), "+f"(d[52]), "+f"(d[53]), "+f"(d[54]), "+f"(d[55]), "+f"(d[56]), "+f"(d[57]), "+f"(d[58]), "+f"(d[59]), "+f"(d[60]), "+f"(d[61]), "+f"(d[62]), "+f"(d[63]), "+f"(d[64]), "+f"(d[65]), "+f"(d[66]), "+f"(d[67]), "+f"(d[68]), "+f"(d[69]), "+f"(d[70]), "+f"(d[71]), "+f"(d[72]), "+f"(d[73]), "+f"(d[74]), "+f"(d[75]), "+f"(d[76]), "+f"(d[77]), "+f"(d[78]), "+f"(d[79])
    : "r"(a0), "r"(a1), "r"(a2), "r"(a3), "l"(db), "r"(scale_d), "n"(TB));
}
template <int TB, int TA = 0>
__device__ __forceinline__ void wgmma_ss_n192(float (&d)[96], uint64_t da, uint64_t db, int scale_d) {
  asm volatile("{\n.reg .pred p;\nsetp.ne.b32 p, %98, 0;\n"
    "wgmma.mma_async.sync.aligned.m64n192k16.f32.bf16.bf16 {%0, %1, %2, %3, %4, %5, %6, %7, %8, %9, %10, %11, %12, %13, %14, %15, %16, %17, %18, %19, %20, %21, %22, %23, %24, %25, %26, %27, %28, %29, %30, %31, %32, %33, %34, %35, %36, %37, %38, %39, %40, %41, %42, %43, %44, %45, %46, %47, %48, %49, %50, %51, %52, %53, %54, %55, %56, %57, %58, %59, %60, %61, %62, %63, %64, %65, %66, %67, %68, %69, %70, %71, %72, %73, %74, %75, %76, %77, %78, %79, %80, %81, %82, %83, %84, %85, %86, %87, %88, %89, %90, %91, %92, %93, %94, %95}, %96, %97, p, 1, 1, %99, %100;\n}\n"
    : "+f"(d[0]), "+f"(d[1]), "+f"(d[2]), "+f"(d[3]), "+f"(d[4]), "+f"(d[5]), "+f"(d[6]), "+f"(d[7]), "+f"(d[8]), "+f"(d[9]), "+f"(d[10]), "+f"(d[11]), "+f"(d[12]), "+f"(d[13]), "+f"(d[14]), "+f"(d[15]), "+f"(d[16]), "+f"(d[17]), "+f"(d[18]), "+f"(d[19]), "+f"(d[20]), "+f"(d[21]), "+f"(d[22]), "+f"(d[23]), "+f"(d[24]), "+f"(d[25]), "+f"(d[26]), "+f"(d[27]), "+f"(d[28]), "+f"(d[29]), "+f"(d[30]), "+f"(d[31]), "+f"(d[32]), "+f"(d[33]), "+f"(d[34]), "+f"(d[35]), "+f"(d[36]), "+f"(d[37]), "+f"(d[38]), "+f"(d[39]), "+f"(d[40]), "+f"(d[41]), "+f"(d[42]), "+f"(d[43]), "+f"(d[44]), "+f"(d[45]), "+f"(d[46]), "+f"(d[47]), "+f"(d[48]), "+f"(d[49]), "+f"(d[50]), "+f"(d[51]), "+f"(d[52]), "+f"(d[53]), "+f"(d[54]), "+f"(d[55]), "+f"(d[56]), "+f"(d[57]), "+f"(d[58]), "+f"(d[59]), "+f"(d[60]), "+f"(d[61]), "+f"(d[62]), "+f"(d[63]), "+f"(d[64]), "+f"(d[65]), "+f"(d[66]), "+f"(d[67]), "+f"(d[68]), "+f"(d[69]), "+f"(d[70]), "+f"(d[71]), "+f"(d[72]), "+f"(d[73]), "+f"(d[74]), "+f"(d[75]), "+f"(d[76]), "+f"(d[77]), "+f"(d[78]), "+f"(d[79]), "+f"(d[80]), "+f"(d[81]), "+f"(d[82]), "+f"(d[83]), "+f"(d[84]), "+f"(d[85]), "+f"(d[86]), "+f"(d[87]), "+f"(d[88]), "+f"(d[89]), "+f"(d[90]), "+f"(d[91]), "+f"(d[92]), "+f"(d[93]), "+f"(d[94]), "+f"(d[95])
    : "l"(da), "l"(db), "r"(scale_d), "n"(TA), "n"(TB));
}
template <int TB>
__device__ __forceinline__ void wgmma_rs_n192(float (&d)[96], uint32_t a0, uint32_t a1, uint32_t a2, uint32_t a3, uint64_t db, int scale_d) {
  asm volatile("{\n.reg .pred p;\nsetp.ne.b32 p, %101, 0;\n"
    "wgmma.mma_async.sync.aligned.m64n192k16.f32.bf16.bf16 {%0, %1, %2, %3, %4, %5, %6, %7, %8, %9, %10, %11, %12, %13, %14, %15, %16, %17, %18, %19, %20, %21, %22, %23, %24, %25, %26, %27, %28, %29, %30, %31, %32, %33, %34, %35, %36, %37, %38, %39, %40, %41, %42, %43, %44, %45, %46, %47, %48, %49, %50, %51, %52, %53, %54, %55, %56, %57, %58, %59, %60, %61, %62, %63, %64, %65, %66, %67, %68, %69, %70, %71, %72, %73, %74, %75, %76, %77, %78, %79, %80, %81, %82, %83, %84, %85, %86, %87, %88, %89, %90, %91, %92, %93, %94, %95}, {%96, %97, %98, %99}, %100, p, 1, 1, %102;\n}\n"
    : "+f"(d[0]), "+f"(d[1]), "+f"(d[2]), "+f"(d[3]), "+f"(d[4]), "+f"(d[5]), "+f"(d[6]), "+f"(d[7]), "+f"(d[8]), "+f"(d[9]), "+f"(d[10]), "+f"(d[11]), "+f"(d[12]), "+f"(d[13]), "+f"(d[14]), "+f"(d[15]), "+f"(d[16]), "+f"(d[17]), "+f"(d[18]), "+f"(d[19]), "+f"(d[20]), "+f"(d[21]), "+f"(d[22]), "+f"(d[23]), "+f"(d[24]), "+f"(d[25]), "+f"(d[26]), "+f"(d[27]), "+f"(d[28]), "+f"(d[29]), "+f"(d[30]), "+f"(d[31]), "+f"(d[32]), "+f"(d[33]), "+f"(d[34]), "+f"(d[35]), "+f"(d[36]), "+f"(d[37]), "+f"(d[38]), "+f"(d[39]), "+f"(d[40]), "+f"(d[41]), "+f"(d[42]), "+f"(d[43]), "+f"(d[44]), "+f"(d[45]), "+f"(d[46]), "+f"(d[47]), "+f"(d[48]), "+f"(d[49]), "+f"(d[50]), "+f"(d[51]), "+f"(d[52]), "+f"(d[53]), "+f"(d[54]), "+f"(d[55]), "+f"(d[56]), "+f"(d[57]), "+f"(d[58]), "+f"(d[59]), "+f"(d[60]), "+f"(d[61]), "+f"(d[62]), "+f"(d[63]), "+f"(d[64]), "+f"(d[65]), "+f"(d[66]), "+f"(d[67]), "+f"(d[68]), "+f"(d[69]), "+f"(d[70]), "+f"(d[71]), "+f"(d[72]), "+f"(d[73]), "+f"(d[74]), "+f"(d[75]), "+f"(d[76]), "+f"(d[77]), "+f"(d[78]), "+f"(d[79]), "+f"(d[80]), "+f"(d[81]), "+f"(d[82]), "+f"(d[83]), "+f"(d[84]), "+f"(d[85]), "+f"(d[86]), "+f"(d[87]), "+f"(d[88]), "+f"(d[89]), "+f"(d[90]), "+f"(d[91]), "+f"(d[92]), "+f"(d[93]), "+f"(d[94]), "+f"(d[95])
    : "r"(a0), "r"(a1), "r"(a2), "r"(a3), "l"(db), "r"(scale_d), "n"(TB));
}

__device__ __forceinline__ uint32_t smem_u32(const void* p) { return (uint32_t)__cvta_generic_to_shared(p); }
__device__ __forceinline__ void wg_fence() { asm volatile("wgmma.fence.sync.aligned;" ::: "memory"); }
__device__ __forceinline__ void wg_commit() { asm volatile("wgmma.commit_group.sync.aligned;" ::: "memory"); }
template <int N> __device__ __forceinline__ void wg_wait() { asm volatile("wgmma.wait_group.sync.aligned %0;" ::"n"(N) : "memory"); }
__device__ __forceinline__ void sched_fence(uint32_t& keep, bool never) {
  asm volatile("{\n.reg .pred p;\nsetp.ne.b32 p, %1, 0;\n@p mov.u32 %0, %%clock;\n}\n" : "+r"(keep) : "r"((int)never) : "memory");
}
template <int N> __device__ __forceinline__ void fence_regs(float (&r)[N]) {
#pragma unroll
  for (int i = 0; i < N; i++) asm volatile("" : "+f"(r[i])::"memory");
}
template <int N> __device__ __forceinline__ void undefine(float (&r)[N]) {
#pragma unroll
  for (int i = 0; i < N; i++) asm volatile("" : "=f"(r[i]));
}
template <int N> __device__ __forceinline__ void fence_regs(uint32_t (&r)[N]) {
#pragma unroll
  for (int i = 0; i < N; i++) asm volatile("" : "+r"(r[i])::"memory");
}
__device__ __forceinline__ uint64_t mk_desc(uint32_t a16, uint32_t lbo, uint32_t sbo, uint32_t swz) {
  uint64_t d;
  asm("mov.b64 %0, {%1, %2};" : "=l"(d) : "r"(a16 + ((lbo >> 4) << 16)), "r"((sbo >> 4) | (swz << 30)));
  return d;
}
__device__ __forceinline__ void mbar_init(uint32_t bar, uint32_t cnt) {
  asm volatile("mbarrier.init.shared::cta.b64 [%0], %1;" ::"r"(bar), "r"(cnt) : "memory");
}
__device__ __forceinline__ void mbar_expect(uint32_t bar, uint32_t tx) {
  asm volatile("mbarrier.arrive.expect_tx.shared::cta.b64 _, [%0], %1;" ::"r"(bar), "r"(tx) : "memory");
}
__device__ __forceinline__ bool mbar_test(uint32_t bar, uint32_t ph) {
  uint32_t ok;
  asm volatile("{\n.reg .pred p;\nmbarrier.test_wait.parity.shared::cta.b64 p, [%1], %2;\nselp.u32 %0, 1, 0, p;\n}\n"
               : "=r"(ok) : "r"(bar), "r"(ph) : "memory");
  return ok;
}
__device__ __forceinline__ bool mbar_try(uint32_t bar, uint32_t ph, uint32_t ns) {
  uint32_t ok;
  asm volatile("{\n.reg .pred p;\nmbarrier.try_wait.parity.shared::cta.b64 p, [%1], %2, %3;\nselp.u32 %0, 1, 0, p;\n}\n"
               : "=r"(ok) : "r"(bar), "r"(ph), "r"(ns) : "memory");
  return ok;
}
__device__ __forceinline__ void mbar_wait(uint32_t bar, uint32_t ph) {
  asm volatile("{\n.reg .pred p;\n.reg .u32 n;\nmov.u32 n, 0;\n"
               "LOOP:\nmbarrier.try_wait.parity.shared::cta.b64 p, [%0], %1;\n@p bra DONE;\n"
               "add.u32 n, n, 1;\nsetp.lt.u32 p, n, 0x1000000;\n@p bra LOOP;\ntrap;\n"
               "DONE:\n}\n" ::"r"(bar), "r"(ph) : "memory");
}
__device__ __forceinline__ void mbar_wait_long(uint32_t bar) {
  asm volatile("{\n.reg .pred p;\n.reg .u32 n;\nmov.u32 n, 0;\n"
               "LOOP:\nmbarrier.try_wait.parity.shared::cta.b64 p, [%0], 0, 20000;\n@p bra DONE;\n"
               "add.u32 n, n, 1;\nsetp.lt.u32 p, n, 0x100000;\n@p bra LOOP;\ntrap;\n"
               "DONE:\n}\n" ::"r"(bar) : "memory");
}
__device__ __forceinline__ void mbar_arrive_cluster_if(bool on, uint32_t addr) {
  asm volatile("{\n.reg .pred p;\nsetp.ne.b32 p, %1, 0;\n@p mbarrier.arrive.shared::cluster.b64 _, [%0];\n}\n" ::"r"(addr), "r"((int)on) : "memory");
}
__device__ __forceinline__ void mbar_arrive_cluster_n(uint32_t n, uint32_t addr) {
  asm volatile("{\n.reg .pred p;\nsetp.ne.b32 p, %1, 0;\n@p mbarrier.arrive.shared::cluster.b64 _, [%0], %1;\n}\n" ::"r"(addr), "r"(n) : "memory");
}
__device__ __forceinline__ void tma2d(uint32_t dst, const CUtensorMap* m, uint32_t bar, int c0, int c1) {
  asm volatile("cp.async.bulk.tensor.2d.shared::cluster.global.mbarrier::complete_tx::bytes [%0], [%1, {%3, %4}], [%2];"
               ::"r"(dst), "l"(m), "r"(bar), "r"(c0), "r"(c1) : "memory");
}
__device__ __forceinline__ void tma3d(uint32_t dst, const CUtensorMap* m, uint32_t bar, int c0, int c1, int c2) {
  asm volatile("cp.async.bulk.tensor.3d.shared::cluster.global.mbarrier::complete_tx::bytes [%0], [%1, {%3, %4, %5}], [%2];"
               ::"r"(dst), "l"(m), "r"(bar), "r"(c0), "r"(c1), "r"(c2) : "memory");
}
__device__ __forceinline__ void tma3d_mc(uint32_t dst, const CUtensorMap* m, uint32_t bar, int c0, int c1, int c2) {
  asm volatile("cp.async.bulk.tensor.3d.shared::cluster.global.mbarrier::complete_tx::bytes.multicast::cluster"
               " [%0], [%1, {%3, %4, %5}], [%2], %6;"
               ::"r"(dst), "l"(m), "r"(bar), "r"(c0), "r"(c1), "r"(c2), "h"((uint16_t)3) : "memory");
}
__device__ __forceinline__ void tma3d_store(const CUtensorMap* m, uint32_t src, int c0, int c1, int c2) {
  asm volatile("cp.async.bulk.tensor.3d.global.shared::cta.bulk_group [%0, {%2, %3, %4}], [%1];"
               ::"l"(m), "r"(src), "r"(c0), "r"(c1), "r"(c2) : "memory");
}
__device__ __forceinline__ void bar_sync(int id, int n) { asm volatile("bar.sync %0, %1;" ::"r"(id), "r"(n) : "memory"); }
__device__ __forceinline__ uint32_t pack_bf16(float lo, float hi) {
  uint32_t r;
  asm("cvt.rn.bf16x2.f32 %0, %1, %2;" : "=r"(r) : "f"(hi), "f"(lo));
  return r;
}
__device__ __forceinline__ float ex2(float x) {
  float y;
  asm("ex2.approx.ftz.f32 %0, %1;" : "=f"(y) : "f"(x));
  return y;
}
__device__ __forceinline__ float rcp(float x) {
  float y;
  asm("rcp.approx.ftz.f32 %0, %1;" : "=f"(y) : "f"(x));
  return y;
}
__device__ __forceinline__ void stsm4(uint32_t addr, uint32_t a, uint32_t b, uint32_t c, uint32_t d) {
  asm volatile("stmatrix.sync.aligned.m8n8.x4.shared.b16 [%0], {%1, %2, %3, %4};" ::"r"(addr), "r"(a), "r"(b), "r"(c), "r"(d) : "memory");
}

__device__ __forceinline__ void tma4d_mc_hint(uint32_t dst, const CUtensorMap* m, uint32_t bar, int c3, uint64_t pol) {
  asm volatile("cp.async.bulk.tensor.4d.shared::cluster.global.mbarrier::complete_tx::bytes.multicast::cluster.L2::cache_hint"
               " [%0], [%1, {%3, %3, %3, %4}], [%2], %5, %6;"
               ::"r"(dst), "l"(m), "r"(bar), "r"(0), "r"(c3), "h"((uint16_t)3), "l"(pol) : "memory");
}
__device__ __forceinline__ void tma5d_mc(uint32_t dst, const CUtensorMap* m, uint32_t bar, int c2, int c4) {
  asm volatile("cp.async.bulk.tensor.5d.shared::cluster.global.mbarrier::complete_tx::bytes.multicast::cluster"
               " [%0], [%1, {%3, %3, %4, %3, %5}], [%2], %6;"
               ::"r"(dst), "l"(m), "r"(bar), "r"(0), "r"(c2), "r"(c4), "h"((uint16_t)3) : "memory");
}
__device__ __forceinline__ void bulk_load_hint(uint32_t dst, const void* src, uint32_t bytes, uint32_t bar, uint64_t pol) {
  asm volatile("cp.async.bulk.shared::cluster.global.mbarrier::complete_tx::bytes.L2::cache_hint [%0], [%1], %2, [%3], %4;"
               ::"r"(dst), "l"(src), "r"(bytes), "r"(bar), "l"(pol) : "memory");
}
__device__ __forceinline__ void stg2_if(bool on, void* p, uint32_t a, uint32_t b, uint32_t c, uint32_t d, uint32_t e, uint32_t f,
                                        uint32_t g, uint32_t h, uint64_t pol) {
  asm volatile("{\n.reg .pred p;\nsetp.ne.b32 p, %10, 0;\n"
               "@p st.global.L2::cache_hint.v4.b32 [%0], {%1, %2, %3, %4}, %9;\n"
               "@p st.global.L2::cache_hint.v4.b32 [%0 + 512], {%5, %6, %7, %8}, %9;\n}\n"
               ::"l"(p), "r"(a), "r"(b), "r"(c), "r"(d), "r"(e), "r"(f), "r"(g), "r"(h), "l"(pol), "r"((int)on) : "memory");
}
__device__ __forceinline__ uint64_t evict_first() {
  uint64_t p;
  asm("createpolicy.fractional.L2::evict_first.b64 %0, 1.0;" : "=l"(p));
  return p;
}
__device__ __forceinline__ bool elect() {
  uint32_t ok;
  asm volatile("{\n.reg .pred p;\nelect.sync _|p, 0xffffffff;\nselp.u32 %0, 1, 0, p;\n}\n" : "=r"(ok));
  return ok;
}
__device__ __forceinline__ void mbar_arrive(uint32_t bar) {
  asm volatile("mbarrier.arrive.shared::cta.b64 _, [%0];" ::"r"(bar) : "memory");
}
__device__ __forceinline__ void mbar_arrive_if(bool on, uint32_t bar) {
  asm volatile("{\n.reg .pred p;\nsetp.ne.b32 p, %1, 0;\n@p mbarrier.arrive.shared::cta.b64 _, [%0];\n}\n" ::"r"(bar), "r"((int)on) : "memory");
}
__device__ __forceinline__ void lds2_if(bool on, uint32_t p, uint32_t (&t)[8]) {
  asm volatile("{\n.reg .pred p;\nsetp.ne.b32 p, %9, 0;\n@p ld.shared.v4.b32 {%0, %1, %2, %3}, [%8];\n@p ld.shared.v4.b32 {%4, %5, %6, %7}, [%8 + 512];\n}\n"
               : "+r"(t[0]), "+r"(t[1]), "+r"(t[2]), "+r"(t[3]), "+r"(t[4]), "+r"(t[5]), "+r"(t[6]), "+r"(t[7]) : "r"(p), "r"((int)on) : "memory");
}
__device__ __forceinline__ void lds128(uint32_t p, uint32_t& a, uint32_t& b, uint32_t& c, uint32_t& d) {
  asm volatile("ld.shared.v4.b32 {%0, %1, %2, %3}, [%4];" : "=r"(a), "=r"(b), "=r"(c), "=r"(d) : "r"(p) : "memory");
}
template <class T> __device__ __forceinline__ T* ptr_add(T* base, uint32_t bytes) {
  T* r;
  asm("{\n.reg .u32 lo, hi;\nmov.b64 {lo, hi}, %1;\nadd.cc.u32 lo, lo, %2;\naddc.u32 hi, hi, 0;\nmov.b64 %0, {lo, hi};\n}\n" : "=l"(r) : "l"(base), "r"(bytes));
  return r;
}
__device__ __forceinline__ uint32_t lds32(uint32_t p) {
  uint32_t v;
  asm volatile("ld.volatile.shared.u32 %0, [%1];" : "=r"(v) : "r"(p) : "memory");
  return v;
}
__device__ __forceinline__ uint32_t flag_get(const unsigned int* p) {
  uint32_t v;
  asm volatile("ld.acquire.gpu.global.u32 %0, [%1];" : "=r"(v) : "l"(p) : "memory");
  return v;
}
__device__ __forceinline__ uint32_t wait_word(uint32_t p, uint32_t target) {
  uint32_t v;
  asm volatile("{\n.reg .pred p;\n.reg .u32 n;\nmov.u32 n, 0;\n"
               "LOOP:\nld.acquire.cta.shared.u32 %0, [%1];\nsetp.ge.u32 p, %0, %2;\n@p bra DONE;\n"
               "nanosleep.u32 %3;\nadd.u32 n, n, 1;\nsetp.lt.u32 p, n, 0x400000;\n@p bra LOOP;\ntrap;\n"
               "DONE:\n}\n" : "=r"(v) : "r"(p), "r"(target), "n"(400) : "memory");
  return v;
}
__device__ __forceinline__ void flag_set(unsigned int* p, uint32_t v) {
  asm volatile("st.release.gpu.global.u32 [%0], %1;" ::"l"(p), "r"(v) : "memory");
}
__device__ __forceinline__ void flag_dec(unsigned int* p) {
  asm volatile("red.relaxed.gpu.global.add.u32 [%0], 0xffffffff;" ::"l"(p) : "memory");
}

struct Cursor {
  int bi;
  uint32_t ph;
  __device__ __forceinline__ void next() {
    if (++bi == NBAR) { bi = 0; ph ^= 1; }
  }
};

constexpr float kScaleLog2 = 0.07216878364870322f * 1.4426950408889634f;
constexpr float kSumLimit = 1048576.0f;

__global__ void __cluster_dims__(2, 1, 1) __launch_bounds__(384, 1)
fused_kernel(const __grid_constant__ Params P) {
  extern __shared__ uint8_t smem_raw[];
  const uint32_t sbase = (smem_u32(smem_raw) + 1023) & ~1023u;
  const uint32_t full0 = sbase + RING, empty0 = full0 + 8 * NBAR, odone0 = empty0 + 8 * NBAR, ev0 = odone0 + 8 * MAX_OPS;
  const uint32_t progress = ev0 + 8 * MAX_EV, jobw = progress + 4;
  const uint32_t rank = blockIdx.x & 1;
  const int role = blockIdx.x >> 1;
  const int wid = __shfl_sync(0xffffffffu, (int)(threadIdx.x >> 5), 0);
  const int wg = wid >> 2;

  if (wid < 8) {
    if (elect()) {
#pragma unroll
      for (int j = 0; j < 16; j++) {
        const int i = EARLY + 16 * wid + j;
        if (i < 2 * NBAR + MAX_OPS + MAX_EV) mbar_init(full0 + 8 * i, i < NBAR ? 1 : i < 2 * NBAR ? 16 : i < 2 * NBAR + MAX_OPS ? 8 : 1);
      }
      if (wid == 7) asm volatile("st.shared.v2.u32 [%0], {0, 0};\nfence.acq_rel.cta;" ::"r"(progress) : "memory");
      asm volatile("fence.mbarrier_init.release.cluster;" ::: "memory");
    }
  } else if (wid > 8) {
    const uint32_t g = blockIdx.x * 96 + threadIdx.x - 288, w = g - 2048;
    if (g < 4096) asm volatile("prefetch.global.L2 [%0];" ::"l"(g < 2048 ? P.xw[0] + g * (kD * 2) : P.xw[1] + (w >> 5) * (kHD * 2) + (w & 31) * 128));
  } else {
    const uint32_t op0 = P.first[role];
    if (elect()) {
#pragma unroll
      for (int k = 0; k < EARLY; k++) mbar_init(full0 + 8 * k, 1);
      asm volatile("fence.mbarrier_init.release.cluster;" ::: "memory");
      const int blk = (op0 >> 10) & 1;
      if ((op0 & 3) == OP_Q) {
#pragma unroll
        for (int k = 0; k < EARLY; k++) {
          mbar_expect(full0 + 8 * k, SZ_Q);
          tma2d(sbase + k * SZ_Q, &P.x[blk], full0 + 8 * k, 64 * k, ((op0 >> 7) & 7) * kSq + rank * 128);
          tma3d(sbase + k * SZ_Q + 16384, &P.wq[blk], full0 + 8 * k, 0, 64 * k, 3 * ((op0 >> 2) & 31));
        }
      }
      asm volatile("prefetch.tensormap [%0];" ::"l"(rank ? &P.v[blk] : &P.k[blk]) : "memory");
    }
  }
  __syncwarp();
  asm volatile("barrier.cluster.arrive.relaxed.aligned;\nbarrier.cluster.wait.aligned;" ::: "memory");

  if (wg < 2) {
    asm volatile("setmaxnreg.inc.sync.aligned.u32 240;");
    const uint32_t* prog = P.prog[role].c;
    const int lane = threadIdx.x & 31, warp = wid & 3;
    uint32_t empty_rem;
    asm volatile("mapa.shared::cluster.u32 %0, %1, %2;" : "=r"(empty_rem) : "r"(empty0), "r"(lane & 1));
    uint32_t keep = (threadIdx.x & 127) < 2 ? 4 : 0;
    auto release = [&](int slot) { mbar_arrive_cluster_n(keep, empty_rem + 8 * slot); };
    auto release_warp = [&](int slot, bool on = true) { mbar_arrive_cluster_if(lane < 2 && on, empty_rem + 8 * slot); };
    Cursor r{0, 0};
    const uint32_t ring16 = (sbase & 0x3FFFF) >> 4;
    uint32_t cur = ring16;
    bool rdy0 = false, rdy1 = false;
    auto probe1 = [&]() { rdy0 = mbar_test(full0 + 8 * r.bi, r.ph); };
    auto probe2 = [&]() {
      Cursor n = r;
      rdy0 = mbar_test(full0 + 8 * n.bi, n.ph);
      n.next();
      rdy1 = mbar_test(full0 + 8 * n.bi, n.ph);
    };
    auto take = [&](bool rdy, uint32_t bytes, uint32_t& addr) {
      const int bi = r.bi;
      if (__builtin_expect(!__all_sync(0xffffffffu, rdy), 0)) mbar_wait(full0 + 8 * r.bi, r.ph);
      r.next();
      if (cur > ring16 + ((RING - bytes) >> 4)) cur = ring16;
      addr = cur;
      cur += bytes >> 4;
      return bi;
    };
    const bool never = P.dbg == 0xffffffffu;
    uint32_t q[48];
#pragma unroll
    for (int i = 0; i < 48; i++) q[i] = 0;
    const int row = wg * 64 + warp * 16 + (lane >> 2);
    const int img0 = row * 4 + ((lane & 3) ^ ((row >> 1) & 3));
    uint4* pend = nullptr;
    bool pend_any = false;
    const uint64_t spol = evict_first();
    int pc = 0;
    auto slab = [&](int c, int i0) {
#pragma unroll
      for (int i = i0; i < 6; i++)
        stg2_if(c == i, pend + i * 512, q[8 * i], q[8 * i + 1], q[8 * i + 2], q[8 * i + 3],
                q[8 * i + 4], q[8 * i + 5], q[8 * i + 6], q[8 * i + 7], spol);
    };
    auto drain = [&](int c) {
      if (!pend_any || c >= 6) return;
      slab(c, 0);
      if (c == 5) {
        __syncwarp();
        mbar_arrive_if(lane == 0, odone0 - 8 + 8 * pc);
      }
    };

    for (;; pc++) {
      uint32_t op = prog[pc];
      const int type = op & 3;
      auto enter = [&]() {
        r.bi = (op >> 15) & 15; r.ph = (op >> 19) & 1; cur = ring16 + (((op >> 20) & 63) << 8);
      };
      enter();
      pend_any = op & C_PEND;
      uint32_t job = 0;
      if ((op & (3 | C_WIDE)) == OP_O) job = __shfl_sync(0xffffffffu, wait_word(jobw, 1), 0);
      if (type == OP_END || job == OP_O) {
#pragma unroll 1
        for (int c = 0; c < 6; c++) drain(c);
        asm volatile("barrier.cluster.arrive.relaxed;" ::: "memory");
        break;
      }
      {
        float s[32], o[96];
        uint32_t ad0;
        int bi0, sk1;
        uint32_t pa[16], pb[16];
        float mc0, mc1, l0, l1;
        bool shifted;
        uint32_t nop;
        auto expo = [&](float (&s)[32], uint32_t (&pout)[16], float& b0, float& b1, bool shift, auto mid) {
          float c0, c1;
#pragma unroll
          for (int i = 0; i < 8; i++) {
            const float e0 = ex2(shift ? s[4 * i] - mc0 : s[4 * i]), e1 = ex2(shift ? s[4 * i + 1] - mc0 : s[4 * i + 1]);
            const float e2 = ex2(shift ? s[4 * i + 2] - mc1 : s[4 * i + 2]), e3 = ex2(shift ? s[4 * i + 3] - mc1 : s[4 * i + 3]);
            if (i) { b0 += e0; c0 += e1; b1 += e2; c1 += e3; } else { b0 = e0; c0 = e1; b1 = e2; c1 = e3; }
            pout[2 * i] = pack_bf16(e0, e1); pout[2 * i + 1] = pack_bf16(e2, e3);
            if (i & 1) mid(i >> 1);
          }
          b0 += c0; b1 += c1;
        };
        auto rowmax = [&](float (&s)[32], float& m0, float& m1) {
          m0 = fmaxf(s[0], s[1]); m1 = fmaxf(s[2], s[3]);
#pragma unroll
          for (int i = 1; i < 8; i++) { m0 = fmaxf(m0, fmaxf(s[4 * i], s[4 * i + 1])); m1 = fmaxf(m1, fmaxf(s[4 * i + 2], s[4 * i + 3])); }
          m0 = fmaxf(m0, __shfl_xor_sync(0xffffffffu, m0, 1)); m1 = fmaxf(m1, __shfl_xor_sync(0xffffffffu, m1, 1));
          m0 = fmaxf(m0, __shfl_xor_sync(0xffffffffu, m0, 2)); m1 = fmaxf(m1, __shfl_xor_sync(0xffffffffu, m1, 2));
        };
        auto first = [&](float (&s)[32], int sk0, auto mid) {
          fence_regs(s);
          release(sk0);
          mc0 = 0.f; mc1 = 0.f;
          expo(s, pa, l0, l1, false, mid);
          shifted = __any_sync(0xffffffffu, !(fmaxf(l0, l1) <= kSumLimit && fminf(l0, l1) >= 1.f / kSumLimit));
          if (shifted) {
            rowmax(s, mc0, mc1);
            expo(s, pa, l0, l1, true, [](int) {});
          }
        };
        auto qk = [&](float (&s)[32], uint32_t ak, int k0 = 0, int k1 = 12) {
#pragma unroll
          for (int kk = k0; kk < k1; kk++)
            wgmma_rs_n64<0>(s, q[4 * kk], q[4 * kk + 1], q[4 * kk + 2], q[4 * kk + 3], mk_desc(ak, 16, KV_SBO, 1) + ((kk >> 2) * KV_CH + (kk & 3) * 2), kk != 0);
          if (k1 == 12) wg_commit();
        };
        auto pv = [&](uint32_t (&pin)[16], uint32_t av, int acc) {
#pragma unroll
          for (int kk = 0; kk < 4; kk++)
            wgmma_rs_n192<1>(o, pin[4 * kk], pin[4 * kk + 1], pin[4 * kk + 2], pin[4 * kk + 3], mk_desc(av, KV_CH * 16, KV_SBO, 1) + (kk * (KV_SBO / 8)), acc || (kk != 0));
          wg_commit();
        };
        auto finish = [&](uint32_t (&pout)[16], int sk, int sv) {
          probe2();
          wg_wait<1>();
          fence_regs(s);
          release(sk);
          float b0, b1;
#pragma unroll 1
          for (bool redo = false;; redo = true) {
            expo(s, pout, b0, b1, false, [](int) {});
            if (!__any_sync(0xffffffffu, !redo && (shifted || !(fmaxf(b0, b1) <= kSumLimit)))) break;
            shifted = true;
            rowmax(s, b0, b1);
            b0 = fmaxf(mc0, b0); b1 = fmaxf(mc1, b1);
            const float a0 = ex2(mc0 - b0), a1 = ex2(mc1 - b1);
            mc0 = b0; mc1 = b1;
            l0 *= a0; l1 *= a1;
            wg_wait<0>();
            fence_regs(o);
#pragma unroll
            for (int i = 0; i < 24; i++) { o[4 * i] *= a0; o[4 * i + 1] *= a0; o[4 * i + 2] *= a1; o[4 * i + 3] *= a1; }
#pragma unroll
            for (int i = 0; i < 32; i++) s[i] -= (i & 2) ? mc1 : mc0;
          }
          l0 += b0; l1 += b1;
          wg_wait<0>();
          fence_regs(o);
          release(sv);
        };
        auto step = [&](uint32_t (&pin)[16], uint32_t (&pout)[16]) {
          uint32_t ak, av;
          const int sk = take(rdy0, SZ_KV, ak), sv = take(rdy1, SZ_KV, av);
          wg_fence();
          qk(s, ak);
          pv(pin, av, 1);
          finish(pout, sk, sv);
        };
        auto unpark = [&]() {
          uint32_t ad, ak;
          const int bi = take(rdy0, SZ_PARK, ad);
#pragma unroll
          for (int i = 0; i < 12; i++) lds128(sbase + (ad - ring16 + img0) * 16 + (i >> 1) * 8192 + (i & 1) * 512, q[4 * i], q[4 * i + 1], q[4 * i + 2], q[4 * i + 3]);
          const int sk0 = take(false, SZ_KV, ak);
          fence_regs(q);
          release_warp(bi);
          wg_fence();
          qk(s, ak);
          probe2();
          return sk0;
        };
        auto mma4 = [&](uint32_t ad, int acc) {
#pragma unroll
          for (int kk = 0; kk < 4; kk++)
            wgmma_ss_n192<1>(o, mk_desc(ad + wg * 512, 16, 1024, 1) + (kk * 2), mk_desc(ad, 8192, 1024, 1) + (1024 + kk * 128), acc || kk != 0);
        };
        auto convert = [&](int i0, int i1) {
          sched_fence(keep, never);
#pragma unroll
          for (int i = i0; i < i1; i++) {
            q[i] = pack_bf16(o[2 * i] * kScaleLog2, o[2 * i + 1] * kScaleLog2);
            if ((i & 7) == 7 && i != i1 - 1) sched_fence(keep, never);
          }
          sched_fence(keep, never);
        };
        auto kend = [&](int bi, int k) {
          wg_commit();
          drain(k < 8 ? (0x54732710u >> (4 * k)) & 7 : 7);
          probe1();
          wg_wait<0>();
          release(bi);
        };
        if (type == OP_O) {
          float c[80];
          int prev = 0;
          auto hand_over = [&](float (&c)[80], uint4* dst) {
            fence_regs(c);
#pragma unroll
            for (int i = 0; i < 48; i++) q[i] = i < 8 ? 0 : pack_bf16(c[2 * i - 16], c[2 * i - 15]);
            pend = dst;
          };
          auto mma2 = [&](float (&c)[80], uint32_t ad, uint32_t oa, uint32_t ob, int acc) {
            wgmma_ss_n160<1>(c, mk_desc(ad + wg * 256, 16, 512, 2) + (oa), mk_desc(ad, 2048, 512, 2) + (1024 + ob), acc);
            wgmma_ss_n160<1>(c, mk_desc(ad + wg * 256, 16, 512, 2) + (oa + 2), mk_desc(ad, 2048, 512, 2) + (1024 + ob + 64), 1);
          };
          auto kstep = [&](float (&c)[80], int acc, auto hook, uint32_t bytes = SZ_O) {
            uint32_t ad;
            const int bi = take(rdy0, bytes, ad);
            wg_fence();
            mma2(c, ad, 0, 0, acc);
            wg_commit();
            if (acc) wg_wait<1>();
            if (acc == 1) release(prev);
            if (acc > 1) release_warp(prev, acc == 2 || wg == 0);
            mma2(c, ad, 512, 640, 1);
            wg_commit();
            prev = bi;
            hook();
            probe1();
            wg_wait<1>();
          };
          if (op & C_WIDE) {
            float d[80];
            const int nk = (op >> 2) & 127;
            uint4* part = ptr_add(P.g->part, (((op >> 9) & 63) * 2 + rank) * SZ_PARK + img0 * 16);
            auto wstep = [&](int acc, auto hook) {
              uint32_t ad;
              const int bi = take(rdy0, SZ_W, ad);
              wg_fence();
              mma2(d, ad, 0, 0, acc);
              mma2(d, ad, 512, 640, 1);
              wg_commit();
              if (acc) { wg_wait<1>(); release(prev); }
              mma2(c, ad, 0, 1280, acc);
              mma2(c, ad, 512, 1920, 1);
              wg_commit();
              prev = bi;
              hook();
              probe1();
              wg_wait<1>();
            };
            wstep(0, [&]() { drain(0); });
#pragma unroll 1
            for (int k = 1; k < 6; k++) wstep(1, [&]() { drain(k); });
#pragma unroll 1
            for (int k = 6 + TAIL; k < nk; k++) {
              wstep(1, []() {});
            }
#pragma unroll 1
            for (int k = 0; k < TAIL; k++) kstep(d, 1, []() {});
            nop = prog[pc + 1];
            kstep(c, 1, [&]() { hand_over(d, part - 6144); });
#pragma unroll 1
            for (int k = 1; k < TAIL; k++) kstep(c, 1, [&]() { slab(k, 1); });
            if ((nop & 3) == OP_Q) {
              op = nop;
              enter();
              pc++;
              pend_any = true;
              bi0 = take(rdy0, SZ_Q, ad0);
              undefine(o);
              wg_fence();
              mma4(ad0, 0);
              wg_commit();
              wg_wait<1>();
              release(prev);
              hand_over(c, part);
              probe1();
              wg_wait<0>();
              release(bi0);
              fence_regs(o);
              goto next_head;
            }
            wg_wait<0>();
            release(prev);
            hand_over(c, part);
            continue;
          }
          auto unblock = [&](int k) {
            if (__all_sync(0xffffffffu, rdy0) || __all_sync(0xffffffffu, mbar_try(full0 + 8 * r.bi, r.ph, 1500))) return;
#pragma unroll 1
            for (; k < 6; k++) drain(k);
            pend_any = false;
          };
          unblock(0);
          kstep(c, 0, [&]() { drain(0); });
          int left = ((job >> 13) & 127) - 6;
#pragma unroll 1
          for (uint32_t k = 1, pace = left >= 29 ? 0x4511 : left <= 17 ? 0x1a : 0x155; k < 6; pace >>= 2, left--) {
            unblock(k);
            kstep(c, 1, [&]() {
#pragma unroll 1
              for (int i = pace & 3; i > 0; i--) drain(k++);
            });
          }
#pragma unroll 1
          for (; left > 0; left--) kstep(c, 1, []() {});
          uint32_t t[8], stage[3];
          float u[80];
          auto unpack = [&](int j) {
#pragma unroll
            for (int i = 0; i < 8; i++) {
              u[16 * j + 2 * i] = __uint_as_float(t[i] << 16); u[16 * j + 2 * i + 1] = __uint_as_float(t[i] & 0xffff0000u);
              asm volatile("" : "+f"(u[16 * j + 2 * i]), "+f"(u[16 * j + 2 * i + 1]));
            }
          };
#pragma unroll
          for (int i = 0; i < 8; i++) t[i] = 0;
          const uint32_t bytes = (job & P_LD) ? SZ_OL : SZ_O;
#pragma unroll
          for (int j = 0; j < 5; j++) {
            if (j == 2 && wg == 1) {
              wg_wait<0>();
              release_warp(prev);
              bar_sync(1, 256);
            }
            kstep(c, j == 2 ? 3 : 2, [&]() {
              if (j == 4) asm volatile("{\n.reg .pred p;\nsetp.eq.u32 p, %0, 0;\n@p bar.arrive 1, 256;\n}\n" ::"r"(wg) : "memory");
              if (j) unpack(j - 1);
              lds2_if(job & P_LD, sbase + (cur - ring16 + img0) * 16 - 8192, t);
              if (j >= 1 && j <= 3) stage[j - 1] = sbase + (cur - ring16) * 16 - bytes + wid * 1024;
            }, bytes);
          }
          unpack(4);
          sched_fence(keep, never);
          wg_wait<0>();
          fence_regs(c);
          release_warp(prev);
          asm volatile("barrier.cluster.arrive.relaxed;" ::: "memory");
#pragma unroll
          for (int i = 0; i < 10; i++) {
            const int v = (i & 1) * 2 + (lane >> 4);
            const uint32_t sa = stage[i >> 2] + (i & 2) * 4096;
            stsm4(sa + (lane & 15) * 64 + ((v ^ ((lane >> 1) & 3)) << 4), pack_bf16(c[8 * i] + u[8 * i], c[8 * i + 1] + u[8 * i + 1]),
                  pack_bf16(c[8 * i + 2] + u[8 * i + 2], c[8 * i + 3] + u[8 * i + 3]), pack_bf16(c[8 * i + 4] + u[8 * i + 4], c[8 * i + 5] + u[8 * i + 5]),
                  pack_bf16(c[8 * i + 6] + u[8 * i + 6], c[8 * i + 7] + u[8 * i + 7]));
          }
          asm volatile("fence.proxy.async.shared::cta;" ::: "memory");
          __syncwarp();
          if (elect()) {
#pragma unroll
            for (int i = 0; i < 5; i++)
              tma3d_store(&P.out, stage[i >> 1] + (i & 1) * 8192, 0, ((job >> 7) & 7) * kSq + rank * 128 + wid * 16, ((job >> 10) & 1) * 20 + ((job >> 20) & 3) * 5 + i);
            asm volatile("cp.async.bulk.commit_group;\ncp.async.bulk.wait_group.read 0;" ::: "memory");
          }
          __syncwarp();
          break;
        }
        bi0 = take(rdy0, SZ_Q, ad0);
        undefine(o);
        wg_fence();
        mma4(ad0, 0);
        kend(bi0, 0);
        fence_regs(o);
      next_head:
        {
#pragma unroll 1
          for (int k = 1; k < ((op & F_PARK) ? 10 : 8); k++) {
            uint32_t ad;
            const int bi = take(rdy0, SZ_Q, ad);
            wg_fence();
            mma4(ad, 1);
            kend(bi, k);
          }
          if (op & F_PARK) {
            fence_regs(o);
            convert(0, 48);
            pend = ptr_add(P.g->tile, (((op >> 2) & 511) * 2 + rank) * SZ_PARK + img0 * 16);
            continue;
          }
          uint32_t a8, a9, ak0, ak1;
          const int b8 = take(rdy0, SZ_Q, a8), b9 = take(false, SZ_Q, a9);
          wg_fence();
          mma4(a8, 1);
          wg_commit();
          mma4(a9, 1);
          wg_commit();
          pc++;
          wg_wait<1>();
          release(b8);
          const int sk0 = take(false, SZ_KV, ak0);
          wg_wait<0>();
          fence_regs(o);
          release(b9);
          float s0[32];
          convert(0, 32);
          wg_fence();
          qk(s0, ak0, 0, 4);
          convert(32, 48);
          wg_fence();
          qk(s0, ak0, 4, 12);
          sk1 = take(false, SZ_KV, ak1);
          probe1();
          wg_wait<0>();
          first(s0, sk0, [&](int i) {
            if (i == 0) return;
            sched_fence(keep, never);
            wg_fence();
            if (i == 1) qk(s, ak1, 0, 4);
            if (i == 2) qk(s, ak1, 4, 8);
            if (i == 3) qk(s, ak1, 8, 12);
            sched_fence(keep, never);
          });
        }
        for (;;) {
          {
            uint32_t av;
            const int sv = take(rdy0, SZ_KV, av);
            undefine(o);
            wg_fence();
            pv(pa, av, 0);
            finish(pb, sk1, sv);
          }
          nop = prog[pc + 1];
#pragma unroll 1
          for (int jj = 0; jj < 7; jj++) {
            step(pb, pa);
            step(pa, pb);
          }
          float i0, i1;
          auto last = [&]() {
            uint32_t av;
            const int sv = take(rdy0, SZ_KV, av);
            wg_fence();
            pv(pb, av, 1);
            sched_fence(keep, never);
            probe1();
            l0 += __shfl_xor_sync(0xffffffffu, l0, 1); l1 += __shfl_xor_sync(0xffffffffu, l1, 1);
            l0 += __shfl_xor_sync(0xffffffffu, l0, 2); l1 += __shfl_xor_sync(0xffffffffu, l1, 2);
            i0 = rcp(l0); i1 = rcp(l1);
            pend = ptr_add(P.g->tile, (((op >> 2) & 511) * 2 + rank) * SZ_PARK + img0 * 16);
            return sv;
          };
          auto normalise = [&](uint32_t (&d)[48], auto mid) {
#pragma unroll
            for (int i = 0; i < 24; i++) {
              d[8 * (i >> 2) + (i & 3)] = pack_bf16(o[4 * i] * i0, o[4 * i + 1] * i0);
              d[8 * (i >> 2) + (i & 3) + 4] = pack_bf16(o[4 * i + 2] * i1, o[4 * i + 3] * i1);
              if ((i & 1) && i != 23) sched_fence(keep, never);
              if ((i & 3) == 3 && i != 23) mid(i >> 2);
            }
          };
          const int sv = last();
          if ((nop & 3) != OP_A) {
            op = nop;
            enter();
            pend_any = true;
            bi0 = take(rdy0 || (nop & 3) != OP_Q, SZ_Q, ad0);
            sched_fence(keep, never);
            wg_wait<0>();
            fence_regs(o);
            release(sv);
            normalise(q, [](int) {});
            undefine(o);
            if ((nop & 3) != OP_Q) break;
            sched_fence(keep, never);
            wg_fence();
            mma4(ad0, 0);
            pc++;
            kend(bi0, 0);
            fence_regs(o);
            goto next_head;
          }
          const int sk0 = unpark();
          wg_wait<1>();
          fence_regs(o);
          release(sv);
          uint32_t t[48];
          auto st = [&](int i) {
            stg2_if(true, pend + i * 512, t[8 * i], t[8 * i + 1], t[8 * i + 2], t[8 * i + 3], t[8 * i + 4], t[8 * i + 5], t[8 * i + 6], t[8 * i + 7], spol);
          };
          normalise(t, [&](int i) { if (!(i & 1)) st(i >> 1); });
          wg_wait<0>();
          first(s, sk0, [&](int i) { if (i < 3) { sched_fence(keep, never); st(3 + i); } });
          __syncwarp();
          mbar_arrive_if(lane == 0, odone0 + 8 * pc);
          pc++;
          op = nop;
          uint32_t ak1;
          sk1 = take(rdy0, SZ_KV, ak1);
          rdy0 = rdy1;
          wg_fence();
          qk(s, ak1);
        }
      }
    }
    asm volatile("barrier.cluster.wait;" ::: "memory");
  } else {
    asm volatile("setmaxnreg.dec.sync.aligned.u32 24;");
    const uint32_t* prog = P.prog[role].p;
    unsigned int* flag = P.g->flag + rank;
    if (wid == 8) {
      Cursor tail{0, 0};
      int head = 0, sh = 0;
      uint32_t cur = 0, used = 0;
      uint64_t fifo = 0;
      uint32_t dst, bar, ev = ev0, done = 0;
      const uint64_t pol = evict_first();
      auto retire = [&]() {
        mbar_wait(empty0 + 8 * tail.bi, tail.ph);
        tail.next();
        used -= (uint32_t)fifo & 31;
        fifo >>= 5;
        sh -= 5;
        asm volatile("st.volatile.shared.u32 [%0], %1;" ::"r"(progress), "r"(++done) : "memory");
      };
      auto acquire = [&](uint32_t bytes) {
        uint32_t fp = bytes >> 12;
        if (cur + fp > (RING >> 12)) { fp += (RING >> 12) - cur; cur = 0; }
        used += fp;
        while (used > (RING >> 12) || sh == 5 * NBAR) retire();
        fifo |= (uint64_t)fp << sh;
        sh += 5;
        dst = sbase + (cur << 12);
        bar = full0 + 8 * head;
        cur += bytes >> 12;
        if (++head == NBAR) head = 0;
      };
      auto gate = [&]() {
        mbar_wait(ev, 0);
        ev += 8;
        asm volatile("fence.proxy.async.global;" ::: "memory");
      };
      for (int pc = 0;; pc++) {
        uint32_t op = prog[pc];
        const int type = op & 3;
        if (type == OP_END) break;
        if (op == OP_O) {
          gate();
          op = __shfl_sync(0xffffffffu, lds32(jobw), 0);
        }
        const int blk = (op >> 10) & 1;
        if (type == OP_Q) {
#pragma unroll 1
          for (int k = 0; k < 10; k++) {
            if (k == 9 && (op & P_GATE)) gate();
            acquire(SZ_Q);
            if ((pc > 0 || k >= EARLY) && elect()) {
              mbar_expect(bar, SZ_Q);
              tma2d(dst, &P.x[blk], bar, 64 * k, ((op >> 7) & 7) * kSq + rank * 128);
              if ((k & 1) == rank) tma3d_mc(dst + 16384, &P.wq[blk], bar, 0, 64 * k, 3 * ((op >> 2) & 31));
            }
          }
        } else if (type == OP_A) {
          const int row0 = ((op >> 2) & 255) * kSk;
          const CUtensorMap* kv_map = rank ? &P.v[blk] : &P.k[blk];
          if (op & F_PARK) {
            gate();
            acquire(SZ_PARK);
            if (elect()) {
              mbar_expect(bar, SZ_PARK);
              bulk_load_hint(dst, &P.g->tile[((op >> 20) * 2 + rank) * 3072], SZ_PARK, bar, pol);
            }
          }
#pragma unroll 1
          for (int t = 0; t < 32; t++) {
            const int isv = t == 31 ? 1 : (t == 0 ? 0 : (~t & 1));
            const int j = isv ? (t - 1) >> 1 : (t + 1) >> 1;
            if (t == 31 && (op & P_GATE)) gate();
            acquire(SZ_KV);
            if (elect()) {
              mbar_expect(bar, SZ_KV);
              if (isv == (int)rank) tma4d_mc_hint(dst, kv_map, bar, row0 / 8 + 8 * j, pol);
            }
          }
        } else {
          const int n = (op >> 13) & 127, nw = (op & P_WIDE) ? n - TAIL : 0;
          const uint4* part = &P.g->part[((((op >> 5) & 60) + ((op >> 20) & 3)) * 2 + rank) * 3072 + 512];
#pragma unroll 1
          for (int i = 0; i < n + (nw ? TAIL : 0); i++) {
            const int k = nw ? (i < n ? i : i - TAIL) : kSteps - n + i, h = (k * 43) >> 7, col = 5 * (((op >> 20) & 3) + (i >= n));
            const uint4* src = &P.g->tile[(P.slot[((op >> 2) & 480) + h] * 2 + rank) * 3072 + (k - 3 * h) * 1024];
            const uint32_t j = (op & P_LD) ? i - n + 5 : 5, bytes = i < nw ? SZ_W : j < 5 ? SZ_OL : SZ_O;
            if ((op & P_PRE) ? i == 0 : j == 0) gate();
            if (i < n && (i == 0 || k == 3 * h)) gate();
            acquire(bytes);
            if (elect()) {
              mbar_expect(bar, bytes);
              tma5d_mc(dst + 16384 + rank * 10240, &P.wo[blk], bar, 8 * k + 4 * rank, col);
              bulk_load_hint(dst, src, 16384, bar, pol);
              if (i < nw) tma5d_mc(dst + SZ_O + rank * 10240, &P.wo[blk], bar, 8 * k + 4 * rank, col + 5);
              if (j < 5) bulk_load_hint(dst + SZ_O, part + j * 512, 8192, bar, pol);
              if ((op & P_PRE) && i < 10) asm volatile("cp.async.bulk.prefetch.L2.global [%0], 4096;" ::"l"(part + i * 256) : "memory");
            }
          }
        }
      }
#pragma unroll 1
      while (sh) retire();
    } else if (threadIdx.x == 288) {
      for (int pc = 0;; pc++) {
        const uint32_t op = prog[pc];
        const int type = op & 3;
        if (type == OP_END) break;
        if (type == OP_Q ? !(op & F_PARK) : type == OP_O && !(op & P_WIDE)) continue;
        const int id = type == OP_A ? (op >> 2) & 511 : type == OP_Q ? N_TILE + ((op >> 13) & 127) : ID_PART + ((op >> 5) & 60) + ((op >> 20) & 3);
        const uint32_t v = type == OP_O ? 1 : P.info[id] & 7;
        mbar_wait_long(odone0 + 8 * pc);
        flag_set(flag + 2 * id, v);
        if (type == OP_O && (op & P_WIDE)) flag_set(flag + 2 * id + 2, v);
      }
    } else if (wid == 10) {
      int i = threadIdx.x & 31;
      uint32_t e = i < 8 ? P.prog[role].ev[i] : 0;
      for (uint32_t n = 0; __any_sync(0xffffffffu, e); n++) {
        uint32_t job = lds32(jobw);
        const int togo = (e & E_DRAW) ? (e & 1023) - lds32(progress) : 99;
        if (togo <= 0 && rank == 0) {
          job = P.job[atomicInc(&P.g->ticket, gridDim.x / 2 - 1)];
          asm volatile("{\n.reg .u32 a;\nmapa.shared::cluster.u32 a, %0, 1;\nst.volatile.shared::cluster.u32 [a], %1;\n"
                       "st.volatile.shared.u32 [%0], %1;\n}\n" ::"r"(jobw), "r"(job) : "memory");
        }
        if ((e & E_JOB) && job) {
          const uint32_t j = e & 63, heads = job == OP_O ? 0 : kH - ((job >> 2) & 31), jp = !(job & P_LD) ? 63 : (job & P_PRE) ? 0 : heads - 1, h = j - (j > jp);
          e = j == jp ? (ID_PART + ((job >> 5) & 60) + ((job >> 20) & 3)) | E_ON | E_LAST : h < heads ? (((job >> 2) & 511) + h) | E_ON | E_LAST : 0;
        }
        unsigned int* f = ptr_add(flag, 8 * (e & 1023));
        const bool ok = (e & E_ON) ? flag_get(f) - 1 < ((e & E_FREE) ? 1 : 7) : (e & E_DRAW) && job;
        if (ok) {
          mbar_arrive(ev0 + 8 * i);
          if (e & (E_FREE | E_LAST)) flag_dec(f);
          i += 8;
          e = i < MAX_EV ? P.prog[role].ev[i] : 0;
        }
        asm volatile("{\n.reg .pred p;\nsetp.ge.u32 p, %0, 0x400000;\n@p trap;\n}\n" ::"r"(n));
        if (!__any_sync(0xffffffffu, ok)) __nanosleep(__any_sync(0xffffffffu, job || togo <= 2) ? 100 : 600);
      }
    } else if (threadIdx.x == 352) {
      uint32_t items = 0;
      auto read = [&](int id) {
        if (!(P.info[id] & I_NEXT)) return;
        wait_word(progress, items);
        flag_dec(flag + 2 * id);
      };
      for (int pc = 0;; pc++) {
        const uint32_t op = prog[pc];
        const int type = op & 3;
        if (type == OP_END) break;
        if (type == OP_O) {
          const uint32_t n = (op >> 13) & 127, base = items;
#pragma unroll 1
          for (uint32_t k = 3, id = (op >> 2) & 511; k <= n; k += 3, id++) {
            items = base + k + (k + TAIL > n ? TAIL : 0);
            read(id);
          }
          items = base + n + TAIL;
        } else if (type == OP_A) {
          if (op & F_PARK) { items++; read(N_TILE + ((op >> 13) & 127)); }
          items += 32;
        } else {
          items += 10;
        }
      }
    }
    __syncwarp();
    asm volatile("barrier.cluster.arrive.relaxed;\nbarrier.cluster.wait;" ::: "memory");
  }
}

typedef CUresult (*EncodeFn)(CUtensorMap*, CUtensorMapDataType, cuuint32_t, void*, const cuuint64_t*, const cuuint64_t*,
                             const cuuint32_t*, const cuuint32_t*, CUtensorMapInterleave, CUtensorMapSwizzle,
                             CUtensorMapL2promotion, CUtensorMapFloatOOBfill);

void encode(EncodeFn fn, CUtensorMap* m, const void* ptr, int rank, const cuuint64_t* dims, const cuuint64_t* strides,
            const cuuint32_t* box, CUtensorMapSwizzle swz) {
  const cuuint32_t es[5] = {1, 1, 1, 1, 1};
  CUresult r = fn(m, CU_TENSOR_MAP_DATA_TYPE_BFLOAT16, rank, const_cast<void*>(ptr), dims, strides, box, es,
                  CU_TENSOR_MAP_INTERLEAVE_NONE, swz, CU_TENSOR_MAP_L2_PROMOTION_L2_128B, CU_TENSOR_MAP_FLOAT_OOB_FILL_NONE);
  if (r != CUDA_SUCCESS) fprintf(stderr, "cuTensorMapEncodeTiled failed: %d\n", (int)r);
}

struct Op { int type, flags, id, n, quarter, park, item0, items; double t0, t1; };
struct Use { double ready, gate, need, freed; int readers, slot, prev; bool next; };
struct PlanStats { double end, slack, park_slack; int slots, parks; uint32_t own[N_CL]; };

bool plan(const char* const* text, int n_pair, int phase, Params& P, PlanStats* stats = nullptr) {
  constexpr double T_Q = 7900, T_A = 24850, T_U = 26300, T_O = 640, T_RUN = 800, T_WIDE = 1900, AHEAD = 3500, PUBLISH = 1500;
  const double margin = 256.0 * ((P.dbg >> 8) & 255);
  static Op op[N_CL][MAX_OPS];
  static Use use[ID_PART];
  int n_op[N_CL], covered[N_TEAM] = {}, finals[N_TEAM] = {};
  auto hex = [](char c) { return c <= '9' ? c - '0' : c - 'a' + 10; };
  for (int i = 0; i < n_pair; i++)
    for (const char* s = text[i]; *s; s++)
      if (*s == 'J') { if (covered[hex(s[1])]) return false; covered[hex(s[1])] = 10 * (s[2] - '0') + s[3] - '0'; }
  for (int c = 0; c < 2 * n_pair; c++) {
    int n = 0, items = 0;
    double t = 0;
    auto add = [&](int type, int flags, int id, int heads, int quarter, int its, double dt) {
      if (n < MAX_OPS) op[c][n] = {type, flags, id, heads, quarter, 0, items, its, t, t + dt};
      n++; items += its; t += dt;
    };
    for (const char* s = text[c >> 1]; *s; s++) {
      const int tm = hex(s[1]) & 15, nj = covered[tm];
      if (*s == 'N') { add(OP_Q, 0, 0, 0, 0, 10, T_Q); add(OP_A, 0, 0, 0, 0, 32, T_A); }
      if (*s == 'P') add(OP_Q, F_PARK, 0, 0, 0, 10, T_Q);
      if (*s == 'U') { if (n == 0 || n > MAX_OPS || op[c][n - 1].type != OP_A) return false; add(OP_A, F_PARK, 0, 0, 0, 33, T_U); }
      if (*s == 'J') { if (nj < TAIL + 6 || nj > kSteps - 11) return false; add(OP_O, P_WIDE, tm * kH, nj, 2 * (c & 1), nj + TAIL, 2 * T_O * nj + T_WIDE); }
      if (*s == 'F') { if (s[2]) return false; add(OP_O, nj ? P_LD : 0, tm * kH + nj / 3, kSteps - nj, finals[tm]++, kSteps - nj, T_O * (kSteps - nj) + T_RUN); }
    }
    if (n && n <= MAX_OPS && (op[c][n - 1].type != OP_O || (op[c][n - 1].flags & P_WIDE))) add(OP_O, 0, 0, 0, 0, 0, 0);
    add(OP_END, 0, 0, 0, 0, 0, 0);
    if (n > MAX_OPS || op[c][0].type != OP_Q) return false;
    n_op[c] = n - 1;
  }
  for (int t = 0; t < N_TEAM; t++) if (finals[t] != 4) return false;
  for (int i = 0; i < ID_PART; i++) use[i] = {0, 0, 1e18, 0, 0, 0, 0, false};
  struct Ref { double t; Op* o; int id; };
  static Ref att[N_TILE + 1], dem[N_TILE], prk[MAX_PARK + 1], unp[MAX_PARK + 1], wr[ID_PART];
  int n_att = 0, n_prk = 0, n_unp = 0;
  auto ready = [&](const Op* o) {
    const int nt = o[1].type;
    return o->t1 + (nt == OP_Q ? 6100 : o[1].n ? ((o[1].flags & P_WIDE) ? 7700 : 3900) : 1500) + PUBLISH;
  };
  for (int c = 0; c < 2 * n_pair; c++)
    for (Op* o = op[c]; o->type != OP_END; o++) {
      if (o->type == OP_A) { att[n_att] = {ready(o), o, 0}; if (++n_att > N_TILE) return false; }
      if (o->type == OP_A && o->flags) { unp[n_unp] = {o->t0 - AHEAD, o, 0}; if (++n_unp > MAX_PARK) return false; }
      if (o->type == OP_Q && o->flags) { prk[n_prk] = {ready(o), o, 0}; if (++n_prk > MAX_PARK) return false; }
      for (int i = 0; o->type == OP_O && i < o->n; i++) {
        const int nw = (o->flags & P_WIDE) ? o->n - TAIL : 0, k = nw ? i : kSteps - o->n + i;
        Use& u = use[o->id / kH * kH + k / 3];
        const double t = o->t0 + T_O * (i + (i < nw ? i : nw));
        if (t - AHEAD < u.need) u.need = t - AHEAD;
        const double f = !nw ? 1e18 : i + NBAR < o->items - TAIL || (nw && o[1].type != OP_O) ? t + T_O * (i < nw ? 2 : 1 + TAIL) + PUBLISH : 1e18;
        if (f > u.freed) u.freed = f;
        if (i == 0 || k % 3 == 0) u.readers++;
      }
    }
  if (n_att != N_TILE || n_prk != n_unp) return false;
  auto sort = [](Ref* r, int n) {
    for (int i = 1; i < n; i++)
      for (int j = i; j > 0 && r[j].t < r[j - 1].t; j--) { Ref x = r[j]; r[j] = r[j - 1]; r[j - 1] = x; }
  };
  for (int i = 0; i < N_TILE; i++) { const int id = (i & 15) * kH + (i >> 4); dem[i] = {use[id].need, nullptr, id}; }
  sort(att, n_att); sort(dem, N_TILE); sort(prk, n_prk); sort(unp, n_unp);
  PlanStats st = {0, 1e18, 1e18, 0, n_prk};
  int n_wr = 0;
  for (int i = 0; i < N_TILE; i++) {
    Op* o = att[i].o;
    o->id = dem[i].id;
    if (!o->flags) o[-1].id = o->id;
    if (dem[i].t - att[i].t < st.slack) st.slack = dem[i].t - att[i].t;
    wr[n_wr++] = {o->t1 - 2 * AHEAD, o, o->id};
  }
  for (int i = 0; i < n_prk; i++) {
    prk[i].o->id = unp[i].o->id;
    prk[i].o->park = unp[i].o->park = i;
    use[N_TILE + i].freed = unp[i].o->t0 + 2 * PUBLISH;
    use[N_TILE + i].readers = 1;
    if (unp[i].t - prk[i].t < st.park_slack) st.park_slack = unp[i].t - prk[i].t;
    wr[n_wr++] = {prk[i].o->t1 - 2 * AHEAD, prk[i].o, N_TILE + i};
  }
  for (int c = 0; c < 2 * n_pair; c++)
    for (int d = 0; d < 2 * n_pair; d++)
      for (Op *f = &op[c][n_op[c] - 1], *o = op[d]; f->n && o->type != OP_END; o++)
        if (o->type == OP_O && (o->flags & P_WIDE) && o->id / kH == f->id / kH) {
          if (f->t0 - o->t1 > 4096.0 * ((P.dbg >> 16) & 255)) f->flags |= P_PRE;
          const double slack = f->t0 + ((f->flags & P_PRE) ? 0 : (f->n - 5) * T_O) - AHEAD - ready(o);
          if (slack < st.park_slack) st.park_slack = slack;
        }
  sort(wr, n_wr);
  int holder[N_TILE];
  for (int i = 0; i < n_wr; i++) {
    int best = -1;
    for (int sl = 0; sl < st.slots; sl++)
      if (use[holder[sl]].freed + margin <= wr[i].t && (best < 0 || use[holder[sl]].freed < use[holder[best]].freed)) best = sl;
    Use& u = use[wr[i].id];
    if (best >= 0) { u.prev = holder[best]; use[u.prev].next = true; wr[i].o->flags |= P_GATE; }
    else if (st.slots == N_TILE) return false;
    else best = st.slots++;
    u.slot = best;
    holder[best] = wr[i].id;
  }
  {
    int pos[N_CL] = {}, flag[ID_PART + 4 * N_TEAM] = {}, seen[ID_PART] = {};
    auto goal = [&](int c) { return op[c][n_op[c] - 1].item0; };
    for (bool moved = true; moved;) {
      moved = false;
      for (int c = 0; c < 2 * n_pair; c++) {
        for (; pos[c] < goal(c); pos[c]++, moved = true) {
          bool ok = true;
          for (const Op* o = op[c]; o->type != OP_END; o++) {
            const int k = pos[c] - o->item0, own = o->type == OP_A ? o->id : N_TILE + o->park;
            if (k < 0 || k >= o->items) continue;
            if (o->type == OP_O) ok = k >= o->n || flag[o->id + k / 3];
            else if (k == o->items - 1 && (o->flags & P_GATE)) ok = seen[use[own].prev] == use[use[own].prev].readers;
            else if (k == 0 && o->type == OP_A && (o->flags & F_PARK)) ok = flag[N_TILE + o->park];
          }
          if (!ok) break;
          for (const Op* o = op[c]; o->type != OP_END; o++) {
            if (pos[c] == o->item0 + o->items + (o[1].type == OP_Q ? 7 : o[1].item0 == goal(c) ? -1 : 5)) {
              if (o->type == OP_A) flag[o->id] = 1;
              if (o->type == OP_Q && (o->flags & F_PARK)) flag[N_TILE + o->park] = 1;
              if (o->type == OP_O) flag[ID_PART + o->id / kH * 4 + o->quarter] = flag[ID_PART + o->id / kH * 4 + o->quarter + 1] = 1;
            }
            const int k = pos[c] - NBAR - o->item0, nw = o->n - TAIL;
            if (k == 0 && o->type == OP_A && (o->flags & F_PARK)) seen[N_TILE + o->park]++;
            if (o->type == OP_O && k >= 0 && k < o->items && (k < nw || k >= o->n) && (k < nw ? k : k - TAIL) % 3 == 2) seen[o->id + (k < nw ? k : k - TAIL) / 3]++;
          }
        }
      }
    }
    for (int c = 0; c < 2 * n_pair; c++) if (pos[c] < goal(c)) return false;
  }
  int n_job = 0, longest = 0;
  for (int t = 0; t < N_TEAM; t++) if (kH - covered[t] / 3 > longest) longest = kH - covered[t] / 3;
  for (int c = 0; c < 2 * n_pair; c++) {
    uint32_t items = 0, cur = 0, pend = 0;
    int n = 0, ev = 0;
    auto item = [&](uint32_t bytes, int count) {
      for (int i = 0; i < count; i++) { if (cur + bytes > RING) cur = 0; cur += bytes; items++; }
    };
    auto event = [&](uint32_t e) { if (ev < MAX_EV) P.prog[c].ev[ev] = e; ev++; };
    for (const Op* o = op[c];; o++) {
      if (o->type != OP_END && phase && (o->type == OP_O) != (phase == 2)) continue;
      uint32_t cw = o->type | (items % NBAR) << 15 | ((items / NBAR) & 1) << 19 | (cur >> 12) << 20 | pend, pw = o->type | o->id << 2 | o->flags;
      const int ps = use[N_TILE + o->park].slot;
      pend = 0;
      if (o->type == OP_O) {
        pw |= o->n << 13 | o->quarter << 20;
        if (o->flags & P_WIDE) {
          cw |= o->n << 2 | (o->id / kH * 4 + o->quarter + 1) << 9 | C_WIDE;
          item(SZ_W, o->n - TAIL);
          item(SZ_O, 2 * TAIL);
          pend = C_PEND;
          for (int i = 0; 3 * i < o->n; i++) event((o->id + i) | E_ON | (use[o->id + i].next ? 0 : E_LAST));
        } else {
          dem[n_job++] = {o->t0 - 1e6 * o->n, nullptr, (int)pw};
          st.own[c] = pw;
          pw = OP_O;
          event(E_DRAW | (items < 16 ? 0 : items - 16));
          for (int i = 0; i <= longest; i++) event(E_JOB | i);
        }
      } else if (o->type != OP_END) {
        const bool parks = o->type == OP_Q && (o->flags & F_PARK);
        cw |= (parks ? ps : use[o->id].slot) << 2 | (o->flags & F_PARK);
        if (o->flags & F_PARK) pw |= o->park << 13 | ps << 20;
        if (o->type == OP_Q) item(SZ_Q, 10);
        else { if (o->flags & F_PARK) { item(SZ_PARK, 1); event((N_TILE + o->park) | E_ON | (use[N_TILE + o->park].next ? 0 : E_LAST)); } item(SZ_KV, 32); }
        if (parks || o->type == OP_A) pend = C_PEND;
        if (o->flags & P_GATE) event(use[parks ? N_TILE + o->park : o->id].prev | E_ON | E_FREE);
      }
      P.prog[c].c[n] = cw; P.prog[c].p[n++] = pw;
      if (o->type == OP_END) { if (o->t0 > st.end) st.end = o->t0; break; }
    }
    if (ev > MAX_EV) return false;
    while (ev < MAX_EV) P.prog[c].ev[ev++] = 0;
    while (n < MAX_OPS) { P.prog[c].c[n] = OP_END; P.prog[c].p[n++] = OP_END; }
    P.first[c] = (uint16_t)(P.prog[c].p[0] & 2047);
  }
  sort(dem, n_job);
  for (int i = 0; i < n_job; i++) P.job[i] = dem[i].id;
  for (int i = 0; i < ID_PART; i++) {
    if (i < N_TILE) P.slot[i] = use[i].slot;
    P.info[i] = (use[i].readers + use[i].next) | (use[i].next ? I_NEXT : 0);
  }
  if (stats) *stats = st;
  return true;
}

const char* const kPrograms[N_CL / 2] = {
  "NNNNNNNNNF4", "NNNNNNNNNF0", "NNNNJf44NNNF7", "PNNNNNNNNNF8", "PNJ664NNNNNF5", "NNNNNNNNNFe",
  "NUNNNNNNNF5", "NNNNNNNNNF6", "NNNNNNNNNFe", "NUNNNJa78NFb", "PNJ281NNNNFc", "PPNJ551NNNNUNF2",
  "NNNNNJc39NNUF2", "NNJ379NNNNF9", "NUNUNJ974NFc", "PNUNNNNNNNF6", "PNJ062NNNNNFd", "NUNNNJd45NNFd",
  "PNNNNNNNNNF8", "NNUJ460Jb60NFf", "NNNNNNNNNFb", "PNJ751NNNNNNF3", "NNNNNNNNNF4", "PNJ172NNNNN",
  "PNNNNNNNNNFa", "NUNNNJe63NNF3", "PNNNNNNNNNF9", "NNNNNNNNNF0", "PNNNNNNNNNFa", "PPNUNNNNNNUF1",
  "NNUNNNNNNF7", "NNNNNJ878NF1", "NUNUNNNNNFf",
};

const char* const* bench_programs() {
  return kPrograms;
}

}

extern "C" void kernel_launch(void* const* d_in, const int* in_sizes, int n_in, void* d_out, int out_size) {
  (void)in_sizes; (void)n_in; (void)out_size;
  static EncodeFn fn = nullptr;
  static int n_clusters = 0;
  if (!fn) {
    cudaDriverEntryPointQueryResult qr;
    void* f = nullptr;
    cudaGetDriverEntryPoint("cuTensorMapEncodeTiled", &f, cudaEnableDefault, &qr);
    fn = (EncodeFn)f;
    cudaFuncSetAttribute(fused_kernel, cudaFuncAttributeMaxDynamicSharedMemorySize, SMEM_BYTES);
    cudaLaunchConfig_t cfg = {};
    cfg.gridDim = dim3(132); cfg.blockDim = dim3(384); cfg.dynamicSmemBytes = SMEM_BYTES;
    cudaLaunchAttribute at[1];
    at[0].id = cudaLaunchAttributeClusterDimension; at[0].val.clusterDim.x = 2; at[0].val.clusterDim.y = 1; at[0].val.clusterDim.z = 1;
    cfg.attrs = at; cfg.numAttrs = 1;
    if (cudaOccupancyMaxActiveClusters(&n_clusters, fused_kernel, &cfg) != cudaSuccess || n_clusters < 1) n_clusters = 1;
    (void)cudaGetLastError();
  }
  static Params P;
  const CUtensorMapSwizzle S128 = CU_TENSOR_MAP_SWIZZLE_128B, S64 = CU_TENSOR_MAP_SWIZZLE_64B;
  for (int blk = 0; blk < 2; blk++) {
    void* const* in = d_in + 5 * blk;
    { const cuuint64_t d[] = {kD, kB * kSq}, s[] = {kD * 2}; const cuuint32_t b[] = {64, 128};
      encode(fn, &P.x[blk], in[0], 2, d, s, b, S128); }
    { const cuuint64_t d[] = {64, 8, 3, (cuuint64_t)kB * kH * kSk / 8}, s[] = {kDh * 2, 128, 8 * kDh * 2}; const cuuint32_t b[] = {64, 8, 3, 8};
      encode(fn, &P.k[blk], in[1], 4, d, s, b, S128);
      encode(fn, &P.v[blk], in[2], 4, d, s, b, S128); }
    { const cuuint64_t d[] = {64, kD, kHD / 64}, s[] = {kHD * 2, 128}; const cuuint32_t b[] = {64, 64, 3};
      encode(fn, &P.wq[blk], in[3], 3, d, s, b, S128); }
    { const cuuint64_t d[] = {32, 2, kHD / 8, 4, kD / 32}, s[] = {kD * 2, 8 * kD * 2, 2 * kD * 2, 64}; const cuuint32_t b[] = {32, 2, 4, 4, 5};
      encode(fn, &P.wo[blk], in[4], 5, d, s, b, S64); }
  }
  { const cuuint64_t d[] = {32, kB * kSq, 2 * kD / 32}, s[] = {2 * kD * 2, 64}; const cuuint32_t b[] = {32, 16, 1};
    encode(fn, &P.out, d_out, 3, d, s, b, S64); }

  P.xw[0] = (const char*)d_in[0]; P.xw[1] = (const char*)d_in[3];
  cudaGetSymbolAddress((void**)&P.g, g_scratch);
  P.dbg = DBG_DEFAULT;
  if (n_clusters >= N_CL && plan(bench_programs(), N_CL / 2, 0, P)) {
    fused_kernel<<<2 * N_CL, 384, SMEM_BYTES>>>(P);
  } else {
    char buf[2 * N_TEAM][16];
    const char* text[2 * N_TEAM];
    for (int i = 0; i < 2 * N_TEAM; i++) { snprintf(buf[i], sizeof(buf[i]), "NNNNNNNNF%x", i / 2); text[i] = buf[i]; }
    for (int phase = 1; phase <= 2; phase++) {
      plan(text, 2 * N_TEAM, phase, P);
      fused_kernel<<<8 * N_TEAM, 384, SMEM_BYTES>>>(P);
    }
  }
}
```

```cpp
#include <cuda_runtime.h>
#include <cuda_bf16.h>
#include <cuda.h>
#include <stdint.h>
#include <stdio.h>

namespace {

constexpr int kB = 8, kSq = 256, kD = 640, kH = 32, kSk = 1024, kDh = 192;
constexpr int kHD = kH * kDh;
constexpr uint32_t RING = 224 * 1024;
constexpr uint32_t SZ_KV = 24576;
constexpr uint32_t SZ_Q = 16384 + 24576;
constexpr uint32_t SZ_O = 16384 + 20480;
constexpr uint32_t SZ_W3 = 16384 + 24576, SZ_W2 = 16384 + 16384, SZ_W = SZ_W3 + 16384;
constexpr uint32_t SZ_PARK = 49152;
constexpr uint32_t SZ_OL = SZ_O + 8192;
constexpr int NBAR = 10;
constexpr int EARLY = 3;
constexpr int kSteps = kHD / 64;
constexpr int TAIL = 4;
constexpr uint32_t KV_CH = 64, KV_SBO = 3072;
constexpr int SMEM_BYTES = RING + 1024 + 1024;
constexpr int N_TEAM = 16, N_CL = 66, MAX_OPS = 24, MAX_EV = 80, N_TILE = N_TEAM * kH, MAX_PARK = 128, ID_PART = N_TILE + MAX_PARK;
enum : uint32_t { OP_END = 0, OP_Q = 1, OP_A = 2, OP_O = 3, F_PARK = 1 << 11,
                  C_WIDE = 1 << 27, C_PEND = 1 << 26, P_GATE = 1 << 12, P_WIDE = 1 << 11, P_LD = 1 << 12, P_PRE = 1 << 22,
                  I_NEXT = 8, E_ON = 1 << 15, E_FREE = 1 << 14, E_LAST = 1 << 13, E_DRAW = 1 << 12, E_JOB = 1 << 11 };

constexpr uint32_t DBG_DEFAULT = 0x040800;

struct alignas(1024) Scratch {
  unsigned int flag[2047];
  unsigned int ticket;
  uint4 part[N_TEAM * 2 * 2 * 5120];
  uint4 tile[N_TILE * 2 * 3072];
};

struct alignas(64) Params {
  const char* xw[2];
  uint16_t first[80];
  Scratch* g;
  uint32_t dbg;
  CUtensorMap x[2], wq[2], k[2], v[2], wo[2], wo3[2], wo2[2], out;
  struct {
    uint32_t c[MAX_OPS];
    uint32_t p[MAX_OPS];
    uint16_t ev[MAX_EV];
  } prog[N_CL];
  uint32_t job[N_CL];
  uint16_t slot[N_TILE];
  uint8_t info[ID_PART];
};

__device__ Scratch g_scratch;

template <int TB, int TA = 0>
__device__ __forceinline__ void wgmma_ss_n64(float (&d)[32], uint64_t da, uint64_t db, int scale_d) {
  asm volatile("{\n.reg .pred p;\nsetp.ne.b32 p, %34, 0;\n"
    "wgmma.mma_async.sync.aligned.m64n64k16.f32.bf16.bf16 {%0, %1, %2, %3, %4, %5, %6, %7, %8, %9, %10, %11, %12, %13, %14, %15, %16, %17, %18, %19, %20, %21, %22, %23, %24, %25, %26, %27, %28, %29, %30, %31}, %32, %33, p, 1, 1, %35, %36;\n}\n"
    : "+f"(d[0]), "+f"(d[1]), "+f"(d[2]), "+f"(d[3]), "+f"(d[4]), "+f"(d[5]), "+f"(d[6]), "+f"(d[7]), "+f"(d[8]), "+f"(d[9]), "+f"(d[10]), "+f"(d[11]), "+f"(d[12]), "+f"(d[13]), "+f"(d[14]), "+f"(d[15]), "+f"(d[16]), "+f"(d[17]), "+f"(d[18]), "+f"(d[19]), "+f"(d[20]), "+f"(d[21]), "+f"(d[22]), "+f"(d[23]), "+f"(d[24]), "+f"(d[25]), "+f"(d[26]), "+f"(d[27]), "+f"(d[28]), "+f"(d[29]), "+f"(d[30]), "+f"(d[31])
    : "l"(da), "l"(db), "r"(scale_d), "n"(TA), "n"(TB));
}
template <int TB>
__device__ __forceinline__ void wgmma_rs_n64(float (&d)[32], uint32_t a0, uint32_t a1, uint32_t a2, uint32_t a3, uint64_t db, int scale_d) {
  asm volatile("{\n.reg .pred p;\nsetp.ne.b32 p, %37, 0;\n"
    "wgmma.mma_async.sync.aligned.m64n64k16.f32.bf16.bf16 {%0, %1, %2, %3, %4, %5, %6, %7, %8, %9, %10, %11, %12, %13, %14, %15, %16, %17, %18, %19, %20, %21, %22, %23, %24, %25, %26, %27, %28, %29, %30, %31}, {%32, %33, %34, %35}, %36, p, 1, 1, %38;\n}\n"
    : "+f"(d[0]), "+f"(d[1]), "+f"(d[2]), "+f"(d[3]), "+f"(d[4]), "+f"(d[5]), "+f"(d[6]), "+f"(d[7]), "+f"(d[8]), "+f"(d[9]), "+f"(d[10]), "+f"(d[11]), "+f"(d[12]), "+f"(d[13]), "+f"(d[14]), "+f"(d[15]), "+f"(d[16]), "+f"(d[17]), "+f"(d[18]), "+f"(d[19]), "+f"(d[20]), "+f"(d[21]), "+f"(d[22]), "+f"(d[23]), "+f"(d[24]), "+f"(d[25]), "+f"(d[26]), "+f"(d[27]), "+f"(d[28]), "+f"(d[29]), "+f"(d[30]), "+f"(d[31])
    : "r"(a0), "r"(a1), "r"(a2), "r"(a3), "l"(db), "r"(scale_d), "n"(TB));
}
template <int TB, int TA = 0>
__device__ __forceinline__ void wgmma_ss_n128(float (&d)[64], uint64_t da, uint64_t db, int scale_d) {
  asm volatile("{\n.reg .pred p;\nsetp.ne.b32 p, %66, 0;\n"
    "wgmma.mma_async.sync.aligned.m64n128k16.f32.bf16.bf16 {%0, %1, %2, %3, %4, %5, %6, %7, %8, %9, %10, %11, %12, %13, %14, %15, %16, %17, %18, %19, %20, %21, %22, %23, %24, %25, %26, %27, %28, %29, %30, %31, %32, %33, %34, %35, %36, %37, %38, %39, %40, %41, %42, %43, %44, %45, %46, %47, %48, %49, %50, %51, %52, %53, %54, %55, %56, %57, %58, %59, %60, %61, %62, %63}, %64, %65, p, 1, 1, %67, %68;\n}\n"
    : "+f"(d[0]), "+f"(d[1]), "+f"(d[2]), "+f"(d[3]), "+f"(d[4]), "+f"(d[5]), "+f"(d[6]), "+f"(d[7]), "+f"(d[8]), "+f"(d[9]), "+f"(d[10]), "+f"(d[11]), "+f"(d[12]), "+f"(d[13]), "+f"(d[14]), "+f"(d[15]), "+f"(d[16]), "+f"(d[17]), "+f"(d[18]), "+f"(d[19]), "+f"(d[20]), "+f"(d[21]), "+f"(d[22]), "+f"(d[23]), "+f"(d[24]), "+f"(d[25]), "+f"(d[26]), "+f"(d[27]), "+f"(d[28]), "+f"(d[29]), "+f"(d[30]), "+f"(d[31]), "+f"(d[32]), "+f"(d[33]), "+f"(d[34]), "+f"(d[35]), "+f"(d[36]), "+f"(d[37]), "+f"(d[38]), "+f"(d[39]), "+f"(d[40]), "+f"(d[41]), "+f"(d[42]), "+f"(d[43]), "+f"(d[44]), "+f"(d[45]), "+f"(d[46]), "+f"(d[47]), "+f"(d[48]), "+f"(d[49]), "+f"(d[50]), "+f"(d[51]), "+f"(d[52]), "+f"(d[53]), "+f"(d[54]), "+f"(d[55]), "+f"(d[56]), "+f"(d[57]), "+f"(d[58]), "+f"(d[59]), "+f"(d[60]), "+f"(d[61]), "+f"(d[62]), "+f"(d[63])
    : "l"(da), "l"(db), "r"(scale_d), "n"(TA), "n"(TB));
}
template <int TB>
__device__ __forceinline__ void wgmma_rs_n128(float (&d)[64], uint32_t a0, uint32_t a1, uint32_t a2, uint32_t a3, uint64_t db, int scale_d) {
  asm volatile("{\n.reg .pred p;\nsetp.ne.b32 p, %69, 0;\n"
    "wgmma.mma_async.sync.aligned.m64n128k16.f32.bf16.bf16 {%0, %1, %2, %3, %4, %5, %6, %7, %8, %9, %10, %11, %12, %13, %14, %15, %16, %17, %18, %19, %20, %21, %22, %23, %24, %25, %26, %27, %28, %29, %30, %31, %32, %33, %34, %35, %36, %37, %38, %39, %40, %41, %42, %43, %44, %45, %46, %47, %48, %49, %50, %51, %52, %53, %54, %55, %56, %57, %58, %59, %60, %61, %62, %63}, {%64, %65, %66, %67}, %68, p, 1, 1, %70;\n}\n"
    : "+f"(d[0]), "+f"(d[1]), "+f"(d[2]), "+f"(d[3]), "+f"(d[4]), "+f"(d[5]), "+f"(d[6]), "+f"(d[7]), "+f"(d[8]), "+f"(d[9]), "+f"(d[10]), "+f"(d[11]), "+f"(d[12]), "+f"(d[13]), "+f"(d[14]), "+f"(d[15]), "+f"(d[16]), "+f"(d[17]), "+f"(d[18]), "+f"(d[19]), "+f"(d[20]), "+f"(d[21]), "+f"(d[22]), "+f"(d[23]), "+f"(d[24]), "+f"(d[25]), "+f"(d[26]), "+f"(d[27]), "+f"(d[28]), "+f"(d[29]), "+f"(d[30]), "+f"(d[31]), "+f"(d[32]), "+f"(d[33]), "+f"(d[34]), "+f"(d[35]), "+f"(d[36]), "+f"(d[37]), "+f"(d[38]), "+f"(d[39]), "+f"(d[40]), "+f"(d[41]), "+f"(d[42]), "+f"(d[43]), "+f"(d[44]), "+f"(d[45]), "+f"(d[46]), "+f"(d[47]), "+f"(d[48]), "+f"(d[49]), "+f"(d[50]), "+f"(d[51]), "+f"(d[52]), "+f"(d[53]), "+f"(d[54]), "+f"(d[55]), "+f"(d[56]), "+f"(d[57]), "+f"(d[58]), "+f"(d[59]), "+f"(d[60]), "+f"(d[61]), "+f"(d[62]), "+f"(d[63])
    : "r"(a0), "r"(a1), "r"(a2), "r"(a3), "l"(db), "r"(scale_d), "n"(TB));
}
template <int TB, int TA = 0>
__device__ __forceinline__ void wgmma_ss_n160(float (&d)[80], uint64_t da, uint64_t db, int scale_d) {
  asm volatile("{\n.reg .pred p;\nsetp.ne.b32 p, %82, 0;\n"
    "wgmma.mma_async.sync.aligned.m64n160k16.f32.bf16.bf16 {%0, %1, %2, %3, %4, %5, %6, %7, %8, %9, %10, %11, %12, %13, %14, %15, %16, %17, %18, %19, %20, %21, %22, %23, %24, %25, %26, %27, %28, %29, %30, %31, %32, %33, %34, %35, %36, %37, %38, %39, %40, %41, %42, %43, %44, %45, %46, %47, %48, %49, %50, %51, %52, %53, %54, %55, %56, %57, %58, %59, %60, %61, %62, %63, %64, %65, %66, %67, %68, %69, %70, %71, %72, %73, %74, %75, %76, %77, %78, %79}, %80, %81, p, 1, 1, %83, %84;\n}\n"
    : "+f"(d[0]), "+f"(d[1]), "+f"(d[2]), "+f"(d[3]), "+f"(d[4]), "+f"(d[5]), "+f"(d[6]), "+f"(d[7]), "+f"(d[8]), "+f"(d[9]), "+f"(d[10]), "+f"(d[11]), "+f"(d[12]), "+f"(d[13]), "+f"(d[14]), "+f"(d[15]), "+f"(d[16]), "+f"(d[17]), "+f"(d[18]), "+f"(d[19]), "+f"(d[20]), "+f"(d[21]), "+f"(d[22]), "+f"(d[23]), "+f"(d[24]), "+f"(d[25]), "+f"(d[26]), "+f"(d[27]), "+f"(d[28]), "+f"(d[29]), "+f"(d[30]), "+f"(d[31]), "+f"(d[32]), "+f"(d[33]), "+f"(d[34]), "+f"(d[35]), "+f"(d[36]), "+f"(d[37]), "+f"(d[38]), "+f"(d[39]), "+f"(d[40]), "+f"(d[41]), "+f"(d[42]), "+f"(d[43]), "+f"(d[44]), "+f"(d[45]), "+f"(d[46]), "+f"(d[47]), "+f"(d[48]), "+f"(d[49]), "+f"(d[50]), "+f"(d[51]), "+f"(d[52]), "+f"(d[53]), "+f"(d[54]), "+f"(d[55]), "+f"(d[56]), "+f"(d[57]), "+f"(d[58]), "+f"(d[59]), "+f"(d[60]), "+f"(d[61]), "+f"(d[62]), "+f"(d[63]), "+f"(d[64]), "+f"(d[65]), "+f"(d[66]), "+f"(d[67]), "+f"(d[68]), "+f"(d[69]), "+f"(d[70]), "+f"(d[71]), "+f"(d[72]), "+f"(d[73]), "+f"(d[74]), "+f"(d[75]), "+f"(d[76]), "+f"(d[77]), "+f"(d[78]), "+f"(d[79])
    : "l"(da), "l"(db), "r"(scale_d), "n"(TA), "n"(TB));
}
template <int TB>
__device__ __forceinline__ void wgmma_rs_n160(float (&d)[80], uint32_t a0, uint32_t a1, uint32_t a2, uint32_t a3, uint64_t db, int scale_d) {
  asm volatile("{\n.reg .pred p;\nsetp.ne.b32 p, %85, 0;\n"
    "wgmma.mma_async.sync.aligned.m64n160k16.f32.bf16.bf16 {%0, %1, %2, %3, %4, %5, %6, %7, %8, %9, %10, %11, %12, %13, %14, %15, %16, %17, %18, %19, %20, %21, %22, %23, %24, %25, %26, %27, %28, %29, %30, %31, %32, %33, %34, %35, %36, %37, %38, %39, %40, %41, %42, %43, %44, %45, %46, %47, %48, %49, %50, %51, %52, %53, %54, %55, %56, %57, %58, %59, %60, %61, %62, %63, %64, %65, %66, %67, %68, %69, %70, %71, %72, %73, %74, %75, %76, %77, %78, %79}, {%80, %81, %82, %83}, %84, p, 1, 1, %86;\n}\n"
    : "+f"(d[0]), "+f"(d[1]), "+f"(d[2]), "+f"(d[3]), "+f"(d[4]), "+f"(d[5]), "+f"(d[6]), "+f"(d[7]), "+f"(d[8]), "+f"(d[9]), "+f"(d[10]), "+f"(d[11]), "+f"(d[12]), "+f"(d[13]), "+f"(d[14]), "+f"(d[15]), "+f"(d[16]), "+f"(d[17]), "+f"(d[18]), "+f"(d[19]), "+f"(d[20]), "+f"(d[21]), "+f"(d[22]), "+f"(d[23]), "+f"(d[24]), "+f"(d[25]), "+f"(d[26]), "+f"(d[27]), "+f"(d[28]), "+f"(d[29]), "+f"(d[30]), "+f"(d[31]), "+f"(d[32]), "+f"(d[33]), "+f"(d[34]), "+f"(d[35]), "+f"(d[36]), "+f"(d[37]), "+f"(d[38]), "+f"(d[39]), "+f"(d[40]), "+f"(d[41]), "+f"(d[42]), "+f"(d[43]), "+f"(d[44]), "+f"(d[45]), "+f"(d[46]), "+f"(d[47]), "+f"(d[48]), "+f"(d[49]), "+f"(d[50]), "+f"(d[51]), "+f"(d[52]), "+f"(d[53]), "+f"(d[54]), "+f"(d[55]), "+f"(d[56]), "+f"(d[57]), "+f"(d[58]), "+f"(d[59]), "+f"(d[60]), "+f"(d[61]), "+f"(d[62]), "+f"(d[63]), "+f"(d[64]), "+f"(d[65]), "+f"(d[66]), "+f"(d[67]), "+f"(d[68]), "+f"(d[69]), "+f"(d[70]), "+f"(d[71]), "+f"(d[72]), "+f"(d[73]), "+f"(d[74]), "+f"(d[75]), "+f"(d[76]), "+f"(d[77]), "+f"(d[78]), "+f"(d[79])
    : "r"(a0), "r"(a1), "r"(a2), "r"(a3), "l"(db), "r"(scale_d), "n"(TB));
}
template <int TB, int TA = 0>
__device__ __forceinline__ void wgmma_ss_n192(float (&d)[96], uint64_t da, uint64_t db, int scale_d) {
  asm volatile("{\n.reg .pred p;\nsetp.ne.b32 p, %98, 0;\n"
    "wgmma.mma_async.sync.aligned.m64n192k16.f32.bf16.bf16 {%0, %1, %2, %3, %4, %5, %6, %7, %8, %9, %10, %11, %12, %13, %14, %15, %16, %17, %18, %19, %20, %21, %22, %23, %24, %25, %26, %27, %28, %29, %30, %31, %32, %33, %34, %35, %36, %37, %38, %39, %40, %41, %42, %43, %44, %45, %46, %47, %48, %49, %50, %51, %52, %53, %54, %55, %56, %57, %58, %59, %60, %61, %62, %63, %64, %65, %66, %67, %68, %69, %70, %71, %72, %73, %74, %75, %76, %77, %78, %79, %80, %81, %82, %83, %84, %85, %86, %87, %88, %89, %90, %91, %92, %93, %94, %95}, %96, %97, p, 1, 1, %99, %100;\n}\n"
    : "+f"(d[0]), "+f"(d[1]), "+f"(d[2]), "+f"(d[3]), "+f"(d[4]), "+f"(d[5]), "+f"(d[6]), "+f"(d[7]), "+f"(d[8]), "+f"(d[9]), "+f"(d[10]), "+f"(d[11]), "+f"(d[12]), "+f"(d[13]), "+f"(d[14]), "+f"(d[15]), "+f"(d[16]), "+f"(d[17]), "+f"(d[18]), "+f"(d[19]), "+f"(d[20]), "+f"(d[21]), "+f"(d[22]), "+f"(d[23]), "+f"(d[24]), "+f"(d[25]), "+f"(d[26]), "+f"(d[27]), "+f"(d[28]), "+f"(d[29]), "+f"(d[30]), "+f"(d[31]), "+f"(d[32]), "+f"(d[33]), "+f"(d[34]), "+f"(d[35]), "+f"(d[36]), "+f"(d[37]), "+f"(d[38]), "+f"(d[39]), "+f"(d[40]), "+f"(d[41]), "+f"(d[42]), "+f"(d[43]), "+f"(d[44]), "+f"(d[45]), "+f"(d[46]), "+f"(d[47]), "+f"(d[48]), "+f"(d[49]), "+f"(d[50]), "+f"(d[51]), "+f"(d[52]), "+f"(d[53]), "+f"(d[54]), "+f"(d[55]), "+f"(d[56]), "+f"(d[57]), "+f"(d[58]), "+f"(d[59]), "+f"(d[60]), "+f"(d[61]), "+f"(d[62]), "+f"(d[63]), "+f"(d[64]), "+f"(d[65]), "+f"(d[66]), "+f"(d[67]), "+f"(d[68]), "+f"(d[69]), "+f"(d[70]), "+f"(d[71]), "+f"(d[72]), "+f"(d[73]), "+f"(d[74]), "+f"(d[75]), "+f"(d[76]), "+f"(d[77]), "+f"(d[78]), "+f"(d[79]), "+f"(d[80]), "+f"(d[81]), "+f"(d[82]), "+f"(d[83]), "+f"(d[84]), "+f"(d[85]), "+f"(d[86]), "+f"(d[87]), "+f"(d[88]), "+f"(d[89]), "+f"(d[90]), "+f"(d[91]), "+f"(d[92]), "+f"(d[93]), "+f"(d[94]), "+f"(d[95])
    : "l"(da), "l"(db), "r"(scale_d), "n"(TA), "n"(TB));
}
template <int TB>
__device__ __forceinline__ void wgmma_rs_n192(float (&d)[96], uint32_t a0, uint32_t a1, uint32_t a2, uint32_t a3, uint64_t db, int scale_d) {
  asm volatile("{\n.reg .pred p;\nsetp.ne.b32 p, %101, 0;\n"
    "wgmma.mma_async.sync.aligned.m64n192k16.f32.bf16.bf16 {%0, %1, %2, %3, %4, %5, %6, %7, %8, %9, %10, %11, %12, %13, %14, %15, %16, %17, %18, %19, %20, %21, %22, %23, %24, %25, %26, %27, %28, %29, %30, %31, %32, %33, %34, %35, %36, %37, %38, %39, %40, %41, %42, %43, %44, %45, %46, %47, %48, %49, %50, %51, %52, %53, %54, %55, %56, %57, %58, %59, %60, %61, %62, %63, %64, %65, %66, %67, %68, %69, %70, %71, %72, %73, %74, %75, %76, %77, %78, %79, %80, %81, %82, %83, %84, %85, %86, %87, %88, %89, %90, %91, %92, %93, %94, %95}, {%96, %97, %98, %99}, %100, p, 1, 1, %102;\n}\n"
    : "+f"(d[0]), "+f"(d[1]), "+f"(d[2]), "+f"(d[3]), "+f"(d[4]), "+f"(d[5]), "+f"(d[6]), "+f"(d[7]), "+f"(d[8]), "+f"(d[9]), "+f"(d[10]), "+f"(d[11]), "+f"(d[12]), "+f"(d[13]), "+f"(d[14]), "+f"(d[15]), "+f"(d[16]), "+f"(d[17]), "+f"(d[18]), "+f"(d[19]), "+f"(d[20]), "+f"(d[21]), "+f"(d[22]), "+f"(d[23]), "+f"(d[24]), "+f"(d[25]), "+f"(d[26]), "+f"(d[27]), "+f"(d[28]), "+f"(d[29]), "+f"(d[30]), "+f"(d[31]), "+f"(d[32]), "+f"(d[33]), "+f"(d[34]), "+f"(d[35]), "+f"(d[36]), "+f"(d[37]), "+f"(d[38]), "+f"(d[39]), "+f"(d[40]), "+f"(d[41]), "+f"(d[42]), "+f"(d[43]), "+f"(d[44]), "+f"(d[45]), "+f"(d[46]), "+f"(d[47]), "+f"(d[48]), "+f"(d[49]), "+f"(d[50]), "+f"(d[51]), "+f"(d[52]), "+f"(d[53]), "+f"(d[54]), "+f"(d[55]), "+f"(d[56]), "+f"(d[57]), "+f"(d[58]), "+f"(d[59]), "+f"(d[60]), "+f"(d[61]), "+f"(d[62]), "+f"(d[63]), "+f"(d[64]), "+f"(d[65]), "+f"(d[66]), "+f"(d[67]), "+f"(d[68]), "+f"(d[69]), "+f"(d[70]), "+f"(d[71]), "+f"(d[72]), "+f"(d[73]), "+f"(d[74]), "+f"(d[75]), "+f"(d[76]), "+f"(d[77]), "+f"(d[78]), "+f"(d[79]), "+f"(d[80]), "+f"(d[81]), "+f"(d[82]), "+f"(d[83]), "+f"(d[84]), "+f"(d[85]), "+f"(d[86]), "+f"(d[87]), "+f"(d[88]), "+f"(d[89]), "+f"(d[90]), "+f"(d[91]), "+f"(d[92]), "+f"(d[93]), "+f"(d[94]), "+f"(d[95])
    : "r"(a0), "r"(a1), "r"(a2), "r"(a3), "l"(db), "r"(scale_d), "n"(TB));
}

__device__ __forceinline__ uint32_t smem_u32(const void* p) { return (uint32_t)__cvta_generic_to_shared(p); }
__device__ __forceinline__ void wg_fence() { asm volatile("wgmma.fence.sync.aligned;" ::: "memory"); }
__device__ __forceinline__ void wg_commit() { asm volatile("wgmma.commit_group.sync.aligned;" ::: "memory"); }
template <int N> __device__ __forceinline__ void wg_wait() { asm volatile("wgmma.wait_group.sync.aligned %0;" ::"n"(N) : "memory"); }
__device__ __forceinline__ void sched_fence(uint32_t& keep, bool never) {
  asm volatile("{\n.reg .pred p;\nsetp.ne.b32 p, %1, 0;\n@p mov.u32 %0, %%clock;\n}\n" : "+r"(keep) : "r"((int)never) : "memory");
}
template <int N> __device__ __forceinline__ void fence_regs(float (&r)[N]) {
#pragma unroll
  for (int i = 0; i < N; i++) asm volatile("" : "+f"(r[i])::"memory");
}
template <int N> __device__ __forceinline__ void undefine(float (&r)[N]) {
#pragma unroll
  for (int i = 0; i < N; i++) asm volatile("" : "=f"(r[i]));
}
template <int N> __device__ __forceinline__ void fence_regs(uint32_t (&r)[N]) {
#pragma unroll
  for (int i = 0; i < N; i++) asm volatile("" : "+r"(r[i])::"memory");
}
__device__ __forceinline__ uint64_t mk_desc(uint32_t a16, uint32_t lbo, uint32_t sbo, uint32_t swz) {
  uint64_t d;
  asm("mov.b64 %0, {%1, %2};" : "=l"(d) : "r"(a16 + ((lbo >> 4) << 16)), "r"((sbo >> 4) | (swz << 30)));
  return d;
}
__device__ __forceinline__ void mbar_init(uint32_t bar, uint32_t cnt) {
  asm volatile("mbarrier.init.shared::cta.b64 [%0], %1;" ::"r"(bar), "r"(cnt) : "memory");
}
__device__ __forceinline__ void mbar_expect(uint32_t bar, uint32_t tx) {
  asm volatile("mbarrier.arrive.expect_tx.shared::cta.b64 _, [%0], %1;" ::"r"(bar), "r"(tx) : "memory");
}
__device__ __forceinline__ bool mbar_test(uint32_t bar, uint32_t ph) {
  uint32_t ok;
  asm volatile("{\n.reg .pred p;\nmbarrier.test_wait.parity.shared::cta.b64 p, [%1], %2;\nselp.u32 %0, 1, 0, p;\n}\n"
               : "=r"(ok) : "r"(bar), "r"(ph) : "memory");
  return ok;
}
__device__ __forceinline__ bool mbar_try(uint32_t bar, uint32_t ph, uint32_t ns) {
  uint32_t ok;
  asm volatile("{\n.reg .pred p;\nmbarrier.try_wait.parity.shared::cta.b64 p, [%1], %2, %3;\nselp.u32 %0, 1, 0, p;\n}\n"
               : "=r"(ok) : "r"(bar), "r"(ph), "r"(ns) : "memory");
  return ok;
}
__device__ __forceinline__ void mbar_wait(uint32_t bar, uint32_t ph) {
  asm volatile("{\n.reg .pred p;\n.reg .u32 n;\nmov.u32 n, 0;\n"
               "LOOP:\nmbarrier.try_wait.parity.shared::cta.b64 p, [%0], %1;\n@p bra DONE;\n"
               "add.u32 n, n, 1;\nsetp.lt.u32 p, n, 0x1000000;\n@p bra LOOP;\ntrap;\n"
               "DONE:\n}\n" ::"r"(bar), "r"(ph) : "memory");
}
__device__ __forceinline__ void mbar_wait_long(uint32_t bar) {
  asm volatile("{\n.reg .pred p;\n.reg .u32 n;\nmov.u32 n, 0;\n"
               "LOOP:\nmbarrier.try_wait.parity.shared::cta.b64 p, [%0], 0, 20000;\n@p bra DONE;\n"
               "add.u32 n, n, 1;\nsetp.lt.u32 p, n, 0x100000;\n@p bra LOOP;\ntrap;\n"
               "DONE:\n}\n" ::"r"(bar) : "memory");
}
__device__ __forceinline__ void mbar_arrive_cluster_if(bool on, uint32_t addr) {
  asm volatile("{\n.reg .pred p;\nsetp.ne.b32 p, %1, 0;\n@p mbarrier.arrive.shared::cluster.b64 _, [%0];\n}\n" ::"r"(addr), "r"((int)on) : "memory");
}
__device__ __forceinline__ void mbar_arrive_cluster_n(uint32_t n, uint32_t addr) {
  asm volatile("{\n.reg .pred p;\nsetp.ne.b32 p, %1, 0;\n@p mbarrier.arrive.shared::cluster.b64 _, [%0], %1;\n}\n" ::"r"(addr), "r"(n) : "memory");
}
__device__ __forceinline__ void tma2d(uint32_t dst, const CUtensorMap* m, uint32_t bar, int c0, int c1) {
  asm volatile("cp.async.bulk.tensor.2d.shared::cluster.global.mbarrier::complete_tx::bytes [%0], [%1, {%3, %4}], [%2];"
               ::"r"(dst), "l"(m), "r"(bar), "r"(c0), "r"(c1) : "memory");
}
__device__ __forceinline__ void tma3d(uint32_t dst, const CUtensorMap* m, uint32_t bar, int c0, int c1, int c2) {
  asm volatile("cp.async.bulk.tensor.3d.shared::cluster.global.mbarrier::complete_tx::bytes [%0], [%1, {%3, %4, %5}], [%2];"
               ::"r"(dst), "l"(m), "r"(bar), "r"(c0), "r"(c1), "r"(c2) : "memory");
}
__device__ __forceinline__ void tma3d_mc(uint32_t dst, const CUtensorMap* m, uint32_t bar, int c0, int c1, int c2) {
  asm volatile("cp.async.bulk.tensor.3d.shared::cluster.global.mbarrier::complete_tx::bytes.multicast::cluster"
               " [%0], [%1, {%3, %4, %5}], [%2], %6;"
               ::"r"(dst), "l"(m), "r"(bar), "r"(c0), "r"(c1), "r"(c2), "h"((uint16_t)3) : "memory");
}
__device__ __forceinline__ void tma3d_store(const CUtensorMap* m, uint32_t src, int c0, int c1, int c2) {
  asm volatile("cp.async.bulk.tensor.3d.global.shared::cta.bulk_group [%0, {%2, %3, %4}], [%1];"
               ::"l"(m), "r"(src), "r"(c0), "r"(c1), "r"(c2) : "memory");
}
__device__ __forceinline__ void bar_sync(int id, int n) { asm volatile("bar.sync %0, %1;" ::"r"(id), "r"(n) : "memory"); }
__device__ __forceinline__ uint32_t pack_bf16(float lo, float hi) {
  uint32_t r;
  asm("cvt.rn.bf16x2.f32 %0, %1, %2;" : "=r"(r) : "f"(hi), "f"(lo));
  return r;
}
__device__ __forceinline__ float ex2(float x) {
  float y;
  asm("ex2.approx.ftz.f32 %0, %1;" : "=f"(y) : "f"(x));
  return y;
}
__device__ __forceinline__ float rcp(float x) {
  float y;
  asm("rcp.approx.ftz.f32 %0, %1;" : "=f"(y) : "f"(x));
  return y;
}
__device__ __forceinline__ void stsm4(uint32_t addr, uint32_t a, uint32_t b, uint32_t c, uint32_t d) {
  asm volatile("stmatrix.sync.aligned.m8n8.x4.shared.b16 [%0], {%1, %2, %3, %4};" ::"r"(addr), "r"(a), "r"(b), "r"(c), "r"(d) : "memory");
}

__device__ __forceinline__ void tma4d_mc_hint(uint32_t dst, const CUtensorMap* m, uint32_t bar, int c3, uint64_t pol) {
  asm volatile("cp.async.bulk.tensor.4d.shared::cluster.global.mbarrier::complete_tx::bytes.multicast::cluster.L2::cache_hint"
               " [%0], [%1, {%3, %3, %3, %4}], [%2], %5, %6;"
               ::"r"(dst), "l"(m), "r"(bar), "r"(0), "r"(c3), "h"((uint16_t)3), "l"(pol) : "memory");
}
__device__ __forceinline__ void tma5d_mc(uint32_t dst, const CUtensorMap* m, uint32_t bar, int c2, int c4) {
  asm volatile("cp.async.bulk.tensor.5d.shared::cluster.global.mbarrier::complete_tx::bytes.multicast::cluster"
               " [%0], [%1, {%3, %3, %4, %3, %5}], [%2], %6;"
               ::"r"(dst), "l"(m), "r"(bar), "r"(0), "r"(c2), "r"(c4), "h"((uint16_t)3) : "memory");
}
__device__ __forceinline__ void bulk_load_hint(uint32_t dst, const void* src, uint32_t bytes, uint32_t bar, uint64_t pol) {
  asm volatile("cp.async.bulk.shared::cluster.global.mbarrier::complete_tx::bytes.L2::cache_hint [%0], [%1], %2, [%3], %4;"
               ::"r"(dst), "l"(src), "r"(bytes), "r"(bar), "l"(pol) : "memory");
}
__device__ __forceinline__ void stg2_if(bool on, void* p, uint32_t a, uint32_t b, uint32_t c, uint32_t d, uint32_t e, uint32_t f,
                                        uint32_t g, uint32_t h, uint64_t pol) {
  asm volatile("{\n.reg .pred p;\nsetp.ne.b32 p, %10, 0;\n"
               "@p st.global.L2::cache_hint.v4.b32 [%0], {%1, %2, %3, %4}, %9;\n"
               "@p st.global.L2::cache_hint.v4.b32 [%0 + 512], {%5, %6, %7, %8}, %9;\n}\n"
               ::"l"(p), "r"(a), "r"(b), "r"(c), "r"(d), "r"(e), "r"(f), "r"(g), "r"(h), "l"(pol), "r"((int)on) : "memory");
}
__device__ __forceinline__ uint64_t evict_first() {
  uint64_t p;
  asm("createpolicy.fractional.L2::evict_first.b64 %0, 1.0;" : "=l"(p));
  return p;
}
__device__ __forceinline__ bool elect() {
  uint32_t ok;
  asm volatile("{\n.reg .pred p;\nelect.sync _|p, 0xffffffff;\nselp.u32 %0, 1, 0, p;\n}\n" : "=r"(ok));
  return ok;
}
__device__ __forceinline__ void mbar_arrive(uint32_t bar) {
  asm volatile("mbarrier.arrive.shared::cta.b64 _, [%0];" ::"r"(bar) : "memory");
}
__device__ __forceinline__ void mbar_arrive_if(bool on, uint32_t bar) {
  asm volatile("{\n.reg .pred p;\nsetp.ne.b32 p, %1, 0;\n@p mbarrier.arrive.shared::cta.b64 _, [%0];\n}\n" ::"r"(bar), "r"((int)on) : "memory");
}
__device__ __forceinline__ void lds2_if(bool on, uint32_t p, uint32_t (&t)[8]) {
  asm volatile("{\n.reg .pred p;\nsetp.ne.b32 p, %9, 0;\n@p ld.shared.v4.b32 {%0, %1, %2, %3}, [%8];\n@p ld.shared.v4.b32 {%4, %5, %6, %7}, [%8 + 512];\n}\n"
               : "+r"(t[0]), "+r"(t[1]), "+r"(t[2]), "+r"(t[3]), "+r"(t[4]), "+r"(t[5]), "+r"(t[6]), "+r"(t[7]) : "r"(p), "r"((int)on) : "memory");
}
__device__ __forceinline__ void lds128(uint32_t p, uint32_t& a, uint32_t& b, uint32_t& c, uint32_t& d) {
  asm volatile("ld.shared.v4.b32 {%0, %1, %2, %3}, [%4];" : "=r"(a), "=r"(b), "=r"(c), "=r"(d) : "r"(p) : "memory");
}
template <class T> __device__ __forceinline__ T* ptr_add(T* base, uint32_t bytes) {
  T* r;
  asm("{\n.reg .u32 lo, hi;\nmov.b64 {lo, hi}, %1;\nadd.cc.u32 lo, lo, %2;\naddc.u32 hi, hi, 0;\nmov.b64 %0, {lo, hi};\n}\n" : "=l"(r) : "l"(base), "r"(bytes));
  return r;
}
__device__ __forceinline__ uint32_t lds32(uint32_t p) {
  uint32_t v;
  asm volatile("ld.volatile.shared.u32 %0, [%1];" : "=r"(v) : "r"(p) : "memory");
  return v;
}
__device__ __forceinline__ uint32_t flag_get(const unsigned int* p) {
  uint32_t v;
  asm volatile("ld.acquire.gpu.global.u32 %0, [%1];" : "=r"(v) : "l"(p) : "memory");
  return v;
}
__device__ __forceinline__ uint32_t wait_word(uint32_t p, uint32_t target) {
  uint32_t v;
  asm volatile("{\n.reg .pred p;\n.reg .u32 n;\nmov.u32 n, 0;\n"
               "LOOP:\nld.acquire.cta.shared.u32 %0, [%1];\nsetp.ge.u32 p, %0, %2;\n@p bra DONE;\n"
               "nanosleep.u32 %3;\nadd.u32 n, n, 1;\nsetp.lt.u32 p, n, 0x400000;\n@p bra LOOP;\ntrap;\n"
               "DONE:\n}\n" : "=r"(v) : "r"(p), "r"(target), "n"(400) : "memory");
  return v;
}
__device__ __forceinline__ void flag_set(unsigned int* p, uint32_t v) {
  asm volatile("st.release.gpu.global.u32 [%0], %1;" ::"l"(p), "r"(v) : "memory");
}
__device__ __forceinline__ void flag_dec(unsigned int* p) {
  asm volatile("red.relaxed.gpu.global.add.u32 [%0], 0xffffffff;" ::"l"(p) : "memory");
}

struct Cursor {
  int bi;
  uint32_t ph;
  __device__ __forceinline__ void next() {
    if (++bi == NBAR) { bi = 0; ph ^= 1; }
  }
};

constexpr float kScaleLog2 = 0.07216878364870322f * 1.4426950408889634f;
constexpr float kSumLimit = 1048576.0f;

__global__ void __cluster_dims__(2, 1, 1) __launch_bounds__(384, 1)
fused_kernel(const __grid_constant__ Params P) {
  extern __shared__ uint8_t smem_raw[];
  const uint32_t sbase = (smem_u32(smem_raw) + 1023) & ~1023u;
  const uint32_t full0 = sbase + RING, empty0 = full0 + 8 * NBAR, odone0 = empty0 + 8 * NBAR, ev0 = odone0 + 8 * MAX_OPS;
  const uint32_t progress = ev0 + 8 * MAX_EV, jobw = progress + 4;
  const uint32_t rank = blockIdx.x & 1;
  const int role = blockIdx.x >> 1;
  const int wid = __shfl_sync(0xffffffffu, (int)(threadIdx.x >> 5), 0);
  const int wg = wid >> 2;

  if (wid < 8) {
    if (elect()) {
#pragma unroll
      for (int j = 0; j < 16; j++) {
        const int i = EARLY + 16 * wid + j;
        if (i < 2 * NBAR + MAX_OPS + MAX_EV) mbar_init(full0 + 8 * i, i < NBAR ? 1 : i < 2 * NBAR ? 16 : i < 2 * NBAR + MAX_OPS ? 8 : 1);
      }
      if (wid == 7) asm volatile("st.shared.v2.u32 [%0], {0, 0};\nfence.acq_rel.cta;" ::"r"(progress) : "memory");
      asm volatile("fence.mbarrier_init.release.cluster;" ::: "memory");
    }
  } else if (wid > 8) {
    const uint32_t g = blockIdx.x * 96 + threadIdx.x - 288, w = g - 2048;
    if (g < 4096) asm volatile("prefetch.global.L2 [%0];" ::"l"(g < 2048 ? P.xw[0] + g * (kD * 2) : P.xw[1] + (w >> 5) * (kHD * 2) + (w & 31) * 128));
  } else {
    const uint32_t op0 = P.first[role];
    if (elect()) {
#pragma unroll
      for (int k = 0; k < EARLY; k++) mbar_init(full0 + 8 * k, 1);
      asm volatile("fence.mbarrier_init.release.cluster;" ::: "memory");
      const int blk = (op0 >> 10) & 1;
      if ((op0 & 3) == OP_Q) {
#pragma unroll
        for (int k = 0; k < EARLY; k++) {
          mbar_expect(full0 + 8 * k, SZ_Q);
          tma2d(sbase + k * SZ_Q, &P.x[blk], full0 + 8 * k, 64 * k, ((op0 >> 7) & 7) * kSq + rank * 128);
          tma3d(sbase + k * SZ_Q + 16384, &P.wq[blk], full0 + 8 * k, 0, 64 * k, 3 * ((op0 >> 2) & 31));
        }
      }
      asm volatile("prefetch.tensormap [%0];" ::"l"(rank ? &P.v[blk] : &P.k[blk]) : "memory");
    }
  }
  __syncwarp();
  asm volatile("barrier.cluster.arrive.relaxed.aligned;\nbarrier.cluster.wait.aligned;" ::: "memory");

  if (wg < 2) {
    asm volatile("setmaxnreg.inc.sync.aligned.u32 240;");
    const uint32_t* prog = P.prog[role].c;
    const int lane = threadIdx.x & 31, warp = wid & 3;
    uint32_t empty_rem;
    asm volatile("mapa.shared::cluster.u32 %0, %1, %2;" : "=r"(empty_rem) : "r"(empty0), "r"(lane & 1));
    uint32_t keep = (threadIdx.x & 127) < 2 ? 4 : 0;
    auto release = [&](int slot) { mbar_arrive_cluster_n(keep, empty_rem + 8 * slot); };
    auto release_warp = [&](int slot, bool on = true) { mbar_arrive_cluster_if(lane < 2 && on, empty_rem + 8 * slot); };
    Cursor r{0, 0};
    const uint32_t ring16 = (sbase & 0x3FFFF) >> 4;
    uint32_t cur = ring16;
    bool rdy0 = false, rdy1 = false;
    auto probe1 = [&]() { rdy0 = mbar_test(full0 + 8 * r.bi, r.ph); };
    auto probe2 = [&]() {
      Cursor n = r;
      rdy0 = mbar_test(full0 + 8 * n.bi, n.ph);
      n.next();
      rdy1 = mbar_test(full0 + 8 * n.bi, n.ph);
    };
    auto take = [&](bool rdy, uint32_t bytes, uint32_t& addr) {
      const int bi = r.bi;
      if (__builtin_expect(!__all_sync(0xffffffffu, rdy), 0)) mbar_wait(full0 + 8 * r.bi, r.ph);
      r.next();
      if (cur > ring16 + ((RING - bytes) >> 4)) cur = ring16;
      addr = cur;
      cur += bytes >> 4;
      return bi;
    };
    const bool never = P.dbg == 0xffffffffu;
    uint32_t q[48];
#pragma unroll
    for (int i = 0; i < 48; i++) q[i] = 0;
    const int row = wg * 64 + warp * 16 + (lane >> 2);
    const int img0 = row * 4 + ((lane & 3) ^ ((row >> 1) & 3));
    uint4* pend = nullptr;
    bool pend_any = false;
    const uint64_t spol = evict_first();
    int pc = 0;
    auto slab = [&](int c, int i0) {
#pragma unroll
      for (int i = i0; i < 6; i++)
        stg2_if(c == i, pend + i * 512, q[8 * i], q[8 * i + 1], q[8 * i + 2], q[8 * i + 3],
                q[8 * i + 4], q[8 * i + 5], q[8 * i + 6], q[8 * i + 7], spol);
    };
    auto drain = [&](int c) {
      if (!pend_any || c >= 6) return;
      slab(c, 0);
      if (c == 5) {
        __syncwarp();
        mbar_arrive_if(lane == 0, odone0 - 8 + 8 * pc);
      }
    };

    for (;; pc++) {
      uint32_t op = prog[pc];
      const int type = op & 3;
      auto enter = [&]() {
        r.bi = (op >> 15) & 15; r.ph = (op >> 19) & 1; cur = ring16 + (((op >> 20) & 63) << 8);
      };
      enter();
      pend_any = op & C_PEND;
      uint32_t job = 0;
      if ((op & (3 | C_WIDE)) == OP_O) job = __shfl_sync(0xffffffffu, wait_word(jobw, 1), 0);
      if (type == OP_END || job == OP_O) {
#pragma unroll 1
        for (int c = 0; c < 6; c++) drain(c);
        asm volatile("barrier.cluster.arrive.relaxed;" ::: "memory");
        break;
      }
      {
        float s[32], o[96];
        uint32_t ad0;
        int bi0, sk1;
        uint32_t pa[16], pb[16];
        float mc0, mc1, l0, l1;
        bool shifted;
        uint32_t nop;
        auto expo = [&](float (&s)[32], uint32_t (&pout)[16], float& b0, float& b1, bool shift, auto mid) {
          float c0, c1;
#pragma unroll
          for (int i = 0; i < 8; i++) {
            const float e0 = ex2(shift ? s[4 * i] - mc0 : s[4 * i]), e1 = ex2(shift ? s[4 * i + 1] - mc0 : s[4 * i + 1]);
            const float e2 = ex2(shift ? s[4 * i + 2] - mc1 : s[4 * i + 2]), e3 = ex2(shift ? s[4 * i + 3] - mc1 : s[4 * i + 3]);
            if (i) { b0 += e0; c0 += e1; b1 += e2; c1 += e3; } else { b0 = e0; c0 = e1; b1 = e2; c1 = e3; }
            pout[2 * i] = pack_bf16(e0, e1); pout[2 * i + 1] = pack_bf16(e2, e3);
            if (i & 1) mid(i >> 1);
          }
          b0 += c0; b1 += c1;
        };
        auto rowmax = [&](float (&s)[32], float& m0, float& m1) {
          m0 = fmaxf(s[0], s[1]); m1 = fmaxf(s[2], s[3]);
#pragma unroll
          for (int i = 1; i < 8; i++) { m0 = fmaxf(m0, fmaxf(s[4 * i], s[4 * i + 1])); m1 = fmaxf(m1, fmaxf(s[4 * i + 2], s[4 * i + 3])); }
          m0 = fmaxf(m0, __shfl_xor_sync(0xffffffffu, m0, 1)); m1 = fmaxf(m1, __shfl_xor_sync(0xffffffffu, m1, 1));
          m0 = fmaxf(m0, __shfl_xor_sync(0xffffffffu, m0, 2)); m1 = fmaxf(m1, __shfl_xor_sync(0xffffffffu, m1, 2));
        };
        auto first = [&](float (&s)[32], int sk0, auto mid) {
          fence_regs(s);
          release(sk0);
          mc0 = 0.f; mc1 = 0.f;
          expo(s, pa, l0, l1, false, mid);
          shifted = __any_sync(0xffffffffu, !(fmaxf(l0, l1) <= kSumLimit && fminf(l0, l1) >= 1.f / kSumLimit));
          if (shifted) {
            rowmax(s, mc0, mc1);
            expo(s, pa, l0, l1, true, [](int) {});
          }
        };
        auto qk = [&](float (&s)[32], uint32_t ak, int k0 = 0, int k1 = 12) {
#pragma unroll
          for (int kk = k0; kk < k1; kk++)
            wgmma_rs_n64<0>(s, q[4 * kk], q[4 * kk + 1], q[4 * kk + 2], q[4 * kk + 3], mk_desc(ak, 16, KV_SBO, 1) + ((kk >> 2) * KV_CH + (kk & 3) * 2), kk != 0);
          if (k1 == 12) wg_commit();
        };
        auto pv = [&](uint32_t (&pin)[16], uint32_t av, int acc) {
#pragma unroll
          for (int kk = 0; kk < 4; kk++)
            wgmma_rs_n192<1>(o, pin[4 * kk], pin[4 * kk + 1], pin[4 * kk + 2], pin[4 * kk + 3], mk_desc(av, KV_CH * 16, KV_SBO, 1) + (kk * (KV_SBO / 8)), acc || (kk != 0));
          wg_commit();
        };
        auto finish = [&](uint32_t (&pout)[16], int sk, int sv) {
          probe2();
          wg_wait<1>();
          fence_regs(s);
          release(sk);
          float b0, b1;
#pragma unroll 1
          for (bool redo = false;; redo = true) {
            expo(s, pout, b0, b1, false, [](int) {});
            if (!__any_sync(0xffffffffu, !redo && (shifted || !(fmaxf(b0, b1) <= kSumLimit)))) break;
            shifted = true;
            rowmax(s, b0, b1);
            b0 = fmaxf(mc0, b0); b1 = fmaxf(mc1, b1);
            const float a0 = ex2(mc0 - b0), a1 = ex2(mc1 - b1);
            mc0 = b0; mc1 = b1;
            l0 *= a0; l1 *= a1;
            wg_wait<0>();
            fence_regs(o);
#pragma unroll
            for (int i = 0; i < 24; i++) { o[4 * i] *= a0; o[4 * i + 1] *= a0; o[4 * i + 2] *= a1; o[4 * i + 3] *= a1; }
#pragma unroll
            for (int i = 0; i < 32; i++) s[i] -= (i & 2) ? mc1 : mc0;
          }
          l0 += b0; l1 += b1;
          wg_wait<0>();
          fence_regs(o);
          release(sv);
        };
        auto step = [&](uint32_t (&pin)[16], uint32_t (&pout)[16]) {
          uint32_t ak, av;
          const int sk = take(rdy0, SZ_KV, ak), sv = take(rdy1, SZ_KV, av);
          wg_fence();
          qk(s, ak);
          pv(pin, av, 1);
          finish(pout, sk, sv);
        };
        auto unpark = [&]() {
          uint32_t ad, ak;
          const int bi = take(rdy0, SZ_PARK, ad);
#pragma unroll
          for (int i = 0; i < 12; i++) lds128(sbase + (ad - ring16 + img0) * 16 + (i >> 1) * 8192 + (i & 1) * 512, q[4 * i], q[4 * i + 1], q[4 * i + 2], q[4 * i + 3]);
          const int sk0 = take(false, SZ_KV, ak);
          fence_regs(q);
          release_warp(bi);
          wg_fence();
          qk(s, ak);
          probe2();
          return sk0;
        };
        auto mma4 = [&](uint32_t ad, int acc) {
#pragma unroll
          for (int kk = 0; kk < 4; kk++)
            wgmma_ss_n192<1>(o, mk_desc(ad + wg * 512, 16, 1024, 1) + (kk * 2), mk_desc(ad, 8192, 1024, 1) + (1024 + kk * 128), acc || kk != 0);
        };
        auto convert = [&](int i0, int i1) {
          sched_fence(keep, never);
#pragma unroll
          for (int i = i0; i < i1; i++) {
            q[i] = pack_bf16(o[2 * i] * kScaleLog2, o[2 * i + 1] * kScaleLog2);
            if ((i & 7) == 7 && i != i1 - 1) sched_fence(keep, never);
          }
          sched_fence(keep, never);
        };
        auto kend = [&](int bi, int k) {
          wg_commit();
          drain(k < 8 ? (0x54732710u >> (4 * k)) & 7 : 7);
          probe1();
          wg_wait<0>();
          release(bi);
        };
        if (type == OP_O) {
          int prev = 0;
          if (op & C_WIDE) {
            float d[64];
            auto mma3 = [&](uint32_t ad, int h, int acc) {
#pragma unroll
              for (int kk = 0; kk < 2; kk++)
                wgmma_ss_n192<1>(o, mk_desc(ad + wg * 256, 16, 512, 2) + (h * 512 + kk * 2), mk_desc(ad, 4096, 1024, 1) + (1024 + h * 768 + kk * 128), acc || kk);
            };
            auto mma2 = [&](uint32_t ad, uint32_t ob, int h, int acc) {
#pragma unroll
              for (int kk = 0; kk < 2; kk++)
                wgmma_ss_n128<1>(d, mk_desc(ad + wg * 256, 16, 512, 2) + (h * 512 + kk * 2), mk_desc(ad, 4096, 1024, 1) + (ob + h * 512 + kk * 128), acc || kk);
            };
            auto wstep = [&](uint32_t bytes, int acc, auto hook) {
              uint32_t ad;
              const int bi = take(rdy0, bytes, ad);
              wg_fence();
              if (bytes == SZ_W2) mma2(ad, 1024, 0, 1); else mma3(ad, 0, acc);
              if (bytes == SZ_W) mma3(ad, 1, 1);
              wg_commit();
              if (acc) { wg_wait<1>(); release(prev); }
              if (bytes == SZ_W) mma2(ad, 2560, 0, acc);
              if (bytes == SZ_W3) mma3(ad, 1, 1); else mma2(ad, bytes == SZ_W ? 2560 : 1024, 1, 1);
              wg_commit();
              prev = bi;
              hook();
              probe1();
              wg_wait<1>();
            };
            undefine(o);
            wstep(SZ_W, 0, [&]() { drain(0); });
#pragma unroll 1
            for (int k = 1; k < 6; k++) wstep(SZ_W, 1, [&]() { drain(k); });
#pragma unroll 1
            for (int k = ((op >> 2) & 127) - TAIL; k > 6; k--) {
              wstep(SZ_W, 1, []() {});
            }
#pragma unroll 1
            for (int k = 0; k < TAIL; k++) wstep(SZ_W2, 1, []() {});
            pend = ptr_add(P.g->part, (((op >> 9) & 31) * 2 + rank) * 81920 + 4 * 8192 + img0 * 16);
            wstep(SZ_W3, 1, [&]() {
              fence_regs(d);
#pragma unroll
              for (int i = 0; i < 32; i++) q[16 + i] = pack_bf16(d[2 * i], d[2 * i + 1]);
              slab(2, 2);
            });
#pragma unroll 1
            for (int k = 3; k < 6; k++) wstep(SZ_W3, 1, [&]() { slab(k, 2); });
            op = prog[pc + 1];
            enter();
            pend_any = true;
            pend -= 4 * 512;
            bi0 = take(rdy0 || (op & 3) != OP_Q, SZ_Q, ad0);
            sched_fence(keep, never);
            wg_wait<0>();
            fence_regs(o);
            release(prev);
#pragma unroll
            for (int i = 0; i < 48; i++) q[i] = pack_bf16(o[2 * i], o[2 * i + 1]);
            if ((op & 3) != OP_Q) continue;
            pc++;
            goto first_step;
          }
          float c[80];
          auto mma2 = [&](uint32_t ad, uint32_t oa, uint32_t ob, int acc) {
            wgmma_ss_n160<1>(c, mk_desc(ad + wg * 256, 16, 512, 2) + (oa), mk_desc(ad, 2048, 512, 2) + (1024 + ob), acc);
            wgmma_ss_n160<1>(c, mk_desc(ad + wg * 256, 16, 512, 2) + (oa + 2), mk_desc(ad, 2048, 512, 2) + (1024 + ob + 64), 1);
          };
          auto kstep = [&](int acc, auto hook, uint32_t bytes = SZ_O) {
            uint32_t ad;
            const int bi = take(rdy0, bytes, ad);
            wg_fence();
            mma2(ad, 0, 0, acc);
            wg_commit();
            if (acc) wg_wait<1>();
            if (acc == 1) release(prev);
            if (acc > 1) release_warp(prev, acc == 2 || wg == 0);
            mma2(ad, 512, 640, 1);
            wg_commit();
            prev = bi;
            hook();
            probe1();
            wg_wait<1>();
          };
          auto unblock = [&](int k) {
            if (__all_sync(0xffffffffu, rdy0) || __all_sync(0xffffffffu, mbar_try(full0 + 8 * r.bi, r.ph, 1500))) return;
#pragma unroll 1
            for (; k < 6; k++) drain(k);
            pend_any = false;
          };
          unblock(0);
          kstep(0, [&]() { drain(0); });
          int left = ((job >> 13) & 127) - 6;
#pragma unroll 1
          for (uint32_t k = 1, pace = left >= 29 ? 0x4511 : left <= 17 ? 0x1a : 0x155; k < 6; pace >>= 2, left--) {
            unblock(k);
            kstep(1, [&]() {
#pragma unroll 1
              for (int i = pace & 3; i > 0; i--) drain(k++);
            });
          }
#pragma unroll 1
          for (; left > 0; left--) kstep(1, []() {});
          uint32_t t[8], stage[3];
          float u[80];
          auto unpack = [&](int j) {
#pragma unroll
            for (int i = 0; i < 8; i++) {
              u[16 * j + 2 * i] = __uint_as_float(t[i] << 16); u[16 * j + 2 * i + 1] = __uint_as_float(t[i] & 0xffff0000u);
              asm volatile("" : "+f"(u[16 * j + 2 * i]), "+f"(u[16 * j + 2 * i + 1]));
            }
          };
#pragma unroll
          for (int i = 0; i < 8; i++) t[i] = 0;
          const uint32_t bytes = (job & P_LD) ? SZ_OL : SZ_O;
#pragma unroll
          for (int j = 0; j < 5; j++) {
            if (j == 2 && wg == 1) {
              wg_wait<0>();
              release_warp(prev);
              bar_sync(1, 256);
            }
            kstep(j == 2 ? 3 : 2, [&]() {
              if (j == 4) asm volatile("{\n.reg .pred p;\nsetp.eq.u32 p, %0, 0;\n@p bar.arrive 1, 256;\n}\n" ::"r"(wg) : "memory");
              if (j) unpack(j - 1);
              lds2_if(job & P_LD, sbase + (cur - ring16 + img0) * 16 - 8192, t);
              if (j >= 1 && j <= 3) stage[j - 1] = sbase + (cur - ring16) * 16 - bytes + wid * 1024;
            }, bytes);
          }
          unpack(4);
          sched_fence(keep, never);
          wg_wait<0>();
          fence_regs(c);
          release_warp(prev);
          asm volatile("barrier.cluster.arrive.relaxed;" ::: "memory");
#pragma unroll
          for (int i = 0; i < 10; i++) {
            const int v = (i & 1) * 2 + (lane >> 4);
            const uint32_t sa = stage[i >> 2] + (i & 2) * 4096;
            stsm4(sa + (lane & 15) * 64 + ((v ^ ((lane >> 1) & 3)) << 4), pack_bf16(c[8 * i] + u[8 * i], c[8 * i + 1] + u[8 * i + 1]),
                  pack_bf16(c[8 * i + 2] + u[8 * i + 2], c[8 * i + 3] + u[8 * i + 3]), pack_bf16(c[8 * i + 4] + u[8 * i + 4], c[8 * i + 5] + u[8 * i + 5]),
                  pack_bf16(c[8 * i + 6] + u[8 * i + 6], c[8 * i + 7] + u[8 * i + 7]));
          }
          asm volatile("fence.proxy.async.shared::cta;" ::: "memory");
          __syncwarp();
          if (elect()) {
#pragma unroll
            for (int i = 0; i < 5; i++)
              tma3d_store(&P.out, stage[i >> 1] + (i & 1) * 8192, 0, ((job >> 7) & 7) * kSq + rank * 128 + wid * 16, ((job >> 10) & 1) * 20 + ((job >> 20) & 3) * 5 + i);
            asm volatile("cp.async.bulk.commit_group;\ncp.async.bulk.wait_group.read 0;" ::: "memory");
          }
          __syncwarp();
          break;
        }
        bi0 = take(rdy0, SZ_Q, ad0);
      first_step:
        undefine(o);
        wg_fence();
        mma4(ad0, 0);
        kend(bi0, 0);
        fence_regs(o);
      next_head:
        {
#pragma unroll 1
          for (int k = 1; k < ((op & F_PARK) ? 10 : 8); k++) {
            uint32_t ad;
            const int bi = take(rdy0, SZ_Q, ad);
            wg_fence();
            mma4(ad, 1);
            kend(bi, k);
          }
          if (op & F_PARK) {
            fence_regs(o);
            convert(0, 48);
            pend = ptr_add(P.g->tile, (((op >> 2) & 511) * 2 + rank) * SZ_PARK + img0 * 16);
            continue;
          }
          uint32_t a8, a9, ak0, ak1;
          const int b8 = take(rdy0, SZ_Q, a8), b9 = take(false, SZ_Q, a9);
          wg_fence();
          mma4(a8, 1);
          wg_commit();
          mma4(a9, 1);
          wg_commit();
          pc++;
          wg_wait<1>();
          release(b8);
          const int sk0 = take(false, SZ_KV, ak0);
          wg_wait<0>();
          fence_regs(o);
          release(b9);
          float s0[32];
          convert(0, 32);
          wg_fence();
          qk(s0, ak0, 0, 4);
          convert(32, 48);
          wg_fence();
          qk(s0, ak0, 4, 12);
          sk1 = take(false, SZ_KV, ak1);
          probe1();
          wg_wait<0>();
          first(s0, sk0, [&](int i) {
            if (i == 0) return;
            sched_fence(keep, never);
            wg_fence();
            if (i == 1) qk(s, ak1, 0, 4);
            if (i == 2) qk(s, ak1, 4, 8);
            if (i == 3) qk(s, ak1, 8, 12);
            sched_fence(keep, never);
          });
        }
        for (;;) {
          {
            uint32_t av;
            const int sv = take(rdy0, SZ_KV, av);
            undefine(o);
            wg_fence();
            pv(pa, av, 0);
            finish(pb, sk1, sv);
          }
          nop = prog[pc + 1];
#pragma unroll 1
          for (int jj = 0; jj < 7; jj++) {
            step(pb, pa);
            step(pa, pb);
          }
          float i0, i1;
          auto last = [&]() {
            uint32_t av;
            const int sv = take(rdy0, SZ_KV, av);
            wg_fence();
            pv(pb, av, 1);
            sched_fence(keep, never);
            probe1();
            l0 += __shfl_xor_sync(0xffffffffu, l0, 1); l1 += __shfl_xor_sync(0xffffffffu, l1, 1);
            l0 += __shfl_xor_sync(0xffffffffu, l0, 2); l1 += __shfl_xor_sync(0xffffffffu, l1, 2);
            i0 = rcp(l0); i1 = rcp(l1);
            pend = ptr_add(P.g->tile, (((op >> 2) & 511) * 2 + rank) * SZ_PARK + img0 * 16);
            return sv;
          };
          auto normalise = [&](uint32_t (&d)[48], auto mid) {
#pragma unroll
            for (int i = 0; i < 24; i++) {
              d[8 * (i >> 2) + (i & 3)] = pack_bf16(o[4 * i] * i0, o[4 * i + 1] * i0);
              d[8 * (i >> 2) + (i & 3) + 4] = pack_bf16(o[4 * i + 2] * i1, o[4 * i + 3] * i1);
              if ((i & 1) && i != 23) sched_fence(keep, never);
              if ((i & 3) == 3 && i != 23) mid(i >> 2);
            }
          };
          const int sv = last();
          if ((nop & 3) != OP_A) {
            op = nop;
            enter();
            pend_any = true;
            bi0 = take(rdy0 || (nop & 3) != OP_Q, SZ_Q, ad0);
            sched_fence(keep, never);
            wg_wait<0>();
            fence_regs(o);
            release(sv);
            normalise(q, [](int) {});
            undefine(o);
            if ((nop & 3) != OP_Q) break;
            sched_fence(keep, never);
            wg_fence();
            mma4(ad0, 0);
            pc++;
            kend(bi0, 0);
            fence_regs(o);
            goto next_head;
          }
          const int sk0 = unpark();
          wg_wait<1>();
          fence_regs(o);
          release(sv);
          uint32_t t[48];
          auto st = [&](int i) {
            stg2_if(true, pend + i * 512, t[8 * i], t[8 * i + 1], t[8 * i + 2], t[8 * i + 3], t[8 * i + 4], t[8 * i + 5], t[8 * i + 6], t[8 * i + 7], spol);
          };
          normalise(t, [&](int i) { if (!(i & 1)) st(i >> 1); });
          wg_wait<0>();
          first(s, sk0, [&](int i) { if (i < 3) { sched_fence(keep, never); st(3 + i); } });
          __syncwarp();
          mbar_arrive_if(lane == 0, odone0 + 8 * pc);
          pc++;
          op = nop;
          uint32_t ak1;
          sk1 = take(rdy0, SZ_KV, ak1);
          rdy0 = rdy1;
          wg_fence();
          qk(s, ak1);
        }
      }
    }
    asm volatile("barrier.cluster.wait;" ::: "memory");
  } else {
    asm volatile("setmaxnreg.dec.sync.aligned.u32 24;");
    const uint32_t* prog = P.prog[role].p;
    unsigned int* flag = P.g->flag + rank;
    if (wid == 8) {
      Cursor tail{0, 0};
      int head = 0, sh = 0;
      uint32_t cur = 0, used = 0;
      uint64_t fifo = 0;
      uint32_t dst, bar, ev = ev0, done = 0;
      const uint64_t pol = evict_first();
      auto retire = [&]() {
        mbar_wait(empty0 + 8 * tail.bi, tail.ph);
        tail.next();
        used -= (uint32_t)fifo & 31;
        fifo >>= 5;
        sh -= 5;
        asm volatile("st.volatile.shared.u32 [%0], %1;" ::"r"(progress), "r"(++done) : "memory");
      };
      auto acquire = [&](uint32_t bytes) {
        uint32_t fp = bytes >> 12;
        if (cur + fp > (RING >> 12)) { fp += (RING >> 12) - cur; cur = 0; }
        used += fp;
        while (used > (RING >> 12) || sh == 5 * NBAR) retire();
        fifo |= (uint64_t)fp << sh;
        sh += 5;
        dst = sbase + (cur << 12);
        bar = full0 + 8 * head;
        cur += bytes >> 12;
        if (++head == NBAR) head = 0;
      };
      auto gate = [&]() {
        mbar_wait(ev, 0);
        ev += 8;
        asm volatile("fence.proxy.async.global;" ::: "memory");
      };
      for (int pc = 0;; pc++) {
        uint32_t op = prog[pc];
        const int type = op & 3;
        if (type == OP_END) break;
        if (op == OP_O) {
          gate();
          op = __shfl_sync(0xffffffffu, lds32(jobw), 0);
        }
        const int blk = (op >> 10) & 1;
        if (type == OP_Q) {
#pragma unroll 1
          for (int k = 0; k < 10; k++) {
            if (k == 9 && (op & P_GATE)) gate();
            acquire(SZ_Q);
            if ((pc > 0 || k >= EARLY) && elect()) {
              mbar_expect(bar, SZ_Q);
              tma2d(dst, &P.x[blk], bar, 64 * k, ((op >> 7) & 7) * kSq + rank * 128);
              if ((k & 1) == rank) tma3d_mc(dst + 16384, &P.wq[blk], bar, 0, 64 * k, 3 * ((op >> 2) & 31));
            }
          }
        } else if (type == OP_A) {
          const int row0 = ((op >> 2) & 255) * kSk;
          const CUtensorMap* kv_map = rank ? &P.v[blk] : &P.k[blk];
          if (op & F_PARK) {
            gate();
            acquire(SZ_PARK);
            if (elect()) {
              mbar_expect(bar, SZ_PARK);
              bulk_load_hint(dst, &P.g->tile[((op >> 20) * 2 + rank) * 3072], SZ_PARK, bar, pol);
            }
          }
#pragma unroll 1
          for (int t = 0; t < 32; t++) {
            const int isv = t == 31 ? 1 : (t == 0 ? 0 : (~t & 1));
            const int j = isv ? (t - 1) >> 1 : (t + 1) >> 1;
            if (t == 31 && (op & P_GATE)) gate();
            acquire(SZ_KV);
            if (elect()) {
              mbar_expect(bar, SZ_KV);
              if (isv == (int)rank) tma4d_mc_hint(dst, kv_map, bar, row0 / 8 + 8 * j, pol);
            }
          }
        } else {
          const int n = (op >> 13) & 127, nw = (op & P_WIDE) ? n - TAIL : 0;
          const uint4* part = &P.g->part[((((op >> 6) & 30) + ((op >> 21) & 1)) * 2 + rank) * 5120 + ((op >> 20) & 1) * 2560];
#pragma unroll 1
          for (int i = 0; i < n + (nw ? TAIL : 0); i++) {
            const int k = nw ? (i < n ? i : i - TAIL) : kSteps - n + i, h = (k * 43) >> 7, col = 5 * ((op >> 20) & 3);
            const uint4* src = &P.g->tile[(P.slot[((op >> 2) & 480) + h] * 2 + rank) * 3072 + (k - 3 * h) * 1024];
            const uint32_t j = (op & P_LD) ? i - n + 5 : 5, bytes = i < nw ? SZ_W : nw ? (i < n ? SZ_W2 : SZ_W3) : j < 5 ? SZ_OL : SZ_O;
            if ((op & P_PRE) ? i == 0 : j == 0) gate();
            if (i < n && (i == 0 || k == 3 * h)) gate();
            acquire(bytes);
            if (elect()) {
              mbar_expect(bar, bytes);
              if (bytes != SZ_W2) tma5d_mc(dst + 16384 + rank * (nw ? 12288 : 10240), nw ? &P.wo3[blk] : &P.wo[blk], bar, 8 * k + 4 * rank, nw ? col / 2 : col);
              bulk_load_hint(dst, src, 16384, bar, pol);
              if (nw && i < n) tma5d_mc(dst + bytes - 16384 + rank * 8192, &P.wo2[blk], bar, 8 * k + 4 * rank, col / 2 + 3);
              if (j < 5) bulk_load_hint(dst + SZ_O, part + j * 512, 8192, bar, pol);
              if ((op & P_PRE) && i < 10) asm volatile("cp.async.bulk.prefetch.L2.global [%0], 4096;" ::"l"(part + i * 256) : "memory");
            }
          }
        }
      }
#pragma unroll 1
      while (sh) retire();
    } else if (threadIdx.x == 288) {
      for (int pc = 0;; pc++) {
        const uint32_t op = prog[pc];
        const int type = op & 3;
        if (type == OP_END) break;
        if (type == OP_Q ? !(op & F_PARK) : type == OP_O && !(op & P_WIDE)) continue;
        const int id = type == OP_A ? (op >> 2) & 511 : type == OP_Q ? N_TILE + ((op >> 13) & 127) : ID_PART + ((op >> 5) & 60) + ((op >> 20) & 3);
        const uint32_t v = type == OP_O ? 1 : P.info[id] & 7;
        mbar_wait_long(odone0 + 8 * pc);
        flag_set(flag + 2 * id, v);
        if (type == OP_O && (op & P_WIDE)) flag_set(flag + 2 * id + 2, v);
      }
    } else if (wid == 10) {
      int i = threadIdx.x & 31;
      uint32_t e = i < 8 ? P.prog[role].ev[i] : 0;
      for (uint32_t n = 0; __any_sync(0xffffffffu, e); n++) {
        uint32_t job = lds32(jobw);
        const int togo = (e & E_DRAW) ? (e & 1023) - lds32(progress) : 99;
        if (togo <= 0 && rank == 0) {
          job = P.job[atomicInc(&P.g->ticket, gridDim.x / 2 - 1)];
          asm volatile("{\n.reg .u32 a;\nmapa.shared::cluster.u32 a, %0, 1;\nst.volatile.shared::cluster.u32 [a], %1;\n"
                       "st.volatile.shared.u32 [%0], %1;\n}\n" ::"r"(jobw), "r"(job) : "memory");
        }
        if ((e & E_JOB) && job) {
          const uint32_t j = e & 63, heads = job == OP_O ? 0 : kH - ((job >> 2) & 31), jp = !(job & P_LD) ? 63 : (job & P_PRE) ? 0 : heads - 1, h = j - (j > jp);
          e = j == jp ? (ID_PART + ((job >> 5) & 60) + ((job >> 20) & 3)) | E_ON | E_LAST : h < heads ? (((job >> 2) & 511) + h) | E_ON | E_LAST : 0;
        }
        unsigned int* f = ptr_add(flag, 8 * (e & 1023));
        const bool ok = (e & E_ON) ? flag_get(f) - 1 < ((e & E_FREE) ? 1 : 7) : (e & E_DRAW) && job;
        if (ok) {
          mbar_arrive(ev0 + 8 * i);
          if (e & (E_FREE | E_LAST)) flag_dec(f);
          i += 8;
          e = i < MAX_EV ? P.prog[role].ev[i] : 0;
        }
        asm volatile("{\n.reg .pred p;\nsetp.ge.u32 p, %0, 0x400000;\n@p trap;\n}\n" ::"r"(n));
        if (!__any_sync(0xffffffffu, ok)) __nanosleep(__any_sync(0xffffffffu, job || togo <= 2) ? 100 : 600);
      }
    } else if (threadIdx.x == 352) {
      uint32_t items = 0;
      auto read = [&](int id) {
        if (!(P.info[id] & I_NEXT)) return;
        wait_word(progress, items);
        flag_dec(flag + 2 * id);
      };
      for (int pc = 0;; pc++) {
        const uint32_t op = prog[pc];
        const int type = op & 3;
        if (type == OP_END) break;
        if (type == OP_O) {
          const uint32_t n = (op >> 13) & 127, base = items;
#pragma unroll 1
          for (uint32_t k = 3, id = (op >> 2) & 511; k <= n; k += 3, id++) {
            items = base + k + (k + TAIL > n ? TAIL : 0);
            read(id);
          }
          items = base + n + TAIL;
        } else if (type == OP_A) {
          if (op & F_PARK) { items++; read(N_TILE + ((op >> 13) & 127)); }
          items += 32;
        } else {
          items += 10;
        }
      }
    }
    __syncwarp();
    asm volatile("barrier.cluster.arrive.relaxed;\nbarrier.cluster.wait;" ::: "memory");
  }
}

typedef CUresult (*EncodeFn)(CUtensorMap*, CUtensorMapDataType, cuuint32_t, void*, const cuuint64_t*, const cuuint64_t*,
                             const cuuint32_t*, const cuuint32_t*, CUtensorMapInterleave, CUtensorMapSwizzle,
                             CUtensorMapL2promotion, CUtensorMapFloatOOBfill);

void encode(EncodeFn fn, CUtensorMap* m, const void* ptr, int rank, const cuuint64_t* dims, const cuuint64_t* strides,
            const cuuint32_t* box, CUtensorMapSwizzle swz) {
  const cuuint32_t es[5] = {1, 1, 1, 1, 1};
  CUresult r = fn(m, CU_TENSOR_MAP_DATA_TYPE_BFLOAT16, rank, const_cast<void*>(ptr), dims, strides, box, es,
                  CU_TENSOR_MAP_INTERLEAVE_NONE, swz, CU_TENSOR_MAP_L2_PROMOTION_L2_128B, CU_TENSOR_MAP_FLOAT_OOB_FILL_NONE);
  if (r != CUDA_SUCCESS) fprintf(stderr, "cuTensorMapEncodeTiled failed: %d\n", (int)r);
}

struct Op { int type, flags, id, n, quarter, park, item0, items; double t0, t1; };
struct Use { double ready, gate, need, freed; int readers, slot, prev; bool next; };
struct PlanStats { double end, slack, park_slack; int slots, parks; uint32_t own[N_CL]; };

bool plan(const char* const* text, int n_pair, int phase, Params& P, PlanStats* stats = nullptr) {
  constexpr double T_Q = 7900, T_A = 24850, T_U = 26300, T_O = 640, T_RUN = 800, T_WIDE = 1900, AHEAD = 3500, PUBLISH = 1500;
  const double margin = 256.0 * ((P.dbg >> 8) & 255);
  static Op op[N_CL][MAX_OPS];
  static Use use[ID_PART];
  int n_op[N_CL], covered[N_TEAM] = {}, finals[N_TEAM] = {};
  auto hex = [](char c) { return c <= '9' ? c - '0' : c - 'a' + 10; };
  for (int i = 0; i < n_pair; i++)
    for (const char* s = text[i]; *s; s++)
      if (*s == 'J') { if (covered[hex(s[1])]) return false; covered[hex(s[1])] = 10 * (s[2] - '0') + s[3] - '0'; }
  for (int c = 0; c < 2 * n_pair; c++) {
    int n = 0, items = 0;
    double t = 0;
    auto add = [&](int type, int flags, int id, int heads, int quarter, int its, double dt) {
      if (n < MAX_OPS) op[c][n] = {type, flags, id, heads, quarter, 0, items, its, t, t + dt};
      n++; items += its; t += dt;
    };
    for (const char* s = text[c >> 1]; *s; s++) {
      const int tm = hex(s[1]) & 15, nj = covered[tm];
      if (*s == 'N') { add(OP_Q, 0, 0, 0, 0, 10, T_Q); add(OP_A, 0, 0, 0, 0, 32, T_A); }
      if (*s == 'P') add(OP_Q, F_PARK, 0, 0, 0, 10, T_Q);
      if (*s == 'U') { if (n == 0 || n > MAX_OPS || op[c][n - 1].type != OP_A) return false; add(OP_A, F_PARK, 0, 0, 0, 33, T_U); }
      if (*s == 'J') { if (nj < TAIL + 6 || nj > kSteps - 11) return false; add(OP_O, P_WIDE, tm * kH, nj, 2 * (c & 1), nj + TAIL, 2 * T_O * nj + T_WIDE); }
      if (*s == 'F') { if (s[2]) return false; add(OP_O, nj ? P_LD : 0, tm * kH + nj / 3, kSteps - nj, finals[tm]++, kSteps - nj, T_O * (kSteps - nj) + T_RUN); }
    }
    if (n && n <= MAX_OPS && (op[c][n - 1].type != OP_O || (op[c][n - 1].flags & P_WIDE))) add(OP_O, 0, 0, 0, 0, 0, 0);
    add(OP_END, 0, 0, 0, 0, 0, 0);
    if (n > MAX_OPS || op[c][0].type != OP_Q) return false;
    n_op[c] = n - 1;
  }
  for (int t = 0; t < N_TEAM; t++) if (finals[t] != 4) return false;
  for (int i = 0; i < ID_PART; i++) use[i] = {0, 0, 1e18, 0, 0, 0, 0, false};
  struct Ref { double t; Op* o; int id; };
  static Ref att[N_TILE + 1], dem[N_TILE], prk[MAX_PARK + 1], unp[MAX_PARK + 1], wr[ID_PART];
  int n_att = 0, n_prk = 0, n_unp = 0;
  auto ready = [&](const Op* o) {
    const int nt = o[1].type;
    return o->t1 + (nt == OP_Q ? 6100 : o[1].n ? ((o[1].flags & P_WIDE) ? 7700 : 3900) : 1500) + PUBLISH;
  };
  for (int c = 0; c < 2 * n_pair; c++)
    for (Op* o = op[c]; o->type != OP_END; o++) {
      if (o->type == OP_A) { att[n_att] = {ready(o), o, 0}; if (++n_att > N_TILE) return false; }
      if (o->type == OP_A && o->flags) { unp[n_unp] = {o->t0 - AHEAD, o, 0}; if (++n_unp > MAX_PARK) return false; }
      if (o->type == OP_Q && o->flags) { prk[n_prk] = {ready(o), o, 0}; if (++n_prk > MAX_PARK) return false; }
      for (int i = 0; o->type == OP_O && i < o->n; i++) {
        const int nw = (o->flags & P_WIDE) ? o->n - TAIL : 0, k = nw ? i : kSteps - o->n + i;
        Use& u = use[o->id / kH * kH + k / 3];
        const double t = o->t0 + T_O * (i + (i < nw ? i : nw));
        if (t - AHEAD < u.need) u.need = t - AHEAD;
        const double f = !nw ? 1e18 : i + NBAR < o->items - TAIL || (nw && o[1].type != OP_O) ? t + T_O * (i < nw ? 2 : 1 + TAIL) + PUBLISH : 1e18;
        if (f > u.freed) u.freed = f;
        if (i == 0 || k % 3 == 0) u.readers++;
      }
    }
  if (n_att != N_TILE || n_prk != n_unp) return false;
  auto sort = [](Ref* r, int n) {
    for (int i = 1; i < n; i++)
      for (int j = i; j > 0 && r[j].t < r[j - 1].t; j--) { Ref x = r[j]; r[j] = r[j - 1]; r[j - 1] = x; }
  };
  for (int i = 0; i < N_TILE; i++) { const int id = (i & 15) * kH + (i >> 4); dem[i] = {use[id].need, nullptr, id}; }
  sort(att, n_att); sort(dem, N_TILE); sort(prk, n_prk); sort(unp, n_unp);
  PlanStats st = {0, 1e18, 1e18, 0, n_prk};
  int n_wr = 0;
  for (int i = 0; i < N_TILE; i++) {
    Op* o = att[i].o;
    o->id = dem[i].id;
    if (!o->flags) o[-1].id = o->id;
    if (dem[i].t - att[i].t < st.slack) st.slack = dem[i].t - att[i].t;
    wr[n_wr++] = {o->t1 - 2 * AHEAD, o, o->id};
  }
  for (int i = 0; i < n_prk; i++) {
    prk[i].o->id = unp[i].o->id;
    prk[i].o->park = unp[i].o->park = i;
    use[N_TILE + i].freed = unp[i].o->t0 + 2 * PUBLISH;
    use[N_TILE + i].readers = 1;
    if (unp[i].t - prk[i].t < st.park_slack) st.park_slack = unp[i].t - prk[i].t;
    wr[n_wr++] = {prk[i].o->t1 - 2 * AHEAD, prk[i].o, N_TILE + i};
  }
  for (int c = 0; c < 2 * n_pair; c++)
    for (int d = 0; d < 2 * n_pair; d++)
      for (Op *f = &op[c][n_op[c] - 1], *o = op[d]; f->n && o->type != OP_END; o++)
        if (o->type == OP_O && (o->flags & P_WIDE) && o->id / kH == f->id / kH) {
          if (f->t0 - o->t1 > 4096.0 * ((P.dbg >> 16) & 255)) f->flags |= P_PRE;
          const double slack = f->t0 + ((f->flags & P_PRE) ? 0 : (f->n - 5) * T_O) - AHEAD - ready(o);
          if (slack < st.park_slack) st.park_slack = slack;
        }
  sort(wr, n_wr);
  int holder[N_TILE];
  for (int i = 0; i < n_wr; i++) {
    int best = -1;
    for (int sl = 0; sl < st.slots; sl++)
      if (use[holder[sl]].freed + margin <= wr[i].t && (best < 0 || use[holder[sl]].freed < use[holder[best]].freed)) best = sl;
    Use& u = use[wr[i].id];
    if (best >= 0) { u.prev = holder[best]; use[u.prev].next = true; wr[i].o->flags |= P_GATE; }
    else if (st.slots == N_TILE) return false;
    else best = st.slots++;
    u.slot = best;
    holder[best] = wr[i].id;
  }
  {
    int pos[N_CL] = {}, flag[ID_PART + 4 * N_TEAM] = {}, seen[ID_PART] = {};
    auto goal = [&](int c) { return op[c][n_op[c] - 1].item0; };
    for (bool moved = true; moved;) {
      moved = false;
      for (int c = 0; c < 2 * n_pair; c++) {
        for (; pos[c] < goal(c); pos[c]++, moved = true) {
          bool ok = true;
          for (const Op* o = op[c]; o->type != OP_END; o++) {
            const int k = pos[c] - o->item0, own = o->type == OP_A ? o->id : N_TILE + o->park;
            if (k < 0 || k >= o->items) continue;
            if (o->type == OP_O) ok = k >= o->n || flag[o->id + k / 3];
            else if (k == o->items - 1 && (o->flags & P_GATE)) ok = seen[use[own].prev] == use[use[own].prev].readers;
            else if (k == 0 && o->type == OP_A && (o->flags & F_PARK)) ok = flag[N_TILE + o->park];
          }
          if (!ok) break;
          for (const Op* o = op[c]; o->type != OP_END; o++) {
            if (pos[c] == o->item0 + o->items + (o[1].type == OP_Q ? 7 : o[1].item0 == goal(c) ? -1 : 5)) {
              if (o->type == OP_A) flag[o->id] = 1;
              if (o->type == OP_Q && (o->flags & F_PARK)) flag[N_TILE + o->park] = 1;
              if (o->type == OP_O) flag[ID_PART + o->id / kH * 4 + o->quarter] = flag[ID_PART + o->id / kH * 4 + o->quarter + 1] = 1;
            }
            const int k = pos[c] - NBAR - o->item0, nw = o->n - TAIL;
            if (k == 0 && o->type == OP_A && (o->flags & F_PARK)) seen[N_TILE + o->park]++;
            if (o->type == OP_O && k >= 0 && k < o->items && (k < nw || k >= o->n) && (k < nw ? k : k - TAIL) % 3 == 2) seen[o->id + (k < nw ? k : k - TAIL) / 3]++;
          }
        }
      }
    }
    for (int c = 0; c < 2 * n_pair; c++) if (pos[c] < goal(c)) return false;
  }
  int n_job = 0, longest = 0;
  for (int t = 0; t < N_TEAM; t++) if (kH - covered[t] / 3 > longest) longest = kH - covered[t] / 3;
  for (int c = 0; c < 2 * n_pair; c++) {
    uint32_t items = 0, cur = 0, pend = 0;
    int n = 0, ev = 0;
    auto item = [&](uint32_t bytes, int count) {
      for (int i = 0; i < count; i++) { if (cur + bytes > RING) cur = 0; cur += bytes; items++; }
    };
    auto event = [&](uint32_t e) { if (ev < MAX_EV) P.prog[c].ev[ev] = e; ev++; };
    for (const Op* o = op[c];; o++) {
      if (o->type != OP_END && phase && (o->type == OP_O) != (phase == 2)) continue;
      uint32_t cw = o->type | (items % NBAR) << 15 | ((items / NBAR) & 1) << 19 | (cur >> 12) << 20 | pend, pw = o->type | o->id << 2 | o->flags;
      const int ps = use[N_TILE + o->park].slot;
      pend = 0;
      if (o->type == OP_O) {
        pw |= o->n << 13 | o->quarter << 20;
        if (o->flags & P_WIDE) {
          cw |= o->n << 2 | (o->id / kH * 2 + o->quarter / 2) << 9 | C_WIDE;
          item(SZ_W, o->n - TAIL);
          item(SZ_W2, TAIL);
          item(SZ_W3, TAIL);
          pend = C_PEND;
          for (int i = 0; 3 * i < o->n; i++) event((o->id + i) | E_ON | (use[o->id + i].next ? 0 : E_LAST));
        } else {
          dem[n_job++] = {o->t0 - 1e6 * o->n, nullptr, (int)pw};
          st.own[c] = pw;
          pw = OP_O;
          event(E_DRAW | (items < 16 ? 0 : items - 16));
          for (int i = 0; i <= longest; i++) event(E_JOB | i);
        }
      } else if (o->type != OP_END) {
        const bool parks = o->type == OP_Q && (o->flags & F_PARK);
        cw |= (parks ? ps : use[o->id].slot) << 2 | (o->flags & F_PARK);
        if (o->flags & F_PARK) pw |= o->park << 13 | ps << 20;
        if (o->type == OP_Q) item(SZ_Q, 10);
        else { if (o->flags & F_PARK) { item(SZ_PARK, 1); event((N_TILE + o->park) | E_ON | (use[N_TILE + o->park].next ? 0 : E_LAST)); } item(SZ_KV, 32); }
        if (parks || o->type == OP_A) pend = C_PEND;
        if (o->flags & P_GATE) event(use[parks ? N_TILE + o->park : o->id].prev | E_ON | E_FREE);
      }
      P.prog[c].c[n] = cw; P.prog[c].p[n++] = pw;
      if (o->type == OP_END) { if (o->t0 > st.end) st.end = o->t0; break; }
    }
    if (ev > MAX_EV) return false;
    while (ev < MAX_EV) P.prog[c].ev[ev++] = 0;
    while (n < MAX_OPS) { P.prog[c].c[n] = OP_END; P.prog[c].p[n++] = OP_END; }
    P.first[c] = (uint16_t)(P.prog[c].p[0] & 2047);
  }
  sort(dem, n_job);
  for (int i = 0; i < n_job; i++) P.job[i] = dem[i].id;
  for (int i = 0; i < ID_PART; i++) {
    if (i < N_TILE) P.slot[i] = use[i].slot;
    P.info[i] = (use[i].readers + use[i].next) | (use[i].next ? I_NEXT : 0);
  }
  if (stats) *stats = st;
  return true;
}

const char* const kPrograms[N_CL / 2] = {
  "NNNNNNNNNF4", "NNNNNNNNNF0", "NNNNJf44NNNF7", "PNNNNNNNNNF8", "PNJ664NNNNNF5", "NNNNNNNNNFe",
  "NUNNNNNNNF5", "NNNNNNNNNF6", "NNNNNNNNNFe", "NUNNNJa78NFb", "PNJ281NNNNFc", "PPNJ551NNNNUNF2",
  "NNNNNJc39NNUF2", "NNJ379NNNNF9", "NUNUNJ974NFc", "PNUNNNNNNNF6", "PNJ062NNNNNFd", "NUNNNJd45NNFd",
  "PNNNNNNNNNF8", "NNUJ460Jb60NFf", "NNNNNNNNNFb", "PNJ751NNNNNNF3", "NNNNNNNNNF4", "PNJ172NNNNN",
  "PNNNNNNNNNFa", "NUNNNJe63NNF3", "PNNNNNNNNNF9", "NNNNNNNNNF0", "PNNNNNNNNNFa", "PPNUNNNNNNUF1",
  "NNUNNNNNNF7", "NNNNNJ878NF1", "NUNUNNNNNFf",
};

const char* const* bench_programs() {
  return kPrograms;
}

}

extern "C" void kernel_launch(void* const* d_in, const int* in_sizes, int n_in, void* d_out, int out_size) {
  (void)in_sizes; (void)n_in; (void)out_size;
  static EncodeFn fn = nullptr;
  static int n_clusters = 0;
  if (!fn) {
    cudaDriverEntryPointQueryResult qr;
    void* f = nullptr;
    cudaGetDriverEntryPoint("cuTensorMapEncodeTiled", &f, cudaEnableDefault, &qr);
    fn = (EncodeFn)f;
    cudaFuncSetAttribute(fused_kernel, cudaFuncAttributeMaxDynamicSharedMemorySize, SMEM_BYTES);
    cudaLaunchConfig_t cfg = {};
    cfg.gridDim = dim3(132); cfg.blockDim = dim3(384); cfg.dynamicSmemBytes = SMEM_BYTES;
    cudaLaunchAttribute at[1];
    at[0].id = cudaLaunchAttributeClusterDimension; at[0].val.clusterDim.x = 2; at[0].val.clusterDim.y = 1; at[0].val.clusterDim.z = 1;
    cfg.attrs = at; cfg.numAttrs = 1;
    if (cudaOccupancyMaxActiveClusters(&n_clusters, fused_kernel, &cfg) != cudaSuccess || n_clusters < 1) n_clusters = 1;
    (void)cudaGetLastError();
  }
  static Params P;
  const CUtensorMapSwizzle S128 = CU_TENSOR_MAP_SWIZZLE_128B, S64 = CU_TENSOR_MAP_SWIZZLE_64B;
  for (int blk = 0; blk < 2; blk++) {
    void* const* in = d_in + 5 * blk;
    { const cuuint64_t d[] = {kD, kB * kSq}, s[] = {kD * 2}; const cuuint32_t b[] = {64, 128};
      encode(fn, &P.x[blk], in[0], 2, d, s, b, S128); }
    { const cuuint64_t d[] = {64, 8, 3, (cuuint64_t)kB * kH * kSk / 8}, s[] = {kDh * 2, 128, 8 * kDh * 2}; const cuuint32_t b[] = {64, 8, 3, 8};
      encode(fn, &P.k[blk], in[1], 4, d, s, b, S128);
      encode(fn, &P.v[blk], in[2], 4, d, s, b, S128); }
    { const cuuint64_t d[] = {64, kD, kHD / 64}, s[] = {kHD * 2, 128}; const cuuint32_t b[] = {64, 64, 3};
      encode(fn, &P.wq[blk], in[3], 3, d, s, b, S128); }
    { const cuuint64_t d[] = {32, 2, kHD / 8, 4, kD / 32}, s[] = {kD * 2, 8 * kD * 2, 2 * kD * 2, 64}; const cuuint32_t b[] = {32, 2, 4, 4, 5};
      encode(fn, &P.wo[blk], in[4], 5, d, s, b, S64); }
    { const cuuint64_t d[] = {64, 2, kHD / 8, 4, kD / 64}, s[] = {kD * 2, 8 * kD * 2, 2 * kD * 2, 128};
      const cuuint32_t b3[] = {64, 2, 4, 4, 3}, b2[] = {64, 2, 4, 4, 2};
      encode(fn, &P.wo3[blk], in[4], 5, d, s, b3, S128);
      encode(fn, &P.wo2[blk], in[4], 5, d, s, b2, S128); }
  }
  { const cuuint64_t d[] = {32, kB * kSq, 2 * kD / 32}, s[] = {2 * kD * 2, 64}; const cuuint32_t b[] = {32, 16, 1};
    encode(fn, &P.out, d_out, 3, d, s, b, S64); }

  P.xw[0] = (const char*)d_in[0]; P.xw[1] = (const char*)d_in[3];
  cudaGetSymbolAddress((void**)&P.g, g_scratch);
  P.dbg = DBG_DEFAULT;
  if (n_clusters >= N_CL && plan(bench_programs(), N_CL / 2, 0, P)) {
    fused_kernel<<<2 * N_CL, 384, SMEM_BYTES>>>(P);
  } else {
    char buf[2 * N_TEAM][16];
    const char* text[2 * N_TEAM];
    for (int i = 0; i < 2 * N_TEAM; i++) { snprintf(buf[i], sizeof(buf[i]), "NNNNNNNNF%x", i / 2); text[i] = buf[i]; }
    for (int phase = 1; phase <= 2; phase++) {
      plan(text, 2 * N_TEAM, phase, P);
      fused_kernel<<<8 * N_TEAM, 384, SMEM_BYTES>>>(P);
    }
  }
}
```

```cpp
#include <cuda_runtime.h>
#include <cuda_bf16.h>
#include <cuda.h>
#include <stdint.h>
#include <stdio.h>

namespace {

constexpr int kB = 8, kSq = 256, kD = 640, kH = 32, kSk = 1024, kDh = 192;
constexpr int kHD = kH * kDh;
constexpr uint32_t RING = 224 * 1024;
constexpr uint32_t SZ_KV = 24576;
constexpr uint32_t SZ_Q = 16384 + 24576;
constexpr uint32_t SZ_O = 16384 + 20480;
constexpr uint32_t SZ_W3 = 16384 + 24576, SZ_W2 = 16384 + 16384, SZ_W = SZ_W3 + 16384;
constexpr uint32_t SZ_PARK = 49152;
constexpr uint32_t SZ_OL = SZ_O + 8192;
constexpr int NBAR = 10;
constexpr int EARLY = 3;
constexpr int kSteps = kHD / 64;
constexpr int TAIL = 4;
constexpr uint32_t KV_CH = 64, KV_SBO = 3072;
constexpr int SMEM_BYTES = RING + 1024 + 1024;
constexpr int N_TEAM = 16, N_CL = 66, MAX_OPS = 24, MAX_EV = 80, N_TILE = N_TEAM * kH, MAX_PARK = 128, ID_PART = N_TILE + MAX_PARK;
enum : uint32_t { OP_END = 0, OP_Q = 1, OP_A = 2, OP_O = 3, F_PARK = 1 << 11,
                  C_WIDE = 1 << 27, C_PEND = 1 << 26, P_GATE = 1 << 12, P_WIDE = 1 << 11, P_LD = 1 << 12, P_PRE = 1 << 22,
                  I_NEXT = 8, E_ON = 1 << 15, E_FREE = 1 << 14, E_LAST = 1 << 13, E_DRAW = 1 << 12, E_JOB = 1 << 11 };

constexpr uint32_t DBG_DEFAULT = 0x040800;

struct alignas(1024) Scratch {
  unsigned int flag[2047];
  unsigned int ticket;
  uint4 part[N_TEAM * 2 * 2 * 5120];
  uint4 tile[N_TILE * 2 * 3072];
};

struct alignas(64) Params {
  const char* xw[2];
  uint16_t first[80];
  Scratch* g;
  uint32_t dbg;
  CUtensorMap x[2], wq[2], k[2], v[2], wo[2], wo3[2], wo2[2], out;
  struct {
    uint32_t c[MAX_OPS];
    uint32_t p[MAX_OPS];
    uint16_t ev[MAX_EV];
  } prog[N_CL];
  uint32_t job[N_CL];
  uint16_t slot[N_TILE];
  uint8_t info[ID_PART];
};

__device__ Scratch g_scratch;

template <int TB, int TA = 0>
__device__ __forceinline__ void wgmma_ss_n64(float (&d)[32], uint64_t da, uint64_t db, int scale_d) {
  asm volatile("{\n.reg .pred p;\nsetp.ne.b32 p, %34, 0;\n"
    "wgmma.mma_async.sync.aligned.m64n64k16.f32.bf16.bf16 {%0, %1, %2, %3, %4, %5, %6, %7, %8, %9, %10, %11, %12, %13, %14, %15, %16, %17, %18, %19, %20, %21, %22, %23, %24, %25, %26, %27, %28, %29, %30, %31}, %32, %33, p, 1, 1, %35, %36;\n}\n"
    : "+f"(d[0]), "+f"(d[1]), "+f"(d[2]), "+f"(d[3]), "+f"(d[4]), "+f"(d[5]), "+f"(d[6]), "+f"(d[7]), "+f"(d[8]), "+f"(d[9]), "+f"(d[10]), "+f"(d[11]), "+f"(d[12]), "+f"(d[13]), "+f"(d[14]), "+f"(d[15]), "+f"(d[16]), "+f"(d[17]), "+f"(d[18]), "+f"(d[19]), "+f"(d[20]), "+f"(d[21]), "+f"(d[22]), "+f"(d[23]), "+f"(d[24]), "+f"(d[25]), "+f"(d[26]), "+f"(d[27]), "+f"(d[28]), "+f"(d[29]), "+f"(d[30]), "+f"(d[31])
    : "l"(da), "l"(db), "r"(scale_d), "n"(TA), "n"(TB));
}
template <int TB>
__device__ __forceinline__ void wgmma_rs_n64(float (&d)[32], uint32_t a0, uint32_t a1, uint32_t a2, uint32_t a3, uint64_t db, int scale_d) {
  asm volatile("{\n.reg .pred p;\nsetp.ne.b32 p, %37, 0;\n"
    "wgmma.mma_async.sync.aligned.m64n64k16.f32.bf16.bf16 {%0, %1, %2, %3, %4, %5, %6, %7, %8, %9, %10, %11, %12, %13, %14, %15, %16, %17, %18, %19, %20, %21, %22, %23, %24, %25, %26, %27, %28, %29, %30, %31}, {%32, %33, %34, %35}, %36, p, 1, 1, %38;\n}\n"
    : "+f"(d[0]), "+f"(d[1]), "+f"(d[2]), "+f"(d[3]), "+f"(d[4]), "+f"(d[5]), "+f"(d[6]), "+f"(d[7]), "+f"(d[8]), "+f"(d[9]), "+f"(d[10]), "+f"(d[11]), "+f"(d[12]), "+f"(d[13]), "+f"(d[14]), "+f"(d[15]), "+f"(d[16]), "+f"(d[17]), "+f"(d[18]), "+f"(d[19]), "+f"(d[20]), "+f"(d[21]), "+f"(d[22]), "+f"(d[23]), "+f"(d[24]), "+f"(d[25]), "+f"(d[26]), "+f"(d[27]), "+f"(d[28]), "+f"(d[29]), "+f"(d[30]), "+f"(d[31])
    : "r"(a0), "r"(a1), "r"(a2), "r"(a3), "l"(db), "r"(scale_d), "n"(TB));
}
template <int TB, int TA = 0>
__device__ __forceinline__ void wgmma_ss_n128(float (&d)[64], uint64_t da, uint64_t db, int scale_d) {
  asm volatile("{\n.reg .pred p;\nsetp.ne.b32 p, %66, 0;\n"
    "wgmma.mma_async.sync.aligned.m64n128k16.f32.bf16.bf16 {%0, %1, %2, %3, %4, %5, %6, %7, %8, %9, %10, %11, %12, %13, %14, %15, %16, %17, %18, %19, %20, %21, %22, %23, %24, %25, %26, %27, %28, %29, %30, %31, %32, %33, %34, %35, %36, %37, %38, %39, %40, %41, %42, %43, %44, %45, %46, %47, %48, %49, %50, %51, %52, %53, %54, %55, %56, %57, %58, %59, %60, %61, %62, %63}, %64, %65, p, 1, 1, %67, %68;\n}\n"
    : "+f"(d[0]), "+f"(d[1]), "+f"(d[2]), "+f"(d[3]), "+f"(d[4]), "+f"(d[5]), "+f"(d[6]), "+f"(d[7]), "+f"(d[8]), "+f"(d[9]), "+f"(d[10]), "+f"(d[11]), "+f"(d[12]), "+f"(d[13]), "+f"(d[14]), "+f"(d[15]), "+f"(d[16]), "+f"(d[17]), "+f"(d[18]), "+f"(d[19]), "+f"(d[20]), "+f"(d[21]), "+f"(d[22]), "+f"(d[23]), "+f"(d[24]), "+f"(d[25]), "+f"(d[26]), "+f"(d[27]), "+f"(d[28]), "+f"(d[29]), "+f"(d[30]), "+f"(d[31]), "+f"(d[32]), "+f"(d[33]), "+f"(d[34]), "+f"(d[35]), "+f"(d[36]), "+f"(d[37]), "+f"(d[38]), "+f"(d[39]), "+f"(d[40]), "+f"(d[41]), "+f"(d[42]), "+f"(d[43]), "+f"(d[44]), "+f"(d[45]), "+f"(d[46]), "+f"(d[47]), "+f"(d[48]), "+f"(d[49]), "+f"(d[50]), "+f"(d[51]), "+f"(d[52]), "+f"(d[53]), "+f"(d[54]), "+f"(d[55]), "+f"(d[56]), "+f"(d[57]), "+f"(d[58]), "+f"(d[59]), "+f"(d[60]), "+f"(d[61]), "+f"(d[62]), "+f"(d[63])
    : "l"(da), "l"(db), "r"(scale_d), "n"(TA), "n"(TB));
}
template <int TB>
__device__ __forceinline__ void wgmma_rs_n128(float (&d)[64], uint32_t a0, uint32_t a1, uint32_t a2, uint32_t a3, uint64_t db, int scale_d) {
  asm volatile("{\n.reg .pred p;\nsetp.ne.b32 p, %69, 0;\n"
    "wgmma.mma_async.sync.aligned.m64n128k16.f32.bf16.bf16 {%0, %1, %2, %3, %4, %5, %6, %7, %8, %9, %10, %11, %12, %13, %14, %15, %16, %17, %18, %19, %20, %21, %22, %23, %24, %25, %26, %27, %28, %29, %30, %31, %32, %33, %34, %35, %36, %37, %38, %39, %40, %41, %42, %43, %44, %45, %46, %47, %48, %49, %50, %51, %52, %53, %54, %55, %56, %57, %58, %59, %60, %61, %62, %63}, {%64, %65, %66, %67}, %68, p, 1, 1, %70;\n}\n"
    : "+f"(d[0]), "+f"(d[1]), "+f"(d[2]), "+f"(d[3]), "+f"(d[4]), "+f"(d[5]), "+f"(d[6]), "+f"(d[7]), "+f"(d[8]), "+f"(d[9]), "+f"(d[10]), "+f"(d[11]), "+f"(d[12]), "+f"(d[13]), "+f"(d[14]), "+f"(d[15]), "+f"(d[16]), "+f"(d[17]), "+f"(d[18]), "+f"(d[19]), "+f"(d[20]), "+f"(d[21]), "+f"(d[22]), "+f"(d[23]), "+f"(d[24]), "+f"(d[25]), "+f"(d[26]), "+f"(d[27]), "+f"(d[28]), "+f"(d[29]), "+f"(d[30]), "+f"(d[31]), "+f"(d[32]), "+f"(d[33]), "+f"(d[34]), "+f"(d[35]), "+f"(d[36]), "+f"(d[37]), "+f"(d[38]), "+f"(d[39]), "+f"(d[40]), "+f"(d[41]), "+f"(d[42]), "+f"(d[43]), "+f"(d[44]), "+f"(d[45]), "+f"(d[46]), "+f"(d[47]), "+f"(d[48]), "+f"(d[49]), "+f"(d[50]), "+f"(d[51]), "+f"(d[52]), "+f"(d[53]), "+f"(d[54]), "+f"(d[55]), "+f"(d[56]), "+f"(d[57]), "+f"(d[58]), "+f"(d[59]), "+f"(d[60]), "+f"(d[61]), "+f"(d[62]), "+f"(d[63])
    : "r"(a0), "r"(a1), "r"(a2), "r"(a3), "l"(db), "r"(scale_d), "n"(TB));
}
template <int TB, int TA = 0>
__device__ __forceinline__ void wgmma_ss_n160(float (&d)[80], uint64_t da, uint64_t db, int scale_d) {
  asm volatile("{\n.reg .pred p;\nsetp.ne.b32 p, %82, 0;\n"
    "wgmma.mma_async.sync.aligned.m64n160k16.f32.bf16.bf16 {%0, %1, %2, %3, %4, %5, %6, %7, %8, %9, %10, %11, %12, %13, %14, %15, %16, %17, %18, %19, %20, %21, %22, %23, %24, %25, %26, %27, %28, %29, %30, %31, %32, %33, %34, %35, %36, %37, %38, %39, %40, %41, %42, %43, %44, %45, %46, %47, %48, %49, %50, %51, %52, %53, %54, %55, %56, %57, %58, %59, %60, %61, %62, %63, %64, %65, %66, %67, %68, %69, %70, %71, %72, %73, %74, %75, %76, %77, %78, %79}, %80, %81, p, 1, 1, %83, %84;\n}\n"
    : "+f"(d[0]), "+f"(d[1]), "+f"(d[2]), "+f"(d[3]), "+f"(d[4]), "+f"(d[5]), "+f"(d[6]), "+f"(d[7]), "+f"(d[8]), "+f"(d[9]), "+f"(d[10]), "+f"(d[11]), "+f"(d[12]), "+f"(d[13]), "+f"(d[14]), "+f"(d[15]), "+f"(d[16]), "+f"(d[17]), "+f"(d[18]), "+f"(d[19]), "+f"(d[20]), "+f"(d[21]), "+f"(d[22]), "+f"(d[23]), "+f"(d[24]), "+f"(d[25]), "+f"(d[26]), "+f"(d[27]), "+f"(d[28]), "+f"(d[29]), "+f"(d[30]), "+f"(d[31]), "+f"(d[32]), "+f"(d[33]), "+f"(d[34]), "+f"(d[35]), "+f"(d[36]), "+f"(d[37]), "+f"(d[38]), "+f"(d[39]), "+f"(d[40]), "+f"(d[41]), "+f"(d[42]), "+f"(d[43]), "+f"(d[44]), "+f"(d[45]), "+f"(d[46]), "+f"(d[47]), "+f"(d[48]), "+f"(d[49]), "+f"(d[50]), "+f"(d[51]), "+f"(d[52]), "+f"(d[53]), "+f"(d[54]), "+f"(d[55]), "+f"(d[56]), "+f"(d[57]), "+f"(d[58]), "+f"(d[59]), "+f"(d[60]), "+f"(d[61]), "+f"(d[62]), "+f"(d[63]), "+f"(d[64]), "+f"(d[65]), "+f"(d[66]), "+f"(d[67]), "+f"(d[68]), "+f"(d[69]), "+f"(d[70]), "+f"(d[71]), "+f"(d[72]), "+f"(d[73]), "+f"(d[74]), "+f"(d[75]), "+f"(d[76]), "+f"(d[77]), "+f"(d[78]), "+f"(d[79])
    : "l"(da), "l"(db), "r"(scale_d), "n"(TA), "n"(TB));
}
template <int TB>
__device__ __forceinline__ void wgmma_rs_n160(float (&d)[80], uint32_t a0, uint32_t a1, uint32_t a2, uint32_t a3, uint64_t db, int scale_d) {
  asm volatile("{\n.reg .pred p;\nsetp.ne.b32 p, %85, 0;\n"
    "wgmma.mma_async.sync.aligned.m64n160k16.f32.bf16.bf16 {%0, %1, %2, %3, %4, %5, %6, %7, %8, %9, %10, %11, %12, %13, %14, %15, %16, %17, %18, %19, %20, %21, %22, %23, %24, %25, %26, %27, %28, %29, %30, %31, %32, %33, %34, %35, %36, %37, %38, %39, %40, %41, %42, %43, %44, %45, %46, %47, %48, %49, %50, %51, %52, %53, %54, %55, %56, %57, %58, %59, %60, %61, %62, %63, %64, %65, %66, %67, %68, %69, %70, %71, %72, %73, %74, %75, %76, %77, %78, %79}, {%80, %81, %82, %83}, %84, p, 1, 1, %86;\n}\n"
    : "+f"(d[0]), "+f"(d[1]), "+f"(d[2]), "+f"(d[3]), "+f"(d[4]), "+f"(d[5]), "+f"(d[6]), "+f"(d[7]), "+f"(d[8]), "+f"(d[9]), "+f"(d[10]), "+f"(d[11]), "+f"(d[12]), "+f"(d[13]), "+f"(d[14]), "+f"(d[15]), "+f"(d[16]), "+f"(d[17]), "+f"(d[18]), "+f"(d[19]), "+f"(d[20]), "+f"(d[21]), "+f"(d[22]), "+f"(d[23]), "+f"(d[24]), "+f"(d[25]), "+f"(d[26]), "+f"(d[27]), "+f"(d[28]), "+f"(d[29]), "+f"(d[30]), "+f"(d[31]), "+f"(d[32]), "+f"(d[33]), "+f"(d[34]), "+f"(d[35]), "+f"(d[36]), "+f"(d[37]), "+f"(d[38]), "+f"(d[39]), "+f"(d[40]), "+f"(d[41]), "+f"(d[42]), "+f"(d[43]), "+f"(d[44]), "+f"(d[45]), "+f"(d[46]), "+f"(d[47]), "+f"(d[48]), "+f"(d[49]), "+f"(d[50]), "+f"(d[51]), "+f"(d[52]), "+f"(d[53]), "+f"(d[54]), "+f"(d[55]), "+f"(d[56]), "+f"(d[57]), "+f"(d[58]), "+f"(d[59]), "+f"(d[60]), "+f"(d[61]), "+f"(d[62]), "+f"(d[63]), "+f"(d[64]), "+f"(d[65]), "+f"(d[66]), "+f"(d[67]), "+f"(d[68]), "+f"(d[69]), "+f"(d[70]), "+f"(d[71]), "+f"(d[72]), "+f"(d[73]), "+f"(d[74]), "+f"(d[75]), "+f"(d[76]), "+f"(d[77]), "+f"(d[78]), "+f"(d[79])
    : "r"(a0), "r"(a1), "r"(a2), "r"(a3), "l"(db), "r"(scale_d), "n"(TB));
}
template <int TB, int TA = 0>
__device__ __forceinline__ void wgmma_ss_n192(float (&d)[96], uint64_t da, uint64_t db, int scale_d) {
  asm volatile("{\n.reg .pred p;\nsetp.ne.b32 p, %98, 0;\n"
    "wgmma.mma_async.sync.aligned.m64n192k16.f32.bf16.bf16 {%0, %1, %2, %3, %4, %5, %6, %7, %8, %9, %10, %11, %12, %13, %14, %15, %16, %17, %18, %19, %20, %21, %22, %23, %24, %25, %26, %27, %28, %29, %30, %31, %32, %33, %34, %35, %36, %37, %38, %39, %40, %41, %42, %43, %44, %45, %46, %47, %48, %49, %50, %51, %52, %53, %54, %55, %56, %57, %58, %59, %60, %61, %62, %63, %64, %65, %66, %67, %68, %69, %70, %71, %72, %73, %74, %75, %76, %77, %78, %79, %80, %81, %82, %83, %84, %85, %86, %87, %88, %89, %90, %91, %92, %93, %94, %95}, %96, %97, p, 1, 1, %99, %100;\n}\n"
    : "+f"(d[0]), "+f"(d[1]), "+f"(d[2]), "+f"(d[3]), "+f"(d[4]), "+f"(d[5]), "+f"(d[6]), "+f"(d[7]), "+f"(d[8]), "+f"(d[9]), "+f"(d[10]), "+f"(d[11]), "+f"(d[12]), "+f"(d[13]), "+f"(d[14]), "+f"(d[15]), "+f"(d[16]), "+f"(d[17]), "+f"(d[18]), "+f"(d[19]), "+f"(d[20]), "+f"(d[21]), "+f"(d[22]), "+f"(d[23]), "+f"(d[24]), "+f"(d[25]), "+f"(d[26]), "+f"(d[27]), "+f"(d[28]), "+f"(d[29]), "+f"(d[30]), "+f"(d[31]), "+f"(d[32]), "+f"(d[33]), "+f"(d[34]), "+f"(d[35]), "+f"(d[36]), "+f"(d[37]), "+f"(d[38]), "+f"(d[39]), "+f"(d[40]), "+f"(d[41]), "+f"(d[42]), "+f"(d[43]), "+f"(d[44]), "+f"(d[45]), "+f"(d[46]), "+f"(d[47]), "+f"(d[48]), "+f"(d[49]), "+f"(d[50]), "+f"(d[51]), "+f"(d[52]), "+f"(d[53]), "+f"(d[54]), "+f"(d[55]), "+f"(d[56]), "+f"(d[57]), "+f"(d[58]), "+f"(d[59]), "+f"(d[60]), "+f"(d[61]), "+f"(d[62]), "+f"(d[63]), "+f"(d[64]), "+f"(d[65]), "+f"(d[66]), "+f"(d[67]), "+f"(d[68]), "+f"(d[69]), "+f"(d[70]), "+f"(d[71]), "+f"(d[72]), "+f"(d[73]), "+f"(d[74]), "+f"(d[75]), "+f"(d[76]), "+f"(d[77]), "+f"(d[78]), "+f"(d[79]), "+f"(d[80]), "+f"(d[81]), "+f"(d[82]), "+f"(d[83]), "+f"(d[84]), "+f"(d[85]), "+f"(d[86]), "+f"(d[87]), "+f"(d[88]), "+f"(d[89]), "+f"(d[90]), "+f"(d[91]), "+f"(d[92]), "+f"(d[93]), "+f"(d[94]), "+f"(d[95])
    : "l"(da), "l"(db), "r"(scale_d), "n"(TA), "n"(TB));
}
template <int TB>
__device__ __forceinline__ void wgmma_rs_n192(float (&d)[96], uint32_t a0, uint32_t a1, uint32_t a2, uint32_t a3, uint64_t db, int scale_d) {
  asm volatile("{\n.reg .pred p;\nsetp.ne.b32 p, %101, 0;\n"
    "wgmma.mma_async.sync.aligned.m64n192k16.f32.bf16.bf16 {%0, %1, %2, %3, %4, %5, %6, %7, %8, %9, %10, %11, %12, %13, %14, %15, %16, %17, %18, %19, %20, %21, %22, %23, %24, %25, %26, %27, %28, %29, %30, %31, %32, %33, %34, %35, %36, %37, %38, %39, %40, %41, %42, %43, %44, %45, %46, %47, %48, %49, %50, %51, %52, %53, %54, %55, %56, %57, %58, %59, %60, %61, %62, %63, %64, %65, %66, %67, %68, %69, %70, %71, %72, %73, %74, %75, %76, %77, %78, %79, %80, %81, %82, %83, %84, %85, %86, %87, %88, %89, %90, %91, %92, %93, %94, %95}, {%96, %97, %98, %99}, %100, p, 1, 1, %102;\n}\n"
    : "+f"(d[0]), "+f"(d[1]), "+f"(d[2]), "+f"(d[3]), "+f"(d[4]), "+f"(d[5]), "+f"(d[6]), "+f"(d[7]), "+f"(d[8]), "+f"(d[9]), "+f"(d[10]), "+f"(d[11]), "+f"(d[12]), "+f"(d[13]), "+f"(d[14]), "+f"(d[15]), "+f"(d[16]), "+f"(d[17]), "+f"(d[18]), "+f"(d[19]), "+f"(d[20]), "+f"(d[21]), "+f"(d[22]), "+f"(d[23]), "+f"(d[24]), "+f"(d[25]), "+f"(d[26]), "+f"(d[27]), "+f"(d[28]), "+f"(d[29]), "+f"(d[30]), "+f"(d[31]), "+f"(d[32]), "+f"(d[33]), "+f"(d[34]), "+f"(d[35]), "+f"(d[36]), "+f"(d[37]), "+f"(d[38]), "+f"(d[39]), "+f"(d[40]), "+f"(d[41]), "+f"(d[42]), "+f"(d[43]), "+f"(d[44]), "+f"(d[45]), "+f"(d[46]), "+f"(d[47]), "+f"(d[48]), "+f"(d[49]), "+f"(d[50]), "+f"(d[51]), "+f"(d[52]), "+f"(d[53]), "+f"(d[54]), "+f"(d[55]), "+f"(d[56]), "+f"(d[57]), "+f"(d[58]), "+f"(d[59]), "+f"(d[60]), "+f"(d[61]), "+f"(d[62]), "+f"(d[63]), "+f"(d[64]), "+f"(d[65]), "+f"(d[66]), "+f"(d[67]), "+f"(d[68]), "+f"(d[69]), "+f"(d[70]), "+f"(d[71]), "+f"(d[72]), "+f"(d[73]), "+f"(d[74]), "+f"(d[75]), "+f"(d[76]), "+f"(d[77]), "+f"(d[78]), "+f"(d[79]), "+f"(d[80]), "+f"(d[81]), "+f"(d[82]), "+f"(d[83]), "+f"(d[84]), "+f"(d[85]), "+f"(d[86]), "+f"(d[87]), "+f"(d[88]), "+f"(d[89]), "+f"(d[90]), "+f"(d[91]), "+f"(d[92]), "+f"(d[93]), "+f"(d[94]), "+f"(d[95])
    : "r"(a0), "r"(a1), "r"(a2), "r"(a3), "l"(db), "r"(scale_d), "n"(TB));
}

__device__ __forceinline__ uint32_t smem_u32(const void* p) { return (uint32_t)__cvta_generic_to_shared(p); }
__device__ __forceinline__ void wg_fence() { asm volatile("wgmma.fence.sync.aligned;" ::: "memory"); }
__device__ __forceinline__ void wg_commit() { asm volatile("wgmma.commit_group.sync.aligned;" ::: "memory"); }
template <int N> __device__ __forceinline__ void wg_wait() { asm volatile("wgmma.wait_group.sync.aligned %0;" ::"n"(N) : "memory"); }
__device__ __forceinline__ void sched_fence(uint32_t& keep, bool never) {
  asm volatile("{\n.reg .pred p;\nsetp.ne.b32 p, %1, 0;\n@p mov.u32 %0, %%clock;\n}\n" : "+r"(keep) : "r"((int)never) : "memory");
}
template <int N> __device__ __forceinline__ void fence_regs(float (&r)[N]) {
#pragma unroll
  for (int i = 0; i < N; i++) asm volatile("" : "+f"(r[i])::"memory");
}
template <int N> __device__ __forceinline__ void undefine(float (&r)[N]) {
#pragma unroll
  for (int i = 0; i < N; i++) asm volatile("" : "=f"(r[i]));
}
template <int N> __device__ __forceinline__ void fence_regs(uint32_t (&r)[N]) {
#pragma unroll
  for (int i = 0; i < N; i++) asm volatile("" : "+r"(r[i])::"memory");
}
__device__ __forceinline__ uint64_t mk_desc(uint32_t a16, uint32_t lbo, uint32_t sbo, uint32_t swz) {
  uint64_t d;
  asm("mov.b64 %0, {%1, %2};" : "=l"(d) : "r"(a16 + ((lbo >> 4) << 16)), "r"((sbo >> 4) | (swz << 30)));
  return d;
}
__device__ __forceinline__ void mbar_init(uint32_t bar, uint32_t cnt) {
  asm volatile("mbarrier.init.shared::cta.b64 [%0], %1;" ::"r"(bar), "r"(cnt) : "memory");
}
__device__ __forceinline__ void mbar_expect(uint32_t bar, uint32_t tx) {
  asm volatile("mbarrier.arrive.expect_tx.shared::cta.b64 _, [%0], %1;" ::"r"(bar), "r"(tx) : "memory");
}
__device__ __forceinline__ bool mbar_test(uint32_t bar, uint32_t ph) {
  uint32_t ok;
  asm volatile("{\n.reg .pred p;\nmbarrier.test_wait.parity.shared::cta.b64 p, [%1], %2;\nselp.u32 %0, 1, 0, p;\n}\n"
               : "=r"(ok) : "r"(bar), "r"(ph) : "memory");
  return ok;
}
__device__ __forceinline__ bool mbar_try(uint32_t bar, uint32_t ph, uint32_t ns) {
  uint32_t ok;
  asm volatile("{\n.reg .pred p;\nmbarrier.try_wait.parity.shared::cta.b64 p, [%1], %2, %3;\nselp.u32 %0, 1, 0, p;\n}\n"
               : "=r"(ok) : "r"(bar), "r"(ph), "r"(ns) : "memory");
  return ok;
}
__device__ __forceinline__ void mbar_wait(uint32_t bar, uint32_t ph) {
  asm volatile("{\n.reg .pred p;\n.reg .u32 n;\nmov.u32 n, 0;\n"
               "LOOP:\nmbarrier.try_wait.parity.shared::cta.b64 p, [%0], %1;\n@p bra DONE;\n"
               "add.u32 n, n, 1;\nsetp.lt.u32 p, n, 0x1000000;\n@p bra LOOP;\ntrap;\n"
               "DONE:\n}\n" ::"r"(bar), "r"(ph) : "memory");
}
__device__ __forceinline__ void mbar_wait_long(uint32_t bar) {
  asm volatile("{\n.reg .pred p;\n.reg .u32 n;\nmov.u32 n, 0;\n"
               "LOOP:\nmbarrier.try_wait.parity.shared::cta.b64 p, [%0], 0, 20000;\n@p bra DONE;\n"
               "add.u32 n, n, 1;\nsetp.lt.u32 p, n, 0x100000;\n@p bra LOOP;\ntrap;\n"
               "DONE:\n}\n" ::"r"(bar) : "memory");
}
__device__ __forceinline__ void mbar_arrive_cluster_if(bool on, uint32_t addr) {
  asm volatile("{\n.reg .pred p;\nsetp.ne.b32 p, %1, 0;\n@p mbarrier.arrive.shared::cluster.b64 _, [%0];\n}\n" ::"r"(addr), "r"((int)on) : "memory");
}
__device__ __forceinline__ void mbar_arrive_cluster_n(uint32_t n, uint32_t addr) {
  asm volatile("{\n.reg .pred p;\nsetp.ne.b32 p, %1, 0;\n@p mbarrier.arrive.shared::cluster.b64 _, [%0], %1;\n}\n" ::"r"(addr), "r"(n) : "memory");
}
__device__ __forceinline__ void tma2d(uint32_t dst, const CUtensorMap* m, uint32_t bar, int c0, int c1) {
  asm volatile("cp.async.bulk.tensor.2d.shared::cluster.global.mbarrier::complete_tx::bytes [%0], [%1, {%3, %4}], [%2];"
               ::"r"(dst), "l"(m), "r"(bar), "r"(c0), "r"(c1) : "memory");
}
__device__ __forceinline__ void tma3d(uint32_t dst, const CUtensorMap* m, uint32_t bar, int c0, int c1, int c2) {
  asm volatile("cp.async.bulk.tensor.3d.shared::cluster.global.mbarrier::complete_tx::bytes [%0], [%1, {%3, %4, %5}], [%2];"
               ::"r"(dst), "l"(m), "r"(bar), "r"(c0), "r"(c1), "r"(c2) : "memory");
}
__device__ __forceinline__ void tma3d_mc(uint32_t dst, const CUtensorMap* m, uint32_t bar, int c0, int c1, int c2) {
  asm volatile("cp.async.bulk.tensor.3d.shared::cluster.global.mbarrier::complete_tx::bytes.multicast::cluster"
               " [%0], [%1, {%3, %4, %5}], [%2], %6;"
               ::"r"(dst), "l"(m), "r"(bar), "r"(c0), "r"(c1), "r"(c2), "h"((uint16_t)3) : "memory");
}
__device__ __forceinline__ void tma3d_store(const CUtensorMap* m, uint32_t src, int c0, int c1, int c2) {
  asm volatile("cp.async.bulk.tensor.3d.global.shared::cta.bulk_group [%0, {%2, %3, %4}], [%1];"
               ::"l"(m), "r"(src), "r"(c0), "r"(c1), "r"(c2) : "memory");
}
__device__ __forceinline__ void bar_sync(int id, int n) { asm volatile("bar.sync %0, %1;" ::"r"(id), "r"(n) : "memory"); }
__device__ __forceinline__ uint32_t pack_bf16(float lo, float hi) {
  uint32_t r;
  asm("cvt.rn.bf16x2.f32 %0, %1, %2;" : "=r"(r) : "f"(hi), "f"(lo));
  return r;
}
__device__ __forceinline__ float ex2(float x) {
  float y;
  asm("ex2.approx.ftz.f32 %0, %1;" : "=f"(y) : "f"(x));
  return y;
}
__device__ __forceinline__ float rcp(float x) {
  float y;
  asm("rcp.approx.ftz.f32 %0, %1;" : "=f"(y) : "f"(x));
  return y;
}
__device__ __forceinline__ void stsm4(uint32_t addr, uint32_t a, uint32_t b, uint32_t c, uint32_t d) {
  asm volatile("stmatrix.sync.aligned.m8n8.x4.shared.b16 [%0], {%1, %2, %3, %4};" ::"r"(addr), "r"(a), "r"(b), "r"(c), "r"(d) : "memory");
}

__device__ __forceinline__ void tma4d_mc_hint(uint32_t dst, const CUtensorMap* m, uint32_t bar, int c3, uint64_t pol) {
  asm volatile("cp.async.bulk.tensor.4d.shared::cluster.global.mbarrier::complete_tx::bytes.multicast::cluster.L2::cache_hint"
               " [%0], [%1, {%3, %3, %3, %4}], [%2], %5, %6;"
               ::"r"(dst), "l"(m), "r"(bar), "r"(0), "r"(c3), "h"((uint16_t)3), "l"(pol) : "memory");
}
__device__ __forceinline__ void tma5d_mc(uint32_t dst, const CUtensorMap* m, uint32_t bar, int c2, int c4) {
  asm volatile("cp.async.bulk.tensor.5d.shared::cluster.global.mbarrier::complete_tx::bytes.multicast::cluster"
               " [%0], [%1, {%3, %3, %4, %3, %5}], [%2], %6;"
               ::"r"(dst), "l"(m), "r"(bar), "r"(0), "r"(c2), "r"(c4), "h"((uint16_t)3) : "memory");
}
__device__ __forceinline__ void bulk_load_hint(uint32_t dst, const void* src, uint32_t bytes, uint32_t bar, uint64_t pol) {
  asm volatile("cp.async.bulk.shared::cluster.global.mbarrier::complete_tx::bytes.L2::cache_hint [%0], [%1], %2, [%3], %4;"
               ::"r"(dst), "l"(src), "r"(bytes), "r"(bar), "l"(pol) : "memory");
}
__device__ __forceinline__ void stg2_if(bool on, void* p, uint32_t a, uint32_t b, uint32_t c, uint32_t d, uint32_t e, uint32_t f,
                                        uint32_t g, uint32_t h, uint64_t pol) {
  asm volatile("{\n.reg .pred p;\nsetp.ne.b32 p, %10, 0;\n"
               "@p st.global.L2::cache_hint.v4.b32 [%0], {%1, %2, %3, %4}, %9;\n"
               "@p st.global.L2::cache_hint.v4.b32 [%0 + 512], {%5, %6, %7, %8}, %9;\n}\n"
               ::"l"(p), "r"(a), "r"(b), "r"(c), "r"(d), "r"(e), "r"(f), "r"(g), "r"(h), "l"(pol), "r"((int)on) : "memory");
}
__device__ __forceinline__ uint64_t evict_first() {
  uint64_t p;
  asm("createpolicy.fractional.L2::evict_first.b64 %0, 1.0;" : "=l"(p));
  return p;
}
__device__ __forceinline__ bool elect() {
  uint32_t ok;
  asm volatile("{\n.reg .pred p;\nelect.sync _|p, 0xffffffff;\nselp.u32 %0, 1, 0, p;\n}\n" : "=r"(ok));
  return ok;
}
__device__ __forceinline__ void mbar_arrive(uint32_t bar) {
  asm volatile("mbarrier.arrive.shared::cta.b64 _, [%0];" ::"r"(bar) : "memory");
}
__device__ __forceinline__ void mbar_arrive_if(bool on, uint32_t bar) {
  asm volatile("{\n.reg .pred p;\nsetp.ne.b32 p, %1, 0;\n@p mbarrier.arrive.shared::cta.b64 _, [%0];\n}\n" ::"r"(bar), "r"((int)on) : "memory");
}
__device__ __forceinline__ void lds2_if(bool on, uint32_t p, uint32_t (&t)[8]) {
  asm volatile("{\n.reg .pred p;\nsetp.ne.b32 p, %9, 0;\n@p ld.shared.v4.b32 {%0, %1, %2, %3}, [%8];\n@p ld.shared.v4.b32 {%4, %5, %6, %7}, [%8 + 512];\n}\n"
               : "+r"(t[0]), "+r"(t[1]), "+r"(t[2]), "+r"(t[3]), "+r"(t[4]), "+r"(t[5]), "+r"(t[6]), "+r"(t[7]) : "r"(p), "r"((int)on) : "memory");
}
__device__ __forceinline__ void lds128(uint32_t p, uint32_t& a, uint32_t& b, uint32_t& c, uint32_t& d) {
  asm volatile("ld.shared.v4.b32 {%0, %1, %2, %3}, [%4];" : "=r"(a), "=r"(b), "=r"(c), "=r"(d) : "r"(p) : "memory");
}
template <class T> __device__ __forceinline__ T* ptr_add(T* base, uint32_t bytes) {
  T* r;
  asm("{\n.reg .u32 lo, hi;\nmov.b64 {lo, hi}, %1;\nadd.cc.u32 lo, lo, %2;\naddc.u32 hi, hi, 0;\nmov.b64 %0, {lo, hi};\n}\n" : "=l"(r) : "l"(base), "r"(bytes));
  return r;
}
__device__ __forceinline__ uint32_t lds32(uint32_t p) {
  uint32_t v;
  asm volatile("ld.volatile.shared.u32 %0, [%1];" : "=r"(v) : "r"(p) : "memory");
  return v;
}
__device__ __forceinline__ uint32_t flag_get(const unsigned int* p) {
  uint32_t v;
  asm volatile("ld.acquire.gpu.global.u32 %0, [%1];" : "=r"(v) : "l"(p) : "memory");
  return v;
}
__device__ __forceinline__ uint32_t wait_word(uint32_t p, uint32_t target) {
  uint32_t v;
  asm volatile("{\n.reg .pred p;\n.reg .u32 n;\nmov.u32 n, 0;\n"
               "LOOP:\nld.acquire.cta.shared.u32 %0, [%1];\nsetp.ge.u32 p, %0, %2;\n@p bra DONE;\n"
               "nanosleep.u32 %3;\nadd.u32 n, n, 1;\nsetp.lt.u32 p, n, 0x400000;\n@p bra LOOP;\ntrap;\n"
               "DONE:\n}\n" : "=r"(v) : "r"(p), "r"(target), "n"(400) : "memory");
  return v;
}
__device__ __forceinline__ void flag_set(unsigned int* p, uint32_t v) {
  asm volatile("st.release.gpu.global.u32 [%0], %1;" ::"l"(p), "r"(v) : "memory");
}
__device__ __forceinline__ void flag_dec(unsigned int* p) {
  asm volatile("red.relaxed.gpu.global.add.u32 [%0], 0xffffffff;" ::"l"(p) : "memory");
}

struct Cursor {
  int bi;
  uint32_t ph;
  __device__ __forceinline__ void next() {
    if (++bi == NBAR) { bi = 0; ph ^= 1; }
  }
};

constexpr float kScaleLog2 = 0.07216878364870322f * 1.4426950408889634f;
constexpr float kSumLimit = 1048576.0f;

__global__ void __cluster_dims__(2, 1, 1) __launch_bounds__(384, 1)
fused_kernel(const __grid_constant__ Params P) {
  extern __shared__ uint8_t smem_raw[];
  const uint32_t sbase = (smem_u32(smem_raw) + 1023) & ~1023u;
  const uint32_t full0 = sbase + RING, empty0 = full0 + 8 * NBAR, odone0 = empty0 + 8 * NBAR, ev0 = odone0 + 8 * MAX_OPS;
  const uint32_t progress = ev0 + 8 * MAX_EV, jobw = progress + 4;
  const uint32_t rank = blockIdx.x & 1;
  const int role = blockIdx.x >> 1;
  const int wid = __shfl_sync(0xffffffffu, (int)(threadIdx.x >> 5), 0);
  const int wg = wid >> 2;

  if (wid < 8) {
    if (elect()) {
#pragma unroll
      for (int j = 0; j < 16; j++) {
        const int i = EARLY + 16 * wid + j;
        if (i < 2 * NBAR + MAX_OPS + MAX_EV) mbar_init(full0 + 8 * i, i < NBAR ? 1 : i < 2 * NBAR ? 16 : i < 2 * NBAR + MAX_OPS ? 8 : 1);
      }
      if (wid == 7) asm volatile("st.shared.v2.u32 [%0], {0, 0};\nfence.acq_rel.cta;" ::"r"(progress) : "memory");
      asm volatile("fence.mbarrier_init.release.cluster;" ::: "memory");
    }
  } else if (wid > 8) {
    const uint32_t g = blockIdx.x * 96 + threadIdx.x - 288, w = g - 2048;
    if (g < 4096) asm volatile("prefetch.global.L2 [%0];" ::"l"(g < 2048 ? P.xw[0] + g * (kD * 2) : P.xw[1] + (w >> 5) * (kHD * 2) + (w & 31) * 128));
  } else {
    const uint32_t op0 = P.first[role];
    if (elect()) {
#pragma unroll
      for (int k = 0; k < EARLY; k++) mbar_init(full0 + 8 * k, 1);
      asm volatile("fence.mbarrier_init.release.cluster;" ::: "memory");
      const int blk = (op0 >> 10) & 1;
      if ((op0 & 3) == OP_Q) {
#pragma unroll
        for (int k = 0; k < EARLY; k++) {
          mbar_expect(full0 + 8 * k, SZ_Q);
          tma2d(sbase + k * SZ_Q, &P.x[blk], full0 + 8 * k, 64 * k, ((op0 >> 7) & 7) * kSq + rank * 128);
          tma3d(sbase + k * SZ_Q + 16384, &P.wq[blk], full0 + 8 * k, 0, 64 * k, 3 * ((op0 >> 2) & 31));
        }
      }
      asm volatile("prefetch.tensormap [%0];" ::"l"(rank ? &P.v[blk] : &P.k[blk]) : "memory");
    }
  }
  __syncwarp();
  asm volatile("barrier.cluster.arrive.relaxed.aligned;\nbarrier.cluster.wait.aligned;" ::: "memory");

  if (wg < 2) {
    asm volatile("setmaxnreg.inc.sync.aligned.u32 240;");
    const uint32_t* prog = P.prog[role].c;
    const int lane = threadIdx.x & 31, warp = wid & 3;
    uint32_t empty_rem;
    asm volatile("mapa.shared::cluster.u32 %0, %1, %2;" : "=r"(empty_rem) : "r"(empty0), "r"(lane & 1));
    uint32_t keep = (threadIdx.x & 127) < 2 ? 4 : 0;
    auto release = [&](int slot) { mbar_arrive_cluster_n(keep, empty_rem + 8 * slot); };
    auto release_warp = [&](int slot, bool on = true) { mbar_arrive_cluster_if(lane < 2 && on, empty_rem + 8 * slot); };
    Cursor r{0, 0};
    const uint32_t ring16 = (sbase & 0x3FFFF) >> 4;
    uint32_t cur = ring16;
    bool rdy0 = false, rdy1 = false;
    auto probe1 = [&]() { rdy0 = mbar_test(full0 + 8 * r.bi, r.ph); };
    auto probe2 = [&]() {
      Cursor n = r;
      rdy0 = mbar_test(full0 + 8 * n.bi, n.ph);
      n.next();
      rdy1 = mbar_test(full0 + 8 * n.bi, n.ph);
    };
    auto take = [&](bool rdy, uint32_t bytes, uint32_t& addr) {
      const int bi = r.bi;
      if (__builtin_expect(!__all_sync(0xffffffffu, rdy), 0)) mbar_wait(full0 + 8 * r.bi, r.ph);
      r.next();
      if (cur > ring16 + ((RING - bytes) >> 4)) cur = ring16;
      addr = cur;
      cur += bytes >> 4;
      return bi;
    };
    const bool never = P.dbg == 0xffffffffu;
    uint32_t q[48];
#pragma unroll
    for (int i = 0; i < 48; i++) q[i] = 0;
    const int row = wg * 64 + warp * 16 + (lane >> 2);
    const int img0 = row * 4 + ((lane & 3) ^ ((row >> 1) & 3));
    uint4* pend = nullptr;
    bool pend_any = false;
    const uint64_t spol = evict_first();
    int pc = 0;
    auto slab = [&](int c, int i0) {
#pragma unroll
      for (int i = i0; i < 6; i++)
        stg2_if(c == i, pend + i * 512, q[8 * i], q[8 * i + 1], q[8 * i + 2], q[8 * i + 3],
                q[8 * i + 4], q[8 * i + 5], q[8 * i + 6], q[8 * i + 7], spol);
    };
    auto drain = [&](int c) {
      if (!pend_any || c >= 6) return;
      slab(c, 0);
      if (c == 5) {
        __syncwarp();
        mbar_arrive_if(lane == 0, odone0 - 8 + 8 * pc);
      }
    };

    for (;; pc++) {
      uint32_t op = prog[pc];
      const int type = op & 3;
      auto enter = [&]() {
        r.bi = (op >> 15) & 15; r.ph = (op >> 19) & 1; cur = ring16 + (((op >> 20) & 63) << 8);
      };
      enter();
      pend_any = op & C_PEND;
      uint32_t job = 0;
      if ((op & (3 | C_WIDE)) == OP_O) job = __shfl_sync(0xffffffffu, wait_word(jobw, 1), 0);
      if (type == OP_END || job == OP_O) {
#pragma unroll 1
        for (int c = 0; c < 6; c++) drain(c);
        asm volatile("barrier.cluster.arrive.relaxed;" ::: "memory");
        break;
      }
      {
        float s[32], o[96];
        uint32_t ad0;
        int bi0, sk1;
        uint32_t pa[16], pb[16];
        float mc0, mc1, l0, l1;
        bool shifted;
        uint32_t nop;
        auto expo = [&](float (&s)[32], uint32_t (&pout)[16], float& b0, float& b1, bool shift, auto mid) {
          float c0, c1;
#pragma unroll
          for (int i = 0; i < 8; i++) {
            const float e0 = ex2(shift ? s[4 * i] - mc0 : s[4 * i]), e1 = ex2(shift ? s[4 * i + 1] - mc0 : s[4 * i + 1]);
            const float e2 = ex2(shift ? s[4 * i + 2] - mc1 : s[4 * i + 2]), e3 = ex2(shift ? s[4 * i + 3] - mc1 : s[4 * i + 3]);
            if (i) { b0 += e0; c0 += e1; b1 += e2; c1 += e3; } else { b0 = e0; c0 = e1; b1 = e2; c1 = e3; }
            pout[2 * i] = pack_bf16(e0, e1); pout[2 * i + 1] = pack_bf16(e2, e3);
            if (i & 1) mid(i >> 1);
          }
          b0 += c0; b1 += c1;
        };
        auto rowmax = [&](float (&s)[32], float& m0, float& m1) {
          m0 = fmaxf(s[0], s[1]); m1 = fmaxf(s[2], s[3]);
#pragma unroll
          for (int i = 1; i < 8; i++) { m0 = fmaxf(m0, fmaxf(s[4 * i], s[4 * i + 1])); m1 = fmaxf(m1, fmaxf(s[4 * i + 2], s[4 * i + 3])); }
          m0 = fmaxf(m0, __shfl_xor_sync(0xffffffffu, m0, 1)); m1 = fmaxf(m1, __shfl_xor_sync(0xffffffffu, m1, 1));
          m0 = fmaxf(m0, __shfl_xor_sync(0xffffffffu, m0, 2)); m1 = fmaxf(m1, __shfl_xor_sync(0xffffffffu, m1, 2));
        };
        auto first = [&](float (&s)[32], int sk0, auto mid) {
          fence_regs(s);
          release(sk0);
          mc0 = 0.f; mc1 = 0.f;
          expo(s, pa, l0, l1, false, mid);
          shifted = __any_sync(0xffffffffu, !(fmaxf(l0, l1) <= kSumLimit && fminf(l0, l1) >= 1.f / kSumLimit));
          if (shifted) {
            rowmax(s, mc0, mc1);
            expo(s, pa, l0, l1, true, [](int) {});
          }
        };
        auto qk = [&](float (&s)[32], uint32_t ak, int k0 = 0, int k1 = 12) {
#pragma unroll
          for (int kk = k0; kk < k1; kk++)
            wgmma_rs_n64<0>(s, q[4 * kk], q[4 * kk + 1], q[4 * kk + 2], q[4 * kk + 3], mk_desc(ak, 16, KV_SBO, 1) + ((kk >> 2) * KV_CH + (kk & 3) * 2), kk != 0);
          if (k1 == 12) wg_commit();
        };
        auto pv = [&](uint32_t (&pin)[16], uint32_t av, int acc) {
#pragma unroll
          for (int kk = 0; kk < 4; kk++)
            wgmma_rs_n192<1>(o, pin[4 * kk], pin[4 * kk + 1], pin[4 * kk + 2], pin[4 * kk + 3], mk_desc(av, KV_CH * 16, KV_SBO, 1) + (kk * (KV_SBO / 8)), acc || (kk != 0));
          wg_commit();
        };
        auto finish = [&](uint32_t (&pout)[16], int sk, int sv) {
          probe2();
          wg_wait<1>();
          fence_regs(s);
          release(sk);
          float b0, b1;
#pragma unroll 1
          for (bool redo = false;; redo = true) {
            expo(s, pout, b0, b1, false, [](int) {});
            if (!__any_sync(0xffffffffu, !redo && (shifted || !(fmaxf(b0, b1) <= kSumLimit)))) break;
            shifted = true;
            rowmax(s, b0, b1);
            b0 = fmaxf(mc0, b0); b1 = fmaxf(mc1, b1);
            const float a0 = ex2(mc0 - b0), a1 = ex2(mc1 - b1);
            mc0 = b0; mc1 = b1;
            l0 *= a0; l1 *= a1;
            wg_wait<0>();
            fence_regs(o);
#pragma unroll
            for (int i = 0; i < 24; i++) { o[4 * i] *= a0; o[4 * i + 1] *= a0; o[4 * i + 2] *= a1; o[4 * i + 3] *= a1; }
#pragma unroll
            for (int i = 0; i < 32; i++) s[i] -= (i & 2) ? mc1 : mc0;
          }
          l0 += b0; l1 += b1;
          wg_wait<0>();
          fence_regs(o);
          release(sv);
        };
        auto step = [&](uint32_t (&pin)[16], uint32_t (&pout)[16]) {
          uint32_t ak, av;
          const int sk = take(rdy0, SZ_KV, ak), sv = take(rdy1, SZ_KV, av);
          wg_fence();
          qk(s, ak);
          pv(pin, av, 1);
          finish(pout, sk, sv);
        };
        auto unpark = [&]() {
          uint32_t ad, ak;
          const int bi = take(rdy0, SZ_PARK, ad);
#pragma unroll
          for (int i = 0; i < 12; i++) lds128(sbase + (ad - ring16 + img0) * 16 + (i >> 1) * 8192 + (i & 1) * 512, q[4 * i], q[4 * i + 1], q[4 * i + 2], q[4 * i + 3]);
          const int sk0 = take(false, SZ_KV, ak);
          fence_regs(q);
          release_warp(bi);
          wg_fence();
          qk(s, ak);
          probe2();
          return sk0;
        };
        auto mma4 = [&](uint32_t ad, int acc) {
#pragma unroll
          for (int kk = 0; kk < 4; kk++)
            wgmma_ss_n192<1>(o, mk_desc(ad + wg * 512, 16, 1024, 1) + (kk * 2), mk_desc(ad, 8192, 1024, 1) + (1024 + kk * 128), acc || kk != 0);
        };
        auto convert = [&](int i0, int i1) {
          sched_fence(keep, never);
#pragma unroll
          for (int i = i0; i < i1; i++) {
            q[i] = pack_bf16(o[2 * i] * kScaleLog2, o[2 * i + 1] * kScaleLog2);
            if ((i & 7) == 7 && i != i1 - 1) sched_fence(keep, never);
          }
          sched_fence(keep, never);
        };
        auto kend = [&](int bi, int k) {
          wg_commit();
          drain(k < 8 ? (0x54732710u >> (4 * k)) & 7 : 7);
          probe1();
          wg_wait<0>();
          release(bi);
        };
        if (type == OP_O) {
          int prev = 0;
          if (op & C_WIDE) {
            float d[64];
            auto mma3 = [&](uint32_t ad, int h, int acc) {
#pragma unroll
              for (int kk = 0; kk < 2; kk++)
                wgmma_ss_n192<1>(o, mk_desc(ad + wg * 256, 16, 512, 2) + (h * 512 + kk * 2), mk_desc(ad, 4096, 1024, 1) + (1024 + h * 768 + kk * 128), acc || kk);
            };
            auto mma2 = [&](uint32_t ad, uint32_t ob, int h, int acc) {
#pragma unroll
              for (int kk = 0; kk < 2; kk++)
                wgmma_ss_n128<1>(d, mk_desc(ad + wg * 256, 16, 512, 2) + (h * 512 + kk * 2), mk_desc(ad, 4096, 1024, 1) + (ob + h * 512 + kk * 128), acc || kk);
            };
            auto wstep = [&](uint32_t bytes, int acc, auto hook) {
              uint32_t ad;
              const int bi = take(rdy0, bytes, ad);
              wg_fence();
              if (bytes == SZ_W2) mma2(ad, 1024, 0, 1); else mma3(ad, 0, acc);
              if (bytes == SZ_W) mma3(ad, 1, 1);
              wg_commit();
              if (acc) { wg_wait<1>(); release(prev); }
              if (bytes == SZ_W) mma2(ad, 2560, 0, acc);
              if (bytes == SZ_W3) mma3(ad, 1, 1); else mma2(ad, bytes == SZ_W ? 2560 : 1024, 1, 1);
              wg_commit();
              prev = bi;
              hook();
              probe1();
              wg_wait<1>();
            };
            undefine(o);
            wstep(SZ_W, 0, [&]() { drain(0); });
#pragma unroll 1
            for (int k = 1; k < 6; k++) wstep(SZ_W, 1, [&]() { drain(k); });
#pragma unroll 1
            for (int k = ((op >> 2) & 127) - TAIL; k > 6; k--) {
              wstep(SZ_W, 1, []() {});
            }
#pragma unroll 1
            for (int k = 0; k < TAIL; k++) wstep(SZ_W2, 1, []() {});
            pend = ptr_add(P.g->part, (((op >> 9) & 31) * 2 + rank) * 81920 + 4 * 8192 + img0 * 16);
            wstep(SZ_W3, 1, [&]() {
              fence_regs(d);
#pragma unroll
              for (int i = 0; i < 32; i++) q[16 + i] = pack_bf16(d[2 * i], d[2 * i + 1]);
              slab(2, 2);
            });
#pragma unroll 1
            for (int k = 3; k < 6; k++) wstep(SZ_W3, 1, [&]() { slab(k, 2); });
            op = prog[pc + 1];
            enter();
            pend_any = true;
            pend -= 4 * 512;
            bi0 = take(rdy0 || (op & 3) != OP_Q, SZ_Q, ad0);
            sched_fence(keep, never);
            wg_wait<0>();
            fence_regs(o);
            release(prev);
#pragma unroll
            for (int i = 0; i < 48; i++) q[i] = pack_bf16(o[2 * i], o[2 * i + 1]);
            if ((op & 3) != OP_Q) continue;
            pc++;
            goto first_step;
          }
          float c[80];
          auto mma2 = [&](uint32_t ad, uint32_t oa, uint32_t ob, int acc) {
            wgmma_ss_n160<1>(c, mk_desc(ad + wg * 256, 16, 512, 2) + (oa), mk_desc(ad, 2048, 512, 2) + (1024 + ob), acc);
            wgmma_ss_n160<1>(c, mk_desc(ad + wg * 256, 16, 512, 2) + (oa + 2), mk_desc(ad, 2048, 512, 2) + (1024 + ob + 64), 1);
          };
          auto kstep = [&](int acc, auto hook, uint32_t bytes = SZ_O) {
            uint32_t ad;
            const int bi = take(rdy0, bytes, ad);
            wg_fence();
            mma2(ad, 0, 0, acc);
            wg_commit();
            if (acc) wg_wait<1>();
            if (acc == 1) release(prev);
            if (acc > 1) release_warp(prev, acc == 2 || wg == 0);
            mma2(ad, 512, 640, 1);
            wg_commit();
            prev = bi;
            hook();
            probe1();
            wg_wait<1>();
          };
          auto unblock = [&](int k) {
            if (__all_sync(0xffffffffu, rdy0) || __all_sync(0xffffffffu, mbar_try(full0 + 8 * r.bi, r.ph, 1500))) return;
#pragma unroll 1
            for (; k < 6; k++) drain(k);
            pend_any = false;
          };
          unblock(0);
          kstep(0, [&]() { drain(0); });
          int left = ((job >> 13) & 127) - 6;
#pragma unroll 1
          for (uint32_t k = 1, pace = left >= 29 ? 0x4511 : left <= 17 ? 0x1a : 0x155; k < 6; pace >>= 2, left--) {
            unblock(k);
            kstep(1, [&]() {
#pragma unroll 1
              for (int i = pace & 3; i > 0; i--) drain(k++);
            });
          }
#pragma unroll 1
          for (; left > 0; left--) kstep(1, []() {});
          uint32_t t[8], stage[3];
          float u[80];
          auto unpack = [&](int j) {
#pragma unroll
            for (int i = 0; i < 8; i++) {
              u[16 * j + 2 * i] = __uint_as_float(t[i] << 16); u[16 * j + 2 * i + 1] = __uint_as_float(t[i] & 0xffff0000u);
              asm volatile("" : "+f"(u[16 * j + 2 * i]), "+f"(u[16 * j + 2 * i + 1]));
            }
          };
#pragma unroll
          for (int i = 0; i < 8; i++) t[i] = 0;
          const uint32_t bytes = (job & P_LD) ? SZ_OL : SZ_O;
#pragma unroll
          for (int j = 0; j < 5; j++) {
            if (j == 2 && wg == 1) {
              wg_wait<0>();
              release_warp(prev);
              bar_sync(1, 256);
            }
            kstep(j == 2 ? 3 : 2, [&]() {
              if (j == 4) asm volatile("{\n.reg .pred p;\nsetp.eq.u32 p, %0, 0;\n@p bar.arrive 1, 256;\n}\n" ::"r"(wg) : "memory");
              if (j) unpack(j - 1);
              lds2_if(job & P_LD, sbase + (cur - ring16 + img0) * 16 - 8192, t);
              if (j >= 1 && j <= 3) stage[j - 1] = sbase + (cur - ring16) * 16 - bytes + wid * 1024;
            }, bytes);
          }
          unpack(4);
          sched_fence(keep, never);
          wg_wait<0>();
          fence_regs(c);
          release_warp(prev);
          asm volatile("barrier.cluster.arrive.relaxed;" ::: "memory");
#pragma unroll
          for (int i = 0; i < 10; i++) {
            const int v = (i & 1) * 2 + (lane >> 4);
            const uint32_t sa = stage[i >> 2] + (i & 2) * 4096;
            stsm4(sa + (lane & 15) * 64 + ((v ^ ((lane >> 1) & 3)) << 4), pack_bf16(c[8 * i] + u[8 * i], c[8 * i + 1] + u[8 * i + 1]),
                  pack_bf16(c[8 * i + 2] + u[8 * i + 2], c[8 * i + 3] + u[8 * i + 3]), pack_bf16(c[8 * i + 4] + u[8 * i + 4], c[8 * i + 5] + u[8 * i + 5]),
                  pack_bf16(c[8 * i + 6] + u[8 * i + 6], c[8 * i + 7] + u[8 * i + 7]));
          }
          asm volatile("fence.proxy.async.shared::cta;" ::: "memory");
          __syncwarp();
          if (elect()) {
#pragma unroll
            for (int i = 0; i < 5; i++)
              tma3d_store(&P.out, stage[i >> 1] + (i & 1) * 8192, 0, ((job >> 7) & 7) * kSq + rank * 128 + wid * 16, ((job >> 10) & 1) * 20 + ((job >> 20) & 3) * 5 + i);
            asm volatile("cp.async.bulk.commit_group;\ncp.async.bulk.wait_group.read 0;" ::: "memory");
          }
          __syncwarp();
          break;
        }
        bi0 = take(rdy0, SZ_Q, ad0);
      first_step:
        undefine(o);
        wg_fence();
        mma4(ad0, 0);
        kend(bi0, 0);
        fence_regs(o);
      next_head:
        {
#pragma unroll 1
          for (int k = 1; k < ((op & F_PARK) ? 10 : 8); k++) {
            uint32_t ad;
            const int bi = take(rdy0, SZ_Q, ad);
            wg_fence();
            mma4(ad, 1);
            kend(bi, k);
          }
          if (op & F_PARK) {
            fence_regs(o);
            convert(0, 48);
            pend = ptr_add(P.g->tile, (((op >> 2) & 511) * 2 + rank) * SZ_PARK + img0 * 16);
            continue;
          }
          uint32_t a8, a9, ak0, ak1;
          const int b8 = take(rdy0, SZ_Q, a8), b9 = take(false, SZ_Q, a9);
          wg_fence();
          mma4(a8, 1);
          wg_commit();
          mma4(a9, 1);
          wg_commit();
          pc++;
          wg_wait<1>();
          release(b8);
          const int sk0 = take(false, SZ_KV, ak0);
          wg_wait<0>();
          fence_regs(o);
          release(b9);
          float s0[32];
          convert(0, 32);
          wg_fence();
          qk(s0, ak0, 0, 4);
          convert(32, 48);
          wg_fence();
          qk(s0, ak0, 4, 12);
          sk1 = take(false, SZ_KV, ak1);
          probe1();
          wg_wait<0>();
          first(s0, sk0, [&](int i) {
            if (i == 0) return;
            sched_fence(keep, never);
            wg_fence();
            if (i == 1) qk(s, ak1, 0, 4);
            if (i == 2) qk(s, ak1, 4, 8);
            if (i == 3) qk(s, ak1, 8, 12);
            sched_fence(keep, never);
          });
        }
        for (;;) {
          {
            uint32_t av;
            const int sv = take(rdy0, SZ_KV, av);
            undefine(o);
            wg_fence();
            pv(pa, av, 0);
            finish(pb, sk1, sv);
          }
          nop = prog[pc + 1];
#pragma unroll 1
          for (int jj = 0; jj < 7; jj++) {
            step(pb, pa);
            step(pa, pb);
          }
          float i0, i1;
          auto last = [&]() {
            uint32_t av;
            const int sv = take(rdy0, SZ_KV, av);
            wg_fence();
            pv(pb, av, 1);
            sched_fence(keep, never);
            probe1();
            l0 += __shfl_xor_sync(0xffffffffu, l0, 1); l1 += __shfl_xor_sync(0xffffffffu, l1, 1);
            l0 += __shfl_xor_sync(0xffffffffu, l0, 2); l1 += __shfl_xor_sync(0xffffffffu, l1, 2);
            i0 = rcp(l0); i1 = rcp(l1);
            pend = ptr_add(P.g->tile, (((op >> 2) & 511) * 2 + rank) * SZ_PARK + img0 * 16);
            return sv;
          };
          auto normalise = [&](uint32_t (&d)[48], auto mid) {
#pragma unroll
            for (int i = 0; i < 24; i++) {
              d[8 * (i >> 2) + (i & 3)] = pack_bf16(o[4 * i] * i0, o[4 * i + 1] * i0);
              d[8 * (i >> 2) + (i & 3) + 4] = pack_bf16(o[4 * i + 2] * i1, o[4 * i + 3] * i1);
              if ((i & 1) && i != 23) sched_fence(keep, never);
              if ((i & 3) == 3 && i != 23) mid(i >> 2);
            }
          };
          const int sv = last();
          if ((nop & 3) != OP_A) {
            op = nop;
            enter();
            pend_any = true;
            bi0 = take(rdy0 || (nop & 3) != OP_Q, SZ_Q, ad0);
            sched_fence(keep, never);
            wg_wait<0>();
            fence_regs(o);
            release(sv);
            normalise(q, [](int) {});
            undefine(o);
            if ((nop & 3) != OP_Q) break;
            sched_fence(keep, never);
            wg_fence();
            mma4(ad0, 0);
            pc++;
            kend(bi0, 0);
            fence_regs(o);
            goto next_head;
          }
          const int sk0 = unpark();
          wg_wait<1>();
          fence_regs(o);
          release(sv);
          uint32_t t[48];
          auto st = [&](int i) {
            stg2_if(true, pend + i * 512, t[8 * i], t[8 * i + 1], t[8 * i + 2], t[8 * i + 3], t[8 * i + 4], t[8 * i + 5], t[8 * i + 6], t[8 * i + 7], spol);
          };
          normalise(t, [&](int i) { if (!(i & 1)) st(i >> 1); });
          wg_wait<0>();
          first(s, sk0, [&](int i) { if (i < 3) { sched_fence(keep, never); st(3 + i); } });
          __syncwarp();
          mbar_arrive_if(lane == 0, odone0 + 8 * pc);
          pc++;
          op = nop;
          uint32_t ak1;
          sk1 = take(rdy0, SZ_KV, ak1);
          rdy0 = rdy1;
          wg_fence();
          qk(s, ak1);
        }
      }
    }
    asm volatile("barrier.cluster.wait;" ::: "memory");
  } else {
    asm volatile("setmaxnreg.dec.sync.aligned.u32 24;");
    const uint32_t* prog = P.prog[role].p;
    unsigned int* flag = P.g->flag + rank;
    if (wid == 8) {
      Cursor tail{0, 0};
      int head = 0, sh = 0;
      uint32_t cur = 0, used = 0;
      uint64_t fifo = 0;
      uint32_t dst, bar, ev = ev0, done = 0;
      const uint64_t pol = evict_first();
      auto retire = [&]() {
        mbar_wait(empty0 + 8 * tail.bi, tail.ph);
        tail.next();
        used -= (uint32_t)fifo & 31;
        fifo >>= 5;
        sh -= 5;
        asm volatile("st.volatile.shared.u32 [%0], %1;" ::"r"(progress), "r"(++done) : "memory");
      };
      auto acquire = [&](uint32_t bytes) {
        uint32_t fp = bytes >> 12;
        if (cur + fp > (RING >> 12)) { fp += (RING >> 12) - cur; cur = 0; }
        used += fp;
        while (used > (RING >> 12) || sh == 5 * NBAR) retire();
        fifo |= (uint64_t)fp << sh;
        sh += 5;
        dst = sbase + (cur << 12);
        bar = full0 + 8 * head;
        cur += bytes >> 12;
        if (++head == NBAR) head = 0;
      };
      auto gate = [&]() {
        mbar_wait(ev, 0);
        ev += 8;
        asm volatile("fence.proxy.async.global;" ::: "memory");
      };
      for (int pc = 0;; pc++) {
        uint32_t op = prog[pc];
        const int type = op & 3;
        if (type == OP_END) break;
        if (op == OP_O) {
          gate();
          op = __shfl_sync(0xffffffffu, lds32(jobw), 0);
        }
        const int blk = (op >> 10) & 1;
        const int hd = P.slot[(op >> 2) & 511] >> 9;
        if (type == OP_Q) {
#pragma unroll 1
          for (int k = 0; k < 10; k++) {
            if (k == 9 && (op & P_GATE)) gate();
            acquire(SZ_Q);
            if ((pc > 0 || k >= EARLY) && elect()) {
              mbar_expect(bar, SZ_Q);
              tma2d(dst, &P.x[blk], bar, 64 * k, ((op >> 7) & 7) * kSq + rank * 128);
              if ((k & 1) == rank) tma3d_mc(dst + 16384, &P.wq[blk], bar, 0, 64 * k, 3 * hd);
            }
          }
        } else if (type == OP_A) {
          const int row0 = (((op >> 2) & 224) + hd) * kSk;
          const CUtensorMap* kv_map = rank ? &P.v[blk] : &P.k[blk];
          if (op & F_PARK) {
            gate();
            acquire(SZ_PARK);
            if (elect()) {
              mbar_expect(bar, SZ_PARK);
              bulk_load_hint(dst, &P.g->tile[((op >> 20) * 2 + rank) * 3072], SZ_PARK, bar, pol);
            }
          }
#pragma unroll 1
          for (int t = 0; t < 32; t++) {
            const int isv = t == 31 ? 1 : (t == 0 ? 0 : (~t & 1));
            const int j = isv ? (t - 1) >> 1 : (t + 1) >> 1;
            if (t == 31 && (op & P_GATE)) gate();
            acquire(SZ_KV);
            if (elect()) {
              mbar_expect(bar, SZ_KV);
              if (isv == (int)rank) tma4d_mc_hint(dst, kv_map, bar, row0 / 8 + 8 * j, pol);
            }
          }
        } else {
          const int n = (op >> 13) & 127, nw = (op & P_WIDE) ? n - TAIL : 0;
          const uint4* part = &P.g->part[((((op >> 6) & 30) + ((op >> 21) & 1)) * 2 + rank) * 5120 + ((op >> 20) & 1) * 2560];
#pragma unroll 1
          for (int i = 0; i < n + (nw ? TAIL : 0); i++) {
            const int k = nw ? (i < n ? i : i - TAIL) : kSteps - n + i, h = (k * 43) >> 7, col = 5 * ((op >> 20) & 3);
            const int sl = P.slot[((op >> 2) & 480) + h], row = 8 * (k + 3 * ((sl >> 9) - h)) + 4 * rank;
            const uint4* src = &P.g->tile[((sl & 511) * 2 + rank) * 3072 + (k - 3 * h) * 1024];
            const uint32_t j = (op & P_LD) ? i - n + 5 : 5, bytes = i < nw ? SZ_W : nw ? (i < n ? SZ_W2 : SZ_W3) : j < 5 ? SZ_OL : SZ_O;
            if ((op & P_PRE) ? i == 0 : j == 0) gate();
            if (i < n && (i == 0 || k == 3 * h)) gate();
            acquire(bytes);
            if (elect()) {
              mbar_expect(bar, bytes);
              if (bytes != SZ_W2) tma5d_mc(dst + 16384 + rank * (nw ? 12288 : 10240), nw ? &P.wo3[blk] : &P.wo[blk], bar, row, nw ? col / 2 : col);
              bulk_load_hint(dst, src, 16384, bar, pol);
              if (nw && i < n) tma5d_mc(dst + bytes - 16384 + rank * 8192, &P.wo2[blk], bar, row, col / 2 + 3);
              if (j < 5) bulk_load_hint(dst + SZ_O, part + j * 512, 8192, bar, pol);
              if ((op & P_PRE) && i < 10) asm volatile("cp.async.bulk.prefetch.L2.global [%0], 4096;" ::"l"(part + i * 256) : "memory");
            }
          }
        }
      }
#pragma unroll 1
      while (sh) retire();
    } else if (threadIdx.x == 288) {
      for (int pc = 0;; pc++) {
        const uint32_t op = prog[pc];
        const int type = op & 3;
        if (type == OP_END) break;
        if (type == OP_Q ? !(op & F_PARK) : type == OP_O && !(op & P_WIDE)) continue;
        const int id = type == OP_A ? (op >> 2) & 511 : type == OP_Q ? N_TILE + ((op >> 13) & 127) : ID_PART + ((op >> 5) & 60) + ((op >> 20) & 3);
        const uint32_t v = type == OP_O ? 1 : P.info[id] & 7;
        mbar_wait_long(odone0 + 8 * pc);
        flag_set(flag + 2 * id, v);
        if (type == OP_O && (op & P_WIDE)) flag_set(flag + 2 * id + 2, v);
      }
    } else if (wid == 10) {
      int i = threadIdx.x & 31;
      uint32_t e = i < 8 ? P.prog[role].ev[i] : 0;
      for (uint32_t n = 0; __any_sync(0xffffffffu, e); n++) {
        uint32_t job = lds32(jobw);
        const int togo = (e & E_DRAW) ? (e & 1023) - lds32(progress) : 99;
        if (togo <= 0 && rank == 0) {
          job = P.job[atomicInc(&P.g->ticket, gridDim.x / 2 - 1)];
          asm volatile("{\n.reg .u32 a;\nmapa.shared::cluster.u32 a, %0, 1;\nst.volatile.shared::cluster.u32 [a], %1;\n"
                       "st.volatile.shared.u32 [%0], %1;\n}\n" ::"r"(jobw), "r"(job) : "memory");
        }
        if ((e & E_JOB) && job) {
          const uint32_t j = e & 63, heads = job == OP_O ? 0 : kH - ((job >> 2) & 31), jp = !(job & P_LD) ? 63 : (job & P_PRE) ? 0 : heads - 1, h = j - (j > jp);
          e = j == jp ? (ID_PART + ((job >> 5) & 60) + ((job >> 20) & 3)) | E_ON | E_LAST : h < heads ? (((job >> 2) & 511) + h) | E_ON | E_LAST : 0;
        }
        unsigned int* f = ptr_add(flag, 8 * (e & 1023));
        const bool ok = (e & E_ON) ? flag_get(f) - 1 < ((e & E_FREE) ? 1 : 7) : (e & E_DRAW) && job;
        if (ok) {
          mbar_arrive(ev0 + 8 * i);
          if (e & (E_FREE | E_LAST)) flag_dec(f);
          i += 8;
          e = i < MAX_EV ? P.prog[role].ev[i] : 0;
        }
        asm volatile("{\n.reg .pred p;\nsetp.ge.u32 p, %0, 0x400000;\n@p trap;\n}\n" ::"r"(n));
        if (!__any_sync(0xffffffffu, ok)) __nanosleep(__any_sync(0xffffffffu, job || togo <= 2) ? 100 : 600);
      }
    } else if (threadIdx.x == 352) {
      uint32_t items = 0;
      auto read = [&](int id) {
        if (!(P.info[id] & I_NEXT)) return;
        wait_word(progress, items);
        flag_dec(flag + 2 * id);
      };
      for (int pc = 0;; pc++) {
        const uint32_t op = prog[pc];
        const int type = op & 3;
        if (type == OP_END) break;
        if (type == OP_O) {
          const uint32_t n = (op >> 13) & 127, base = items;
#pragma unroll 1
          for (uint32_t k = 3, id = (op >> 2) & 511; k <= n; k += 3, id++) {
            items = base + k + (k + TAIL > n ? TAIL : 0);
            read(id);
          }
          items = base + n + TAIL;
        } else if (type == OP_A) {
          if (op & F_PARK) { items++; read(N_TILE + ((op >> 13) & 127)); }
          items += 32;
        } else {
          items += 10;
        }
      }
    }
    __syncwarp();
    asm volatile("barrier.cluster.arrive.relaxed;\nbarrier.cluster.wait;" ::: "memory");
  }
}

typedef CUresult (*EncodeFn)(CUtensorMap*, CUtensorMapDataType, cuuint32_t, void*, const cuuint64_t*, const cuuint64_t*,
                             const cuuint32_t*, const cuuint32_t*, CUtensorMapInterleave, CUtensorMapSwizzle,
                             CUtensorMapL2promotion, CUtensorMapFloatOOBfill);

void encode(EncodeFn fn, CUtensorMap* m, const void* ptr, int rank, const cuuint64_t* dims, const cuuint64_t* strides,
            const cuuint32_t* box, CUtensorMapSwizzle swz) {
  const cuuint32_t es[5] = {1, 1, 1, 1, 1};
  CUresult r = fn(m, CU_TENSOR_MAP_DATA_TYPE_BFLOAT16, rank, const_cast<void*>(ptr), dims, strides, box, es,
                  CU_TENSOR_MAP_INTERLEAVE_NONE, swz, CU_TENSOR_MAP_L2_PROMOTION_L2_128B, CU_TENSOR_MAP_FLOAT_OOB_FILL_NONE);
  if (r != CUDA_SUCCESS) fprintf(stderr, "cuTensorMapEncodeTiled failed: %d\n", (int)r);
}

struct Op { int type, flags, id, n, quarter, park, item0, items; double t0, t1; };
struct Use { double ready, gate, need, freed; int readers, slot, prev; bool next; };
struct PlanStats { double end, slack, park_slack; int slots, parks; uint32_t own[N_CL]; };

bool plan(const char* const* text, int n_pair, int phase, Params& P, PlanStats* stats = nullptr) {
  constexpr double T_Q = 7900, T_A = 24850, T_U = 26300, T_O = 640, T_RUN = 800, T_WIDE = 1900, AHEAD = 3500, PUBLISH = 1500;
  const double margin = 256.0 * ((P.dbg >> 8) & 255);
  static Op op[N_CL][MAX_OPS];
  static Use use[ID_PART];
  int n_op[N_CL], covered[N_TEAM] = {}, finals[N_TEAM] = {};
  auto hex = [](char c) { return c <= '9' ? c - '0' : c - 'a' + 10; };
  for (int i = 0; i < n_pair; i++)
    for (const char* s = text[i]; *s; s++)
      if (*s == 'J') { if (covered[hex(s[1])]) return false; covered[hex(s[1])] = 10 * (s[2] - '0') + s[3] - '0'; }
  for (int c = 0; c < 2 * n_pair; c++) {
    int n = 0, items = 0;
    double t = 0;
    auto add = [&](int type, int flags, int id, int heads, int quarter, int its, double dt) {
      if (n < MAX_OPS) op[c][n] = {type, flags, id, heads, quarter, 0, items, its, t, t + dt};
      n++; items += its; t += dt;
    };
    for (const char* s = text[c >> 1]; *s; s++) {
      const int tm = hex(s[1]) & 15, nj = covered[tm];
      if (*s == 'N') { add(OP_Q, 0, 0, 0, 0, 10, T_Q); add(OP_A, 0, 0, 0, 0, 32, T_A); }
      if (*s == 'P') add(OP_Q, F_PARK, 0, 0, 0, 10, T_Q);
      if (*s == 'U') { if (n == 0 || n > MAX_OPS || op[c][n - 1].type != OP_A) return false; add(OP_A, F_PARK, 0, 0, 0, 33, T_U); }
      if (*s == 'J') { if (nj < TAIL + 6 || nj > kSteps - 11) return false; add(OP_O, P_WIDE, tm * kH, nj, 2 * (c & 1), nj + TAIL, 2 * T_O * nj + T_WIDE); }
      if (*s == 'F') { if (s[2]) return false; add(OP_O, nj ? P_LD : 0, tm * kH + nj / 3, kSteps - nj, finals[tm]++, kSteps - nj, T_O * (kSteps - nj) + T_RUN); }
    }
    if (n && n <= MAX_OPS && (op[c][n - 1].type != OP_O || (op[c][n - 1].flags & P_WIDE))) add(OP_O, 0, 0, 0, 0, 0, 0);
    add(OP_END, 0, 0, 0, 0, 0, 0);
    if (n > MAX_OPS || op[c][0].type != OP_Q) return false;
    n_op[c] = n - 1;
  }
  for (int t = 0; t < N_TEAM; t++) if (finals[t] != 4) return false;
  for (int i = 0; i < ID_PART; i++) use[i] = {0, 0, 1e18, 0, 0, 0, 0, false};
  struct Ref { double t; Op* o; int id; };
  static Ref att[N_TILE + 1], dem[N_TILE], prk[MAX_PARK + 1], unp[MAX_PARK + 1], wr[ID_PART];
  int n_att = 0, n_prk = 0, n_unp = 0;
  auto ready = [&](const Op* o) {
    const int nt = o[1].type;
    return o->t1 + (nt == OP_Q ? 6100 : o[1].n ? ((o[1].flags & P_WIDE) ? 7700 : 3900) : 1500) + PUBLISH;
  };
  for (int c = 0; c < 2 * n_pair; c++)
    for (Op* o = op[c]; o->type != OP_END; o++) {
      if (o->type == OP_A) { att[n_att] = {ready(o), o, 0}; if (++n_att > N_TILE) return false; }
      if (o->type == OP_A && o->flags) { unp[n_unp] = {o->t0 - AHEAD, o, 0}; if (++n_unp > MAX_PARK) return false; }
      if (o->type == OP_Q && o->flags) { prk[n_prk] = {ready(o), o, 0}; if (++n_prk > MAX_PARK) return false; }
      for (int i = 0; o->type == OP_O && i < o->n; i++) {
        const int nw = (o->flags & P_WIDE) ? o->n - TAIL : 0, k = nw ? i : kSteps - o->n + i;
        Use& u = use[o->id / kH * kH + k / 3];
        const double t = o->t0 + T_O * (i + (i < nw ? i : nw));
        if (t - AHEAD < u.need) u.need = t - AHEAD;
        const double f = !nw ? 1e18 : i + NBAR < o->items - TAIL || (nw && o[1].type != OP_O) ? t + T_O * (i < nw ? 2 : 1 + TAIL) + PUBLISH : 1e18;
        if (f > u.freed) u.freed = f;
        if (i == 0 || k % 3 == 0) u.readers++;
      }
    }
  if (n_att != N_TILE || n_prk != n_unp) return false;
  auto sort = [](Ref* r, int n) {
    for (int i = 1; i < n; i++)
      for (int j = i; j > 0 && r[j].t < r[j - 1].t; j--) { Ref x = r[j]; r[j] = r[j - 1]; r[j - 1] = x; }
  };
  for (int i = 0; i < N_TILE; i++) { const int id = (i & 15) * kH + (i >> 4); dem[i] = {use[id].need, nullptr, id}; }
  sort(att, n_att); sort(dem, N_TILE); sort(prk, n_prk); sort(unp, n_unp);
  PlanStats st = {0, 1e18, 1e18, 0, n_prk};
  int n_wr = 0;
  for (int i = 0; i < N_TILE; i++) {
    Op* o = att[i].o;
    o->id = dem[i].id;
    if (!o->flags) o[-1].id = o->id;
    if (dem[i].t - att[i].t < st.slack) st.slack = dem[i].t - att[i].t;
    wr[n_wr++] = {o->t1 - 2 * AHEAD, o, o->id};
  }
  for (int i = 0; i < n_prk; i++) {
    prk[i].o->id = unp[i].o->id;
    prk[i].o->park = unp[i].o->park = i;
    use[N_TILE + i].freed = unp[i].o->t0 + 2 * PUBLISH;
    use[N_TILE + i].readers = 1;
    if (unp[i].t - prk[i].t < st.park_slack) st.park_slack = unp[i].t - prk[i].t;
    wr[n_wr++] = {prk[i].o->t1 - 2 * AHEAD, prk[i].o, N_TILE + i};
  }
  for (int c = 0; c < 2 * n_pair; c++)
    for (int d = 0; d < 2 * n_pair; d++)
      for (Op *f = &op[c][n_op[c] - 1], *o = op[d]; f->n && o->type != OP_END; o++)
        if (o->type == OP_O && (o->flags & P_WIDE) && o->id / kH == f->id / kH) {
          if (f->t0 - o->t1 > 4096.0 * ((P.dbg >> 16) & 255)) f->flags |= P_PRE;
          const double slack = f->t0 + ((f->flags & P_PRE) ? 0 : (f->n - 5) * T_O) - AHEAD - ready(o);
          if (slack < st.park_slack) st.park_slack = slack;
        }
  int head[N_TILE];
  {
    const double window = 1024.0 * (P.dbg & 255);
    double last[2 * kH];
    int users[2 * kH] = {}, n = 0;
    bool done[N_TILE] = {};
    for (int c = 0; c < 2 * n_pair; c++)
      for (Op* o = op[c]; o->type != OP_END; o++) if (o->type == OP_Q) att[n++] = {o->t0 + 1e-3 * (o->id & 31), o, o->id};
    sort(att, n);
    for (int i = 0; i < n; i++) {
      const int id = att[i].id, t0 = id / kH * kH, b0 = id / (8 * kH) * kH;
      int best = -1;
      auto rank = [&](int h) {
        return users[b0 + h] && att[i].t - last[b0 + h] <= window ? last[b0 + h] - 1e9 : users[b0 + h] ? users[b0 + h] : -1.0;
      };
      for (int h = 0; h < kH; h++) if (!done[t0 + h] && (best < 0 || rank(h) < rank(best))) best = h;
      if (window == 0) best = id & 31;
      head[id] = best; done[t0 + best] = true; users[b0 + best]++; last[b0 + best] = att[i].t;
    }
  }
  sort(wr, n_wr);
  int holder[N_TILE];
  for (int i = 0; i < n_wr; i++) {
    int best = -1;
    for (int sl = 0; sl < st.slots; sl++)
      if (use[holder[sl]].freed + margin <= wr[i].t && (best < 0 || use[holder[sl]].freed < use[holder[best]].freed)) best = sl;
    Use& u = use[wr[i].id];
    if (best >= 0) { u.prev = holder[best]; use[u.prev].next = true; wr[i].o->flags |= P_GATE; }
    else if (st.slots == N_TILE) return false;
    else best = st.slots++;
    u.slot = best;
    holder[best] = wr[i].id;
  }
  {
    int pos[N_CL] = {}, flag[ID_PART + 4 * N_TEAM] = {}, seen[ID_PART] = {};
    auto goal = [&](int c) { return op[c][n_op[c] - 1].item0; };
    for (bool moved = true; moved;) {
      moved = false;
      for (int c = 0; c < 2 * n_pair; c++) {
        for (; pos[c] < goal(c); pos[c]++, moved = true) {
          bool ok = true;
          for (const Op* o = op[c]; o->type != OP_END; o++) {
            const int k = pos[c] - o->item0, own = o->type == OP_A ? o->id : N_TILE + o->park;
            if (k < 0 || k >= o->items) continue;
            if (o->type == OP_O) ok = k >= o->n || flag[o->id + k / 3];
            else if (k == o->items - 1 && (o->flags & P_GATE)) ok = seen[use[own].prev] == use[use[own].prev].readers;
            else if (k == 0 && o->type == OP_A && (o->flags & F_PARK)) ok = flag[N_TILE + o->park];
          }
          if (!ok) break;
          for (const Op* o = op[c]; o->type != OP_END; o++) {
            if (pos[c] == o->item0 + o->items + (o[1].type == OP_Q ? 7 : o[1].item0 == goal(c) ? -1 : 5)) {
              if (o->type == OP_A) flag[o->id] = 1;
              if (o->type == OP_Q && (o->flags & F_PARK)) flag[N_TILE + o->park] = 1;
              if (o->type == OP_O) flag[ID_PART + o->id / kH * 4 + o->quarter] = flag[ID_PART + o->id / kH * 4 + o->quarter + 1] = 1;
            }
            const int k = pos[c] - NBAR - o->item0, nw = o->n - TAIL;
            if (k == 0 && o->type == OP_A && (o->flags & F_PARK)) seen[N_TILE + o->park]++;
            if (o->type == OP_O && k >= 0 && k < o->items && (k < nw || k >= o->n) && (k < nw ? k : k - TAIL) % 3 == 2) seen[o->id + (k < nw ? k : k - TAIL) / 3]++;
          }
        }
      }
    }
    for (int c = 0; c < 2 * n_pair; c++) if (pos[c] < goal(c)) return false;
  }
  int n_job = 0, longest = 0;
  for (int t = 0; t < N_TEAM; t++) if (kH - covered[t] / 3 > longest) longest = kH - covered[t] / 3;
  for (int c = 0; c < 2 * n_pair; c++) {
    uint32_t items = 0, cur = 0, pend = 0;
    int n = 0, ev = 0;
    auto item = [&](uint32_t bytes, int count) {
      for (int i = 0; i < count; i++) { if (cur + bytes > RING) cur = 0; cur += bytes; items++; }
    };
    auto event = [&](uint32_t e) { if (ev < MAX_EV) P.prog[c].ev[ev] = e; ev++; };
    for (const Op* o = op[c];; o++) {
      if (o->type != OP_END && phase && (o->type == OP_O) != (phase == 2)) continue;
      uint32_t cw = o->type | (items % NBAR) << 15 | ((items / NBAR) & 1) << 19 | (cur >> 12) << 20 | pend, pw = o->type | o->id << 2 | o->flags;
      const int ps = use[N_TILE + o->park].slot;
      pend = 0;
      if (o->type == OP_O) {
        pw |= o->n << 13 | o->quarter << 20;
        if (o->flags & P_WIDE) {
          cw |= o->n << 2 | (o->id / kH * 2 + o->quarter / 2) << 9 | C_WIDE;
          item(SZ_W, o->n - TAIL);
          item(SZ_W2, TAIL);
          item(SZ_W3, TAIL);
          pend = C_PEND;
          for (int i = 0; 3 * i < o->n; i++) event((o->id + i) | E_ON | (use[o->id + i].next ? 0 : E_LAST));
        } else {
          dem[n_job++] = {o->t0 - 1e6 * o->n, nullptr, (int)pw};
          st.own[c] = pw;
          pw = OP_O;
          event(E_DRAW | (items < 16 ? 0 : items - 16));
          for (int i = 0; i <= longest; i++) event(E_JOB | i);
        }
      } else if (o->type != OP_END) {
        const bool parks = o->type == OP_Q && (o->flags & F_PARK);
        cw |= (parks ? ps : use[o->id].slot) << 2 | (o->flags & F_PARK);
        if (o->flags & F_PARK) pw |= o->park << 13 | ps << 20;
        if (o->type == OP_Q) item(SZ_Q, 10);
        else { if (o->flags & F_PARK) { item(SZ_PARK, 1); event((N_TILE + o->park) | E_ON | (use[N_TILE + o->park].next ? 0 : E_LAST)); } item(SZ_KV, 32); }
        if (parks || o->type == OP_A) pend = C_PEND;
        if (o->flags & P_GATE) event(use[parks ? N_TILE + o->park : o->id].prev | E_ON | E_FREE);
      }
      P.prog[c].c[n] = cw; P.prog[c].p[n++] = pw;
      if (o->type == OP_END) { if (o->t0 > st.end) st.end = o->t0; break; }
    }
    if (ev > MAX_EV) return false;
    while (ev < MAX_EV) P.prog[c].ev[ev++] = 0;
    while (n < MAX_OPS) { P.prog[c].c[n] = OP_END; P.prog[c].p[n++] = OP_END; }
    P.first[c] = (uint16_t)((P.prog[c].p[0] & (2047 - 124)) | head[(P.prog[c].p[0] >> 2) & 511] << 2);
  }
  sort(dem, n_job);
  for (int i = 0; i < n_job; i++) P.job[i] = dem[i].id;
  for (int i = 0; i < ID_PART; i++) {
    if (i < N_TILE) P.slot[i] = use[i].slot | head[i] << 9;
    P.info[i] = (use[i].readers + use[i].next) | (use[i].next ? I_NEXT : 0);
  }
  if (stats) *stats = st;
  return true;
}

const char* const kPrograms[N_CL / 2] = {
  "NNNNNNNNNF4", "NNNNNNNNNF0", "NNNNJf44NNNF7", "PNNNNNNNNNF8", "PNJ664NNNNNF5", "NNNNNNNNNFe",
  "NUNNNNNNNF5", "NNNNNNNNNF6", "NNNNNNNNNFe", "NUNNNJa78NFb", "PNJ281NNNNFc", "PPNJ551NNNNUNF2",
  "NNNNNJc39NNUF2", "NNJ379NNNNF9", "NUNUNJ974NFc", "PNUNNNNNNNF6", "PNJ062NNNNNFd", "NUNNNJd45NNFd",
  "PNNNNNNNNNF8", "NNUJ460Jb60NFf", "NNNNNNNNNFb", "PNJ751NNNNNNF3", "NNNNNNNNNF4", "PNJ172NNNNN",
  "PNNNNNNNNNFa", "NUNNNJe63NNF3", "PNNNNNNNNNF9", "NNNNNNNNNF0", "PNNNNNNNNNFa", "PPNUNNNNNNUF1",
  "NNUNNNNNNF7", "NNNNNJ878NF1", "NUNUNNNNNFf",
};

const char* const* bench_programs() {
  return kPrograms;
}

}

extern "C" void kernel_launch(void* const* d_in, const int* in_sizes, int n_in, void* d_out, int out_size) {
  (void)in_sizes; (void)n_in; (void)out_size;
  static EncodeFn fn = nullptr;
  static int n_clusters = 0;
  if (!fn) {
    cudaDriverEntryPointQueryResult qr;
    void* f = nullptr;
    cudaGetDriverEntryPoint("cuTensorMapEncodeTiled", &f, cudaEnableDefault, &qr);
    fn = (EncodeFn)f;
    cudaFuncSetAttribute(fused_kernel, cudaFuncAttributeMaxDynamicSharedMemorySize, SMEM_BYTES);
    cudaLaunchConfig_t cfg = {};
    cfg.gridDim = dim3(132); cfg.blockDim = dim3(384); cfg.dynamicSmemBytes = SMEM_BYTES;
    cudaLaunchAttribute at[1];
    at[0].id = cudaLaunchAttributeClusterDimension; at[0].val.clusterDim.x = 2; at[0].val.clusterDim.y = 1; at[0].val.clusterDim.z = 1;
    cfg.attrs = at; cfg.numAttrs = 1;
    if (cudaOccupancyMaxActiveClusters(&n_clusters, fused_kernel, &cfg) != cudaSuccess || n_clusters < 1) n_clusters = 1;
    (void)cudaGetLastError();
  }
  static Params P;
  const CUtensorMapSwizzle S128 = CU_TENSOR_MAP_SWIZZLE_128B, S64 = CU_TENSOR_MAP_SWIZZLE_64B;
  for (int blk = 0; blk < 2; blk++) {
    void* const* in = d_in + 5 * blk;
    { const cuuint64_t d[] = {kD, kB * kSq}, s[] = {kD * 2}; const cuuint32_t b[] = {64, 128};
      encode(fn, &P.x[blk], in[0], 2, d, s, b, S128); }
    { const cuuint64_t d[] = {64, 8, 3, (cuuint64_t)kB * kH * kSk / 8}, s[] = {kDh * 2, 128, 8 * kDh * 2}; const cuuint32_t b[] = {64, 8, 3, 8};
      encode(fn, &P.k[blk], in[1], 4, d, s, b, S128);
      encode(fn, &P.v[blk], in[2], 4, d, s, b, S128); }
    { const cuuint64_t d[] = {64, kD, kHD / 64}, s[] = {kHD * 2, 128}; const cuuint32_t b[] = {64, 64, 3};
      encode(fn, &P.wq[blk], in[3], 3, d, s, b, S128); }
    { const cuuint64_t d[] = {32, 2, kHD / 8, 4, kD / 32}, s[] = {kD * 2, 8 * kD * 2, 2 * kD * 2, 64}; const cuuint32_t b[] = {32, 2, 4, 4, 5};
      encode(fn, &P.wo[blk], in[4], 5, d, s, b, S64); }
    { const cuuint64_t d[] = {64, 2, kHD / 8, 4, kD / 64}, s[] = {kD * 2, 8 * kD * 2, 2 * kD * 2, 128};
      const cuuint32_t b3[] = {64, 2, 4, 4, 3}, b2[] = {64, 2, 4, 4, 2};
      encode(fn, &P.wo3[blk], in[4], 5, d, s, b3, S128);
      encode(fn, &P.wo2[blk], in[4], 5, d, s, b2, S128); }
  }
  { const cuuint64_t d[] = {32, kB * kSq, 2 * kD / 32}, s[] = {2 * kD * 2, 64}; const cuuint32_t b[] = {32, 16, 1};
    encode(fn, &P.out, d_out, 3, d, s, b, S64); }

  P.xw[0] = (const char*)d_in[0]; P.xw[1] = (const char*)d_in[3];
  cudaGetSymbolAddress((void**)&P.g, g_scratch);
  P.dbg = DBG_DEFAULT;
  if (n_clusters >= N_CL && plan(bench_programs(), N_CL / 2, 0, P)) {
    fused_kernel<<<2 * N_CL, 384, SMEM_BYTES>>>(P);
  } else {
    char buf[2 * N_TEAM][16];
    const char* text[2 * N_TEAM];
    for (int i = 0; i < 2 * N_TEAM; i++) { snprintf(buf[i], sizeof(buf[i]), "NNNNNNNNF%x", i / 2); text[i] = buf[i]; }
    for (int phase = 1; phase <= 2; phase++) {
      plan(text, 2 * N_TEAM, phase, P);
      fused_kernel<<<8 * N_TEAM, 384, SMEM_BYTES>>>(P);
    }
  }
}
```

```cpp
#include <cuda_runtime.h>
#include <cuda_bf16.h>
#include <cuda.h>
#include <stdint.h>
#include <stdio.h>

namespace {

constexpr int kB = 8, kSq = 256, kD = 640, kH = 32, kSk = 1024, kDh = 192;
constexpr int kHD = kH * kDh;
constexpr uint32_t RING = 224 * 1024;
constexpr uint32_t SZ_KV = 24576;
constexpr uint32_t SZ_Q = 16384 + 24576;
constexpr uint32_t SZ_O = 16384 + 20480;
constexpr uint32_t SZ_W3 = 16384 + 24576, SZ_W2 = 16384 + 16384, SZ_W = SZ_W3 + 16384;
constexpr uint32_t SZ_PARK = 49152;
constexpr uint32_t SZ_OL = SZ_O + 8192;
constexpr int NBAR = 10;
constexpr int EARLY = 3;
constexpr int kSteps = kHD / 64;
constexpr int TAIL = 4;
constexpr uint32_t KV_CH = 64, KV_SBO = 3072;
constexpr int SMEM_BYTES = RING + 1024 + 1024;
constexpr int N_TEAM = 16, N_CL = 66, MAX_OPS = 22, MAX_EV = 80, MAX_TAB = 47, N_TILE = N_TEAM * kH, MAX_PARK = 128, ID_PART = N_TILE + MAX_PARK;
enum : uint32_t { OP_END = 0, OP_Q = 1, OP_A = 2, OP_O = 3, F_PARK = 1 << 11,
                  C_WIDE = 1 << 27, C_PEND = 1 << 26, P_GATE = 1 << 12, P_WIDE = 1 << 11, P_LD = 1 << 12, P_PRE = 1 << 22,
                  I_NEXT = 8, E_ON = 1 << 15, E_FREE = 1 << 14, E_LAST = 1 << 13, E_DRAW = 1 << 12, E_JOB = 1 << 11 };

#define TU 25900
#define TW 1600
#define TP 1000
constexpr uint32_t DBG_DEFAULT = 0x040800;

struct alignas(1024) Scratch {
  unsigned int flag[2047];
  unsigned int ticket;
  uint4 part[N_TEAM * 2 * 2 * 5120];
  uint4 tile[N_TILE * 2 * 3072];
};

struct alignas(64) Params {
  const char* xw[2];
  uint16_t first[80];
  Scratch* g;
  uint32_t dbg;
  CUtensorMap x[2], wq[2], k[2], v[2], wo[2], wo3[2], wo2[2], out;
  struct {
    uint32_t c[MAX_OPS];
    uint32_t p[MAX_OPS];
    uint16_t n_ev, ev[MAX_TAB];
  } prog[N_CL];
  uint32_t job[N_CL];
  uint16_t slot[N_TILE];
  uint8_t info[ID_PART];
};

__device__ Scratch g_scratch;

template <int TB, int TA = 0>
__device__ __forceinline__ void wgmma_ss_n64(float (&d)[32], uint64_t da, uint64_t db, int scale_d) {
  asm volatile("{\n.reg .pred p;\nsetp.ne.b32 p, %34, 0;\n"
    "wgmma.mma_async.sync.aligned.m64n64k16.f32.bf16.bf16 {%0, %1, %2, %3, %4, %5, %6, %7, %8, %9, %10, %11, %12, %13, %14, %15, %16, %17, %18, %19, %20, %21, %22, %23, %24, %25, %26, %27, %28, %29, %30, %31}, %32, %33, p, 1, 1, %35, %36;\n}\n"
    : "+f"(d[0]), "+f"(d[1]), "+f"(d[2]), "+f"(d[3]), "+f"(d[4]), "+f"(d[5]), "+f"(d[6]), "+f"(d[7]), "+f"(d[8]), "+f"(d[9]), "+f"(d[10]), "+f"(d[11]), "+f"(d[12]), "+f"(d[13]), "+f"(d[14]), "+f"(d[15]), "+f"(d[16]), "+f"(d[17]), "+f"(d[18]), "+f"(d[19]), "+f"(d[20]), "+f"(d[21]), "+f"(d[22]), "+f"(d[23]), "+f"(d[24]), "+f"(d[25]), "+f"(d[26]), "+f"(d[27]), "+f"(d[28]), "+f"(d[29]), "+f"(d[30]), "+f"(d[31])
    : "l"(da), "l"(db), "r"(scale_d), "n"(TA), "n"(TB));
}
template <int TB>
__device__ __forceinline__ void wgmma_rs_n64(float (&d)[32], uint32_t a0, uint32_t a1, uint32_t a2, uint32_t a3, uint64_t db, int scale_d) {
  asm volatile("{\n.reg .pred p;\nsetp.ne.b32 p, %37, 0;\n"
    "wgmma.mma_async.sync.aligned.m64n64k16.f32.bf16.bf16 {%0, %1, %2, %3, %4, %5, %6, %7, %8, %9, %10, %11, %12, %13, %14, %15, %16, %17, %18, %19, %20, %21, %22, %23, %24, %25, %26, %27, %28, %29, %30, %31}, {%32, %33, %34, %35}, %36, p, 1, 1, %38;\n}\n"
    : "+f"(d[0]), "+f"(d[1]), "+f"(d[2]), "+f"(d[3]), "+f"(d[4]), "+f"(d[5]), "+f"(d[6]), "+f"(d[7]), "+f"(d[8]), "+f"(d[9]), "+f"(d[10]), "+f"(d[11]), "+f"(d[12]), "+f"(d[13]), "+f"(d[14]), "+f"(d[15]), "+f"(d[16]), "+f"(d[17]), "+f"(d[18]), "+f"(d[19]), "+f"(d[20]), "+f"(d[21]), "+f"(d[22]), "+f"(d[23]), "+f"(d[24]), "+f"(d[25]), "+f"(d[26]), "+f"(d[27]), "+f"(d[28]), "+f"(d[29]), "+f"(d[30]), "+f"(d[31])
    : "r"(a0), "r"(a1), "r"(a2), "r"(a3), "l"(db), "r"(scale_d), "n"(TB));
}
template <int TB, int TA = 0>
__device__ __forceinline__ void wgmma_ss_n128(float (&d)[64], uint64_t da, uint64_t db, int scale_d) {
  asm volatile("{\n.reg .pred p;\nsetp.ne.b32 p, %66, 0;\n"
    "wgmma.mma_async.sync.aligned.m64n128k16.f32.bf16.bf16 {%0, %1, %2, %3, %4, %5, %6, %7, %8, %9, %10, %11, %12, %13, %14, %15, %16, %17, %18, %19, %20, %21, %22, %23, %24, %25, %26, %27, %28, %29, %30, %31, %32, %33, %34, %35, %36, %37, %38, %39, %40, %41, %42, %43, %44, %45, %46, %47, %48, %49, %50, %51, %52, %53, %54, %55, %56, %57, %58, %59, %60, %61, %62, %63}, %64, %65, p, 1, 1, %67, %68;\n}\n"
    : "+f"(d[0]), "+f"(d[1]), "+f"(d[2]), "+f"(d[3]), "+f"(d[4]), "+f"(d[5]), "+f"(d[6]), "+f"(d[7]), "+f"(d[8]), "+f"(d[9]), "+f"(d[10]), "+f"(d[11]), "+f"(d[12]), "+f"(d[13]), "+f"(d[14]), "+f"(d[15]), "+f"(d[16]), "+f"(d[17]), "+f"(d[18]), "+f"(d[19]), "+f"(d[20]), "+f"(d[21]), "+f"(d[22]), "+f"(d[23]), "+f"(d[24]), "+f"(d[25]), "+f"(d[26]), "+f"(d[27]), "+f"(d[28]), "+f"(d[29]), "+f"(d[30]), "+f"(d[31]), "+f"(d[32]), "+f"(d[33]), "+f"(d[34]), "+f"(d[35]), "+f"(d[36]), "+f"(d[37]), "+f"(d[38]), "+f"(d[39]), "+f"(d[40]), "+f"(d[41]), "+f"(d[42]), "+f"(d[43]), "+f"(d[44]), "+f"(d[45]), "+f"(d[46]), "+f"(d[47]), "+f"(d[48]), "+f"(d[49]), "+f"(d[50]), "+f"(d[51]), "+f"(d[52]), "+f"(d[53]), "+f"(d[54]), "+f"(d[55]), "+f"(d[56]), "+f"(d[57]), "+f"(d[58]), "+f"(d[59]), "+f"(d[60]), "+f"(d[61]), "+f"(d[62]), "+f"(d[63])
    : "l"(da), "l"(db), "r"(scale_d), "n"(TA), "n"(TB));
}
template <int TB>
__device__ __forceinline__ void wgmma_rs_n128(float (&d)[64], uint32_t a0, uint32_t a1, uint32_t a2, uint32_t a3, uint64_t db, int scale_d) {
  asm volatile("{\n.reg .pred p;\nsetp.ne.b32 p, %69, 0;\n"
    "wgmma.mma_async.sync.aligned.m64n128k16.f32.bf16.bf16 {%0, %1, %2, %3, %4, %5, %6, %7, %8, %9, %10, %11, %12, %13, %14, %15, %16, %17, %18, %19, %20, %21, %22, %23, %24, %25, %26, %27, %28, %29, %30, %31, %32, %33, %34, %35, %36, %37, %38, %39, %40, %41, %42, %43, %44, %45, %46, %47, %48, %49, %50, %51, %52, %53, %54, %55, %56, %57, %58, %59, %60, %61, %62, %63}, {%64, %65, %66, %67}, %68, p, 1, 1, %70;\n}\n"
    : "+f"(d[0]), "+f"(d[1]), "+f"(d[2]), "+f"(d[3]), "+f"(d[4]), "+f"(d[5]), "+f"(d[6]), "+f"(d[7]), "+f"(d[8]), "+f"(d[9]), "+f"(d[10]), "+f"(d[11]), "+f"(d[12]), "+f"(d[13]), "+f"(d[14]), "+f"(d[15]), "+f"(d[16]), "+f"(d[17]), "+f"(d[18]), "+f"(d[19]), "+f"(d[20]), "+f"(d[21]), "+f"(d[22]), "+f"(d[23]), "+f"(d[24]), "+f"(d[25]), "+f"(d[26]), "+f"(d[27]), "+f"(d[28]), "+f"(d[29]), "+f"(d[30]), "+f"(d[31]), "+f"(d[32]), "+f"(d[33]), "+f"(d[34]), "+f"(d[35]), "+f"(d[36]), "+f"(d[37]), "+f"(d[38]), "+f"(d[39]), "+f"(d[40]), "+f"(d[41]), "+f"(d[42]), "+f"(d[43]), "+f"(d[44]), "+f"(d[45]), "+f"(d[46]), "+f"(d[47]), "+f"(d[48]), "+f"(d[49]), "+f"(d[50]), "+f"(d[51]), "+f"(d[52]), "+f"(d[53]), "+f"(d[54]), "+f"(d[55]), "+f"(d[56]), "+f"(d[57]), "+f"(d[58]), "+f"(d[59]), "+f"(d[60]), "+f"(d[61]), "+f"(d[62]), "+f"(d[63])
    : "r"(a0), "r"(a1), "r"(a2), "r"(a3), "l"(db), "r"(scale_d), "n"(TB));
}
template <int TB, int TA = 0>
__device__ __forceinline__ void wgmma_ss_n160(float (&d)[80], uint64_t da, uint64_t db, int scale_d) {
  asm volatile("{\n.reg .pred p;\nsetp.ne.b32 p, %82, 0;\n"
    "wgmma.mma_async.sync.aligned.m64n160k16.f32.bf16.bf16 {%0, %1, %2, %3, %4, %5, %6, %7, %8, %9, %10, %11, %12, %13, %14, %15, %16, %17, %18, %19, %20, %21, %22, %23, %24, %25, %26, %27, %28, %29, %30, %31, %32, %33, %34, %35, %36, %37, %38, %39, %40, %41, %42, %43, %44, %45, %46, %47, %48, %49, %50, %51, %52, %53, %54, %55, %56, %57, %58, %59, %60, %61, %62, %63, %64, %65, %66, %67, %68, %69, %70, %71, %72, %73, %74, %75, %76, %77, %78, %79}, %80, %81, p, 1, 1, %83, %84;\n}\n"
    : "+f"(d[0]), "+f"(d[1]), "+f"(d[2]), "+f"(d[3]), "+f"(d[4]), "+f"(d[5]), "+f"(d[6]), "+f"(d[7]), "+f"(d[8]), "+f"(d[9]), "+f"(d[10]), "+f"(d[11]), "+f"(d[12]), "+f"(d[13]), "+f"(d[14]), "+f"(d[15]), "+f"(d[16]), "+f"(d[17]), "+f"(d[18]), "+f"(d[19]), "+f"(d[20]), "+f"(d[21]), "+f"(d[22]), "+f"(d[23]), "+f"(d[24]), "+f"(d[25]), "+f"(d[26]), "+f"(d[27]), "+f"(d[28]), "+f"(d[29]), "+f"(d[30]), "+f"(d[31]), "+f"(d[32]), "+f"(d[33]), "+f"(d[34]), "+f"(d[35]), "+f"(d[36]), "+f"(d[37]), "+f"(d[38]), "+f"(d[39]), "+f"(d[40]), "+f"(d[41]), "+f"(d[42]), "+f"(d[43]), "+f"(d[44]), "+f"(d[45]), "+f"(d[46]), "+f"(d[47]), "+f"(d[48]), "+f"(d[49]), "+f"(d[50]), "+f"(d[51]), "+f"(d[52]), "+f"(d[53]), "+f"(d[54]), "+f"(d[55]), "+f"(d[56]), "+f"(d[57]), "+f"(d[58]), "+f"(d[59]), "+f"(d[60]), "+f"(d[61]), "+f"(d[62]), "+f"(d[63]), "+f"(d[64]), "+f"(d[65]), "+f"(d[66]), "+f"(d[67]), "+f"(d[68]), "+f"(d[69]), "+f"(d[70]), "+f"(d[71]), "+f"(d[72]), "+f"(d[73]), "+f"(d[74]), "+f"(d[75]), "+f"(d[76]), "+f"(d[77]), "+f"(d[78]), "+f"(d[79])
    : "l"(da), "l"(db), "r"(scale_d), "n"(TA), "n"(TB));
}
template <int TB>
__device__ __forceinline__ void wgmma_rs_n160(float (&d)[80], uint32_t a0, uint32_t a1, uint32_t a2, uint32_t a3, uint64_t db, int scale_d) {
  asm volatile("{\n.reg .pred p;\nsetp.ne.b32 p, %85, 0;\n"
    "wgmma.mma_async.sync.aligned.m64n160k16.f32.bf16.bf16 {%0, %1, %2, %3, %4, %5, %6, %7, %8, %9, %10, %11, %12, %13, %14, %15, %16, %17, %18, %19, %20, %21, %22, %23, %24, %25, %26, %27, %28, %29, %30, %31, %32, %33, %34, %35, %36, %37, %38, %39, %40, %41, %42, %43, %44, %45, %46, %47, %48, %49, %50, %51, %52, %53, %54, %55, %56, %57, %58, %59, %60, %61, %62, %63, %64, %65, %66, %67, %68, %69, %70, %71, %72, %73, %74, %75, %76, %77, %78, %79}, {%80, %81, %82, %83}, %84, p, 1, 1, %86;\n}\n"
    : "+f"(d[0]), "+f"(d[1]), "+f"(d[2]), "+f"(d[3]), "+f"(d[4]), "+f"(d[5]), "+f"(d[6]), "+f"(d[7]), "+f"(d[8]), "+f"(d[9]), "+f"(d[10]), "+f"(d[11]), "+f"(d[12]), "+f"(d[13]), "+f"(d[14]), "+f"(d[15]), "+f"(d[16]), "+f"(d[17]), "+f"(d[18]), "+f"(d[19]), "+f"(d[20]), "+f"(d[21]), "+f"(d[22]), "+f"(d[23]), "+f"(d[24]), "+f"(d[25]), "+f"(d[26]), "+f"(d[27]), "+f"(d[28]), "+f"(d[29]), "+f"(d[30]), "+f"(d[31]), "+f"(d[32]), "+f"(d[33]), "+f"(d[34]), "+f"(d[35]), "+f"(d[36]), "+f"(d[37]), "+f"(d[38]), "+f"(d[39]), "+f"(d[40]), "+f"(d[41]), "+f"(d[42]), "+f"(d[43]), "+f"(d[44]), "+f"(d[45]), "+f"(d[46]), "+f"(d[47]), "+f"(d[48]), "+f"(d[49]), "+f"(d[50]), "+f"(d[51]), "+f"(d[52]), "+f"(d[53]), "+f"(d[54]), "+f"(d[55]), "+f"(d[56]), "+f"(d[57]), "+f"(d[58]), "+f"(d[59]), "+f"(d[60]), "+f"(d[61]), "+f"(d[62]), "+f"(d[63]), "+f"(d[64]), "+f"(d[65]), "+f"(d[66]), "+f"(d[67]), "+f"(d[68]), "+f"(d[69]), "+f"(d[70]), "+f"(d[71]), "+f"(d[72]), "+f"(d[73]), "+f"(d[74]), "+f"(d[75]), "+f"(d[76]), "+f"(d[77]), "+f"(d[78]), "+f"(d[79])
    : "r"(a0), "r"(a1), "r"(a2), "r"(a3), "l"(db), "r"(scale_d), "n"(TB));
}
template <int TB, int TA = 0>
__device__ __forceinline__ void wgmma_ss_n192(float (&d)[96], uint64_t da, uint64_t db, int scale_d) {
  asm volatile("{\n.reg .pred p;\nsetp.ne.b32 p, %98, 0;\n"
    "wgmma.mma_async.sync.aligned.m64n192k16.f32.bf16.bf16 {%0, %1, %2, %3, %4, %5, %6, %7, %8, %9, %10, %11, %12, %13, %14, %15, %16, %17, %18, %19, %20, %21, %22, %23, %24, %25, %26, %27, %28, %29, %30, %31, %32, %33, %34, %35, %36, %37, %38, %39, %40, %41, %42, %43, %44, %45, %46, %47, %48, %49, %50, %51, %52, %53, %54, %55, %56, %57, %58, %59, %60, %61, %62, %63, %64, %65, %66, %67, %68, %69, %70, %71, %72, %73, %74, %75, %76, %77, %78, %79, %80, %81, %82, %83, %84, %85, %86, %87, %88, %89, %90, %91, %92, %93, %94, %95}, %96, %97, p, 1, 1, %99, %100;\n}\n"
    : "+f"(d[0]), "+f"(d[1]), "+f"(d[2]), "+f"(d[3]), "+f"(d[4]), "+f"(d[5]), "+f"(d[6]), "+f"(d[7]), "+f"(d[8]), "+f"(d[9]), "+f"(d[10]), "+f"(d[11]), "+f"(d[12]), "+f"(d[13]), "+f"(d[14]), "+f"(d[15]), "+f"(d[16]), "+f"(d[17]), "+f"(d[18]), "+f"(d[19]), "+f"(d[20]), "+f"(d[21]), "+f"(d[22]), "+f"(d[23]), "+f"(d[24]), "+f"(d[25]), "+f"(d[26]), "+f"(d[27]), "+f"(d[28]), "+f"(d[29]), "+f"(d[30]), "+f"(d[31]), "+f"(d[32]), "+f"(d[33]), "+f"(d[34]), "+f"(d[35]), "+f"(d[36]), "+f"(d[37]), "+f"(d[38]), "+f"(d[39]), "+f"(d[40]), "+f"(d[41]), "+f"(d[42]), "+f"(d[43]), "+f"(d[44]), "+f"(d[45]), "+f"(d[46]), "+f"(d[47]), "+f"(d[48]), "+f"(d[49]), "+f"(d[50]), "+f"(d[51]), "+f"(d[52]), "+f"(d[53]), "+f"(d[54]), "+f"(d[55]), "+f"(d[56]), "+f"(d[57]), "+f"(d[58]), "+f"(d[59]), "+f"(d[60]), "+f"(d[61]), "+f"(d[62]), "+f"(d[63]), "+f"(d[64]), "+f"(d[65]), "+f"(d[66]), "+f"(d[67]), "+f"(d[68]), "+f"(d[69]), "+f"(d[70]), "+f"(d[71]), "+f"(d[72]), "+f"(d[73]), "+f"(d[74]), "+f"(d[75]), "+f"(d[76]), "+f"(d[77]), "+f"(d[78]), "+f"(d[79]), "+f"(d[80]), "+f"(d[81]), "+f"(d[82]), "+f"(d[83]), "+f"(d[84]), "+f"(d[85]), "+f"(d[86]), "+f"(d[87]), "+f"(d[88]), "+f"(d[89]), "+f"(d[90]), "+f"(d[91]), "+f"(d[92]), "+f"(d[93]), "+f"(d[94]), "+f"(d[95])
    : "l"(da), "l"(db), "r"(scale_d), "n"(TA), "n"(TB));
}
template <int TB>
__device__ __forceinline__ void wgmma_rs_n192(float (&d)[96], uint32_t a0, uint32_t a1, uint32_t a2, uint32_t a3, uint64_t db, int scale_d) {
  asm volatile("{\n.reg .pred p;\nsetp.ne.b32 p, %101, 0;\n"
    "wgmma.mma_async.sync.aligned.m64n192k16.f32.bf16.bf16 {%0, %1, %2, %3, %4, %5, %6, %7, %8, %9, %10, %11, %12, %13, %14, %15, %16, %17, %18, %19, %20, %21, %22, %23, %24, %25, %26, %27, %28, %29, %30, %31, %32, %33, %34, %35, %36, %37, %38, %39, %40, %41, %42, %43, %44, %45, %46, %47, %48, %49, %50, %51, %52, %53, %54, %55, %56, %57, %58, %59, %60, %61, %62, %63, %64, %65, %66, %67, %68, %69, %70, %71, %72, %73, %74, %75, %76, %77, %78, %79, %80, %81, %82, %83, %84, %85, %86, %87, %88, %89, %90, %91, %92, %93, %94, %95}, {%96, %97, %98, %99}, %100, p, 1, 1, %102;\n}\n"
    : "+f"(d[0]), "+f"(d[1]), "+f"(d[2]), "+f"(d[3]), "+f"(d[4]), "+f"(d[5]), "+f"(d[6]), "+f"(d[7]), "+f"(d[8]), "+f"(d[9]), "+f"(d[10]), "+f"(d[11]), "+f"(d[12]), "+f"(d[13]), "+f"(d[14]), "+f"(d[15]), "+f"(d[16]), "+f"(d[17]), "+f"(d[18]), "+f"(d[19]), "+f"(d[20]), "+f"(d[21]), "+f"(d[22]), "+f"(d[23]), "+f"(d[24]), "+f"(d[25]), "+f"(d[26]), "+f"(d[27]), "+f"(d[28]), "+f"(d[29]), "+f"(d[30]), "+f"(d[31]), "+f"(d[32]), "+f"(d[33]), "+f"(d[34]), "+f"(d[35]), "+f"(d[36]), "+f"(d[37]), "+f"(d[38]), "+f"(d[39]), "+f"(d[40]), "+f"(d[41]), "+f"(d[42]), "+f"(d[43]), "+f"(d[44]), "+f"(d[45]), "+f"(d[46]), "+f"(d[47]), "+f"(d[48]), "+f"(d[49]), "+f"(d[50]), "+f"(d[51]), "+f"(d[52]), "+f"(d[53]), "+f"(d[54]), "+f"(d[55]), "+f"(d[56]), "+f"(d[57]), "+f"(d[58]), "+f"(d[59]), "+f"(d[60]), "+f"(d[61]), "+f"(d[62]), "+f"(d[63]), "+f"(d[64]), "+f"(d[65]), "+f"(d[66]), "+f"(d[67]), "+f"(d[68]), "+f"(d[69]), "+f"(d[70]), "+f"(d[71]), "+f"(d[72]), "+f"(d[73]), "+f"(d[74]), "+f"(d[75]), "+f"(d[76]), "+f"(d[77]), "+f"(d[78]), "+f"(d[79]), "+f"(d[80]), "+f"(d[81]), "+f"(d[82]), "+f"(d[83]), "+f"(d[84]), "+f"(d[85]), "+f"(d[86]), "+f"(d[87]), "+f"(d[88]), "+f"(d[89]), "+f"(d[90]), "+f"(d[91]), "+f"(d[92]), "+f"(d[93]), "+f"(d[94]), "+f"(d[95])
    : "r"(a0), "r"(a1), "r"(a2), "r"(a3), "l"(db), "r"(scale_d), "n"(TB));
}

__device__ __forceinline__ uint32_t smem_u32(const void* p) { return (uint32_t)__cvta_generic_to_shared(p); }
__device__ __forceinline__ void wg_fence() { asm volatile("wgmma.fence.sync.aligned;" ::: "memory"); }
__device__ __forceinline__ void wg_commit() { asm volatile("wgmma.commit_group.sync.aligned;" ::: "memory"); }
template <int N> __device__ __forceinline__ void wg_wait() { asm volatile("wgmma.wait_group.sync.aligned %0;" ::"n"(N) : "memory"); }
__device__ __forceinline__ void sched_fence(uint32_t& keep, bool never) {
  asm volatile("{\n.reg .pred p;\nsetp.ne.b32 p, %1, 0;\n@p mov.u32 %0, %%clock;\n}\n" : "+r"(keep) : "r"((int)never) : "memory");
}
template <int N> __device__ __forceinline__ void fence_regs(float (&r)[N]) {
#pragma unroll
  for (int i = 0; i < N; i++) asm volatile("" : "+f"(r[i])::"memory");
}
template <int N> __device__ __forceinline__ void undefine(float (&r)[N]) {
#pragma unroll
  for (int i = 0; i < N; i++) asm volatile("" : "=f"(r[i]));
}
template <int N> __device__ __forceinline__ void fence_regs(uint32_t (&r)[N]) {
#pragma unroll
  for (int i = 0; i < N; i++) asm volatile("" : "+r"(r[i])::"memory");
}
__device__ __forceinline__ uint64_t mk_desc(uint32_t a16, uint32_t lbo, uint32_t sbo, uint32_t swz) {
  uint64_t d;
  asm("mov.b64 %0, {%1, %2};" : "=l"(d) : "r"(a16 + ((lbo >> 4) << 16)), "r"((sbo >> 4) | (swz << 30)));
  return d;
}
__device__ __forceinline__ void mbar_init(uint32_t bar, uint32_t cnt) {
  asm volatile("mbarrier.init.shared::cta.b64 [%0], %1;" ::"r"(bar), "r"(cnt) : "memory");
}
__device__ __forceinline__ void mbar_expect(uint32_t bar, uint32_t tx) {
  asm volatile("mbarrier.arrive.expect_tx.shared::cta.b64 _, [%0], %1;" ::"r"(bar), "r"(tx) : "memory");
}
__device__ __forceinline__ bool mbar_test(uint32_t bar, uint32_t ph) {
  uint32_t ok;
  asm volatile("{\n.reg .pred p;\nmbarrier.test_wait.parity.shared::cta.b64 p, [%1], %2;\nselp.u32 %0, 1, 0, p;\n}\n"
               : "=r"(ok) : "r"(bar), "r"(ph) : "memory");
  return ok;
}
__device__ __forceinline__ bool mbar_try(uint32_t bar, uint32_t ph, uint32_t ns) {
  uint32_t ok;
  asm volatile("{\n.reg .pred p;\nmbarrier.try_wait.parity.shared::cta.b64 p, [%1], %2, %3;\nselp.u32 %0, 1, 0, p;\n}\n"
               : "=r"(ok) : "r"(bar), "r"(ph), "r"(ns) : "memory");
  return ok;
}
__device__ __forceinline__ void mbar_wait(uint32_t bar, uint32_t ph) {
  asm volatile("{\n.reg .pred p;\n.reg .u32 n;\nmov.u32 n, 0;\n"
               "LOOP:\nmbarrier.try_wait.parity.shared::cta.b64 p, [%0], %1;\n@p bra DONE;\n"
               "add.u32 n, n, 1;\nsetp.lt.u32 p, n, 0x1000000;\n@p bra LOOP;\ntrap;\n"
               "DONE:\n}\n" ::"r"(bar), "r"(ph) : "memory");
}
__device__ __forceinline__ void mbar_wait_long(uint32_t bar) {
  asm volatile("{\n.reg .pred p;\n.reg .u32 n;\nmov.u32 n, 0;\n"
               "LOOP:\nmbarrier.try_wait.parity.shared::cta.b64 p, [%0], 0, 20000;\n@p bra DONE;\n"
               "add.u32 n, n, 1;\nsetp.lt.u32 p, n, 0x100000;\n@p bra LOOP;\ntrap;\n"
               "DONE:\n}\n" ::"r"(bar) : "memory");
}
__device__ __forceinline__ void mbar_arrive_cluster_if(bool on, uint32_t addr) {
  asm volatile("{\n.reg .pred p;\nsetp.ne.b32 p, %1, 0;\n@p mbarrier.arrive.shared::cluster.b64 _, [%0];\n}\n" ::"r"(addr), "r"((int)on) : "memory");
}
__device__ __forceinline__ void mbar_arrive_cluster_n(uint32_t n, uint32_t addr) {
  asm volatile("{\n.reg .pred p;\nsetp.ne.b32 p, %1, 0;\n@p mbarrier.arrive.shared::cluster.b64 _, [%0], %1;\n}\n" ::"r"(addr), "r"(n) : "memory");
}
__device__ __forceinline__ void tma2d(uint32_t dst, const CUtensorMap* m, uint32_t bar, int c0, int c1) {
  asm volatile("cp.async.bulk.tensor.2d.shared::cluster.global.mbarrier::complete_tx::bytes [%0], [%1, {%3, %4}], [%2];"
               ::"r"(dst), "l"(m), "r"(bar), "r"(c0), "r"(c1) : "memory");
}
__device__ __forceinline__ void tma3d(uint32_t dst, const CUtensorMap* m, uint32_t bar, int c0, int c1, int c2) {
  asm volatile("cp.async.bulk.tensor.3d.shared::cluster.global.mbarrier::complete_tx::bytes [%0], [%1, {%3, %4, %5}], [%2];"
               ::"r"(dst), "l"(m), "r"(bar), "r"(c0), "r"(c1), "r"(c2) : "memory");
}
__device__ __forceinline__ void tma3d_mc(uint32_t dst, const CUtensorMap* m, uint32_t bar, int c0, int c1, int c2) {
  asm volatile("cp.async.bulk.tensor.3d.shared::cluster.global.mbarrier::complete_tx::bytes.multicast::cluster"
               " [%0], [%1, {%3, %4, %5}], [%2], %6;"
               ::"r"(dst), "l"(m), "r"(bar), "r"(c0), "r"(c1), "r"(c2), "h"((uint16_t)3) : "memory");
}
__device__ __forceinline__ void tma3d_store(const CUtensorMap* m, uint32_t src, int c0, int c1, int c2) {
  asm volatile("cp.async.bulk.tensor.3d.global.shared::cta.bulk_group [%0, {%2, %3, %4}], [%1];"
               ::"l"(m), "r"(src), "r"(c0), "r"(c1), "r"(c2) : "memory");
}
__device__ __forceinline__ void bar_sync(int id, int n) { asm volatile("bar.sync %0, %1;" ::"r"(id), "r"(n) : "memory"); }
__device__ __forceinline__ uint32_t pack_bf16(float lo, float hi) {
  uint32_t r;
  asm("cvt.rn.bf16x2.f32 %0, %1, %2;" : "=r"(r) : "f"(hi), "f"(lo));
  return r;
}
__device__ __forceinline__ float ex2(float x) {
  float y;
  asm("ex2.approx.ftz.f32 %0, %1;" : "=f"(y) : "f"(x));
  return y;
}
__device__ __forceinline__ float rcp(float x) {
  float y;
  asm("rcp.approx.ftz.f32 %0, %1;" : "=f"(y) : "f"(x));
  return y;
}
__device__ __forceinline__ void stsm4(uint32_t addr, uint32_t a, uint32_t b, uint32_t c, uint32_t d) {
  asm volatile("stmatrix.sync.aligned.m8n8.x4.shared.b16 [%0], {%1, %2, %3, %4};" ::"r"(addr), "r"(a), "r"(b), "r"(c), "r"(d) : "memory");
}

__device__ __forceinline__ void tma4d_mc_hint(uint32_t dst, const CUtensorMap* m, uint32_t bar, int c3, uint64_t pol) {
  asm volatile("cp.async.bulk.tensor.4d.shared::cluster.global.mbarrier::complete_tx::bytes.multicast::cluster.L2::cache_hint"
               " [%0], [%1, {%3, %3, %3, %4}], [%2], %5, %6;"
               ::"r"(dst), "l"(m), "r"(bar), "r"(0), "r"(c3), "h"((uint16_t)3), "l"(pol) : "memory");
}
__device__ __forceinline__ void tma5d_mc(uint32_t dst, const CUtensorMap* m, uint32_t bar, int c2, int c4) {
  asm volatile("cp.async.bulk.tensor.5d.shared::cluster.global.mbarrier::complete_tx::bytes.multicast::cluster"
               " [%0], [%1, {%3, %3, %4, %3, %5}], [%2], %6;"
               ::"r"(dst), "l"(m), "r"(bar), "r"(0), "r"(c2), "r"(c4), "h"((uint16_t)3) : "memory");
}
__device__ __forceinline__ void bulk_load_hint(uint32_t dst, const void* src, uint32_t bytes, uint32_t bar, uint64_t pol) {
  asm volatile("cp.async.bulk.shared::cluster.global.mbarrier::complete_tx::bytes.L2::cache_hint [%0], [%1], %2, [%3], %4;"
               ::"r"(dst), "l"(src), "r"(bytes), "r"(bar), "l"(pol) : "memory");
}
__device__ __forceinline__ void stg2_if(bool on, void* p, uint32_t a, uint32_t b, uint32_t c, uint32_t d, uint32_t e, uint32_t f,
                                        uint32_t g, uint32_t h, uint64_t pol) {
  asm volatile("{\n.reg .pred p;\nsetp.ne.b32 p, %10, 0;\n"
               "@p st.global.L2::cache_hint.v4.b32 [%0], {%1, %2, %3, %4}, %9;\n"
               "@p st.global.L2::cache_hint.v4.b32 [%0 + 512], {%5, %6, %7, %8}, %9;\n}\n"
               ::"l"(p), "r"(a), "r"(b), "r"(c), "r"(d), "r"(e), "r"(f), "r"(g), "r"(h), "l"(pol), "r"((int)on) : "memory");
}
__device__ __forceinline__ uint64_t evict_first() {
  uint64_t p;
  asm("createpolicy.fractional.L2::evict_first.b64 %0, 1.0;" : "=l"(p));
  return p;
}
__device__ __forceinline__ bool elect() {
  uint32_t ok;
  asm volatile("{\n.reg .pred p;\nelect.sync _|p, 0xffffffff;\nselp.u32 %0, 1, 0, p;\n}\n" : "=r"(ok));
  return ok;
}
__device__ __forceinline__ void mbar_arrive(uint32_t bar) {
  asm volatile("mbarrier.arrive.shared::cta.b64 _, [%0];" ::"r"(bar) : "memory");
}
__device__ __forceinline__ void mbar_arrive_if(bool on, uint32_t bar) {
  asm volatile("{\n.reg .pred p;\nsetp.ne.b32 p, %1, 0;\n@p mbarrier.arrive.shared::cta.b64 _, [%0];\n}\n" ::"r"(bar), "r"((int)on) : "memory");
}
__device__ __forceinline__ void lds2_if(bool on, uint32_t p, uint32_t (&t)[8]) {
  asm volatile("{\n.reg .pred p;\nsetp.ne.b32 p, %9, 0;\n@p ld.shared.v4.b32 {%0, %1, %2, %3}, [%8];\n@p ld.shared.v4.b32 {%4, %5, %6, %7}, [%8 + 512];\n}\n"
               : "+r"(t[0]), "+r"(t[1]), "+r"(t[2]), "+r"(t[3]), "+r"(t[4]), "+r"(t[5]), "+r"(t[6]), "+r"(t[7]) : "r"(p), "r"((int)on) : "memory");
}
__device__ __forceinline__ void lds128(uint32_t p, uint32_t& a, uint32_t& b, uint32_t& c, uint32_t& d) {
  asm volatile("ld.shared.v4.b32 {%0, %1, %2, %3}, [%4];" : "=r"(a), "=r"(b), "=r"(c), "=r"(d) : "r"(p) : "memory");
}
template <class T> __device__ __forceinline__ T* ptr_add(T* base, uint32_t bytes) {
  T* r;
  asm("{\n.reg .u32 lo, hi;\nmov.b64 {lo, hi}, %1;\nadd.cc.u32 lo, lo, %2;\naddc.u32 hi, hi, 0;\nmov.b64 %0, {lo, hi};\n}\n" : "=l"(r) : "l"(base), "r"(bytes));
  return r;
}
__device__ __forceinline__ uint32_t lds32(uint32_t p) {
  uint32_t v;
  asm volatile("ld.volatile.shared.u32 %0, [%1];" : "=r"(v) : "r"(p) : "memory");
  return v;
}
__device__ __forceinline__ uint32_t flag_get(const unsigned int* p) {
  uint32_t v;
  asm volatile("ld.acquire.gpu.global.u32 %0, [%1];" : "=r"(v) : "l"(p) : "memory");
  return v;
}
__device__ __forceinline__ uint32_t wait_word(uint32_t p, uint32_t target) {
  uint32_t v;
  asm volatile("{\n.reg .pred p;\n.reg .u32 n;\nmov.u32 n, 0;\n"
               "LOOP:\nld.acquire.cta.shared.u32 %0, [%1];\nsetp.ge.u32 p, %0, %2;\n@p bra DONE;\n"
               "nanosleep.u32 %3;\nadd.u32 n, n, 1;\nsetp.lt.u32 p, n, 0x400000;\n@p bra LOOP;\ntrap;\n"
               "DONE:\n}\n" : "=r"(v) : "r"(p), "r"(target), "n"(400) : "memory");
  return v;
}
__device__ __forceinline__ void flag_set(unsigned int* p, uint32_t v) {
  asm volatile("st.release.gpu.global.u32 [%0], %1;" ::"l"(p), "r"(v) : "memory");
}
__device__ __forceinline__ void flag_dec(unsigned int* p) {
  asm volatile("red.relaxed.gpu.global.add.u32 [%0], 0xffffffff;" ::"l"(p) : "memory");
}

struct Cursor {
  int bi;
  uint32_t ph;
  __device__ __forceinline__ void next() {
    if (++bi == NBAR) { bi = 0; ph ^= 1; }
  }
};

constexpr float kScaleLog2 = 0.07216878364870322f * 1.4426950408889634f;
constexpr float kSumLimit = 1048576.0f;

__global__ void __cluster_dims__(2, 1, 1) __launch_bounds__(384, 1)
fused_kernel(const __grid_constant__ Params P) {
  extern __shared__ uint8_t smem_raw[];
  const uint32_t sbase = (smem_u32(smem_raw) + 1023) & ~1023u;
  const uint32_t full0 = sbase + RING, empty0 = full0 + 8 * NBAR, odone0 = empty0 + 8 * NBAR, ev0 = odone0 + 8 * MAX_OPS;
  const uint32_t progress = ev0 + 8 * MAX_EV, jobw = progress + 4;
  const uint32_t rank = blockIdx.x & 1;
  const int role = blockIdx.x >> 1;
  const int wid = __shfl_sync(0xffffffffu, (int)(threadIdx.x >> 5), 0);
  const int wg = wid >> 2;

  if (wid < 8) {
    if (elect()) {
#pragma unroll
      for (int j = 0; j < 16; j++) {
        const int i = EARLY + 16 * wid + j;
        if (i < 2 * NBAR + MAX_OPS + MAX_EV) mbar_init(full0 + 8 * i, i < NBAR ? 1 : i < 2 * NBAR ? 16 : i < 2 * NBAR + MAX_OPS ? 8 : 1);
      }
      if (wid == 7) asm volatile("st.shared.v2.u32 [%0], {0, 0};\nfence.acq_rel.cta;" ::"r"(progress) : "memory");
      asm volatile("fence.mbarrier_init.release.cluster;" ::: "memory");
    }
  } else if (wid > 8) {
    const uint32_t g = blockIdx.x * 96 + threadIdx.x - 288, w = g - 2048;
    if (g < 4096) asm volatile("prefetch.global.L2 [%0];" ::"l"(g < 2048 ? P.xw[0] + g * (kD * 2) : P.xw[1] + (w >> 5) * (kHD * 2) + (w & 31) * 128));
  } else {
    const uint32_t op0 = P.first[role];
    if (elect()) {
#pragma unroll
      for (int k = 0; k < EARLY; k++) mbar_init(full0 + 8 * k, 1);
      asm volatile("fence.mbarrier_init.release.cluster;" ::: "memory");
      const int blk = (op0 >> 10) & 1;
      if ((op0 & 3) == OP_Q) {
#pragma unroll
        for (int k = 0; k < EARLY; k++) {
          mbar_expect(full0 + 8 * k, SZ_Q);
          tma2d(sbase + k * SZ_Q, &P.x[blk], full0 + 8 * k, 64 * k, ((op0 >> 7) & 7) * kSq + rank * 128);
          tma3d(sbase + k * SZ_Q + 16384, &P.wq[blk], full0 + 8 * k, 0, 64 * k, 3 * ((op0 >> 2) & 31));
        }
      }
      asm volatile("prefetch.tensormap [%0];" ::"l"(rank ? &P.v[blk] : &P.k[blk]) : "memory");
    }
  }
  __syncwarp();
  asm volatile("barrier.cluster.arrive.relaxed.aligned;\nbarrier.cluster.wait.aligned;" ::: "memory");

  if (wg < 2) {
    asm volatile("setmaxnreg.inc.sync.aligned.u32 240;");
    const uint32_t* prog = P.prog[role].c;
    const int lane = threadIdx.x & 31, warp = wid & 3;
    uint32_t empty_rem;
    asm volatile("mapa.shared::cluster.u32 %0, %1, %2;" : "=r"(empty_rem) : "r"(empty0), "r"(lane & 1));
    uint32_t keep = (threadIdx.x & 127) < 2 ? 4 : 0;
    auto release = [&](int slot) { mbar_arrive_cluster_n(keep, empty_rem + 8 * slot); };
    auto release_warp = [&](int slot, bool on = true) { mbar_arrive_cluster_if(lane < 2 && on, empty_rem + 8 * slot); };
    Cursor r{0, 0};
    const uint32_t ring16 = (sbase & 0x3FFFF) >> 4;
    uint32_t cur = ring16;
    bool rdy0 = false, rdy1 = false;
    auto probe1 = [&]() { rdy0 = mbar_test(full0 + 8 * r.bi, r.ph); };
    auto probe2 = [&]() {
      Cursor n = r;
      rdy0 = mbar_test(full0 + 8 * n.bi, n.ph);
      n.next();
      rdy1 = mbar_test(full0 + 8 * n.bi, n.ph);
    };
    auto take = [&](bool rdy, uint32_t bytes, uint32_t& addr) {
      const int bi = r.bi;
      if (__builtin_expect(!__all_sync(0xffffffffu, rdy), 0)) mbar_wait(full0 + 8 * r.bi, r.ph);
      r.next();
      if (cur > ring16 + ((RING - bytes) >> 4)) cur = ring16;
      addr = cur;
      cur += bytes >> 4;
      return bi;
    };
    const bool never = P.dbg == 0xffffffffu;
    uint32_t q[48];
#pragma unroll
    for (int i = 0; i < 48; i++) q[i] = 0;
    const int row = wg * 64 + warp * 16 + (lane >> 2);
    const int img0 = row * 4 + ((lane & 3) ^ ((row >> 1) & 3));
    uint4* pend = nullptr;
    bool pend_any = false;
    const uint64_t spol = evict_first();
    int pc = 0;
    auto slab = [&](int c, int i0) {
#pragma unroll
      for (int i = i0; i < 6; i++)
        stg2_if(c == i, pend + i * 512, q[8 * i], q[8 * i + 1], q[8 * i + 2], q[8 * i + 3],
                q[8 * i + 4], q[8 * i + 5], q[8 * i + 6], q[8 * i + 7], spol);
    };
    auto drain = [&](int c) {
      if (!pend_any || c >= 6) return;
      slab(c, 0);
      if (c == 5) {
        __syncwarp();
        mbar_arrive_if(lane == 0, odone0 - 8 + 8 * pc);
      }
    };

    for (;; pc++) {
      uint32_t op = prog[pc];
      const int type = op & 3;
      auto enter = [&]() {
        r.bi = (op >> 15) & 15; r.ph = (op >> 19) & 1; cur = ring16 + (((op >> 20) & 63) << 8);
      };
      enter();
      pend_any = op & C_PEND;
      uint32_t job = 0;
      if ((op & (3 | C_WIDE)) == OP_O) job = __shfl_sync(0xffffffffu, wait_word(jobw, 1), 0);
      if (type == OP_END || job == OP_O) {
#pragma unroll 1
        for (int c = 0; c < 6; c++) drain(c);
        asm volatile("barrier.cluster.arrive.relaxed;" ::: "memory");
        break;
      }
      {
        float s[32], o[96];
        uint32_t ad0;
        int bi0, sk1;
        uint32_t pa[16], pb[16];
        float mc0, mc1, l0, l1;
        bool shifted;
        uint32_t nop;
        auto expo = [&](float (&s)[32], uint32_t (&pout)[16], float& b0, float& b1, bool shift, auto mid) {
          float c0, c1;
#pragma unroll
          for (int i = 0; i < 8; i++) {
            const float e0 = ex2(shift ? s[4 * i] - mc0 : s[4 * i]), e1 = ex2(shift ? s[4 * i + 1] - mc0 : s[4 * i + 1]);
            const float e2 = ex2(shift ? s[4 * i + 2] - mc1 : s[4 * i + 2]), e3 = ex2(shift ? s[4 * i + 3] - mc1 : s[4 * i + 3]);
            if (i) { b0 += e0; c0 += e1; b1 += e2; c1 += e3; } else { b0 = e0; c0 = e1; b1 = e2; c1 = e3; }
            pout[2 * i] = pack_bf16(e0, e1); pout[2 * i + 1] = pack_bf16(e2, e3);
            if (i & 1) mid(i >> 1);
          }
          b0 += c0; b1 += c1;
        };
        auto rowmax = [&](float (&s)[32], float& m0, float& m1) {
          m0 = fmaxf(s[0], s[1]); m1 = fmaxf(s[2], s[3]);
#pragma unroll
          for (int i = 1; i < 8; i++) { m0 = fmaxf(m0, fmaxf(s[4 * i], s[4 * i + 1])); m1 = fmaxf(m1, fmaxf(s[4 * i + 2], s[4 * i + 3])); }
          m0 = fmaxf(m0, __shfl_xor_sync(0xffffffffu, m0, 1)); m1 = fmaxf(m1, __shfl_xor_sync(0xffffffffu, m1, 1));
          m0 = fmaxf(m0, __shfl_xor_sync(0xffffffffu, m0, 2)); m1 = fmaxf(m1, __shfl_xor_sync(0xffffffffu, m1, 2));
        };
        auto first = [&](float (&s)[32], int sk0, auto mid) {
          fence_regs(s);
          release(sk0);
          mc0 = 0.f; mc1 = 0.f;
          expo(s, pa, l0, l1, false, mid);
          shifted = __any_sync(0xffffffffu, !(fmaxf(l0, l1) <= kSumLimit && fminf(l0, l1) >= 1.f / kSumLimit));
          if (shifted) {
            rowmax(s, mc0, mc1);
            expo(s, pa, l0, l1, true, [](int) {});
          }
        };
        auto qk = [&](float (&s)[32], uint32_t ak, int k0 = 0, int k1 = 12) {
#pragma unroll
          for (int kk = k0; kk < k1; kk++)
            wgmma_rs_n64<0>(s, q[4 * kk], q[4 * kk + 1], q[4 * kk + 2], q[4 * kk + 3], mk_desc(ak, 16, KV_SBO, 1) + ((kk >> 2) * KV_CH + (kk & 3) * 2), kk != 0);
          if (k1 == 12) wg_commit();
        };
        auto pv = [&](uint32_t (&pin)[16], uint32_t av, int acc) {
#pragma unroll
          for (int kk = 0; kk < 4; kk++)
            wgmma_rs_n192<1>(o, pin[4 * kk], pin[4 * kk + 1], pin[4 * kk + 2], pin[4 * kk + 3], mk_desc(av, KV_CH * 16, KV_SBO, 1) + (kk * (KV_SBO / 8)), acc || (kk != 0));
          wg_commit();
        };
        auto finish = [&](uint32_t (&pout)[16], int sk, int sv) {
          probe2();
          wg_wait<1>();
          fence_regs(s);
          release(sk);
          float b0, b1;
#pragma unroll 1
          for (bool redo = false;; redo = true) {
            expo(s, pout, b0, b1, false, [](int) {});
            if (!__any_sync(0xffffffffu, !redo && (shifted || !(fmaxf(b0, b1) <= kSumLimit)))) break;
            shifted = true;
            rowmax(s, b0, b1);
            b0 = fmaxf(mc0, b0); b1 = fmaxf(mc1, b1);
            const float a0 = ex2(mc0 - b0), a1 = ex2(mc1 - b1);
            mc0 = b0; mc1 = b1;
            l0 *= a0; l1 *= a1;
            wg_wait<0>();
            fence_regs(o);
#pragma unroll
            for (int i = 0; i < 24; i++) { o[4 * i] *= a0; o[4 * i + 1] *= a0; o[4 * i + 2] *= a1; o[4 * i + 3] *= a1; }
#pragma unroll
            for (int i = 0; i < 32; i++) s[i] -= (i & 2) ? mc1 : mc0;
          }
          l0 += b0; l1 += b1;
          wg_wait<0>();
          fence_regs(o);
          release(sv);
        };
        auto step = [&](uint32_t (&pin)[16], uint32_t (&pout)[16]) {
          uint32_t ak, av;
          const int sk = take(rdy0, SZ_KV, ak), sv = take(rdy1, SZ_KV, av);
          wg_fence();
          qk(s, ak);
          pv(pin, av, 1);
          finish(pout, sk, sv);
        };
        auto unpark = [&]() {
          uint32_t ad, ak;
          const int bi = take(rdy0, SZ_PARK, ad);
#pragma unroll
          for (int i = 0; i < 12; i++) lds128(sbase + (ad - ring16 + img0) * 16 + (i >> 1) * 8192 + (i & 1) * 512, q[4 * i], q[4 * i + 1], q[4 * i + 2], q[4 * i + 3]);
          const int sk0 = take(false, SZ_KV, ak);
          fence_regs(q);
          release_warp(bi);
          wg_fence();
          qk(s, ak);
          probe2();
          return sk0;
        };
        auto mma4 = [&](uint32_t ad, int acc) {
#pragma unroll
          for (int kk = 0; kk < 4; kk++)
            wgmma_ss_n192<1>(o, mk_desc(ad + wg * 512, 16, 1024, 1) + (kk * 2), mk_desc(ad, 8192, 1024, 1) + (1024 + kk * 128), acc || kk != 0);
        };
        auto convert = [&](int i0, int i1) {
          sched_fence(keep, never);
#pragma unroll
          for (int i = i0; i < i1; i++) {
            q[i] = pack_bf16(o[2 * i] * kScaleLog2, o[2 * i + 1] * kScaleLog2);
            if ((i & 7) == 7 && i != i1 - 1) sched_fence(keep, never);
          }
          sched_fence(keep, never);
        };
        auto kend = [&](int bi, int k) {
          wg_commit();
          drain(k < 8 ? (0x54732710u >> (4 * k)) & 7 : 7);
          probe1();
          wg_wait<0>();
          release(bi);
        };
        if (type == OP_O) {
          int prev = 0;
          if (op & C_WIDE) {
            float d[64];
            auto mma3 = [&](uint32_t ad, int h, int acc) {
#pragma unroll
              for (int kk = 0; kk < 2; kk++)
                wgmma_ss_n192<1>(o, mk_desc(ad + wg * 256, 16, 512, 2) + (h * 512 + kk * 2), mk_desc(ad, 4096, 1024, 1) + (1024 + h * 768 + kk * 128), acc || kk);
            };
            auto mma2 = [&](uint32_t ad, uint32_t ob, int h, int acc) {
#pragma unroll
              for (int kk = 0; kk < 2; kk++)
                wgmma_ss_n128<1>(d, mk_desc(ad + wg * 256, 16, 512, 2) + (h * 512 + kk * 2), mk_desc(ad, 4096, 1024, 1) + (ob + h * 512 + kk * 128), acc || kk);
            };
            auto wstep = [&](uint32_t bytes, int acc, auto hook) {
              uint32_t ad;
              const int bi = take(rdy0, bytes, ad);
              wg_fence();
              if (bytes == SZ_W2) mma2(ad, 1024, 0, 1); else mma3(ad, 0, acc);
              if (bytes == SZ_W) mma3(ad, 1, 1);
              wg_commit();
              if (acc) { wg_wait<1>(); release(prev); }
              if (bytes == SZ_W) mma2(ad, 2560, 0, acc);
              if (bytes == SZ_W3) mma3(ad, 1, 1); else mma2(ad, bytes == SZ_W ? 2560 : 1024, 1, 1);
              wg_commit();
              prev = bi;
              hook();
              probe1();
              wg_wait<1>();
            };
            undefine(o);
            wstep(SZ_W, 0, [&]() { drain(0); });
#pragma unroll 1
            for (int k = 1; k < ((op >> 2) & 127) - TAIL; k++) wstep(SZ_W, 1, [&]() { drain(k); });
#pragma unroll 1
            for (int k = 0; k < TAIL; k++) wstep(SZ_W2, 1, []() {});
            pend = ptr_add(P.g->part, (((op >> 9) & 31) * 2 + rank) * 81920 + 4 * 8192 + img0 * 16);
            wstep(SZ_W3, 1, [&]() {
              fence_regs(d);
#pragma unroll
              for (int i = 0; i < 32; i++) q[16 + i] = pack_bf16(d[2 * i], d[2 * i + 1]);
              slab(2, 2);
            });
#pragma unroll 1
            for (int k = 3; k < 6; k++) wstep(SZ_W3, 1, [&]() { slab(k, 2); });
            op = prog[pc + 1];
            enter();
            pend_any = true;
            pend -= 4 * 512;
            bi0 = take(rdy0 || (op & 3) != OP_Q, SZ_Q, ad0);
            sched_fence(keep, never);
            wg_wait<0>();
            fence_regs(o);
            release(prev);
#pragma unroll
            for (int i = 0; i < 48; i++) q[i] = pack_bf16(o[2 * i], o[2 * i + 1]);
            if ((op & 3) != OP_Q) continue;
            pc++;
            goto first_step;
          }
          float c[80];
          auto mma2 = [&](uint32_t ad, uint32_t oa, uint32_t ob, int acc) {
            wgmma_ss_n160<1>(c, mk_desc(ad + wg * 256, 16, 512, 2) + (oa), mk_desc(ad, 2048, 512, 2) + (1024 + ob), acc);
            wgmma_ss_n160<1>(c, mk_desc(ad + wg * 256, 16, 512, 2) + (oa + 2), mk_desc(ad, 2048, 512, 2) + (1024 + ob + 64), 1);
          };
          auto kstep = [&](int acc, auto hook, uint32_t bytes = SZ_O) {
            uint32_t ad;
            const int bi = take(rdy0, bytes, ad);
            wg_fence();
            mma2(ad, 0, 0, acc);
            wg_commit();
            if (acc) wg_wait<1>();
            if (acc == 1) release(prev);
            if (acc > 1) release_warp(prev, acc == 2 || wg == 0);
            mma2(ad, 512, 640, 1);
            wg_commit();
            prev = bi;
            hook();
            probe1();
            wg_wait<1>();
          };
          auto unblock = [&](int k) {
            if (__all_sync(0xffffffffu, rdy0) || __all_sync(0xffffffffu, mbar_try(full0 + 8 * r.bi, r.ph, 1500))) return;
#pragma unroll 1
            for (; k < 6; k++) drain(k);
            pend_any = false;
          };
          unblock(0);
          kstep(0, [&]() { drain(0); });
          int left = ((job >> 13) & 127) - 6;
#pragma unroll 1
          for (uint32_t k = 1, pace = left >= 29 ? 0x4511 : left <= 17 ? 0x1a : 0x155; left > 0; pace >>= 2, left--) {
            unblock(k);
            kstep(1, [&]() {
#pragma unroll 1
              for (int i = pace & 3; i > 0; i--) drain(k++);
            });
          }
          uint32_t t[8], stage[3];
          float u[80];
          auto unpack = [&](int j) {
#pragma unroll
            for (int i = 0; i < 8; i++) {
              u[16 * j + 2 * i] = __uint_as_float(t[i] << 16); u[16 * j + 2 * i + 1] = __uint_as_float(t[i] & 0xffff0000u);
              asm volatile("" : "+f"(u[16 * j + 2 * i]), "+f"(u[16 * j + 2 * i + 1]));
            }
          };
#pragma unroll
          for (int i = 0; i < 8; i++) t[i] = 0;
          const uint32_t bytes = (job & P_LD) ? SZ_OL : SZ_O;
#pragma unroll
          for (int j = 0; j < 5; j++) {
            if (j == 2 && wg == 1) {
              wg_wait<0>();
              release_warp(prev);
              bar_sync(1, 256);
            }
            kstep(j == 2 ? 3 : 2, [&]() {
              if (j == 4) asm volatile("{\n.reg .pred p;\nsetp.eq.u32 p, %0, 0;\n@p bar.arrive 1, 256;\n}\n" ::"r"(wg) : "memory");
              if (j) unpack(j - 1);
              lds2_if(job & P_LD, sbase + (cur - ring16 + img0) * 16 - 8192, t);
              if (j >= 1 && j <= 3) stage[j - 1] = sbase + (cur - ring16) * 16 - bytes + wid * 1024;
            }, bytes);
          }
          unpack(4);
          sched_fence(keep, never);
          wg_wait<0>();
          fence_regs(c);
          release_warp(prev);
          asm volatile("barrier.cluster.arrive.relaxed;" ::: "memory");
#pragma unroll
          for (int i = 0; i < 10; i++) {
            const int v = (i & 1) * 2 + (lane >> 4);
            const uint32_t sa = stage[i >> 2] + (i & 2) * 4096;
            stsm4(sa + (lane & 15) * 64 + ((v ^ ((lane >> 1) & 3)) << 4), pack_bf16(c[8 * i] + u[8 * i], c[8 * i + 1] + u[8 * i + 1]),
                  pack_bf16(c[8 * i + 2] + u[8 * i + 2], c[8 * i + 3] + u[8 * i + 3]), pack_bf16(c[8 * i + 4] + u[8 * i + 4], c[8 * i + 5] + u[8 * i + 5]),
                  pack_bf16(c[8 * i + 6] + u[8 * i + 6], c[8 * i + 7] + u[8 * i + 7]));
          }
          asm volatile("fence.proxy.async.shared::cta;" ::: "memory");
          __syncwarp();
          if (elect()) {
#pragma unroll
            for (int i = 0; i < 5; i++)
              tma3d_store(&P.out, stage[i >> 1] + (i & 1) * 8192, 0, ((job >> 7) & 7) * kSq + rank * 128 + wid * 16, ((job >> 10) & 1) * 20 + ((job >> 20) & 3) * 5 + i);
            asm volatile("cp.async.bulk.commit_group;\ncp.async.bulk.wait_group.read 0;" ::: "memory");
          }
          __syncwarp();
          break;
        }
        bi0 = take(rdy0, SZ_Q, ad0);
      first_step:
        undefine(o);
        wg_fence();
        mma4(ad0, 0);
        kend(bi0, 0);
        fence_regs(o);
      next_head:
        {
#pragma unroll 1
          for (int k = 1; k < ((op & F_PARK) ? 10 : 8); k++) {
            uint32_t ad;
            const int bi = take(rdy0, SZ_Q, ad);
            wg_fence();
            mma4(ad, 1);
            kend(bi, k);
          }
          if (op & F_PARK) {
            fence_regs(o);
            convert(0, 48);
            pend = ptr_add(P.g->tile, (((op >> 2) & 511) * 2 + rank) * SZ_PARK + img0 * 16);
            continue;
          }
          uint32_t a8, a9, ak0, ak1;
          const int b8 = take(rdy0, SZ_Q, a8), b9 = take(false, SZ_Q, a9);
          wg_fence();
          mma4(a8, 1);
          wg_commit();
          mma4(a9, 1);
          wg_commit();
          pc++;
          wg_wait<1>();
          release(b8);
          const int sk0 = take(false, SZ_KV, ak0);
          wg_wait<0>();
          fence_regs(o);
          release(b9);
          float s0[32];
          convert(0, 32);
          wg_fence();
          qk(s0, ak0, 0, 4);
          convert(32, 48);
          wg_fence();
          qk(s0, ak0, 4, 12);
          sk1 = take(false, SZ_KV, ak1);
          probe1();
          wg_wait<0>();
          first(s0, sk0, [&](int i) {
            if (i == 0) return;
            sched_fence(keep, never);
            wg_fence();
            if (i == 1) qk(s, ak1, 0, 4);
            if (i == 2) qk(s, ak1, 4, 8);
            if (i == 3) qk(s, ak1, 8, 12);
            sched_fence(keep, never);
          });
        }
        for (;;) {
          {
            uint32_t av;
            const int sv = take(rdy0, SZ_KV, av);
            undefine(o);
            wg_fence();
            pv(pa, av, 0);
            finish(pb, sk1, sv);
          }
          nop = prog[pc + 1];
#pragma unroll 1
          for (int jj = 0; jj < 7; jj++) {
            step(pb, pa);
            step(pa, pb);
          }
          float i0, i1;
          auto last = [&]() {
            uint32_t av;
            const int sv = take(rdy0, SZ_KV, av);
            wg_fence();
            pv(pb, av, 1);
            sched_fence(keep, never);
            probe1();
            l0 += __shfl_xor_sync(0xffffffffu, l0, 1); l1 += __shfl_xor_sync(0xffffffffu, l1, 1);
            l0 += __shfl_xor_sync(0xffffffffu, l0, 2); l1 += __shfl_xor_sync(0xffffffffu, l1, 2);
            i0 = rcp(l0); i1 = rcp(l1);
            pend = ptr_add(P.g->tile, (((op >> 2) & 511) * 2 + rank) * SZ_PARK + img0 * 16);
            return sv;
          };
          auto normalise = [&](uint32_t (&d)[48], auto mid) {
#pragma unroll
            for (int i = 0; i < 24; i++) {
              d[8 * (i >> 2) + (i & 3)] = pack_bf16(o[4 * i] * i0, o[4 * i + 1] * i0);
              d[8 * (i >> 2) + (i & 3) + 4] = pack_bf16(o[4 * i + 2] * i1, o[4 * i + 3] * i1);
              if ((i & 1) && i != 23) sched_fence(keep, never);
              if ((i & 3) == 3 && i != 23) mid(i >> 2);
            }
          };
          const int sv = last();
          if ((nop & 3) != OP_A) {
            op = nop;
            enter();
            pend_any = true;
            bi0 = take(rdy0 || (nop & 3) != OP_Q, SZ_Q, ad0);
            sched_fence(keep, never);
            wg_wait<0>();
            fence_regs(o);
            release(sv);
            normalise(q, [](int) {});
            undefine(o);
            if ((nop & 3) != OP_Q) break;
            sched_fence(keep, never);
            wg_fence();
            mma4(ad0, 0);
            pc++;
            kend(bi0, 0);
            fence_regs(o);
            goto next_head;
          }
          const int sk0 = unpark();
          wg_wait<1>();
          fence_regs(o);
          release(sv);
          uint32_t t[48];
          auto st = [&](int i) {
            stg2_if(true, pend + i * 512, t[8 * i], t[8 * i + 1], t[8 * i + 2], t[8 * i + 3], t[8 * i + 4], t[8 * i + 5], t[8 * i + 6], t[8 * i + 7], spol);
          };
          normalise(t, [&](int i) { if (!(i & 1)) st(i >> 1); });
          wg_wait<0>();
          first(s, sk0, [&](int i) { if (i < 3) { sched_fence(keep, never); st(3 + i); } });
          __syncwarp();
          mbar_arrive_if(lane == 0, odone0 + 8 * pc);
          pc++;
          op = nop;
          uint32_t ak1;
          sk1 = take(rdy0, SZ_KV, ak1);
          rdy0 = rdy1;
          wg_fence();
          qk(s, ak1);
        }
      }
    }
    asm volatile("barrier.cluster.wait;" ::: "memory");
  } else {
    asm volatile("setmaxnreg.dec.sync.aligned.u32 24;");
    const uint32_t* prog = P.prog[role].p;
    unsigned int* flag = P.g->flag + rank;
    if (wid == 8) {
      Cursor tail{0, 0};
      int head = 0, sh = 0;
      uint32_t cur = 0, used = 0;
      uint64_t fifo = 0;
      uint32_t dst, bar, ev = ev0, done = 0;
      const uint64_t pol = evict_first();
      auto retire = [&]() {
        mbar_wait(empty0 + 8 * tail.bi, tail.ph);
        tail.next();
        used -= (uint32_t)fifo & 31;
        fifo >>= 5;
        sh -= 5;
        asm volatile("st.volatile.shared.u32 [%0], %1;" ::"r"(progress), "r"(++done) : "memory");
      };
      auto acquire = [&](uint32_t bytes) {
        uint32_t fp = bytes >> 12;
        if (cur + fp > (RING >> 12)) { fp += (RING >> 12) - cur; cur = 0; }
        used += fp;
        while (used > (RING >> 12) || sh == 5 * NBAR) retire();
        fifo |= (uint64_t)fp << sh;
        sh += 5;
        dst = sbase + (cur << 12);
        bar = full0 + 8 * head;
        cur += bytes >> 12;
        if (++head == NBAR) head = 0;
      };
      auto gate = [&]() {
        mbar_wait(ev, 0);
        ev += 8;
        asm volatile("fence.proxy.async.global;" ::: "memory");
      };
      for (int pc = 0;; pc++) {
        uint32_t op = prog[pc];
        const int type = op & 3;
        if (type == OP_END) break;
        if (op == OP_O) {
          gate();
          op = __shfl_sync(0xffffffffu, lds32(jobw), 0);
        }
        const int blk = (op >> 10) & 1;
        if (type == OP_Q) {
#pragma unroll 1
          for (int k = 0; k < 10; k++) {
            if (k == 9 && (op & P_GATE)) gate();
            acquire(SZ_Q);
            if ((pc > 0 || k >= EARLY) && elect()) {
              mbar_expect(bar, SZ_Q);
              tma2d(dst, &P.x[blk], bar, 64 * k, ((op >> 7) & 7) * kSq + rank * 128);
              if ((k & 1) == rank) tma3d_mc(dst + 16384, &P.wq[blk], bar, 0, 64 * k, 3 * ((op >> 2) & 31));
            }
          }
        } else if (type == OP_A) {
          const int row0 = ((op >> 2) & 255) * kSk;
          const CUtensorMap* kv_map = rank ? &P.v[blk] : &P.k[blk];
          if (op & F_PARK) {
            gate();
            acquire(SZ_PARK);
            if (elect()) {
              mbar_expect(bar, SZ_PARK);
              bulk_load_hint(dst, &P.g->tile[((op >> 20) * 2 + rank) * 3072], SZ_PARK, bar, pol);
            }
          }
#pragma unroll 1
          for (int t = 0; t < 32; t++) {
            const int isv = t == 31 ? 1 : (t == 0 ? 0 : (~t & 1));
            const int j = isv ? (t - 1) >> 1 : (t + 1) >> 1;
            if (t == 31 && (op & P_GATE)) gate();
            acquire(SZ_KV);
            if (elect()) {
              mbar_expect(bar, SZ_KV);
              if (isv == (int)rank) tma4d_mc_hint(dst, kv_map, bar, row0 / 8 + 8 * j, pol);
            }
          }
        } else {
          const int n = (op >> 13) & 127, nw = (op & P_WIDE) ? n - TAIL : 0;
          const uint4* part = &P.g->part[((((op >> 6) & 30) + ((op >> 21) & 1)) * 2 + rank) * 5120 + ((op >> 20) & 1) * 2560];
#pragma unroll 1
          for (int i = 0; i < n + (nw ? TAIL : 0); i++) {
            const int k = nw ? (i < n ? i : i - TAIL) : kSteps - n + i, h = (k * 43) >> 7, col = 5 * ((op >> 20) & 3);
            const uint4* src = &P.g->tile[(P.slot[((op >> 2) & 480) + h] * 2 + rank) * 3072 + (k - 3 * h) * 1024];
            const uint32_t j = (op & P_LD) ? i - n + 5 : 5, bytes = i < nw ? SZ_W : nw ? (i < n ? SZ_W2 : SZ_W3) : j < 5 ? SZ_OL : SZ_O;
            if ((op & P_PRE) ? i == 0 : j == 0) gate();
            if (i < n && (i == 0 || k == 3 * h)) gate();
            acquire(bytes);
            if (elect()) {
              mbar_expect(bar, bytes);
              if (bytes != SZ_W2) tma5d_mc(dst + 16384 + rank * (nw ? 12288 : 10240), nw ? &P.wo3[blk] : &P.wo[blk], bar, 8 * k + 4 * rank, nw ? col / 2 : col);
              bulk_load_hint(dst, src, 16384, bar, pol);
              if (nw && i < n) tma5d_mc(dst + bytes - 16384 + rank * 8192, &P.wo2[blk], bar, 8 * k + 4 * rank, col / 2 + 3);
              if (j < 5) bulk_load_hint(dst + SZ_O, part + j * 512, 8192, bar, pol);
              if ((op & P_PRE) && i < 10) asm volatile("cp.async.bulk.prefetch.L2.global [%0], 4096;" ::"l"(part + i * 256) : "memory");
            }
          }
        }
      }
#pragma unroll 1
      while (sh) retire();
    } else if (threadIdx.x == 288) {
      for (int pc = 0;; pc++) {
        const uint32_t op = prog[pc];
        const int type = op & 3;
        if (type == OP_END) break;
        if (type == OP_Q ? !(op & F_PARK) : type == OP_O && !(op & P_WIDE)) continue;
        const int id = type == OP_A ? (op >> 2) & 511 : type == OP_Q ? N_TILE + ((op >> 13) & 127) : ID_PART + ((op >> 5) & 60) + ((op >> 20) & 3);
        const uint32_t v = type == OP_O ? 1 : P.info[id] & 7;
        mbar_wait_long(odone0 + 8 * pc);
        flag_set(flag + 2 * id, v);
        if (type == OP_O && (op & P_WIDE)) flag_set(flag + 2 * id + 2, v);
      }
    } else if (wid == 10) {
      int i = threadIdx.x & 31;
      const int n_ev = P.prog[role].n_ev;
      auto event = [&]() { return i < n_ev ? P.prog[role].ev[i] : n_ev ? E_JOB | (i - n_ev) : 0; };
      uint32_t e = i < 8 ? event() : 0;
      for (uint32_t n = 0; __any_sync(0xffffffffu, e); n++) {
        uint32_t job = lds32(jobw);
        const int togo = (e & E_DRAW) ? (e & 1023) - lds32(progress) : 99;
        if (togo <= 0 && rank == 0) {
          job = P.job[atomicInc(&P.g->ticket, gridDim.x / 2 - 1)];
          asm volatile("{\n.reg .u32 a;\nmapa.shared::cluster.u32 a, %0, 1;\nst.volatile.shared::cluster.u32 [a], %1;\n"
                       "st.volatile.shared.u32 [%0], %1;\n}\n" ::"r"(jobw), "r"(job) : "memory");
        }
        if ((e & E_JOB) && job) {
          const uint32_t j = e & 63, heads = job == OP_O ? 0 : kH - ((job >> 2) & 31), jp = !(job & P_LD) ? 63 : (job & P_PRE) ? 0 : heads - 1, h = j - (j > jp);
          e = j == jp ? (ID_PART + ((job >> 5) & 60) + ((job >> 20) & 3)) | E_ON | E_LAST : h < heads ? (((job >> 2) & 511) + h) | E_ON | E_LAST : 0;
        }
        unsigned int* f = ptr_add(flag, 8 * (e & 1023));
        const bool ok = (e & E_ON) ? flag_get(f) - 1 < ((e & E_FREE) ? 1 : 7) : (e & E_DRAW) && job;
        if (ok) {
          mbar_arrive(ev0 + 8 * i);
          if (e & (E_FREE | E_LAST)) flag_dec(f);
          i += 8;
          e = event();
        }
        asm volatile("{\n.reg .pred p;\nsetp.ge.u32 p, %0, 0x400000;\n@p trap;\n}\n" ::"r"(n));
        if (!__any_sync(0xffffffffu, ok)) __nanosleep(__any_sync(0xffffffffu, job || togo <= 2) ? 100 : 600);
      }
    } else if (threadIdx.x == 352) {
      uint32_t items = 0;
      auto read = [&](int id) {
        if (!(P.info[id] & I_NEXT)) return;
        wait_word(progress, items);
        flag_dec(flag + 2 * id);
      };
      for (int pc = 0;; pc++) {
        const uint32_t op = prog[pc];
        const int type = op & 3;
        if (type == OP_END) break;
        if (type == OP_O) {
          const uint32_t n = (op >> 13) & 127, base = items;
#pragma unroll 1
          for (uint32_t k = 3, id = (op >> 2) & 511; k <= n; k += 3, id++) {
            items = base + k + (k + TAIL > n ? TAIL : 0);
            read(id);
          }
          items = base + n + TAIL;
        } else if (type == OP_A) {
          if (op & F_PARK) { items++; read(N_TILE + ((op >> 13) & 127)); }
          items += 32;
        } else {
          items += 10;
        }
      }
    }
    __syncwarp();
    asm volatile("barrier.cluster.arrive.relaxed;\nbarrier.cluster.wait;" ::: "memory");
  }
}

typedef CUresult (*EncodeFn)(CUtensorMap*, CUtensorMapDataType, cuuint32_t, void*, const cuuint64_t*, const cuuint64_t*,
                             const cuuint32_t*, const cuuint32_t*, CUtensorMapInterleave, CUtensorMapSwizzle,
                             CUtensorMapL2promotion, CUtensorMapFloatOOBfill);

void encode(EncodeFn fn, CUtensorMap* m, const void* ptr, int rank, const cuuint64_t* dims, const cuuint64_t* strides,
            const cuuint32_t* box, CUtensorMapSwizzle swz) {
  const cuuint32_t es[5] = {1, 1, 1, 1, 1};
  CUresult r = fn(m, CU_TENSOR_MAP_DATA_TYPE_BFLOAT16, rank, const_cast<void*>(ptr), dims, strides, box, es,
                  CU_TENSOR_MAP_INTERLEAVE_NONE, swz, CU_TENSOR_MAP_L2_PROMOTION_L2_128B, CU_TENSOR_MAP_FLOAT_OOB_FILL_NONE);
  if (r != CUDA_SUCCESS) fprintf(stderr, "cuTensorMapEncodeTiled failed: %d\n", (int)r);
}

struct Op { int type, flags, id, n, quarter, park, item0, items; double t0, t1; };
struct Use { double ready, gate, need, freed; int readers, slot, prev; bool next; };
struct PlanStats { double end, slack, park_slack; int slots, parks; uint32_t own[N_CL]; };

bool plan(const char* const* text, int n_pair, int phase, Params& P, PlanStats* stats = nullptr) {
  constexpr double T_Q = 7900, T_A = 24800, T_U = TU, T_O = 640, T_RUN = 800, T_WIDE = TW, AHEAD = 3500, PUBLISH = 1500;
  const double margin = 256.0 * ((P.dbg >> 8) & 255);
  static Op op[N_CL][MAX_OPS];
  static Use use[ID_PART];
  int n_op[N_CL], covered[N_TEAM] = {};
  struct Ref { double t; Op* o; int id; };
  static Ref att[N_TILE + 1], dem[N_TILE], prk[MAX_PARK + 1], unp[MAX_PARK + 1], wr[ID_PART];
  auto sort = [](Ref* r, int n) {
    for (int i = 1; i < n; i++)
      for (int j = i; j > 0 && r[j].t < r[j - 1].t; j--) { Ref x = r[j]; r[j] = r[j - 1]; r[j - 1] = x; }
  };
  auto hex = [](char c) { return c <= '9' ? c - '0' : c - 'a' + 10; };
  for (int i = 0; i < n_pair; i++)
    for (const char* s = text[i]; *s; s++)
      if (*s == 'J') { if (covered[hex(s[1])]) return false; covered[hex(s[1])] = 10 * (s[2] - '0') + s[3] - '0'; }
  for (int c = 0; c < 2 * n_pair; c++) {
    int n = 0, items = 0;
    double t = 0;
    auto add = [&](int type, int flags, int id, int heads, int quarter, int its, double dt) {
      if (n < MAX_OPS) op[c][n] = {type, flags, id, heads, quarter, 0, items, its, t, t + dt};
      n++; items += its; t += dt;
    };
    for (const char* s = text[c >> 1]; *s; s++) {
      const int tm = hex(s[1]) & 15, nj = covered[tm];
      if (*s == 'N') { add(OP_Q, 0, 0, 0, 0, 10, T_Q); add(OP_A, 0, 0, 0, 0, 32, T_A); }
      if (*s == 'P') add(OP_Q, F_PARK, 0, 0, 0, 10, T_Q + TP);
      if (*s == '+' || *s == '-') t += *s == '+' ? 1000 : -1000;
      if (*s == 'U') { if (n == 0 || n > MAX_OPS || op[c][n - 1].type != OP_A) return false; add(OP_A, F_PARK, 0, 0, 0, 33, T_U); }
      if (*s == 'J') { if (nj < TAIL + 6 || nj > kSteps - 11) return false; add(OP_O, P_WIDE, tm * kH, nj, 2 * (c & 1), nj + TAIL, 2 * T_O * nj + T_WIDE); }
    }
    add(OP_O, 0, 0, 0, 0, 0, 0);
    add(OP_END, 0, 0, 0, 0, 0, 0);
    if (n > MAX_OPS || op[c][0].type != OP_Q) return false;
    n_op[c] = n - 1;
    att[c] = {t, &op[c][n - 2], 0};
  }
  for (int i = 0; i < 4 * N_TEAM; i++) dem[i] = {(double)covered[i / 4], nullptr, i};
  sort(att, 2 * n_pair); sort(dem, 4 * N_TEAM);
  for (int i = 0; i < 4 * N_TEAM; i++) {
    Op* f = att[i].o;
    const int nj = covered[dem[i].id / 4];
    f->flags = nj ? P_LD : 0;
    f->id = dem[i].id / 4 * kH + nj / 3; f->quarter = dem[i].id & 3; f->items = f->n = kSteps - nj;
    f[1].t0 = f[1].t1 = f->t1 = f->t0 + T_O * f->n + T_RUN; f[1].item0 += f->n;
  }
  for (int i = 0; i < ID_PART; i++) use[i] = {0, 0, 1e18, 0, 0, 0, 0, false};
  int n_att = 0, n_prk = 0, n_unp = 0;
  auto ready = [&](const Op* o) {
    const int nt = o[1].type;
    return o->t1 + (nt == OP_Q ? 6100 : o[1].n ? ((o[1].flags & P_WIDE) ? 7700 : 3900) : 1500) + PUBLISH;
  };
  for (int c = 0; c < 2 * n_pair; c++)
    for (Op* o = op[c]; o->type != OP_END; o++) {
      if (o->type == OP_A) { att[n_att] = {ready(o), o, 0}; if (++n_att > N_TILE) return false; }
      if (o->type == OP_A && o->flags) { unp[n_unp] = {o->t0 - AHEAD, o, 0}; if (++n_unp > MAX_PARK) return false; }
      if (o->type == OP_Q && o->flags) { prk[n_prk] = {ready(o), o, 0}; if (++n_prk > MAX_PARK) return false; }
      for (int i = 0; o->type == OP_O && i < o->n; i++) {
        const int nw = (o->flags & P_WIDE) ? o->n - TAIL : 0, k = nw ? i : kSteps - o->n + i;
        Use& u = use[o->id / kH * kH + k / 3];
        const double t = o->t0 + T_O * (i + (i < nw ? i : nw));
        if (t - AHEAD < u.need) u.need = t - AHEAD;
        const double f = !nw ? 1e18 : i + NBAR < o->items - TAIL || (nw && o[1].type != OP_O) ? t + T_O * (i < nw ? 2 : 1 + TAIL) + PUBLISH : 1e18;
        if (f > u.freed) u.freed = f;
        if (i == 0 || k % 3 == 0) u.readers++;
      }
    }
  if (n_att != N_TILE || n_prk != n_unp) return false;
  for (int i = 0; i < N_TILE; i++) { const int id = (i & 15) * kH + (i >> 4); dem[i] = {use[id].need, nullptr, id}; }
  sort(att, n_att); sort(dem, N_TILE); sort(prk, n_prk); sort(unp, n_unp);
  PlanStats st = {0, 1e18, 1e18, 0, n_prk};
  int n_wr = 0;
  for (int i = 0; i < N_TILE; i++) {
    Op* o = att[i].o;
    o->id = dem[i].id;
    if (!o->flags) o[-1].id = o->id;
    if (dem[i].t - att[i].t < st.slack) st.slack = dem[i].t - att[i].t;
    wr[n_wr++] = {o->t1 - 2 * AHEAD, o, o->id};
  }
  for (int i = 0; i < n_prk; i++) {
    prk[i].o->id = unp[i].o->id;
    prk[i].o->park = unp[i].o->park = i;
    use[N_TILE + i].freed = unp[i].o->t0 + 2 * PUBLISH;
    use[N_TILE + i].readers = 1;
    if (unp[i].t - prk[i].t < st.park_slack) st.park_slack = unp[i].t - prk[i].t;
    wr[n_wr++] = {prk[i].o->t1 - 2 * AHEAD, prk[i].o, N_TILE + i};
  }
  for (int c = 0; c < 2 * n_pair; c++)
    for (int d = 0; d < 2 * n_pair; d++)
      for (Op *f = &op[c][n_op[c] - 1], *o = op[d]; f->n && o->type != OP_END; o++)
        if (o->type == OP_O && (o->flags & P_WIDE) && o->id / kH == f->id / kH) {
          if (f->t0 - o->t1 > 4096.0 * ((P.dbg >> 16) & 255)) f->flags |= P_PRE;
          const double slack = f->t0 + ((f->flags & P_PRE) ? 0 : (f->n - 5) * T_O) - AHEAD - ready(o);
          if (slack < st.park_slack) st.park_slack = slack;
        }
  sort(wr, n_wr);
  int holder[N_TILE];
  for (int i = 0; i < n_wr; i++) {
    int best = -1;
    for (int sl = 0; sl < st.slots; sl++)
      if (use[holder[sl]].freed + margin <= wr[i].t && (best < 0 || use[holder[sl]].freed < use[holder[best]].freed)) best = sl;
    Use& u = use[wr[i].id];
    if (best >= 0) { u.prev = holder[best]; use[u.prev].next = true; wr[i].o->flags |= P_GATE; }
    else if (st.slots == N_TILE) return false;
    else best = st.slots++;
    u.slot = best;
    holder[best] = wr[i].id;
  }
  {
    int pos[N_CL] = {}, flag[ID_PART + 4 * N_TEAM] = {}, seen[ID_PART] = {};
    auto goal = [&](int c) { return op[c][n_op[c] - 1].item0; };
    for (bool moved = true; moved;) {
      moved = false;
      for (int c = 0; c < 2 * n_pair; c++) {
        for (; pos[c] < goal(c); pos[c]++, moved = true) {
          bool ok = true;
          for (const Op* o = op[c]; o->type != OP_END; o++) {
            const int k = pos[c] - o->item0, own = o->type == OP_A ? o->id : N_TILE + o->park;
            if (k < 0 || k >= o->items) continue;
            if (o->type == OP_O) ok = k >= o->n || flag[o->id + k / 3];
            else if (k == o->items - 1 && (o->flags & P_GATE)) ok = seen[use[own].prev] == use[use[own].prev].readers;
            else if (k == 0 && o->type == OP_A && (o->flags & F_PARK)) ok = flag[N_TILE + o->park];
          }
          if (!ok) break;
          for (const Op* o = op[c]; o->type != OP_END; o++) {
            if (pos[c] == o->item0 + o->items + (o[1].type == OP_Q ? 7 : o[1].item0 == goal(c) ? -1 : 5)) {
              if (o->type == OP_A) flag[o->id] = 1;
              if (o->type == OP_Q && (o->flags & F_PARK)) flag[N_TILE + o->park] = 1;
              if (o->type == OP_O) flag[ID_PART + o->id / kH * 4 + o->quarter] = flag[ID_PART + o->id / kH * 4 + o->quarter + 1] = 1;
            }
            const int k = pos[c] - NBAR - o->item0, nw = o->n - TAIL;
            if (k == 0 && o->type == OP_A && (o->flags & F_PARK)) seen[N_TILE + o->park]++;
            if (o->type == OP_O && k >= 0 && k < o->items && (k < nw || k >= o->n) && (k < nw ? k : k - TAIL) % 3 == 2) seen[o->id + (k < nw ? k : k - TAIL) / 3]++;
          }
        }
      }
    }
    for (int c = 0; c < 2 * n_pair; c++) if (pos[c] < goal(c)) return false;
  }
  int n_job = 0;
  for (int c = 0; c < 2 * n_pair; c++) {
    uint32_t items = 0, cur = 0, pend = 0;
    int n = 0, ev = 0;
    auto item = [&](uint32_t bytes, int count) {
      for (int i = 0; i < count; i++) { if (cur + bytes > RING) cur = 0; cur += bytes; items++; }
    };
    auto event = [&](uint32_t e) { if (ev < MAX_TAB) P.prog[c].ev[ev] = e; ev++; };
    for (const Op* o = op[c];; o++) {
      if (o->type != OP_END && phase && (o->type == OP_O) != (phase == 2)) continue;
      uint32_t cw = o->type | (items % NBAR) << 15 | ((items / NBAR) & 1) << 19 | (cur >> 12) << 20 | pend, pw = o->type | o->id << 2 | o->flags;
      const int ps = use[N_TILE + o->park].slot;
      pend = 0;
      if (o->type == OP_O) {
        pw |= o->n << 13 | o->quarter << 20;
        if (o->flags & P_WIDE) {
          cw |= o->n << 2 | (o->id / kH * 2 + o->quarter / 2) << 9 | C_WIDE;
          item(SZ_W, o->n - TAIL);
          item(SZ_W2, TAIL);
          item(SZ_W3, TAIL);
          pend = C_PEND;
          for (int i = 0; 3 * i < o->n; i++) event((o->id + i) | E_ON | (use[o->id + i].next ? 0 : E_LAST));
        } else {
          dem[n_job++] = {o->t0 - 1e6 * o->n, nullptr, (int)pw};
          st.own[c] = pw;
          pw = OP_O;
          event(E_DRAW | (items < 16 ? 0 : items - 16));
        }
      } else if (o->type != OP_END) {
        const bool parks = o->type == OP_Q && (o->flags & F_PARK);
        cw |= (parks ? ps : use[o->id].slot) << 2 | (o->flags & F_PARK);
        if (o->flags & F_PARK) pw |= o->park << 13 | ps << 20;
        if (o->type == OP_Q) item(SZ_Q, 10);
        else { if (o->flags & F_PARK) { item(SZ_PARK, 1); event((N_TILE + o->park) | E_ON | (use[N_TILE + o->park].next ? 0 : E_LAST)); } item(SZ_KV, 32); }
        if (parks || o->type == OP_A) pend = C_PEND;
        if (o->flags & P_GATE) event(use[parks ? N_TILE + o->park : o->id].prev | E_ON | E_FREE);
      }
      P.prog[c].c[n] = cw; P.prog[c].p[n++] = pw;
      if (o->type == OP_END) { if (o->t0 > st.end) st.end = o->t0; break; }
    }
    if (ev > MAX_TAB) return false;
    P.prog[c].n_ev = ev;
    while (n < MAX_OPS) { P.prog[c].c[n] = OP_END; P.prog[c].p[n++] = OP_END; }
    P.first[c] = (uint16_t)(P.prog[c].p[0] & 2047);
  }
  sort(dem, n_job);
  for (int i = 0; i < n_job; i++) P.job[i] = dem[i].id;
  for (int i = 0; i < ID_PART; i++) {
    if (i < N_TILE) P.slot[i] = use[i].slot;
    P.info[i] = (use[i].readers + use[i].next) | (use[i].next ? I_NEXT : 0);
  }
  if (stats) *stats = st;
  return true;
}

const char* const kPrograms[N_CL / 2] = {
  "PNJ065NNNNN", "PNJ158NNNNN", "PNJ256NNNNN", "PNJ354+NNNNN", "PNJ478NNNNN", "PNJ573NNNNN",
  "NNJ680NNNN", "NNJ768NNNN", "NNNNNJ835NN", "NNNNNNJf43N", "NNNNNJa52NN", "NNNNNJb48NN",
  "NUNNNNNNN", "NUNNNJd53NN", "NUNNNJe63NN", "NNNNNJ976N", "PNNNNNNNNN", "PNNNNNNNNN",
  "PNNNNNNNNN", "PNNNNNNNNN", "PNNNNNNNNN", "NNNNNNNNN", "NNNNNNNNN", "NNNNNNNNN",
  "NUNNNNNNN", "NNNNNNNNN", "NUNNNNNNN", "NUNNNNNNN", "NNUNNNNNN", "NUNNNNNNN",
  "NUNNNNNNN", "NNUNNJc53NN", "NUNNNNNNN",
};

const char* const* bench_programs() {
  return kPrograms;
}

}

extern "C" void kernel_launch(void* const* d_in, const int* in_sizes, int n_in, void* d_out, int out_size) {
  (void)in_sizes; (void)n_in; (void)out_size;
  static EncodeFn fn = nullptr;
  static int n_clusters = 0;
  if (!fn) {
    cudaDriverEntryPointQueryResult qr;
    void* f = nullptr;
    cudaGetDriverEntryPoint("cuTensorMapEncodeTiled", &f, cudaEnableDefault, &qr);
    fn = (EncodeFn)f;
    cudaFuncSetAttribute(fused_kernel, cudaFuncAttributeMaxDynamicSharedMemorySize, SMEM_BYTES);
    cudaLaunchConfig_t cfg = {};
    cfg.gridDim = dim3(132); cfg.blockDim = dim3(384); cfg.dynamicSmemBytes = SMEM_BYTES;
    cudaLaunchAttribute at[1];
    at[0].id = cudaLaunchAttributeClusterDimension; at[0].val.clusterDim.x = 2; at[0].val.clusterDim.y = 1; at[0].val.clusterDim.z = 1;
    cfg.attrs = at; cfg.numAttrs = 1;
    if (cudaOccupancyMaxActiveClusters(&n_clusters, fused_kernel, &cfg) != cudaSuccess || n_clusters < 1) n_clusters = 1;
    (void)cudaGetLastError();
  }
  static Params P;
  const CUtensorMapSwizzle S128 = CU_TENSOR_MAP_SWIZZLE_128B, S64 = CU_TENSOR_MAP_SWIZZLE_64B;
  for (int blk = 0; blk < 2; blk++) {
    void* const* in = d_in + 5 * blk;
    { const cuuint64_t d[] = {kD, kB * kSq}, s[] = {kD * 2}; const cuuint32_t b[] = {64, 128};
      encode(fn, &P.x[blk], in[0], 2, d, s, b, S128); }
    { const cuuint64_t d[] = {64, 8, 3, (cuuint64_t)kB * kH * kSk / 8}, s[] = {kDh * 2, 128, 8 * kDh * 2}; const cuuint32_t b[] = {64, 8, 3, 8};
      encode(fn, &P.k[blk], in[1], 4, d, s, b, S128);
      encode(fn, &P.v[blk], in[2], 4, d, s, b, S128); }
    { const cuuint64_t d[] = {64, kD, kHD / 64}, s[] = {kHD * 2, 128}; const cuuint32_t b[] = {64, 64, 3};
      encode(fn, &P.wq[blk], in[3], 3, d, s, b, S128); }
    { const cuuint64_t d[] = {32, 2, kHD / 8, 4, kD / 32}, s[] = {kD * 2, 8 * kD * 2, 2 * kD * 2, 64}; const cuuint32_t b[] = {32, 2, 4, 4, 5};
      encode(fn, &P.wo[blk], in[4], 5, d, s, b, S64); }
    { const cuuint64_t d[] = {64, 2, kHD / 8, 4, kD / 64}, s[] = {kD * 2, 8 * kD * 2, 2 * kD * 2, 128};
      const cuuint32_t b3[] = {64, 2, 4, 4, 3}, b2[] = {64, 2, 4, 4, 2};
      encode(fn, &P.wo3[blk], in[4], 5, d, s, b3, S128);
      encode(fn, &P.wo2[blk], in[4], 5, d, s, b2, S128); }
  }
  { const cuuint64_t d[] = {32, kB * kSq, 2 * kD / 32}, s[] = {2 * kD * 2, 64}; const cuuint32_t b[] = {32, 16, 1};
    encode(fn, &P.out, d_out, 3, d, s, b, S64); }

  P.xw[0] = (const char*)d_in[0]; P.xw[1] = (const char*)d_in[3];
  cudaGetSymbolAddress((void**)&P.g, g_scratch);
  P.dbg = DBG_DEFAULT;
  if (n_clusters >= N_CL && plan(bench_programs(), N_CL / 2, 0, P)) {
    fused_kernel<<<2 * N_CL, 384, SMEM_BYTES>>>(P);
  } else {
    const char* text[2 * N_TEAM];
    for (int i = 0; i < 2 * N_TEAM; i++) text[i] = "NNNNNNNN";
    for (int phase = 1; phase <= 2; phase++) {
      plan(text, 2 * N_TEAM, phase, P);
      fused_kernel<<<8 * N_TEAM, 384, SMEM_BYTES>>>(P);
    }
  }
}
```

```cpp
#include <cuda_runtime.h>
#include <cuda_bf16.h>
#include <cuda.h>
#include <stdint.h>
#include <stdio.h>

namespace {

constexpr int kB = 8, kSq = 256, kD = 640, kH = 32, kSk = 1024, kDh = 192;
constexpr int kHD = kH * kDh;
constexpr uint32_t RING = 224 * 1024;
constexpr uint32_t SZ_KV = 24576;
constexpr uint32_t SZ_Q = 16384 + 24576;
constexpr uint32_t SZ_O = 16384 + 20480;
constexpr uint32_t SZ_W3 = 16384 + 24576, SZ_W2 = 16384 + 16384, SZ_W = SZ_W3 + 16384;
constexpr uint32_t SZ_PARK = 49152;
constexpr uint32_t SZ_OL = SZ_O + 8192;
constexpr int NBAR = 10;
constexpr int EARLY = 3;
constexpr int kSteps = kHD / 64;
constexpr int TAIL = 4;
constexpr uint32_t KV_CH = 64, KV_SBO = 3072;
constexpr int SMEM_BYTES = RING + 1024 + 1024;
constexpr int N_TEAM = 16, N_CL = 66, MAX_OPS = 22, MAX_EV = 80, MAX_TAB = 47, N_TILE = N_TEAM * kH, MAX_PARK = 128, ID_PART = N_TILE + MAX_PARK;
enum : uint32_t { OP_END = 0, OP_Q = 1, OP_A = 2, OP_O = 3, F_PARK = 1 << 11,
                  C_WIDE = 1 << 27, C_PEND = 1 << 26, P_GATE = 1 << 12, P_WIDE = 1 << 11, P_LD = 1 << 12, P_PRE = 1 << 22,
                  I_NEXT = 8, E_ON = 1 << 15, E_FREE = 1 << 14, E_LAST = 1 << 13, E_DRAW = 1 << 12, E_JOB = 1 << 11 };

#define TU 25900
#define TW 1600
#define TP 1000
constexpr uint32_t DBG_DEFAULT = 0x040800;

struct alignas(1024) Scratch {
  unsigned int flag[2047];
  unsigned int ticket;
  uint4 part[N_TEAM * 2 * 2 * 5120];
  uint4 tile[N_TILE * 2 * 3072];
};

struct alignas(64) Params {
  const char* xw[2];
  uint16_t first[80];
  Scratch* g;
  uint32_t dbg;
  CUtensorMap x[2], wq[2], k[2], v[2], wo[2], wo3[2], wo2[2], out;
  struct {
    uint32_t c[MAX_OPS];
    uint32_t p[MAX_OPS];
    uint16_t n_ev, ev[MAX_TAB];
  } prog[N_CL];
  uint32_t job[N_CL];
  uint16_t slot[N_TILE];
  uint8_t info[ID_PART];
};

__device__ Scratch g_scratch;

template <int TB, int TA = 0>
__device__ __forceinline__ void wgmma_ss_n64(float (&d)[32], uint64_t da, uint64_t db, int scale_d) {
  asm volatile("{\n.reg .pred p;\nsetp.ne.b32 p, %34, 0;\n"
    "wgmma.mma_async.sync.aligned.m64n64k16.f32.bf16.bf16 {%0, %1, %2, %3, %4, %5, %6, %7, %8, %9, %10, %11, %12, %13, %14, %15, %16, %17, %18, %19, %20, %21, %22, %23, %24, %25, %26, %27, %28, %29, %30, %31}, %32, %33, p, 1, 1, %35, %36;\n}\n"
    : "+f"(d[0]), "+f"(d[1]), "+f"(d[2]), "+f"(d[3]), "+f"(d[4]), "+f"(d[5]), "+f"(d[6]), "+f"(d[7]), "+f"(d[8]), "+f"(d[9]), "+f"(d[10]), "+f"(d[11]), "+f"(d[12]), "+f"(d[13]), "+f"(d[14]), "+f"(d[15]), "+f"(d[16]), "+f"(d[17]), "+f"(d[18]), "+f"(d[19]), "+f"(d[20]), "+f"(d[21]), "+f"(d[22]), "+f"(d[23]), "+f"(d[24]), "+f"(d[25]), "+f"(d[26]), "+f"(d[27]), "+f"(d[28]), "+f"(d[29]), "+f"(d[30]), "+f"(d[31])
    : "l"(da), "l"(db), "r"(scale_d), "n"(TA), "n"(TB));
}
template <int TB>
__device__ __forceinline__ void wgmma_rs_n64(float (&d)[32], uint32_t a0, uint32_t a1, uint32_t a2, uint32_t a3, uint64_t db, int scale_d) {
  asm volatile("{\n.reg .pred p;\nsetp.ne.b32 p, %37, 0;\n"
    "wgmma.mma_async.sync.aligned.m64n64k16.f32.bf16.bf16 {%0, %1, %2, %3, %4, %5, %6, %7, %8, %9, %10, %11, %12, %13, %14, %15, %16, %17, %18, %19, %20, %21, %22, %23, %24, %25, %26, %27, %28, %29, %30, %31}, {%32, %33, %34, %35}, %36, p, 1, 1, %38;\n}\n"
    : "+f"(d[0]), "+f"(d[1]), "+f"(d[2]), "+f"(d[3]), "+f"(d[4]), "+f"(d[5]), "+f"(d[6]), "+f"(d[7]), "+f"(d[8]), "+f"(d[9]), "+f"(d[10]), "+f"(d[11]), "+f"(d[12]), "+f"(d[13]), "+f"(d[14]), "+f"(d[15]), "+f"(d[16]), "+f"(d[17]), "+f"(d[18]), "+f"(d[19]), "+f"(d[20]), "+f"(d[21]), "+f"(d[22]), "+f"(d[23]), "+f"(d[24]), "+f"(d[25]), "+f"(d[26]), "+f"(d[27]), "+f"(d[28]), "+f"(d[29]), "+f"(d[30]), "+f"(d[31])
    : "r"(a0), "r"(a1), "r"(a2), "r"(a3), "l"(db), "r"(scale_d), "n"(TB));
}
template <int TB, int TA = 0>
__device__ __forceinline__ void wgmma_ss_n128(float (&d)[64], uint64_t da, uint64_t db, int scale_d) {
  asm volatile("{\n.reg .pred p;\nsetp.ne.b32 p, %66, 0;\n"
    "wgmma.mma_async.sync.aligned.m64n128k16.f32.bf16.bf16 {%0, %1, %2, %3, %4, %5, %6, %7, %8, %9, %10, %11, %12, %13, %14, %15, %16, %17, %18, %19, %20, %21, %22, %23, %24, %25, %26, %27, %28, %29, %30, %31, %32, %33, %34, %35, %36, %37, %38, %39, %40, %41, %42, %43, %44, %45, %46, %47, %48, %49, %50, %51, %52, %53, %54, %55, %56, %57, %58, %59, %60, %61, %62, %63}, %64, %65, p, 1, 1, %67, %68;\n}\n"
    : "+f"(d[0]), "+f"(d[1]), "+f"(d[2]), "+f"(d[3]), "+f"(d[4]), "+f"(d[5]), "+f"(d[6]), "+f"(d[7]), "+f"(d[8]), "+f"(d[9]), "+f"(d[10]), "+f"(d[11]), "+f"(d[12]), "+f"(d[13]), "+f"(d[14]), "+f"(d[15]), "+f"(d[16]), "+f"(d[17]), "+f"(d[18]), "+f"(d[19]), "+f"(d[20]), "+f"(d[21]), "+f"(d[22]), "+f"(d[23]), "+f"(d[24]), "+f"(d[25]), "+f"(d[26]), "+f"(d[27]), "+f"(d[28]), "+f"(d[29]), "+f"(d[30]), "+f"(d[31]), "+f"(d[32]), "+f"(d[33]), "+f"(d[34]), "+f"(d[35]), "+f"(d[36]), "+f"(d[37]), "+f"(d[38]), "+f"(d[39]), "+f"(d[40]), "+f"(d[41]), "+f"(d[42]), "+f"(d[43]), "+f"(d[44]), "+f"(d[45]), "+f"(d[46]), "+f"(d[47]), "+f"(d[48]), "+f"(d[49]), "+f"(d[50]), "+f"(d[51]), "+f"(d[52]), "+f"(d[53]), "+f"(d[54]), "+f"(d[55]), "+f"(d[56]), "+f"(d[57]), "+f"(d[58]), "+f"(d[59]), "+f"(d[60]), "+f"(d[61]), "+f"(d[62]), "+f"(d[63])
    : "l"(da), "l"(db), "r"(scale_d), "n"(TA), "n"(TB));
}
template <int TB>
__device__ __forceinline__ void wgmma_rs_n128(float (&d)[64], uint32_t a0, uint32_t a1, uint32_t a2, uint32_t a3, uint64_t db, int scale_d) {
  asm volatile("{\n.reg .pred p;\nsetp.ne.b32 p, %69, 0;\n"
    "wgmma.mma_async.sync.aligned.m64n128k16.f32.bf16.bf16 {%0, %1, %2, %3, %4, %5, %6, %7, %8, %9, %10, %11, %12, %13, %14, %15, %16, %17, %18, %19, %20, %21, %22, %23, %24, %25, %26, %27, %28, %29, %30, %31, %32, %33, %34, %35, %36, %37, %38, %39, %40, %41, %42, %43, %44, %45, %46, %47, %48, %49, %50, %51, %52, %53, %54, %55, %56, %57, %58, %59, %60, %61, %62, %63}, {%64, %65, %66, %67}, %68, p, 1, 1, %70;\n}\n"
    : "+f"(d[0]), "+f"(d[1]), "+f"(d[2]), "+f"(d[3]), "+f"(d[4]), "+f"(d[5]), "+f"(d[6]), "+f"(d[7]), "+f"(d[8]), "+f"(d[9]), "+f"(d[10]), "+f"(d[11]), "+f"(d[12]), "+f"(d[13]), "+f"(d[14]), "+f"(d[15]), "+f"(d[16]), "+f"(d[17]), "+f"(d[18]), "+f"(d[19]), "+f"(d[20]), "+f"(d[21]), "+f"(d[22]), "+f"(d[23]), "+f"(d[24]), "+f"(d[25]), "+f"(d[26]), "+f"(d[27]), "+f"(d[28]), "+f"(d[29]), "+f"(d[30]), "+f"(d[31]), "+f"(d[32]), "+f"(d[33]), "+f"(d[34]), "+f"(d[35]), "+f"(d[36]), "+f"(d[37]), "+f"(d[38]), "+f"(d[39]), "+f"(d[40]), "+f"(d[41]), "+f"(d[42]), "+f"(d[43]), "+f"(d[44]), "+f"(d[45]), "+f"(d[46]), "+f"(d[47]), "+f"(d[48]), "+f"(d[49]), "+f"(d[50]), "+f"(d[51]), "+f"(d[52]), "+f"(d[53]), "+f"(d[54]), "+f"(d[55]), "+f"(d[56]), "+f"(d[57]), "+f"(d[58]), "+f"(d[59]), "+f"(d[60]), "+f"(d[61]), "+f"(d[62]), "+f"(d[63])
    : "r"(a0), "r"(a1), "r"(a2), "r"(a3), "l"(db), "r"(scale_d), "n"(TB));
}
template <int TB, int TA = 0>
__device__ __forceinline__ void wgmma_ss_n160(float (&d)[80], uint64_t da, uint64_t db, int scale_d) {
  asm volatile("{\n.reg .pred p;\nsetp.ne.b32 p, %82, 0;\n"
    "wgmma.mma_async.sync.aligned.m64n160k16.f32.bf16.bf16 {%0, %1, %2, %3, %4, %5, %6, %7, %8, %9, %10, %11, %12, %13, %14, %15, %16, %17, %18, %19, %20, %21, %22, %23, %24, %25, %26, %27, %28, %29, %30, %31, %32, %33, %34, %35, %36, %37, %38, %39, %40, %41, %42, %43, %44, %45, %46, %47, %48, %49, %50, %51, %52, %53, %54, %55, %56, %57, %58, %59, %60, %61, %62, %63, %64, %65, %66, %67, %68, %69, %70, %71, %72, %73, %74, %75, %76, %77, %78, %79}, %80, %81, p, 1, 1, %83, %84;\n}\n"
    : "+f"(d[0]), "+f"(d[1]), "+f"(d[2]), "+f"(d[3]), "+f"(d[4]), "+f"(d[5]), "+f"(d[6]), "+f"(d[7]), "+f"(d[8]), "+f"(d[9]), "+f"(d[10]), "+f"(d[11]), "+f"(d[12]), "+f"(d[13]), "+f"(d[14]), "+f"(d[15]), "+f"(d[16]), "+f"(d[17]), "+f"(d[18]), "+f"(d[19]), "+f"(d[20]), "+f"(d[21]), "+f"(d[22]), "+f"(d[23]), "+f"(d[24]), "+f"(d[25]), "+f"(d[26]), "+f"(d[27]), "+f"(d[28]), "+f"(d[29]), "+f"(d[30]), "+f"(d[31]), "+f"(d[32]), "+f"(d[33]), "+f"(d[34]), "+f"(d[35]), "+f"(d[36]), "+f"(d[37]), "+f"(d[38]), "+f"(d[39]), "+f"(d[40]), "+f"(d[41]), "+f"(d[42]), "+f"(d[43]), "+f"(d[44]), "+f"(d[45]), "+f"(d[46]), "+f"(d[47]), "+f"(d[48]), "+f"(d[49]), "+f"(d[50]), "+f"(d[51]), "+f"(d[52]), "+f"(d[53]), "+f"(d[54]), "+f"(d[55]), "+f"(d[56]), "+f"(d[57]), "+f"(d[58]), "+f"(d[59]), "+f"(d[60]), "+f"(d[61]), "+f"(d[62]), "+f"(d[63]), "+f"(d[64]), "+f"(d[65]), "+f"(d[66]), "+f"(d[67]), "+f"(d[68]), "+f"(d[69]), "+f"(d[70]), "+f"(d[71]), "+f"(d[72]), "+f"(d[73]), "+f"(d[74]), "+f"(d[75]), "+f"(d[76]), "+f"(d[77]), "+f"(d[78]), "+f"(d[79])
    : "l"(da), "l"(db), "r"(scale_d), "n"(TA), "n"(TB));
}
template <int TB>
__device__ __forceinline__ void wgmma_rs_n160(float (&d)[80], uint32_t a0, uint32_t a1, uint32_t a2, uint32_t a3, uint64_t db, int scale_d) {
  asm volatile("{\n.reg .pred p;\nsetp.ne.b32 p, %85, 0;\n"
    "wgmma.mma_async.sync.aligned.m64n160k16.f32.bf16.bf16 {%0, %1, %2, %3, %4, %5, %6, %7, %8, %9, %10, %11, %12, %13, %14, %15, %16, %17, %18, %19, %20, %21, %22, %23, %24, %25, %26, %27, %28, %29, %30, %31, %32, %33, %34, %35, %36, %37, %38, %39, %40, %41, %42, %43, %44, %45, %46, %47, %48, %49, %50, %51, %52, %53, %54, %55, %56, %57, %58, %59, %60, %61, %62, %63, %64, %65, %66, %67, %68, %69, %70, %71, %72, %73, %74, %75, %76, %77, %78, %79}, {%80, %81, %82, %83}, %84, p, 1, 1, %86;\n}\n"
    : "+f"(d[0]), "+f"(d[1]), "+f"(d[2]), "+f"(d[3]), "+f"(d[4]), "+f"(d[5]), "+f"(d[6]), "+f"(d[7]), "+f"(d[8]), "+f"(d[9]), "+f"(d[10]), "+f"(d[11]), "+f"(d[12]), "+f"(d[13]), "+f"(d[14]), "+f"(d[15]), "+f"(d[16]), "+f"(d[17]), "+f"(d[18]), "+f"(d[19]), "+f"(d[20]), "+f"(d[21]), "+f"(d[22]), "+f"(d[23]), "+f"(d[24]), "+f"(d[25]), "+f"(d[26]), "+f"(d[27]), "+f"(d[28]), "+f"(d[29]), "+f"(d[30]), "+f"(d[31]), "+f"(d[32]), "+f"(d[33]), "+f"(d[34]), "+f"(d[35]), "+f"(d[36]), "+f"(d[37]), "+f"(d[38]), "+f"(d[39]), "+f"(d[40]), "+f"(d[41]), "+f"(d[42]), "+f"(d[43]), "+f"(d[44]), "+f"(d[45]), "+f"(d[46]), "+f"(d[47]), "+f"(d[48]), "+f"(d[49]), "+f"(d[50]), "+f"(d[51]), "+f"(d[52]), "+f"(d[53]), "+f"(d[54]), "+f"(d[55]), "+f"(d[56]), "+f"(d[57]), "+f"(d[58]), "+f"(d[59]), "+f"(d[60]), "+f"(d[61]), "+f"(d[62]), "+f"(d[63]), "+f"(d[64]), "+f"(d[65]), "+f"(d[66]), "+f"(d[67]), "+f"(d[68]), "+f"(d[69]), "+f"(d[70]), "+f"(d[71]), "+f"(d[72]), "+f"(d[73]), "+f"(d[74]), "+f"(d[75]), "+f"(d[76]), "+f"(d[77]), "+f"(d[78]), "+f"(d[79])
    : "r"(a0), "r"(a1), "r"(a2), "r"(a3), "l"(db), "r"(scale_d), "n"(TB));
}
template <int TB, int TA = 0>
__device__ __forceinline__ void wgmma_ss_n192(float (&d)[96], uint64_t da, uint64_t db, int scale_d) {
  asm volatile("{\n.reg .pred p;\nsetp.ne.b32 p, %98, 0;\n"
    "wgmma.mma_async.sync.aligned.m64n192k16.f32.bf16.bf16 {%0, %1, %2, %3, %4, %5, %6, %7, %8, %9, %10, %11, %12, %13, %14, %15, %16, %17, %18, %19, %20, %21, %22, %23, %24, %25, %26, %27, %28, %29, %30, %31, %32, %33, %34, %35, %36, %37, %38, %39, %40, %41, %42, %43, %44, %45, %46, %47, %48, %49, %50, %51, %52, %53, %54, %55, %56, %57, %58, %59, %60, %61, %62, %63, %64, %65, %66, %67, %68, %69, %70, %71, %72, %73, %74, %75, %76, %77, %78, %79, %80, %81, %82, %83, %84, %85, %86, %87, %88, %89, %90, %91, %92, %93, %94, %95}, %96, %97, p, 1, 1, %99, %100;\n}\n"
    : "+f"(d[0]), "+f"(d[1]), "+f"(d[2]), "+f"(d[3]), "+f"(d[4]), "+f"(d[5]), "+f"(d[6]), "+f"(d[7]), "+f"(d[8]), "+f"(d[9]), "+f"(d[10]), "+f"(d[11]), "+f"(d[12]), "+f"(d[13]), "+f"(d[14]), "+f"(d[15]), "+f"(d[16]), "+f"(d[17]), "+f"(d[18]), "+f"(d[19]), "+f"(d[20]), "+f"(d[21]), "+f"(d[22]), "+f"(d[23]), "+f"(d[24]), "+f"(d[25]), "+f"(d[26]), "+f"(d[27]), "+f"(d[28]), "+f"(d[29]), "+f"(d[30]), "+f"(d[31]), "+f"(d[32]), "+f"(d[33]), "+f"(d[34]), "+f"(d[35]), "+f"(d[36]), "+f"(d[37]), "+f"(d[38]), "+f"(d[39]), "+f"(d[40]), "+f"(d[41]), "+f"(d[42]), "+f"(d[43]), "+f"(d[44]), "+f"(d[45]), "+f"(d[46]), "+f"(d[47]), "+f"(d[48]), "+f"(d[49]), "+f"(d[50]), "+f"(d[51]), "+f"(d[52]), "+f"(d[53]), "+f"(d[54]), "+f"(d[55]), "+f"(d[56]), "+f"(d[57]), "+f"(d[58]), "+f"(d[59]), "+f"(d[60]), "+f"(d[61]), "+f"(d[62]), "+f"(d[63]), "+f"(d[64]), "+f"(d[65]), "+f"(d[66]), "+f"(d[67]), "+f"(d[68]), "+f"(d[69]), "+f"(d[70]), "+f"(d[71]), "+f"(d[72]), "+f"(d[73]), "+f"(d[74]), "+f"(d[75]), "+f"(d[76]), "+f"(d[77]), "+f"(d[78]), "+f"(d[79]), "+f"(d[80]), "+f"(d[81]), "+f"(d[82]), "+f"(d[83]), "+f"(d[84]), "+f"(d[85]), "+f"(d[86]), "+f"(d[87]), "+f"(d[88]), "+f"(d[89]), "+f"(d[90]), "+f"(d[91]), "+f"(d[92]), "+f"(d[93]), "+f"(d[94]), "+f"(d[95])
    : "l"(da), "l"(db), "r"(scale_d), "n"(TA), "n"(TB));
}
template <int TB>
__device__ __forceinline__ void wgmma_rs_n192(float (&d)[96], uint32_t a0, uint32_t a1, uint32_t a2, uint32_t a3, uint64_t db, int scale_d) {
  asm volatile("{\n.reg .pred p;\nsetp.ne.b32 p, %101, 0;\n"
    "wgmma.mma_async.sync.aligned.m64n192k16.f32.bf16.bf16 {%0, %1, %2, %3, %4, %5, %6, %7, %8, %9, %10, %11, %12, %13, %14, %15, %16, %17, %18, %19, %20, %21, %22, %23, %24, %25, %26, %27, %28, %29, %30, %31, %32, %33, %34, %35, %36, %37, %38, %39, %40, %41, %42, %43, %44, %45, %46, %47, %48, %49, %50, %51, %52, %53, %54, %55, %56, %57, %58, %59, %60, %61, %62, %63, %64, %65, %66, %67, %68, %69, %70, %71, %72, %73, %74, %75, %76, %77, %78, %79, %80, %81, %82, %83, %84, %85, %86, %87, %88, %89, %90, %91, %92, %93, %94, %95}, {%96, %97, %98, %99}, %100, p, 1, 1, %102;\n}\n"
    : "+f"(d[0]), "+f"(d[1]), "+f"(d[2]), "+f"(d[3]), "+f"(d[4]), "+f"(d[5]), "+f"(d[6]), "+f"(d[7]), "+f"(d[8]), "+f"(d[9]), "+f"(d[10]), "+f"(d[11]), "+f"(d[12]), "+f"(d[13]), "+f"(d[14]), "+f"(d[15]), "+f"(d[16]), "+f"(d[17]), "+f"(d[18]), "+f"(d[19]), "+f"(d[20]), "+f"(d[21]), "+f"(d[22]), "+f"(d[23]), "+f"(d[24]), "+f"(d[25]), "+f"(d[26]), "+f"(d[27]), "+f"(d[28]), "+f"(d[29]), "+f"(d[30]), "+f"(d[31]), "+f"(d[32]), "+f"(d[33]), "+f"(d[34]), "+f"(d[35]), "+f"(d[36]), "+f"(d[37]), "+f"(d[38]), "+f"(d[39]), "+f"(d[40]), "+f"(d[41]), "+f"(d[42]), "+f"(d[43]), "+f"(d[44]), "+f"(d[45]), "+f"(d[46]), "+f"(d[47]), "+f"(d[48]), "+f"(d[49]), "+f"(d[50]), "+f"(d[51]), "+f"(d[52]), "+f"(d[53]), "+f"(d[54]), "+f"(d[55]), "+f"(d[56]), "+f"(d[57]), "+f"(d[58]), "+f"(d[59]), "+f"(d[60]), "+f"(d[61]), "+f"(d[62]), "+f"(d[63]), "+f"(d[64]), "+f"(d[65]), "+f"(d[66]), "+f"(d[67]), "+f"(d[68]), "+f"(d[69]), "+f"(d[70]), "+f"(d[71]), "+f"(d[72]), "+f"(d[73]), "+f"(d[74]), "+f"(d[75]), "+f"(d[76]), "+f"(d[77]), "+f"(d[78]), "+f"(d[79]), "+f"(d[80]), "+f"(d[81]), "+f"(d[82]), "+f"(d[83]), "+f"(d[84]), "+f"(d[85]), "+f"(d[86]), "+f"(d[87]), "+f"(d[88]), "+f"(d[89]), "+f"(d[90]), "+f"(d[91]), "+f"(d[92]), "+f"(d[93]), "+f"(d[94]), "+f"(d[95])
    : "r"(a0), "r"(a1), "r"(a2), "r"(a3), "l"(db), "r"(scale_d), "n"(TB));
}

__device__ __forceinline__ uint32_t smem_u32(const void* p) { return (uint32_t)__cvta_generic_to_shared(p); }
__device__ __forceinline__ void wg_fence() { asm volatile("wgmma.fence.sync.aligned;" ::: "memory"); }
__device__ __forceinline__ void wg_commit() { asm volatile("wgmma.commit_group.sync.aligned;" ::: "memory"); }
template <int N> __device__ __forceinline__ void wg_wait() { asm volatile("wgmma.wait_group.sync.aligned %0;" ::"n"(N) : "memory"); }
__device__ __forceinline__ void sched_fence(uint32_t& keep, bool never) {
  asm volatile("{\n.reg .pred p;\nsetp.ne.b32 p, %1, 0;\n@p mov.u32 %0, %%clock;\n}\n" : "+r"(keep) : "r"((int)never) : "memory");
}
template <int N> __device__ __forceinline__ void fence_regs(float (&r)[N]) {
#pragma unroll
  for (int i = 0; i < N; i++) asm volatile("" : "+f"(r[i])::"memory");
}
template <int N> __device__ __forceinline__ void undefine(float (&r)[N]) {
#pragma unroll
  for (int i = 0; i < N; i++) asm volatile("" : "=f"(r[i]));
}
template <int N> __device__ __forceinline__ void fence_regs(uint32_t (&r)[N]) {
#pragma unroll
  for (int i = 0; i < N; i++) asm volatile("" : "+r"(r[i])::"memory");
}
__device__ __forceinline__ uint64_t mk_desc(uint32_t a16, uint32_t lbo, uint32_t sbo, uint32_t swz) {
  uint64_t d;
  asm("mov.b64 %0, {%1, %2};" : "=l"(d) : "r"(a16 + ((lbo >> 4) << 16)), "r"((sbo >> 4) | (swz << 30)));
  return d;
}
__device__ __forceinline__ void mbar_init(uint32_t bar, uint32_t cnt) {
  asm volatile("mbarrier.init.shared::cta.b64 [%0], %1;" ::"r"(bar), "r"(cnt) : "memory");
}
__device__ __forceinline__ void mbar_expect(uint32_t bar, uint32_t tx) {
  asm volatile("mbarrier.arrive.expect_tx.shared::cta.b64 _, [%0], %1;" ::"r"(bar), "r"(tx) : "memory");
}
__device__ __forceinline__ bool mbar_test(uint32_t bar, uint32_t ph) {
  uint32_t ok;
  asm volatile("{\n.reg .pred p;\nmbarrier.test_wait.parity.shared::cta.b64 p, [%1], %2;\nselp.u32 %0, 1, 0, p;\n}\n"
               : "=r"(ok) : "r"(bar), "r"(ph) : "memory");
  return ok;
}
__device__ __forceinline__ bool mbar_try(uint32_t bar, uint32_t ph, uint32_t ns) {
  uint32_t ok;
  asm volatile("{\n.reg .pred p;\nmbarrier.try_wait.parity.shared::cta.b64 p, [%1], %2, %3;\nselp.u32 %0, 1, 0, p;\n}\n"
               : "=r"(ok) : "r"(bar), "r"(ph), "r"(ns) : "memory");
  return ok;
}
__device__ __forceinline__ void mbar_wait(uint32_t bar, uint32_t ph) {
  asm volatile("{\n.reg .pred p;\n.reg .u32 n;\nmov.u32 n, 0;\n"
               "LOOP:\nmbarrier.try_wait.parity.shared::cta.b64 p, [%0], %1;\n@p bra DONE;\n"
               "add.u32 n, n, 1;\nsetp.lt.u32 p, n, 0x1000000;\n@p bra LOOP;\ntrap;\n"
               "DONE:\n}\n" ::"r"(bar), "r"(ph) : "memory");
}
__device__ __forceinline__ void mbar_wait_long(uint32_t bar) {
  asm volatile("{\n.reg .pred p;\n.reg .u32 n;\nmov.u32 n, 0;\n"
               "LOOP:\nmbarrier.try_wait.parity.shared::cta.b64 p, [%0], 0, 20000;\n@p bra DONE;\n"
               "add.u32 n, n, 1;\nsetp.lt.u32 p, n, 0x100000;\n@p bra LOOP;\ntrap;\n"
               "DONE:\n}\n" ::"r"(bar) : "memory");
}
__device__ __forceinline__ void mbar_arrive_cluster_if(bool on, uint32_t addr) {
  asm volatile("{\n.reg .pred p;\nsetp.ne.b32 p, %1, 0;\n@p mbarrier.arrive.shared::cluster.b64 _, [%0];\n}\n" ::"r"(addr), "r"((int)on) : "memory");
}
__device__ __forceinline__ void mbar_arrive_cluster_n(uint32_t n, uint32_t addr) {
  asm volatile("{\n.reg .pred p;\nsetp.ne.b32 p, %1, 0;\n@p mbarrier.arrive.shared::cluster.b64 _, [%0], %1;\n}\n" ::"r"(addr), "r"(n) : "memory");
}
__device__ __forceinline__ void tma2d(uint32_t dst, const CUtensorMap* m, uint32_t bar, int c0, int c1) {
  asm volatile("cp.async.bulk.tensor.2d.shared::cluster.global.mbarrier::complete_tx::bytes [%0], [%1, {%3, %4}], [%2];"
               ::"r"(dst), "l"(m), "r"(bar), "r"(c0), "r"(c1) : "memory");
}
__device__ __forceinline__ void tma3d(uint32_t dst, const CUtensorMap* m, uint32_t bar, int c0, int c1, int c2) {
  asm volatile("cp.async.bulk.tensor.3d.shared::cluster.global.mbarrier::complete_tx::bytes [%0], [%1, {%3, %4, %5}], [%2];"
               ::"r"(dst), "l"(m), "r"(bar), "r"(c0), "r"(c1), "r"(c2) : "memory");
}
__device__ __forceinline__ void tma3d_mc(uint32_t dst, const CUtensorMap* m, uint32_t bar, int c0, int c1, int c2) {
  asm volatile("cp.async.bulk.tensor.3d.shared::cluster.global.mbarrier::complete_tx::bytes.multicast::cluster"
               " [%0], [%1, {%3, %4, %5}], [%2], %6;"
               ::"r"(dst), "l"(m), "r"(bar), "r"(c0), "r"(c1), "r"(c2), "h"((uint16_t)3) : "memory");
}
__device__ __forceinline__ void tma3d_store(const CUtensorMap* m, uint32_t src, int c0, int c1, int c2) {
  asm volatile("cp.async.bulk.tensor.3d.global.shared::cta.bulk_group [%0, {%2, %3, %4}], [%1];"
               ::"l"(m), "r"(src), "r"(c0), "r"(c1), "r"(c2) : "memory");
}
__device__ __forceinline__ void bar_sync(int id, int n) { asm volatile("bar.sync %0, %1;" ::"r"(id), "r"(n) : "memory"); }
__device__ __forceinline__ uint32_t pack_bf16(float lo, float hi) {
  uint32_t r;
  asm("cvt.rn.bf16x2.f32 %0, %1, %2;" : "=r"(r) : "f"(hi), "f"(lo));
  return r;
}
__device__ __forceinline__ float ex2(float x) {
  float y;
  asm("ex2.approx.ftz.f32 %0, %1;" : "=f"(y) : "f"(x));
  return y;
}
__device__ __forceinline__ float rcp(float x) {
  float y;
  asm("rcp.approx.ftz.f32 %0, %1;" : "=f"(y) : "f"(x));
  return y;
}
__device__ __forceinline__ void stsm4(uint32_t addr, uint32_t a, uint32_t b, uint32_t c, uint32_t d) {
  asm volatile("stmatrix.sync.aligned.m8n8.x4.shared.b16 [%0], {%1, %2, %3, %4};" ::"r"(addr), "r"(a), "r"(b), "r"(c), "r"(d) : "memory");
}

__device__ __forceinline__ void tma4d_mc_hint(uint32_t dst, const CUtensorMap* m, uint32_t bar, int c3, uint64_t pol) {
  asm volatile("cp.async.bulk.tensor.4d.shared::cluster.global.mbarrier::complete_tx::bytes.multicast::cluster.L2::cache_hint"
               " [%0], [%1, {%3, %3, %3, %4}], [%2], %5, %6;"
               ::"r"(dst), "l"(m), "r"(bar), "r"(0), "r"(c3), "h"((uint16_t)3), "l"(pol) : "memory");
}
__device__ __forceinline__ void tma5d_mc(uint32_t dst, const CUtensorMap* m, uint32_t bar, int c2, int c4) {
  asm volatile("cp.async.bulk.tensor.5d.shared::cluster.global.mbarrier::complete_tx::bytes.multicast::cluster"
               " [%0], [%1, {%3, %3, %4, %3, %5}], [%2], %6;"
               ::"r"(dst), "l"(m), "r"(bar), "r"(0), "r"(c2), "r"(c4), "h"((uint16_t)3) : "memory");
}
__device__ __forceinline__ void bulk_load_hint(uint32_t dst, const void* src, uint32_t bytes, uint32_t bar, uint64_t pol) {
  asm volatile("cp.async.bulk.shared::cluster.global.mbarrier::complete_tx::bytes.L2::cache_hint [%0], [%1], %2, [%3], %4;"
               ::"r"(dst), "l"(src), "r"(bytes), "r"(bar), "l"(pol) : "memory");
}
__device__ __forceinline__ void stg2_if(bool on, void* p, uint32_t a, uint32_t b, uint32_t c, uint32_t d, uint32_t e, uint32_t f,
                                        uint32_t g, uint32_t h, uint64_t pol) {
  asm volatile("{\n.reg .pred p;\nsetp.ne.b32 p, %10, 0;\n"
               "@p st.global.L2::cache_hint.v4.b32 [%0], {%1, %2, %3, %4}, %9;\n"
               "@p st.global.L2::cache_hint.v4.b32 [%0 + 512], {%5, %6, %7, %8}, %9;\n}\n"
               ::"l"(p), "r"(a), "r"(b), "r"(c), "r"(d), "r"(e), "r"(f), "r"(g), "r"(h), "l"(pol), "r"((int)on) : "memory");
}
__device__ __forceinline__ uint64_t evict_first() {
  uint64_t p;
  asm("createpolicy.fractional.L2::evict_first.b64 %0, 1.0;" : "=l"(p));
  return p;
}
__device__ __forceinline__ bool elect() {
  uint32_t ok;
  asm volatile("{\n.reg .pred p;\nelect.sync _|p, 0xffffffff;\nselp.u32 %0, 1, 0, p;\n}\n" : "=r"(ok));
  return ok;
}
__device__ __forceinline__ void mbar_arrive(uint32_t bar) {
  asm volatile("mbarrier.arrive.shared::cta.b64 _, [%0];" ::"r"(bar) : "memory");
}
__device__ __forceinline__ void mbar_arrive_if(bool on, uint32_t bar) {
  asm volatile("{\n.reg .pred p;\nsetp.ne.b32 p, %1, 0;\n@p mbarrier.arrive.shared::cta.b64 _, [%0];\n}\n" ::"r"(bar), "r"((int)on) : "memory");
}
__device__ __forceinline__ void lds2_if(bool on, uint32_t p, uint32_t (&t)[8]) {
  asm volatile("{\n.reg .pred p;\nsetp.ne.b32 p, %9, 0;\n@p ld.shared.v4.b32 {%0, %1, %2, %3}, [%8];\n@p ld.shared.v4.b32 {%4, %5, %6, %7}, [%8 + 512];\n}\n"
               : "+r"(t[0]), "+r"(t[1]), "+r"(t[2]), "+r"(t[3]), "+r"(t[4]), "+r"(t[5]), "+r"(t[6]), "+r"(t[7]) : "r"(p), "r"((int)on) : "memory");
}
__device__ __forceinline__ void lds128(uint32_t p, uint32_t& a, uint32_t& b, uint32_t& c, uint32_t& d) {
  asm volatile("ld.shared.v4.b32 {%0, %1, %2, %3}, [%4];" : "=r"(a), "=r"(b), "=r"(c), "=r"(d) : "r"(p) : "memory");
}
template <class T> __device__ __forceinline__ T* ptr_add(T* base, uint32_t bytes) {
  T* r;
  asm("{\n.reg .u32 lo, hi;\nmov.b64 {lo, hi}, %1;\nadd.cc.u32 lo, lo, %2;\naddc.u32 hi, hi, 0;\nmov.b64 %0, {lo, hi};\n}\n" : "=l"(r) : "l"(base), "r"(bytes));
  return r;
}
__device__ __forceinline__ uint32_t lds32(uint32_t p) {
  uint32_t v;
  asm volatile("ld.volatile.shared.u32 %0, [%1];" : "=r"(v) : "r"(p) : "memory");
  return v;
}
__device__ __forceinline__ uint32_t flag_get(const unsigned int* p) {
  uint32_t v;
  asm volatile("ld.acquire.gpu.global.u32 %0, [%1];" : "=r"(v) : "l"(p) : "memory");
  return v;
}
__device__ __forceinline__ uint32_t wait_word(uint32_t p, uint32_t target) {
  uint32_t v;
  asm volatile("{\n.reg .pred p;\n.reg .u32 n;\nmov.u32 n, 0;\n"
               "LOOP:\nld.acquire.cta.shared.u32 %0, [%1];\nsetp.ge.u32 p, %0, %2;\n@p bra DONE;\n"
               "nanosleep.u32 %3;\nadd.u32 n, n, 1;\nsetp.lt.u32 p, n, 0x400000;\n@p bra LOOP;\ntrap;\n"
               "DONE:\n}\n" : "=r"(v) : "r"(p), "r"(target), "n"(400) : "memory");
  return v;
}
__device__ __forceinline__ void flag_set(unsigned int* p, uint32_t v) {
  asm volatile("st.release.gpu.global.u32 [%0], %1;" ::"l"(p), "r"(v) : "memory");
}
__device__ __forceinline__ void flag_dec(unsigned int* p) {
  asm volatile("red.relaxed.gpu.global.add.u32 [%0], 0xffffffff;" ::"l"(p) : "memory");
}

struct Cursor {
  int bi;
  uint32_t ph;
  __device__ __forceinline__ void next() {
    if (++bi == NBAR) { bi = 0; ph ^= 1; }
  }
};

constexpr float kScaleLog2 = 0.07216878364870322f * 1.4426950408889634f;
constexpr float kSumLimit = 1048576.0f;

__global__ void __cluster_dims__(2, 1, 1) __launch_bounds__(384, 1)
fused_kernel(const __grid_constant__ Params P) {
  extern __shared__ uint8_t smem_raw[];
  const uint32_t sbase = (smem_u32(smem_raw) + 1023) & ~1023u;
  const uint32_t full0 = sbase + RING, empty0 = full0 + 8 * NBAR, odone0 = empty0 + 8 * NBAR, ev0 = odone0 + 8 * MAX_OPS;
  const uint32_t progress = ev0 + 8 * MAX_EV, jobw = progress + 4;
  const uint32_t rank = blockIdx.x & 1;
  const int role = blockIdx.x >> 1;
  const int wid = __shfl_sync(0xffffffffu, (int)(threadIdx.x >> 5), 0);
  const int wg = wid >> 2;

  if (wid < 8) {
    if (elect()) {
#pragma unroll
      for (int j = 0; j < 16; j++) {
        const int i = EARLY + 16 * wid + j;
        if (i < 2 * NBAR + MAX_OPS + MAX_EV) mbar_init(full0 + 8 * i, i < NBAR ? 1 : i < 2 * NBAR ? 16 : i < 2 * NBAR + MAX_OPS ? 8 : 1);
      }
      if (wid == 7) asm volatile("st.shared.v2.u32 [%0], {0, 0};\nfence.acq_rel.cta;" ::"r"(progress) : "memory");
      asm volatile("fence.mbarrier_init.release.cluster;" ::: "memory");
    }
  } else if (wid > 8) {
    const uint32_t g = blockIdx.x * 96 + threadIdx.x - 288, w = g - 2048;
    if (g < 4096) asm volatile("prefetch.global.L2 [%0];" ::"l"(g < 2048 ? P.xw[0] + g * (kD * 2) : P.xw[1] + (w >> 5) * (kHD * 2) + (w & 31) * 128));
  } else {
    const uint32_t op0 = P.first[role];
    if (elect()) {
#pragma unroll
      for (int k = 0; k < EARLY; k++) mbar_init(full0 + 8 * k, 1);
      asm volatile("fence.mbarrier_init.release.cluster;" ::: "memory");
      const int blk = (op0 >> 10) & 1;
      if ((op0 & 3) == OP_Q) {
#pragma unroll
        for (int k = 0; k < EARLY; k++) {
          mbar_expect(full0 + 8 * k, SZ_Q);
          tma2d(sbase + k * SZ_Q, &P.x[blk], full0 + 8 * k, 64 * k, ((op0 >> 7) & 7) * kSq + rank * 128);
          tma3d(sbase + k * SZ_Q + 16384, &P.wq[blk], full0 + 8 * k, 0, 64 * k, 3 * ((op0 >> 2) & 31));
        }
      }
      asm volatile("prefetch.tensormap [%0];" ::"l"(rank ? &P.v[blk] : &P.k[blk]) : "memory");
    }
  }
  __syncwarp();
  asm volatile("barrier.cluster.arrive.relaxed.aligned;\nbarrier.cluster.wait.aligned;" ::: "memory");

  if (wg < 2) {
    asm volatile("setmaxnreg.inc.sync.aligned.u32 240;");
    const uint32_t* prog = P.prog[role].c;
    const int lane = threadIdx.x & 31, warp = wid & 3;
    uint32_t empty_rem;
    asm volatile("mapa.shared::cluster.u32 %0, %1, %2;" : "=r"(empty_rem) : "r"(empty0), "r"(lane & 1));
    uint32_t keep = (threadIdx.x & 127) < 2 ? 4 : 0;
    auto release = [&](int slot) { mbar_arrive_cluster_n(keep, empty_rem + 8 * slot); };
    auto release_warp = [&](int slot, bool on = true) { mbar_arrive_cluster_if(lane < 2 && on, empty_rem + 8 * slot); };
    Cursor r{0, 0};
    const uint32_t ring16 = (sbase & 0x3FFFF) >> 4;
    uint32_t cur = ring16;
    bool rdy0 = false, rdy1 = false;
    auto probe1 = [&]() { rdy0 = mbar_test(full0 + 8 * r.bi, r.ph); };
    auto probe2 = [&]() {
      Cursor n = r;
      rdy0 = mbar_test(full0 + 8 * n.bi, n.ph);
      n.next();
      rdy1 = mbar_test(full0 + 8 * n.bi, n.ph);
    };
    auto take = [&](bool rdy, uint32_t bytes, uint32_t& addr) {
      const int bi = r.bi;
      if (__builtin_expect(!__all_sync(0xffffffffu, rdy), 0)) mbar_wait(full0 + 8 * r.bi, r.ph);
      r.next();
      if (cur > ring16 + ((RING - bytes) >> 4)) cur = ring16;
      addr = cur;
      cur += bytes >> 4;
      return bi;
    };
    const bool never = P.dbg == 0xffffffffu;
    uint32_t q[48];
#pragma unroll
    for (int i = 0; i < 48; i++) q[i] = 0;
    const int row = wg * 64 + warp * 16 + (lane >> 2);
    const int img0 = row * 4 + ((lane & 3) ^ ((row >> 1) & 3));
    uint4* pend = nullptr;
    bool pend_any = false;
    const uint64_t spol = evict_first();
    int pc = 0;
    auto slab = [&](int c, int i0) {
#pragma unroll
      for (int i = i0; i < 6; i++)
        stg2_if(c == i, pend + i * 512, q[8 * i], q[8 * i + 1], q[8 * i + 2], q[8 * i + 3],
                q[8 * i + 4], q[8 * i + 5], q[8 * i + 6], q[8 * i + 7], spol);
    };
    auto drain = [&](int c) {
      if (!pend_any || c >= 6) return;
      slab(c, 0);
      if (c == 5) {
        __syncwarp();
        mbar_arrive_if(lane == 0, odone0 - 8 + 8 * pc);
      }
    };

    for (;; pc++) {
      uint32_t op = prog[pc];
      const int type = op & 3;
      auto enter = [&]() {
        r.bi = (op >> 15) & 15; r.ph = (op >> 19) & 1; cur = ring16 + (((op >> 20) & 63) << 8);
      };
      enter();
      pend_any = op & C_PEND;
      uint32_t job = 0;
      if ((op & (3 | C_WIDE)) == OP_O) job = __shfl_sync(0xffffffffu, wait_word(jobw, 1), 0);
      if (type == OP_END || job == OP_O) {
#pragma unroll 1
        for (int c = 0; c < 6; c++) drain(c);
        asm volatile("barrier.cluster.arrive.relaxed;" ::: "memory");
        break;
      }
      {
        float s[32], o[96];
        uint32_t ad0;
        int bi0, sk1;
        uint32_t pa[16], pb[16];
        float mc0, mc1, l0, l1;
        bool shifted;
        uint32_t nop;
        auto expo = [&](float (&s)[32], uint32_t (&pout)[16], float& b0, float& b1, bool shift, auto mid) {
          float c0, c1;
#pragma unroll
          for (int i = 0; i < 8; i++) {
            const float e0 = ex2(shift ? s[4 * i] - mc0 : s[4 * i]), e1 = ex2(shift ? s[4 * i + 1] - mc0 : s[4 * i + 1]);
            const float e2 = ex2(shift ? s[4 * i + 2] - mc1 : s[4 * i + 2]), e3 = ex2(shift ? s[4 * i + 3] - mc1 : s[4 * i + 3]);
            if (i) { b0 += e0; c0 += e1; b1 += e2; c1 += e3; } else { b0 = e0; c0 = e1; b1 = e2; c1 = e3; }
            pout[2 * i] = pack_bf16(e0, e1); pout[2 * i + 1] = pack_bf16(e2, e3);
            if (i & 1) mid(i >> 1);
          }
          b0 += c0; b1 += c1;
        };
        auto rowmax = [&](float (&s)[32], float& m0, float& m1) {
          m0 = fmaxf(s[0], s[1]); m1 = fmaxf(s[2], s[3]);
#pragma unroll
          for (int i = 1; i < 8; i++) { m0 = fmaxf(m0, fmaxf(s[4 * i], s[4 * i + 1])); m1 = fmaxf(m1, fmaxf(s[4 * i + 2], s[4 * i + 3])); }
          m0 = fmaxf(m0, __shfl_xor_sync(0xffffffffu, m0, 1)); m1 = fmaxf(m1, __shfl_xor_sync(0xffffffffu, m1, 1));
          m0 = fmaxf(m0, __shfl_xor_sync(0xffffffffu, m0, 2)); m1 = fmaxf(m1, __shfl_xor_sync(0xffffffffu, m1, 2));
        };
        auto first = [&](float (&s)[32], int sk0, auto mid) {
          fence_regs(s);
          release(sk0);
          mc0 = 0.f; mc1 = 0.f;
          expo(s, pa, l0, l1, false, mid);
          shifted = __any_sync(0xffffffffu, !(fmaxf(l0, l1) <= kSumLimit && fminf(l0, l1) >= 1.f / kSumLimit));
          if (shifted) {
            rowmax(s, mc0, mc1);
            expo(s, pa, l0, l1, true, [](int) {});
          }
        };
        auto qk = [&](float (&s)[32], uint32_t ak, int k0 = 0, int k1 = 12) {
#pragma unroll
          for (int kk = k0; kk < k1; kk++)
            wgmma_rs_n64<0>(s, q[4 * kk], q[4 * kk + 1], q[4 * kk + 2], q[4 * kk + 3], mk_desc(ak, 16, KV_SBO, 1) + ((kk >> 2) * KV_CH + (kk & 3) * 2), kk != 0);
          if (k1 == 12) wg_commit();
        };
        auto pv = [&](uint32_t (&pin)[16], uint32_t av, int acc) {
#pragma unroll
          for (int kk = 0; kk < 4; kk++)
            wgmma_rs_n192<1>(o, pin[4 * kk], pin[4 * kk + 1], pin[4 * kk + 2], pin[4 * kk + 3], mk_desc(av, KV_CH * 16, KV_SBO, 1) + (kk * (KV_SBO / 8)), acc || (kk != 0));
          wg_commit();
        };
        auto finish = [&](uint32_t (&pout)[16], int sk, int sv) {
          probe2();
          wg_wait<1>();
          fence_regs(s);
          release(sk);
          float b0, b1;
#pragma unroll 1
          for (bool redo = false;; redo = true) {
            expo(s, pout, b0, b1, false, [](int) {});
            if (!__any_sync(0xffffffffu, !redo && (shifted || !(fmaxf(b0, b1) <= kSumLimit)))) break;
            shifted = true;
            rowmax(s, b0, b1);
            b0 = fmaxf(mc0, b0); b1 = fmaxf(mc1, b1);
            const float a0 = ex2(mc0 - b0), a1 = ex2(mc1 - b1);
            mc0 = b0; mc1 = b1;
            l0 *= a0; l1 *= a1;
            wg_wait<0>();
            fence_regs(o);
#pragma unroll
            for (int i = 0; i < 24; i++) { o[4 * i] *= a0; o[4 * i + 1] *= a0; o[4 * i + 2] *= a1; o[4 * i + 3] *= a1; }
#pragma unroll
            for (int i = 0; i < 32; i++) s[i] -= (i & 2) ? mc1 : mc0;
          }
          l0 += b0; l1 += b1;
          wg_wait<0>();
          fence_regs(o);
          release(sv);
        };
        auto step = [&](uint32_t (&pin)[16], uint32_t (&pout)[16]) {
          uint32_t ak, av;
          const int sk = take(rdy0, SZ_KV, ak), sv = take(rdy1, SZ_KV, av);
          wg_fence();
          qk(s, ak);
          pv(pin, av, 1);
          finish(pout, sk, sv);
        };
        auto unpark = [&]() {
          uint32_t ad, ak;
          const int bi = take(rdy0, SZ_PARK, ad);
#pragma unroll
          for (int i = 0; i < 12; i++) lds128(sbase + (ad - ring16 + img0) * 16 + (i >> 1) * 8192 + (i & 1) * 512, q[4 * i], q[4 * i + 1], q[4 * i + 2], q[4 * i + 3]);
          const int sk0 = take(false, SZ_KV, ak);
          fence_regs(q);
          release_warp(bi);
          wg_fence();
          qk(s, ak);
          probe2();
          return sk0;
        };
        auto mma4 = [&](uint32_t ad, int acc) {
#pragma unroll
          for (int kk = 0; kk < 4; kk++)
            wgmma_ss_n192<1>(o, mk_desc(ad + wg * 512, 16, 1024, 1) + (kk * 2), mk_desc(ad, 8192, 1024, 1) + (1024 + kk * 128), acc || kk != 0);
        };
        auto convert = [&](int i0, int i1) {
          sched_fence(keep, never);
#pragma unroll
          for (int i = i0; i < i1; i++) {
            q[i] = pack_bf16(o[2 * i] * kScaleLog2, o[2 * i + 1] * kScaleLog2);
            if ((i & 7) == 7 && i != i1 - 1) sched_fence(keep, never);
          }
          sched_fence(keep, never);
        };
        auto kend = [&](int bi, int k) {
          wg_commit();
          drain(k < 8 ? (0x54732710u >> (4 * k)) & 7 : 7);
          probe1();
          wg_wait<0>();
          release(bi);
        };
        if (type == OP_O) {
          int prev = 0;
          if (op & C_WIDE) {
            float d[64];
            auto mma3 = [&](uint32_t ad, int h, int acc) {
#pragma unroll
              for (int kk = 0; kk < 2; kk++)
                wgmma_ss_n192<1>(o, mk_desc(ad + wg * 256, 16, 512, 2) + (h * 512 + kk * 2), mk_desc(ad, 4096, 1024, 1) + (1024 + h * 768 + kk * 128), acc || kk);
            };
            auto mma2 = [&](uint32_t ad, uint32_t ob, int h, int acc) {
#pragma unroll
              for (int kk = 0; kk < 2; kk++)
                wgmma_ss_n128<1>(d, mk_desc(ad + wg * 256, 16, 512, 2) + (h * 512 + kk * 2), mk_desc(ad, 4096, 1024, 1) + (ob + h * 512 + kk * 128), acc || kk);
            };
            auto wstep = [&](uint32_t bytes, int acc, auto hook) {
              uint32_t ad;
              const int bi = take(rdy0, bytes, ad);
              wg_fence();
              if (bytes == SZ_W2) mma2(ad, 1024, 0, 1); else mma3(ad, 0, acc);
              if (bytes == SZ_W) mma3(ad, 1, 1);
              wg_commit();
              if (acc) { wg_wait<1>(); release(prev); }
              if (bytes == SZ_W) mma2(ad, 2560, 0, acc);
              if (bytes == SZ_W3) mma3(ad, 1, 1); else mma2(ad, bytes == SZ_W ? 2560 : 1024, 1, 1);
              wg_commit();
              prev = bi;
              hook();
              probe1();
              wg_wait<1>();
            };
            undefine(o);
            wstep(SZ_W, 0, [&]() { drain(0); });
#pragma unroll 1
            for (int k = 1; k < ((op >> 2) & 127) - TAIL; k++) wstep(SZ_W, 1, [&]() { drain(k); });
#pragma unroll 1
            for (int k = 0; k < TAIL; k++) wstep(SZ_W2, 1, []() {});
            pend = ptr_add(P.g->part, (((op >> 9) & 31) * 2 + rank) * 81920 + 4 * 8192 + img0 * 16);
            wstep(SZ_W3, 1, [&]() {
              fence_regs(d);
#pragma unroll
              for (int i = 0; i < 32; i++) q[16 + i] = pack_bf16(d[2 * i], d[2 * i + 1]);
              slab(2, 2);
            });
#pragma unroll 1
            for (int k = 3; k < 6; k++) wstep(SZ_W3, 1, [&]() { slab(k, 2); });
            op = prog[pc + 1];
            enter();
            pend_any = true;
            pend -= 4 * 512;
            bi0 = take(rdy0 || (op & 3) != OP_Q, SZ_Q, ad0);
            sched_fence(keep, never);
            wg_wait<0>();
            fence_regs(o);
            release(prev);
#pragma unroll
            for (int i = 0; i < 48; i++) q[i] = pack_bf16(o[2 * i], o[2 * i + 1]);
            if ((op & 3) != OP_Q) continue;
            pc++;
            goto first_step;
          }
          float c[80];
          auto mma2 = [&](uint32_t ad, uint32_t oa, uint32_t ob, int acc) {
            wgmma_ss_n160<1>(c, mk_desc(ad + wg * 256, 16, 512, 2) + (oa), mk_desc(ad, 2048, 512, 2) + (1024 + ob), acc);
            wgmma_ss_n160<1>(c, mk_desc(ad + wg * 256, 16, 512, 2) + (oa + 2), mk_desc(ad, 2048, 512, 2) + (1024 + ob + 64), 1);
          };
          auto kstep = [&](int acc, auto hook, uint32_t bytes = SZ_O) {
            uint32_t ad;
            const int bi = take(rdy0, bytes, ad);
            wg_fence();
            mma2(ad, 0, 0, acc);
            wg_commit();
            if (acc) wg_wait<1>();
            if (acc == 1) release(prev);
            if (acc > 1) release_warp(prev, acc == 2 || wg == 0);
            mma2(ad, 512, 640, 1);
            wg_commit();
            prev = bi;
            hook();
            probe1();
            wg_wait<1>();
          };
          auto unblock = [&](int k) {
            if (__all_sync(0xffffffffu, rdy0) || __all_sync(0xffffffffu, mbar_try(full0 + 8 * r.bi, r.ph, 1500))) return;
#pragma unroll 1
            for (; k < 6; k++) drain(k);
            pend_any = false;
          };
          unblock(0);
          kstep(0, [&]() { drain(0); });
          int left = ((job >> 13) & 127) - 6;
#pragma unroll 1
          for (uint32_t k = 1, pace = left >= 29 ? 0x4511 : left <= 17 ? 0x1a : 0x155; left > 0; pace >>= 2, left--) {
            unblock(k);
            kstep(1, [&]() {
#pragma unroll 1
              for (int i = pace & 3; i > 0; i--) drain(k++);
            });
          }
          uint32_t t[8], stage[3];
          float u[80];
          auto unpack = [&](int j) {
#pragma unroll
            for (int i = 0; i < 8; i++) {
              u[16 * j + 2 * i] = __uint_as_float(t[i] << 16); u[16 * j + 2 * i + 1] = __uint_as_float(t[i] & 0xffff0000u);
              asm volatile("" : "+f"(u[16 * j + 2 * i]), "+f"(u[16 * j + 2 * i + 1]));
            }
          };
#pragma unroll
          for (int i = 0; i < 8; i++) t[i] = 0;
          const uint32_t bytes = (job & P_LD) ? SZ_OL : SZ_O;
#pragma unroll
          for (int j = 0; j < 5; j++) {
            if (j == 2 && wg == 1) {
              wg_wait<0>();
              release_warp(prev);
              bar_sync(1, 256);
            }
            kstep(j == 2 ? 3 : 2, [&]() {
              if (j == 4) asm volatile("{\n.reg .pred p;\nsetp.eq.u32 p, %0, 0;\n@p bar.arrive 1, 256;\n}\n" ::"r"(wg) : "memory");
              if (j) unpack(j - 1);
              lds2_if(job & P_LD, sbase + (cur - ring16 + img0) * 16 - 8192, t);
              if (j >= 1 && j <= 3) stage[j - 1] = sbase + (cur - ring16) * 16 - bytes + wid * 1024;
            }, bytes);
          }
          unpack(4);
          sched_fence(keep, never);
          wg_wait<0>();
          fence_regs(c);
          release_warp(prev);
          asm volatile("barrier.cluster.arrive.relaxed;" ::: "memory");
#pragma unroll
          for (int i = 0; i < 10; i++) {
            const int v = (i & 1) * 2 + (lane >> 4);
            const uint32_t sa = stage[i >> 2] + (i & 2) * 4096;
            stsm4(sa + (lane & 15) * 64 + ((v ^ ((lane >> 1) & 3)) << 4), pack_bf16(c[8 * i] + u[8 * i], c[8 * i + 1] + u[8 * i + 1]),
                  pack_bf16(c[8 * i + 2] + u[8 * i + 2], c[8 * i + 3] + u[8 * i + 3]), pack_bf16(c[8 * i + 4] + u[8 * i + 4], c[8 * i + 5] + u[8 * i + 5]),
                  pack_bf16(c[8 * i + 6] + u[8 * i + 6], c[8 * i + 7] + u[8 * i + 7]));
          }
          asm volatile("fence.proxy.async.shared::cta;" ::: "memory");
          __syncwarp();
          if (elect()) {
#pragma unroll
            for (int i = 0; i < 5; i++)
              tma3d_store(&P.out, stage[i >> 1] + (i & 1) * 8192, 0, ((job >> 7) & 7) * kSq + rank * 128 + wid * 16, ((job >> 10) & 1) * 20 + ((job >> 20) & 3) * 5 + i);
            asm volatile("cp.async.bulk.commit_group;\ncp.async.bulk.wait_group.read 0;" ::: "memory");
          }
          __syncwarp();
          break;
        }
        bi0 = take(rdy0, SZ_Q, ad0);
      first_step:
        undefine(o);
        wg_fence();
        mma4(ad0, 0);
        kend(bi0, 0);
        fence_regs(o);
      next_head:
        {
#pragma unroll 1
          for (int k = 1; k < ((op & F_PARK) ? 10 : 8); k++) {
            uint32_t ad;
            const int bi = take(rdy0, SZ_Q, ad);
            wg_fence();
            mma4(ad, 1);
            kend(bi, k);
          }
          if (op & F_PARK) {
            fence_regs(o);
            convert(0, 48);
            pend = ptr_add(P.g->tile, (((op >> 2) & 511) * 2 + rank) * SZ_PARK + img0 * 16);
            continue;
          }
          uint32_t a8, a9, ak0, ak1;
          const int b8 = take(rdy0, SZ_Q, a8), b9 = take(false, SZ_Q, a9);
          wg_fence();
          mma4(a8, 1);
          wg_commit();
          mma4(a9, 1);
          wg_commit();
          pc++;
          wg_wait<1>();
          release(b8);
          const int sk0 = take(false, SZ_KV, ak0);
          wg_wait<0>();
          fence_regs(o);
          release(b9);
          float s0[32];
          convert(0, 32);
          wg_fence();
          qk(s0, ak0, 0, 4);
          convert(32, 48);
          wg_fence();
          qk(s0, ak0, 4, 12);
          sk1 = take(false, SZ_KV, ak1);
          probe1();
          wg_wait<0>();
          first(s0, sk0, [&](int i) {
            if (i == 0) return;
            sched_fence(keep, never);
            wg_fence();
            if (i == 1) qk(s, ak1, 0, 4);
            if (i == 2) qk(s, ak1, 4, 8);
            if (i == 3) qk(s, ak1, 8, 12);
            sched_fence(keep, never);
          });
        }
        for (;;) {
          {
            uint32_t av;
            const int sv = take(rdy0, SZ_KV, av);
            undefine(o);
            wg_fence();
            pv(pa, av, 0);
            finish(pb, sk1, sv);
          }
          nop = prog[pc + 1];
#pragma unroll 1
          for (int jj = 0; jj < 7; jj++) {
            step(pb, pa);
            step(pa, pb);
          }
          float i0, i1;
          auto last = [&]() {
            uint32_t av;
            const int sv = take(rdy0, SZ_KV, av);
            wg_fence();
            pv(pb, av, 1);
            sched_fence(keep, never);
            probe1();
            l0 += __shfl_xor_sync(0xffffffffu, l0, 1); l1 += __shfl_xor_sync(0xffffffffu, l1, 1);
            l0 += __shfl_xor_sync(0xffffffffu, l0, 2); l1 += __shfl_xor_sync(0xffffffffu, l1, 2);
            i0 = rcp(l0); i1 = rcp(l1);
            pend = ptr_add(P.g->tile, (((op >> 2) & 511) * 2 + rank) * SZ_PARK + img0 * 16);
            return sv;
          };
          auto normalise = [&](uint32_t (&d)[48], auto mid) {
#pragma unroll
            for (int i = 0; i < 24; i++) {
              d[8 * (i >> 2) + (i & 3)] = pack_bf16(o[4 * i] * i0, o[4 * i + 1] * i0);
              d[8 * (i >> 2) + (i & 3) + 4] = pack_bf16(o[4 * i + 2] * i1, o[4 * i + 3] * i1);
              if ((i & 1) && i != 23) sched_fence(keep, never);
              if ((i & 3) == 3 && i != 23) mid(i >> 2);
            }
          };
          const int sv = last();
          if ((nop & 3) != OP_A) {
            op = nop;
            enter();
            pend_any = true;
            bi0 = take(rdy0 || (nop & 3) != OP_Q, SZ_Q, ad0);
            sched_fence(keep, never);
            wg_wait<0>();
            fence_regs(o);
            release(sv);
            normalise(q, [](int) {});
            undefine(o);
            if ((nop & 3) != OP_Q) break;
            sched_fence(keep, never);
            wg_fence();
            mma4(ad0, 0);
            pc++;
            kend(bi0, 0);
            fence_regs(o);
            goto next_head;
          }
          const int sk0 = unpark();
          wg_wait<1>();
          fence_regs(o);
          release(sv);
          uint32_t t[48];
          auto st = [&](int i) {
            stg2_if(true, pend + i * 512, t[8 * i], t[8 * i + 1], t[8 * i + 2], t[8 * i + 3], t[8 * i + 4], t[8 * i + 5], t[8 * i + 6], t[8 * i + 7], spol);
          };
          normalise(t, [&](int i) { if (!(i & 1)) st(i >> 1); });
          wg_wait<0>();
          first(s, sk0, [&](int i) { if (i < 3) { sched_fence(keep, never); st(3 + i); } });
          __syncwarp();
          mbar_arrive_if(lane == 0, odone0 + 8 * pc);
          pc++;
          op = nop;
          uint32_t ak1;
          sk1 = take(rdy0, SZ_KV, ak1);
          rdy0 = rdy1;
          wg_fence();
          qk(s, ak1);
        }
      }
    }
    asm volatile("barrier.cluster.wait;" ::: "memory");
  } else {
    asm volatile("setmaxnreg.dec.sync.aligned.u32 24;");
    const uint32_t* prog = P.prog[role].p;
    unsigned int* flag = P.g->flag + rank;
    if (wid == 8) {
      Cursor tail{0, 0};
      int head = 0, sh = 0;
      uint32_t cur = 0, used = 0;
      uint64_t fifo = 0;
      uint32_t dst, bar, ev = ev0, done = 0;
      const uint64_t pol = evict_first();
      auto retire = [&]() {
        mbar_wait(empty0 + 8 * tail.bi, tail.ph);
        tail.next();
        used -= (uint32_t)fifo & 31;
        fifo >>= 5;
        sh -= 5;
        asm volatile("st.volatile.shared.u32 [%0], %1;" ::"r"(progress), "r"(++done) : "memory");
      };
      auto acquire = [&](uint32_t bytes) {
        uint32_t fp = bytes >> 12;
        if (cur + fp > (RING >> 12)) { fp += (RING >> 12) - cur; cur = 0; }
        used += fp;
        while (used > (RING >> 12) || sh == 5 * NBAR) retire();
        fifo |= (uint64_t)fp << sh;
        sh += 5;
        dst = sbase + (cur << 12);
        bar = full0 + 8 * head;
        cur += bytes >> 12;
        if (++head == NBAR) head = 0;
      };
      auto gate = [&]() {
        mbar_wait(ev, 0);
        ev += 8;
        asm volatile("fence.proxy.async.global;" ::: "memory");
      };
      for (int pc = 0;; pc++) {
        uint32_t op = prog[pc];
        const int type = op & 3;
        if (type == OP_END) break;
        if (op == OP_O) {
          gate();
          op = __shfl_sync(0xffffffffu, lds32(jobw), 0);
        }
        const int blk = (op >> 10) & 1;
        if (type == OP_Q) {
#pragma unroll 1
          for (int k = 0; k < 10; k++) {
            if (k == 9 && (op & P_GATE)) gate();
            acquire(SZ_Q);
            if ((pc > 0 || k >= EARLY) && elect()) {
              mbar_expect(bar, SZ_Q);
              tma2d(dst, &P.x[blk], bar, 64 * k, ((op >> 7) & 7) * kSq + rank * 128);
              if ((k & 1) == rank) tma3d_mc(dst + 16384, &P.wq[blk], bar, 0, 64 * k, 3 * ((op >> 2) & 31));
            }
          }
        } else if (type == OP_A) {
          const int row0 = ((op >> 2) & 255) * kSk;
          const CUtensorMap* kv_map = rank ? &P.v[blk] : &P.k[blk];
          if (op & F_PARK) {
            gate();
            acquire(SZ_PARK);
            if (elect()) {
              mbar_expect(bar, SZ_PARK);
              bulk_load_hint(dst, &P.g->tile[((op >> 20) * 2 + rank) * 3072], SZ_PARK, bar, pol);
            }
          }
#pragma unroll 1
          for (int t = 0; t < 32; t++) {
            const int isv = t == 31 ? 1 : (t == 0 ? 0 : (~t & 1));
            const int j = isv ? (t - 1) >> 1 : (t + 1) >> 1;
            if (t == 31 && (op & P_GATE)) gate();
            acquire(SZ_KV);
            if (elect()) {
              mbar_expect(bar, SZ_KV);
              if (isv == (int)rank) tma4d_mc_hint(dst, kv_map, bar, row0 / 8 + 8 * j, pol);
            }
          }
        } else {
          const int n = (op >> 13) & 127, nw = (op & P_WIDE) ? n - TAIL : 0;
          const uint4* part = &P.g->part[((((op >> 6) & 30) + ((op >> 21) & 1)) * 2 + rank) * 5120 + ((op >> 20) & 1) * 2560];
#pragma unroll 1
          for (int i = 0; i < n + (nw ? TAIL : 0); i++) {
            const int k = nw ? (i < n ? i : i - TAIL) : kSteps - n + i, h = (k * 43) >> 7, col = 5 * ((op >> 20) & 3);
            const uint4* src = &P.g->tile[(P.slot[((op >> 2) & 480) + h] * 2 + rank) * 3072 + (k - 3 * h) * 1024];
            const uint32_t j = (op & P_LD) ? i - n + 5 : 5, bytes = i < nw ? SZ_W : nw ? (i < n ? SZ_W2 : SZ_W3) : j < 5 ? SZ_OL : SZ_O;
            if ((op & P_PRE) ? i == 0 : j == 0) gate();
            if (i < n && (i == 0 || k == 3 * h)) gate();
            acquire(bytes);
            if (elect()) {
              mbar_expect(bar, bytes);
              if (bytes != SZ_W2) tma5d_mc(dst + 16384 + rank * (nw ? 12288 : 10240), nw ? &P.wo3[blk] : &P.wo[blk], bar, 8 * k + 4 * rank, nw ? col / 2 : col);
              bulk_load_hint(dst, src, 16384, bar, pol);
              if (nw && i < n) tma5d_mc(dst + bytes - 16384 + rank * 8192, &P.wo2[blk], bar, 8 * k + 4 * rank, col / 2 + 3);
              if (j < 5) bulk_load_hint(dst + SZ_O, part + j * 512, 8192, bar, pol);
              if ((op & P_PRE) && i < 10) asm volatile("cp.async.bulk.prefetch.L2.global [%0], 4096;" ::"l"(part + i * 256) : "memory");
            }
          }
        }
      }
#pragma unroll 1
      while (sh) retire();
    } else if (threadIdx.x == 288) {
      for (int pc = 0;; pc++) {
        const uint32_t op = prog[pc];
        const int type = op & 3;
        if (type == OP_END) break;
        if (type == OP_Q ? !(op & F_PARK) : type == OP_O && !(op & P_WIDE)) continue;
        const int id = type == OP_A ? (op >> 2) & 511 : type == OP_Q ? N_TILE + ((op >> 13) & 127) : ID_PART + ((op >> 5) & 60) + ((op >> 20) & 3);
        const uint32_t v = type == OP_O ? 1 : P.info[id] & 7;
        mbar_wait_long(odone0 + 8 * pc);
        flag_set(flag + 2 * id, v);
        if (type == OP_O && (op & P_WIDE)) flag_set(flag + 2 * id + 2, v);
      }
    } else if (wid == 10) {
      int i = threadIdx.x & 31;
      const int n_ev = P.prog[role].n_ev;
      auto event = [&]() { return i < n_ev ? P.prog[role].ev[i] : n_ev ? E_JOB | (i - n_ev) : 0; };
      uint32_t e = i < 8 ? event() : 0;
      for (uint32_t n = 0; __any_sync(0xffffffffu, e); n++) {
        uint32_t job = lds32(jobw);
        const int togo = (e & E_DRAW) ? (e & 1023) - lds32(progress) : 99;
        if (togo <= 0 && rank == 0) {
          job = P.job[atomicInc(&P.g->ticket, gridDim.x / 2 - 1)];
          asm volatile("{\n.reg .u32 a;\nmapa.shared::cluster.u32 a, %0, 1;\nst.volatile.shared::cluster.u32 [a], %1;\n"
                       "st.volatile.shared.u32 [%0], %1;\n}\n" ::"r"(jobw), "r"(job) : "memory");
        }
        if ((e & E_JOB) && job) {
          const uint32_t j = e & 63, heads = job == OP_O ? 0 : kH - ((job >> 2) & 31), jp = !(job & P_LD) ? 63 : (job & P_PRE) ? 0 : heads - 1, h = j - (j > jp);
          e = j == jp ? (ID_PART + ((job >> 5) & 60) + ((job >> 20) & 3)) | E_ON | E_LAST : h < heads ? (((job >> 2) & 511) + h) | E_ON | E_LAST : 0;
        }
        unsigned int* f = ptr_add(flag, 8 * (e & 1023));
        const bool ok = (e & E_ON) ? flag_get(f) - 1 < ((e & E_FREE) ? 1 : 7) : (e & E_DRAW) && job;
        if (ok) {
          mbar_arrive(ev0 + 8 * i);
          if (e & (E_FREE | E_LAST)) flag_dec(f);
          i += 8;
          e = event();
        }
        asm volatile("{\n.reg .pred p;\nsetp.ge.u32 p, %0, 0x400000;\n@p trap;\n}\n" ::"r"(n));
        if (!__any_sync(0xffffffffu, ok)) __nanosleep(__any_sync(0xffffffffu, job || togo <= 2) ? 100 : 600);
      }
    } else if (threadIdx.x == 352) {
      uint32_t items = 0;
      auto read = [&](int id) {
        if (!(P.info[id] & I_NEXT)) return;
        wait_word(progress, items);
        flag_dec(flag + 2 * id);
      };
      for (int pc = 0;; pc++) {
        const uint32_t op = prog[pc];
        const int type = op & 3;
        if (type == OP_END) break;
        if (type == OP_O) {
          const uint32_t n = (op >> 13) & 127, base = items;
#pragma unroll 1
          for (uint32_t k = 3, id = (op >> 2) & 511; k <= n; k += 3, id++) {
            items = base + k + (k + TAIL > n ? TAIL : 0);
            read(id);
          }
          items = base + n + TAIL;
        } else if (type == OP_A) {
          if (op & F_PARK) { items++; read(N_TILE + ((op >> 13) & 127)); }
          items += 32;
        } else {
          items += 10;
        }
      }
    }
    __syncwarp();
    asm volatile("barrier.cluster.arrive.relaxed;\nbarrier.cluster.wait;" ::: "memory");
  }
}

typedef CUresult (*EncodeFn)(CUtensorMap*, CUtensorMapDataType, cuuint32_t, void*, const cuuint64_t*, const cuuint64_t*,
                             const cuuint32_t*, const cuuint32_t*, CUtensorMapInterleave, CUtensorMapSwizzle,
                             CUtensorMapL2promotion, CUtensorMapFloatOOBfill);

void encode(EncodeFn fn, CUtensorMap* m, const void* ptr, int rank, const cuuint64_t* dims, const cuuint64_t* strides,
            const cuuint32_t* box, CUtensorMapSwizzle swz) {
  const cuuint32_t es[5] = {1, 1, 1, 1, 1};
  CUresult r = fn(m, CU_TENSOR_MAP_DATA_TYPE_BFLOAT16, rank, const_cast<void*>(ptr), dims, strides, box, es,
                  CU_TENSOR_MAP_INTERLEAVE_NONE, swz, CU_TENSOR_MAP_L2_PROMOTION_L2_128B, CU_TENSOR_MAP_FLOAT_OOB_FILL_NONE);
  if (r != CUDA_SUCCESS) fprintf(stderr, "cuTensorMapEncodeTiled failed: %d\n", (int)r);
}

struct Op { int type, flags, id, n, quarter, park, item0, items; double t0, t1; };
struct Use { double ready, gate, need, freed; int readers, slot, prev; bool next; };
struct PlanStats { double end, slack, park_slack; int slots, parks; uint32_t own[N_CL]; };

bool plan(const char* const* text, int n_pair, int phase, Params& P, PlanStats* stats = nullptr) {
  constexpr double T_Q = 7900, T_A = 24800, T_U = TU, T_O = 640, T_RUN = 800, T_WIDE = TW, AHEAD = 3500, PUBLISH = 1500;
  const double margin = 256.0 * ((P.dbg >> 8) & 255);
  static Op op[N_CL][MAX_OPS];
  static Use use[ID_PART];
  int n_op[N_CL], covered[2 * N_TEAM] = {};
  struct Ref { double t; Op* o; int id; };
  static Ref att[N_TILE + 1], dem[N_TILE], prk[MAX_PARK + 1], unp[MAX_PARK + 1], wr[ID_PART];
  auto sort = [](Ref* r, int n) {
    for (int i = 1; i < n; i++)
      for (int j = i; j > 0 && r[j].t < r[j - 1].t; j--) { Ref x = r[j]; r[j] = r[j - 1]; r[j - 1] = x; }
  };
  auto hex = [](char c) { return c <= '9' ? c - '0' : c - 'a' + 10; };
  for (int i = 0; i < n_pair; i++)
    for (const char* s = text[i]; *s; s++)
      for (int h = 0; *s == 'J' && h < 2; h++) {
        if (covered[2 * hex(s[1]) + h]) return false;
        covered[2 * hex(s[1]) + h] = 10 * (s[2 + 2 * h] - '0') + s[3 + 2 * h] - '0';
      }
  for (int c = 0; c < 2 * n_pair; c++) {
    int n = 0, items = 0;
    double t = 0;
    auto add = [&](int type, int flags, int id, int heads, int quarter, int its, double dt) {
      if (n < MAX_OPS) op[c][n] = {type, flags, id, heads, quarter, 0, items, its, t, t + dt};
      n++; items += its; t += dt;
    };
    for (const char* s = text[c >> 1]; *s; s++) {
      const int tm = hex(s[1]) & 15, nj = covered[2 * tm + (c & 1)];
      if (*s == 'N') { add(OP_Q, 0, 0, 0, 0, 10, T_Q); add(OP_A, 0, 0, 0, 0, 32, T_A); }
      if (*s == 'P') add(OP_Q, F_PARK, 0, 0, 0, 10, T_Q + TP);
      if (*s == '+' || *s == '-') t += *s == '+' ? 1000 : -1000;
      if (*s == 'U') { if (n == 0 || n > MAX_OPS || op[c][n - 1].type != OP_A) return false; add(OP_A, F_PARK, 0, 0, 0, 33, T_U); }
      if (*s == 'J') { if (nj < TAIL + 6 || nj > kSteps - 11) return false; add(OP_O, P_WIDE, tm * kH, nj, 2 * (c & 1), nj + TAIL, 2 * T_O * nj + T_WIDE); }
    }
    add(OP_O, 0, 0, 0, 0, 0, 0);
    add(OP_END, 0, 0, 0, 0, 0, 0);
    if (n > MAX_OPS || op[c][0].type != OP_Q) return false;
    n_op[c] = n - 1;
    att[c] = {t, &op[c][n - 2], 0};
  }
  for (int i = 0; i < 4 * N_TEAM; i++) dem[i] = {(double)covered[i / 2], nullptr, i};
  sort(att, 2 * n_pair); sort(dem, 4 * N_TEAM);
  for (int i = 0; i < 4 * N_TEAM; i++) {
    Op* f = att[i].o;
    const int nj = covered[dem[i].id / 2];
    f->flags = nj ? P_LD : 0;
    f->id = dem[i].id / 4 * kH + nj / 3; f->quarter = dem[i].id & 3; f->items = f->n = kSteps - nj;
    f[1].t0 = f[1].t1 = f->t1 = f->t0 + T_O * f->n + T_RUN; f[1].item0 += f->n;
  }
  for (int i = 0; i < ID_PART; i++) use[i] = {0, 0, 1e18, 0, 0, 0, 0, false};
  int n_att = 0, n_prk = 0, n_unp = 0;
  auto ready = [&](const Op* o) {
    const int nt = o[1].type;
    return o->t1 + (nt == OP_Q ? 6100 : o[1].n ? ((o[1].flags & P_WIDE) ? 7700 : 3900) : 1500) + PUBLISH;
  };
  for (int c = 0; c < 2 * n_pair; c++)
    for (Op* o = op[c]; o->type != OP_END; o++) {
      if (o->type == OP_A) { att[n_att] = {ready(o), o, 0}; if (++n_att > N_TILE) return false; }
      if (o->type == OP_A && o->flags) { unp[n_unp] = {o->t0 - AHEAD, o, 0}; if (++n_unp > MAX_PARK) return false; }
      if (o->type == OP_Q && o->flags) { prk[n_prk] = {ready(o), o, 0}; if (++n_prk > MAX_PARK) return false; }
      for (int i = 0; o->type == OP_O && i < o->n; i++) {
        const int nw = (o->flags & P_WIDE) ? o->n - TAIL : 0, k = nw ? i : kSteps - o->n + i;
        Use& u = use[o->id / kH * kH + k / 3];
        const double t = o->t0 + T_O * (i + (i < nw ? i : nw));
        if (t - AHEAD < u.need) u.need = t - AHEAD;
        const double f = !nw ? 1e18 : i + NBAR < o->items - TAIL || (nw && o[1].type != OP_O) ? t + T_O * (i < nw ? 2 : 1 + TAIL) + PUBLISH : 1e18;
        if (f > u.freed) u.freed = f;
        if (i == 0 || k % 3 == 0) u.readers++;
      }
    }
  if (n_att != N_TILE || n_prk != n_unp) return false;
  for (int i = 0; i < N_TILE; i++) { const int id = (i & 15) * kH + (i >> 4); dem[i] = {use[id].need, nullptr, id}; }
  sort(att, n_att); sort(dem, N_TILE); sort(prk, n_prk); sort(unp, n_unp);
  PlanStats st = {0, 1e18, 1e18, 0, n_prk};
  int n_wr = 0;
  for (int i = 0; i < N_TILE; i++) {
    Op* o = att[i].o;
    o->id = dem[i].id;
    if (!o->flags) o[-1].id = o->id;
    if (dem[i].t - att[i].t < st.slack) st.slack = dem[i].t - att[i].t;
    wr[n_wr++] = {o->t1 - 2 * AHEAD, o, o->id};
  }
  for (int i = 0; i < n_prk; i++) {
    prk[i].o->id = unp[i].o->id;
    prk[i].o->park = unp[i].o->park = i;
    use[N_TILE + i].freed = unp[i].o->t0 + 2 * PUBLISH;
    use[N_TILE + i].readers = 1;
    if (unp[i].t - prk[i].t < st.park_slack) st.park_slack = unp[i].t - prk[i].t;
    wr[n_wr++] = {prk[i].o->t1 - 2 * AHEAD, prk[i].o, N_TILE + i};
  }
  for (int c = 0; c < 2 * n_pair; c++)
    for (int d = 0; d < 2 * n_pair; d++)
      for (Op *f = &op[c][n_op[c] - 1], *o = op[d]; f->n && o->type != OP_END; o++)
        if (o->type == OP_O && (o->flags & P_WIDE) && o->id / kH == f->id / kH && o->quarter / 2 == f->quarter / 2) {
          if (f->t0 - o->t1 > 4096.0 * ((P.dbg >> 16) & 255)) f->flags |= P_PRE;
          const double slack = f->t0 + ((f->flags & P_PRE) ? 0 : (f->n - 5) * T_O) - AHEAD - ready(o);
          if (slack < st.park_slack) st.park_slack = slack;
        }
  sort(wr, n_wr);
  int holder[N_TILE];
  for (int i = 0; i < n_wr; i++) {
    int best = -1;
    for (int sl = 0; sl < st.slots; sl++)
      if (use[holder[sl]].freed + margin <= wr[i].t && (best < 0 || use[holder[sl]].freed < use[holder[best]].freed)) best = sl;
    Use& u = use[wr[i].id];
    if (best >= 0) { u.prev = holder[best]; use[u.prev].next = true; wr[i].o->flags |= P_GATE; }
    else if (st.slots == N_TILE) return false;
    else best = st.slots++;
    u.slot = best;
    holder[best] = wr[i].id;
  }
  {
    int pos[N_CL] = {}, flag[ID_PART + 4 * N_TEAM] = {}, seen[ID_PART] = {};
    auto goal = [&](int c) { return op[c][n_op[c] - 1].item0; };
    for (bool moved = true; moved;) {
      moved = false;
      for (int c = 0; c < 2 * n_pair; c++) {
        for (; pos[c] < goal(c); pos[c]++, moved = true) {
          bool ok = true;
          for (const Op* o = op[c]; o->type != OP_END; o++) {
            const int k = pos[c] - o->item0, own = o->type == OP_A ? o->id : N_TILE + o->park;
            if (k < 0 || k >= o->items) continue;
            if (o->type == OP_O) ok = k >= o->n || flag[o->id + k / 3];
            else if (k == o->items - 1 && (o->flags & P_GATE)) ok = seen[use[own].prev] == use[use[own].prev].readers;
            else if (k == 0 && o->type == OP_A && (o->flags & F_PARK)) ok = flag[N_TILE + o->park];
          }
          if (!ok) break;
          for (const Op* o = op[c]; o->type != OP_END; o++) {
            if (pos[c] == o->item0 + o->items + (o[1].type == OP_Q ? 7 : o[1].item0 == goal(c) ? -1 : 5)) {
              if (o->type == OP_A) flag[o->id] = 1;
              if (o->type == OP_Q && (o->flags & F_PARK)) flag[N_TILE + o->park] = 1;
              if (o->type == OP_O) flag[ID_PART + o->id / kH * 4 + o->quarter] = flag[ID_PART + o->id / kH * 4 + o->quarter + 1] = 1;
            }
            const int k = pos[c] - NBAR - o->item0, nw = o->n - TAIL;
            if (k == 0 && o->type == OP_A && (o->flags & F_PARK)) seen[N_TILE + o->park]++;
            if (o->type == OP_O && k >= 0 && k < o->items && (k < nw || k >= o->n) && (k < nw ? k : k - TAIL) % 3 == 2) seen[o->id + (k < nw ? k : k - TAIL) / 3]++;
          }
        }
      }
    }
    for (int c = 0; c < 2 * n_pair; c++) if (pos[c] < goal(c)) return false;
  }
  int n_job = 0;
  for (int c = 0; c < 2 * n_pair; c++) {
    uint32_t items = 0, cur = 0, pend = 0;
    int n = 0, ev = 0;
    auto item = [&](uint32_t bytes, int count) {
      for (int i = 0; i < count; i++) { if (cur + bytes > RING) cur = 0; cur += bytes; items++; }
    };
    auto event = [&](uint32_t e) { if (ev < MAX_TAB) P.prog[c].ev[ev] = e; ev++; };
    for (const Op* o = op[c];; o++) {
      if (o->type != OP_END && phase && (o->type == OP_O) != (phase == 2)) continue;
      uint32_t cw = o->type | (items % NBAR) << 15 | ((items / NBAR) & 1) << 19 | (cur >> 12) << 20 | pend, pw = o->type | o->id << 2 | o->flags;
      const int ps = use[N_TILE + o->park].slot;
      pend = 0;
      if (o->type == OP_O) {
        pw |= o->n << 13 | o->quarter << 20;
        if (o->flags & P_WIDE) {
          cw |= o->n << 2 | (o->id / kH * 2 + o->quarter / 2) << 9 | C_WIDE;
          item(SZ_W, o->n - TAIL);
          item(SZ_W2, TAIL);
          item(SZ_W3, TAIL);
          pend = C_PEND;
          for (int i = 0; 3 * i < o->n; i++) event((o->id + i) | E_ON | (use[o->id + i].next ? 0 : E_LAST));
        } else {
          dem[n_job++] = {o->t0 - 1e6 * o->n, nullptr, (int)pw};
          st.own[c] = pw;
          pw = OP_O;
          event(E_DRAW | (items < 16 ? 0 : items - 16));
        }
      } else if (o->type != OP_END) {
        const bool parks = o->type == OP_Q && (o->flags & F_PARK);
        cw |= (parks ? ps : use[o->id].slot) << 2 | (o->flags & F_PARK);
        if (o->flags & F_PARK) pw |= o->park << 13 | ps << 20;
        if (o->type == OP_Q) item(SZ_Q, 10);
        else { if (o->flags & F_PARK) { item(SZ_PARK, 1); event((N_TILE + o->park) | E_ON | (use[N_TILE + o->park].next ? 0 : E_LAST)); } item(SZ_KV, 32); }
        if (parks || o->type == OP_A) pend = C_PEND;
        if (o->flags & P_GATE) event(use[parks ? N_TILE + o->park : o->id].prev | E_ON | E_FREE);
      }
      P.prog[c].c[n] = cw; P.prog[c].p[n++] = pw;
      if (o->type == OP_END) { if (o->t0 > st.end) st.end = o->t0; break; }
    }
    if (ev > MAX_TAB) return false;
    P.prog[c].n_ev = ev;
    while (n < MAX_OPS) { P.prog[c].c[n] = OP_END; P.prog[c].p[n++] = OP_END; }
    P.first[c] = (uint16_t)(P.prog[c].p[0] & 2047);
  }
  sort(dem, n_job);
  for (int i = 0; i < n_job; i++) P.job[i] = dem[i].id;
  for (int i = 0; i < ID_PART; i++) {
    if (i < N_TILE) P.slot[i] = use[i].slot;
    P.info[i] = (use[i].readers + use[i].next) | (use[i].next ? I_NEXT : 0);
  }
  if (stats) *stats = st;
  return true;
}

const char* const kPrograms[N_CL / 2] = {
  "PNJ06565NNNNN", "PNJ15858NNNNN", "PNJ25656NNNNN", "PNJ35454+NNNNN", "PNJ47878NNNNN", "PNJ57373NNNNN",
  "NNJ68080NNNN", "NNJ76868NNNN", "NNNNNJ83535NN", "NNNNNNJf4343N", "NNNNNJa5252NN", "NNNNNJb4848NN",
  "NUNNNNNNN", "NUNNNJd5353NN", "NUNNNJe6363NN", "NNNNNJ97676N", "PNNNNNNNNN", "PNNNNNNNNN",
  "PNNNNNNNNN", "PNNNNNNNNN", "PNNNNNNNNN", "NNNNNNNNN", "NNNNNNNNN", "NNNNNNNNN",
  "NUNNNNNNN", "NNNNNNNNN", "NUNNNNNNN", "NUNNNNNNN", "NNUNNNNNN", "NUNNNNNNN",
  "NUNNNNNNN", "NNUNNJc5353NN", "NUNNNNNNN",
};

const char* const* bench_programs() {
  return kPrograms;
}

}

extern "C" void kernel_launch(void* const* d_in, const int* in_sizes, int n_in, void* d_out, int out_size) {
  (void)in_sizes; (void)n_in; (void)out_size;
  static EncodeFn fn = nullptr;
  static int n_clusters = 0;
  if (!fn) {
    cudaDriverEntryPointQueryResult qr;
    void* f = nullptr;
    cudaGetDriverEntryPoint("cuTensorMapEncodeTiled", &f, cudaEnableDefault, &qr);
    fn = (EncodeFn)f;
    cudaFuncSetAttribute(fused_kernel, cudaFuncAttributeMaxDynamicSharedMemorySize, SMEM_BYTES);
    cudaLaunchConfig_t cfg = {};
    cfg.gridDim = dim3(132); cfg.blockDim = dim3(384); cfg.dynamicSmemBytes = SMEM_BYTES;
    cudaLaunchAttribute at[1];
    at[0].id = cudaLaunchAttributeClusterDimension; at[0].val.clusterDim.x = 2; at[0].val.clusterDim.y = 1; at[0].val.clusterDim.z = 1;
    cfg.attrs = at; cfg.numAttrs = 1;
    if (cudaOccupancyMaxActiveClusters(&n_clusters, fused_kernel, &cfg) != cudaSuccess || n_clusters < 1) n_clusters = 1;
    (void)cudaGetLastError();
  }
  static Params P;
  const CUtensorMapSwizzle S128 = CU_TENSOR_MAP_SWIZZLE_128B, S64 = CU_TENSOR_MAP_SWIZZLE_64B;
  for (int blk = 0; blk < 2; blk++) {
    void* const* in = d_in + 5 * blk;
    { const cuuint64_t d[] = {kD, kB * kSq}, s[] = {kD * 2}; const cuuint32_t b[] = {64, 128};
      encode(fn, &P.x[blk], in[0], 2, d, s, b, S128); }
    { const cuuint64_t d[] = {64, 8, 3, (cuuint64_t)kB * kH * kSk / 8}, s[] = {kDh * 2, 128, 8 * kDh * 2}; const cuuint32_t b[] = {64, 8, 3, 8};
      encode(fn, &P.k[blk], in[1], 4, d, s, b, S128);
      encode(fn, &P.v[blk], in[2], 4, d, s, b, S128); }
    { const cuuint64_t d[] = {64, kD, kHD / 64}, s[] = {kHD * 2, 128}; const cuuint32_t b[] = {64, 64, 3};
      encode(fn, &P.wq[blk], in[3], 3, d, s, b, S128); }
    { const cuuint64_t d[] = {32, 2, kHD / 8, 4, kD / 32}, s[] = {kD * 2, 8 * kD * 2, 2 * kD * 2, 64}; const cuuint32_t b[] = {32, 2, 4, 4, 5};
      encode(fn, &P.wo[blk], in[4], 5, d, s, b, S64); }
    { const cuuint64_t d[] = {64, 2, kHD / 8, 4, kD / 64}, s[] = {kD * 2, 8 * kD * 2, 2 * kD * 2, 128};
      const cuuint32_t b3[] = {64, 2, 4, 4, 3}, b2[] = {64, 2, 4, 4, 2};
      encode(fn, &P.wo3[blk], in[4], 5, d, s, b3, S128);
      encode(fn, &P.wo2[blk], in[4], 5, d, s, b2, S128); }
  }
  { const cuuint64_t d[] = {32, kB * kSq, 2 * kD / 32}, s[] = {2 * kD * 2, 64}; const cuuint32_t b[] = {32, 16, 1};
    encode(fn, &P.out, d_out, 3, d, s, b, S64); }

  P.xw[0] = (const char*)d_in[0]; P.xw[1] = (const char*)d_in[3];
  cudaGetSymbolAddress((void**)&P.g, g_scratch);
  P.dbg = DBG_DEFAULT;
  if (n_clusters >= N_CL && plan(bench_programs(), N_CL / 2, 0, P)) {
    fused_kernel<<<2 * N_CL, 384, SMEM_BYTES>>>(P);
  } else {
    const char* text[2 * N_TEAM];
    for (int i = 0; i < 2 * N_TEAM; i++) text[i] = "NNNNNNNN";
    for (int phase = 1; phase <= 2; phase++) {
      plan(text, 2 * N_TEAM, phase, P);
      fused_kernel<<<8 * N_TEAM, 384, SMEM_BYTES>>>(P);
    }
  }
}
```

```cpp
#include <cuda_runtime.h>
#include <cuda_bf16.h>
#include <cuda.h>
#include <stdint.h>
#include <stdio.h>

namespace {

constexpr int kB = 8, kSq = 256, kD = 640, kH = 32, kSk = 1024, kDh = 192;
constexpr int kHD = kH * kDh;
constexpr uint32_t RING = 224 * 1024;
constexpr uint32_t SZ_KV = 24576;
constexpr uint32_t SZ_Q = 16384 + 24576;
constexpr uint32_t SZ_O = 16384 + 20480;
constexpr uint32_t SZ_W3 = 16384 + 24576, SZ_W2 = 16384 + 16384, SZ_W = SZ_W3 + 16384;
constexpr uint32_t SZ_PARK = 49152;
constexpr uint32_t SZ_OL = SZ_O + 8192;
constexpr int NBAR = 10;
constexpr int EARLY = 3;
constexpr int kSteps = kHD / 64;
constexpr int TAIL = 4;
constexpr uint32_t KV_CH = 64, KV_SBO = 3072;
constexpr int SMEM_BYTES = RING + 1024 + 1024;
constexpr int N_TEAM = 16, N_CL = 66, MAX_OPS = 22, MAX_EV = 80, MAX_TAB = 47, N_TILE = N_TEAM * kH, MAX_PARK = 128, ID_PART = N_TILE + MAX_PARK;
enum : uint32_t { OP_END = 0, OP_Q = 1, OP_A = 2, OP_O = 3, F_PARK = 1 << 11,
                  C_WIDE = 1 << 27, C_PEND = 1 << 26, P_GATE = 1 << 12, P_WIDE = 1 << 11, P_LD = 1 << 12, P_PRE = 1 << 22,
                  I_NEXT = 8, E_ON = 1 << 15, E_FREE = 1 << 14, E_LAST = 1 << 13, E_DRAW = 1 << 12, E_JOB = 1 << 11 };

#define TU 25900
#define TW 1600
#define TP 1000
constexpr uint32_t DBG_DEFAULT = 0x040800;

struct alignas(1024) Scratch {
  unsigned int flag[2047];
  unsigned int ticket;
  uint4 part[N_TEAM * 2 * 2 * 5120];
  uint4 tile[N_TILE * 2 * 3072];
};

struct alignas(64) Params {
  const char* xw[2];
  uint16_t first[80];
  Scratch* g;
  uint32_t dbg;
  CUtensorMap x[2], wq[2], k[2], v[2], wo[2], wo3[2], wo2[2], out;
  struct {
    uint32_t c[MAX_OPS];
    uint32_t p[MAX_OPS];
    uint16_t n_ev, ev[MAX_TAB];
  } prog[N_CL];
  const char* kv[4];
  uint32_t job[N_CL];
  uint16_t slot[N_TILE];
  uint8_t info[ID_PART];
};

__device__ Scratch g_scratch;

template <int TB, int TA = 0>
__device__ __forceinline__ void wgmma_ss_n64(float (&d)[32], uint64_t da, uint64_t db, int scale_d) {
  asm volatile("{\n.reg .pred p;\nsetp.ne.b32 p, %34, 0;\n"
    "wgmma.mma_async.sync.aligned.m64n64k16.f32.bf16.bf16 {%0, %1, %2, %3, %4, %5, %6, %7, %8, %9, %10, %11, %12, %13, %14, %15, %16, %17, %18, %19, %20, %21, %22, %23, %24, %25, %26, %27, %28, %29, %30, %31}, %32, %33, p, 1, 1, %35, %36;\n}\n"
    : "+f"(d[0]), "+f"(d[1]), "+f"(d[2]), "+f"(d[3]), "+f"(d[4]), "+f"(d[5]), "+f"(d[6]), "+f"(d[7]), "+f"(d[8]), "+f"(d[9]), "+f"(d[10]), "+f"(d[11]), "+f"(d[12]), "+f"(d[13]), "+f"(d[14]), "+f"(d[15]), "+f"(d[16]), "+f"(d[17]), "+f"(d[18]), "+f"(d[19]), "+f"(d[20]), "+f"(d[21]), "+f"(d[22]), "+f"(d[23]), "+f"(d[24]), "+f"(d[25]), "+f"(d[26]), "+f"(d[27]), "+f"(d[28]), "+f"(d[29]), "+f"(d[30]), "+f"(d[31])
    : "l"(da), "l"(db), "r"(scale_d), "n"(TA), "n"(TB));
}
template <int TB>
__device__ __forceinline__ void wgmma_rs_n64(float (&d)[32], uint32_t a0, uint32_t a1, uint32_t a2, uint32_t a3, uint64_t db, int scale_d) {
  asm volatile("{\n.reg .pred p;\nsetp.ne.b32 p, %37, 0;\n"
    "wgmma.mma_async.sync.aligned.m64n64k16.f32.bf16.bf16 {%0, %1, %2, %3, %4, %5, %6, %7, %8, %9, %10, %11, %12, %13, %14, %15, %16, %17, %18, %19, %20, %21, %22, %23, %24, %25, %26, %27, %28, %29, %30, %31}, {%32, %33, %34, %35}, %36, p, 1, 1, %38;\n}\n"
    : "+f"(d[0]), "+f"(d[1]), "+f"(d[2]), "+f"(d[3]), "+f"(d[4]), "+f"(d[5]), "+f"(d[6]), "+f"(d[7]), "+f"(d[8]), "+f"(d[9]), "+f"(d[10]), "+f"(d[11]), "+f"(d[12]), "+f"(d[13]), "+f"(d[14]), "+f"(d[15]), "+f"(d[16]), "+f"(d[17]), "+f"(d[18]), "+f"(d[19]), "+f"(d[20]), "+f"(d[21]), "+f"(d[22]), "+f"(d[23]), "+f"(d[24]), "+f"(d[25]), "+f"(d[26]), "+f"(d[27]), "+f"(d[28]), "+f"(d[29]), "+f"(d[30]), "+f"(d[31])
    : "r"(a0), "r"(a1), "r"(a2), "r"(a3), "l"(db), "r"(scale_d), "n"(TB));
}
template <int TB, int TA = 0>
__device__ __forceinline__ void wgmma_ss_n128(float (&d)[64], uint64_t da, uint64_t db, int scale_d) {
  asm volatile("{\n.reg .pred p;\nsetp.ne.b32 p, %66, 0;\n"
    "wgmma.mma_async.sync.aligned.m64n128k16.f32.bf16.bf16 {%0, %1, %2, %3, %4, %5, %6, %7, %8, %9, %10, %11, %12, %13, %14, %15, %16, %17, %18, %19, %20, %21, %22, %23, %24, %25, %26, %27, %28, %29, %30, %31, %32, %33, %34, %35, %36, %37, %38, %39, %40, %41, %42, %43, %44, %45, %46, %47, %48, %49, %50, %51, %52, %53, %54, %55, %56, %57, %58, %59, %60, %61, %62, %63}, %64, %65, p, 1, 1, %67, %68;\n}\n"
    : "+f"(d[0]), "+f"(d[1]), "+f"(d[2]), "+f"(d[3]), "+f"(d[4]), "+f"(d[5]), "+f"(d[6]), "+f"(d[7]), "+f"(d[8]), "+f"(d[9]), "+f"(d[10]), "+f"(d[11]), "+f"(d[12]), "+f"(d[13]), "+f"(d[14]), "+f"(d[15]), "+f"(d[16]), "+f"(d[17]), "+f"(d[18]), "+f"(d[19]), "+f"(d[20]), "+f"(d[21]), "+f"(d[22]), "+f"(d[23]), "+f"(d[24]), "+f"(d[25]), "+f"(d[26]), "+f"(d[27]), "+f"(d[28]), "+f"(d[29]), "+f"(d[30]), "+f"(d[31]), "+f"(d[32]), "+f"(d[33]), "+f"(d[34]), "+f"(d[35]), "+f"(d[36]), "+f"(d[37]), "+f"(d[38]), "+f"(d[39]), "+f"(d[40]), "+f"(d[41]), "+f"(d[42]), "+f"(d[43]), "+f"(d[44]), "+f"(d[45]), "+f"(d[46]), "+f"(d[47]), "+f"(d[48]), "+f"(d[49]), "+f"(d[50]), "+f"(d[51]), "+f"(d[52]), "+f"(d[53]), "+f"(d[54]), "+f"(d[55]), "+f"(d[56]), "+f"(d[57]), "+f"(d[58]), "+f"(d[59]), "+f"(d[60]), "+f"(d[61]), "+f"(d[62]), "+f"(d[63])
    : "l"(da), "l"(db), "r"(scale_d), "n"(TA), "n"(TB));
}
template <int TB>
__device__ __forceinline__ void wgmma_rs_n128(float (&d)[64], uint32_t a0, uint32_t a1, uint32_t a2, uint32_t a3, uint64_t db, int scale_d) {
  asm volatile("{\n.reg .pred p;\nsetp.ne.b32 p, %69, 0;\n"
    "wgmma.mma_async.sync.aligned.m64n128k16.f32.bf16.bf16 {%0, %1, %2, %3, %4, %5, %6, %7, %8, %9, %10, %11, %12, %13, %14, %15, %16, %17, %18, %19, %20, %21, %22, %23, %24, %25, %26, %27, %28, %29, %30, %31, %32, %33, %34, %35, %36, %37, %38, %39, %40, %41, %42, %43, %44, %45, %46, %47, %48, %49, %50, %51, %52, %53, %54, %55, %56, %57, %58, %59, %60, %61, %62, %63}, {%64, %65, %66, %67}, %68, p, 1, 1, %70;\n}\n"
    : "+f"(d[0]), "+f"(d[1]), "+f"(d[2]), "+f"(d[3]), "+f"(d[4]), "+f"(d[5]), "+f"(d[6]), "+f"(d[7]), "+f"(d[8]), "+f"(d[9]), "+f"(d[10]), "+f"(d[11]), "+f"(d[12]), "+f"(d[13]), "+f"(d[14]), "+f"(d[15]), "+f"(d[16]), "+f"(d[17]), "+f"(d[18]), "+f"(d[19]), "+f"(d[20]), "+f"(d[21]), "+f"(d[22]), "+f"(d[23]), "+f"(d[24]), "+f"(d[25]), "+f"(d[26]), "+f"(d[27]), "+f"(d[28]), "+f"(d[29]), "+f"(d[30]), "+f"(d[31]), "+f"(d[32]), "+f"(d[33]), "+f"(d[34]), "+f"(d[35]), "+f"(d[36]), "+f"(d[37]), "+f"(d[38]), "+f"(d[39]), "+f"(d[40]), "+f"(d[41]), "+f"(d[42]), "+f"(d[43]), "+f"(d[44]), "+f"(d[45]), "+f"(d[46]), "+f"(d[47]), "+f"(d[48]), "+f"(d[49]), "+f"(d[50]), "+f"(d[51]), "+f"(d[52]), "+f"(d[53]), "+f"(d[54]), "+f"(d[55]), "+f"(d[56]), "+f"(d[57]), "+f"(d[58]), "+f"(d[59]), "+f"(d[60]), "+f"(d[61]), "+f"(d[62]), "+f"(d[63])
    : "r"(a0), "r"(a1), "r"(a2), "r"(a3), "l"(db), "r"(scale_d), "n"(TB));
}
template <int TB, int TA = 0>
__device__ __forceinline__ void wgmma_ss_n160(float (&d)[80], uint64_t da, uint64_t db, int scale_d) {
  asm volatile("{\n.reg .pred p;\nsetp.ne.b32 p, %82, 0;\n"
    "wgmma.mma_async.sync.aligned.m64n160k16.f32.bf16.bf16 {%0, %1, %2, %3, %4, %5, %6, %7, %8, %9, %10, %11, %12, %13, %14, %15, %16, %17, %18, %19, %20, %21, %22, %23, %24, %25, %26, %27, %28, %29, %30, %31, %32, %33, %34, %35, %36, %37, %38, %39, %40, %41, %42, %43, %44, %45, %46, %47, %48, %49, %50, %51, %52, %53, %54, %55, %56, %57, %58, %59, %60, %61, %62, %63, %64, %65, %66, %67, %68, %69, %70, %71, %72, %73, %74, %75, %76, %77, %78, %79}, %80, %81, p, 1, 1, %83, %84;\n}\n"
    : "+f"(d[0]), "+f"(d[1]), "+f"(d[2]), "+f"(d[3]), "+f"(d[4]), "+f"(d[5]), "+f"(d[6]), "+f"(d[7]), "+f"(d[8]), "+f"(d[9]), "+f"(d[10]), "+f"(d[11]), "+f"(d[12]), "+f"(d[13]), "+f"(d[14]), "+f"(d[15]), "+f"(d[16]), "+f"(d[17]), "+f"(d[18]), "+f"(d[19]), "+f"(d[20]), "+f"(d[21]), "+f"(d[22]), "+f"(d[23]), "+f"(d[24]), "+f"(d[25]), "+f"(d[26]), "+f"(d[27]), "+f"(d[28]), "+f"(d[29]), "+f"(d[30]), "+f"(d[31]), "+f"(d[32]), "+f"(d[33]), "+f"(d[34]), "+f"(d[35]), "+f"(d[36]), "+f"(d[37]), "+f"(d[38]), "+f"(d[39]), "+f"(d[40]), "+f"(d[41]), "+f"(d[42]), "+f"(d[43]), "+f"(d[44]), "+f"(d[45]), "+f"(d[46]), "+f"(d[47]), "+f"(d[48]), "+f"(d[49]), "+f"(d[50]), "+f"(d[51]), "+f"(d[52]), "+f"(d[53]), "+f"(d[54]), "+f"(d[55]), "+f"(d[56]), "+f"(d[57]), "+f"(d[58]), "+f"(d[59]), "+f"(d[60]), "+f"(d[61]), "+f"(d[62]), "+f"(d[63]), "+f"(d[64]), "+f"(d[65]), "+f"(d[66]), "+f"(d[67]), "+f"(d[68]), "+f"(d[69]), "+f"(d[70]), "+f"(d[71]), "+f"(d[72]), "+f"(d[73]), "+f"(d[74]), "+f"(d[75]), "+f"(d[76]), "+f"(d[77]), "+f"(d[78]), "+f"(d[79])
    : "l"(da), "l"(db), "r"(scale_d), "n"(TA), "n"(TB));
}
template <int TB>
__device__ __forceinline__ void wgmma_rs_n160(float (&d)[80], uint32_t a0, uint32_t a1, uint32_t a2, uint32_t a3, uint64_t db, int scale_d) {
  asm volatile("{\n.reg .pred p;\nsetp.ne.b32 p, %85, 0;\n"
    "wgmma.mma_async.sync.aligned.m64n160k16.f32.bf16.bf16 {%0, %1, %2, %3, %4, %5, %6, %7, %8, %9, %10, %11, %12, %13, %14, %15, %16, %17, %18, %19, %20, %21, %22, %23, %24, %25, %26, %27, %28, %29, %30, %31, %32, %33, %34, %35, %36, %37, %38, %39, %40, %41, %42, %43, %44, %45, %46, %47, %48, %49, %50, %51, %52, %53, %54, %55, %56, %57, %58, %59, %60, %61, %62, %63, %64, %65, %66, %67, %68, %69, %70, %71, %72, %73, %74, %75, %76, %77, %78, %79}, {%80, %81, %82, %83}, %84, p, 1, 1, %86;\n}\n"
    : "+f"(d[0]), "+f"(d[1]), "+f"(d[2]), "+f"(d[3]), "+f"(d[4]), "+f"(d[5]), "+f"(d[6]), "+f"(d[7]), "+f"(d[8]), "+f"(d[9]), "+f"(d[10]), "+f"(d[11]), "+f"(d[12]), "+f"(d[13]), "+f"(d[14]), "+f"(d[15]), "+f"(d[16]), "+f"(d[17]), "+f"(d[18]), "+f"(d[19]), "+f"(d[20]), "+f"(d[21]), "+f"(d[22]), "+f"(d[23]), "+f"(d[24]), "+f"(d[25]), "+f"(d[26]), "+f"(d[27]), "+f"(d[28]), "+f"(d[29]), "+f"(d[30]), "+f"(d[31]), "+f"(d[32]), "+f"(d[33]), "+f"(d[34]), "+f"(d[35]), "+f"(d[36]), "+f"(d[37]), "+f"(d[38]), "+f"(d[39]), "+f"(d[40]), "+f"(d[41]), "+f"(d[42]), "+f"(d[43]), "+f"(d[44]), "+f"(d[45]), "+f"(d[46]), "+f"(d[47]), "+f"(d[48]), "+f"(d[49]), "+f"(d[50]), "+f"(d[51]), "+f"(d[52]), "+f"(d[53]), "+f"(d[54]), "+f"(d[55]), "+f"(d[56]), "+f"(d[57]), "+f"(d[58]), "+f"(d[59]), "+f"(d[60]), "+f"(d[61]), "+f"(d[62]), "+f"(d[63]), "+f"(d[64]), "+f"(d[65]), "+f"(d[66]), "+f"(d[67]), "+f"(d[68]), "+f"(d[69]), "+f"(d[70]), "+f"(d[71]), "+f"(d[72]), "+f"(d[73]), "+f"(d[74]), "+f"(d[75]), "+f"(d[76]), "+f"(d[77]), "+f"(d[78]), "+f"(d[79])
    : "r"(a0), "r"(a1), "r"(a2), "r"(a3), "l"(db), "r"(scale_d), "n"(TB));
}
template <int TB, int TA = 0>
__device__ __forceinline__ void wgmma_ss_n192(float (&d)[96], uint64_t da, uint64_t db, int scale_d) {
  asm volatile("{\n.reg .pred p;\nsetp.ne.b32 p, %98, 0;\n"
    "wgmma.mma_async.sync.aligned.m64n192k16.f32.bf16.bf16 {%0, %1, %2, %3, %4, %5, %6, %7, %8, %9, %10, %11, %12, %13, %14, %15, %16, %17, %18, %19, %20, %21, %22, %23, %24, %25, %26, %27, %28, %29, %30, %31, %32, %33, %34, %35, %36, %37, %38, %39, %40, %41, %42, %43, %44, %45, %46, %47, %48, %49, %50, %51, %52, %53, %54, %55, %56, %57, %58, %59, %60, %61, %62, %63, %64, %65, %66, %67, %68, %69, %70, %71, %72, %73, %74, %75, %76, %77, %78, %79, %80, %81, %82, %83, %84, %85, %86, %87, %88, %89, %90, %91, %92, %93, %94, %95}, %96, %97, p, 1, 1, %99, %100;\n}\n"
    : "+f"(d[0]), "+f"(d[1]), "+f"(d[2]), "+f"(d[3]), "+f"(d[4]), "+f"(d[5]), "+f"(d[6]), "+f"(d[7]), "+f"(d[8]), "+f"(d[9]), "+f"(d[10]), "+f"(d[11]), "+f"(d[12]), "+f"(d[13]), "+f"(d[14]), "+f"(d[15]), "+f"(d[16]), "+f"(d[17]), "+f"(d[18]), "+f"(d[19]), "+f"(d[20]), "+f"(d[21]), "+f"(d[22]), "+f"(d[23]), "+f"(d[24]), "+f"(d[25]), "+f"(d[26]), "+f"(d[27]), "+f"(d[28]), "+f"(d[29]), "+f"(d[30]), "+f"(d[31]), "+f"(d[32]), "+f"(d[33]), "+f"(d[34]), "+f"(d[35]), "+f"(d[36]), "+f"(d[37]), "+f"(d[38]), "+f"(d[39]), "+f"(d[40]), "+f"(d[41]), "+f"(d[42]), "+f"(d[43]), "+f"(d[44]), "+f"(d[45]), "+f"(d[46]), "+f"(d[47]), "+f"(d[48]), "+f"(d[49]), "+f"(d[50]), "+f"(d[51]), "+f"(d[52]), "+f"(d[53]), "+f"(d[54]), "+f"(d[55]), "+f"(d[56]), "+f"(d[57]), "+f"(d[58]), "+f"(d[59]), "+f"(d[60]), "+f"(d[61]), "+f"(d[62]), "+f"(d[63]), "+f"(d[64]), "+f"(d[65]), "+f"(d[66]), "+f"(d[67]), "+f"(d[68]), "+f"(d[69]), "+f"(d[70]), "+f"(d[71]), "+f"(d[72]), "+f"(d[73]), "+f"(d[74]), "+f"(d[75]), "+f"(d[76]), "+f"(d[77]), "+f"(d[78]), "+f"(d[79]), "+f"(d[80]), "+f"(d[81]), "+f"(d[82]), "+f"(d[83]), "+f"(d[84]), "+f"(d[85]), "+f"(d[86]), "+f"(d[87]), "+f"(d[88]), "+f"(d[89]), "+f"(d[90]), "+f"(d[91]), "+f"(d[92]), "+f"(d[93]), "+f"(d[94]), "+f"(d[95])
    : "l"(da), "l"(db), "r"(scale_d), "n"(TA), "n"(TB));
}
template <int TB>
__device__ __forceinline__ void wgmma_rs_n192(float (&d)[96], uint32_t a0, uint32_t a1, uint32_t a2, uint32_t a3, uint64_t db, int scale_d) {
  asm volatile("{\n.reg .pred p;\nsetp.ne.b32 p, %101, 0;\n"
    "wgmma.mma_async.sync.aligned.m64n192k16.f32.bf16.bf16 {%0, %1, %2, %3, %4, %5, %6, %7, %8, %9, %10, %11, %12, %13, %14, %15, %16, %17, %18, %19, %20, %21, %22, %23, %24, %25, %26, %27, %28, %29, %30, %31, %32, %33, %34, %35, %36, %37, %38, %39, %40, %41, %42, %43, %44, %45, %46, %47, %48, %49, %50, %51, %52, %53, %54, %55, %56, %57, %58, %59, %60, %61, %62, %63, %64, %65, %66, %67, %68, %69, %70, %71, %72, %73, %74, %75, %76, %77, %78, %79, %80, %81, %82, %83, %84, %85, %86, %87, %88, %89, %90, %91, %92, %93, %94, %95}, {%96, %97, %98, %99}, %100, p, 1, 1, %102;\n}\n"
    : "+f"(d[0]), "+f"(d[1]), "+f"(d[2]), "+f"(d[3]), "+f"(d[4]), "+f"(d[5]), "+f"(d[6]), "+f"(d[7]), "+f"(d[8]), "+f"(d[9]), "+f"(d[10]), "+f"(d[11]), "+f"(d[12]), "+f"(d[13]), "+f"(d[14]), "+f"(d[15]), "+f"(d[16]), "+f"(d[17]), "+f"(d[18]), "+f"(d[19]), "+f"(d[20]), "+f"(d[21]), "+f"(d[22]), "+f"(d[23]), "+f"(d[24]), "+f"(d[25]), "+f"(d[26]), "+f"(d[27]), "+f"(d[28]), "+f"(d[29]), "+f"(d[30]), "+f"(d[31]), "+f"(d[32]), "+f"(d[33]), "+f"(d[34]), "+f"(d[35]), "+f"(d[36]), "+f"(d[37]), "+f"(d[38]), "+f"(d[39]), "+f"(d[40]), "+f"(d[41]), "+f"(d[42]), "+f"(d[43]), "+f"(d[44]), "+f"(d[45]), "+f"(d[46]), "+f"(d[47]), "+f"(d[48]), "+f"(d[49]), "+f"(d[50]), "+f"(d[51]), "+f"(d[52]), "+f"(d[53]), "+f"(d[54]), "+f"(d[55]), "+f"(d[56]), "+f"(d[57]), "+f"(d[58]), "+f"(d[59]), "+f"(d[60]), "+f"(d[61]), "+f"(d[62]), "+f"(d[63]), "+f"(d[64]), "+f"(d[65]), "+f"(d[66]), "+f"(d[67]), "+f"(d[68]), "+f"(d[69]), "+f"(d[70]), "+f"(d[71]), "+f"(d[72]), "+f"(d[73]), "+f"(d[74]), "+f"(d[75]), "+f"(d[76]), "+f"(d[77]), "+f"(d[78]), "+f"(d[79]), "+f"(d[80]), "+f"(d[81]), "+f"(d[82]), "+f"(d[83]), "+f"(d[84]), "+f"(d[85]), "+f"(d[86]), "+f"(d[87]), "+f"(d[88]), "+f"(d[89]), "+f"(d[90]), "+f"(d[91]), "+f"(d[92]), "+f"(d[93]), "+f"(d[94]), "+f"(d[95])
    : "r"(a0), "r"(a1), "r"(a2), "r"(a3), "l"(db), "r"(scale_d), "n"(TB));
}

__device__ __forceinline__ uint32_t smem_u32(const void* p) { return (uint32_t)__cvta_generic_to_shared(p); }
__device__ __forceinline__ void wg_fence() { asm volatile("wgmma.fence.sync.aligned;" ::: "memory"); }
__device__ __forceinline__ void wg_commit() { asm volatile("wgmma.commit_group.sync.aligned;" ::: "memory"); }
template <int N> __device__ __forceinline__ void wg_wait() { asm volatile("wgmma.wait_group.sync.aligned %0;" ::"n"(N) : "memory"); }
__device__ __forceinline__ void sched_fence(uint32_t& keep, bool never) {
  asm volatile("{\n.reg .pred p;\nsetp.ne.b32 p, %1, 0;\n@p mov.u32 %0, %%clock;\n}\n" : "+r"(keep) : "r"((int)never) : "memory");
}
template <int N> __device__ __forceinline__ void fence_regs(float (&r)[N]) {
#pragma unroll
  for (int i = 0; i < N; i++) asm volatile("" : "+f"(r[i])::"memory");
}
template <int N> __device__ __forceinline__ void undefine(float (&r)[N]) {
#pragma unroll
  for (int i = 0; i < N; i++) asm volatile("" : "=f"(r[i]));
}
template <int N> __device__ __forceinline__ void fence_regs(uint32_t (&r)[N]) {
#pragma unroll
  for (int i = 0; i < N; i++) asm volatile("" : "+r"(r[i])::"memory");
}
__device__ __forceinline__ uint64_t mk_desc(uint32_t a16, uint32_t lbo, uint32_t sbo, uint32_t swz) {
  uint64_t d;
  asm("mov.b64 %0, {%1, %2};" : "=l"(d) : "r"(a16 + ((lbo >> 4) << 16)), "r"((sbo >> 4) | (swz << 30)));
  return d;
}
__device__ __forceinline__ void mbar_init(uint32_t bar, uint32_t cnt) {
  asm volatile("mbarrier.init.shared::cta.b64 [%0], %1;" ::"r"(bar), "r"(cnt) : "memory");
}
__device__ __forceinline__ void mbar_expect(uint32_t bar, uint32_t tx) {
  asm volatile("mbarrier.arrive.expect_tx.shared::cta.b64 _, [%0], %1;" ::"r"(bar), "r"(tx) : "memory");
}
__device__ __forceinline__ bool mbar_test(uint32_t bar, uint32_t ph) {
  uint32_t ok;
  asm volatile("{\n.reg .pred p;\nmbarrier.test_wait.parity.shared::cta.b64 p, [%1], %2;\nselp.u32 %0, 1, 0, p;\n}\n"
               : "=r"(ok) : "r"(bar), "r"(ph) : "memory");
  return ok;
}
__device__ __forceinline__ bool mbar_try(uint32_t bar, uint32_t ph, uint32_t ns) {
  uint32_t ok;
  asm volatile("{\n.reg .pred p;\nmbarrier.try_wait.parity.shared::cta.b64 p, [%1], %2, %3;\nselp.u32 %0, 1, 0, p;\n}\n"
               : "=r"(ok) : "r"(bar), "r"(ph), "r"(ns) : "memory");
  return ok;
}
__device__ __forceinline__ void mbar_wait(uint32_t bar, uint32_t ph) {
  asm volatile("{\n.reg .pred p;\n.reg .u32 n;\nmov.u32 n, 0;\n"
               "LOOP:\nmbarrier.try_wait.parity.shared::cta.b64 p, [%0], %1;\n@p bra DONE;\n"
               "add.u32 n, n, 1;\nsetp.lt.u32 p, n, 0x1000000;\n@p bra LOOP;\ntrap;\n"
               "DONE:\n}\n" ::"r"(bar), "r"(ph) : "memory");
}
__device__ __forceinline__ void mbar_wait_long(uint32_t bar) {
  asm volatile("{\n.reg .pred p;\n.reg .u32 n;\nmov.u32 n, 0;\n"
               "LOOP:\nmbarrier.try_wait.parity.shared::cta.b64 p, [%0], 0, 20000;\n@p bra DONE;\n"
               "add.u32 n, n, 1;\nsetp.lt.u32 p, n, 0x100000;\n@p bra LOOP;\ntrap;\n"
               "DONE:\n}\n" ::"r"(bar) : "memory");
}
__device__ __forceinline__ void mbar_arrive_cluster_if(bool on, uint32_t addr) {
  asm volatile("{\n.reg .pred p;\nsetp.ne.b32 p, %1, 0;\n@p mbarrier.arrive.shared::cluster.b64 _, [%0];\n}\n" ::"r"(addr), "r"((int)on) : "memory");
}
__device__ __forceinline__ void mbar_arrive_cluster_n(uint32_t n, uint32_t addr) {
  asm volatile("{\n.reg .pred p;\nsetp.ne.b32 p, %1, 0;\n@p mbarrier.arrive.shared::cluster.b64 _, [%0], %1;\n}\n" ::"r"(addr), "r"(n) : "memory");
}
__device__ __forceinline__ void tma2d(uint32_t dst, const CUtensorMap* m, uint32_t bar, int c0, int c1) {
  asm volatile("cp.async.bulk.tensor.2d.shared::cluster.global.mbarrier::complete_tx::bytes [%0], [%1, {%3, %4}], [%2];"
               ::"r"(dst), "l"(m), "r"(bar), "r"(c0), "r"(c1) : "memory");
}
__device__ __forceinline__ void tma3d(uint32_t dst, const CUtensorMap* m, uint32_t bar, int c0, int c1, int c2) {
  asm volatile("cp.async.bulk.tensor.3d.shared::cluster.global.mbarrier::complete_tx::bytes [%0], [%1, {%3, %4, %5}], [%2];"
               ::"r"(dst), "l"(m), "r"(bar), "r"(c0), "r"(c1), "r"(c2) : "memory");
}
__device__ __forceinline__ void tma3d_mc(uint32_t dst, const CUtensorMap* m, uint32_t bar, int c0, int c1, int c2) {
  asm volatile("cp.async.bulk.tensor.3d.shared::cluster.global.mbarrier::complete_tx::bytes.multicast::cluster"
               " [%0], [%1, {%3, %4, %5}], [%2], %6;"
               ::"r"(dst), "l"(m), "r"(bar), "r"(c0), "r"(c1), "r"(c2), "h"((uint16_t)3) : "memory");
}
__device__ __forceinline__ void tma3d_store(const CUtensorMap* m, uint32_t src, int c0, int c1, int c2) {
  asm volatile("cp.async.bulk.tensor.3d.global.shared::cta.bulk_group [%0, {%2, %3, %4}], [%1];"
               ::"l"(m), "r"(src), "r"(c0), "r"(c1), "r"(c2) : "memory");
}
__device__ __forceinline__ void bar_sync(int id, int n) { asm volatile("bar.sync %0, %1;" ::"r"(id), "r"(n) : "memory"); }
__device__ __forceinline__ uint32_t pack_bf16(float lo, float hi) {
  uint32_t r;
  asm("cvt.rn.bf16x2.f32 %0, %1, %2;" : "=r"(r) : "f"(hi), "f"(lo));
  return r;
}
__device__ __forceinline__ float ex2(float x) {
  float y;
  asm("ex2.approx.ftz.f32 %0, %1;" : "=f"(y) : "f"(x));
  return y;
}
__device__ __forceinline__ float rcp(float x) {
  float y;
  asm("rcp.approx.ftz.f32 %0, %1;" : "=f"(y) : "f"(x));
  return y;
}
__device__ __forceinline__ void stsm4(uint32_t addr, uint32_t a, uint32_t b, uint32_t c, uint32_t d) {
  asm volatile("stmatrix.sync.aligned.m8n8.x4.shared.b16 [%0], {%1, %2, %3, %4};" ::"r"(addr), "r"(a), "r"(b), "r"(c), "r"(d) : "memory");
}

__device__ __forceinline__ void tma4d_mc_hint(uint32_t dst, const CUtensorMap* m, uint32_t bar, int c3, uint64_t pol) {
  asm volatile("cp.async.bulk.tensor.4d.shared::cluster.global.mbarrier::complete_tx::bytes.multicast::cluster.L2::cache_hint"
               " [%0], [%1, {%3, %3, %3, %4}], [%2], %5, %6;"
               ::"r"(dst), "l"(m), "r"(bar), "r"(0), "r"(c3), "h"((uint16_t)3), "l"(pol) : "memory");
}
__device__ __forceinline__ void tma5d_mc(uint32_t dst, const CUtensorMap* m, uint32_t bar, int c2, int c4) {
  asm volatile("cp.async.bulk.tensor.5d.shared::cluster.global.mbarrier::complete_tx::bytes.multicast::cluster"
               " [%0], [%1, {%3, %3, %4, %3, %5}], [%2], %6;"
               ::"r"(dst), "l"(m), "r"(bar), "r"(0), "r"(c2), "r"(c4), "h"((uint16_t)3) : "memory");
}
__device__ __forceinline__ void bulk_load_hint(uint32_t dst, const void* src, uint32_t bytes, uint32_t bar, uint64_t pol) {
  asm volatile("cp.async.bulk.shared::cluster.global.mbarrier::complete_tx::bytes.L2::cache_hint [%0], [%1], %2, [%3], %4;"
               ::"r"(dst), "l"(src), "r"(bytes), "r"(bar), "l"(pol) : "memory");
}
__device__ __forceinline__ void stg2_if(bool on, void* p, uint32_t a, uint32_t b, uint32_t c, uint32_t d, uint32_t e, uint32_t f,
                                        uint32_t g, uint32_t h, uint64_t pol) {
  asm volatile("{\n.reg .pred p;\nsetp.ne.b32 p, %10, 0;\n"
               "@p st.global.L2::cache_hint.v4.b32 [%0], {%1, %2, %3, %4}, %9;\n"
               "@p st.global.L2::cache_hint.v4.b32 [%0 + 512], {%5, %6, %7, %8}, %9;\n}\n"
               ::"l"(p), "r"(a), "r"(b), "r"(c), "r"(d), "r"(e), "r"(f), "r"(g), "r"(h), "l"(pol), "r"((int)on) : "memory");
}
__device__ __forceinline__ uint64_t evict_first() {
  uint64_t p;
  asm("createpolicy.fractional.L2::evict_first.b64 %0, 1.0;" : "=l"(p));
  return p;
}
__device__ __forceinline__ bool elect() {
  uint32_t ok;
  asm volatile("{\n.reg .pred p;\nelect.sync _|p, 0xffffffff;\nselp.u32 %0, 1, 0, p;\n}\n" : "=r"(ok));
  return ok;
}
__device__ __forceinline__ void mbar_arrive(uint32_t bar) {
  asm volatile("mbarrier.arrive.shared::cta.b64 _, [%0];" ::"r"(bar) : "memory");
}
__device__ __forceinline__ void mbar_arrive_if(bool on, uint32_t bar) {
  asm volatile("{\n.reg .pred p;\nsetp.ne.b32 p, %1, 0;\n@p mbarrier.arrive.shared::cta.b64 _, [%0];\n}\n" ::"r"(bar), "r"((int)on) : "memory");
}
__device__ __forceinline__ void lds2_if(bool on, uint32_t p, uint32_t (&t)[8]) {
  asm volatile("{\n.reg .pred p;\nsetp.ne.b32 p, %9, 0;\n@p ld.shared.v4.b32 {%0, %1, %2, %3}, [%8];\n@p ld.shared.v4.b32 {%4, %5, %6, %7}, [%8 + 512];\n}\n"
               : "+r"(t[0]), "+r"(t[1]), "+r"(t[2]), "+r"(t[3]), "+r"(t[4]), "+r"(t[5]), "+r"(t[6]), "+r"(t[7]) : "r"(p), "r"((int)on) : "memory");
}
__device__ __forceinline__ void lds128(uint32_t p, uint32_t& a, uint32_t& b, uint32_t& c, uint32_t& d) {
  asm volatile("ld.shared.v4.b32 {%0, %1, %2, %3}, [%4];" : "=r"(a), "=r"(b), "=r"(c), "=r"(d) : "r"(p) : "memory");
}
template <class T> __device__ __forceinline__ T* ptr_add(T* base, uint32_t bytes) {
  T* r;
  asm("{\n.reg .u32 lo, hi;\nmov.b64 {lo, hi}, %1;\nadd.cc.u32 lo, lo, %2;\naddc.u32 hi, hi, 0;\nmov.b64 %0, {lo, hi};\n}\n" : "=l"(r) : "l"(base), "r"(bytes));
  return r;
}
__device__ __forceinline__ uint32_t lds32(uint32_t p) {
  uint32_t v;
  asm volatile("ld.volatile.shared.u32 %0, [%1];" : "=r"(v) : "r"(p) : "memory");
  return v;
}
__device__ __forceinline__ uint32_t flag_get(const unsigned int* p) {
  uint32_t v;
  asm volatile("ld.acquire.gpu.global.u32 %0, [%1];" : "=r"(v) : "l"(p) : "memory");
  return v;
}
__device__ __forceinline__ uint32_t wait_word(uint32_t p, uint32_t target) {
  uint32_t v;
  asm volatile("{\n.reg .pred p;\n.reg .u32 n;\nmov.u32 n, 0;\n"
               "LOOP:\nld.acquire.cta.shared.u32 %0, [%1];\nsetp.ge.u32 p, %0, %2;\n@p bra DONE;\n"
               "nanosleep.u32 %3;\nadd.u32 n, n, 1;\nsetp.lt.u32 p, n, 0x400000;\n@p bra LOOP;\ntrap;\n"
               "DONE:\n}\n" : "=r"(v) : "r"(p), "r"(target), "n"(400) : "memory");
  return v;
}
__device__ __forceinline__ void flag_set(unsigned int* p, uint32_t v) {
  asm volatile("st.release.gpu.global.u32 [%0], %1;" ::"l"(p), "r"(v) : "memory");
}
__device__ __forceinline__ void flag_dec(unsigned int* p) {
  asm volatile("red.relaxed.gpu.global.add.u32 [%0], 0xffffffff;" ::"l"(p) : "memory");
}

struct Cursor {
  int bi;
  uint32_t ph;
  __device__ __forceinline__ void next() {
    if (++bi == NBAR) { bi = 0; ph ^= 1; }
  }
};

constexpr float kScaleLog2 = 0.07216878364870322f * 1.4426950408889634f;
constexpr float kSumLimit = 1048576.0f;

__global__ void __cluster_dims__(2, 1, 1) __launch_bounds__(384, 1)
fused_kernel(const __grid_constant__ Params P) {
  extern __shared__ uint8_t smem_raw[];
  const uint32_t sbase = (smem_u32(smem_raw) + 1023) & ~1023u;
  const uint32_t full0 = sbase + RING, empty0 = full0 + 8 * NBAR, odone0 = empty0 + 8 * NBAR, ev0 = odone0 + 8 * MAX_OPS;
  const uint32_t progress = ev0 + 8 * MAX_EV, jobw = progress + 4;
  const uint32_t rank = blockIdx.x & 1;
  const int role = blockIdx.x >> 1;
  const int wid = __shfl_sync(0xffffffffu, (int)(threadIdx.x >> 5), 0);
  const int wg = wid >> 2;

  if (wid < 8) {
    if (elect()) {
#pragma unroll
      for (int j = 0; j < 16; j++) {
        const int i = EARLY + 16 * wid + j;
        if (i < 2 * NBAR + MAX_OPS + MAX_EV) mbar_init(full0 + 8 * i, i < NBAR ? 1 : i < 2 * NBAR ? 16 : i < 2 * NBAR + MAX_OPS ? 8 : 1);
      }
      if (wid == 7) asm volatile("st.shared.v2.u32 [%0], {0, 0};\nfence.acq_rel.cta;" ::"r"(progress) : "memory");
      asm volatile("fence.mbarrier_init.release.cluster;" ::: "memory");
    }
  } else if (wid > 8) {
    const uint32_t g = blockIdx.x * 96 + threadIdx.x - 288, w = g - 2048;
    if (g < 4096) asm volatile("prefetch.global.L2 [%0];" ::"l"(g < 2048 ? P.xw[0] + g * (kD * 2) : P.xw[1] + (w >> 5) * (kHD * 2) + (w & 31) * 128));
  } else {
    const uint32_t op0 = P.first[role];
    if (elect()) {
#pragma unroll
      for (int k = 0; k < EARLY; k++) mbar_init(full0 + 8 * k, 1);
      asm volatile("fence.mbarrier_init.release.cluster;" ::: "memory");
      const int blk = (op0 >> 10) & 1;
      if ((op0 & 3) == OP_Q) {
#pragma unroll
        for (int k = 0; k < EARLY; k++) {
          mbar_expect(full0 + 8 * k, SZ_Q);
          tma2d(sbase + k * SZ_Q, &P.x[blk], full0 + 8 * k, 64 * k, ((op0 >> 7) & 7) * kSq + rank * 128);
          tma3d(sbase + k * SZ_Q + 16384, &P.wq[blk], full0 + 8 * k, 0, 64 * k, 3 * ((op0 >> 2) & 31));
        }
      }
      asm volatile("prefetch.tensormap [%0];" ::"l"(rank ? &P.v[blk] : &P.k[blk]) : "memory");
    }
  }
  __syncwarp();
  asm volatile("barrier.cluster.arrive.relaxed.aligned;\nbarrier.cluster.wait.aligned;" ::: "memory");

  if (wg < 2) {
    asm volatile("setmaxnreg.inc.sync.aligned.u32 240;");
    const uint32_t* prog = P.prog[role].c;
    const int lane = threadIdx.x & 31, warp = wid & 3;
    uint32_t empty_rem;
    asm volatile("mapa.shared::cluster.u32 %0, %1, %2;" : "=r"(empty_rem) : "r"(empty0), "r"(lane & 1));
    uint32_t keep = (threadIdx.x & 127) < 2 ? 4 : 0;
    auto release = [&](int slot) { mbar_arrive_cluster_n(keep, empty_rem + 8 * slot); };
    auto release_warp = [&](int slot, bool on = true) { mbar_arrive_cluster_if(lane < 2 && on, empty_rem + 8 * slot); };
    Cursor r{0, 0};
    const uint32_t ring16 = (sbase & 0x3FFFF) >> 4;
    uint32_t cur = ring16;
    bool rdy0 = false, rdy1 = false;
    auto probe1 = [&]() { rdy0 = mbar_test(full0 + 8 * r.bi, r.ph); };
    auto probe2 = [&]() {
      Cursor n = r;
      rdy0 = mbar_test(full0 + 8 * n.bi, n.ph);
      n.next();
      rdy1 = mbar_test(full0 + 8 * n.bi, n.ph);
    };
    auto take = [&](bool rdy, uint32_t bytes, uint32_t& addr) {
      const int bi = r.bi;
      if (__builtin_expect(!__all_sync(0xffffffffu, rdy), 0)) mbar_wait(full0 + 8 * r.bi, r.ph);
      r.next();
      if (cur > ring16 + ((RING - bytes) >> 4)) cur = ring16;
      addr = cur;
      cur += bytes >> 4;
      return bi;
    };
    const bool never = P.dbg == 0xffffffffu;
    uint32_t q[48];
#pragma unroll
    for (int i = 0; i < 48; i++) q[i] = 0;
    const int row = wg * 64 + warp * 16 + (lane >> 2);
    const int img0 = row * 4 + ((lane & 3) ^ ((row >> 1) & 3));
    uint4* pend = nullptr;
    bool pend_any = false;
    const uint64_t spol = evict_first();
    int pc = 0;
    auto slab = [&](int c, int i0) {
#pragma unroll
      for (int i = i0; i < 6; i++)
        stg2_if(c == i, pend + i * 512, q[8 * i], q[8 * i + 1], q[8 * i + 2], q[8 * i + 3],
                q[8 * i + 4], q[8 * i + 5], q[8 * i + 6], q[8 * i + 7], spol);
    };
    auto drain = [&](int c) {
      if (!pend_any || c >= 6) return;
      slab(c, 0);
      if (c == 5) {
        __syncwarp();
        mbar_arrive_if(lane == 0, odone0 - 8 + 8 * pc);
      }
    };

    for (;; pc++) {
      uint32_t op = prog[pc];
      const int type = op & 3;
      auto enter = [&]() {
        r.bi = (op >> 15) & 15; r.ph = (op >> 19) & 1; cur = ring16 + (((op >> 20) & 63) << 8);
      };
      enter();
      pend_any = op & C_PEND;
      uint32_t job = 0;
      if ((op & (3 | C_WIDE)) == OP_O) job = __shfl_sync(0xffffffffu, wait_word(jobw, 1), 0);
      if (type == OP_END || job == OP_O) {
#pragma unroll 1
        for (int c = 0; c < 6; c++) drain(c);
        asm volatile("barrier.cluster.arrive.relaxed;" ::: "memory");
        break;
      }
      {
        float s[32], o[96];
        uint32_t ad0;
        int bi0, sk1;
        uint32_t pa[16], pb[16];
        float mc0, mc1, l0, l1;
        bool shifted;
        uint32_t nop;
        auto expo = [&](float (&s)[32], uint32_t (&pout)[16], float& b0, float& b1, bool shift, auto mid) {
          float c0, c1;
#pragma unroll
          for (int i = 0; i < 8; i++) {
            const float e0 = ex2(shift ? s[4 * i] - mc0 : s[4 * i]), e1 = ex2(shift ? s[4 * i + 1] - mc0 : s[4 * i + 1]);
            const float e2 = ex2(shift ? s[4 * i + 2] - mc1 : s[4 * i + 2]), e3 = ex2(shift ? s[4 * i + 3] - mc1 : s[4 * i + 3]);
            if (i) { b0 += e0; c0 += e1; b1 += e2; c1 += e3; } else { b0 = e0; c0 = e1; b1 = e2; c1 = e3; }
            pout[2 * i] = pack_bf16(e0, e1); pout[2 * i + 1] = pack_bf16(e2, e3);
            if (i & 1) mid(i >> 1);
          }
          b0 += c0; b1 += c1;
        };
        auto rowmax = [&](float (&s)[32], float& m0, float& m1) {
          m0 = fmaxf(s[0], s[1]); m1 = fmaxf(s[2], s[3]);
#pragma unroll
          for (int i = 1; i < 8; i++) { m0 = fmaxf(m0, fmaxf(s[4 * i], s[4 * i + 1])); m1 = fmaxf(m1, fmaxf(s[4 * i + 2], s[4 * i + 3])); }
          m0 = fmaxf(m0, __shfl_xor_sync(0xffffffffu, m0, 1)); m1 = fmaxf(m1, __shfl_xor_sync(0xffffffffu, m1, 1));
          m0 = fmaxf(m0, __shfl_xor_sync(0xffffffffu, m0, 2)); m1 = fmaxf(m1, __shfl_xor_sync(0xffffffffu, m1, 2));
        };
        auto first = [&](float (&s)[32], int sk0, auto mid) {
          fence_regs(s);
          release(sk0);
          mc0 = 0.f; mc1 = 0.f;
          expo(s, pa, l0, l1, false, mid);
          shifted = __any_sync(0xffffffffu, !(fmaxf(l0, l1) <= kSumLimit && fminf(l0, l1) >= 1.f / kSumLimit));
          if (shifted) {
            rowmax(s, mc0, mc1);
            expo(s, pa, l0, l1, true, [](int) {});
          }
        };
        auto qk = [&](float (&s)[32], uint32_t ak, int k0 = 0, int k1 = 12) {
#pragma unroll
          for (int kk = k0; kk < k1; kk++)
            wgmma_rs_n64<0>(s, q[4 * kk], q[4 * kk + 1], q[4 * kk + 2], q[4 * kk + 3], mk_desc(ak, 16, KV_SBO, 1) + ((kk >> 2) * KV_CH + (kk & 3) * 2), kk != 0);
          if (k1 == 12) wg_commit();
        };
        auto pv = [&](uint32_t (&pin)[16], uint32_t av, int acc) {
#pragma unroll
          for (int kk = 0; kk < 4; kk++)
            wgmma_rs_n192<1>(o, pin[4 * kk], pin[4 * kk + 1], pin[4 * kk + 2], pin[4 * kk + 3], mk_desc(av, KV_CH * 16, KV_SBO, 1) + (kk * (KV_SBO / 8)), acc || (kk != 0));
          wg_commit();
        };
        auto finish = [&](uint32_t (&pout)[16], int sk, int sv) {
          probe2();
          wg_wait<1>();
          fence_regs(s);
          release(sk);
          float b0, b1;
#pragma unroll 1
          for (bool redo = false;; redo = true) {
            expo(s, pout, b0, b1, false, [](int) {});
            if (!__any_sync(0xffffffffu, !redo && (shifted || !(fmaxf(b0, b1) <= kSumLimit)))) break;
            shifted = true;
            rowmax(s, b0, b1);
            b0 = fmaxf(mc0, b0); b1 = fmaxf(mc1, b1);
            const float a0 = ex2(mc0 - b0), a1 = ex2(mc1 - b1);
            mc0 = b0; mc1 = b1;
            l0 *= a0; l1 *= a1;
            wg_wait<0>();
            fence_regs(o);
#pragma unroll
            for (int i = 0; i < 24; i++) { o[4 * i] *= a0; o[4 * i + 1] *= a0; o[4 * i + 2] *= a1; o[4 * i + 3] *= a1; }
#pragma unroll
            for (int i = 0; i < 32; i++) s[i] -= (i & 2) ? mc1 : mc0;
          }
          l0 += b0; l1 += b1;
          wg_wait<0>();
          fence_regs(o);
          release(sv);
        };
        auto step = [&](uint32_t (&pin)[16], uint32_t (&pout)[16]) {
          uint32_t ak, av;
          const int sk = take(rdy0, SZ_KV, ak), sv = take(rdy1, SZ_KV, av);
          wg_fence();
          qk(s, ak);
          pv(pin, av, 1);
          finish(pout, sk, sv);
        };
        auto unpark = [&]() {
          uint32_t ad, ak;
          const int bi = take(rdy0, SZ_PARK, ad);
#pragma unroll
          for (int i = 0; i < 12; i++) lds128(sbase + (ad - ring16 + img0) * 16 + (i >> 1) * 8192 + (i & 1) * 512, q[4 * i], q[4 * i + 1], q[4 * i + 2], q[4 * i + 3]);
          const int sk0 = take(false, SZ_KV, ak);
          fence_regs(q);
          release_warp(bi);
          wg_fence();
          qk(s, ak);
          probe2();
          return sk0;
        };
        auto mma4 = [&](uint32_t ad, int acc) {
#pragma unroll
          for (int kk = 0; kk < 4; kk++)
            wgmma_ss_n192<1>(o, mk_desc(ad + wg * 512, 16, 1024, 1) + (kk * 2), mk_desc(ad, 8192, 1024, 1) + (1024 + kk * 128), acc || kk != 0);
        };
        auto convert = [&](int i0, int i1) {
          sched_fence(keep, never);
#pragma unroll
          for (int i = i0; i < i1; i++) {
            q[i] = pack_bf16(o[2 * i] * kScaleLog2, o[2 * i + 1] * kScaleLog2);
            if ((i & 7) == 7 && i != i1 - 1) sched_fence(keep, never);
          }
          sched_fence(keep, never);
        };
        auto kend = [&](int bi, int k) {
          wg_commit();
          drain(k < 8 ? (0x54732710u >> (4 * k)) & 7 : 7);
          probe1();
          wg_wait<0>();
          release(bi);
        };
        if (type == OP_O) {
          int prev = 0;
          if (op & C_WIDE) {
            float d[64];
            auto mma3 = [&](uint32_t ad, int h, int acc) {
#pragma unroll
              for (int kk = 0; kk < 2; kk++)
                wgmma_ss_n192<1>(o, mk_desc(ad + wg * 256, 16, 512, 2) + (h * 512 + kk * 2), mk_desc(ad, 4096, 1024, 1) + (1024 + h * 768 + kk * 128), acc || kk);
            };
            auto mma2 = [&](uint32_t ad, uint32_t ob, int h, int acc) {
#pragma unroll
              for (int kk = 0; kk < 2; kk++)
                wgmma_ss_n128<1>(d, mk_desc(ad + wg * 256, 16, 512, 2) + (h * 512 + kk * 2), mk_desc(ad, 4096, 1024, 1) + (ob + h * 512 + kk * 128), acc || kk);
            };
            auto wstep = [&](uint32_t bytes, int acc, auto hook) {
              uint32_t ad;
              const int bi = take(rdy0, bytes, ad);
              wg_fence();
              if (bytes == SZ_W2) mma2(ad, 1024, 0, 1); else mma3(ad, 0, acc);
              if (bytes == SZ_W) mma3(ad, 1, 1);
              wg_commit();
              if (acc) { wg_wait<1>(); release(prev); }
              if (bytes == SZ_W) mma2(ad, 2560, 0, acc);
              if (bytes == SZ_W3) mma3(ad, 1, 1); else mma2(ad, bytes == SZ_W ? 2560 : 1024, 1, 1);
              wg_commit();
              prev = bi;
              hook();
              probe1();
              wg_wait<1>();
            };
            undefine(o);
            wstep(SZ_W, 0, [&]() { drain(0); });
#pragma unroll 1
            for (int k = 1; k < ((op >> 2) & 127) - TAIL; k++) wstep(SZ_W, 1, [&]() { drain(k); });
#pragma unroll 1
            for (int k = 0; k < TAIL; k++) wstep(SZ_W2, 1, []() {});
            pend = ptr_add(P.g->part, (((op >> 9) & 31) * 2 + rank) * 81920 + 4 * 8192 + img0 * 16);
            wstep(SZ_W3, 1, [&]() {
              fence_regs(d);
#pragma unroll
              for (int i = 0; i < 32; i++) q[16 + i] = pack_bf16(d[2 * i], d[2 * i + 1]);
              slab(2, 2);
            });
#pragma unroll 1
            for (int k = 3; k < 6; k++) wstep(SZ_W3, 1, [&]() { slab(k, 2); });
            op = prog[pc + 1];
            enter();
            pend_any = true;
            pend -= 4 * 512;
            bi0 = take(rdy0 || (op & 3) != OP_Q, SZ_Q, ad0);
            sched_fence(keep, never);
            wg_wait<0>();
            fence_regs(o);
            release(prev);
#pragma unroll
            for (int i = 0; i < 48; i++) q[i] = pack_bf16(o[2 * i], o[2 * i + 1]);
            if ((op & 3) != OP_Q) continue;
            pc++;
            goto first_step;
          }
          float c[80];
          auto mma2 = [&](uint32_t ad, uint32_t oa, uint32_t ob, int acc) {
            wgmma_ss_n160<1>(c, mk_desc(ad + wg * 256, 16, 512, 2) + (oa), mk_desc(ad, 2048, 512, 2) + (1024 + ob), acc);
            wgmma_ss_n160<1>(c, mk_desc(ad + wg * 256, 16, 512, 2) + (oa + 2), mk_desc(ad, 2048, 512, 2) + (1024 + ob + 64), 1);
          };
          auto kstep = [&](int acc, auto hook, uint32_t bytes = SZ_O) {
            uint32_t ad;
            const int bi = take(rdy0, bytes, ad);
            wg_fence();
            mma2(ad, 0, 0, acc);
            wg_commit();
            if (acc) wg_wait<1>();
            if (acc == 1) release(prev);
            if (acc > 1) release_warp(prev, acc == 2 || wg == 0);
            mma2(ad, 512, 640, 1);
            wg_commit();
            prev = bi;
            hook();
            probe1();
            wg_wait<1>();
          };
          auto unblock = [&](int k) {
            if (__all_sync(0xffffffffu, rdy0) || __all_sync(0xffffffffu, mbar_try(full0 + 8 * r.bi, r.ph, 1500))) return;
#pragma unroll 1
            for (; k < 6; k++) drain(k);
            pend_any = false;
          };
          unblock(0);
          kstep(0, [&]() { drain(0); });
          int left = ((job >> 13) & 127) - 6;
#pragma unroll 1
          for (uint32_t k = 1, pace = left >= 29 ? 0x4511 : left <= 17 ? 0x1a : 0x155; left > 0; pace >>= 2, left--) {
            unblock(k);
            kstep(1, [&]() {
#pragma unroll 1
              for (int i = pace & 3; i > 0; i--) drain(k++);
            });
          }
          uint32_t t[8], stage[3];
          float u[80];
          auto unpack = [&](int j) {
#pragma unroll
            for (int i = 0; i < 8; i++) {
              u[16 * j + 2 * i] = __uint_as_float(t[i] << 16); u[16 * j + 2 * i + 1] = __uint_as_float(t[i] & 0xffff0000u);
              asm volatile("" : "+f"(u[16 * j + 2 * i]), "+f"(u[16 * j + 2 * i + 1]));
            }
          };
#pragma unroll
          for (int i = 0; i < 8; i++) t[i] = 0;
          const uint32_t bytes = (job & P_LD) ? SZ_OL : SZ_O;
#pragma unroll
          for (int j = 0; j < 5; j++) {
            if (j == 2 && wg == 1) {
              wg_wait<0>();
              release_warp(prev);
              bar_sync(1, 256);
            }
            kstep(j == 2 ? 3 : 2, [&]() {
              if (j == 4) asm volatile("{\n.reg .pred p;\nsetp.eq.u32 p, %0, 0;\n@p bar.arrive 1, 256;\n}\n" ::"r"(wg) : "memory");
              if (j) unpack(j - 1);
              lds2_if(job & P_LD, sbase + (cur - ring16 + img0) * 16 - 8192, t);
              if (j >= 1 && j <= 3) stage[j - 1] = sbase + (cur - ring16) * 16 - bytes + wid * 1024;
            }, bytes);
          }
          unpack(4);
          sched_fence(keep, never);
          wg_wait<0>();
          fence_regs(c);
          release_warp(prev);
          asm volatile("barrier.cluster.arrive.relaxed;" ::: "memory");
#pragma unroll
          for (int i = 0; i < 10; i++) {
            const int v = (i & 1) * 2 + (lane >> 4);
            const uint32_t sa = stage[i >> 2] + (i & 2) * 4096;
            stsm4(sa + (lane & 15) * 64 + ((v ^ ((lane >> 1) & 3)) << 4), pack_bf16(c[8 * i] + u[8 * i], c[8 * i + 1] + u[8 * i + 1]),
                  pack_bf16(c[8 * i + 2] + u[8 * i + 2], c[8 * i + 3] + u[8 * i + 3]), pack_bf16(c[8 * i + 4] + u[8 * i + 4], c[8 * i + 5] + u[8 * i + 5]),
                  pack_bf16(c[8 * i + 6] + u[8 * i + 6], c[8 * i + 7] + u[8 * i + 7]));
          }
          asm volatile("fence.proxy.async.shared::cta;" ::: "memory");
          __syncwarp();
          if (elect()) {
#pragma unroll
            for (int i = 0; i < 5; i++)
              tma3d_store(&P.out, stage[i >> 1] + (i & 1) * 8192, 0, ((job >> 7) & 7) * kSq + rank * 128 + wid * 16, ((job >> 10) & 1) * 20 + ((job >> 20) & 3) * 5 + i);
            asm volatile("cp.async.bulk.commit_group;\ncp.async.bulk.wait_group.read 0;" ::: "memory");
          }
          __syncwarp();
          break;
        }
        bi0 = take(rdy0, SZ_Q, ad0);
      first_step:
        undefine(o);
        wg_fence();
        mma4(ad0, 0);
        kend(bi0, 0);
        fence_regs(o);
      next_head:
        {
#pragma unroll 1
          for (int k = 1; k < ((op & F_PARK) ? 10 : 8); k++) {
            uint32_t ad;
            const int bi = take(rdy0, SZ_Q, ad);
            wg_fence();
            mma4(ad, 1);
            kend(bi, k);
          }
          if (op & F_PARK) {
            fence_regs(o);
            convert(0, 48);
            pend = ptr_add(P.g->tile, (((op >> 2) & 511) * 2 + rank) * SZ_PARK + img0 * 16);
            continue;
          }
          uint32_t a8, a9, ak0, ak1;
          const int b8 = take(rdy0, SZ_Q, a8), b9 = take(false, SZ_Q, a9);
          wg_fence();
          mma4(a8, 1);
          wg_commit();
          mma4(a9, 1);
          wg_commit();
          pc++;
          wg_wait<1>();
          release(b8);
          const int sk0 = take(false, SZ_KV, ak0);
          wg_wait<0>();
          fence_regs(o);
          release(b9);
          float s0[32];
          convert(0, 32);
          wg_fence();
          qk(s0, ak0, 0, 4);
          convert(32, 48);
          wg_fence();
          qk(s0, ak0, 4, 12);
          sk1 = take(false, SZ_KV, ak1);
          probe1();
          wg_wait<0>();
          first(s0, sk0, [&](int i) {
            if (i == 0) return;
            sched_fence(keep, never);
            wg_fence();
            if (i == 1) qk(s, ak1, 0, 4);
            if (i == 2) qk(s, ak1, 4, 8);
            if (i == 3) qk(s, ak1, 8, 12);
            sched_fence(keep, never);
          });
        }
        for (;;) {
          {
            uint32_t av;
            const int sv = take(rdy0, SZ_KV, av);
            undefine(o);
            wg_fence();
            pv(pa, av, 0);
            finish(pb, sk1, sv);
          }
          nop = prog[pc + 1];
#pragma unroll 1
          for (int jj = 0; jj < 7; jj++) {
            step(pb, pa);
            step(pa, pb);
          }
          float i0, i1;
          auto last = [&]() {
            uint32_t av;
            const int sv = take(rdy0, SZ_KV, av);
            wg_fence();
            pv(pb, av, 1);
            sched_fence(keep, never);
            probe1();
            l0 += __shfl_xor_sync(0xffffffffu, l0, 1); l1 += __shfl_xor_sync(0xffffffffu, l1, 1);
            l0 += __shfl_xor_sync(0xffffffffu, l0, 2); l1 += __shfl_xor_sync(0xffffffffu, l1, 2);
            i0 = rcp(l0); i1 = rcp(l1);
            pend = ptr_add(P.g->tile, (((op >> 2) & 511) * 2 + rank) * SZ_PARK + img0 * 16);
            return sv;
          };
          auto normalise = [&](uint32_t (&d)[48], auto mid) {
#pragma unroll
            for (int i = 0; i < 24; i++) {
              d[8 * (i >> 2) + (i & 3)] = pack_bf16(o[4 * i] * i0, o[4 * i + 1] * i0);
              d[8 * (i >> 2) + (i & 3) + 4] = pack_bf16(o[4 * i + 2] * i1, o[4 * i + 3] * i1);
              if ((i & 1) && i != 23) sched_fence(keep, never);
              if ((i & 3) == 3 && i != 23) mid(i >> 2);
            }
          };
          const int sv = last();
          if ((nop & 3) != OP_A) {
            op = nop;
            enter();
            pend_any = true;
            bi0 = take(rdy0 || (nop & 3) != OP_Q, SZ_Q, ad0);
            sched_fence(keep, never);
            wg_wait<0>();
            fence_regs(o);
            release(sv);
            normalise(q, [](int) {});
            undefine(o);
            if ((nop & 3) != OP_Q) break;
            sched_fence(keep, never);
            wg_fence();
            mma4(ad0, 0);
            pc++;
            kend(bi0, 0);
            fence_regs(o);
            goto next_head;
          }
          const int sk0 = unpark();
          wg_wait<1>();
          fence_regs(o);
          release(sv);
          uint32_t t[48];
          auto st = [&](int i) {
            stg2_if(true, pend + i * 512, t[8 * i], t[8 * i + 1], t[8 * i + 2], t[8 * i + 3], t[8 * i + 4], t[8 * i + 5], t[8 * i + 6], t[8 * i + 7], spol);
          };
          normalise(t, [&](int i) { if (!(i & 1)) st(i >> 1); });
          wg_wait<0>();
          first(s, sk0, [&](int i) { if (i < 3) { sched_fence(keep, never); st(3 + i); } });
          __syncwarp();
          mbar_arrive_if(lane == 0, odone0 + 8 * pc);
          pc++;
          op = nop;
          uint32_t ak1;
          sk1 = take(rdy0, SZ_KV, ak1);
          rdy0 = rdy1;
          wg_fence();
          qk(s, ak1);
        }
      }
    }
    asm volatile("barrier.cluster.wait;" ::: "memory");
  } else {
    asm volatile("setmaxnreg.dec.sync.aligned.u32 24;");
    const uint32_t* prog = P.prog[role].p;
    unsigned int* flag = P.g->flag + rank;
    if (wid == 11 && (prog[0] & 3) == OP_Q) {
      const uint32_t a = prog[1];
      const char* p = ptr_add(P.kv[rank * 2 + ((a >> 10) & 1)], ((a >> 2) & 255) * (kSk * kDh * 2) + (threadIdx.x & 31) * 128);
#pragma unroll 1
      for (uint32_t k = 0; k < 3; k++) {
        wait_word(progress, k);
        p += SZ_KV;
        asm volatile("prefetch.global.L2 [%0];\nprefetch.global.L2 [%0 + 4096];" ::"l"(p));
      }
      __syncwarp();
    }
    if (wid == 8) {
      Cursor tail{0, 0};
      int head = 0, sh = 0;
      uint32_t cur = 0, used = 0;
      uint64_t fifo = 0;
      uint32_t dst, bar, ev = ev0, done = 0;
      const uint64_t pol = evict_first();
      auto retire = [&]() {
        mbar_wait(empty0 + 8 * tail.bi, tail.ph);
        tail.next();
        used -= (uint32_t)fifo & 31;
        fifo >>= 5;
        sh -= 5;
        asm volatile("st.volatile.shared.u32 [%0], %1;" ::"r"(progress), "r"(++done) : "memory");
      };
      auto acquire = [&](uint32_t bytes) {
        uint32_t fp = bytes >> 12;
        if (cur + fp > (RING >> 12)) { fp += (RING >> 12) - cur; cur = 0; }
        used += fp;
        while (used > (RING >> 12) || sh == 5 * NBAR) retire();
        fifo |= (uint64_t)fp << sh;
        sh += 5;
        dst = sbase + (cur << 12);
        bar = full0 + 8 * head;
        cur += bytes >> 12;
        if (++head == NBAR) head = 0;
      };
      auto gate = [&]() {
        mbar_wait(ev, 0);
        ev += 8;
        asm volatile("fence.proxy.async.global;" ::: "memory");
      };
      for (int pc = 0;; pc++) {
        uint32_t op = prog[pc];
        const int type = op & 3;
        if (type == OP_END) break;
        if (op == OP_O) {
          gate();
          op = __shfl_sync(0xffffffffu, lds32(jobw), 0);
        }
        const int blk = (op >> 10) & 1;
        if (type == OP_Q) {
#pragma unroll 1
          for (int k = 0; k < 10; k++) {
            if (k == 9 && (op & P_GATE)) gate();
            acquire(SZ_Q);
            if ((pc > 0 || k >= EARLY) && elect()) {
              mbar_expect(bar, SZ_Q);
              tma2d(dst, &P.x[blk], bar, 64 * k, ((op >> 7) & 7) * kSq + rank * 128);
              if ((k & 1) == rank) tma3d_mc(dst + 16384, &P.wq[blk], bar, 0, 64 * k, 3 * ((op >> 2) & 31));
            }
          }
        } else if (type == OP_A) {
          const int row0 = ((op >> 2) & 255) * kSk;
          const CUtensorMap* kv_map = rank ? &P.v[blk] : &P.k[blk];
          if (op & F_PARK) {
            gate();
            acquire(SZ_PARK);
            if (elect()) {
              mbar_expect(bar, SZ_PARK);
              bulk_load_hint(dst, &P.g->tile[((op >> 20) * 2 + rank) * 3072], SZ_PARK, bar, pol);
            }
          }
#pragma unroll 1
          for (int t = 0; t < 32; t++) {
            const int isv = t == 31 ? 1 : (t == 0 ? 0 : (~t & 1));
            const int j = isv ? (t - 1) >> 1 : (t + 1) >> 1;
            if (t == 31 && (op & P_GATE)) gate();
            acquire(SZ_KV);
            if (elect()) {
              mbar_expect(bar, SZ_KV);
              if (isv == (int)rank) tma4d_mc_hint(dst, kv_map, bar, row0 / 8 + 8 * j, pol);
            }
          }
        } else {
          const int n = (op >> 13) & 127, nw = (op & P_WIDE) ? n - TAIL : 0;
          const uint4* part = &P.g->part[((((op >> 6) & 30) + ((op >> 21) & 1)) * 2 + rank) * 5120 + ((op >> 20) & 1) * 2560];
#pragma unroll 1
          for (int i = 0; i < n + (nw ? TAIL : 0); i++) {
            const int k = nw ? (i < n ? i : i - TAIL) : kSteps - n + i, h = (k * 43) >> 7, col = 5 * ((op >> 20) & 3);
            const uint4* src = &P.g->tile[(P.slot[((op >> 2) & 480) + h] * 2 + rank) * 3072 + (k - 3 * h) * 1024];
            const uint32_t j = (op & P_LD) ? i - n + 5 : 5, bytes = i < nw ? SZ_W : nw ? (i < n ? SZ_W2 : SZ_W3) : j < 5 ? SZ_OL : SZ_O;
            if ((op & P_PRE) ? i == 0 : j == 0) gate();
            if (i < n && (i == 0 || k == 3 * h)) gate();
            acquire(bytes);
            if (elect()) {
              mbar_expect(bar, bytes);
              if (bytes != SZ_W2) tma5d_mc(dst + 16384 + rank * (nw ? 12288 : 10240), nw ? &P.wo3[blk] : &P.wo[blk], bar, 8 * k + 4 * rank, nw ? col / 2 : col);
              bulk_load_hint(dst, src, 16384, bar, pol);
              if (nw && i < n) tma5d_mc(dst + bytes - 16384 + rank * 8192, &P.wo2[blk], bar, 8 * k + 4 * rank, col / 2 + 3);
              if (j < 5) bulk_load_hint(dst + SZ_O, part + j * 512, 8192, bar, pol);
              if ((op & P_PRE) && i < 10) asm volatile("cp.async.bulk.prefetch.L2.global [%0], 4096;" ::"l"(part + i * 256) : "memory");
            }
          }
        }
      }
#pragma unroll 1
      while (sh) retire();
    } else if (threadIdx.x == 288) {
      for (int pc = 0;; pc++) {
        const uint32_t op = prog[pc];
        const int type = op & 3;
        if (type == OP_END) break;
        if (type == OP_Q ? !(op & F_PARK) : type == OP_O && !(op & P_WIDE)) continue;
        const int id = type == OP_A ? (op >> 2) & 511 : type == OP_Q ? N_TILE + ((op >> 13) & 127) : ID_PART + ((op >> 5) & 60) + ((op >> 20) & 3);
        const uint32_t v = type == OP_O ? 1 : P.info[id] & 7;
        mbar_wait_long(odone0 + 8 * pc);
        flag_set(flag + 2 * id, v);
        if (type == OP_O && (op & P_WIDE)) flag_set(flag + 2 * id + 2, v);
      }
    } else if (wid == 10) {
      int i = threadIdx.x & 31;
      const int n_ev = P.prog[role].n_ev;
      auto event = [&]() { return i < n_ev ? P.prog[role].ev[i] : n_ev ? E_JOB | (i - n_ev) : 0; };
      uint32_t e = i < 8 ? event() : 0;
      for (uint32_t n = 0; __any_sync(0xffffffffu, e); n++) {
        uint32_t job = lds32(jobw);
        const int togo = (e & E_DRAW) ? (e & 1023) - lds32(progress) : 99;
        if (togo <= 0 && rank == 0) {
          job = P.job[atomicInc(&P.g->ticket, gridDim.x / 2 - 1)];
          asm volatile("{\n.reg .u32 a;\nmapa.shared::cluster.u32 a, %0, 1;\nst.volatile.shared::cluster.u32 [a], %1;\n"
                       "st.volatile.shared.u32 [%0], %1;\n}\n" ::"r"(jobw), "r"(job) : "memory");
        }
        if ((e & E_JOB) && job) {
          const uint32_t j = e & 63, heads = job == OP_O ? 0 : kH - ((job >> 2) & 31), jp = !(job & P_LD) ? 63 : (job & P_PRE) ? 0 : heads - 1, h = j - (j > jp);
          e = j == jp ? (ID_PART + ((job >> 5) & 60) + ((job >> 20) & 3)) | E_ON | E_LAST : h < heads ? (((job >> 2) & 511) + h) | E_ON | E_LAST : 0;
        }
        unsigned int* f = ptr_add(flag, 8 * (e & 1023));
        const bool ok = (e & E_ON) ? flag_get(f) - 1 < ((e & E_FREE) ? 1 : 7) : (e & E_DRAW) && job;
        if (ok) {
          mbar_arrive(ev0 + 8 * i);
          if (e & (E_FREE | E_LAST)) flag_dec(f);
          i += 8;
          e = event();
        }
        asm volatile("{\n.reg .pred p;\nsetp.ge.u32 p, %0, 0x400000;\n@p trap;\n}\n" ::"r"(n));
        if (!__any_sync(0xffffffffu, ok)) __nanosleep(__any_sync(0xffffffffu, job || togo <= 2) ? 100 : 600);
      }
    } else if (threadIdx.x == 352) {
      uint32_t items = 0;
      auto read = [&](int id) {
        if (!(P.info[id] & I_NEXT)) return;
        wait_word(progress, items);
        flag_dec(flag + 2 * id);
      };
      for (int pc = 0;; pc++) {
        const uint32_t op = prog[pc];
        const int type = op & 3;
        if (type == OP_END) break;
        if (type == OP_O) {
          const uint32_t n = (op >> 13) & 127, base = items;
#pragma unroll 1
          for (uint32_t k = 3, id = (op >> 2) & 511; k <= n; k += 3, id++) {
            items = base + k + (k + TAIL > n ? TAIL : 0);
            read(id);
          }
          items = base + n + TAIL;
        } else if (type == OP_A) {
          if (op & F_PARK) { items++; read(N_TILE + ((op >> 13) & 127)); }
          items += 32;
        } else {
          items += 10;
        }
      }
    }
    __syncwarp();
    asm volatile("barrier.cluster.arrive.relaxed;\nbarrier.cluster.wait;" ::: "memory");
  }
}

typedef CUresult (*EncodeFn)(CUtensorMap*, CUtensorMapDataType, cuuint32_t, void*, const cuuint64_t*, const cuuint64_t*,
                             const cuuint32_t*, const cuuint32_t*, CUtensorMapInterleave, CUtensorMapSwizzle,
                             CUtensorMapL2promotion, CUtensorMapFloatOOBfill);

void encode(EncodeFn fn, CUtensorMap* m, const void* ptr, int rank, const cuuint64_t* dims, const cuuint64_t* strides,
            const cuuint32_t* box, CUtensorMapSwizzle swz) {
  const cuuint32_t es[5] = {1, 1, 1, 1, 1};
  CUresult r = fn(m, CU_TENSOR_MAP_DATA_TYPE_BFLOAT16, rank, const_cast<void*>(ptr), dims, strides, box, es,
                  CU_TENSOR_MAP_INTERLEAVE_NONE, swz, CU_TENSOR_MAP_L2_PROMOTION_L2_128B, CU_TENSOR_MAP_FLOAT_OOB_FILL_NONE);
  if (r != CUDA_SUCCESS) fprintf(stderr, "cuTensorMapEncodeTiled failed: %d\n", (int)r);
}

struct Op { int type, flags, id, n, quarter, park, item0, items; double t0, t1; };
struct Use { double ready, gate, need, freed; int readers, slot, prev; bool next; };
struct PlanStats { double end, slack, park_slack; int slots, parks; uint32_t own[N_CL]; };

bool plan(const char* const* text, int n_pair, int phase, Params& P, PlanStats* stats = nullptr) {
  constexpr double T_Q = 7900, T_A = 24800, T_U = TU, T_O = 640, T_RUN = 800, T_WIDE = TW, AHEAD = 3500, PUBLISH = 1500;
  const double margin = 256.0 * ((P.dbg >> 8) & 255);
  static Op op[N_CL][MAX_OPS];
  static Use use[ID_PART];
  int n_op[N_CL], covered[2 * N_TEAM] = {};
  struct Ref { double t; Op* o; int id; };
  static Ref att[N_TILE + 1], dem[N_TILE], prk[MAX_PARK + 1], unp[MAX_PARK + 1], wr[ID_PART];
  auto sort = [](Ref* r, int n) {
    for (int i = 1; i < n; i++)
      for (int j = i; j > 0 && r[j].t < r[j - 1].t; j--) { Ref x = r[j]; r[j] = r[j - 1]; r[j - 1] = x; }
  };
  auto hex = [](char c) { return c <= '9' ? c - '0' : c - 'a' + 10; };
  for (int i = 0; i < n_pair; i++)
    for (const char* s = text[i]; *s; s++)
      for (int h = 0; *s == 'J' && h < 2; h++) {
        if (covered[2 * hex(s[1]) + h]) return false;
        covered[2 * hex(s[1]) + h] = 10 * (s[2 + 2 * h] - '0') + s[3 + 2 * h] - '0';
      }
  for (int c = 0; c < 2 * n_pair; c++) {
    int n = 0, items = 0;
    double t = 0;
    auto add = [&](int type, int flags, int id, int heads, int quarter, int its, double dt) {
      if (n < MAX_OPS) op[c][n] = {type, flags, id, heads, quarter, 0, items, its, t, t + dt};
      n++; items += its; t += dt;
    };
    for (const char* s = text[c >> 1]; *s; s++) {
      const int tm = hex(s[1]) & 15, nj = covered[2 * tm + (c & 1)];
      if (*s == 'N') { add(OP_Q, 0, 0, 0, 0, 10, T_Q); add(OP_A, 0, 0, 0, 0, 32, T_A); }
      if (*s == 'P') add(OP_Q, F_PARK, 0, 0, 0, 10, T_Q + TP);
      if (*s == '+' || *s == '-') t += *s == '+' ? 1000 : -1000;
      if (*s == 'U') { if (n == 0 || n > MAX_OPS || op[c][n - 1].type != OP_A) return false; add(OP_A, F_PARK, 0, 0, 0, 33, T_U); }
      if (*s == 'J') { if (nj < TAIL + 6 || nj > kSteps - 11) return false; add(OP_O, P_WIDE, tm * kH, nj, 2 * (c & 1), nj + TAIL, 2 * T_O * nj + T_WIDE); }
    }
    add(OP_O, 0, 0, 0, 0, 0, 0);
    add(OP_END, 0, 0, 0, 0, 0, 0);
    if (n > MAX_OPS || op[c][0].type != OP_Q) return false;
    n_op[c] = n - 1;
    att[c] = {t, &op[c][n - 2], 0};
  }
  for (int i = 0; i < 4 * N_TEAM; i++) dem[i] = {(double)covered[i / 2], nullptr, i};
  sort(att, 2 * n_pair); sort(dem, 4 * N_TEAM);
  for (int i = 0; i < 4 * N_TEAM; i++) {
    Op* f = att[i].o;
    const int nj = covered[dem[i].id / 2];
    f->flags = nj ? P_LD : 0;
    f->id = dem[i].id / 4 * kH + nj / 3; f->quarter = dem[i].id & 3; f->items = f->n = kSteps - nj;
    f[1].t0 = f[1].t1 = f->t1 = f->t0 + T_O * f->n + T_RUN; f[1].item0 += f->n;
  }
  for (int i = 0; i < ID_PART; i++) use[i] = {0, 0, 1e18, 0, 0, 0, 0, false};
  int n_att = 0, n_prk = 0, n_unp = 0;
  auto ready = [&](const Op* o) {
    const int nt = o[1].type;
    return o->t1 + (nt == OP_Q ? 6100 : o[1].n ? ((o[1].flags & P_WIDE) ? 7700 : 3900) : 1500) + PUBLISH;
  };
  for (int c = 0; c < 2 * n_pair; c++)
    for (Op* o = op[c]; o->type != OP_END; o++) {
      if (o->type == OP_A) { att[n_att] = {ready(o), o, 0}; if (++n_att > N_TILE) return false; }
      if (o->type == OP_A && o->flags) { unp[n_unp] = {o->t0 - AHEAD, o, 0}; if (++n_unp > MAX_PARK) return false; }
      if (o->type == OP_Q && o->flags) { prk[n_prk] = {ready(o), o, 0}; if (++n_prk > MAX_PARK) return false; }
      for (int i = 0; o->type == OP_O && i < o->n; i++) {
        const int nw = (o->flags & P_WIDE) ? o->n - TAIL : 0, k = nw ? i : kSteps - o->n + i;
        Use& u = use[o->id / kH * kH + k / 3];
        const double t = o->t0 + T_O * (i + (i < nw ? i : nw));
        if (t - AHEAD < u.need) u.need = t - AHEAD;
        const double f = !nw ? 1e18 : i + NBAR < o->items - TAIL || (nw && o[1].type != OP_O) ? t + T_O * (i < nw ? 2 : 1 + TAIL) + PUBLISH : 1e18;
        if (f > u.freed) u.freed = f;
        if (i == 0 || k % 3 == 0) u.readers++;
      }
    }
  if (n_att != N_TILE || n_prk != n_unp) return false;
  for (int i = 0; i < N_TILE; i++) { const int id = (i & 15) * kH + (i >> 4); dem[i] = {use[id].need, nullptr, id}; }
  sort(att, n_att); sort(dem, N_TILE); sort(prk, n_prk); sort(unp, n_unp);
  PlanStats st = {0, 1e18, 1e18, 0, n_prk};
  int n_wr = 0;
  for (int i = 0; i < N_TILE; i++) {
    Op* o = att[i].o;
    o->id = dem[i].id;
    if (!o->flags) o[-1].id = o->id;
    if (dem[i].t - att[i].t < st.slack) st.slack = dem[i].t - att[i].t;
    wr[n_wr++] = {o->t1 - 2 * AHEAD, o, o->id};
  }
  for (int i = 0; i < n_prk; i++) {
    prk[i].o->id = unp[i].o->id;
    prk[i].o->park = unp[i].o->park = i;
    use[N_TILE + i].freed = unp[i].o->t0 + 2 * PUBLISH;
    use[N_TILE + i].readers = 1;
    if (unp[i].t - prk[i].t < st.park_slack) st.park_slack = unp[i].t - prk[i].t;
    wr[n_wr++] = {prk[i].o->t1 - 2 * AHEAD, prk[i].o, N_TILE + i};
  }
  for (int c = 0; c < 2 * n_pair; c++)
    for (int d = 0; d < 2 * n_pair; d++)
      for (Op *f = &op[c][n_op[c] - 1], *o = op[d]; f->n && o->type != OP_END; o++)
        if (o->type == OP_O && (o->flags & P_WIDE) && o->id / kH == f->id / kH && o->quarter / 2 == f->quarter / 2) {
          if (f->t0 - o->t1 > 4096.0 * ((P.dbg >> 16) & 255)) f->flags |= P_PRE;
          const double slack = f->t0 + ((f->flags & P_PRE) ? 0 : (f->n - 5) * T_O) - AHEAD - ready(o);
          if (slack < st.park_slack) st.park_slack = slack;
        }
  sort(wr, n_wr);
  int holder[N_TILE];
  for (int i = 0; i < n_wr; i++) {
    int best = -1;
    for (int sl = 0; sl < st.slots; sl++)
      if (use[holder[sl]].freed + margin <= wr[i].t && (best < 0 || use[holder[sl]].freed < use[holder[best]].freed)) best = sl;
    Use& u = use[wr[i].id];
    if (best >= 0) { u.prev = holder[best]; use[u.prev].next = true; wr[i].o->flags |= P_GATE; }
    else if (st.slots == N_TILE) return false;
    else best = st.slots++;
    u.slot = best;
    holder[best] = wr[i].id;
  }
  {
    int pos[N_CL] = {}, flag[ID_PART + 4 * N_TEAM] = {}, seen[ID_PART] = {};
    auto goal = [&](int c) { return op[c][n_op[c] - 1].item0; };
    for (bool moved = true; moved;) {
      moved = false;
      for (int c = 0; c < 2 * n_pair; c++) {
        for (; pos[c] < goal(c); pos[c]++, moved = true) {
          bool ok = true;
          for (const Op* o = op[c]; o->type != OP_END; o++) {
            const int k = pos[c] - o->item0, own = o->type == OP_A ? o->id : N_TILE + o->park;
            if (k < 0 || k >= o->items) continue;
            if (o->type == OP_O) ok = k >= o->n || flag[o->id + k / 3];
            else if (k == o->items - 1 && (o->flags & P_GATE)) ok = seen[use[own].prev] == use[use[own].prev].readers;
            else if (k == 0 && o->type == OP_A && (o->flags & F_PARK)) ok = flag[N_TILE + o->park];
          }
          if (!ok) break;
          for (const Op* o = op[c]; o->type != OP_END; o++) {
            if (pos[c] == o->item0 + o->items + (o[1].type == OP_Q ? 7 : o[1].item0 == goal(c) ? -1 : 5)) {
              if (o->type == OP_A) flag[o->id] = 1;
              if (o->type == OP_Q && (o->flags & F_PARK)) flag[N_TILE + o->park] = 1;
              if (o->type == OP_O) flag[ID_PART + o->id / kH * 4 + o->quarter] = flag[ID_PART + o->id / kH * 4 + o->quarter + 1] = 1;
            }
            const int k = pos[c] - NBAR - o->item0, nw = o->n - TAIL;
            if (k == 0 && o->type == OP_A && (o->flags & F_PARK)) seen[N_TILE + o->park]++;
            if (o->type == OP_O && k >= 0 && k < o->items && (k < nw || k >= o->n) && (k < nw ? k : k - TAIL) % 3 == 2) seen[o->id + (k < nw ? k : k - TAIL) / 3]++;
          }
        }
      }
    }
    for (int c = 0; c < 2 * n_pair; c++) if (pos[c] < goal(c)) return false;
  }
  int n_job = 0;
  for (int c = 0; c < 2 * n_pair; c++) {
    uint32_t items = 0, cur = 0, pend = 0;
    int n = 0, ev = 0;
    auto item = [&](uint32_t bytes, int count) {
      for (int i = 0; i < count; i++) { if (cur + bytes > RING) cur = 0; cur += bytes; items++; }
    };
    auto event = [&](uint32_t e) { if (ev < MAX_TAB) P.prog[c].ev[ev] = e; ev++; };
    for (const Op* o = op[c];; o++) {
      if (o->type != OP_END && phase && (o->type == OP_O) != (phase == 2)) continue;
      uint32_t cw = o->type | (items % NBAR) << 15 | ((items / NBAR) & 1) << 19 | (cur >> 12) << 20 | pend, pw = o->type | o->id << 2 | o->flags;
      const int ps = use[N_TILE + o->park].slot;
      pend = 0;
      if (o->type == OP_O) {
        pw |= o->n << 13 | o->quarter << 20;
        if (o->flags & P_WIDE) {
          cw |= o->n << 2 | (o->id / kH * 2 + o->quarter / 2) << 9 | C_WIDE;
          item(SZ_W, o->n - TAIL);
          item(SZ_W2, TAIL);
          item(SZ_W3, TAIL);
          pend = C_PEND;
          for (int i = 0; 3 * i < o->n; i++) event((o->id + i) | E_ON | (use[o->id + i].next ? 0 : E_LAST));
        } else {
          dem[n_job++] = {o->t0 - 1e6 * o->n, nullptr, (int)pw};
          st.own[c] = pw;
          pw = OP_O;
          event(E_DRAW | (items < 16 ? 0 : items - 16));
        }
      } else if (o->type != OP_END) {
        const bool parks = o->type == OP_Q && (o->flags & F_PARK);
        cw |= (parks ? ps : use[o->id].slot) << 2 | (o->flags & F_PARK);
        if (o->flags & F_PARK) pw |= o->park << 13 | ps << 20;
        if (o->type == OP_Q) item(SZ_Q, 10);
        else { if (o->flags & F_PARK) { item(SZ_PARK, 1); event((N_TILE + o->park) | E_ON | (use[N_TILE + o->park].next ? 0 : E_LAST)); } item(SZ_KV, 32); }
        if (parks || o->type == OP_A) pend = C_PEND;
        if (o->flags & P_GATE) event(use[parks ? N_TILE + o->park : o->id].prev | E_ON | E_FREE);
      }
      P.prog[c].c[n] = cw; P.prog[c].p[n++] = pw;
      if (o->type == OP_END) { if (o->t0 > st.end) st.end = o->t0; break; }
    }
    if (ev > MAX_TAB) return false;
    P.prog[c].n_ev = ev;
    while (n < MAX_OPS) { P.prog[c].c[n] = OP_END; P.prog[c].p[n++] = OP_END; }
    P.first[c] = (uint16_t)(P.prog[c].p[0] & 2047);
  }
  sort(dem, n_job);
  for (int i = 0; i < n_job; i++) P.job[i] = dem[i].id;
  for (int i = 0; i < ID_PART; i++) {
    if (i < N_TILE) P.slot[i] = use[i].slot;
    P.info[i] = (use[i].readers + use[i].next) | (use[i].next ? I_NEXT : 0);
  }
  if (stats) *stats = st;
  return true;
}

const char* const kPrograms[N_CL / 2] = {
  "PNJ06565NNNNN", "PNJ15858NNNNN", "PNJ25656NNNNN", "PNJ35454+NNNNN", "PNJ47878NNNNN", "PNJ57373NNNNN",
  "NNJ68080NNNN", "NNJ76868NNNN", "NNNNNJ83535NN", "NNNNNNJf4343N", "NNNNNJa5252NN", "NNNNNJb4848NN",
  "NUNNNNNNN", "NUNNNJd5353NN", "NUNNNJe6363NN", "NNNNNJ97676N", "PNNNNNNNNN", "PNNNNNNNNN",
  "PNNNNNNNNN", "PNNNNNNNNN", "PNNNNNNNNN", "NNNNNNNNN", "NNNNNNNNN", "NNNNNNNNN",
  "NUNNNNNNN", "NNNNNNNNN", "NUNNNNNNN", "NUNNNNNNN", "NNUNNNNNN", "NUNNNNNNN",
  "NUNNNNNNN", "NNUNNJc5353NN", "NUNNNNNNN",
};

const char* const* bench_programs() {
  return kPrograms;
}

}

extern "C" void kernel_launch(void* const* d_in, const int* in_sizes, int n_in, void* d_out, int out_size) {
  (void)in_sizes; (void)n_in; (void)out_size;
  static EncodeFn fn = nullptr;
  static int n_clusters = 0;
  if (!fn) {
    cudaDriverEntryPointQueryResult qr;
    void* f = nullptr;
    cudaGetDriverEntryPoint("cuTensorMapEncodeTiled", &f, cudaEnableDefault, &qr);
    fn = (EncodeFn)f;
    cudaFuncSetAttribute(fused_kernel, cudaFuncAttributeMaxDynamicSharedMemorySize, SMEM_BYTES);
    cudaLaunchConfig_t cfg = {};
    cfg.gridDim = dim3(132); cfg.blockDim = dim3(384); cfg.dynamicSmemBytes = SMEM_BYTES;
    cudaLaunchAttribute at[1];
    at[0].id = cudaLaunchAttributeClusterDimension; at[0].val.clusterDim.x = 2; at[0].val.clusterDim.y = 1; at[0].val.clusterDim.z = 1;
    cfg.attrs = at; cfg.numAttrs = 1;
    if (cudaOccupancyMaxActiveClusters(&n_clusters, fused_kernel, &cfg) != cudaSuccess || n_clusters < 1) n_clusters = 1;
    (void)cudaGetLastError();
  }
  static Params P;
  const CUtensorMapSwizzle S128 = CU_TENSOR_MAP_SWIZZLE_128B, S64 = CU_TENSOR_MAP_SWIZZLE_64B;
  for (int blk = 0; blk < 2; blk++) {
    void* const* in = d_in + 5 * blk;
    { const cuuint64_t d[] = {kD, kB * kSq}, s[] = {kD * 2}; const cuuint32_t b[] = {64, 128};
      encode(fn, &P.x[blk], in[0], 2, d, s, b, S128); }
    { const cuuint64_t d[] = {64, 8, 3, (cuuint64_t)kB * kH * kSk / 8}, s[] = {kDh * 2, 128, 8 * kDh * 2}; const cuuint32_t b[] = {64, 8, 3, 8};
      encode(fn, &P.k[blk], in[1], 4, d, s, b, S128);
      encode(fn, &P.v[blk], in[2], 4, d, s, b, S128); }
    { const cuuint64_t d[] = {64, kD, kHD / 64}, s[] = {kHD * 2, 128}; const cuuint32_t b[] = {64, 64, 3};
      encode(fn, &P.wq[blk], in[3], 3, d, s, b, S128); }
    { const cuuint64_t d[] = {32, 2, kHD / 8, 4, kD / 32}, s[] = {kD * 2, 8 * kD * 2, 2 * kD * 2, 64}; const cuuint32_t b[] = {32, 2, 4, 4, 5};
      encode(fn, &P.wo[blk], in[4], 5, d, s, b, S64); }
    { const cuuint64_t d[] = {64, 2, kHD / 8, 4, kD / 64}, s[] = {kD * 2, 8 * kD * 2, 2 * kD * 2, 128};
      const cuuint32_t b3[] = {64, 2, 4, 4, 3}, b2[] = {64, 2, 4, 4, 2};
      encode(fn, &P.wo3[blk], in[4], 5, d, s, b3, S128);
      encode(fn, &P.wo2[blk], in[4], 5, d, s, b2, S128); }
  }
  { const cuuint64_t d[] = {32, kB * kSq, 2 * kD / 32}, s[] = {2 * kD * 2, 64}; const cuuint32_t b[] = {32, 16, 1};
    encode(fn, &P.out, d_out, 3, d, s, b, S64); }

  P.kv[0] = (const char*)d_in[1]; P.kv[1] = (const char*)d_in[6]; P.kv[2] = (const char*)d_in[2]; P.kv[3] = (const char*)d_in[7];
  P.xw[0] = (const char*)d_in[0]; P.xw[1] = (const char*)d_in[3];
  cudaGetSymbolAddress((void**)&P.g, g_scratch);
  P.dbg = DBG_DEFAULT;
  if (n_clusters >= N_CL && plan(bench_programs(), N_CL / 2, 0, P)) {
    fused_kernel<<<2 * N_CL, 384, SMEM_BYTES>>>(P);
  } else {
    const char* text[2 * N_TEAM];
    for (int i = 0; i < 2 * N_TEAM; i++) text[i] = "NNNNNNNN";
    for (int phase = 1; phase <= 2; phase++) {
      plan(text, 2 * N_TEAM, phase, P);
      fused_kernel<<<8 * N_TEAM, 384, SMEM_BYTES>>>(P);
    }
  }
}
```

```cpp
#include <cuda_runtime.h>
#include <cuda_bf16.h>
#include <cuda.h>
#include <stdint.h>
#include <stdio.h>

namespace {

constexpr int kB = 8, kSq = 256, kD = 640, kH = 32, kSk = 1024, kDh = 192;
constexpr int kHD = kH * kDh;
constexpr uint32_t RING = 224 * 1024;
constexpr uint32_t SZ_KV = 24576;
constexpr uint32_t SZ_Q = 16384 + 24576;
constexpr uint32_t SZ_O = 16384 + 20480;
constexpr uint32_t SZ_W3 = 16384 + 24576, SZ_W2 = 16384 + 16384, SZ_W = SZ_W3 + 16384;
constexpr uint32_t SZ_PARK = 49152;
constexpr uint32_t SZ_OL = SZ_O + 8192;
constexpr int NBAR = 10;
constexpr int EARLY = 3;
constexpr int kSteps = kHD / 64;
constexpr int TAIL = 4;
constexpr uint32_t KV_CH = 64, KV_SBO = 3072;
constexpr int SMEM_BYTES = RING + 1024 + 1024;
constexpr int N_TEAM = 16, N_CL = 66, MAX_OPS = 22, MAX_EV = 80, MAX_TAB = 47, N_TILE = N_TEAM * kH, MAX_PARK = 128, ID_PART = N_TILE + MAX_PARK;
enum : uint32_t { OP_END = 0, OP_Q = 1, OP_A = 2, OP_O = 3, F_PARK = 1 << 11,
                  C_WIDE = 1 << 27, C_PEND = 1 << 26, P_GATE = 1 << 12, P_WIDE = 1 << 11, P_LD = 1 << 12, P_PRE = 1 << 22,
                  I_NEXT = 8, E_ON = 1 << 15, E_FREE = 1 << 14, E_LAST = 1 << 13, E_DRAW = 1 << 12, E_JOB = 1 << 11 };

#define TU 25900
#define TW 1600
#define TP 1000
constexpr uint32_t DBG_DEFAULT = 0x040800;

struct alignas(1024) Scratch {
  unsigned int flag[2047];
  unsigned int ticket;
  uint4 part[N_TEAM * 2 * 2 * 5120];
  uint4 tile[N_TILE * 2 * 3072];
};

struct alignas(64) Params {
  const char* xw[2];
  uint16_t first[80];
  Scratch* g;
  uint32_t dbg;
  CUtensorMap x[2], wq[2], k[2], v[2], wo[2], wo3[2], wo2[2], out;
  struct {
    uint32_t c[MAX_OPS];
    uint32_t p[MAX_OPS];
    uint16_t n_ev, ev[MAX_TAB];
  } prog[N_CL];
  const char* kv[4];
  uint32_t job[N_CL];
  uint16_t slot[N_TILE];
  uint8_t info[ID_PART];
};

__device__ Scratch g_scratch;

template <int TB, int TA = 0>
__device__ __forceinline__ void wgmma_ss_n64(float (&d)[32], uint64_t da, uint64_t db, int scale_d) {
  asm volatile("{\n.reg .pred p;\nsetp.ne.b32 p, %34, 0;\n"
    "wgmma.mma_async.sync.aligned.m64n64k16.f32.bf16.bf16 {%0, %1, %2, %3, %4, %5, %6, %7, %8, %9, %10, %11, %12, %13, %14, %15, %16, %17, %18, %19, %20, %21, %22, %23, %24, %25, %26, %27, %28, %29, %30, %31}, %32, %33, p, 1, 1, %35, %36;\n}\n"
    : "+f"(d[0]), "+f"(d[1]), "+f"(d[2]), "+f"(d[3]), "+f"(d[4]), "+f"(d[5]), "+f"(d[6]), "+f"(d[7]), "+f"(d[8]), "+f"(d[9]), "+f"(d[10]), "+f"(d[11]), "+f"(d[12]), "+f"(d[13]), "+f"(d[14]), "+f"(d[15]), "+f"(d[16]), "+f"(d[17]), "+f"(d[18]), "+f"(d[19]), "+f"(d[20]), "+f"(d[21]), "+f"(d[22]), "+f"(d[23]), "+f"(d[24]), "+f"(d[25]), "+f"(d[26]), "+f"(d[27]), "+f"(d[28]), "+f"(d[29]), "+f"(d[30]), "+f"(d[31])
    : "l"(da), "l"(db), "r"(scale_d), "n"(TA), "n"(TB));
}
template <int TB>
__device__ __forceinline__ void wgmma_rs_n64(float (&d)[32], uint32_t a0, uint32_t a1, uint32_t a2, uint32_t a3, uint64_t db, int scale_d) {
  asm volatile("{\n.reg .pred p;\nsetp.ne.b32 p, %37, 0;\n"
    "wgmma.mma_async.sync.aligned.m64n64k16.f32.bf16.bf16 {%0, %1, %2, %3, %4, %5, %6, %7, %8, %9, %10, %11, %12, %13, %14, %15, %16, %17, %18, %19, %20, %21, %22, %23, %24, %25, %26, %27, %28, %29, %30, %31}, {%32, %33, %34, %35}, %36, p, 1, 1, %38;\n}\n"
    : "+f"(d[0]), "+f"(d[1]), "+f"(d[2]), "+f"(d[3]), "+f"(d[4]), "+f"(d[5]), "+f"(d[6]), "+f"(d[7]), "+f"(d[8]), "+f"(d[9]), "+f"(d[10]), "+f"(d[11]), "+f"(d[12]), "+f"(d[13]), "+f"(d[14]), "+f"(d[15]), "+f"(d[16]), "+f"(d[17]), "+f"(d[18]), "+f"(d[19]), "+f"(d[20]), "+f"(d[21]), "+f"(d[22]), "+f"(d[23]), "+f"(d[24]), "+f"(d[25]), "+f"(d[26]), "+f"(d[27]), "+f"(d[28]), "+f"(d[29]), "+f"(d[30]), "+f"(d[31])
    : "r"(a0), "r"(a1), "r"(a2), "r"(a3), "l"(db), "r"(scale_d), "n"(TB));
}
template <int TB, int TA = 0>
__device__ __forceinline__ void wgmma_ss_n128(float (&d)[64], uint64_t da, uint64_t db, int scale_d) {
  asm volatile("{\n.reg .pred p;\nsetp.ne.b32 p, %66, 0;\n"
    "wgmma.mma_async.sync.aligned.m64n128k16.f32.bf16.bf16 {%0, %1, %2, %3, %4, %5, %6, %7, %8, %9, %10, %11, %12, %13, %14, %15, %16, %17, %18, %19, %20, %21, %22, %23, %24, %25, %26, %27, %28, %29, %30, %31, %32, %33, %34, %35, %36, %37, %38, %39, %40, %41, %42, %43, %44, %45, %46, %47, %48, %49, %50, %51, %52, %53, %54, %55, %56, %57, %58, %59, %60, %61, %62, %63}, %64, %65, p, 1, 1, %67, %68;\n}\n"
    : "+f"(d[0]), "+f"(d[1]), "+f"(d[2]), "+f"(d[3]), "+f"(d[4]), "+f"(d[5]), "+f"(d[6]), "+f"(d[7]), "+f"(d[8]), "+f"(d[9]), "+f"(d[10]), "+f"(d[11]), "+f"(d[12]), "+f"(d[13]), "+f"(d[14]), "+f"(d[15]), "+f"(d[16]), "+f"(d[17]), "+f"(d[18]), "+f"(d[19]), "+f"(d[20]), "+f"(d[21]), "+f"(d[22]), "+f"(d[23]), "+f"(d[24]), "+f"(d[25]), "+f"(d[26]), "+f"(d[27]), "+f"(d[28]), "+f"(d[29]), "+f"(d[30]), "+f"(d[31]), "+f"(d[32]), "+f"(d[33]), "+f"(d[34]), "+f"(d[35]), "+f"(d[36]), "+f"(d[37]), "+f"(d[38]), "+f"(d[39]), "+f"(d[40]), "+f"(d[41]), "+f"(d[42]), "+f"(d[43]), "+f"(d[44]), "+f"(d[45]), "+f"(d[46]), "+f"(d[47]), "+f"(d[48]), "+f"(d[49]), "+f"(d[50]), "+f"(d[51]), "+f"(d[52]), "+f"(d[53]), "+f"(d[54]), "+f"(d[55]), "+f"(d[56]), "+f"(d[57]), "+f"(d[58]), "+f"(d[59]), "+f"(d[60]), "+f"(d[61]), "+f"(d[62]), "+f"(d[63])
    : "l"(da), "l"(db), "r"(scale_d), "n"(TA), "n"(TB));
}
template <int TB>
__device__ __forceinline__ void wgmma_rs_n128(float (&d)[64], uint32_t a0, uint32_t a1, uint32_t a2, uint32_t a3, uint64_t db, int scale_d) {
  asm volatile("{\n.reg .pred p;\nsetp.ne.b32 p, %69, 0;\n"
    "wgmma.mma_async.sync.aligned.m64n128k16.f32.bf16.bf16 {%0, %1, %2, %3, %4, %5, %6, %7, %8, %9, %10, %11, %12, %13, %14, %15, %16, %17, %18, %19, %20, %21, %22, %23, %24, %25, %26, %27, %28, %29, %30, %31, %32, %33, %34, %35, %36, %37, %38, %39, %40, %41, %42, %43, %44, %45, %46, %47, %48, %49, %50, %51, %52, %53, %54, %55, %56, %57, %58, %59, %60, %61, %62, %63}, {%64, %65, %66, %67}, %68, p, 1, 1, %70;\n}\n"
    : "+f"(d[0]), "+f"(d[1]), "+f"(d[2]), "+f"(d[3]), "+f"(d[4]), "+f"(d[5]), "+f"(d[6]), "+f"(d[7]), "+f"(d[8]), "+f"(d[9]), "+f"(d[10]), "+f"(d[11]), "+f"(d[12]), "+f"(d[13]), "+f"(d[14]), "+f"(d[15]), "+f"(d[16]), "+f"(d[17]), "+f"(d[18]), "+f"(d[19]), "+f"(d[20]), "+f"(d[21]), "+f"(d[22]), "+f"(d[23]), "+f"(d[24]), "+f"(d[25]), "+f"(d[26]), "+f"(d[27]), "+f"(d[28]), "+f"(d[29]), "+f"(d[30]), "+f"(d[31]), "+f"(d[32]), "+f"(d[33]), "+f"(d[34]), "+f"(d[35]), "+f"(d[36]), "+f"(d[37]), "+f"(d[38]), "+f"(d[39]), "+f"(d[40]), "+f"(d[41]), "+f"(d[42]), "+f"(d[43]), "+f"(d[44]), "+f"(d[45]), "+f"(d[46]), "+f"(d[47]), "+f"(d[48]), "+f"(d[49]), "+f"(d[50]), "+f"(d[51]), "+f"(d[52]), "+f"(d[53]), "+f"(d[54]), "+f"(d[55]), "+f"(d[56]), "+f"(d[57]), "+f"(d[58]), "+f"(d[59]), "+f"(d[60]), "+f"(d[61]), "+f"(d[62]), "+f"(d[63])
    : "r"(a0), "r"(a1), "r"(a2), "r"(a3), "l"(db), "r"(scale_d), "n"(TB));
}
template <int TB, int TA = 0>
__device__ __forceinline__ void wgmma_ss_n160(float (&d)[80], uint64_t da, uint64_t db, int scale_d) {
  asm volatile("{\n.reg .pred p;\nsetp.ne.b32 p, %82, 0;\n"
    "wgmma.mma_async.sync.aligned.m64n160k16.f32.bf16.bf16 {%0, %1, %2, %3, %4, %5, %6, %7, %8, %9, %10, %11, %12, %13, %14, %15, %16, %17, %18, %19, %20, %21, %22, %23, %24, %25, %26, %27, %28, %29, %30, %31, %32, %33, %34, %35, %36, %37, %38, %39, %40, %41, %42, %43, %44, %45, %46, %47, %48, %49, %50, %51, %52, %53, %54, %55, %56, %57, %58, %59, %60, %61, %62, %63, %64, %65, %66, %67, %68, %69, %70, %71, %72, %73, %74, %75, %76, %77, %78, %79}, %80, %81, p, 1, 1, %83, %84;\n}\n"
    : "+f"(d[0]), "+f"(d[1]), "+f"(d[2]), "+f"(d[3]), "+f"(d[4]), "+f"(d[5]), "+f"(d[6]), "+f"(d[7]), "+f"(d[8]), "+f"(d[9]), "+f"(d[10]), "+f"(d[11]), "+f"(d[12]), "+f"(d[13]), "+f"(d[14]), "+f"(d[15]), "+f"(d[16]), "+f"(d[17]), "+f"(d[18]), "+f"(d[19]), "+f"(d[20]), "+f"(d[21]), "+f"(d[22]), "+f"(d[23]), "+f"(d[24]), "+f"(d[25]), "+f"(d[26]), "+f"(d[27]), "+f"(d[28]), "+f"(d[29]), "+f"(d[30]), "+f"(d[31]), "+f"(d[32]), "+f"(d[33]), "+f"(d[34]), "+f"(d[35]), "+f"(d[36]), "+f"(d[37]), "+f"(d[38]), "+f"(d[39]), "+f"(d[40]), "+f"(d[41]), "+f"(d[42]), "+f"(d[43]), "+f"(d[44]), "+f"(d[45]), "+f"(d[46]), "+f"(d[47]), "+f"(d[48]), "+f"(d[49]), "+f"(d[50]), "+f"(d[51]), "+f"(d[52]), "+f"(d[53]), "+f"(d[54]), "+f"(d[55]), "+f"(d[56]), "+f"(d[57]), "+f"(d[58]), "+f"(d[59]), "+f"(d[60]), "+f"(d[61]), "+f"(d[62]), "+f"(d[63]), "+f"(d[64]), "+f"(d[65]), "+f"(d[66]), "+f"(d[67]), "+f"(d[68]), "+f"(d[69]), "+f"(d[70]), "+f"(d[71]), "+f"(d[72]), "+f"(d[73]), "+f"(d[74]), "+f"(d[75]), "+f"(d[76]), "+f"(d[77]), "+f"(d[78]), "+f"(d[79])
    : "l"(da), "l"(db), "r"(scale_d), "n"(TA), "n"(TB));
}
template <int TB>
__device__ __forceinline__ void wgmma_rs_n160(float (&d)[80], uint32_t a0, uint32_t a1, uint32_t a2, uint32_t a3, uint64_t db, int scale_d) {
  asm volatile("{\n.reg .pred p;\nsetp.ne.b32 p, %85, 0;\n"
    "wgmma.mma_async.sync.aligned.m64n160k16.f32.bf16.bf16 {%0, %1, %2, %3, %4, %5, %6, %7, %8, %9, %10, %11, %12, %13, %14, %15, %16, %17, %18, %19, %20, %21, %22, %23, %24, %25, %26, %27, %28, %29, %30, %31, %32, %33, %34, %35, %36, %37, %38, %39, %40, %41, %42, %43, %44, %45, %46, %47, %48, %49, %50, %51, %52, %53, %54, %55, %56, %57, %58, %59, %60, %61, %62, %63, %64, %65, %66, %67, %68, %69, %70, %71, %72, %73, %74, %75, %76, %77, %78, %79}, {%80, %81, %82, %83}, %84, p, 1, 1, %86;\n}\n"
    : "+f"(d[0]), "+f"(d[1]), "+f"(d[2]), "+f"(d[3]), "+f"(d[4]), "+f"(d[5]), "+f"(d[6]), "+f"(d[7]), "+f"(d[8]), "+f"(d[9]), "+f"(d[10]), "+f"(d[11]), "+f"(d[12]), "+f"(d[13]), "+f"(d[14]), "+f"(d[15]), "+f"(d[16]), "+f"(d[17]), "+f"(d[18]), "+f"(d[19]), "+f"(d[20]), "+f"(d[21]), "+f"(d[22]), "+f"(d[23]), "+f"(d[24]), "+f"(d[25]), "+f"(d[26]), "+f"(d[27]), "+f"(d[28]), "+f"(d[29]), "+f"(d[30]), "+f"(d[31]), "+f"(d[32]), "+f"(d[33]), "+f"(d[34]), "+f"(d[35]), "+f"(d[36]), "+f"(d[37]), "+f"(d[38]), "+f"(d[39]), "+f"(d[40]), "+f"(d[41]), "+f"(d[42]), "+f"(d[43]), "+f"(d[44]), "+f"(d[45]), "+f"(d[46]), "+f"(d[47]), "+f"(d[48]), "+f"(d[49]), "+f"(d[50]), "+f"(d[51]), "+f"(d[52]), "+f"(d[53]), "+f"(d[54]), "+f"(d[55]), "+f"(d[56]), "+f"(d[57]), "+f"(d[58]), "+f"(d[59]), "+f"(d[60]), "+f"(d[61]), "+f"(d[62]), "+f"(d[63]), "+f"(d[64]), "+f"(d[65]), "+f"(d[66]), "+f"(d[67]), "+f"(d[68]), "+f"(d[69]), "+f"(d[70]), "+f"(d[71]), "+f"(d[72]), "+f"(d[73]), "+f"(d[74]), "+f"(d[75]), "+f"(d[76]), "+f"(d[77]), "+f"(d[78]), "+f"(d[79])
    : "r"(a0), "r"(a1), "r"(a2), "r"(a3), "l"(db), "r"(scale_d), "n"(TB));
}
template <int TB, int TA = 0>
__device__ __forceinline__ void wgmma_ss_n192(float (&d)[96], uint64_t da, uint64_t db, int scale_d) {
  asm volatile("{\n.reg .pred p;\nsetp.ne.b32 p, %98, 0;\n"
    "wgmma.mma_async.sync.aligned.m64n192k16.f32.bf16.bf16 {%0, %1, %2, %3, %4, %5, %6, %7, %8, %9, %10, %11, %12, %13, %14, %15, %16, %17, %18, %19, %20, %21, %22, %23, %24, %25, %26, %27, %28, %29, %30, %31, %32, %33, %34, %35, %36, %37, %38, %39, %40, %41, %42, %43, %44, %45, %46, %47, %48, %49, %50, %51, %52, %53, %54, %55, %56, %57, %58, %59, %60, %61, %62, %63, %64, %65, %66, %67, %68, %69, %70, %71, %72, %73, %74, %75, %76, %77, %78, %79, %80, %81, %82, %83, %84, %85, %86, %87, %88, %89, %90, %91, %92, %93, %94, %95}, %96, %97, p, 1, 1, %99, %100;\n}\n"
    : "+f"(d[0]), "+f"(d[1]), "+f"(d[2]), "+f"(d[3]), "+f"(d[4]), "+f"(d[5]), "+f"(d[6]), "+f"(d[7]), "+f"(d[8]), "+f"(d[9]), "+f"(d[10]), "+f"(d[11]), "+f"(d[12]), "+f"(d[13]), "+f"(d[14]), "+f"(d[15]), "+f"(d[16]), "+f"(d[17]), "+f"(d[18]), "+f"(d[19]), "+f"(d[20]), "+f"(d[21]), "+f"(d[22]), "+f"(d[23]), "+f"(d[24]), "+f"(d[25]), "+f"(d[26]), "+f"(d[27]), "+f"(d[28]), "+f"(d[29]), "+f"(d[30]), "+f"(d[31]), "+f"(d[32]), "+f"(d[33]), "+f"(d[34]), "+f"(d[35]), "+f"(d[36]), "+f"(d[37]), "+f"(d[38]), "+f"(d[39]), "+f"(d[40]), "+f"(d[41]), "+f"(d[42]), "+f"(d[43]), "+f"(d[44]), "+f"(d[45]), "+f"(d[46]), "+f"(d[47]), "+f"(d[48]), "+f"(d[49]), "+f"(d[50]), "+f"(d[51]), "+f"(d[52]), "+f"(d[53]), "+f"(d[54]), "+f"(d[55]), "+f"(d[56]), "+f"(d[57]), "+f"(d[58]), "+f"(d[59]), "+f"(d[60]), "+f"(d[61]), "+f"(d[62]), "+f"(d[63]), "+f"(d[64]), "+f"(d[65]), "+f"(d[66]), "+f"(d[67]), "+f"(d[68]), "+f"(d[69]), "+f"(d[70]), "+f"(d[71]), "+f"(d[72]), "+f"(d[73]), "+f"(d[74]), "+f"(d[75]), "+f"(d[76]), "+f"(d[77]), "+f"(d[78]), "+f"(d[79]), "+f"(d[80]), "+f"(d[81]), "+f"(d[82]), "+f"(d[83]), "+f"(d[84]), "+f"(d[85]), "+f"(d[86]), "+f"(d[87]), "+f"(d[88]), "+f"(d[89]), "+f"(d[90]), "+f"(d[91]), "+f"(d[92]), "+f"(d[93]), "+f"(d[94]), "+f"(d[95])
    : "l"(da), "l"(db), "r"(scale_d), "n"(TA), "n"(TB));
}
template <int TB>
__device__ __forceinline__ void wgmma_rs_n192(float (&d)[96], uint32_t a0, uint32_t a1, uint32_t a2, uint32_t a3, uint64_t db, int scale_d) {
  asm volatile("{\n.reg .pred p;\nsetp.ne.b32 p, %101, 0;\n"
    "wgmma.mma_async.sync.aligned.m64n192k16.f32.bf16.bf16 {%0, %1, %2, %3, %4, %5, %6, %7, %8, %9, %10, %11, %12, %13, %14, %15, %16, %17, %18, %19, %20, %21, %22, %23, %24, %25, %26, %27, %28, %29, %30, %31, %32, %33, %34, %35, %36, %37, %38, %39, %40, %41, %42, %43, %44, %45, %46, %47, %48, %49, %50, %51, %52, %53, %54, %55, %56, %57, %58, %59, %60, %61, %62, %63, %64, %65, %66, %67, %68, %69, %70, %71, %72, %73, %74, %75, %76, %77, %78, %79, %80, %81, %82, %83, %84, %85, %86, %87, %88, %89, %90, %91, %92, %93, %94, %95}, {%96, %97, %98, %99}, %100, p, 1, 1, %102;\n}\n"
    : "+f"(d[0]), "+f"(d[1]), "+f"(d[2]), "+f"(d[3]), "+f"(d[4]), "+f"(d[5]), "+f"(d[6]), "+f"(d[7]), "+f"(d[8]), "+f"(d[9]), "+f"(d[10]), "+f"(d[11]), "+f"(d[12]), "+f"(d[13]), "+f"(d[14]), "+f"(d[15]), "+f"(d[16]), "+f"(d[17]), "+f"(d[18]), "+f"(d[19]), "+f"(d[20]), "+f"(d[21]), "+f"(d[22]), "+f"(d[23]), "+f"(d[24]), "+f"(d[25]), "+f"(d[26]), "+f"(d[27]), "+f"(d[28]), "+f"(d[29]), "+f"(d[30]), "+f"(d[31]), "+f"(d[32]), "+f"(d[33]), "+f"(d[34]), "+f"(d[35]), "+f"(d[36]), "+f"(d[37]), "+f"(d[38]), "+f"(d[39]), "+f"(d[40]), "+f"(d[41]), "+f"(d[42]), "+f"(d[43]), "+f"(d[44]), "+f"(d[45]), "+f"(d[46]), "+f"(d[47]), "+f"(d[48]), "+f"(d[49]), "+f"(d[50]), "+f"(d[51]), "+f"(d[52]), "+f"(d[53]), "+f"(d[54]), "+f"(d[55]), "+f"(d[56]), "+f"(d[57]), "+f"(d[58]), "+f"(d[59]), "+f"(d[60]), "+f"(d[61]), "+f"(d[62]), "+f"(d[63]), "+f"(d[64]), "+f"(d[65]), "+f"(d[66]), "+f"(d[67]), "+f"(d[68]), "+f"(d[69]), "+f"(d[70]), "+f"(d[71]), "+f"(d[72]), "+f"(d[73]), "+f"(d[74]), "+f"(d[75]), "+f"(d[76]), "+f"(d[77]), "+f"(d[78]), "+f"(d[79]), "+f"(d[80]), "+f"(d[81]), "+f"(d[82]), "+f"(d[83]), "+f"(d[84]), "+f"(d[85]), "+f"(d[86]), "+f"(d[87]), "+f"(d[88]), "+f"(d[89]), "+f"(d[90]), "+f"(d[91]), "+f"(d[92]), "+f"(d[93]), "+f"(d[94]), "+f"(d[95])
    : "r"(a0), "r"(a1), "r"(a2), "r"(a3), "l"(db), "r"(scale_d), "n"(TB));
}

__device__ __forceinline__ uint32_t smem_u32(const void* p) { return (uint32_t)__cvta_generic_to_shared(p); }
__device__ __forceinline__ void wg_fence() { asm volatile("wgmma.fence.sync.aligned;" ::: "memory"); }
__device__ __forceinline__ void wg_commit() { asm volatile("wgmma.commit_group.sync.aligned;" ::: "memory"); }
template <int N> __device__ __forceinline__ void wg_wait() { asm volatile("wgmma.wait_group.sync.aligned %0;" ::"n"(N) : "memory"); }
__device__ __forceinline__ void sched_fence(uint32_t& keep, bool never) {
  asm volatile("{\n.reg .pred p;\nsetp.ne.b32 p, %1, 0;\n@p mov.u32 %0, %%clock;\n}\n" : "+r"(keep) : "r"((int)never) : "memory");
}
template <int N> __device__ __forceinline__ void fence_regs(float (&r)[N]) {
#pragma unroll
  for (int i = 0; i < N; i++) asm volatile("" : "+f"(r[i])::"memory");
}
template <int N> __device__ __forceinline__ void undefine(float (&r)[N]) {
#pragma unroll
  for (int i = 0; i < N; i++) asm volatile("" : "=f"(r[i]));
}
template <int N> __device__ __forceinline__ void fence_regs(uint32_t (&r)[N]) {
#pragma unroll
  for (int i = 0; i < N; i++) asm volatile("" : "+r"(r[i])::"memory");
}
__device__ __forceinline__ uint64_t mk_desc(uint32_t a16, uint32_t lbo, uint32_t sbo, uint32_t swz) {
  uint64_t d;
  asm("mov.b64 %0, {%1, %2};" : "=l"(d) : "r"(a16 + ((lbo >> 4) << 16)), "r"((sbo >> 4) | (swz << 30)));
  return d;
}
__device__ __forceinline__ void mbar_init(uint32_t bar, uint32_t cnt) {
  asm volatile("mbarrier.init.shared::cta.b64 [%0], %1;" ::"r"(bar), "r"(cnt) : "memory");
}
__device__ __forceinline__ void mbar_expect(uint32_t bar, uint32_t tx) {
  asm volatile("mbarrier.arrive.expect_tx.shared::cta.b64 _, [%0], %1;" ::"r"(bar), "r"(tx) : "memory");
}
__device__ __forceinline__ bool mbar_test(uint32_t bar, uint32_t ph) {
  uint32_t ok;
  asm volatile("{\n.reg .pred p;\nmbarrier.test_wait.parity.shared::cta.b64 p, [%1], %2;\nselp.u32 %0, 1, 0, p;\n}\n"
               : "=r"(ok) : "r"(bar), "r"(ph) : "memory");
  return ok;
}
__device__ __forceinline__ bool mbar_try(uint32_t bar, uint32_t ph, uint32_t ns) {
  uint32_t ok;
  asm volatile("{\n.reg .pred p;\nmbarrier.try_wait.parity.shared::cta.b64 p, [%1], %2, %3;\nselp.u32 %0, 1, 0, p;\n}\n"
               : "=r"(ok) : "r"(bar), "r"(ph), "r"(ns) : "memory");
  return ok;
}
__device__ __forceinline__ void mbar_wait(uint32_t bar, uint32_t ph) {
  asm volatile("{\n.reg .pred p;\n.reg .u32 n;\nmov.u32 n, 0;\n"
               "LOOP:\nmbarrier.try_wait.parity.shared::cta.b64 p, [%0], %1;\n@p bra DONE;\n"
               "add.u32 n, n, 1;\nsetp.lt.u32 p, n, 0x1000000;\n@p bra LOOP;\ntrap;\n"
               "DONE:\n}\n" ::"r"(bar), "r"(ph) : "memory");
}
__device__ __forceinline__ void mbar_wait_long(uint32_t bar) {
  asm volatile("{\n.reg .pred p;\n.reg .u32 n;\nmov.u32 n, 0;\n"
               "LOOP:\nmbarrier.try_wait.parity.shared::cta.b64 p, [%0], 0, 20000;\n@p bra DONE;\n"
               "add.u32 n, n, 1;\nsetp.lt.u32 p, n, 0x100000;\n@p bra LOOP;\ntrap;\n"
               "DONE:\n}\n" ::"r"(bar) : "memory");
}
__device__ __forceinline__ void mbar_arrive_cluster_if(bool on, uint32_t addr) {
  asm volatile("{\n.reg .pred p;\nsetp.ne.b32 p, %1, 0;\n@p mbarrier.arrive.shared::cluster.b64 _, [%0];\n}\n" ::"r"(addr), "r"((int)on) : "memory");
}
__device__ __forceinline__ void mbar_arrive_cluster_n(uint32_t n, uint32_t addr) {
  asm volatile("{\n.reg .pred p;\nsetp.ne.b32 p, %1, 0;\n@p mbarrier.arrive.shared::cluster.b64 _, [%0], %1;\n}\n" ::"r"(addr), "r"(n) : "memory");
}
__device__ __forceinline__ void tma2d(uint32_t dst, const CUtensorMap* m, uint32_t bar, int c0, int c1) {
  asm volatile("cp.async.bulk.tensor.2d.shared::cluster.global.mbarrier::complete_tx::bytes [%0], [%1, {%3, %4}], [%2];"
               ::"r"(dst), "l"(m), "r"(bar), "r"(c0), "r"(c1) : "memory");
}
__device__ __forceinline__ void tma3d(uint32_t dst, const CUtensorMap* m, uint32_t bar, int c0, int c1, int c2) {
  asm volatile("cp.async.bulk.tensor.3d.shared::cluster.global.mbarrier::complete_tx::bytes [%0], [%1, {%3, %4, %5}], [%2];"
               ::"r"(dst), "l"(m), "r"(bar), "r"(c0), "r"(c1), "r"(c2) : "memory");
}
__device__ __forceinline__ void tma3d_mc(uint32_t dst, const CUtensorMap* m, uint32_t bar, int c0, int c1, int c2) {
  asm volatile("cp.async.bulk.tensor.3d.shared::cluster.global.mbarrier::complete_tx::bytes.multicast::cluster"
               " [%0], [%1, {%3, %4, %5}], [%2], %6;"
               ::"r"(dst), "l"(m), "r"(bar), "r"(c0), "r"(c1), "r"(c2), "h"((uint16_t)3) : "memory");
}
__device__ __forceinline__ void tma3d_store(const CUtensorMap* m, uint32_t src, int c0, int c1, int c2) {
  asm volatile("cp.async.bulk.tensor.3d.global.shared::cta.bulk_group [%0, {%2, %3, %4}], [%1];"
               ::"l"(m), "r"(src), "r"(c0), "r"(c1), "r"(c2) : "memory");
}
__device__ __forceinline__ void bar_sync(int id, int n) { asm volatile("bar.sync %0, %1;" ::"r"(id), "r"(n) : "memory"); }
__device__ __forceinline__ uint32_t pack_bf16(float lo, float hi) {
  uint32_t r;
  asm("cvt.rn.bf16x2.f32 %0, %1, %2;" : "=r"(r) : "f"(hi), "f"(lo));
  return r;
}
__device__ __forceinline__ float ex2(float x) {
  float y;
  asm("ex2.approx.ftz.f32 %0, %1;" : "=f"(y) : "f"(x));
  return y;
}
__device__ __forceinline__ float rcp(float x) {
  float y;
  asm("rcp.approx.ftz.f32 %0, %1;" : "=f"(y) : "f"(x));
  return y;
}
__device__ __forceinline__ void stsm4(uint32_t addr, uint32_t a, uint32_t b, uint32_t c, uint32_t d) {
  asm volatile("stmatrix.sync.aligned.m8n8.x4.shared.b16 [%0], {%1, %2, %3, %4};" ::"r"(addr), "r"(a), "r"(b), "r"(c), "r"(d) : "memory");
}

__device__ __forceinline__ void tma4d_mc_hint(uint32_t dst, const CUtensorMap* m, uint32_t bar, int c3, uint64_t pol) {
  asm volatile("cp.async.bulk.tensor.4d.shared::cluster.global.mbarrier::complete_tx::bytes.multicast::cluster.L2::cache_hint"
               " [%0], [%1, {%3, %3, %3, %4}], [%2], %5, %6;"
               ::"r"(dst), "l"(m), "r"(bar), "r"(0), "r"(c3), "h"((uint16_t)3), "l"(pol) : "memory");
}
__device__ __forceinline__ void tma5d_mc(uint32_t dst, const CUtensorMap* m, uint32_t bar, int c2, int c4) {
  asm volatile("cp.async.bulk.tensor.5d.shared::cluster.global.mbarrier::complete_tx::bytes.multicast::cluster"
               " [%0], [%1, {%3, %3, %4, %3, %5}], [%2], %6;"
               ::"r"(dst), "l"(m), "r"(bar), "r"(0), "r"(c2), "r"(c4), "h"((uint16_t)3) : "memory");
}
__device__ __forceinline__ void bulk_load_hint(uint32_t dst, const void* src, uint32_t bytes, uint32_t bar, uint64_t pol) {
  asm volatile("cp.async.bulk.shared::cluster.global.mbarrier::complete_tx::bytes.L2::cache_hint [%0], [%1], %2, [%3], %4;"
               ::"r"(dst), "l"(src), "r"(bytes), "r"(bar), "l"(pol) : "memory");
}
__device__ __forceinline__ void stg2_if(bool on, void* p, uint32_t a, uint32_t b, uint32_t c, uint32_t d, uint32_t e, uint32_t f,
                                        uint32_t g, uint32_t h, uint64_t pol) {
  asm volatile("{\n.reg .pred p;\nsetp.ne.b32 p, %10, 0;\n"
               "@p st.global.L2::cache_hint.v4.b32 [%0], {%1, %2, %3, %4}, %9;\n"
               "@p st.global.L2::cache_hint.v4.b32 [%0 + 512], {%5, %6, %7, %8}, %9;\n}\n"
               ::"l"(p), "r"(a), "r"(b), "r"(c), "r"(d), "r"(e), "r"(f), "r"(g), "r"(h), "l"(pol), "r"((int)on) : "memory");
}
__device__ __forceinline__ uint64_t evict_first() {
  uint64_t p;
  asm("createpolicy.fractional.L2::evict_first.b64 %0, 1.0;" : "=l"(p));
  return p;
}
__device__ __forceinline__ bool elect() {
  uint32_t ok;
  asm volatile("{\n.reg .pred p;\nelect.sync _|p, 0xffffffff;\nselp.u32 %0, 1, 0, p;\n}\n" : "=r"(ok));
  return ok;
}
__device__ __forceinline__ void mbar_arrive(uint32_t bar) {
  asm volatile("mbarrier.arrive.shared::cta.b64 _, [%0];" ::"r"(bar) : "memory");
}
__device__ __forceinline__ void mbar_arrive_if(bool on, uint32_t bar) {
  asm volatile("{\n.reg .pred p;\nsetp.ne.b32 p, %1, 0;\n@p mbarrier.arrive.shared::cta.b64 _, [%0];\n}\n" ::"r"(bar), "r"((int)on) : "memory");
}
__device__ __forceinline__ void lds2_if(bool on, uint32_t p, uint32_t (&t)[8]) {
  asm volatile("{\n.reg .pred p;\nsetp.ne.b32 p, %9, 0;\n@p ld.shared.v4.b32 {%0, %1, %2, %3}, [%8];\n@p ld.shared.v4.b32 {%4, %5, %6, %7}, [%8 + 512];\n}\n"
               : "+r"(t[0]), "+r"(t[1]), "+r"(t[2]), "+r"(t[3]), "+r"(t[4]), "+r"(t[5]), "+r"(t[6]), "+r"(t[7]) : "r"(p), "r"((int)on) : "memory");
}
__device__ __forceinline__ void lds128(uint32_t p, uint32_t& a, uint32_t& b, uint32_t& c, uint32_t& d) {
  asm volatile("ld.shared.v4.b32 {%0, %1, %2, %3}, [%4];" : "=r"(a), "=r"(b), "=r"(c), "=r"(d) : "r"(p) : "memory");
}
template <class T> __device__ __forceinline__ T* ptr_add(T* base, uint32_t bytes) {
  T* r;
  asm("{\n.reg .u32 lo, hi;\nmov.b64 {lo, hi}, %1;\nadd.cc.u32 lo, lo, %2;\naddc.u32 hi, hi, 0;\nmov.b64 %0, {lo, hi};\n}\n" : "=l"(r) : "l"(base), "r"(bytes));
  return r;
}
__device__ __forceinline__ uint32_t lds32(uint32_t p) {
  uint32_t v;
  asm volatile("ld.volatile.shared.u32 %0, [%1];" : "=r"(v) : "r"(p) : "memory");
  return v;
}
__device__ __forceinline__ uint32_t flag_get(const unsigned int* p) {
  uint32_t v;
  asm volatile("ld.acquire.gpu.global.u32 %0, [%1];" : "=r"(v) : "l"(p) : "memory");
  return v;
}
__device__ __forceinline__ uint32_t wait_word(uint32_t p, uint32_t target) {
  uint32_t v;
  asm volatile("{\n.reg .pred p;\n.reg .u32 n;\nmov.u32 n, 0;\n"
               "LOOP:\nld.acquire.cta.shared.u32 %0, [%1];\nsetp.ge.u32 p, %0, %2;\n@p bra DONE;\n"
               "nanosleep.u32 %3;\nadd.u32 n, n, 1;\nsetp.lt.u32 p, n, 0x400000;\n@p bra LOOP;\ntrap;\n"
               "DONE:\n}\n" : "=r"(v) : "r"(p), "r"(target), "n"(400) : "memory");
  return v;
}
__device__ __forceinline__ void flag_set(unsigned int* p, uint32_t v) {
  asm volatile("st.release.gpu.global.u32 [%0], %1;" ::"l"(p), "r"(v) : "memory");
}
__device__ __forceinline__ void flag_dec(unsigned int* p) {
  asm volatile("red.relaxed.gpu.global.add.u32 [%0], 0xffffffff;" ::"l"(p) : "memory");
}

struct Cursor {
  int bi;
  uint32_t ph;
  __device__ __forceinline__ void next() {
    if (++bi == NBAR) { bi = 0; ph ^= 1; }
  }
};

constexpr float kScaleLog2 = 0.07216878364870322f * 1.4426950408889634f;
constexpr float kSumLimit = 1048576.0f;

__global__ void __cluster_dims__(2, 1, 1) __launch_bounds__(384, 1)
fused_kernel(const __grid_constant__ Params P) {
  extern __shared__ uint8_t smem_raw[];
  const uint32_t sbase = (smem_u32(smem_raw) + 1023) & ~1023u;
  const uint32_t full0 = sbase + RING, empty0 = full0 + 8 * NBAR, odone0 = empty0 + 8 * NBAR, ev0 = odone0 + 8 * MAX_OPS;
  const uint32_t progress = ev0 + 8 * MAX_EV, jobw = progress + 4;
  const uint32_t rank = blockIdx.x & 1;
  const int role = blockIdx.x >> 1;
  const int wid = __shfl_sync(0xffffffffu, (int)(threadIdx.x >> 5), 0);
  const int wg = wid >> 2;

  if (wid < 8) {
    if (elect()) {
#pragma unroll
      for (int j = 0; j < 16; j++) {
        const int i = EARLY + 16 * wid + j;
        if (i < 2 * NBAR + MAX_OPS + MAX_EV) mbar_init(full0 + 8 * i, i < NBAR ? 1 : i < 2 * NBAR ? 16 : i < 2 * NBAR + MAX_OPS ? 8 : 1);
      }
      if (wid == 7) asm volatile("st.shared.v2.u32 [%0], {0, 0};\nfence.acq_rel.cta;" ::"r"(progress) : "memory");
      asm volatile("fence.mbarrier_init.release.cluster;" ::: "memory");
    }
  } else if (wid > 8) {
    const uint32_t g = blockIdx.x * 96 + threadIdx.x - 288, w = g - 2048;
    if (g < 4096) asm volatile("prefetch.global.L2 [%0];" ::"l"(g < 2048 ? P.xw[0] + g * (kD * 2) : P.xw[1] + (w >> 5) * (kHD * 2) + (w & 31) * 128));
  } else {
    const uint32_t op0 = P.first[role];
    if (elect()) {
#pragma unroll
      for (int k = 0; k < EARLY; k++) mbar_init(full0 + 8 * k, 1);
      asm volatile("fence.mbarrier_init.release.cluster;" ::: "memory");
      const int blk = (op0 >> 10) & 1;
      if ((op0 & 3) == OP_Q) {
#pragma unroll
        for (int k = 0; k < EARLY; k++) {
          mbar_expect(full0 + 8 * k, SZ_Q);
          tma2d(sbase + k * SZ_Q, &P.x[blk], full0 + 8 * k, 64 * k, ((op0 >> 7) & 7) * kSq + rank * 128);
          tma3d(sbase + k * SZ_Q + 16384, &P.wq[blk], full0 + 8 * k, 0, 64 * k, 3 * ((op0 >> 2) & 31));
        }
      }
      asm volatile("prefetch.tensormap [%0];" ::"l"(rank ? &P.v[blk] : &P.k[blk]) : "memory");
    }
  }
  __syncwarp();
  asm volatile("barrier.cluster.arrive.relaxed.aligned;\nbarrier.cluster.wait.aligned;" ::: "memory");

  if (wg < 2) {
    asm volatile("setmaxnreg.inc.sync.aligned.u32 240;");
    const uint32_t* prog = P.prog[role].c;
    const int lane = threadIdx.x & 31, warp = wid & 3;
    uint32_t empty_rem;
    asm volatile("mapa.shared::cluster.u32 %0, %1, %2;" : "=r"(empty_rem) : "r"(empty0), "r"(lane & 1));
    uint32_t keep = (threadIdx.x & 127) < 2 ? 4 : 0;
    auto release = [&](int slot) { mbar_arrive_cluster_n(keep, empty_rem + 8 * slot); };
    auto release_warp = [&](int slot, bool on = true) { mbar_arrive_cluster_if(lane < 2 && on, empty_rem + 8 * slot); };
    Cursor r{0, 0};
    const uint32_t ring16 = (sbase & 0x3FFFF) >> 4;
    uint32_t cur = ring16;
    bool rdy0 = false, rdy1 = false;
    auto probe1 = [&]() { rdy0 = mbar_test(full0 + 8 * r.bi, r.ph); };
    auto probe2 = [&]() {
      Cursor n = r;
      rdy0 = mbar_test(full0 + 8 * n.bi, n.ph);
      n.next();
      rdy1 = mbar_test(full0 + 8 * n.bi, n.ph);
    };
    auto advance = [&](uint32_t bytes, uint32_t& addr) {
      const int bi = r.bi;
      r.next();
      if (cur > ring16 + ((RING - bytes) >> 4)) cur = ring16;
      addr = cur;
      cur += bytes >> 4;
      return bi;
    };
    auto take = [&](bool rdy, uint32_t bytes, uint32_t& addr) {
      if (__builtin_expect(!__all_sync(0xffffffffu, rdy), 0)) mbar_wait(full0 + 8 * r.bi, r.ph);
      return advance(bytes, addr);
    };
    const bool never = P.dbg == 0xffffffffu;
    uint32_t q[48];
#pragma unroll
    for (int i = 0; i < 48; i++) q[i] = 0;
    const int row = wg * 64 + warp * 16 + (lane >> 2);
    const int img0 = row * 4 + ((lane & 3) ^ ((row >> 1) & 3));
    uint4* pend = nullptr;
    bool pend_any = false;
    const uint64_t spol = evict_first();
    int pc = 0;
    auto slab = [&](int c, int i0) {
#pragma unroll
      for (int i = i0; i < 6; i++)
        stg2_if(c == i, pend + i * 512, q[8 * i], q[8 * i + 1], q[8 * i + 2], q[8 * i + 3],
                q[8 * i + 4], q[8 * i + 5], q[8 * i + 6], q[8 * i + 7], spol);
    };
    auto drain = [&](int c) {
      if (!pend_any || c >= 6) return;
      slab(c, 0);
      if (c == 5) {
        __syncwarp();
        mbar_arrive_if(lane == 0, odone0 - 8 + 8 * pc);
      }
    };

    for (;; pc++) {
      uint32_t op = prog[pc];
      const int type = op & 3;
      auto enter = [&]() {
        r.bi = (op >> 15) & 15; r.ph = (op >> 19) & 1; cur = ring16 + (((op >> 20) & 63) << 8);
      };
      enter();
      pend_any = op & C_PEND;
      uint32_t job = 0;
      if ((op & (3 | C_WIDE)) == OP_O) job = __shfl_sync(0xffffffffu, wait_word(jobw, 1), 0);
      if (type == OP_END || job == OP_O) {
#pragma unroll 1
        for (int c = 0; c < 6; c++) drain(c);
        asm volatile("barrier.cluster.arrive.relaxed;" ::: "memory");
        break;
      }
      {
        float s[32], o[96];
        uint32_t ad0;
        int bi0, sk1;
        uint32_t pa[16], pb[16];
        float mc0, mc1, l0, l1;
        bool shifted;
        uint32_t nop;
        auto expo = [&](float (&s)[32], uint32_t (&pout)[16], float& b0, float& b1, bool shift, auto mid) {
          float c0, c1;
#pragma unroll
          for (int i = 0; i < 8; i++) {
            const float e0 = ex2(shift ? s[4 * i] - mc0 : s[4 * i]), e1 = ex2(shift ? s[4 * i + 1] - mc0 : s[4 * i + 1]);
            const float e2 = ex2(shift ? s[4 * i + 2] - mc1 : s[4 * i + 2]), e3 = ex2(shift ? s[4 * i + 3] - mc1 : s[4 * i + 3]);
            if (i) { b0 += e0; c0 += e1; b1 += e2; c1 += e3; } else { b0 = e0; c0 = e1; b1 = e2; c1 = e3; }
            pout[2 * i] = pack_bf16(e0, e1); pout[2 * i + 1] = pack_bf16(e2, e3);
            if (i & 1) mid(i >> 1);
          }
          b0 += c0; b1 += c1;
        };
        auto rowmax = [&](float (&s)[32], float& m0, float& m1) {
          m0 = fmaxf(s[0], s[1]); m1 = fmaxf(s[2], s[3]);
#pragma unroll
          for (int i = 1; i < 8; i++) { m0 = fmaxf(m0, fmaxf(s[4 * i], s[4 * i + 1])); m1 = fmaxf(m1, fmaxf(s[4 * i + 2], s[4 * i + 3])); }
          m0 = fmaxf(m0, __shfl_xor_sync(0xffffffffu, m0, 1)); m1 = fmaxf(m1, __shfl_xor_sync(0xffffffffu, m1, 1));
          m0 = fmaxf(m0, __shfl_xor_sync(0xffffffffu, m0, 2)); m1 = fmaxf(m1, __shfl_xor_sync(0xffffffffu, m1, 2));
        };
        auto first = [&](float (&s)[32], int sk0, auto mid) {
          fence_regs(s);
          release(sk0);
          mc0 = 0.f; mc1 = 0.f;
          expo(s, pa, l0, l1, false, mid);
          shifted = __any_sync(0xffffffffu, !(fmaxf(l0, l1) <= kSumLimit && fminf(l0, l1) >= 1.f / kSumLimit));
          if (shifted) {
            rowmax(s, mc0, mc1);
            expo(s, pa, l0, l1, true, [](int) {});
          }
        };
        auto qk = [&](float (&s)[32], uint32_t ak, int k0 = 0, int k1 = 12) {
#pragma unroll
          for (int kk = k0; kk < k1; kk++)
            wgmma_rs_n64<0>(s, q[4 * kk], q[4 * kk + 1], q[4 * kk + 2], q[4 * kk + 3], mk_desc(ak, 16, KV_SBO, 1) + ((kk >> 2) * KV_CH + (kk & 3) * 2), kk != 0);
          if (k1 == 12) wg_commit();
        };
        auto pv = [&](uint32_t (&pin)[16], uint32_t av, int acc) {
#pragma unroll
          for (int kk = 0; kk < 4; kk++)
            wgmma_rs_n192<1>(o, pin[4 * kk], pin[4 * kk + 1], pin[4 * kk + 2], pin[4 * kk + 3], mk_desc(av, KV_CH * 16, KV_SBO, 1) + (kk * (KV_SBO / 8)), acc || (kk != 0));
          wg_commit();
        };
        auto finish = [&](uint32_t (&pout)[16], int sk, int sv) {
          probe1();
          wg_wait<1>();
          fence_regs(s);
          release(sk);
          float b0, b1;
#pragma unroll 1
          for (bool redo = false;; redo = true) {
            expo(s, pout, b0, b1, false, [](int) {});
            if (!__any_sync(0xffffffffu, !redo && (shifted || !(fmaxf(b0, b1) <= kSumLimit)))) break;
            shifted = true;
            rowmax(s, b0, b1);
            b0 = fmaxf(mc0, b0); b1 = fmaxf(mc1, b1);
            const float a0 = ex2(mc0 - b0), a1 = ex2(mc1 - b1);
            mc0 = b0; mc1 = b1;
            l0 *= a0; l1 *= a1;
            wg_wait<0>();
            fence_regs(o);
#pragma unroll
            for (int i = 0; i < 24; i++) { o[4 * i] *= a0; o[4 * i + 1] *= a0; o[4 * i + 2] *= a1; o[4 * i + 3] *= a1; }
#pragma unroll
            for (int i = 0; i < 32; i++) s[i] -= (i & 2) ? mc1 : mc0;
          }
          l0 += b0; l1 += b1;
          wg_wait<0>();
          fence_regs(o);
          release(sv);
        };
        auto step = [&](uint32_t (&pin)[16], uint32_t (&pout)[16]) {
          uint32_t ak, av;
          const int sk = take(rdy0, SZ_KV, ak), sv = advance(SZ_KV, av);
          wg_fence();
          qk(s, ak);
          pv(pin, av, 1);
          finish(pout, sk, sv);
        };
        auto unpark = [&]() {
          uint32_t ad, ak;
          const int bi = take(rdy0, SZ_PARK, ad);
#pragma unroll
          for (int i = 0; i < 12; i++) lds128(sbase + (ad - ring16 + img0) * 16 + (i >> 1) * 8192 + (i & 1) * 512, q[4 * i], q[4 * i + 1], q[4 * i + 2], q[4 * i + 3]);
          const int sk0 = take(false, SZ_KV, ak);
          fence_regs(q);
          release_warp(bi);
          wg_fence();
          qk(s, ak);
          probe2();
          return sk0;
        };
        auto mma4 = [&](uint32_t ad, int acc) {
#pragma unroll
          for (int kk = 0; kk < 4; kk++)
            wgmma_ss_n192<1>(o, mk_desc(ad + wg * 512, 16, 1024, 1) + (kk * 2), mk_desc(ad, 8192, 1024, 1) + (1024 + kk * 128), acc || kk != 0);
        };
        auto convert = [&](int i0, int i1) {
          sched_fence(keep, never);
#pragma unroll
          for (int i = i0; i < i1; i++) {
            q[i] = pack_bf16(o[2 * i] * kScaleLog2, o[2 * i + 1] * kScaleLog2);
            if ((i & 7) == 7 && i != i1 - 1) sched_fence(keep, never);
          }
          sched_fence(keep, never);
        };
        auto kend = [&](int bi, int k) {
          wg_commit();
          drain(k < 8 ? (0x54732710u >> (4 * k)) & 7 : 7);
          probe1();
          wg_wait<0>();
          release(bi);
        };
        if (type == OP_O) {
          int prev = 0;
          if (op & C_WIDE) {
            float d[64];
            auto mma3 = [&](uint32_t ad, int h, int acc) {
#pragma unroll
              for (int kk = 0; kk < 2; kk++)
                wgmma_ss_n192<1>(o, mk_desc(ad + wg * 256, 16, 512, 2) + (h * 512 + kk * 2), mk_desc(ad, 4096, 1024, 1) + (1024 + h * 768 + kk * 128), acc || kk);
            };
            auto mma2 = [&](uint32_t ad, uint32_t ob, int h, int acc) {
#pragma unroll
              for (int kk = 0; kk < 2; kk++)
                wgmma_ss_n128<1>(d, mk_desc(ad + wg * 256, 16, 512, 2) + (h * 512 + kk * 2), mk_desc(ad, 4096, 1024, 1) + (ob + h * 512 + kk * 128), acc || kk);
            };
            auto wstep = [&](uint32_t bytes, int acc, auto hook) {
              uint32_t ad;
              const int bi = take(rdy0, bytes, ad);
              wg_fence();
              if (bytes == SZ_W2) mma2(ad, 1024, 0, 1); else mma3(ad, 0, acc);
              if (bytes == SZ_W) mma3(ad, 1, 1);
              wg_commit();
              if (acc) { wg_wait<1>(); release(prev); }
              if (bytes == SZ_W) mma2(ad, 2560, 0, acc);
              if (bytes == SZ_W3) mma3(ad, 1, 1); else mma2(ad, bytes == SZ_W ? 2560 : 1024, 1, 1);
              wg_commit();
              prev = bi;
              hook();
              probe1();
              wg_wait<1>();
            };
            undefine(o);
            wstep(SZ_W, 0, [&]() { drain(0); });
#pragma unroll 1
            for (int k = 1; k < ((op >> 2) & 127) - TAIL; k++) wstep(SZ_W, 1, [&]() { drain(k); });
#pragma unroll 1
            for (int k = 0; k < TAIL; k++) wstep(SZ_W2, 1, []() {});
            pend = ptr_add(P.g->part, (((op >> 9) & 31) * 2 + rank) * 81920 + 4 * 8192 + img0 * 16);
            wstep(SZ_W3, 1, [&]() {
              fence_regs(d);
#pragma unroll
              for (int i = 0; i < 32; i++) q[16 + i] = pack_bf16(d[2 * i], d[2 * i + 1]);
              slab(2, 2);
            });
#pragma unroll 1
            for (int k = 3; k < 6; k++) wstep(SZ_W3, 1, [&]() { slab(k, 2); });
            op = prog[pc + 1];
            enter();
            pend_any = true;
            pend -= 4 * 512;
            bi0 = take(rdy0 || (op & 3) != OP_Q, SZ_Q, ad0);
            sched_fence(keep, never);
            wg_wait<0>();
            fence_regs(o);
            release(prev);
#pragma unroll
            for (int i = 0; i < 48; i++) q[i] = pack_bf16(o[2 * i], o[2 * i + 1]);
            if ((op & 3) != OP_Q) continue;
            pc++;
            goto first_step;
          }
          float c[80];
          auto mma2 = [&](uint32_t ad, uint32_t oa, uint32_t ob, int acc) {
            wgmma_ss_n160<1>(c, mk_desc(ad + wg * 256, 16, 512, 2) + (oa), mk_desc(ad, 2048, 512, 2) + (1024 + ob), acc);
            wgmma_ss_n160<1>(c, mk_desc(ad + wg * 256, 16, 512, 2) + (oa + 2), mk_desc(ad, 2048, 512, 2) + (1024 + ob + 64), 1);
          };
          auto kstep = [&](int acc, auto hook, uint32_t bytes = SZ_O) {
            uint32_t ad;
            const int bi = take(rdy0, bytes, ad);
            wg_fence();
            mma2(ad, 0, 0, acc);
            wg_commit();
            if (acc) wg_wait<1>();
            if (acc == 1) release(prev);
            if (acc > 1) release_warp(prev, acc == 2 || wg == 0);
            mma2(ad, 512, 640, 1);
            wg_commit();
            prev = bi;
            hook();
            probe1();
            wg_wait<1>();
          };
          auto unblock = [&](int k) {
            if (__all_sync(0xffffffffu, rdy0) || __all_sync(0xffffffffu, mbar_try(full0 + 8 * r.bi, r.ph, 1500))) return;
#pragma unroll 1
            for (; k < 6; k++) drain(k);
            pend_any = false;
          };
          unblock(0);
          kstep(0, [&]() { drain(0); });
          int left = ((job >> 13) & 127) - 6;
#pragma unroll 1
          for (uint32_t k = 1, pace = left >= 29 ? 0x4511 : left <= 17 ? 0x1a : 0x155; left > 0; pace >>= 2, left--) {
            unblock(k);
            kstep(1, [&]() {
#pragma unroll 1
              for (int i = pace & 3; i > 0; i--) drain(k++);
            });
          }
          uint32_t t[8], stage[3];
          float u[80];
          auto unpack = [&](int j) {
#pragma unroll
            for (int i = 0; i < 8; i++) {
              u[16 * j + 2 * i] = __uint_as_float(t[i] << 16); u[16 * j + 2 * i + 1] = __uint_as_float(t[i] & 0xffff0000u);
              asm volatile("" : "+f"(u[16 * j + 2 * i]), "+f"(u[16 * j + 2 * i + 1]));
            }
          };
#pragma unroll
          for (int i = 0; i < 8; i++) t[i] = 0;
          const uint32_t bytes = (job & P_LD) ? SZ_OL : SZ_O;
#pragma unroll
          for (int j = 0; j < 5; j++) {
            if (j == 2 && wg == 1) {
              wg_wait<0>();
              release_warp(prev);
              bar_sync(1, 256);
            }
            kstep(j == 2 ? 3 : 2, [&]() {
              if (j == 4) asm volatile("{\n.reg .pred p;\nsetp.eq.u32 p, %0, 0;\n@p bar.arrive 1, 256;\n}\n" ::"r"(wg) : "memory");
              if (j) unpack(j - 1);
              lds2_if(job & P_LD, sbase + (cur - ring16 + img0) * 16 - 8192, t);
              if (j >= 1 && j <= 3) stage[j - 1] = sbase + (cur - ring16) * 16 - bytes + wid * 1024;
            }, bytes);
          }
          unpack(4);
          sched_fence(keep, never);
          wg_wait<0>();
          fence_regs(c);
          release_warp(prev);
          asm volatile("barrier.cluster.arrive.relaxed;" ::: "memory");
#pragma unroll
          for (int i = 0; i < 10; i++) {
            const int v = (i & 1) * 2 + (lane >> 4);
            const uint32_t sa = stage[i >> 2] + (i & 2) * 4096;
            stsm4(sa + (lane & 15) * 64 + ((v ^ ((lane >> 1) & 3)) << 4), pack_bf16(c[8 * i] + u[8 * i], c[8 * i + 1] + u[8 * i + 1]),
                  pack_bf16(c[8 * i + 2] + u[8 * i + 2], c[8 * i + 3] + u[8 * i + 3]), pack_bf16(c[8 * i + 4] + u[8 * i + 4], c[8 * i + 5] + u[8 * i + 5]),
                  pack_bf16(c[8 * i + 6] + u[8 * i + 6], c[8 * i + 7] + u[8 * i + 7]));
          }
          asm volatile("fence.proxy.async.shared::cta;" ::: "memory");
          __syncwarp();
          if (elect()) {
#pragma unroll
            for (int i = 0; i < 5; i++)
              tma3d_store(&P.out, stage[i >> 1] + (i & 1) * 8192, 0, ((job >> 7) & 7) * kSq + rank * 128 + wid * 16, ((job >> 10) & 1) * 20 + ((job >> 20) & 3) * 5 + i);
            asm volatile("cp.async.bulk.commit_group;\ncp.async.bulk.wait_group.read 0;" ::: "memory");
          }
          __syncwarp();
          break;
        }
        bi0 = take(rdy0, SZ_Q, ad0);
      first_step:
        undefine(o);
        wg_fence();
        mma4(ad0, 0);
        kend(bi0, 0);
        fence_regs(o);
      next_head:
        {
#pragma unroll 1
          for (int k = 1; k < ((op & F_PARK) ? 10 : 8); k++) {
            uint32_t ad;
            const int bi = take(rdy0, SZ_Q, ad);
            wg_fence();
            mma4(ad, 1);
            kend(bi, k);
          }
          if (op & F_PARK) {
            fence_regs(o);
            convert(0, 48);
            pend = ptr_add(P.g->tile, (((op >> 2) & 511) * 2 + rank) * SZ_PARK + img0 * 16);
            continue;
          }
          uint32_t a8, a9, ak0, ak1;
          const int b8 = take(rdy0, SZ_Q, a8), b9 = take(false, SZ_Q, a9);
          wg_fence();
          mma4(a8, 1);
          wg_commit();
          mma4(a9, 1);
          wg_commit();
          pc++;
          wg_wait<1>();
          release(b8);
          const int sk0 = take(false, SZ_KV, ak0);
          wg_wait<0>();
          fence_regs(o);
          release(b9);
          float s0[32];
          convert(0, 32);
          wg_fence();
          qk(s0, ak0, 0, 4);
          convert(32, 48);
          wg_fence();
          qk(s0, ak0, 4, 12);
          sk1 = take(false, SZ_KV, ak1);
          probe1();
          wg_wait<0>();
          first(s0, sk0, [&](int i) {
            if (i == 0) return;
            sched_fence(keep, never);
            wg_fence();
            if (i == 1) qk(s, ak1, 0, 4);
            if (i == 2) qk(s, ak1, 4, 8);
            if (i == 3) qk(s, ak1, 8, 12);
            sched_fence(keep, never);
          });
        }
        for (;;) {
          {
            uint32_t av;
            const int sv = take(rdy0, SZ_KV, av);
            undefine(o);
            wg_fence();
            pv(pa, av, 0);
            finish(pb, sk1, sv);
          }
          nop = prog[pc + 1];
#pragma unroll 1
          for (int jj = 0; jj < 7; jj++) {
            step(pb, pa);
            step(pa, pb);
          }
          float i0, i1;
          auto last = [&]() {
            uint32_t av;
            const int sv = take(rdy0, SZ_KV, av);
            wg_fence();
            pv(pb, av, 1);
            sched_fence(keep, never);
            probe1();
            l0 += __shfl_xor_sync(0xffffffffu, l0, 1); l1 += __shfl_xor_sync(0xffffffffu, l1, 1);
            l0 += __shfl_xor_sync(0xffffffffu, l0, 2); l1 += __shfl_xor_sync(0xffffffffu, l1, 2);
            i0 = rcp(l0); i1 = rcp(l1);
            pend = ptr_add(P.g->tile, (((op >> 2) & 511) * 2 + rank) * SZ_PARK + img0 * 16);
            return sv;
          };
          auto normalise = [&](uint32_t (&d)[48], auto mid) {
#pragma unroll
            for (int i = 0; i < 24; i++) {
              d[8 * (i >> 2) + (i & 3)] = pack_bf16(o[4 * i] * i0, o[4 * i + 1] * i0);
              d[8 * (i >> 2) + (i & 3) + 4] = pack_bf16(o[4 * i + 2] * i1, o[4 * i + 3] * i1);
              if ((i & 1) && i != 23) sched_fence(keep, never);
              if ((i & 3) == 3 && i != 23) mid(i >> 2);
            }
          };
          const int sv = last();
          if ((nop & 3) != OP_A) {
            op = nop;
            enter();
            pend_any = true;
            bi0 = take(rdy0 || (nop & 3) != OP_Q, SZ_Q, ad0);
            sched_fence(keep, never);
            wg_wait<0>();
            fence_regs(o);
            release(sv);
            normalise(q, [](int) {});
            undefine(o);
            if ((nop & 3) != OP_Q) break;
            sched_fence(keep, never);
            wg_fence();
            mma4(ad0, 0);
            pc++;
            kend(bi0, 0);
            fence_regs(o);
            goto next_head;
          }
          const int sk0 = unpark();
          wg_wait<1>();
          fence_regs(o);
          release(sv);
          uint32_t t[48];
          auto st = [&](int i) {
            stg2_if(true, pend + i * 512, t[8 * i], t[8 * i + 1], t[8 * i + 2], t[8 * i + 3], t[8 * i + 4], t[8 * i + 5], t[8 * i + 6], t[8 * i + 7], spol);
          };
          normalise(t, [&](int i) { if (!(i & 1)) st(i >> 1); });
          wg_wait<0>();
          first(s, sk0, [&](int i) { if (i < 3) { sched_fence(keep, never); st(3 + i); } });
          __syncwarp();
          mbar_arrive_if(lane == 0, odone0 + 8 * pc);
          pc++;
          op = nop;
          uint32_t ak1;
          sk1 = take(rdy0, SZ_KV, ak1);
          rdy0 = rdy1;
          wg_fence();
          qk(s, ak1);
        }
      }
    }
    asm volatile("barrier.cluster.wait;" ::: "memory");
  } else {
    asm volatile("setmaxnreg.dec.sync.aligned.u32 24;");
    const uint32_t* prog = P.prog[role].p;
    unsigned int* flag = P.g->flag + rank;
    if (wid == 11 && (prog[0] & 3) == OP_Q) {
      const uint32_t a = prog[1];
      const char* p = ptr_add(P.kv[rank * 2 + ((a >> 10) & 1)], ((a >> 2) & 255) * (kSk * kDh * 2) + (threadIdx.x & 31) * 128);
#pragma unroll 1
      for (uint32_t k = 0; k < 3; k++) {
        wait_word(progress, k);
        p += SZ_KV;
        asm volatile("prefetch.global.L2 [%0];\nprefetch.global.L2 [%0 + 4096];" ::"l"(p));
      }
      __syncwarp();
    }
    if (wid == 8) {
      Cursor tail{0, 0};
      int head = 0, sh = 0;
      uint32_t cur = 0, used = 0;
      uint64_t fifo = 0;
      uint32_t dst, bar = 0, ev = ev0, done = 0;
      const uint64_t pol = evict_first();
      auto retire = [&]() {
        mbar_wait(empty0 + 8 * tail.bi, tail.ph);
        tail.next();
        used -= (uint32_t)fifo & 31;
        fifo >>= 5;
        sh -= 5;
        asm volatile("st.volatile.shared.u32 [%0], %1;" ::"r"(progress), "r"(++done) : "memory");
      };
      auto acquire = [&](uint32_t bytes) {
        uint32_t fp = bytes >> 12;
        if (cur + fp > (RING >> 12)) { fp += (RING >> 12) - cur; cur = 0; }
        used += fp;
        while (used > (RING >> 12) || sh == 5 * NBAR) retire();
        fifo |= (uint64_t)fp << sh;
        sh += 5;
        dst = sbase + (cur << 12);
        bar = full0 + 8 * head;
        cur += bytes >> 12;
        if (++head == NBAR) head = 0;
      };
      auto gate = [&]() {
        mbar_wait(ev, 0);
        ev += 8;
        asm volatile("fence.proxy.async.global;" ::: "memory");
      };
      for (int pc = 0;; pc++) {
        uint32_t op = prog[pc];
        const int type = op & 3;
        if (type == OP_END) break;
        if (op == OP_O) {
          gate();
          op = __shfl_sync(0xffffffffu, lds32(jobw), 0);
        }
        const int blk = (op >> 10) & 1;
        if (type == OP_Q) {
#pragma unroll 1
          for (int k = 0; k < 10; k++) {
            if (k == 9 && (op & P_GATE)) gate();
            acquire(SZ_Q);
            if ((pc > 0 || k >= EARLY) && elect()) {
              mbar_expect(bar, SZ_Q);
              tma2d(dst, &P.x[blk], bar, 64 * k, ((op >> 7) & 7) * kSq + rank * 128);
              if ((k & 1) == rank) tma3d_mc(dst + 16384, &P.wq[blk], bar, 0, 64 * k, 3 * ((op >> 2) & 31));
            }
          }
        } else if (type == OP_A) {
          const int row0 = ((op >> 2) & 255) * kSk;
          const CUtensorMap* kv_map = rank ? &P.v[blk] : &P.k[blk];
          if (op & F_PARK) {
            gate();
            acquire(SZ_PARK);
            if (elect()) {
              mbar_expect(bar, SZ_PARK);
              bulk_load_hint(dst, &P.g->tile[((op >> 20) * 2 + rank) * 3072], SZ_PARK, bar, pol);
            }
          }
#pragma unroll 1
          for (int t = 0; t < 32; t++) {
            const int isv = t == 31 ? 1 : (t == 0 ? 0 : (~t & 1));
            const int j = isv ? (t - 1) >> 1 : (t + 1) >> 1;
            const bool pair = t >= 3 && t < 31;
            const uint32_t kbar = bar;
            if (t == 31 && (op & P_GATE)) gate();
            acquire(SZ_KV);
            if (elect()) {
              mbar_expect(bar, !pair ? SZ_KV : isv ? 0 : 2 * SZ_KV);
              if (isv == (int)rank) tma4d_mc_hint(dst, kv_map, pair && isv ? kbar : bar, row0 / 8 + 8 * j, pol);
            }
          }
        } else {
          const int n = (op >> 13) & 127, nw = (op & P_WIDE) ? n - TAIL : 0;
          const uint4* part = &P.g->part[((((op >> 6) & 30) + ((op >> 21) & 1)) * 2 + rank) * 5120 + ((op >> 20) & 1) * 2560];
#pragma unroll 1
          for (int i = 0; i < n + (nw ? TAIL : 0); i++) {
            const int k = nw ? (i < n ? i : i - TAIL) : kSteps - n + i, h = (k * 43) >> 7, col = 5 * ((op >> 20) & 3);
            const uint4* src = &P.g->tile[(P.slot[((op >> 2) & 480) + h] * 2 + rank) * 3072 + (k - 3 * h) * 1024];
            const uint32_t j = (op & P_LD) ? i - n + 5 : 5, bytes = i < nw ? SZ_W : nw ? (i < n ? SZ_W2 : SZ_W3) : j < 5 ? SZ_OL : SZ_O;
            if ((op & P_PRE) ? i == 0 : j == 0) gate();
            if (i < n && (i == 0 || k == 3 * h)) gate();
            acquire(bytes);
            if (elect()) {
              mbar_expect(bar, bytes);
              if (bytes != SZ_W2) tma5d_mc(dst + 16384 + rank * (nw ? 12288 : 10240), nw ? &P.wo3[blk] : &P.wo[blk], bar, 8 * k + 4 * rank, nw ? col / 2 : col);
              bulk_load_hint(dst, src, 16384, bar, pol);
              if (nw && i < n) tma5d_mc(dst + bytes - 16384 + rank * 8192, &P.wo2[blk], bar, 8 * k + 4 * rank, col / 2 + 3);
              if (j < 5) bulk_load_hint(dst + SZ_O, part + j * 512, 8192, bar, pol);
              if ((op & P_PRE) && i < 10) asm volatile("cp.async.bulk.prefetch.L2.global [%0], 4096;" ::"l"(part + i * 256) : "memory");
            }
          }
        }
      }
#pragma unroll 1
      while (sh) retire();
    } else if (threadIdx.x == 288) {
      for (int pc = 0;; pc++) {
        const uint32_t op = prog[pc];
        const int type = op & 3;
        if (type == OP_END) break;
        if (type == OP_Q ? !(op & F_PARK) : type == OP_O && !(op & P_WIDE)) continue;
        const int id = type == OP_A ? (op >> 2) & 511 : type == OP_Q ? N_TILE + ((op >> 13) & 127) : ID_PART + ((op >> 5) & 60) + ((op >> 20) & 3);
        const uint32_t v = type == OP_O ? 1 : P.info[id] & 7;
        mbar_wait_long(odone0 + 8 * pc);
        flag_set(flag + 2 * id, v);
        if (type == OP_O && (op & P_WIDE)) flag_set(flag + 2 * id + 2, v);
      }
    } else if (wid == 10) {
      int i = threadIdx.x & 31;
      const int n_ev = P.prog[role].n_ev;
      auto event = [&]() { return i < n_ev ? P.prog[role].ev[i] : n_ev ? E_JOB | (i - n_ev) : 0; };
      uint32_t e = i < 8 ? event() : 0;
      for (uint32_t n = 0; __any_sync(0xffffffffu, e); n++) {
        uint32_t job = lds32(jobw);
        const int togo = (e & E_DRAW) ? (e & 1023) - lds32(progress) : 99;
        if (togo <= 0 && rank == 0) {
          job = P.job[atomicInc(&P.g->ticket, gridDim.x / 2 - 1)];
          asm volatile("{\n.reg .u32 a;\nmapa.shared::cluster.u32 a, %0, 1;\nst.volatile.shared::cluster.u32 [a], %1;\n"
                       "st.volatile.shared.u32 [%0], %1;\n}\n" ::"r"(jobw), "r"(job) : "memory");
        }
        if ((e & E_JOB) && job) {
          const uint32_t j = e & 63, heads = job == OP_O ? 0 : kH - ((job >> 2) & 31), jp = !(job & P_LD) ? 63 : (job & P_PRE) ? 0 : heads - 1, h = j - (j > jp);
          e = j == jp ? (ID_PART + ((job >> 5) & 60) + ((job >> 20) & 3)) | E_ON | E_LAST : h < heads ? (((job >> 2) & 511) + h) | E_ON | E_LAST : 0;
        }
        unsigned int* f = ptr_add(flag, 8 * (e & 1023));
        const bool ok = (e & E_ON) ? flag_get(f) - 1 < ((e & E_FREE) ? 1 : 7) : (e & E_DRAW) && job;
        if (ok) {
          mbar_arrive(ev0 + 8 * i);
          if (e & (E_FREE | E_LAST)) flag_dec(f);
          i += 8;
          e = event();
        }
        asm volatile("{\n.reg .pred p;\nsetp.ge.u32 p, %0, 0x400000;\n@p trap;\n}\n" ::"r"(n));
        if (!__any_sync(0xffffffffu, ok)) __nanosleep(__any_sync(0xffffffffu, job || togo <= 2) ? 100 : 600);
      }
    } else if (threadIdx.x == 352) {
      uint32_t items = 0;
      auto read = [&](int id) {
        if (!(P.info[id] & I_NEXT)) return;
        wait_word(progress, items);
        flag_dec(flag + 2 * id);
      };
      for (int pc = 0;; pc++) {
        const uint32_t op = prog[pc];
        const int type = op & 3;
        if (type == OP_END) break;
        if (type == OP_O) {
          const uint32_t n = (op >> 13) & 127, base = items;
#pragma unroll 1
          for (uint32_t k = 3, id = (op >> 2) & 511; k <= n; k += 3, id++) {
            items = base + k + (k + TAIL > n ? TAIL : 0);
            read(id);
          }
          items = base + n + TAIL;
        } else if (type == OP_A) {
          if (op & F_PARK) { items++; read(N_TILE + ((op >> 13) & 127)); }
          items += 32;
        } else {
          items += 10;
        }
      }
    }
    __syncwarp();
    asm volatile("barrier.cluster.arrive.relaxed;\nbarrier.cluster.wait;" ::: "memory");
  }
}

typedef CUresult (*EncodeFn)(CUtensorMap*, CUtensorMapDataType, cuuint32_t, void*, const cuuint64_t*, const cuuint64_t*,
                             const cuuint32_t*, const cuuint32_t*, CUtensorMapInterleave, CUtensorMapSwizzle,
                             CUtensorMapL2promotion, CUtensorMapFloatOOBfill);

void encode(EncodeFn fn, CUtensorMap* m, const void* ptr, int rank, const cuuint64_t* dims, const cuuint64_t* strides,
            const cuuint32_t* box, CUtensorMapSwizzle swz) {
  const cuuint32_t es[5] = {1, 1, 1, 1, 1};
  CUresult r = fn(m, CU_TENSOR_MAP_DATA_TYPE_BFLOAT16, rank, const_cast<void*>(ptr), dims, strides, box, es,
                  CU_TENSOR_MAP_INTERLEAVE_NONE, swz, CU_TENSOR_MAP_L2_PROMOTION_L2_128B, CU_TENSOR_MAP_FLOAT_OOB_FILL_NONE);
  if (r != CUDA_SUCCESS) fprintf(stderr, "cuTensorMapEncodeTiled failed: %d\n", (int)r);
}

struct Op { int type, flags, id, n, quarter, park, item0, items; double t0, t1; };
struct Use { double ready, gate, need, freed; int readers, slot, prev; bool next; };
struct PlanStats { double end, slack, park_slack; int slots, parks; uint32_t own[N_CL]; };

bool plan(const char* const* text, int n_pair, int phase, Params& P, PlanStats* stats = nullptr) {
  constexpr double T_Q = 7900, T_A = 24800, T_U = TU, T_O = 640, T_RUN = 800, T_WIDE = TW, AHEAD = 3500, PUBLISH = 1500;
  const double margin = 256.0 * ((P.dbg >> 8) & 255);
  static Op op[N_CL][MAX_OPS];
  static Use use[ID_PART];
  int n_op[N_CL], covered[2 * N_TEAM] = {};
  struct Ref { double t; Op* o; int id; };
  static Ref att[N_TILE + 1], dem[N_TILE], prk[MAX_PARK + 1], unp[MAX_PARK + 1], wr[ID_PART];
  auto sort = [](Ref* r, int n) {
    for (int i = 1; i < n; i++)
      for (int j = i; j > 0 && r[j].t < r[j - 1].t; j--) { Ref x = r[j]; r[j] = r[j - 1]; r[j - 1] = x; }
  };
  auto hex = [](char c) { return c <= '9' ? c - '0' : c - 'a' + 10; };
  for (int i = 0; i < n_pair; i++)
    for (const char* s = text[i]; *s; s++)
      for (int h = 0; *s == 'J' && h < 2; h++) {
        if (covered[2 * hex(s[1]) + h]) return false;
        covered[2 * hex(s[1]) + h] = 10 * (s[2 + 2 * h] - '0') + s[3 + 2 * h] - '0';
      }
  for (int c = 0; c < 2 * n_pair; c++) {
    int n = 0, items = 0;
    double t = 0;
    auto add = [&](int type, int flags, int id, int heads, int quarter, int its, double dt) {
      if (n < MAX_OPS) op[c][n] = {type, flags, id, heads, quarter, 0, items, its, t, t + dt};
      n++; items += its; t += dt;
    };
    for (const char* s = text[c >> 1]; *s; s++) {
      const int tm = hex(s[1]) & 15, nj = covered[2 * tm + (c & 1)];
      if (*s == 'N') { add(OP_Q, 0, 0, 0, 0, 10, T_Q); add(OP_A, 0, 0, 0, 0, 32, T_A); }
      if (*s == 'P') add(OP_Q, F_PARK, 0, 0, 0, 10, T_Q + TP);
      if (*s == '+' || *s == '-') t += *s == '+' ? 1000 : -1000;
      if (*s == 'U') { if (n == 0 || n > MAX_OPS || op[c][n - 1].type != OP_A) return false; add(OP_A, F_PARK, 0, 0, 0, 33, T_U); }
      if (*s == 'J') { if (nj < TAIL + 6 || nj > kSteps - 11) return false; add(OP_O, P_WIDE, tm * kH, nj, 2 * (c & 1), nj + TAIL, 2 * T_O * nj + T_WIDE); }
    }
    add(OP_O, 0, 0, 0, 0, 0, 0);
    add(OP_END, 0, 0, 0, 0, 0, 0);
    if (n > MAX_OPS || op[c][0].type != OP_Q) return false;
    n_op[c] = n - 1;
    att[c] = {t, &op[c][n - 2], 0};
  }
  for (int i = 0; i < 4 * N_TEAM; i++) dem[i] = {(double)covered[i / 2], nullptr, i};
  sort(att, 2 * n_pair); sort(dem, 4 * N_TEAM);
  for (int i = 0; i < 4 * N_TEAM; i++) {
    Op* f = att[i].o;
    const int nj = covered[dem[i].id / 2];
    f->flags = nj ? P_LD : 0;
    f->id = dem[i].id / 4 * kH + nj / 3; f->quarter = dem[i].id & 3; f->items = f->n = kSteps - nj;
    f[1].t0 = f[1].t1 = f->t1 = f->t0 + T_O * f->n + T_RUN; f[1].item0 += f->n;
  }
  for (int i = 0; i < ID_PART; i++) use[i] = {0, 0, 1e18, 0, 0, 0, 0, false};
  int n_att = 0, n_prk = 0, n_unp = 0;
  auto ready = [&](const Op* o) {
    const int nt = o[1].type;
    return o->t1 + (nt == OP_Q ? 6100 : o[1].n ? ((o[1].flags & P_WIDE) ? 7700 : 3900) : 1500) + PUBLISH;
  };
  for (int c = 0; c < 2 * n_pair; c++)
    for (Op* o = op[c]; o->type != OP_END; o++) {
      if (o->type == OP_A) { att[n_att] = {ready(o), o, 0}; if (++n_att > N_TILE) return false; }
      if (o->type == OP_A && o->flags) { unp[n_unp] = {o->t0 - AHEAD, o, 0}; if (++n_unp > MAX_PARK) return false; }
      if (o->type == OP_Q && o->flags) { prk[n_prk] = {ready(o), o, 0}; if (++n_prk > MAX_PARK) return false; }
      for (int i = 0; o->type == OP_O && i < o->n; i++) {
        const int nw = (o->flags & P_WIDE) ? o->n - TAIL : 0, k = nw ? i : kSteps - o->n + i;
        Use& u = use[o->id / kH * kH + k / 3];
        const double t = o->t0 + T_O * (i + (i < nw ? i : nw));
        if (t - AHEAD < u.need) u.need = t - AHEAD;
        const double f = !nw ? 1e18 : i + NBAR < o->items - TAIL || (nw && o[1].type != OP_O) ? t + T_O * (i < nw ? 2 : 1 + TAIL) + PUBLISH : 1e18;
        if (f > u.freed) u.freed = f;
        if (i == 0 || k % 3 == 0) u.readers++;
      }
    }
  if (n_att != N_TILE || n_prk != n_unp) return false;
  for (int i = 0; i < N_TILE; i++) { const int id = (i & 15) * kH + (i >> 4); dem[i] = {use[id].need, nullptr, id}; }
  sort(att, n_att); sort(dem, N_TILE); sort(prk, n_prk); sort(unp, n_unp);
  PlanStats st = {0, 1e18, 1e18, 0, n_prk};
  int n_wr = 0;
  for (int i = 0; i < N_TILE; i++) {
    Op* o = att[i].o;
    o->id = dem[i].id;
    if (!o->flags) o[-1].id = o->id;
    if (dem[i].t - att[i].t < st.slack) st.slack = dem[i].t - att[i].t;
    wr[n_wr++] = {o->t1 - 2 * AHEAD, o, o->id};
  }
  for (int i = 0; i < n_prk; i++) {
    prk[i].o->id = unp[i].o->id;
    prk[i].o->park = unp[i].o->park = i;
    use[N_TILE + i].freed = unp[i].o->t0 + 2 * PUBLISH;
    use[N_TILE + i].readers = 1;
    if (unp[i].t - prk[i].t < st.park_slack) st.park_slack = unp[i].t - prk[i].t;
    wr[n_wr++] = {prk[i].o->t1 - 2 * AHEAD, prk[i].o, N_TILE + i};
  }
  for (int c = 0; c < 2 * n_pair; c++)
    for (int d = 0; d < 2 * n_pair; d++)
      for (Op *f = &op[c][n_op[c] - 1], *o = op[d]; f->n && o->type != OP_END; o++)
        if (o->type == OP_O && (o->flags & P_WIDE) && o->id / kH == f->id / kH && o->quarter / 2 == f->quarter / 2) {
          if (f->t0 - o->t1 > 4096.0 * ((P.dbg >> 16) & 255)) f->flags |= P_PRE;
          const double slack = f->t0 + ((f->flags & P_PRE) ? 0 : (f->n - 5) * T_O) - AHEAD - ready(o);
          if (slack < st.park_slack) st.park_slack = slack;
        }
  sort(wr, n_wr);
  int holder[N_TILE];
  for (int i = 0; i < n_wr; i++) {
    int best = -1;
    for (int sl = 0; sl < st.slots; sl++)
      if (use[holder[sl]].freed + margin <= wr[i].t && (best < 0 || use[holder[sl]].freed < use[holder[best]].freed)) best = sl;
    Use& u = use[wr[i].id];
    if (best >= 0) { u.prev = holder[best]; use[u.prev].next = true; wr[i].o->flags |= P_GATE; }
    else if (st.slots == N_TILE) return false;
    else best = st.slots++;
    u.slot = best;
    holder[best] = wr[i].id;
  }
  {
    int pos[N_CL] = {}, flag[ID_PART + 4 * N_TEAM] = {}, seen[ID_PART] = {};
    auto goal = [&](int c) { return op[c][n_op[c] - 1].item0; };
    for (bool moved = true; moved;) {
      moved = false;
      for (int c = 0; c < 2 * n_pair; c++) {
        for (; pos[c] < goal(c); pos[c]++, moved = true) {
          bool ok = true;
          for (const Op* o = op[c]; o->type != OP_END; o++) {
            const int k = pos[c] - o->item0, own = o->type == OP_A ? o->id : N_TILE + o->park;
            if (k < 0 || k >= o->items) continue;
            if (o->type == OP_O) ok = k >= o->n || flag[o->id + k / 3];
            else if (k == o->items - 1 && (o->flags & P_GATE)) ok = seen[use[own].prev] == use[use[own].prev].readers;
            else if (k == 0 && o->type == OP_A && (o->flags & F_PARK)) ok = flag[N_TILE + o->park];
          }
          if (!ok) break;
          for (const Op* o = op[c]; o->type != OP_END; o++) {
            if (pos[c] == o->item0 + o->items + (o[1].type == OP_Q ? 7 : o[1].item0 == goal(c) ? -1 : 5)) {
              if (o->type == OP_A) flag[o->id] = 1;
              if (o->type == OP_Q && (o->flags & F_PARK)) flag[N_TILE + o->park] = 1;
              if (o->type == OP_O) flag[ID_PART + o->id / kH * 4 + o->quarter] = flag[ID_PART + o->id / kH * 4 + o->quarter + 1] = 1;
            }
            const int k = pos[c] - NBAR - o->item0, nw = o->n - TAIL;
            if (k == 0 && o->type == OP_A && (o->flags & F_PARK)) seen[N_TILE + o->park]++;
            if (o->type == OP_O && k >= 0 && k < o->items && (k < nw || k >= o->n) && (k < nw ? k : k - TAIL) % 3 == 2) seen[o->id + (k < nw ? k : k - TAIL) / 3]++;
          }
        }
      }
    }
    for (int c = 0; c < 2 * n_pair; c++) if (pos[c] < goal(c)) return false;
  }
  int n_job = 0;
  for (int c = 0; c < 2 * n_pair; c++) {
    uint32_t items = 0, cur = 0, pend = 0;
    int n = 0, ev = 0;
    auto item = [&](uint32_t bytes, int count) {
      for (int i = 0; i < count; i++) { if (cur + bytes > RING) cur = 0; cur += bytes; items++; }
    };
    auto event = [&](uint32_t e) { if (ev < MAX_TAB) P.prog[c].ev[ev] = e; ev++; };
    for (const Op* o = op[c];; o++) {
      if (o->type != OP_END && phase && (o->type == OP_O) != (phase == 2)) continue;
      uint32_t cw = o->type | (items % NBAR) << 15 | ((items / NBAR) & 1) << 19 | (cur >> 12) << 20 | pend, pw = o->type | o->id << 2 | o->flags;
      const int ps = use[N_TILE + o->park].slot;
      pend = 0;
      if (o->type == OP_O) {
        pw |= o->n << 13 | o->quarter << 20;
        if (o->flags & P_WIDE) {
          cw |= o->n << 2 | (o->id / kH * 2 + o->quarter / 2) << 9 | C_WIDE;
          item(SZ_W, o->n - TAIL);
          item(SZ_W2, TAIL);
          item(SZ_W3, TAIL);
          pend = C_PEND;
          for (int i = 0; 3 * i < o->n; i++) event((o->id + i) | E_ON | (use[o->id + i].next ? 0 : E_LAST));
        } else {
          dem[n_job++] = {o->t0 - 1e6 * o->n, nullptr, (int)pw};
          st.own[c] = pw;
          pw = OP_O;
          event(E_DRAW | (items < 16 ? 0 : items - 16));
        }
      } else if (o->type != OP_END) {
        const bool parks = o->type == OP_Q && (o->flags & F_PARK);
        cw |= (parks ? ps : use[o->id].slot) << 2 | (o->flags & F_PARK);
        if (o->flags & F_PARK) pw |= o->park << 13 | ps << 20;
        if (o->type == OP_Q) item(SZ_Q, 10);
        else { if (o->flags & F_PARK) { item(SZ_PARK, 1); event((N_TILE + o->park) | E_ON | (use[N_TILE + o->park].next ? 0 : E_LAST)); } item(SZ_KV, 32); }
        if (parks || o->type == OP_A) pend = C_PEND;
        if (o->flags & P_GATE) event(use[parks ? N_TILE + o->park : o->id].prev | E_ON | E_FREE);
      }
      P.prog[c].c[n] = cw; P.prog[c].p[n++] = pw;
      if (o->type == OP_END) { if (o->t0 > st.end) st.end = o->t0; break; }
    }
    if (ev > MAX_TAB) return false;
    P.prog[c].n_ev = ev;
    while (n < MAX_OPS) { P.prog[c].c[n] = OP_END; P.prog[c].p[n++] = OP_END; }
    P.first[c] = (uint16_t)(P.prog[c].p[0] & 2047);
  }
  sort(dem, n_job);
  for (int i = 0; i < n_job; i++) P.job[i] = dem[i].id;
  for (int i = 0; i < ID_PART; i++) {
    if (i < N_TILE) P.slot[i] = use[i].slot;
    P.info[i] = (use[i].readers + use[i].next) | (use[i].next ? I_NEXT : 0);
  }
  if (stats) *stats = st;
  return true;
}

const char* const kPrograms[N_CL / 2] = {
  "PNJ06565NNNNN", "PNJ15858NNNNN", "PNJ25656NNNNN", "PNJ35454+NNNNN", "PNJ47878NNNNN", "PNJ57373NNNNN",
  "NNJ68080NNNN", "NNJ76868NNNN", "NNNNNJ83535NN", "NNNNNNJf4343N", "NNNNNJa5252NN", "NNNNNJb4848NN",
  "NUNNNNNNN", "NUNNNJd5353NN", "NUNNNJe6363NN", "NNNNNJ97676N", "PNNNNNNNNN", "PNNNNNNNNN",
  "PNNNNNNNNN", "PNNNNNNNNN", "PNNNNNNNNN", "NNNNNNNNN", "NNNNNNNNN", "NNNNNNNNN",
  "NUNNNNNNN", "NNNNNNNNN", "NUNNNNNNN", "NUNNNNNNN", "NNUNNNNNN", "NUNNNNNNN",
  "NUNNNNNNN", "NNUNNJc5353NN", "NUNNNNNNN",
};

const char* const* bench_programs() {
  return kPrograms;
}

}

extern "C" void kernel_launch(void* const* d_in, const int* in_sizes, int n_in, void* d_out, int out_size) {
  (void)in_sizes; (void)n_in; (void)out_size;
  static EncodeFn fn = nullptr;
  static int n_clusters = 0;
  if (!fn) {
    cudaDriverEntryPointQueryResult qr;
    void* f = nullptr;
    cudaGetDriverEntryPoint("cuTensorMapEncodeTiled", &f, cudaEnableDefault, &qr);
    fn = (EncodeFn)f;
    cudaFuncSetAttribute(fused_kernel, cudaFuncAttributeMaxDynamicSharedMemorySize, SMEM_BYTES);
    cudaLaunchConfig_t cfg = {};
    cfg.gridDim = dim3(132); cfg.blockDim = dim3(384); cfg.dynamicSmemBytes = SMEM_BYTES;
    cudaLaunchAttribute at[1];
    at[0].id = cudaLaunchAttributeClusterDimension; at[0].val.clusterDim.x = 2; at[0].val.clusterDim.y = 1; at[0].val.clusterDim.z = 1;
    cfg.attrs = at; cfg.numAttrs = 1;
    if (cudaOccupancyMaxActiveClusters(&n_clusters, fused_kernel, &cfg) != cudaSuccess || n_clusters < 1) n_clusters = 1;
    (void)cudaGetLastError();
  }
  static Params P;
  const CUtensorMapSwizzle S128 = CU_TENSOR_MAP_SWIZZLE_128B, S64 = CU_TENSOR_MAP_SWIZZLE_64B;
  for (int blk = 0; blk < 2; blk++) {
    void* const* in = d_in + 5 * blk;
    { const cuuint64_t d[] = {kD, kB * kSq}, s[] = {kD * 2}; const cuuint32_t b[] = {64, 128};
      encode(fn, &P.x[blk], in[0], 2, d, s, b, S128); }
    { const cuuint64_t d[] = {64, 8, 3, (cuuint64_t)kB * kH * kSk / 8}, s[] = {kDh * 2, 128, 8 * kDh * 2}; const cuuint32_t b[] = {64, 8, 3, 8};
      encode(fn, &P.k[blk], in[1], 4, d, s, b, S128);
      encode(fn, &P.v[blk], in[2], 4, d, s, b, S128); }
    { const cuuint64_t d[] = {64, kD, kHD / 64}, s[] = {kHD * 2, 128}; const cuuint32_t b[] = {64, 64, 3};
      encode(fn, &P.wq[blk], in[3], 3, d, s, b, S128); }
    { const cuuint64_t d[] = {32, 2, kHD / 8, 4, kD / 32}, s[] = {kD * 2, 8 * kD * 2, 2 * kD * 2, 64}; const cuuint32_t b[] = {32, 2, 4, 4, 5};
      encode(fn, &P.wo[blk], in[4], 5, d, s, b, S64); }
    { const cuuint64_t d[] = {64, 2, kHD / 8, 4, kD / 64}, s[] = {kD * 2, 8 * kD * 2, 2 * kD * 2, 128};
      const cuuint32_t b3[] = {64, 2, 4, 4, 3}, b2[] = {64, 2, 4, 4, 2};
      encode(fn, &P.wo3[blk], in[4], 5, d, s, b3, S128);
      encode(fn, &P.wo2[blk], in[4], 5, d, s, b2, S128); }
  }
  { const cuuint64_t d[] = {32, kB * kSq, 2 * kD / 32}, s[] = {2 * kD * 2, 64}; const cuuint32_t b[] = {32, 16, 1};
    encode(fn, &P.out, d_out, 3, d, s, b, S64); }

  P.kv[0] = (const char*)d_in[1]; P.kv[1] = (const char*)d_in[6]; P.kv[2] = (const char*)d_in[2]; P.kv[3] = (const char*)d_in[7];
  P.xw[0] = (const char*)d_in[0]; P.xw[1] = (const char*)d_in[3];
  cudaGetSymbolAddress((void**)&P.g, g_scratch);
  P.dbg = DBG_DEFAULT;
  if (n_clusters >= N_CL && plan(bench_programs(), N_CL / 2, 0, P)) {
    fused_kernel<<<2 * N_CL, 384, SMEM_BYTES>>>(P);
  } else {
    const char* text[2 * N_TEAM];
    for (int i = 0; i < 2 * N_TEAM; i++) text[i] = "NNNNNNNN";
    for (int phase = 1; phase <= 2; phase++) {
      plan(text, 2 * N_TEAM, phase, P);
      fused_kernel<<<8 * N_TEAM, 384, SMEM_BYTES>>>(P);
    }
  }
}
```

```cpp
#include <cuda_runtime.h>
#include <cuda_bf16.h>
#include <cuda.h>
#include <stdint.h>
#include <stdio.h>

namespace {

constexpr int kB = 8, kSq = 256, kD = 640, kH = 32, kSk = 1024, kDh = 192;
constexpr int kHD = kH * kDh;
constexpr uint32_t RING = 224 * 1024;
constexpr uint32_t SZ_KV = 24576;
constexpr uint32_t SZ_Q = 16384 + 24576;
constexpr uint32_t SZ_O = 16384 + 20480;
constexpr uint32_t SZ_W3 = 16384 + 24576, SZ_W2 = 16384 + 16384, SZ_W = SZ_W3 + 16384;
constexpr uint32_t SZ_PARK = 49152;
constexpr uint32_t SZ_OL = SZ_O + 8192;
constexpr int NBAR = 16, FLIGHT = RING / SZ_KV + 1;
constexpr int EARLY = 3;
constexpr int kSteps = kHD / 64;
constexpr int TAIL = 4;
constexpr uint32_t KV_CH = 64, KV_SBO = 3072;
constexpr int SMEM_BYTES = RING + 1024 + 1024;
constexpr int N_TEAM = 16, N_CL = 66, MAX_OPS = 22, MAX_EV = 72, MAX_TAB = 47, N_TILE = N_TEAM * kH, MAX_PARK = 128, ID_PART = N_TILE + MAX_PARK;
enum : uint32_t { OP_END = 0, OP_Q = 1, OP_A = 2, OP_O = 3, F_PARK = 1 << 11,
                  C_WIDE = 1 << 27, C_PEND = 1 << 26, P_GATE = 1 << 12, P_WIDE = 1 << 11, P_LD = 1 << 12, P_PRE = 1 << 22, P_LASTW = 1 << 29, P_LASTX = 1 << 30,
                  I_NEXT = 8, E_ON = 1 << 15, E_FREE = 1 << 14, E_LAST = 1 << 13, E_DRAW = 1 << 12, E_JOB = 1 << 11 };

#define TU 25900
#define TW 1600
#define TP 1000
constexpr uint32_t DBG_DEFAULT = 0x040800;

struct alignas(1024) Scratch {
  unsigned int flag[2047];
  unsigned int ticket;
  uint4 part[N_TEAM * 2 * 2 * 5120];
  uint4 tile[N_TILE * 2 * 3072];
};

struct alignas(64) Params {
  const char* xw[2];
  uint16_t first[80];
  Scratch* g;
  uint32_t dbg;
  CUtensorMap x[2], wq[2], k[2], v[2], wo[2], wo3[2], wo2[2], out;
  struct {
    uint32_t c[MAX_OPS];
    uint32_t p[MAX_OPS];
    uint16_t n_ev, ev[MAX_TAB];
  } prog[N_CL];
  const char* kv[4];
  uint32_t job[N_CL];
  uint16_t slot[N_TILE];
  uint8_t info[ID_PART];
};

__device__ Scratch g_scratch;

template <int TB, int TA = 0>
__device__ __forceinline__ void wgmma_ss_n64(float (&d)[32], uint64_t da, uint64_t db, int scale_d) {
  asm volatile("{\n.reg .pred p;\nsetp.ne.b32 p, %34, 0;\n"
    "wgmma.mma_async.sync.aligned.m64n64k16.f32.bf16.bf16 {%0, %1, %2, %3, %4, %5, %6, %7, %8, %9, %10, %11, %12, %13, %14, %15, %16, %17, %18, %19, %20, %21, %22, %23, %24, %25, %26, %27, %28, %29, %30, %31}, %32, %33, p, 1, 1, %35, %36;\n}\n"
    : "+f"(d[0]), "+f"(d[1]), "+f"(d[2]), "+f"(d[3]), "+f"(d[4]), "+f"(d[5]), "+f"(d[6]), "+f"(d[7]), "+f"(d[8]), "+f"(d[9]), "+f"(d[10]), "+f"(d[11]), "+f"(d[12]), "+f"(d[13]), "+f"(d[14]), "+f"(d[15]), "+f"(d[16]), "+f"(d[17]), "+f"(d[18]), "+f"(d[19]), "+f"(d[20]), "+f"(d[21]), "+f"(d[22]), "+f"(d[23]), "+f"(d[24]), "+f"(d[25]), "+f"(d[26]), "+f"(d[27]), "+f"(d[28]), "+f"(d[29]), "+f"(d[30]), "+f"(d[31])
    : "l"(da), "l"(db), "r"(scale_d), "n"(TA), "n"(TB));
}
template <int TB>
__device__ __forceinline__ void wgmma_rs_n64(float (&d)[32], uint32_t a0, uint32_t a1, uint32_t a2, uint32_t a3, uint64_t db, int scale_d) {
  asm volatile("{\n.reg .pred p;\nsetp.ne.b32 p, %37, 0;\n"
    "wgmma.mma_async.sync.aligned.m64n64k16.f32.bf16.bf16 {%0, %1, %2, %3, %4, %5, %6, %7, %8, %9, %10, %11, %12, %13, %14, %15, %16, %17, %18, %19, %20, %21, %22, %23, %24, %25, %26, %27, %28, %29, %30, %31}, {%32, %33, %34, %35}, %36, p, 1, 1, %38;\n}\n"
    : "+f"(d[0]), "+f"(d[1]), "+f"(d[2]), "+f"(d[3]), "+f"(d[4]), "+f"(d[5]), "+f"(d[6]), "+f"(d[7]), "+f"(d[8]), "+f"(d[9]), "+f"(d[10]), "+f"(d[11]), "+f"(d[12]), "+f"(d[13]), "+f"(d[14]), "+f"(d[15]), "+f"(d[16]), "+f"(d[17]), "+f"(d[18]), "+f"(d[19]), "+f"(d[20]), "+f"(d[21]), "+f"(d[22]), "+f"(d[23]), "+f"(d[24]), "+f"(d[25]), "+f"(d[26]), "+f"(d[27]), "+f"(d[28]), "+f"(d[29]), "+f"(d[30]), "+f"(d[31])
    : "r"(a0), "r"(a1), "r"(a2), "r"(a3), "l"(db), "r"(scale_d), "n"(TB));
}
template <int TB, int TA = 0>
__device__ __forceinline__ void wgmma_ss_n128(float (&d)[64], uint64_t da, uint64_t db, int scale_d) {
  asm volatile("{\n.reg .pred p;\nsetp.ne.b32 p, %66, 0;\n"
    "wgmma.mma_async.sync.aligned.m64n128k16.f32.bf16.bf16 {%0, %1, %2, %3, %4, %5, %6, %7, %8, %9, %10, %11, %12, %13, %14, %15, %16, %17, %18, %19, %20, %21, %22, %23, %24, %25, %26, %27, %28, %29, %30, %31, %32, %33, %34, %35, %36, %37, %38, %39, %40, %41, %42, %43, %44, %45, %46, %47, %48, %49, %50, %51, %52, %53, %54, %55, %56, %57, %58, %59, %60, %61, %62, %63}, %64, %65, p, 1, 1, %67, %68;\n}\n"
    : "+f"(d[0]), "+f"(d[1]), "+f"(d[2]), "+f"(d[3]), "+f"(d[4]), "+f"(d[5]), "+f"(d[6]), "+f"(d[7]), "+f"(d[8]), "+f"(d[9]), "+f"(d[10]), "+f"(d[11]), "+f"(d[12]), "+f"(d[13]), "+f"(d[14]), "+f"(d[15]), "+f"(d[16]), "+f"(d[17]), "+f"(d[18]), "+f"(d[19]), "+f"(d[20]), "+f"(d[21]), "+f"(d[22]), "+f"(d[23]), "+f"(d[24]), "+f"(d[25]), "+f"(d[26]), "+f"(d[27]), "+f"(d[28]), "+f"(d[29]), "+f"(d[30]), "+f"(d[31]), "+f"(d[32]), "+f"(d[33]), "+f"(d[34]), "+f"(d[35]), "+f"(d[36]), "+f"(d[37]), "+f"(d[38]), "+f"(d[39]), "+f"(d[40]), "+f"(d[41]), "+f"(d[42]), "+f"(d[43]), "+f"(d[44]), "+f"(d[45]), "+f"(d[46]), "+f"(d[47]), "+f"(d[48]), "+f"(d[49]), "+f"(d[50]), "+f"(d[51]), "+f"(d[52]), "+f"(d[53]), "+f"(d[54]), "+f"(d[55]), "+f"(d[56]), "+f"(d[57]), "+f"(d[58]), "+f"(d[59]), "+f"(d[60]), "+f"(d[61]), "+f"(d[62]), "+f"(d[63])
    : "l"(da), "l"(db), "r"(scale_d), "n"(TA), "n"(TB));
}
template <int TB>
__device__ __forceinline__ void wgmma_rs_n128(float (&d)[64], uint32_t a0, uint32_t a1, uint32_t a2, uint32_t a3, uint64_t db, int scale_d) {
  asm volatile("{\n.reg .pred p;\nsetp.ne.b32 p, %69, 0;\n"
    "wgmma.mma_async.sync.aligned.m64n128k16.f32.bf16.bf16 {%0, %1, %2, %3, %4, %5, %6, %7, %8, %9, %10, %11, %12, %13, %14, %15, %16, %17, %18, %19, %20, %21, %22, %23, %24, %25, %26, %27, %28, %29, %30, %31, %32, %33, %34, %35, %36, %37, %38, %39, %40, %41, %42, %43, %44, %45, %46, %47, %48, %49, %50, %51, %52, %53, %54, %55, %56, %57, %58, %59, %60, %61, %62, %63}, {%64, %65, %66, %67}, %68, p, 1, 1, %70;\n}\n"
    : "+f"(d[0]), "+f"(d[1]), "+f"(d[2]), "+f"(d[3]), "+f"(d[4]), "+f"(d[5]), "+f"(d[6]), "+f"(d[7]), "+f"(d[8]), "+f"(d[9]), "+f"(d[10]), "+f"(d[11]), "+f"(d[12]), "+f"(d[13]), "+f"(d[14]), "+f"(d[15]), "+f"(d[16]), "+f"(d[17]), "+f"(d[18]), "+f"(d[19]), "+f"(d[20]), "+f"(d[21]), "+f"(d[22]), "+f"(d[23]), "+f"(d[24]), "+f"(d[25]), "+f"(d[26]), "+f"(d[27]), "+f"(d[28]), "+f"(d[29]), "+f"(d[30]), "+f"(d[31]), "+f"(d[32]), "+f"(d[33]), "+f"(d[34]), "+f"(d[35]), "+f"(d[36]), "+f"(d[37]), "+f"(d[38]), "+f"(d[39]), "+f"(d[40]), "+f"(d[41]), "+f"(d[42]), "+f"(d[43]), "+f"(d[44]), "+f"(d[45]), "+f"(d[46]), "+f"(d[47]), "+f"(d[48]), "+f"(d[49]), "+f"(d[50]), "+f"(d[51]), "+f"(d[52]), "+f"(d[53]), "+f"(d[54]), "+f"(d[55]), "+f"(d[56]), "+f"(d[57]), "+f"(d[58]), "+f"(d[59]), "+f"(d[60]), "+f"(d[61]), "+f"(d[62]), "+f"(d[63])
    : "r"(a0), "r"(a1), "r"(a2), "r"(a3), "l"(db), "r"(scale_d), "n"(TB));
}
template <int TB, int TA = 0>
__device__ __forceinline__ void wgmma_ss_n160(float (&d)[80], uint64_t da, uint64_t db, int scale_d) {
  asm volatile("{\n.reg .pred p;\nsetp.ne.b32 p, %82, 0;\n"
    "wgmma.mma_async.sync.aligned.m64n160k16.f32.bf16.bf16 {%0, %1, %2, %3, %4, %5, %6, %7, %8, %9, %10, %11, %12, %13, %14, %15, %16, %17, %18, %19, %20, %21, %22, %23, %24, %25, %26, %27, %28, %29, %30, %31, %32, %33, %34, %35, %36, %37, %38, %39, %40, %41, %42, %43, %44, %45, %46, %47, %48, %49, %50, %51, %52, %53, %54, %55, %56, %57, %58, %59, %60, %61, %62, %63, %64, %65, %66, %67, %68, %69, %70, %71, %72, %73, %74, %75, %76, %77, %78, %79}, %80, %81, p, 1, 1, %83, %84;\n}\n"
    : "+f"(d[0]), "+f"(d[1]), "+f"(d[2]), "+f"(d[3]), "+f"(d[4]), "+f"(d[5]), "+f"(d[6]), "+f"(d[7]), "+f"(d[8]), "+f"(d[9]), "+f"(d[10]), "+f"(d[11]), "+f"(d[12]), "+f"(d[13]), "+f"(d[14]), "+f"(d[15]), "+f"(d[16]), "+f"(d[17]), "+f"(d[18]), "+f"(d[19]), "+f"(d[20]), "+f"(d[21]), "+f"(d[22]), "+f"(d[23]), "+f"(d[24]), "+f"(d[25]), "+f"(d[26]), "+f"(d[27]), "+f"(d[28]), "+f"(d[29]), "+f"(d[30]), "+f"(d[31]), "+f"(d[32]), "+f"(d[33]), "+f"(d[34]), "+f"(d[35]), "+f"(d[36]), "+f"(d[37]), "+f"(d[38]), "+f"(d[39]), "+f"(d[40]), "+f"(d[41]), "+f"(d[42]), "+f"(d[43]), "+f"(d[44]), "+f"(d[45]), "+f"(d[46]), "+f"(d[47]), "+f"(d[48]), "+f"(d[49]), "+f"(d[50]), "+f"(d[51]), "+f"(d[52]), "+f"(d[53]), "+f"(d[54]), "+f"(d[55]), "+f"(d[56]), "+f"(d[57]), "+f"(d[58]), "+f"(d[59]), "+f"(d[60]), "+f"(d[61]), "+f"(d[62]), "+f"(d[63]), "+f"(d[64]), "+f"(d[65]), "+f"(d[66]), "+f"(d[67]), "+f"(d[68]), "+f"(d[69]), "+f"(d[70]), "+f"(d[71]), "+f"(d[72]), "+f"(d[73]), "+f"(d[74]), "+f"(d[75]), "+f"(d[76]), "+f"(d[77]), "+f"(d[78]), "+f"(d[79])
    : "l"(da), "l"(db), "r"(scale_d), "n"(TA), "n"(TB));
}
template <int TB>
__device__ __forceinline__ void wgmma_rs_n160(float (&d)[80], uint32_t a0, uint32_t a1, uint32_t a2, uint32_t a3, uint64_t db, int scale_d) {
  asm volatile("{\n.reg .pred p;\nsetp.ne.b32 p, %85, 0;\n"
    "wgmma.mma_async.sync.aligned.m64n160k16.f32.bf16.bf16 {%0, %1, %2, %3, %4, %5, %6, %7, %8, %9, %10, %11, %12, %13, %14, %15, %16, %17, %18, %19, %20, %21, %22, %23, %24, %25, %26, %27, %28, %29, %30, %31, %32, %33, %34, %35, %36, %37, %38, %39, %40, %41, %42, %43, %44, %45, %46, %47, %48, %49, %50, %51, %52, %53, %54, %55, %56, %57, %58, %59, %60, %61, %62, %63, %64, %65, %66, %67, %68, %69, %70, %71, %72, %73, %74, %75, %76, %77, %78, %79}, {%80, %81, %82, %83}, %84, p, 1, 1, %86;\n}\n"
    : "+f"(d[0]), "+f"(d[1]), "+f"(d[2]), "+f"(d[3]), "+f"(d[4]), "+f"(d[5]), "+f"(d[6]), "+f"(d[7]), "+f"(d[8]), "+f"(d[9]), "+f"(d[10]), "+f"(d[11]), "+f"(d[12]), "+f"(d[13]), "+f"(d[14]), "+f"(d[15]), "+f"(d[16]), "+f"(d[17]), "+f"(d[18]), "+f"(d[19]), "+f"(d[20]), "+f"(d[21]), "+f"(d[22]), "+f"(d[23]), "+f"(d[24]), "+f"(d[25]), "+f"(d[26]), "+f"(d[27]), "+f"(d[28]), "+f"(d[29]), "+f"(d[30]), "+f"(d[31]), "+f"(d[32]), "+f"(d[33]), "+f"(d[34]), "+f"(d[35]), "+f"(d[36]), "+f"(d[37]), "+f"(d[38]), "+f"(d[39]), "+f"(d[40]), "+f"(d[41]), "+f"(d[42]), "+f"(d[43]), "+f"(d[44]), "+f"(d[45]), "+f"(d[46]), "+f"(d[47]), "+f"(d[48]), "+f"(d[49]), "+f"(d[50]), "+f"(d[51]), "+f"(d[52]), "+f"(d[53]), "+f"(d[54]), "+f"(d[55]), "+f"(d[56]), "+f"(d[57]), "+f"(d[58]), "+f"(d[59]), "+f"(d[60]), "+f"(d[61]), "+f"(d[62]), "+f"(d[63]), "+f"(d[64]), "+f"(d[65]), "+f"(d[66]), "+f"(d[67]), "+f"(d[68]), "+f"(d[69]), "+f"(d[70]), "+f"(d[71]), "+f"(d[72]), "+f"(d[73]), "+f"(d[74]), "+f"(d[75]), "+f"(d[76]), "+f"(d[77]), "+f"(d[78]), "+f"(d[79])
    : "r"(a0), "r"(a1), "r"(a2), "r"(a3), "l"(db), "r"(scale_d), "n"(TB));
}
template <int TB, int TA = 0>
__device__ __forceinline__ void wgmma_ss_n192(float (&d)[96], uint64_t da, uint64_t db, int scale_d) {
  asm volatile("{\n.reg .pred p;\nsetp.ne.b32 p, %98, 0;\n"
    "wgmma.mma_async.sync.aligned.m64n192k16.f32.bf16.bf16 {%0, %1, %2, %3, %4, %5, %6, %7, %8, %9, %10, %11, %12, %13, %14, %15, %16, %17, %18, %19, %20, %21, %22, %23, %24, %25, %26, %27, %28, %29, %30, %31, %32, %33, %34, %35, %36, %37, %38, %39, %40, %41, %42, %43, %44, %45, %46, %47, %48, %49, %50, %51, %52, %53, %54, %55, %56, %57, %58, %59, %60, %61, %62, %63, %64, %65, %66, %67, %68, %69, %70, %71, %72, %73, %74, %75, %76, %77, %78, %79, %80, %81, %82, %83, %84, %85, %86, %87, %88, %89, %90, %91, %92, %93, %94, %95}, %96, %97, p, 1, 1, %99, %100;\n}\n"
    : "+f"(d[0]), "+f"(d[1]), "+f"(d[2]), "+f"(d[3]), "+f"(d[4]), "+f"(d[5]), "+f"(d[6]), "+f"(d[7]), "+f"(d[8]), "+f"(d[9]), "+f"(d[10]), "+f"(d[11]), "+f"(d[12]), "+f"(d[13]), "+f"(d[14]), "+f"(d[15]), "+f"(d[16]), "+f"(d[17]), "+f"(d[18]), "+f"(d[19]), "+f"(d[20]), "+f"(d[21]), "+f"(d[22]), "+f"(d[23]), "+f"(d[24]), "+f"(d[25]), "+f"(d[26]), "+f"(d[27]), "+f"(d[28]), "+f"(d[29]), "+f"(d[30]), "+f"(d[31]), "+f"(d[32]), "+f"(d[33]), "+f"(d[34]), "+f"(d[35]), "+f"(d[36]), "+f"(d[37]), "+f"(d[38]), "+f"(d[39]), "+f"(d[40]), "+f"(d[41]), "+f"(d[42]), "+f"(d[43]), "+f"(d[44]), "+f"(d[45]), "+f"(d[46]), "+f"(d[47]), "+f"(d[48]), "+f"(d[49]), "+f"(d[50]), "+f"(d[51]), "+f"(d[52]), "+f"(d[53]), "+f"(d[54]), "+f"(d[55]), "+f"(d[56]), "+f"(d[57]), "+f"(d[58]), "+f"(d[59]), "+f"(d[60]), "+f"(d[61]), "+f"(d[62]), "+f"(d[63]), "+f"(d[64]), "+f"(d[65]), "+f"(d[66]), "+f"(d[67]), "+f"(d[68]), "+f"(d[69]), "+f"(d[70]), "+f"(d[71]), "+f"(d[72]), "+f"(d[73]), "+f"(d[74]), "+f"(d[75]), "+f"(d[76]), "+f"(d[77]), "+f"(d[78]), "+f"(d[79]), "+f"(d[80]), "+f"(d[81]), "+f"(d[82]), "+f"(d[83]), "+f"(d[84]), "+f"(d[85]), "+f"(d[86]), "+f"(d[87]), "+f"(d[88]), "+f"(d[89]), "+f"(d[90]), "+f"(d[91]), "+f"(d[92]), "+f"(d[93]), "+f"(d[94]), "+f"(d[95])
    : "l"(da), "l"(db), "r"(scale_d), "n"(TA), "n"(TB));
}
template <int TB>
__device__ __forceinline__ void wgmma_rs_n192(float (&d)[96], uint32_t a0, uint32_t a1, uint32_t a2, uint32_t a3, uint64_t db, int scale_d) {
  asm volatile("{\n.reg .pred p;\nsetp.ne.b32 p, %101, 0;\n"
    "wgmma.mma_async.sync.aligned.m64n192k16.f32.bf16.bf16 {%0, %1, %2, %3, %4, %5, %6, %7, %8, %9, %10, %11, %12, %13, %14, %15, %16, %17, %18, %19, %20, %21, %22, %23, %24, %25, %26, %27, %28, %29, %30, %31, %32, %33, %34, %35, %36, %37, %38, %39, %40, %41, %42, %43, %44, %45, %46, %47, %48, %49, %50, %51, %52, %53, %54, %55, %56, %57, %58, %59, %60, %61, %62, %63, %64, %65, %66, %67, %68, %69, %70, %71, %72, %73, %74, %75, %76, %77, %78, %79, %80, %81, %82, %83, %84, %85, %86, %87, %88, %89, %90, %91, %92, %93, %94, %95}, {%96, %97, %98, %99}, %100, p, 1, 1, %102;\n}\n"
    : "+f"(d[0]), "+f"(d[1]), "+f"(d[2]), "+f"(d[3]), "+f"(d[4]), "+f"(d[5]), "+f"(d[6]), "+f"(d[7]), "+f"(d[8]), "+f"(d[9]), "+f"(d[10]), "+f"(d[11]), "+f"(d[12]), "+f"(d[13]), "+f"(d[14]), "+f"(d[15]), "+f"(d[16]), "+f"(d[17]), "+f"(d[18]), "+f"(d[19]), "+f"(d[20]), "+f"(d[21]), "+f"(d[22]), "+f"(d[23]), "+f"(d[24]), "+f"(d[25]), "+f"(d[26]), "+f"(d[27]), "+f"(d[28]), "+f"(d[29]), "+f"(d[30]), "+f"(d[31]), "+f"(d[32]), "+f"(d[33]), "+f"(d[34]), "+f"(d[35]), "+f"(d[36]), "+f"(d[37]), "+f"(d[38]), "+f"(d[39]), "+f"(d[40]), "+f"(d[41]), "+f"(d[42]), "+f"(d[43]), "+f"(d[44]), "+f"(d[45]), "+f"(d[46]), "+f"(d[47]), "+f"(d[48]), "+f"(d[49]), "+f"(d[50]), "+f"(d[51]), "+f"(d[52]), "+f"(d[53]), "+f"(d[54]), "+f"(d[55]), "+f"(d[56]), "+f"(d[57]), "+f"(d[58]), "+f"(d[59]), "+f"(d[60]), "+f"(d[61]), "+f"(d[62]), "+f"(d[63]), "+f"(d[64]), "+f"(d[65]), "+f"(d[66]), "+f"(d[67]), "+f"(d[68]), "+f"(d[69]), "+f"(d[70]), "+f"(d[71]), "+f"(d[72]), "+f"(d[73]), "+f"(d[74]), "+f"(d[75]), "+f"(d[76]), "+f"(d[77]), "+f"(d[78]), "+f"(d[79]), "+f"(d[80]), "+f"(d[81]), "+f"(d[82]), "+f"(d[83]), "+f"(d[84]), "+f"(d[85]), "+f"(d[86]), "+f"(d[87]), "+f"(d[88]), "+f"(d[89]), "+f"(d[90]), "+f"(d[91]), "+f"(d[92]), "+f"(d[93]), "+f"(d[94]), "+f"(d[95])
    : "r"(a0), "r"(a1), "r"(a2), "r"(a3), "l"(db), "r"(scale_d), "n"(TB));
}

__device__ __forceinline__ uint32_t smem_u32(const void* p) { return (uint32_t)__cvta_generic_to_shared(p); }
__device__ __forceinline__ void wg_fence() { asm volatile("wgmma.fence.sync.aligned;" ::: "memory"); }
__device__ __forceinline__ void wg_commit() { asm volatile("wgmma.commit_group.sync.aligned;" ::: "memory"); }
template <int N> __device__ __forceinline__ void wg_wait() { asm volatile("wgmma.wait_group.sync.aligned %0;" ::"n"(N) : "memory"); }
__device__ __forceinline__ void sched_fence(uint32_t& keep, bool never) {
  asm volatile("{\n.reg .pred p;\nsetp.ne.b32 p, %1, 0;\n@p mov.u32 %0, %%clock;\n}\n" : "+r"(keep) : "r"((int)never) : "memory");
}
template <int N> __device__ __forceinline__ void fence_regs(float (&r)[N]) {
#pragma unroll
  for (int i = 0; i < N; i++) asm volatile("" : "+f"(r[i])::"memory");
}
template <int N> __device__ __forceinline__ void undefine(float (&r)[N]) {
#pragma unroll
  for (int i = 0; i < N; i++) asm volatile("" : "=f"(r[i]));
}
template <int N> __device__ __forceinline__ void fence_regs(uint32_t (&r)[N]) {
#pragma unroll
  for (int i = 0; i < N; i++) asm volatile("" : "+r"(r[i])::"memory");
}
__device__ __forceinline__ uint64_t mk_desc(uint32_t a16, uint32_t lbo, uint32_t sbo, uint32_t swz) {
  uint64_t d;
  asm("mov.b64 %0, {%1, %2};" : "=l"(d) : "r"(a16 + ((lbo >> 4) << 16)), "r"((sbo >> 4) | (swz << 30)));
  return d;
}
__device__ __forceinline__ void mbar_init(uint32_t bar, uint32_t cnt) {
  asm volatile("mbarrier.init.shared::cta.b64 [%0], %1;" ::"r"(bar), "r"(cnt) : "memory");
}
__device__ __forceinline__ void mbar_expect(uint32_t bar, uint32_t tx) {
  asm volatile("mbarrier.arrive.expect_tx.shared::cta.b64 _, [%0], %1;" ::"r"(bar), "r"(tx) : "memory");
}
__device__ __forceinline__ bool mbar_test(uint32_t bar, uint32_t ph) {
  uint32_t ok;
  asm volatile("{\n.reg .pred p;\nmbarrier.test_wait.parity.shared::cta.b64 p, [%1], %2;\nselp.u32 %0, 1, 0, p;\n}\n"
               : "=r"(ok) : "r"(bar), "r"(ph) : "memory");
  return ok;
}
__device__ __forceinline__ bool mbar_try(uint32_t bar, uint32_t ph, uint32_t ns) {
  uint32_t ok;
  asm volatile("{\n.reg .pred p;\nmbarrier.try_wait.parity.shared::cta.b64 p, [%1], %2, %3;\nselp.u32 %0, 1, 0, p;\n}\n"
               : "=r"(ok) : "r"(bar), "r"(ph), "r"(ns) : "memory");
  return ok;
}
__device__ __forceinline__ void mbar_wait(uint32_t bar, uint32_t ph) {
  asm volatile("{\n.reg .pred p;\n.reg .u32 n;\nmov.u32 n, 0;\n"
               "LOOP:\nmbarrier.try_wait.parity.shared::cta.b64 p, [%0], %1;\n@p bra DONE;\n"
               "add.u32 n, n, 1;\nsetp.lt.u32 p, n, 0x1000000;\n@p bra LOOP;\ntrap;\n"
               "DONE:\n}\n" ::"r"(bar), "r"(ph) : "memory");
}
__device__ __forceinline__ void mbar_wait_long(uint32_t bar) {
  asm volatile("{\n.reg .pred p;\n.reg .u32 n;\nmov.u32 n, 0;\n"
               "LOOP:\nmbarrier.try_wait.parity.shared::cta.b64 p, [%0], 0, 20000;\n@p bra DONE;\n"
               "add.u32 n, n, 1;\nsetp.lt.u32 p, n, 0x100000;\n@p bra LOOP;\ntrap;\n"
               "DONE:\n}\n" ::"r"(bar) : "memory");
}
__device__ __forceinline__ void mbar_arrive_cluster_if(bool on, uint32_t addr) {
  asm volatile("{\n.reg .pred p;\nsetp.ne.b32 p, %1, 0;\n@p mbarrier.arrive.shared::cluster.b64 _, [%0];\n}\n" ::"r"(addr), "r"((int)on) : "memory");
}
__device__ __forceinline__ void mbar_arrive_cluster_n(uint32_t n, uint32_t addr) {
  asm volatile("{\n.reg .pred p;\nsetp.ne.b32 p, %1, 0;\n@p mbarrier.arrive.shared::cluster.b64 _, [%0], %1;\n}\n" ::"r"(addr), "r"(n) : "memory");
}
__device__ __forceinline__ void tma2d(uint32_t dst, const CUtensorMap* m, uint32_t bar, int c0, int c1) {
  asm volatile("cp.async.bulk.tensor.2d.shared::cluster.global.mbarrier::complete_tx::bytes [%0], [%1, {%3, %4}], [%2];"
               ::"r"(dst), "l"(m), "r"(bar), "r"(c0), "r"(c1) : "memory");
}
__device__ __forceinline__ void tma3d(uint32_t dst, const CUtensorMap* m, uint32_t bar, int c0, int c1, int c2) {
  asm volatile("cp.async.bulk.tensor.3d.shared::cluster.global.mbarrier::complete_tx::bytes [%0], [%1, {%3, %4, %5}], [%2];"
               ::"r"(dst), "l"(m), "r"(bar), "r"(c0), "r"(c1), "r"(c2) : "memory");
}
__device__ __forceinline__ void tma2d_last(uint32_t dst, const CUtensorMap* m, uint32_t bar, int c0, int c1, bool last, uint64_t pol) {
  asm volatile("{\n.reg .pred p;\nsetp.ne.b32 p, %6, 0;\n"
               "@p cp.async.bulk.tensor.2d.shared::cluster.global.mbarrier::complete_tx::bytes.L2::cache_hint [%0], [%1, {%3, %4}], [%2], %5;\n"
               "@!p cp.async.bulk.tensor.2d.shared::cluster.global.mbarrier::complete_tx::bytes [%0], [%1, {%3, %4}], [%2];\n}\n"
               ::"r"(dst), "l"(m), "r"(bar), "r"(c0), "r"(c1), "l"(pol), "r"((int)last) : "memory");
}
__device__ __forceinline__ void tma3d_mc_last(uint32_t dst, const CUtensorMap* m, uint32_t bar, int c1, int c2, bool last, uint64_t pol) {
  asm volatile("{\n.reg .pred p;\nsetp.ne.b32 p, %8, 0;\n"
               "@p cp.async.bulk.tensor.3d.shared::cluster.global.mbarrier::complete_tx::bytes.multicast::cluster.L2::cache_hint"
               " [%0], [%1, {%3, %4, %5}], [%2], %6, %7;\n"
               "@!p cp.async.bulk.tensor.3d.shared::cluster.global.mbarrier::complete_tx::bytes.multicast::cluster"
               " [%0], [%1, {%3, %4, %5}], [%2], %6;\n}\n"
               ::"r"(dst), "l"(m), "r"(bar), "r"(0), "r"(c1), "r"(c2), "h"((uint16_t)3), "l"(pol), "r"((int)last) : "memory");
}
__device__ __forceinline__ void tma5d_mc_last(uint32_t dst, const CUtensorMap* m, uint32_t bar, int c2, int c4, bool last, uint64_t pol) {
  asm volatile("{\n.reg .pred p;\nsetp.ne.b32 p, %8, 0;\n"
               "@p cp.async.bulk.tensor.5d.shared::cluster.global.mbarrier::complete_tx::bytes.multicast::cluster.L2::cache_hint"
               " [%0], [%1, {%3, %3, %4, %3, %5}], [%2], %6, %7;\n"
               "@!p cp.async.bulk.tensor.5d.shared::cluster.global.mbarrier::complete_tx::bytes.multicast::cluster"
               " [%0], [%1, {%3, %3, %4, %3, %5}], [%2], %6;\n}\n"
               ::"r"(dst), "l"(m), "r"(bar), "r"(0), "r"(c2), "r"(c4), "h"((uint16_t)3), "l"(pol), "r"((int)last) : "memory");
}
__device__ __forceinline__ void tma3d_store(const CUtensorMap* m, uint32_t src, int c0, int c1, int c2) {
  asm volatile("cp.async.bulk.tensor.3d.global.shared::cta.bulk_group [%0, {%2, %3, %4}], [%1];"
               ::"l"(m), "r"(src), "r"(c0), "r"(c1), "r"(c2) : "memory");
}
__device__ __forceinline__ void bar_sync(int id, int n) { asm volatile("bar.sync %0, %1;" ::"r"(id), "r"(n) : "memory"); }
__device__ __forceinline__ uint32_t pack_bf16(float lo, float hi) {
  uint32_t r;
  asm("cvt.rn.bf16x2.f32 %0, %1, %2;" : "=r"(r) : "f"(hi), "f"(lo));
  return r;
}
__device__ __forceinline__ float ex2(float x) {
  float y;
  asm("ex2.approx.ftz.f32 %0, %1;" : "=f"(y) : "f"(x));
  return y;
}
__device__ __forceinline__ float rcp(float x) {
  float y;
  asm("rcp.approx.ftz.f32 %0, %1;" : "=f"(y) : "f"(x));
  return y;
}
__device__ __forceinline__ void stsm4(uint32_t addr, uint32_t a, uint32_t b, uint32_t c, uint32_t d) {
  asm volatile("stmatrix.sync.aligned.m8n8.x4.shared.b16 [%0], {%1, %2, %3, %4};" ::"r"(addr), "r"(a), "r"(b), "r"(c), "r"(d) : "memory");
}

__device__ __forceinline__ void tma4d_mc_hint(uint32_t dst, const CUtensorMap* m, uint32_t bar, int c3, uint64_t pol) {
  asm volatile("cp.async.bulk.tensor.4d.shared::cluster.global.mbarrier::complete_tx::bytes.multicast::cluster.L2::cache_hint"
               " [%0], [%1, {%3, %3, %3, %4}], [%2], %5, %6;"
               ::"r"(dst), "l"(m), "r"(bar), "r"(0), "r"(c3), "h"((uint16_t)3), "l"(pol) : "memory");
}
__device__ __forceinline__ void bulk_load_hint(uint32_t dst, const void* src, uint32_t bytes, uint32_t bar, uint64_t pol) {
  asm volatile("cp.async.bulk.shared::cluster.global.mbarrier::complete_tx::bytes.L2::cache_hint [%0], [%1], %2, [%3], %4;"
               ::"r"(dst), "l"(src), "r"(bytes), "r"(bar), "l"(pol) : "memory");
}
__device__ __forceinline__ void stg2_if(bool on, void* p, uint32_t a, uint32_t b, uint32_t c, uint32_t d, uint32_t e, uint32_t f,
                                        uint32_t g, uint32_t h, uint64_t pol) {
  asm volatile("{\n.reg .pred p;\nsetp.ne.b32 p, %10, 0;\n"
               "@p st.global.L2::cache_hint.v4.b32 [%0], {%1, %2, %3, %4}, %9;\n"
               "@p st.global.L2::cache_hint.v4.b32 [%0 + 512], {%5, %6, %7, %8}, %9;\n}\n"
               ::"l"(p), "r"(a), "r"(b), "r"(c), "r"(d), "r"(e), "r"(f), "r"(g), "r"(h), "l"(pol), "r"((int)on) : "memory");
}
__device__ __forceinline__ uint64_t evict_first() {
  uint64_t p;
  asm("createpolicy.fractional.L2::evict_first.b64 %0, 1.0;" : "=l"(p));
  return p;
}
__device__ __forceinline__ bool elect() {
  uint32_t ok;
  asm volatile("{\n.reg .pred p;\nelect.sync _|p, 0xffffffff;\nselp.u32 %0, 1, 0, p;\n}\n" : "=r"(ok));
  return ok;
}
__device__ __forceinline__ void mbar_arrive(uint32_t bar) {
  asm volatile("mbarrier.arrive.shared::cta.b64 _, [%0];" ::"r"(bar) : "memory");
}
__device__ __forceinline__ void mbar_arrive_if(bool on, uint32_t bar) {
  asm volatile("{\n.reg .pred p;\nsetp.ne.b32 p, %1, 0;\n@p mbarrier.arrive.shared::cta.b64 _, [%0];\n}\n" ::"r"(bar), "r"((int)on) : "memory");
}
__device__ __forceinline__ void lds2_if(bool on, uint32_t p, uint32_t (&t)[8]) {
  asm volatile("{\n.reg .pred p;\nsetp.ne.b32 p, %9, 0;\n@p ld.shared.v4.b32 {%0, %1, %2, %3}, [%8];\n@p ld.shared.v4.b32 {%4, %5, %6, %7}, [%8 + 512];\n}\n"
               : "+r"(t[0]), "+r"(t[1]), "+r"(t[2]), "+r"(t[3]), "+r"(t[4]), "+r"(t[5]), "+r"(t[6]), "+r"(t[7]) : "r"(p), "r"((int)on) : "memory");
}
__device__ __forceinline__ void lds128(uint32_t p, uint32_t& a, uint32_t& b, uint32_t& c, uint32_t& d) {
  asm volatile("ld.shared.v4.b32 {%0, %1, %2, %3}, [%4];" : "=r"(a), "=r"(b), "=r"(c), "=r"(d) : "r"(p) : "memory");
}
template <class T> __device__ __forceinline__ T* ptr_add(T* base, uint32_t bytes) {
  T* r;
  asm("{\n.reg .u32 lo, hi;\nmov.b64 {lo, hi}, %1;\nadd.cc.u32 lo, lo, %2;\naddc.u32 hi, hi, 0;\nmov.b64 %0, {lo, hi};\n}\n" : "=l"(r) : "l"(base), "r"(bytes));
  return r;
}
__device__ __forceinline__ uint32_t lds32(uint32_t p) {
  uint32_t v;
  asm volatile("ld.volatile.shared.u32 %0, [%1];" : "=r"(v) : "r"(p) : "memory");
  return v;
}
__device__ __forceinline__ uint32_t flag_get(const unsigned int* p) {
  uint32_t v;
  asm volatile("ld.acquire.gpu.global.u32 %0, [%1];" : "=r"(v) : "l"(p) : "memory");
  return v;
}
__device__ __forceinline__ uint32_t wait_word(uint32_t p, uint32_t target) {
  uint32_t v;
  asm volatile("{\n.reg .pred p;\n.reg .u32 n;\nmov.u32 n, 0;\n"
               "LOOP:\nld.acquire.cta.shared.u32 %0, [%1];\nsetp.ge.u32 p, %0, %2;\n@p bra DONE;\n"
               "nanosleep.u32 %3;\nadd.u32 n, n, 1;\nsetp.lt.u32 p, n, 0x400000;\n@p bra LOOP;\ntrap;\n"
               "DONE:\n}\n" : "=r"(v) : "r"(p), "r"(target), "n"(400) : "memory");
  return v;
}
__device__ __forceinline__ void flag_set(unsigned int* p, uint32_t v) {
  asm volatile("st.release.gpu.global.u32 [%0], %1;" ::"l"(p), "r"(v) : "memory");
}
__device__ __forceinline__ void flag_dec(unsigned int* p) {
  asm volatile("red.relaxed.gpu.global.add.u32 [%0], 0xffffffff;" ::"l"(p) : "memory");
}

struct Cursor {
  uint32_t n;
  __device__ __forceinline__ uint32_t off() const { return n & (8 * NBAR - 8); }
  __device__ __forceinline__ uint32_t ph() const { return (n / (8 * NBAR)) & 1; }
  __device__ __forceinline__ void next() { n += 8; }
};

constexpr float kScaleLog2 = 0.07216878364870322f * 1.4426950408889634f;
constexpr float kSumLimit = 1048576.0f;

__global__ void __cluster_dims__(2, 1, 1) __launch_bounds__(384, 1)
fused_kernel(const __grid_constant__ Params P) {
  extern __shared__ uint8_t smem_raw[];
  const uint32_t sbase = (smem_u32(smem_raw) + 1023) & ~1023u;
  const uint32_t full0 = sbase + RING, empty0 = full0 + 8 * NBAR, odone0 = empty0 + 8 * NBAR, ev0 = odone0 + 8 * MAX_OPS;
  const uint32_t progress = ev0 + 8 * MAX_EV, jobw = progress + 4;
  const uint32_t rank = blockIdx.x & 1;
  const int role = blockIdx.x >> 1;
  const int wid = __shfl_sync(0xffffffffu, (int)(threadIdx.x >> 5), 0);
  const int wg = wid >> 2;

  if (wid < 8) {
    if (elect()) {
#pragma unroll
      for (int j = 0; j < 16; j++) {
        const int i = EARLY + 16 * wid + j;
        if (i < 2 * NBAR + MAX_OPS + MAX_EV) mbar_init(full0 + 8 * i, i < NBAR ? 1 : i < 2 * NBAR ? 16 : i < 2 * NBAR + MAX_OPS ? 8 : 1);
      }
      if (wid == 7) asm volatile("st.shared.v2.u32 [%0], {0, 0};\nfence.acq_rel.cta;" ::"r"(progress) : "memory");
      asm volatile("fence.mbarrier_init.release.cluster;" ::: "memory");
    }
  } else if (wid > 8) {
    const uint32_t g = blockIdx.x * 96 + threadIdx.x - 288, w = g - 2048;
    if (g < 4096) asm volatile("prefetch.global.L2 [%0];" ::"l"(g < 2048 ? P.xw[0] + g * (kD * 2) : P.xw[1] + (w >> 5) * (kHD * 2) + (w & 31) * 128));
  } else {
    const uint32_t op0 = P.first[role];
    if (elect()) {
#pragma unroll
      for (int k = 0; k < EARLY; k++) mbar_init(full0 + 8 * k, 1);
      asm volatile("fence.mbarrier_init.release.cluster;" ::: "memory");
      const int blk = (op0 >> 10) & 1;
      if ((op0 & 3) == OP_Q) {
#pragma unroll
        for (int k = 0; k < EARLY; k++) {
          mbar_expect(full0 + 8 * k, SZ_Q);
          tma2d(sbase + k * SZ_Q, &P.x[blk], full0 + 8 * k, 64 * k, ((op0 >> 7) & 7) * kSq + rank * 128);
          tma3d(sbase + k * SZ_Q + 16384, &P.wq[blk], full0 + 8 * k, 0, 64 * k, 3 * ((op0 >> 2) & 31));
        }
      }
      asm volatile("prefetch.tensormap [%0];" ::"l"(rank ? &P.v[blk] : &P.k[blk]) : "memory");
    }
  }
  __syncwarp();
  asm volatile("barrier.cluster.arrive.relaxed.aligned;\nbarrier.cluster.wait.aligned;" ::: "memory");

  if (wg < 2) {
    asm volatile("setmaxnreg.inc.sync.aligned.u32 240;");
    const uint32_t* prog = P.prog[role].c;
    const int wid = __shfl_sync(0xffffffffu, (int)(threadIdx.x >> 5), 1), wg = wid >> 2;
    const int lane = threadIdx.x & 31, warp = wid & 3;
    uint32_t empty_rem;
    asm volatile("mapa.shared::cluster.u32 %0, %1, %2;" : "=r"(empty_rem) : "r"(empty0), "r"(lane & 1));
    uint32_t keep = (threadIdx.x & 127) < 2 ? 4 : 0;
    auto release = [&](int slot) { mbar_arrive_cluster_n(keep, empty_rem + slot); };
    auto release_warp = [&](int slot, bool on = true) { mbar_arrive_cluster_if(lane < 2 && on, empty_rem + slot); };
    Cursor r{0};
    const uint32_t ring16 = (sbase & 0x3FFFF) >> 4;
    uint32_t cur = ring16;
    bool rdy0 = false, rdy1 = false;
    auto probe1 = [&]() { rdy0 = mbar_test(full0 + r.off(), r.ph()); };
    auto probe2 = [&]() {
      Cursor n = r;
      rdy0 = mbar_test(full0 + n.off(), n.ph());
      n.next();
      rdy1 = mbar_test(full0 + n.off(), n.ph());
    };
    auto advance = [&](uint32_t bytes, uint32_t& addr) {
      const int bi = r.off();
      r.next();
      if (cur > ring16 + ((RING - bytes) >> 4)) cur = ring16;
      addr = cur;
      cur += bytes >> 4;
      return bi;
    };
    auto take = [&](bool rdy, uint32_t bytes, uint32_t& addr) {
      if (__builtin_expect(!__all_sync(0xffffffffu, rdy), 0)) mbar_wait(full0 + r.off(), r.ph());
      return advance(bytes, addr);
    };
    const bool never = P.dbg == 0xffffffffu;
    uint32_t q[48];
#pragma unroll
    for (int i = 0; i < 48; i++) q[i] = 0;
    const int row = wg * 64 + warp * 16 + (lane >> 2);
    const int img0 = row * 4 + ((lane & 3) ^ ((row >> 1) & 3));
    uint4* pend = nullptr;
    bool pend_any = false;
    const uint64_t spol = evict_first();
    int pc = 0;
    auto slab = [&](int c, int i0) {
#pragma unroll
      for (int i = i0; i < 6; i++)
        stg2_if(c == i, pend + i * 512, q[8 * i], q[8 * i + 1], q[8 * i + 2], q[8 * i + 3],
                q[8 * i + 4], q[8 * i + 5], q[8 * i + 6], q[8 * i + 7], spol);
    };
    auto drain = [&](int c) {
      if (!pend_any || c >= 6) return;
      slab(c, 0);
      if (c == 5) {
        __syncwarp();
        mbar_arrive_if(lane == 0, odone0 - 8 + 8 * pc);
      }
    };

    for (;; pc++) {
      uint32_t op = prog[pc];
      const int type = op & 3;
      auto enter = [&]() {
        r.n = (op >> 12) & 248; cur = ring16 + (((op >> 20) & 63) << 8);
      };
      enter();
      pend_any = op & C_PEND;
      uint32_t job = 0;
      if ((op & (3 | C_WIDE)) == OP_O) job = __shfl_sync(0xffffffffu, wait_word(jobw, 1), 0);
      if (type == OP_END || job == OP_O) {
#pragma unroll 1
        for (int c = 0; c < 6; c++) drain(c);
        asm volatile("barrier.cluster.arrive.relaxed;" ::: "memory");
        break;
      }
      {
        float s[32], o[96];
        uint32_t ad0;
        int bi0, sk1;
        uint32_t pa[16], pb[16];
        float mc0, mc1, l0, l1;
        bool shifted;
        uint32_t nop;
        auto expo = [&](float (&s)[32], uint32_t (&pout)[16], float& b0, float& b1, bool shift, auto mid) {
          float c0, c1;
#pragma unroll
          for (int i = 0; i < 8; i++) {
            const float e0 = ex2(shift ? s[4 * i] - mc0 : s[4 * i]), e1 = ex2(shift ? s[4 * i + 1] - mc0 : s[4 * i + 1]);
            const float e2 = ex2(shift ? s[4 * i + 2] - mc1 : s[4 * i + 2]), e3 = ex2(shift ? s[4 * i + 3] - mc1 : s[4 * i + 3]);
            if (i) { b0 += e0; c0 += e1; b1 += e2; c1 += e3; } else { b0 = e0; c0 = e1; b1 = e2; c1 = e3; }
            pout[2 * i] = pack_bf16(e0, e1); pout[2 * i + 1] = pack_bf16(e2, e3);
            if (i & 1) mid(i >> 1);
          }
          b0 += c0; b1 += c1;
        };
        auto rowmax = [&](float (&s)[32], float& m0, float& m1) {
          m0 = fmaxf(s[0], s[1]); m1 = fmaxf(s[2], s[3]);
#pragma unroll
          for (int i = 1; i < 8; i++) { m0 = fmaxf(m0, fmaxf(s[4 * i], s[4 * i + 1])); m1 = fmaxf(m1, fmaxf(s[4 * i + 2], s[4 * i + 3])); }
          m0 = fmaxf(m0, __shfl_xor_sync(0xffffffffu, m0, 1)); m1 = fmaxf(m1, __shfl_xor_sync(0xffffffffu, m1, 1));
          m0 = fmaxf(m0, __shfl_xor_sync(0xffffffffu, m0, 2)); m1 = fmaxf(m1, __shfl_xor_sync(0xffffffffu, m1, 2));
        };
        auto first = [&](float (&s)[32], int sk0, auto mid) {
          fence_regs(s);
          release(sk0);
          mc0 = 0.f; mc1 = 0.f;
          expo(s, pa, l0, l1, false, mid);
          shifted = __any_sync(0xffffffffu, !(fmaxf(l0, l1) <= kSumLimit && fminf(l0, l1) >= 1.f / kSumLimit));
          if (shifted) {
            rowmax(s, mc0, mc1);
            expo(s, pa, l0, l1, true, [](int) {});
          }
        };
        auto qk = [&](float (&s)[32], uint32_t ak, int k0 = 0, int k1 = 12) {
#pragma unroll
          for (int kk = k0; kk < k1; kk++)
            wgmma_rs_n64<0>(s, q[4 * kk], q[4 * kk + 1], q[4 * kk + 2], q[4 * kk + 3], mk_desc(ak, 16, KV_SBO, 1) + ((kk >> 2) * KV_CH + (kk & 3) * 2), kk != 0);
          if (k1 == 12) wg_commit();
        };
        auto pv = [&](uint32_t (&pin)[16], uint32_t av, int acc) {
#pragma unroll
          for (int kk = 0; kk < 4; kk++)
            wgmma_rs_n192<1>(o, pin[4 * kk], pin[4 * kk + 1], pin[4 * kk + 2], pin[4 * kk + 3], mk_desc(av, KV_CH * 16, KV_SBO, 1) + (kk * (KV_SBO / 8)), acc || (kk != 0));
          wg_commit();
        };
        auto finish = [&](uint32_t (&pout)[16], int sk, int sv) {
          probe1();
          wg_wait<1>();
          fence_regs(s);
          release(sk);
          float b0, b1;
#pragma unroll 1
          for (bool redo = false;; redo = true) {
            expo(s, pout, b0, b1, false, [](int) {});
            if (!__any_sync(0xffffffffu, !redo && (shifted || !(fmaxf(b0, b1) <= kSumLimit)))) break;
            shifted = true;
            rowmax(s, b0, b1);
            b0 = fmaxf(mc0, b0); b1 = fmaxf(mc1, b1);
            const float a0 = ex2(mc0 - b0), a1 = ex2(mc1 - b1);
            mc0 = b0; mc1 = b1;
            l0 *= a0; l1 *= a1;
            wg_wait<0>();
            fence_regs(o);
#pragma unroll
            for (int i = 0; i < 24; i++) { o[4 * i] *= a0; o[4 * i + 1] *= a0; o[4 * i + 2] *= a1; o[4 * i + 3] *= a1; }
#pragma unroll
            for (int i = 0; i < 32; i++) s[i] -= (i & 2) ? mc1 : mc0;
          }
          l0 += b0; l1 += b1;
          wg_wait<0>();
          fence_regs(o);
          release(sv);
        };
        auto step = [&](uint32_t (&pin)[16], uint32_t (&pout)[16]) {
          uint32_t ak, av;
          const int sk = take(rdy0, SZ_KV, ak), sv = advance(SZ_KV, av);
          wg_fence();
          qk(s, ak);
          pv(pin, av, 1);
          finish(pout, sk, sv);
        };
        auto unpark = [&]() {
          uint32_t ad, ak;
          const int bi = take(rdy0, SZ_PARK, ad);
#pragma unroll
          for (int i = 0; i < 12; i++) lds128(sbase + (ad - ring16 + img0) * 16 + (i >> 1) * 8192 + (i & 1) * 512, q[4 * i], q[4 * i + 1], q[4 * i + 2], q[4 * i + 3]);
          const int sk0 = take(false, SZ_KV, ak);
          fence_regs(q);
          release_warp(bi);
          wg_fence();
          qk(s, ak);
          probe2();
          return sk0;
        };
        auto mma4 = [&](uint32_t ad, int acc) {
#pragma unroll
          for (int kk = 0; kk < 4; kk++)
            wgmma_ss_n192<1>(o, mk_desc(ad + wg * 512, 16, 1024, 1) + (kk * 2), mk_desc(ad, 8192, 1024, 1) + (1024 + kk * 128), acc || kk != 0);
        };
        auto convert = [&](int i0, int i1) {
          sched_fence(keep, never);
#pragma unroll
          for (int i = i0; i < i1; i++) {
            q[i] = pack_bf16(o[2 * i] * kScaleLog2, o[2 * i + 1] * kScaleLog2);
            if ((i & 7) == 7 && i != i1 - 1) sched_fence(keep, never);
          }
          sched_fence(keep, never);
        };
        auto kend = [&](int bi, int k) {
          wg_commit();
          drain(k < 8 ? (0x54732710u >> (4 * k)) & 7 : 7);
          probe1();
          wg_wait<0>();
          release(bi);
        };
        if (type == OP_O) {
          int prev = 0;
          if (op & C_WIDE) {
            float d[64];
            auto mma3 = [&](uint32_t ad, int h, int acc) {
#pragma unroll
              for (int kk = 0; kk < 2; kk++)
                wgmma_ss_n192<1>(o, mk_desc(ad + wg * 256, 16, 512, 2) + (h * 512 + kk * 2), mk_desc(ad, 4096, 1024, 1) + (1024 + h * 768 + kk * 128), acc || kk);
            };
            auto mma2 = [&](uint32_t ad, uint32_t ob, int h, int acc) {
#pragma unroll
              for (int kk = 0; kk < 2; kk++)
                wgmma_ss_n128<1>(d, mk_desc(ad + wg * 256, 16, 512, 2) + (h * 512 + kk * 2), mk_desc(ad, 4096, 1024, 1) + (ob + h * 512 + kk * 128), acc || kk);
            };
            auto wstep = [&](uint32_t bytes, int acc, auto hook) {
              uint32_t ad;
              const int bi = take(rdy0, bytes, ad);
              wg_fence();
              if (bytes == SZ_W2) mma2(ad, 1024, 0, 1); else mma3(ad, 0, acc);
              if (bytes == SZ_W) mma3(ad, 1, 1);
              wg_commit();
              if (acc) { wg_wait<1>(); release(prev); }
              if (bytes == SZ_W) mma2(ad, 2560, 0, acc);
              if (bytes == SZ_W3) mma3(ad, 1, 1); else mma2(ad, bytes == SZ_W ? 2560 : 1024, 1, 1);
              wg_commit();
              prev = bi;
              hook();
              probe1();
              wg_wait<1>();
            };
            undefine(o);
            wstep(SZ_W, 0, [&]() { drain(0); });
#pragma unroll 1
            for (int k = 1; k < ((op >> 2) & 127) - TAIL; k++) wstep(SZ_W, 1, [&]() { drain(k); });
#pragma unroll 1
            for (int k = 0; k < TAIL; k++) wstep(SZ_W2, 1, []() {});
            pend = ptr_add(P.g->part, (((op >> 9) & 31) * 2 + rank) * 81920 + 4 * 8192 + img0 * 16);
            wstep(SZ_W3, 1, [&]() {
              fence_regs(d);
#pragma unroll
              for (int i = 0; i < 32; i++) q[16 + i] = pack_bf16(d[2 * i], d[2 * i + 1]);
              slab(2, 2);
            });
#pragma unroll 1
            for (int k = 3; k < 6; k++) wstep(SZ_W3, 1, [&]() { slab(k, 2); });
            op = prog[pc + 1];
            enter();
            pend_any = true;
            pend -= 4 * 512;
            bi0 = take(rdy0 || (op & 3) != OP_Q, SZ_Q, ad0);
            sched_fence(keep, never);
            wg_wait<0>();
            fence_regs(o);
            release(prev);
#pragma unroll
            for (int i = 0; i < 48; i++) q[i] = pack_bf16(o[2 * i], o[2 * i + 1]);
            if ((op & 3) != OP_Q) continue;
            pc++;
            goto first_step;
          }
          float c[80];
          auto mma2 = [&](uint32_t ad, uint32_t oa, uint32_t ob, int acc) {
            wgmma_ss_n160<1>(c, mk_desc(ad + wg * 256, 16, 512, 2) + (oa), mk_desc(ad, 2048, 512, 2) + (1024 + ob), acc);
            wgmma_ss_n160<1>(c, mk_desc(ad + wg * 256, 16, 512, 2) + (oa + 2), mk_desc(ad, 2048, 512, 2) + (1024 + ob + 64), 1);
          };
          auto kstep = [&](int acc, auto hook, uint32_t bytes = SZ_O) {
            uint32_t ad;
            const int bi = take(rdy0, bytes, ad);
            wg_fence();
            mma2(ad, 0, 0, acc);
            wg_commit();
            if (acc) wg_wait<1>();
            if (acc == 1) release(prev);
            if (acc > 1) release_warp(prev, acc == 2 || wg == 0);
            mma2(ad, 512, 640, 1);
            wg_commit();
            prev = bi;
            hook();
            probe1();
            wg_wait<1>();
          };
          auto unblock = [&](int k) {
            if (__all_sync(0xffffffffu, rdy0) || __all_sync(0xffffffffu, mbar_try(full0 + r.off(), r.ph(), 1500))) return;
#pragma unroll 1
            for (; k < 6; k++) drain(k);
            pend_any = false;
          };
          unblock(0);
          kstep(0, [&]() { drain(0); });
          int left = ((job >> 13) & 127) - 6;
#pragma unroll 1
          for (uint32_t k = 1, pace = left >= 29 ? 0x4511 : left <= 17 ? 0x1a : 0x155; left > 0; pace >>= 2, left--) {
            unblock(k);
            kstep(1, [&]() {
#pragma unroll 1
              for (int i = pace & 3; i > 0; i--) drain(k++);
            });
          }
          uint32_t t[8], stage[3];
          float u[80];
          auto unpack = [&](int j) {
#pragma unroll
            for (int i = 0; i < 8; i++) {
              u[16 * j + 2 * i] = __uint_as_float(t[i] << 16); u[16 * j + 2 * i + 1] = __uint_as_float(t[i] & 0xffff0000u);
              asm volatile("" : "+f"(u[16 * j + 2 * i]), "+f"(u[16 * j + 2 * i + 1]));
            }
          };
#pragma unroll
          for (int i = 0; i < 8; i++) t[i] = 0;
          const uint32_t bytes = (job & P_LD) ? SZ_OL : SZ_O;
#pragma unroll
          for (int j = 0; j < 5; j++) {
            if (j == 2 && wg == 1) {
              wg_wait<0>();
              release_warp(prev);
              bar_sync(1, 256);
            }
            kstep(j == 2 ? 3 : 2, [&]() {
              if (j == 4) asm volatile("{\n.reg .pred p;\nsetp.eq.u32 p, %0, 0;\n@p bar.arrive 1, 256;\n}\n" ::"r"(wg) : "memory");
              if (j) unpack(j - 1);
              lds2_if(job & P_LD, sbase + (cur - ring16 + img0) * 16 - 8192, t);
              if (j >= 1 && j <= 3) stage[j - 1] = sbase + (cur - ring16) * 16 - bytes + wid * 1024;
            }, bytes);
          }
          unpack(4);
          sched_fence(keep, never);
          wg_wait<0>();
          fence_regs(c);
          release_warp(prev);
          asm volatile("barrier.cluster.arrive.relaxed;" ::: "memory");
#pragma unroll
          for (int i = 0; i < 10; i++) {
            const int v = (i & 1) * 2 + (lane >> 4);
            const uint32_t sa = stage[i >> 2] + (i & 2) * 4096;
            stsm4(sa + (lane & 15) * 64 + ((v ^ ((lane >> 1) & 3)) << 4), pack_bf16(c[8 * i] + u[8 * i], c[8 * i + 1] + u[8 * i + 1]),
                  pack_bf16(c[8 * i + 2] + u[8 * i + 2], c[8 * i + 3] + u[8 * i + 3]), pack_bf16(c[8 * i + 4] + u[8 * i + 4], c[8 * i + 5] + u[8 * i + 5]),
                  pack_bf16(c[8 * i + 6] + u[8 * i + 6], c[8 * i + 7] + u[8 * i + 7]));
          }
          asm volatile("fence.proxy.async.shared::cta;" ::: "memory");
          __syncwarp();
          if (elect()) {
#pragma unroll
            for (int i = 0; i < 5; i++)
              tma3d_store(&P.out, stage[i >> 1] + (i & 1) * 8192, 0, ((job >> 7) & 7) * kSq + rank * 128 + wid * 16, ((job >> 10) & 1) * 20 + ((job >> 20) & 3) * 5 + i);
            asm volatile("cp.async.bulk.commit_group;\ncp.async.bulk.wait_group.read 0;" ::: "memory");
          }
          __syncwarp();
          break;
        }
        bi0 = take(rdy0, SZ_Q, ad0);
      first_step:
        undefine(o);
        wg_fence();
        mma4(ad0, 0);
        kend(bi0, 0);
        fence_regs(o);
      next_head:
        {
#pragma unroll 1
          for (int k = 1; k < ((op & F_PARK) ? 10 : 8); k++) {
            uint32_t ad;
            const int bi = take(rdy0, SZ_Q, ad);
            wg_fence();
            mma4(ad, 1);
            kend(bi, k);
          }
          if (op & F_PARK) {
            fence_regs(o);
            convert(0, 48);
            pend = ptr_add(P.g->tile, (((op >> 2) & 511) * 2 + rank) * SZ_PARK + img0 * 16);
            continue;
          }
          uint32_t a8, a9, ak0, ak1;
          const int b8 = take(rdy0, SZ_Q, a8), b9 = take(false, SZ_Q, a9);
          wg_fence();
          mma4(a8, 1);
          wg_commit();
          mma4(a9, 1);
          wg_commit();
          pc++;
          wg_wait<1>();
          release(b8);
          const int sk0 = take(false, SZ_KV, ak0);
          wg_wait<0>();
          fence_regs(o);
          release(b9);
          float s0[32];
          convert(0, 32);
          wg_fence();
          qk(s0, ak0, 0, 4);
          convert(32, 48);
          wg_fence();
          qk(s0, ak0, 4, 12);
          sk1 = take(false, SZ_KV, ak1);
          probe1();
          wg_wait<0>();
          first(s0, sk0, [&](int i) {
            if (i == 0) return;
            sched_fence(keep, never);
            wg_fence();
            if (i == 1) qk(s, ak1, 0, 4);
            if (i == 2) qk(s, ak1, 4, 8);
            if (i == 3) qk(s, ak1, 8, 12);
            sched_fence(keep, never);
          });
        }
        for (;;) {
          {
            uint32_t av;
            const int sv = take(rdy0, SZ_KV, av);
            undefine(o);
            wg_fence();
            pv(pa, av, 0);
            finish(pb, sk1, sv);
          }
          nop = prog[pc + 1];
#pragma unroll 1
          for (int jj = 0; jj < 7; jj++) {
            step(pb, pa);
            step(pa, pb);
          }
          float i0, i1;
          auto last = [&]() {
            uint32_t av;
            const int sv = take(rdy0, SZ_KV, av);
            wg_fence();
            pv(pb, av, 1);
            sched_fence(keep, never);
            probe1();
            l0 += __shfl_xor_sync(0xffffffffu, l0, 1); l1 += __shfl_xor_sync(0xffffffffu, l1, 1);
            l0 += __shfl_xor_sync(0xffffffffu, l0, 2); l1 += __shfl_xor_sync(0xffffffffu, l1, 2);
            i0 = rcp(l0); i1 = rcp(l1);
            pend = ptr_add(P.g->tile, (((op >> 2) & 511) * 2 + rank) * SZ_PARK + img0 * 16);
            return sv;
          };
          auto normalise = [&](uint32_t (&d)[48], auto mid) {
#pragma unroll
            for (int i = 0; i < 24; i++) {
              d[8 * (i >> 2) + (i & 3)] = pack_bf16(o[4 * i] * i0, o[4 * i + 1] * i0);
              d[8 * (i >> 2) + (i & 3) + 4] = pack_bf16(o[4 * i + 2] * i1, o[4 * i + 3] * i1);
              if ((i & 1) && i != 23) sched_fence(keep, never);
              if ((i & 3) == 3 && i != 23) mid(i >> 2);
            }
          };
          const int sv = last();
          if ((nop & 3) != OP_A) {
            op = nop;
            enter();
            pend_any = true;
            bi0 = take(rdy0 || (nop & 3) != OP_Q, SZ_Q, ad0);
            sched_fence(keep, never);
            wg_wait<0>();
            fence_regs(o);
            release(sv);
            normalise(q, [](int) {});
            undefine(o);
            if ((nop & 3) != OP_Q) break;
            sched_fence(keep, never);
            wg_fence();
            mma4(ad0, 0);
            pc++;
            kend(bi0, 0);
            fence_regs(o);
            goto next_head;
          }
          const int sk0 = unpark();
          wg_wait<1>();
          fence_regs(o);
          release(sv);
          uint32_t t[48];
          auto st = [&](int i) {
            stg2_if(true, pend + i * 512, t[8 * i], t[8 * i + 1], t[8 * i + 2], t[8 * i + 3], t[8 * i + 4], t[8 * i + 5], t[8 * i + 6], t[8 * i + 7], spol);
          };
          normalise(t, [&](int i) { if (!(i & 1)) st(i >> 1); });
          wg_wait<0>();
          first(s, sk0, [&](int i) { if (i < 3) { sched_fence(keep, never); st(3 + i); } });
          __syncwarp();
          mbar_arrive_if(lane == 0, odone0 + 8 * pc);
          pc++;
          op = nop;
          uint32_t ak1;
          sk1 = take(rdy0, SZ_KV, ak1);
          rdy0 = rdy1;
          wg_fence();
          qk(s, ak1);
        }
      }
    }
    asm volatile("barrier.cluster.wait;" ::: "memory");
  } else {
    asm volatile("setmaxnreg.dec.sync.aligned.u32 24;");
    const uint32_t* prog = P.prog[role].p;
    unsigned int* flag = P.g->flag + rank;
    if (wid == 11 && (prog[0] & 3) == OP_Q) {
      const uint32_t a = prog[1];
      const char* p = ptr_add(P.kv[rank * 2 + ((a >> 10) & 1)], ((a >> 2) & 255) * (kSk * kDh * 2) + (threadIdx.x & 31) * 128);
#pragma unroll 1
      for (uint32_t k = 0; k < 3; k++) {
        wait_word(progress, 8 * k);
        p += SZ_KV;
        asm volatile("prefetch.global.L2 [%0];\nprefetch.global.L2 [%0 + 4096];" ::"l"(p));
      }
      __syncwarp();
    }
    if (wid == 8) {
      Cursor head{0}, tail{0};
      int sh = 0, room = RING >> 12;
      uint32_t cur = 0;
      uint64_t fifo = 0;
      uint32_t dst, bar = 0, ev = ev0;
      const uint64_t pol = evict_first();
      auto retire = [&]() {
        mbar_wait(empty0 + tail.off(), tail.ph());
        tail.next();
        room += (uint32_t)fifo & 31;
        fifo >>= 5;
        sh -= 5;
        asm volatile("st.volatile.shared.u32 [%0], %1;" ::"r"(progress), "r"(tail.n) : "memory");
      };
      auto acquire = [&](uint32_t bytes) {
        uint32_t fp = bytes >> 12;
        if (cur + fp > (RING >> 12)) { fp += (RING >> 12) - cur; cur = 0; }
        room -= fp;
        while (room < 0) retire();
        fifo |= (uint64_t)fp << sh;
        sh += 5;
        dst = sbase + (cur << 12);
        bar = full0 + head.off();
        cur += bytes >> 12;
        head.next();
      };
      auto gate = [&]() {
        mbar_wait(ev, 0);
        ev += 8;
        asm volatile("fence.proxy.async.global;" ::: "memory");
      };
      for (int pc = 0;; pc++) {
        uint32_t op = prog[pc];
        const int type = op & 3;
        if (type == OP_END) break;
        if (op == OP_O) {
          gate();
          op = __shfl_sync(0xffffffffu, lds32(jobw), 0);
        }
        const int blk = (op >> 10) & 1;
        if (type == OP_Q) {
#pragma unroll 1
          for (int k = 0; k < 10; k++) {
            if (k == 9 && (op & P_GATE)) gate();
            acquire(SZ_Q);
            if ((pc > 0 || k >= EARLY) && elect()) {
              mbar_expect(bar, SZ_Q);
              tma2d_last(dst, &P.x[blk], bar, 64 * k, ((op >> 7) & 7) * kSq + rank * 128, op & P_LASTX, pol);
              if ((k & 1) == rank) tma3d_mc_last(dst + 16384, &P.wq[blk], bar, 64 * k, 3 * ((op >> 2) & 31), op & P_LASTW, pol);
            }
          }
        } else if (type == OP_A) {
          const int row0 = ((op >> 2) & 255) * kSk;
          const CUtensorMap* kv_map = rank ? &P.v[blk] : &P.k[blk];
          if (op & F_PARK) {
            gate();
            acquire(SZ_PARK);
            if (elect()) {
              mbar_expect(bar, SZ_PARK);
              bulk_load_hint(dst, &P.g->tile[(((op >> 20) & 511) * 2 + rank) * 3072], SZ_PARK, bar, pol);
            }
          }
          auto kv = [&](uint32_t tx, uint32_t who, int c3) {
            const uint32_t before = bar;
            acquire(SZ_KV);
            if (elect()) {
              mbar_expect(bar, tx);
              if (who == rank) tma4d_mc_hint(dst, kv_map, tx ? bar : before, c3, pol);
            }
          };
          int c3 = row0 / 8;
          kv(SZ_KV, 0, c3);
#pragma unroll 1
          for (uint32_t tv = SZ_KV; c3 != row0 / 8 + 120; tv = 0, c3 += 8) {
            kv(2 * SZ_KV - tv, 0, c3 + 8);
            kv(tv, 1, c3);
          }
          if (op & P_GATE) gate();
          kv(SZ_KV, 1, c3);
        } else {
          const uint4* part = &P.g->part[((((op >> 6) & 30) + ((op >> 21) & 1)) * 2 + rank) * 5120 + ((op >> 20) & 1) * 2560];
          auto run = [&](const uint32_t bytes, int k, int cnt, int gates) {
            const int col = bytes == SZ_O || bytes == SZ_OL ? 5 * ((op >> 20) & 3) : 5 * ((op >> 21) & 1);
            int row = 8 * k + 4 * rank, pre = bytes == SZ_O && (op & P_PRE) ? 0 : 2560;
#pragma unroll 1
            for (int h = (k * 43) >> 7, k0 = k - 3 * h; cnt > 0; h++, k0 = 0, gates = gates >> 1 | (gates & 2)) {
              const uint4* src = &P.g->tile[(P.slot[((op >> 2) & 480) + h] * 2 + rank) * 3072 + k0 * 1024];
              const bool last = h >= ((op >> 23) & 31) && h < 2 * (op >> 28);
              if (gates & 1) gate();
              int m = min(3 - k0, cnt);
              cnt -= m;
#pragma unroll 1
              for (; m > 0; m--, src += 1024, row += 8) {
                acquire(bytes);
                if (elect()) {
                  mbar_expect(bar, bytes);
                  if (bytes == SZ_O || bytes == SZ_OL) tma5d_mc_last(dst + 16384 + rank * 10240, &P.wo[blk], bar, row, col, false, 0);
                  if (bytes == SZ_W || bytes == SZ_W3) tma5d_mc_last(dst + 16384 + rank * 12288, &P.wo3[blk], bar, row, col, last, pol);
                  bulk_load_hint(dst, src, 16384, bar, pol);
                  if (bytes == SZ_W || bytes == SZ_W2) tma5d_mc_last(dst + bytes - 16384 + rank * 8192, &P.wo2[blk], bar, row, col + 3, last, pol);
                  if (bytes == SZ_OL) bulk_load_hint(dst + SZ_O, part, 8192, bar, pol);
                }
                if (bytes == SZ_OL) part += 512;
              }
              if (pre < 2560) {
                if (elect()) asm volatile("cp.async.bulk.prefetch.L2.global [%0], 10240;" ::"l"(part + pre) : "memory");
                pre += 640;
              }
            }
          };
          const int n = (op >> 13) & 127;
          if (op & P_WIDE) {
            run(SZ_W, 0, n - TAIL, 3);
            run(SZ_W2, n - TAIL, TAIL, (n - TAIL) % 3 ? 2 : 3);
            run(SZ_W3, n - TAIL, TAIL, 0);
          } else {
            if (op & P_PRE) gate();
            run(SZ_O, kSteps - n, (op & P_LD) ? n - 5 : n, 3);
            if (op & P_LD) {
              if (!(op & P_PRE)) gate();
              run(SZ_OL, kSteps - 5, 5, 2);
            }
          }
        }
      }
#pragma unroll 1
      while (sh) retire();
    } else if (threadIdx.x == 288) {
      for (int pc = 0;; pc++) {
        const uint32_t op = prog[pc];
        const int type = op & 3;
        if (type == OP_END) break;
        if (type == OP_Q ? !(op & F_PARK) : type == OP_O && !(op & P_WIDE)) continue;
        const int id = type == OP_A ? (op >> 2) & 511 : type == OP_Q ? N_TILE + ((op >> 13) & 127) : ID_PART + ((op >> 5) & 60) + ((op >> 20) & 3);
        const uint32_t v = type == OP_O ? 1 : P.info[id] & 7;
        mbar_wait_long(odone0 + 8 * pc);
        flag_set(flag + 2 * id, v);
        if (type == OP_O && (op & P_WIDE)) flag_set(flag + 2 * id + 2, v);
      }
    } else if (wid == 10) {
      int i = threadIdx.x & 31;
      const int n_ev = P.prog[role].n_ev;
      auto event = [&]() { return i < n_ev ? P.prog[role].ev[i] : n_ev ? E_JOB | (i - n_ev) : 0; };
      uint32_t e = i < 8 ? event() : 0;
      for (uint32_t n = 0; __any_sync(0xffffffffu, e); n++) {
        uint32_t job = lds32(jobw);
        const int togo = (e & E_DRAW) ? (e & 1023) - (lds32(progress) >> 3) : 99;
        if (togo <= 0 && rank == 0) {
          job = P.job[atomicInc(&P.g->ticket, gridDim.x / 2 - 1)];
          asm volatile("{\n.reg .u32 a;\nmapa.shared::cluster.u32 a, %0, 1;\nst.volatile.shared::cluster.u32 [a], %1;\n"
                       "st.volatile.shared.u32 [%0], %1;\n}\n" ::"r"(jobw), "r"(job) : "memory");
        }
        if ((e & E_JOB) && job) {
          const uint32_t j = e & 63, heads = job == OP_O ? 0 : kH - ((job >> 2) & 31), jp = !(job & P_LD) ? 63 : (job & P_PRE) ? 0 : heads - 1, h = j - (j > jp);
          e = j == jp ? (ID_PART + ((job >> 5) & 60) + ((job >> 20) & 3)) | E_ON | E_LAST : h < heads ? (((job >> 2) & 511) + h) | E_ON | E_LAST : 0;
        }
        unsigned int* f = ptr_add(flag, 8 * (e & 1023));
        const bool ok = (e & E_ON) ? flag_get(f) - 1 < ((e & E_FREE) ? 1 : 7) : (e & E_DRAW) && job;
        if (ok) {
          mbar_arrive(ev0 + 8 * i);
          if (e & (E_FREE | E_LAST)) flag_dec(f);
          i += 8;
          e = event();
        }
        asm volatile("{\n.reg .pred p;\nsetp.ge.u32 p, %0, 0x400000;\n@p trap;\n}\n" ::"r"(n));
        if (!__any_sync(0xffffffffu, ok)) __nanosleep(__any_sync(0xffffffffu, job || togo <= 2) ? 100 : 600);
      }
    } else if (threadIdx.x == 352) {
      uint32_t items = 0;
      auto read = [&](int id) {
        if (!(P.info[id] & I_NEXT)) return;
        wait_word(progress, 8 * items);
        flag_dec(flag + 2 * id);
      };
      for (int pc = 0;; pc++) {
        const uint32_t op = prog[pc];
        const int type = op & 3;
        if (type == OP_END) break;
        if (type == OP_O) {
          const uint32_t n = (op >> 13) & 127, base = items;
#pragma unroll 1
          for (uint32_t k = 3, id = (op >> 2) & 511; k <= n; k += 3, id++) {
            items = base + k + (k + TAIL > n ? TAIL : 0);
            read(id);
          }
          items = base + n + TAIL;
        } else if (type == OP_A) {
          if (op & F_PARK) { items++; read(N_TILE + ((op >> 13) & 127)); }
          items += 32;
        } else {
          items += 10;
        }
      }
    }
    __syncwarp();
    asm volatile("barrier.cluster.arrive.relaxed;\nbarrier.cluster.wait;" ::: "memory");
  }
}

typedef CUresult (*EncodeFn)(CUtensorMap*, CUtensorMapDataType, cuuint32_t, void*, const cuuint64_t*, const cuuint64_t*,
                             const cuuint32_t*, const cuuint32_t*, CUtensorMapInterleave, CUtensorMapSwizzle,
                             CUtensorMapL2promotion, CUtensorMapFloatOOBfill);

void encode(EncodeFn fn, CUtensorMap* m, const void* ptr, int rank, const cuuint64_t* dims, const cuuint64_t* strides,
            const cuuint32_t* box, CUtensorMapSwizzle swz) {
  const cuuint32_t es[5] = {1, 1, 1, 1, 1};
  CUresult r = fn(m, CU_TENSOR_MAP_DATA_TYPE_BFLOAT16, rank, const_cast<void*>(ptr), dims, strides, box, es,
                  CU_TENSOR_MAP_INTERLEAVE_NONE, swz, CU_TENSOR_MAP_L2_PROMOTION_L2_128B, CU_TENSOR_MAP_FLOAT_OOB_FILL_NONE);
  if (r != CUDA_SUCCESS) fprintf(stderr, "cuTensorMapEncodeTiled failed: %d\n", (int)r);
}

struct Op { int type, flags, id, n, quarter, park, item0, items; double t0, t1; };
struct Use { double ready, gate, need, freed; int readers, slot, prev; bool next; };
struct PlanStats { double end, slack, park_slack; int slots, parks; uint32_t own[N_CL]; };

bool plan(const char* const* text, int n_pair, int phase, Params& P, PlanStats* stats = nullptr) {
  constexpr double T_Q = 7900, T_A = 24800, T_U = TU, T_O = 640, T_RUN = 800, T_WIDE = TW, AHEAD = 3500, PUBLISH = 1500;
  const double margin = 256.0 * ((P.dbg >> 8) & 255);
  static Op op[N_CL][MAX_OPS];
  static Use use[ID_PART];
  int n_op[N_CL], covered[2 * N_TEAM] = {};
  struct Ref { double t; Op* o; int id; };
  static Ref att[N_TILE + 1], dem[N_TILE], prk[MAX_PARK + 1], unp[MAX_PARK + 1], wr[ID_PART];
  auto sort = [](Ref* r, int n) {
    for (int i = 1; i < n; i++)
      for (int j = i; j > 0 && r[j].t < r[j - 1].t; j--) { Ref x = r[j]; r[j] = r[j - 1]; r[j - 1] = x; }
  };
  auto hex = [](char c) { return c <= '9' ? c - '0' : c - 'a' + 10; };
  for (int i = 0; i < n_pair; i++)
    for (const char* s = text[i]; *s; s++)
      for (int h = 0; *s == 'J' && h < 2; h++) {
        if (covered[2 * hex(s[1]) + h]) return false;
        covered[2 * hex(s[1]) + h] = 10 * (s[2 + 2 * h] - '0') + s[3 + 2 * h] - '0';
      }
  for (int c = 0; c < 2 * n_pair; c++) {
    int n = 0, items = 0;
    double t = 0;
    auto add = [&](int type, int flags, int id, int heads, int quarter, int its, double dt) {
      if (n < MAX_OPS) op[c][n] = {type, flags, id, heads, quarter, 0, items, its, t, t + dt};
      n++; items += its; t += dt;
    };
    for (const char* s = text[c >> 1]; *s; s++) {
      const int tm = hex(s[1]) & 15, nj = covered[2 * tm + (c & 1)];
      if (*s == 'N') { add(OP_Q, 0, 0, 0, 0, 10, T_Q); add(OP_A, 0, 0, 0, 0, 32, T_A); }
      if (*s == 'P') add(OP_Q, F_PARK, 0, 0, 0, 10, T_Q + TP);
      if (*s == '+' || *s == '-') t += *s == '+' ? 1000 : -1000;
      if (*s == 'U') { if (n == 0 || n > MAX_OPS || op[c][n - 1].type != OP_A) return false; add(OP_A, F_PARK, 0, 0, 0, 33, T_U); }
      if (*s == 'J') { if (nj < TAIL + 6 || nj > kSteps - 11) return false; add(OP_O, P_WIDE, tm * kH, nj, 2 * (c & 1), nj + TAIL, 2 * T_O * nj + T_WIDE); }
    }
    add(OP_O, 0, 0, 0, 0, 0, 0);
    add(OP_END, 0, 0, 0, 0, 0, 0);
    if (n > MAX_OPS || op[c][0].type != OP_Q) return false;
    n_op[c] = n - 1;
    att[c] = {t, &op[c][n - 2], 0};
  }
  for (int i = 0; i < 4 * N_TEAM; i++) dem[i] = {(double)covered[i / 2], nullptr, i};
  sort(att, 2 * n_pair); sort(dem, 4 * N_TEAM);
  for (int i = 0; i < 4 * N_TEAM; i++) {
    Op* f = att[i].o;
    const int nj = covered[dem[i].id / 2];
    f->flags = nj ? P_LD : 0;
    f->id = dem[i].id / 4 * kH + nj / 3; f->quarter = dem[i].id & 3; f->items = f->n = kSteps - nj;
    f[1].t0 = f[1].t1 = f->t1 = f->t0 + T_O * f->n + T_RUN; f[1].item0 += f->n;
  }
  for (int i = 0; i < ID_PART; i++) use[i] = {0, 0, 1e18, 0, 0, 0, 0, false};
  int n_att = 0, n_prk = 0, n_unp = 0;
  auto ready = [&](const Op* o) {
    const int nt = o[1].type;
    return o->t1 + (nt == OP_Q ? 6100 : o[1].n ? ((o[1].flags & P_WIDE) ? 7700 : 3900) : 1500) + PUBLISH;
  };
  for (int c = 0; c < 2 * n_pair; c++)
    for (Op* o = op[c]; o->type != OP_END; o++) {
      if (o->type == OP_A) { att[n_att] = {ready(o), o, 0}; if (++n_att > N_TILE) return false; }
      if (o->type == OP_A && o->flags) { unp[n_unp] = {o->t0 - AHEAD, o, 0}; if (++n_unp > MAX_PARK) return false; }
      if (o->type == OP_Q && o->flags) { prk[n_prk] = {ready(o), o, 0}; if (++n_prk > MAX_PARK) return false; }
      for (int i = 0; o->type == OP_O && i < o->n; i++) {
        const int nw = (o->flags & P_WIDE) ? o->n - TAIL : 0, k = nw ? i : kSteps - o->n + i;
        Use& u = use[o->id / kH * kH + k / 3];
        const double t = o->t0 + T_O * (i + (i < nw ? i : nw));
        if (t - AHEAD < u.need) u.need = t - AHEAD;
        const double f = !nw ? 1e18 : i + FLIGHT < o->items - TAIL || (nw && o[1].type != OP_O) ? t + T_O * (i < nw ? 2 : 1 + TAIL) + PUBLISH : 1e18;
        if (f > u.freed) u.freed = f;
        if (i == 0 || k % 3 == 0) u.readers++;
      }
    }
  if (n_att != N_TILE || n_prk != n_unp) return false;
  for (int i = 0; i < N_TILE; i++) { const int id = (i & 15) * kH + (i >> 4); dem[i] = {use[id].need, nullptr, id}; }
  sort(att, n_att); sort(dem, N_TILE); sort(prk, n_prk); sort(unp, n_unp);
  PlanStats st = {0, 1e18, 1e18, 0, n_prk};
  int n_wr = 0;
  for (int i = 0; i < N_TILE; i++) {
    Op* o = att[i].o;
    o->id = dem[i].id;
    if (!o->flags) o[-1].id = o->id;
    if (dem[i].t - att[i].t < st.slack) st.slack = dem[i].t - att[i].t;
    wr[n_wr++] = {o->t1 - 2 * AHEAD, o, o->id};
  }
  for (int i = 0; i < n_prk; i++) {
    prk[i].o->id = unp[i].o->id;
    prk[i].o->park = unp[i].o->park = i;
    use[N_TILE + i].freed = unp[i].o->t0 + 2 * PUBLISH;
    use[N_TILE + i].readers = 1;
    if (unp[i].t - prk[i].t < st.park_slack) st.park_slack = unp[i].t - prk[i].t;
    wr[n_wr++] = {prk[i].o->t1 - 2 * AHEAD, prk[i].o, N_TILE + i};
  }
  for (int c = 0; c < 2 * n_pair; c++)
    for (int d = 0; d < 2 * n_pair; d++)
      for (Op *f = &op[c][n_op[c] - 1], *o = op[d]; f->n && o->type != OP_END; o++)
        if (o->type == OP_O && (o->flags & P_WIDE) && o->id / kH == f->id / kH && o->quarter / 2 == f->quarter / 2) {
          if (f->t0 - o->t1 > 4096.0 * ((P.dbg >> 16) & 255)) f->flags |= P_PRE;
          const double slack = f->t0 + ((f->flags & P_PRE) ? 0 : (f->n - 5) * T_O) - AHEAD - ready(o);
          if (slack < st.park_slack) st.park_slack = slack;
        }
  constexpr double long_while = 160000;
  for (int c = 0; c < 2 * n_pair; c++)
    for (Op* o = op[c]; o->type != OP_END; o++) {
      if (o->type == OP_O && (o->flags & P_WIDE)) {
        int run = 0, best = 0, end = 0;
        for (int h = 0; 3 * h < o->n; h++) {
          bool last = true;
          for (int d = 0; d < 2 * n_pair; d++)
            for (const Op* e = op[d]; e->type != OP_END; e++) {
              if (e->type != OP_O || e == o || ((e->id ^ o->id) & 256) || e->quarter / 2 != o->quarter / 2) continue;
              const bool wide = e->flags & P_WIDE;
              if (wide ? 3 * h >= e->n : 3 * h + 3 <= kSteps - e->n) continue;
              const double dt = e->t0 + T_O * (wide ? 6 * h : 3 * h - kSteps + e->n) - o->t0 - T_O * 6 * h + (d - c) * 1e-3;
              if (dt > 0 && dt < long_while) last = false;
            }
          run = last ? run + 1 : 0;
          if (run > best) { best = run; end = h + 1; }
        }
        if (3 * end >= o->n) end++;
        o->park = (end - best) | (end / 2) << 5;
      }
      if (o->type != OP_Q) continue;
      bool lw = true, lx = true;
      for (int d = 0; d < 2 * n_pair; d++)
        for (const Op* e = op[d]; e->type != OP_END; e++) {
          const double dt = e->t0 - o->t0 + (d - c) * 1e-3;
          if (e->type != OP_Q || e == o || dt < 0 || dt > long_while) continue;
          if (((e->id ^ o->id) & (256 + 31)) == 0) lw = false;
          if (e->id / kH == o->id / kH) lx = false;
        }
      o->quarter = (lw ? P_LASTW : 0) | (lx ? P_LASTX : 0);
    }
  sort(wr, n_wr);
  int holder[N_TILE];
  for (int i = 0; i < n_wr; i++) {
    int best = -1;
    for (int sl = 0; sl < st.slots; sl++)
      if (use[holder[sl]].freed + margin <= wr[i].t && (best < 0 || use[holder[sl]].freed < use[holder[best]].freed)) best = sl;
    Use& u = use[wr[i].id];
    if (best >= 0) { u.prev = holder[best]; use[u.prev].next = true; wr[i].o->flags |= P_GATE; }
    else if (st.slots == N_TILE) return false;
    else best = st.slots++;
    u.slot = best;
    holder[best] = wr[i].id;
  }
  {
    int pos[N_CL] = {}, flag[ID_PART + 4 * N_TEAM] = {}, seen[ID_PART] = {};
    auto goal = [&](int c) { return op[c][n_op[c] - 1].item0; };
    for (bool moved = true; moved;) {
      moved = false;
      for (int c = 0; c < 2 * n_pair; c++) {
        for (; pos[c] < goal(c); pos[c]++, moved = true) {
          bool ok = true;
          for (const Op* o = op[c]; o->type != OP_END; o++) {
            const int k = pos[c] - o->item0, own = o->type == OP_A ? o->id : N_TILE + (o->park & 127);
            if (k < 0 || k >= o->items) continue;
            if (o->type == OP_O) ok = k >= o->n || flag[o->id + k / 3];
            else if (k == o->items - 1 && (o->flags & P_GATE)) ok = seen[use[own].prev] == use[use[own].prev].readers;
            else if (k == 0 && o->type == OP_A && (o->flags & F_PARK)) ok = flag[N_TILE + o->park];
          }
          if (!ok) break;
          for (const Op* o = op[c]; o->type != OP_END; o++) {
            if (pos[c] == o->item0 + o->items + (o[1].type == OP_Q ? 7 : o[1].item0 == goal(c) ? -1 : 5)) {
              if (o->type == OP_A) flag[o->id] = 1;
              if (o->type == OP_Q && (o->flags & F_PARK)) flag[N_TILE + o->park] = 1;
              if (o->type == OP_O) flag[ID_PART + o->id / kH * 4 + o->quarter] = flag[ID_PART + o->id / kH * 4 + o->quarter + 1] = 1;
            }
            const int k = pos[c] - FLIGHT - o->item0, nw = o->n - TAIL;
            if (k == 0 && o->type == OP_A && (o->flags & F_PARK)) seen[N_TILE + o->park]++;
            if (o->type == OP_O && k >= 0 && k < o->items && (k < nw || k >= o->n) && (k < nw ? k : k - TAIL) % 3 == 2) seen[o->id + (k < nw ? k : k - TAIL) / 3]++;
          }
        }
      }
    }
    for (int c = 0; c < 2 * n_pair; c++) if (pos[c] < goal(c)) return false;
  }
  int n_job = 0, longest = 0;
  for (int i = 0; i < 2 * N_TEAM; i++) if (kH + 1 - covered[i] / 3 > longest) longest = kH + 1 - covered[i] / 3;
  for (int c = 0; c < 2 * n_pair; c++) {
    uint32_t items = 0, cur = 0, pend = 0;
    int n = 0, ev = 0;
    auto item = [&](uint32_t bytes, int count) {
      for (int i = 0; i < count; i++) { if (cur + bytes > RING) cur = 0; cur += bytes; items++; }
    };
    auto event = [&](uint32_t e) { if (ev < MAX_TAB) P.prog[c].ev[ev] = e; ev++; };
    for (const Op* o = op[c];; o++) {
      if (o->type != OP_END && phase && (o->type == OP_O) != (phase == 2)) continue;
      uint32_t cw = o->type | (items % (2 * NBAR)) << 15 | (cur >> 12) << 20 | pend, pw = o->type | o->id << 2 | o->flags;
      const int ps = use[N_TILE + (o->park & 127)].slot;
      pend = 0;
      if (o->type == OP_O) {
        pw |= o->n << 13 | o->quarter << 20 | (uint32_t)o->park << 23;
        if (o->flags & P_WIDE) {
          cw |= o->n << 2 | (o->id / kH * 2 + o->quarter / 2) << 9 | C_WIDE;
          item(SZ_W, o->n - TAIL);
          item(SZ_W2, TAIL);
          item(SZ_W3, TAIL);
          pend = C_PEND;
          for (int i = 0; 3 * i < o->n; i++) event((o->id + i) | E_ON | (use[o->id + i].next ? 0 : E_LAST));
        } else {
          dem[n_job++] = {o->t0 - 1e6 * o->n, nullptr, (int)pw};
          st.own[c] = pw;
          pw = OP_O;
          event(E_DRAW | (items < 16 ? 0 : items - 16));
        }
      } else if (o->type != OP_END) {
        const bool parks = o->type == OP_Q && (o->flags & F_PARK);
        cw |= (parks ? ps : use[o->id].slot) << 2 | (o->flags & F_PARK);
        if (o->flags & F_PARK) pw |= o->park << 13 | ps << 20;
        if (o->type == OP_Q) { item(SZ_Q, 10); pw |= o->quarter; }
        else { if (o->flags & F_PARK) { item(SZ_PARK, 1); event((N_TILE + o->park) | E_ON | (use[N_TILE + o->park].next ? 0 : E_LAST)); } item(SZ_KV, 32); }
        if (parks || o->type == OP_A) pend = C_PEND;
        if (o->flags & P_GATE) event(use[parks ? N_TILE + o->park : o->id].prev | E_ON | E_FREE);
      }
      P.prog[c].c[n] = cw; P.prog[c].p[n++] = pw;
      if (o->type == OP_END) { if (o->t0 > st.end) st.end = o->t0; break; }
    }
    if (ev > MAX_TAB || ev + longest > MAX_EV) return false;
    P.prog[c].n_ev = ev;
    while (n < MAX_OPS) { P.prog[c].c[n] = OP_END; P.prog[c].p[n++] = OP_END; }
    P.first[c] = (uint16_t)(P.prog[c].p[0] & 2047);
  }
  sort(dem, n_job);
  for (int i = 0; i < n_job; i++) P.job[i] = dem[i].id;
  for (int i = 0; i < ID_PART; i++) {
    if (i < N_TILE) P.slot[i] = use[i].slot;
    P.info[i] = (use[i].readers + use[i].next) | (use[i].next ? I_NEXT : 0);
  }
  if (stats) *stats = st;
  return true;
}

const char* const kPrograms[N_CL / 2] = {
  "PNJ06565NNNNN", "PNJ15858NNNNN", "PNJ25656NNNNN", "PNJ35454+NNNNN", "PNJ47878NNNNN", "PNJ57373NNNNN",
  "NNJ68080NNNN", "NNJ76868NNNN", "NNNNNJ83535NN", "NNNNNNJf4343N", "NNNNNJa5252NN", "NNNNNJb4848NN",
  "NUNNNNNNN", "NUNNNJd5353NN", "NUNNNJe6363NN", "NNNNNJ97676N", "PNNNNNNNNN", "PNNNNNNNNN",
  "PNNNNNNNNN", "PNNNNNNNNN", "PNNNNNNNNN", "NNNNNNNNN", "NNNNNNNNN", "NNNNNNNNN",
  "NUNNNNNNN", "NNNNNNNNN", "NUNNNNNNN", "NUNNNNNNN", "NNUNNNNNN", "NUNNNNNNN",
  "NUNNNNNNN", "NNUNNJc5353NN", "NUNNNNNNN",
};

const char* const* bench_programs() {
  return kPrograms;
}

}

extern "C" void kernel_launch(void* const* d_in, const int* in_sizes, int n_in, void* d_out, int out_size) {
  (void)in_sizes; (void)n_in; (void)out_size;
  static EncodeFn fn = nullptr;
  static int n_clusters = 0;
  if (!fn) {
    cudaDriverEntryPointQueryResult qr;
    void* f = nullptr;
    cudaGetDriverEntryPoint("cuTensorMapEncodeTiled", &f, cudaEnableDefault, &qr);
    fn = (EncodeFn)f;
    cudaFuncSetAttribute(fused_kernel, cudaFuncAttributeMaxDynamicSharedMemorySize, SMEM_BYTES);
    cudaLaunchConfig_t cfg = {};
    cfg.gridDim = dim3(132); cfg.blockDim = dim3(384); cfg.dynamicSmemBytes = SMEM_BYTES;
    cudaLaunchAttribute at[1];
    at[0].id = cudaLaunchAttributeClusterDimension; at[0].val.clusterDim.x = 2; at[0].val.clusterDim.y = 1; at[0].val.clusterDim.z = 1;
    cfg.attrs = at; cfg.numAttrs = 1;
    if (cudaOccupancyMaxActiveClusters(&n_clusters, fused_kernel, &cfg) != cudaSuccess || n_clusters < 1) n_clusters = 1;
    (void)cudaGetLastError();
  }
  static Params P;
  const CUtensorMapSwizzle S128 = CU_TENSOR_MAP_SWIZZLE_128B, S64 = CU_TENSOR_MAP_SWIZZLE_64B;
  for (int blk = 0; blk < 2; blk++) {
    void* const* in = d_in + 5 * blk;
    { const cuuint64_t d[] = {kD, kB * kSq}, s[] = {kD * 2}; const cuuint32_t b[] = {64, 128};
      encode(fn, &P.x[blk], in[0], 2, d, s, b, S128); }
    { const cuuint64_t d[] = {64, 8, 3, (cuuint64_t)kB * kH * kSk / 8}, s[] = {kDh * 2, 128, 8 * kDh * 2}; const cuuint32_t b[] = {64, 8, 3, 8};
      encode(fn, &P.k[blk], in[1], 4, d, s, b, S128);
      encode(fn, &P.v[blk], in[2], 4, d, s, b, S128); }
    { const cuuint64_t d[] = {64, kD, kHD / 64}, s[] = {kHD * 2, 128}; const cuuint32_t b[] = {64, 64, 3};
      encode(fn, &P.wq[blk], in[3], 3, d, s, b, S128); }
    { const cuuint64_t d[] = {32, 2, kHD / 8, 4, kD / 32}, s[] = {kD * 2, 8 * kD * 2, 2 * kD * 2, 64}; const cuuint32_t b[] = {32, 2, 4, 4, 5};
      encode(fn, &P.wo[blk], in[4], 5, d, s, b, S64); }
    { const cuuint64_t d[] = {64, 2, kHD / 8, 4, kD / 64}, s[] = {kD * 2, 8 * kD * 2, 2 * kD * 2, 128};
      const cuuint32_t b3[] = {64, 2, 4, 4, 3}, b2[] = {64, 2, 4, 4, 2};
      encode(fn, &P.wo3[blk], in[4], 5, d, s, b3, S128);
      encode(fn, &P.wo2[blk], in[4], 5, d, s, b2, S128); }
  }
  { const cuuint64_t d[] = {32, kB * kSq, 2 * kD / 32}, s[] = {2 * kD * 2, 64}; const cuuint32_t b[] = {32, 16, 1};
    encode(fn, &P.out, d_out, 3, d, s, b, S64); }

  P.kv[0] = (const char*)d_in[1]; P.kv[1] = (const char*)d_in[6]; P.kv[2] = (const char*)d_in[2]; P.kv[3] = (const char*)d_in[7];
  P.xw[0] = (const char*)d_in[0]; P.xw[1] = (const char*)d_in[3];
  cudaGetSymbolAddress((void**)&P.g, g_scratch);
  P.dbg = DBG_DEFAULT;
  if (n_clusters >= N_CL && plan(bench_programs(), N_CL / 2, 0, P)) {
    fused_kernel<<<2 * N_CL, 384, SMEM_BYTES>>>(P);
  } else {
    const char* text[2 * N_TEAM];
    for (int i = 0; i < 2 * N_TEAM; i++) text[i] = "NNNNNNNN";
    for (int phase = 1; phase <= 2; phase++) {
      plan(text, 2 * N_TEAM, phase, P);
      fused_kernel<<<8 * N_TEAM, 384, SMEM_BYTES>>>(P);
    }
  }
}
```

```cpp
#include <cuda_runtime.h>
#include <cuda_bf16.h>
#include <cuda.h>
#include <cuda/annotated_ptr>
#include <stdint.h>
#include <stdio.h>

namespace {

constexpr int kB = 8, kSq = 256, kD = 640, kH = 32, kSk = 1024, kDh = 192;
constexpr int kHD = kH * kDh;
constexpr uint32_t RING = 224 * 1024;
constexpr uint32_t SZ_KV = 24576;
constexpr uint32_t SZ_Q = 16384 + 24576;
constexpr uint32_t SZ_O = 16384 + 20480;
constexpr uint32_t SZ_W3 = 16384 + 24576, SZ_W2 = 16384 + 16384, SZ_W = SZ_W3 + 16384;
constexpr uint32_t SZ_PARK = 49152;
constexpr uint32_t SZ_OL = SZ_O + 8192;
constexpr int NBAR = 16, FLIGHT = RING / SZ_KV + 1;
constexpr int EARLY = 3;
constexpr int kSteps = kHD / 64;
constexpr int TAIL = 4;
constexpr uint32_t KV_CH = 64, KV_SBO = 3072;
constexpr int SMEM_BYTES = RING + 1024 + 1024;
constexpr int N_TEAM = 16, N_CL = 66, MAX_OPS = 22, MAX_EV = 72, MAX_TAB = 47, N_TILE = N_TEAM * kH, MAX_PARK = 128, ID_PART = N_TILE + MAX_PARK;
enum : uint32_t { OP_END = 0, OP_Q = 1, OP_A = 2, OP_O = 3, F_PARK = 1 << 11,
                  C_WIDE = 1 << 27, C_PEND = 1 << 26, P_GATE = 1 << 12, P_WIDE = 1 << 11, P_LD = 1 << 12, P_PRE = 1 << 22, P_LASTW = 1 << 29, P_LASTX = 1 << 30,
                  I_NEXT = 8, E_ON = 1 << 15, E_FREE = 1 << 14, E_LAST = 1 << 13, E_DRAW = 1 << 12, E_JOB = 1 << 11 };

#define TU 25900
#define TW 1600
#define TP 1000
constexpr uint32_t DBG_DEFAULT = 0x040800;

struct alignas(1024) Scratch {
  unsigned int flag[2047];
  unsigned int ticket;
  uint4 part[N_TEAM * 2 * 2 * 5120];
  uint4 tile[N_TILE * 2 * 3072];
};

struct alignas(64) Params {
  const char* xw[2];
  uint16_t first[80];
  Scratch* g;
  uint32_t dbg;
  CUtensorMap x[2], wq[2], k[2], v[2], wo[2], wo3[2], wo2[2], out;
  struct {
    uint32_t c[MAX_OPS];
    uint32_t p[MAX_OPS];
    uint16_t n_ev, ev[MAX_TAB];
  } prog[N_CL];
  const char* kv[4];
  uint32_t job[N_CL];
  uint16_t slot[N_TILE];
  uint8_t info[ID_PART];
};

__device__ Scratch g_scratch;

template <int TB, int TA = 0>
__device__ __forceinline__ void wgmma_ss_n64(float (&d)[32], uint64_t da, uint64_t db, int scale_d) {
  asm volatile("{\n.reg .pred p;\nsetp.ne.b32 p, %34, 0;\n"
    "wgmma.mma_async.sync.aligned.m64n64k16.f32.bf16.bf16 {%0, %1, %2, %3, %4, %5, %6, %7, %8, %9, %10, %11, %12, %13, %14, %15, %16, %17, %18, %19, %20, %21, %22, %23, %24, %25, %26, %27, %28, %29, %30, %31}, %32, %33, p, 1, 1, %35, %36;\n}\n"
    : "+f"(d[0]), "+f"(d[1]), "+f"(d[2]), "+f"(d[3]), "+f"(d[4]), "+f"(d[5]), "+f"(d[6]), "+f"(d[7]), "+f"(d[8]), "+f"(d[9]), "+f"(d[10]), "+f"(d[11]), "+f"(d[12]), "+f"(d[13]), "+f"(d[14]), "+f"(d[15]), "+f"(d[16]), "+f"(d[17]), "+f"(d[18]), "+f"(d[19]), "+f"(d[20]), "+f"(d[21]), "+f"(d[22]), "+f"(d[23]), "+f"(d[24]), "+f"(d[25]), "+f"(d[26]), "+f"(d[27]), "+f"(d[28]), "+f"(d[29]), "+f"(d[30]), "+f"(d[31])
    : "l"(da), "l"(db), "r"(scale_d), "n"(TA), "n"(TB));
}
template <int TB>
__device__ __forceinline__ void wgmma_rs_n64(float (&d)[32], uint32_t a0, uint32_t a1, uint32_t a2, uint32_t a3, uint64_t db, int scale_d) {
  asm volatile("{\n.reg .pred p;\nsetp.ne.b32 p, %37, 0;\n"
    "wgmma.mma_async.sync.aligned.m64n64k16.f32.bf16.bf16 {%0, %1, %2, %3, %4, %5, %6, %7, %8, %9, %10, %11, %12, %13, %14, %15, %16, %17, %18, %19, %20, %21, %22, %23, %24, %25, %26, %27, %28, %29, %30, %31}, {%32, %33, %34, %35}, %36, p, 1, 1, %38;\n}\n"
    : "+f"(d[0]), "+f"(d[1]), "+f"(d[2]), "+f"(d[3]), "+f"(d[4]), "+f"(d[5]), "+f"(d[6]), "+f"(d[7]), "+f"(d[8]), "+f"(d[9]), "+f"(d[10]), "+f"(d[11]), "+f"(d[12]), "+f"(d[13]), "+f"(d[14]), "+f"(d[15]), "+f"(d[16]), "+f"(d[17]), "+f"(d[18]), "+f"(d[19]), "+f"(d[20]), "+f"(d[21]), "+f"(d[22]), "+f"(d[23]), "+f"(d[24]), "+f"(d[25]), "+f"(d[26]), "+f"(d[27]), "+f"(d[28]), "+f"(d[29]), "+f"(d[30]), "+f"(d[31])
    : "r"(a0), "r"(a1), "r"(a2), "r"(a3), "l"(db), "r"(scale_d), "n"(TB));
}
template <int TB, int TA = 0>
__device__ __forceinline__ void wgmma_ss_n128(float (&d)[64], uint64_t da, uint64_t db, int scale_d) {
  asm volatile("{\n.reg .pred p;\nsetp.ne.b32 p, %66, 0;\n"
    "wgmma.mma_async.sync.aligned.m64n128k16.f32.bf16.bf16 {%0, %1, %2, %3, %4, %5, %6, %7, %8, %9, %10, %11, %12, %13, %14, %15, %16, %17, %18, %19, %20, %21, %22, %23, %24, %25, %26, %27, %28, %29, %30, %31, %32, %33, %34, %35, %36, %37, %38, %39, %40, %41, %42, %43, %44, %45, %46, %47, %48, %49, %50, %51, %52, %53, %54, %55, %56, %57, %58, %59, %60, %61, %62, %63}, %64, %65, p, 1, 1, %67, %68;\n}\n"
    : "+f"(d[0]), "+f"(d[1]), "+f"(d[2]), "+f"(d[3]), "+f"(d[4]), "+f"(d[5]), "+f"(d[6]), "+f"(d[7]), "+f"(d[8]), "+f"(d[9]), "+f"(d[10]), "+f"(d[11]), "+f"(d[12]), "+f"(d[13]), "+f"(d[14]), "+f"(d[15]), "+f"(d[16]), "+f"(d[17]), "+f"(d[18]), "+f"(d[19]), "+f"(d[20]), "+f"(d[21]), "+f"(d[22]), "+f"(d[23]), "+f"(d[24]), "+f"(d[25]), "+f"(d[26]), "+f"(d[27]), "+f"(d[28]), "+f"(d[29]), "+f"(d[30]), "+f"(d[31]), "+f"(d[32]), "+f"(d[33]), "+f"(d[34]), "+f"(d[35]), "+f"(d[36]), "+f"(d[37]), "+f"(d[38]), "+f"(d[39]), "+f"(d[40]), "+f"(d[41]), "+f"(d[42]), "+f"(d[43]), "+f"(d[44]), "+f"(d[45]), "+f"(d[46]), "+f"(d[47]), "+f"(d[48]), "+f"(d[49]), "+f"(d[50]), "+f"(d[51]), "+f"(d[52]), "+f"(d[53]), "+f"(d[54]), "+f"(d[55]), "+f"(d[56]), "+f"(d[57]), "+f"(d[58]), "+f"(d[59]), "+f"(d[60]), "+f"(d[61]), "+f"(d[62]), "+f"(d[63])
    : "l"(da), "l"(db), "r"(scale_d), "n"(TA), "n"(TB));
}
template <int TB>
__device__ __forceinline__ void wgmma_rs_n128(float (&d)[64], uint32_t a0, uint32_t a1, uint32_t a2, uint32_t a3, uint64_t db, int scale_d) {
  asm volatile("{\n.reg .pred p;\nsetp.ne.b32 p, %69, 0;\n"
    "wgmma.mma_async.sync.aligned.m64n128k16.f32.bf16.bf16 {%0, %1, %2, %3, %4, %5, %6, %7, %8, %9, %10, %11, %12, %13, %14, %15, %16, %17, %18, %19, %20, %21, %22, %23, %24, %25, %26, %27, %28, %29, %30, %31, %32, %33, %34, %35, %36, %37, %38, %39, %40, %41, %42, %43, %44, %45, %46, %47, %48, %49, %50, %51, %52, %53, %54, %55, %56, %57, %58, %59, %60, %61, %62, %63}, {%64, %65, %66, %67}, %68, p, 1, 1, %70;\n}\n"
    : "+f"(d[0]), "+f"(d[1]), "+f"(d[2]), "+f"(d[3]), "+f"(d[4]), "+f"(d[5]), "+f"(d[6]), "+f"(d[7]), "+f"(d[8]), "+f"(d[9]), "+f"(d[10]), "+f"(d[11]), "+f"(d[12]), "+f"(d[13]), "+f"(d[14]), "+f"(d[15]), "+f"(d[16]), "+f"(d[17]), "+f"(d[18]), "+f"(d[19]), "+f"(d[20]), "+f"(d[21]), "+f"(d[22]), "+f"(d[23]), "+f"(d[24]), "+f"(d[25]), "+f"(d[26]), "+f"(d[27]), "+f"(d[28]), "+f"(d[29]), "+f"(d[30]), "+f"(d[31]), "+f"(d[32]), "+f"(d[33]), "+f"(d[34]), "+f"(d[35]), "+f"(d[36]), "+f"(d[37]), "+f"(d[38]), "+f"(d[39]), "+f"(d[40]), "+f"(d[41]), "+f"(d[42]), "+f"(d[43]), "+f"(d[44]), "+f"(d[45]), "+f"(d[46]), "+f"(d[47]), "+f"(d[48]), "+f"(d[49]), "+f"(d[50]), "+f"(d[51]), "+f"(d[52]), "+f"(d[53]), "+f"(d[54]), "+f"(d[55]), "+f"(d[56]), "+f"(d[57]), "+f"(d[58]), "+f"(d[59]), "+f"(d[60]), "+f"(d[61]), "+f"(d[62]), "+f"(d[63])
    : "r"(a0), "r"(a1), "r"(a2), "r"(a3), "l"(db), "r"(scale_d), "n"(TB));
}
template <int TB, int TA = 0>
__device__ __forceinline__ void wgmma_ss_n160(float (&d)[80], uint64_t da, uint64_t db, int scale_d) {
  asm volatile("{\n.reg .pred p;\nsetp.ne.b32 p, %82, 0;\n"
    "wgmma.mma_async.sync.aligned.m64n160k16.f32.bf16.bf16 {%0, %1, %2, %3, %4, %5, %6, %7, %8, %9, %10, %11, %12, %13, %14, %15, %16, %17, %18, %19, %20, %21, %22, %23, %24, %25, %26, %27, %28, %29, %30, %31, %32, %33, %34, %35, %36, %37, %38, %39, %40, %41, %42, %43, %44, %45, %46, %47, %48, %49, %50, %51, %52, %53, %54, %55, %56, %57, %58, %59, %60, %61, %62, %63, %64, %65, %66, %67, %68, %69, %70, %71, %72, %73, %74, %75, %76, %77, %78, %79}, %80, %81, p, 1, 1, %83, %84;\n}\n"
    : "+f"(d[0]), "+f"(d[1]), "+f"(d[2]), "+f"(d[3]), "+f"(d[4]), "+f"(d[5]), "+f"(d[6]), "+f"(d[7]), "+f"(d[8]), "+f"(d[9]), "+f"(d[10]), "+f"(d[11]), "+f"(d[12]), "+f"(d[13]), "+f"(d[14]), "+f"(d[15]), "+f"(d[16]), "+f"(d[17]), "+f"(d[18]), "+f"(d[19]), "+f"(d[20]), "+f"(d[21]), "+f"(d[22]), "+f"(d[23]), "+f"(d[24]), "+f"(d[25]), "+f"(d[26]), "+f"(d[27]), "+f"(d[28]), "+f"(d[29]), "+f"(d[30]), "+f"(d[31]), "+f"(d[32]), "+f"(d[33]), "+f"(d[34]), "+f"(d[35]), "+f"(d[36]), "+f"(d[37]), "+f"(d[38]), "+f"(d[39]), "+f"(d[40]), "+f"(d[41]), "+f"(d[42]), "+f"(d[43]), "+f"(d[44]), "+f"(d[45]), "+f"(d[46]), "+f"(d[47]), "+f"(d[48]), "+f"(d[49]), "+f"(d[50]), "+f"(d[51]), "+f"(d[52]), "+f"(d[53]), "+f"(d[54]), "+f"(d[55]), "+f"(d[56]), "+f"(d[57]), "+f"(d[58]), "+f"(d[59]), "+f"(d[60]), "+f"(d[61]), "+f"(d[62]), "+f"(d[63]), "+f"(d[64]), "+f"(d[65]), "+f"(d[66]), "+f"(d[67]), "+f"(d[68]), "+f"(d[69]), "+f"(d[70]), "+f"(d[71]), "+f"(d[72]), "+f"(d[73]), "+f"(d[74]), "+f"(d[75]), "+f"(d[76]), "+f"(d[77]), "+f"(d[78]), "+f"(d[79])
    : "l"(da), "l"(db), "r"(scale_d), "n"(TA), "n"(TB));
}
template <int TB>
__device__ __forceinline__ void wgmma_rs_n160(float (&d)[80], uint32_t a0, uint32_t a1, uint32_t a2, uint32_t a3, uint64_t db, int scale_d) {
  asm volatile("{\n.reg .pred p;\nsetp.ne.b32 p, %85, 0;\n"
    "wgmma.mma_async.sync.aligned.m64n160k16.f32.bf16.bf16 {%0, %1, %2, %3, %4, %5, %6, %7, %8, %9, %10, %11, %12, %13, %14, %15, %16, %17, %18, %19, %20, %21, %22, %23, %24, %25, %26, %27, %28, %29, %30, %31, %32, %33, %34, %35, %36, %37, %38, %39, %40, %41, %42, %43, %44, %45, %46, %47, %48, %49, %50, %51, %52, %53, %54, %55, %56, %57, %58, %59, %60, %61, %62, %63, %64, %65, %66, %67, %68, %69, %70, %71, %72, %73, %74, %75, %76, %77, %78, %79}, {%80, %81, %82, %83}, %84, p, 1, 1, %86;\n}\n"
    : "+f"(d[0]), "+f"(d[1]), "+f"(d[2]), "+f"(d[3]), "+f"(d[4]), "+f"(d[5]), "+f"(d[6]), "+f"(d[7]), "+f"(d[8]), "+f"(d[9]), "+f"(d[10]), "+f"(d[11]), "+f"(d[12]), "+f"(d[13]), "+f"(d[14]), "+f"(d[15]), "+f"(d[16]), "+f"(d[17]), "+f"(d[18]), "+f"(d[19]), "+f"(d[20]), "+f"(d[21]), "+f"(d[22]), "+f"(d[23]), "+f"(d[24]), "+f"(d[25]), "+f"(d[26]), "+f"(d[27]), "+f"(d[28]), "+f"(d[29]), "+f"(d[30]), "+f"(d[31]), "+f"(d[32]), "+f"(d[33]), "+f"(d[34]), "+f"(d[35]), "+f"(d[36]), "+f"(d[37]), "+f"(d[38]), "+f"(d[39]), "+f"(d[40]), "+f"(d[41]), "+f"(d[42]), "+f"(d[43]), "+f"(d[44]), "+f"(d[45]), "+f"(d[46]), "+f"(d[47]), "+f"(d[48]), "+f"(d[49]), "+f"(d[50]), "+f"(d[51]), "+f"(d[52]), "+f"(d[53]), "+f"(d[54]), "+f"(d[55]), "+f"(d[56]), "+f"(d[57]), "+f"(d[58]), "+f"(d[59]), "+f"(d[60]), "+f"(d[61]), "+f"(d[62]), "+f"(d[63]), "+f"(d[64]), "+f"(d[65]), "+f"(d[66]), "+f"(d[67]), "+f"(d[68]), "+f"(d[69]), "+f"(d[70]), "+f"(d[71]), "+f"(d[72]), "+f"(d[73]), "+f"(d[74]), "+f"(d[75]), "+f"(d[76]), "+f"(d[77]), "+f"(d[78]), "+f"(d[79])
    : "r"(a0), "r"(a1), "r"(a2), "r"(a3), "l"(db), "r"(scale_d), "n"(TB));
}
template <int TB, int TA = 0>
__device__ __forceinline__ void wgmma_ss_n192(float (&d)[96], uint64_t da, uint64_t db, int scale_d) {
  asm volatile("{\n.reg .pred p;\nsetp.ne.b32 p, %98, 0;\n"
    "wgmma.mma_async.sync.aligned.m64n192k16.f32.bf16.bf16 {%0, %1, %2, %3, %4, %5, %6, %7, %8, %9, %10, %11, %12, %13, %14, %15, %16, %17, %18, %19, %20, %21, %22, %23, %24, %25, %26, %27, %28, %29, %30, %31, %32, %33, %34, %35, %36, %37, %38, %39, %40, %41, %42, %43, %44, %45, %46, %47, %48, %49, %50, %51, %52, %53, %54, %55, %56, %57, %58, %59, %60, %61, %62, %63, %64, %65, %66, %67, %68, %69, %70, %71, %72, %73, %74, %75, %76, %77, %78, %79, %80, %81, %82, %83, %84, %85, %86, %87, %88, %89, %90, %91, %92, %93, %94, %95}, %96, %97, p, 1, 1, %99, %100;\n}\n"
    : "+f"(d[0]), "+f"(d[1]), "+f"(d[2]), "+f"(d[3]), "+f"(d[4]), "+f"(d[5]), "+f"(d[6]), "+f"(d[7]), "+f"(d[8]), "+f"(d[9]), "+f"(d[10]), "+f"(d[11]), "+f"(d[12]), "+f"(d[13]), "+f"(d[14]), "+f"(d[15]), "+f"(d[16]), "+f"(d[17]), "+f"(d[18]), "+f"(d[19]), "+f"(d[20]), "+f"(d[21]), "+f"(d[22]), "+f"(d[23]), "+f"(d[24]), "+f"(d[25]), "+f"(d[26]), "+f"(d[27]), "+f"(d[28]), "+f"(d[29]), "+f"(d[30]), "+f"(d[31]), "+f"(d[32]), "+f"(d[33]), "+f"(d[34]), "+f"(d[35]), "+f"(d[36]), "+f"(d[37]), "+f"(d[38]), "+f"(d[39]), "+f"(d[40]), "+f"(d[41]), "+f"(d[42]), "+f"(d[43]), "+f"(d[44]), "+f"(d[45]), "+f"(d[46]), "+f"(d[47]), "+f"(d[48]), "+f"(d[49]), "+f"(d[50]), "+f"(d[51]), "+f"(d[52]), "+f"(d[53]), "+f"(d[54]), "+f"(d[55]), "+f"(d[56]), "+f"(d[57]), "+f"(d[58]), "+f"(d[59]), "+f"(d[60]), "+f"(d[61]), "+f"(d[62]), "+f"(d[63]), "+f"(d[64]), "+f"(d[65]), "+f"(d[66]), "+f"(d[67]), "+f"(d[68]), "+f"(d[69]), "+f"(d[70]), "+f"(d[71]), "+f"(d[72]), "+f"(d[73]), "+f"(d[74]), "+f"(d[75]), "+f"(d[76]), "+f"(d[77]), "+f"(d[78]), "+f"(d[79]), "+f"(d[80]), "+f"(d[81]), "+f"(d[82]), "+f"(d[83]), "+f"(d[84]), "+f"(d[85]), "+f"(d[86]), "+f"(d[87]), "+f"(d[88]), "+f"(d[89]), "+f"(d[90]), "+f"(d[91]), "+f"(d[92]), "+f"(d[93]), "+f"(d[94]), "+f"(d[95])
    : "l"(da), "l"(db), "r"(scale_d), "n"(TA), "n"(TB));
}
template <int TB>
__device__ __forceinline__ void wgmma_rs_n192(float (&d)[96], uint32_t a0, uint32_t a1, uint32_t a2, uint32_t a3, uint64_t db, int scale_d) {
  asm volatile("{\n.reg .pred p;\nsetp.ne.b32 p, %101, 0;\n"
    "wgmma.mma_async.sync.aligned.m64n192k16.f32.bf16.bf16 {%0, %1, %2, %3, %4, %5, %6, %7, %8, %9, %10, %11, %12, %13, %14, %15, %16, %17, %18, %19, %20, %21, %22, %23, %24, %25, %26, %27, %28, %29, %30, %31, %32, %33, %34, %35, %36, %37, %38, %39, %40, %41, %42, %43, %44, %45, %46, %47, %48, %49, %50, %51, %52, %53, %54, %55, %56, %57, %58, %59, %60, %61, %62, %63, %64, %65, %66, %67, %68, %69, %70, %71, %72, %73, %74, %75, %76, %77, %78, %79, %80, %81, %82, %83, %84, %85, %86, %87, %88, %89, %90, %91, %92, %93, %94, %95}, {%96, %97, %98, %99}, %100, p, 1, 1, %102;\n}\n"
    : "+f"(d[0]), "+f"(d[1]), "+f"(d[2]), "+f"(d[3]), "+f"(d[4]), "+f"(d[5]), "+f"(d[6]), "+f"(d[7]), "+f"(d[8]), "+f"(d[9]), "+f"(d[10]), "+f"(d[11]), "+f"(d[12]), "+f"(d[13]), "+f"(d[14]), "+f"(d[15]), "+f"(d[16]), "+f"(d[17]), "+f"(d[18]), "+f"(d[19]), "+f"(d[20]), "+f"(d[21]), "+f"(d[22]), "+f"(d[23]), "+f"(d[24]), "+f"(d[25]), "+f"(d[26]), "+f"(d[27]), "+f"(d[28]), "+f"(d[29]), "+f"(d[30]), "+f"(d[31]), "+f"(d[32]), "+f"(d[33]), "+f"(d[34]), "+f"(d[35]), "+f"(d[36]), "+f"(d[37]), "+f"(d[38]), "+f"(d[39]), "+f"(d[40]), "+f"(d[41]), "+f"(d[42]), "+f"(d[43]), "+f"(d[44]), "+f"(d[45]), "+f"(d[46]), "+f"(d[47]), "+f"(d[48]), "+f"(d[49]), "+f"(d[50]), "+f"(d[51]), "+f"(d[52]), "+f"(d[53]), "+f"(d[54]), "+f"(d[55]), "+f"(d[56]), "+f"(d[57]), "+f"(d[58]), "+f"(d[59]), "+f"(d[60]), "+f"(d[61]), "+f"(d[62]), "+f"(d[63]), "+f"(d[64]), "+f"(d[65]), "+f"(d[66]), "+f"(d[67]), "+f"(d[68]), "+f"(d[69]), "+f"(d[70]), "+f"(d[71]), "+f"(d[72]), "+f"(d[73]), "+f"(d[74]), "+f"(d[75]), "+f"(d[76]), "+f"(d[77]), "+f"(d[78]), "+f"(d[79]), "+f"(d[80]), "+f"(d[81]), "+f"(d[82]), "+f"(d[83]), "+f"(d[84]), "+f"(d[85]), "+f"(d[86]), "+f"(d[87]), "+f"(d[88]), "+f"(d[89]), "+f"(d[90]), "+f"(d[91]), "+f"(d[92]), "+f"(d[93]), "+f"(d[94]), "+f"(d[95])
    : "r"(a0), "r"(a1), "r"(a2), "r"(a3), "l"(db), "r"(scale_d), "n"(TB));
}

__device__ __forceinline__ uint32_t smem_u32(const void* p) { return (uint32_t)__cvta_generic_to_shared(p); }
__device__ __forceinline__ void wg_fence() { asm volatile("wgmma.fence.sync.aligned;" ::: "memory"); }
__device__ __forceinline__ void wg_commit() { asm volatile("wgmma.commit_group.sync.aligned;" ::: "memory"); }
template <int N> __device__ __forceinline__ void wg_wait() { asm volatile("wgmma.wait_group.sync.aligned %0;" ::"n"(N) : "memory"); }
__device__ __forceinline__ void sched_fence(uint32_t& keep, bool never) {
  asm volatile("{\n.reg .pred p;\nsetp.ne.b32 p, %1, 0;\n@p mov.u32 %0, %%clock;\n}\n" : "+r"(keep) : "r"((int)never) : "memory");
}
template <int N> __device__ __forceinline__ void fence_regs(float (&r)[N]) {
#pragma unroll
  for (int i = 0; i < N; i++) asm volatile("" : "+f"(r[i])::"memory");
}
template <int N> __device__ __forceinline__ void undefine(float (&r)[N]) {
#pragma unroll
  for (int i = 0; i < N; i++) asm volatile("" : "=f"(r[i]));
}
template <int N> __device__ __forceinline__ void fence_regs(uint32_t (&r)[N]) {
#pragma unroll
  for (int i = 0; i < N; i++) asm volatile("" : "+r"(r[i])::"memory");
}
__device__ __forceinline__ uint64_t mk_desc(uint32_t a16, uint32_t lbo, uint32_t sbo, uint32_t swz) {
  uint64_t d;
  asm("mov.b64 %0, {%1, %2};" : "=l"(d) : "r"(a16 + ((lbo >> 4) << 16)), "r"((sbo >> 4) | (swz << 30)));
  return d;
}
__device__ __forceinline__ void mbar_init(uint32_t bar, uint32_t cnt) {
  asm volatile("mbarrier.init.shared::cta.b64 [%0], %1;" ::"r"(bar), "r"(cnt) : "memory");
}
__device__ __forceinline__ void mbar_expect(uint32_t bar, uint32_t tx) {
  asm volatile("mbarrier.arrive.expect_tx.shared::cta.b64 _, [%0], %1;" ::"r"(bar), "r"(tx) : "memory");
}
__device__ __forceinline__ bool mbar_test(uint32_t bar, uint32_t ph) {
  uint32_t ok;
  asm volatile("{\n.reg .pred p;\nmbarrier.test_wait.parity.shared::cta.b64 p, [%1], %2;\nselp.u32 %0, 1, 0, p;\n}\n"
               : "=r"(ok) : "r"(bar), "r"(ph) : "memory");
  return ok;
}
__device__ __forceinline__ bool mbar_try(uint32_t bar, uint32_t ph, uint32_t ns) {
  uint32_t ok;
  asm volatile("{\n.reg .pred p;\nmbarrier.try_wait.parity.shared::cta.b64 p, [%1], %2, %3;\nselp.u32 %0, 1, 0, p;\n}\n"
               : "=r"(ok) : "r"(bar), "r"(ph), "r"(ns) : "memory");
  return ok;
}
__device__ __forceinline__ void mbar_wait(uint32_t bar, uint32_t ph) {
  asm volatile("{\n.reg .pred p;\n.reg .u32 n;\nmov.u32 n, 0;\n"
               "LOOP:\nmbarrier.try_wait.parity.shared::cta.b64 p, [%0], %1;\n@p bra DONE;\n"
               "add.u32 n, n, 1;\nsetp.lt.u32 p, n, 0x1000000;\n@p bra LOOP;\ntrap;\n"
               "DONE:\n}\n" ::"r"(bar), "r"(ph) : "memory");
}
__device__ __forceinline__ void mbar_wait_long(uint32_t bar) {
  asm volatile("{\n.reg .pred p;\n.reg .u32 n;\nmov.u32 n, 0;\n"
               "LOOP:\nmbarrier.try_wait.parity.shared::cta.b64 p, [%0], 0, 20000;\n@p bra DONE;\n"
               "add.u32 n, n, 1;\nsetp.lt.u32 p, n, 0x100000;\n@p bra LOOP;\ntrap;\n"
               "DONE:\n}\n" ::"r"(bar) : "memory");
}
__device__ __forceinline__ void mbar_arrive_cluster_if(bool on, uint32_t addr) {
  asm volatile("{\n.reg .pred p;\nsetp.ne.b32 p, %1, 0;\n@p mbarrier.arrive.shared::cluster.b64 _, [%0];\n}\n" ::"r"(addr), "r"((int)on) : "memory");
}
__device__ __forceinline__ void mbar_arrive_cluster_n(uint32_t n, uint32_t addr) {
  asm volatile("{\n.reg .pred p;\nsetp.ne.b32 p, %1, 0;\n@p mbarrier.arrive.shared::cluster.b64 _, [%0], %1;\n}\n" ::"r"(addr), "r"(n) : "memory");
}
__device__ __forceinline__ void tma2d(uint32_t dst, const CUtensorMap* m, uint32_t bar, int c0, int c1) {
  asm volatile("cp.async.bulk.tensor.2d.shared::cluster.global.mbarrier::complete_tx::bytes [%0], [%1, {%3, %4}], [%2];"
               ::"r"(dst), "l"(m), "r"(bar), "r"(c0), "r"(c1) : "memory");
}
__device__ __forceinline__ void tma3d(uint32_t dst, const CUtensorMap* m, uint32_t bar, int c0, int c1, int c2) {
  asm volatile("cp.async.bulk.tensor.3d.shared::cluster.global.mbarrier::complete_tx::bytes [%0], [%1, {%3, %4, %5}], [%2];"
               ::"r"(dst), "l"(m), "r"(bar), "r"(c0), "r"(c1), "r"(c2) : "memory");
}
__device__ __forceinline__ void tma2d_hint(uint32_t dst, const CUtensorMap* m, uint32_t bar, int c0, int c1, uint64_t pol) {
  asm volatile("cp.async.bulk.tensor.2d.shared::cluster.global.mbarrier::complete_tx::bytes.L2::cache_hint [%0], [%1, {%3, %4}], [%2], %5;"
               ::"r"(dst), "l"(m), "r"(bar), "r"(c0), "r"(c1), "l"(pol) : "memory");
}
__device__ __forceinline__ void tma3d_mc_hint(uint32_t dst, const CUtensorMap* m, uint32_t bar, int c1, int c2, uint64_t pol) {
  asm volatile("cp.async.bulk.tensor.3d.shared::cluster.global.mbarrier::complete_tx::bytes.multicast::cluster.L2::cache_hint"
               " [%0], [%1, {%3, %4, %5}], [%2], %6, %7;"
               ::"r"(dst), "l"(m), "r"(bar), "r"(0), "r"(c1), "r"(c2), "h"((uint16_t)3), "l"(pol) : "memory");
}
__device__ __forceinline__ void tma5d_mc_hint(uint32_t dst, const CUtensorMap* m, uint32_t bar, int c2, int c4, uint64_t pol) {
  asm volatile("cp.async.bulk.tensor.5d.shared::cluster.global.mbarrier::complete_tx::bytes.multicast::cluster.L2::cache_hint"
               " [%0], [%1, {%3, %3, %4, %3, %5}], [%2], %6, %7;"
               ::"r"(dst), "l"(m), "r"(bar), "r"(0), "r"(c2), "r"(c4), "h"((uint16_t)3), "l"(pol) : "memory");
}
__device__ __forceinline__ void tma3d_store(const CUtensorMap* m, uint32_t src, int c0, int c1, int c2) {
  asm volatile("cp.async.bulk.tensor.3d.global.shared::cta.bulk_group [%0, {%2, %3, %4}], [%1];"
               ::"l"(m), "r"(src), "r"(c0), "r"(c1), "r"(c2) : "memory");
}
__device__ __forceinline__ void bar_sync(int id, int n) { asm volatile("bar.sync %0, %1;" ::"r"(id), "r"(n) : "memory"); }
__device__ __forceinline__ uint32_t pack_bf16(float lo, float hi) {
  uint32_t r;
  asm("cvt.rn.bf16x2.f32 %0, %1, %2;" : "=r"(r) : "f"(hi), "f"(lo));
  return r;
}
__device__ __forceinline__ float ex2(float x) {
  float y;
  asm("ex2.approx.ftz.f32 %0, %1;" : "=f"(y) : "f"(x));
  return y;
}
__device__ __forceinline__ float rcp(float x) {
  float y;
  asm("rcp.approx.ftz.f32 %0, %1;" : "=f"(y) : "f"(x));
  return y;
}
__device__ __forceinline__ void stsm4(uint32_t addr, uint32_t a, uint32_t b, uint32_t c, uint32_t d) {
  asm volatile("stmatrix.sync.aligned.m8n8.x4.shared.b16 [%0], {%1, %2, %3, %4};" ::"r"(addr), "r"(a), "r"(b), "r"(c), "r"(d) : "memory");
}

__device__ __forceinline__ void tma4d_mc_hint(uint32_t dst, const CUtensorMap* m, uint32_t bar, int c3, uint64_t pol) {
  asm volatile("cp.async.bulk.tensor.4d.shared::cluster.global.mbarrier::complete_tx::bytes.multicast::cluster.L2::cache_hint"
               " [%0], [%1, {%3, %3, %3, %4}], [%2], %5, %6;"
               ::"r"(dst), "l"(m), "r"(bar), "r"(0), "r"(c3), "h"((uint16_t)3), "l"(pol) : "memory");
}
__device__ __forceinline__ void bulk_load_hint(uint32_t dst, const void* src, uint32_t bytes, uint32_t bar, uint64_t pol) {
  asm volatile("cp.async.bulk.shared::cluster.global.mbarrier::complete_tx::bytes.L2::cache_hint [%0], [%1], %2, [%3], %4;"
               ::"r"(dst), "l"(src), "r"(bytes), "r"(bar), "l"(pol) : "memory");
}
__device__ __forceinline__ void stg2_if(bool on, void* p, uint32_t a, uint32_t b, uint32_t c, uint32_t d, uint32_t e, uint32_t f,
                                        uint32_t g, uint32_t h, uint64_t pol) {
  asm volatile("{\n.reg .pred p;\nsetp.ne.b32 p, %10, 0;\n"
               "@p st.global.L2::cache_hint.v4.b32 [%0], {%1, %2, %3, %4}, %9;\n"
               "@p st.global.L2::cache_hint.v4.b32 [%0 + 512], {%5, %6, %7, %8}, %9;\n}\n"
               ::"l"(p), "r"(a), "r"(b), "r"(c), "r"(d), "r"(e), "r"(f), "r"(g), "r"(h), "l"(pol), "r"((int)on) : "memory");
}
__device__ __forceinline__ uint64_t evict_first() {
  uint64_t p;
  asm("createpolicy.fractional.L2::evict_first.b64 %0, 1.0;" : "=l"(p));
  return p;
}
__device__ __forceinline__ uint64_t no_hint() {
  uint64_t p;
  asm("createpolicy.cvt.L2.b64 %0, %1;" : "=l"(p) : "l"(static_cast<uint64_t>(cuda::access_property{})));
  return p;
}
__device__ __forceinline__ bool elect() {
  uint32_t ok;
  asm volatile("{\n.reg .pred p;\nelect.sync _|p, 0xffffffff;\nselp.u32 %0, 1, 0, p;\n}\n" : "=r"(ok));
  return ok;
}
__device__ __forceinline__ void mbar_arrive(uint32_t bar) {
  asm volatile("mbarrier.arrive.shared::cta.b64 _, [%0];" ::"r"(bar) : "memory");
}
__device__ __forceinline__ void mbar_arrive_if(bool on, uint32_t bar) {
  asm volatile("{\n.reg .pred p;\nsetp.ne.b32 p, %1, 0;\n@p mbarrier.arrive.shared::cta.b64 _, [%0];\n}\n" ::"r"(bar), "r"((int)on) : "memory");
}
__device__ __forceinline__ void lds2_if(bool on, uint32_t p, uint32_t (&t)[8]) {
  asm volatile("{\n.reg .pred p;\nsetp.ne.b32 p, %9, 0;\n@p ld.shared.v4.b32 {%0, %1, %2, %3}, [%8];\n@p ld.shared.v4.b32 {%4, %5, %6, %7}, [%8 + 512];\n}\n"
               : "+r"(t[0]), "+r"(t[1]), "+r"(t[2]), "+r"(t[3]), "+r"(t[4]), "+r"(t[5]), "+r"(t[6]), "+r"(t[7]) : "r"(p), "r"((int)on) : "memory");
}
__device__ __forceinline__ void lds128(uint32_t p, uint32_t& a, uint32_t& b, uint32_t& c, uint32_t& d) {
  asm volatile("ld.shared.v4.b32 {%0, %1, %2, %3}, [%4];" : "=r"(a), "=r"(b), "=r"(c), "=r"(d) : "r"(p) : "memory");
}
template <class T> __device__ __forceinline__ T* ptr_add(T* base, uint32_t bytes) {
  T* r;
  asm("{\n.reg .u32 lo, hi;\nmov.b64 {lo, hi}, %1;\nadd.cc.u32 lo, lo, %2;\naddc.u32 hi, hi, 0;\nmov.b64 %0, {lo, hi};\n}\n" : "=l"(r) : "l"(base), "r"(bytes));
  return r;
}
__device__ __forceinline__ uint32_t lds32(uint32_t p) {
  uint32_t v;
  asm volatile("ld.volatile.shared.u32 %0, [%1];" : "=r"(v) : "r"(p) : "memory");
  return v;
}
__device__ __forceinline__ uint32_t flag_get(const unsigned int* p) {
  uint32_t v;
  asm volatile("ld.acquire.gpu.global.u32 %0, [%1];" : "=r"(v) : "l"(p) : "memory");
  return v;
}
__device__ __forceinline__ uint32_t wait_word(uint32_t p, uint32_t target) {
  uint32_t v;
  asm volatile("{\n.reg .pred p;\n.reg .u32 n;\nmov.u32 n, 0;\n"
               "LOOP:\nld.acquire.cta.shared.u32 %0, [%1];\nsetp.ge.u32 p, %0, %2;\n@p bra DONE;\n"
               "nanosleep.u32 %3;\nadd.u32 n, n, 1;\nsetp.lt.u32 p, n, 0x400000;\n@p bra LOOP;\ntrap;\n"
               "DONE:\n}\n" : "=r"(v) : "r"(p), "r"(target), "n"(400) : "memory");
  return v;
}
__device__ __forceinline__ void flag_set(unsigned int* p, uint32_t v) {
  asm volatile("st.release.gpu.global.u32 [%0], %1;" ::"l"(p), "r"(v) : "memory");
}
__device__ __forceinline__ void flag_dec(unsigned int* p) {
  asm volatile("red.relaxed.gpu.global.add.u32 [%0], 0xffffffff;" ::"l"(p) : "memory");
}

struct Cursor {
  uint32_t n;
  __device__ __forceinline__ uint32_t off() const { return n & (8 * NBAR - 8); }
  __device__ __forceinline__ uint32_t ph() const { return (n / (8 * NBAR)) & 1; }
  __device__ __forceinline__ void next() { n += 8; }
};

constexpr float kScaleLog2 = 0.07216878364870322f * 1.4426950408889634f;
constexpr float kSumLimit = 1048576.0f;

__global__ void __cluster_dims__(2, 1, 1) __launch_bounds__(384, 1)
fused_kernel(const __grid_constant__ Params P) {
  extern __shared__ uint8_t smem_raw[];
  const uint32_t sbase = (smem_u32(smem_raw) + 1023) & ~1023u;
  const uint32_t full0 = sbase + RING, empty0 = full0 + 8 * NBAR, odone0 = empty0 + 8 * NBAR, ev0 = odone0 + 8 * MAX_OPS;
  const uint32_t progress = ev0 + 8 * MAX_EV, jobw = progress + 4;
  const uint32_t rank = blockIdx.x & 1;
  const int role = blockIdx.x >> 1;
  const int wid = __shfl_sync(0xffffffffu, (int)(threadIdx.x >> 5), 0);
  const int wg = wid >> 2;

  if (wid < 8) {
    if (elect()) {
#pragma unroll
      for (int j = 0; j < 16; j++) {
        const int i = EARLY + 16 * wid + j;
        if (i < 2 * NBAR + MAX_OPS + MAX_EV) mbar_init(full0 + 8 * i, i < NBAR ? 1 : i < 2 * NBAR ? 16 : i < 2 * NBAR + MAX_OPS ? 8 : 1);
      }
      if (wid == 7) asm volatile("st.shared.v2.u32 [%0], {0, 0};\nfence.acq_rel.cta;" ::"r"(progress) : "memory");
      asm volatile("fence.mbarrier_init.release.cluster;" ::: "memory");
    }
  } else if (wid > 8) {
    const uint32_t g = blockIdx.x * 96 + threadIdx.x - 288, w = g - 2048;
    if (g < 4096) asm volatile("prefetch.global.L2 [%0];" ::"l"(g < 2048 ? P.xw[0] + g * (kD * 2) : P.xw[1] + (w >> 5) * (kHD * 2) + (w & 31) * 128));
  } else {
    const uint32_t op0 = P.first[role];
    if (elect()) {
#pragma unroll
      for (int k = 0; k < EARLY; k++) mbar_init(full0 + 8 * k, 1);
      asm volatile("fence.mbarrier_init.release.cluster;" ::: "memory");
      const int blk = (op0 >> 10) & 1;
      if ((op0 & 3) == OP_Q) {
#pragma unroll
        for (int k = 0; k < EARLY; k++) {
          mbar_expect(full0 + 8 * k, SZ_Q);
          tma2d(sbase + k * SZ_Q, &P.x[blk], full0 + 8 * k, 64 * k, ((op0 >> 7) & 7) * kSq + rank * 128);
          tma3d(sbase + k * SZ_Q + 16384, &P.wq[blk], full0 + 8 * k, 0, 64 * k, 3 * ((op0 >> 2) & 31));
          tma3d(sbase + k * SZ_Q + 28672, &P.wq[blk], full0 + 8 * k, 0, 64 * k + 32, 3 * ((op0 >> 2) & 31));
        }
      }
      asm volatile("prefetch.tensormap [%0];\nprefetch.tensormap [%1];" ::"l"(&P.k[blk]), "l"(&P.v[blk]) : "memory");
    }
  }
  __syncwarp();
  asm volatile("barrier.cluster.arrive.relaxed.aligned;\nbarrier.cluster.wait.aligned;" ::: "memory");

  if (wg < 2) {
    asm volatile("setmaxnreg.inc.sync.aligned.u32 240;");
    const uint32_t* prog = P.prog[role].c;
    const int wid = __shfl_sync(0xffffffffu, (int)(threadIdx.x >> 5), 1), wg = wid >> 2;
    const int lane = threadIdx.x & 31, warp = wid & 3;
    uint32_t empty_rem;
    asm volatile("mapa.shared::cluster.u32 %0, %1, %2;" : "=r"(empty_rem) : "r"(empty0), "r"(lane & 1));
    uint32_t keep = (threadIdx.x & 127) < 2 ? 4 : 0;
    auto release = [&](int slot) { mbar_arrive_cluster_n(keep, empty_rem + slot); };
    auto release_warp = [&](int slot, bool on = true) { mbar_arrive_cluster_if(lane < 2 && on, empty_rem + slot); };
    Cursor r{0};
    const uint32_t ring16 = (sbase & 0x3FFFF) >> 4;
    uint32_t cur = ring16;
    bool rdy0 = false, rdy1 = false;
    auto probe1 = [&]() { rdy0 = mbar_test(full0 + r.off(), r.ph()); };
    auto probe2 = [&]() {
      Cursor n = r;
      rdy0 = mbar_test(full0 + n.off(), n.ph());
      n.next();
      rdy1 = mbar_test(full0 + n.off(), n.ph());
    };
    auto advance = [&](uint32_t bytes, uint32_t& addr) {
      const int bi = r.off();
      r.next();
      if (cur > ring16 + ((RING - bytes) >> 4)) cur = ring16;
      addr = cur;
      cur += bytes >> 4;
      return bi;
    };
    auto take = [&](bool rdy, uint32_t bytes, uint32_t& addr) {
      if (__builtin_expect(!__all_sync(0xffffffffu, rdy), 0)) mbar_wait(full0 + r.off(), r.ph());
      return advance(bytes, addr);
    };
    const bool never = P.dbg == 0xffffffffu;
    uint32_t q[48];
#pragma unroll
    for (int i = 0; i < 48; i++) q[i] = 0;
    const int row = wg * 64 + warp * 16 + (lane >> 2);
    const int img0 = row * 4 + ((lane & 3) ^ ((row >> 1) & 3));
    uint4* pend = nullptr;
    bool pend_any = false;
    const uint64_t spol = evict_first();
    int pc = 0;
    auto slab = [&](int c, int i0) {
#pragma unroll
      for (int i = i0; i < 6; i++)
        stg2_if(c == i, pend + i * 512, q[8 * i], q[8 * i + 1], q[8 * i + 2], q[8 * i + 3],
                q[8 * i + 4], q[8 * i + 5], q[8 * i + 6], q[8 * i + 7], spol);
    };
    auto drain = [&](int c) {
      if (!pend_any || c >= 6) return;
      slab(c, 0);
      if (c == 5) {
        __syncwarp();
        mbar_arrive_if(lane == 0, odone0 - 8 + 8 * pc);
      }
    };

    for (;; pc++) {
      uint32_t op = prog[pc];
      const int type = op & 3;
      auto enter = [&]() {
        r.n = (op >> 12) & 248; cur = ring16 + (((op >> 20) & 63) << 8);
      };
      enter();
      pend_any = op & C_PEND;
      uint32_t job = 0;
      if ((op & (3 | C_WIDE)) == OP_O) job = __shfl_sync(0xffffffffu, wait_word(jobw, 1), 0);
      if (type == OP_END || job == OP_O) {
#pragma unroll 1
        for (int c = 0; c < 6; c++) drain(c);
        asm volatile("barrier.cluster.arrive.relaxed;" ::: "memory");
        break;
      }
      {
        float s[32], o[96];
        uint32_t ad0;
        int bi0, sk1;
        uint32_t pa[16], pb[16];
        float mc0, mc1, l0, l1;
        bool shifted;
        uint32_t nop;
        auto expo = [&](float (&s)[32], uint32_t (&pout)[16], float& b0, float& b1, bool shift, auto mid) {
          float c0, c1;
#pragma unroll
          for (int i = 0; i < 8; i++) {
            const float e0 = ex2(shift ? s[4 * i] - mc0 : s[4 * i]), e1 = ex2(shift ? s[4 * i + 1] - mc0 : s[4 * i + 1]);
            const float e2 = ex2(shift ? s[4 * i + 2] - mc1 : s[4 * i + 2]), e3 = ex2(shift ? s[4 * i + 3] - mc1 : s[4 * i + 3]);
            if (i) { b0 += e0; c0 += e1; b1 += e2; c1 += e3; } else { b0 = e0; c0 = e1; b1 = e2; c1 = e3; }
            pout[2 * i] = pack_bf16(e0, e1); pout[2 * i + 1] = pack_bf16(e2, e3);
            if (i & 1) mid(i >> 1);
          }
          b0 += c0; b1 += c1;
        };
        auto rowmax = [&](float (&s)[32], float& m0, float& m1) {
          m0 = fmaxf(s[0], s[1]); m1 = fmaxf(s[2], s[3]);
#pragma unroll
          for (int i = 1; i < 8; i++) { m0 = fmaxf(m0, fmaxf(s[4 * i], s[4 * i + 1])); m1 = fmaxf(m1, fmaxf(s[4 * i + 2], s[4 * i + 3])); }
          m0 = fmaxf(m0, __shfl_xor_sync(0xffffffffu, m0, 1)); m1 = fmaxf(m1, __shfl_xor_sync(0xffffffffu, m1, 1));
          m0 = fmaxf(m0, __shfl_xor_sync(0xffffffffu, m0, 2)); m1 = fmaxf(m1, __shfl_xor_sync(0xffffffffu, m1, 2));
        };
        auto first = [&](float (&s)[32], int sk0, auto mid) {
          fence_regs(s);
          release(sk0);
          mc0 = 0.f; mc1 = 0.f;
          expo(s, pa, l0, l1, false, mid);
          shifted = __any_sync(0xffffffffu, !(fmaxf(l0, l1) <= kSumLimit && fminf(l0, l1) >= 1.f / kSumLimit));
          if (shifted) {
            rowmax(s, mc0, mc1);
            expo(s, pa, l0, l1, true, [](int) {});
          }
        };
        auto qk = [&](float (&s)[32], uint32_t ak, int k0 = 0, int k1 = 12) {
#pragma unroll
          for (int kk = k0; kk < k1; kk++)
            wgmma_rs_n64<0>(s, q[4 * kk], q[4 * kk + 1], q[4 * kk + 2], q[4 * kk + 3], mk_desc(ak, 16, KV_SBO, 1) + ((kk >> 2) * KV_CH + (kk & 3) * 2), kk != 0);
          if (k1 == 12) wg_commit();
        };
        auto pv = [&](uint32_t (&pin)[16], uint32_t av, int acc) {
#pragma unroll
          for (int kk = 0; kk < 4; kk++)
            wgmma_rs_n192<1>(o, pin[4 * kk], pin[4 * kk + 1], pin[4 * kk + 2], pin[4 * kk + 3], mk_desc(av, KV_CH * 16, KV_SBO, 1) + (kk * (KV_SBO / 8)), acc || (kk != 0));
          wg_commit();
        };
        auto finish = [&](uint32_t (&pout)[16], int sk, int sv) {
          probe1();
          wg_wait<1>();
          fence_regs(s);
          release(sk);
          float b0, b1;
#pragma unroll 1
          for (bool redo = false;; redo = true) {
            expo(s, pout, b0, b1, false, [](int) {});
            if (!__any_sync(0xffffffffu, !redo && (shifted || !(fmaxf(b0, b1) <= kSumLimit)))) break;
            shifted = true;
            rowmax(s, b0, b1);
            b0 = fmaxf(mc0, b0); b1 = fmaxf(mc1, b1);
            const float a0 = ex2(mc0 - b0), a1 = ex2(mc1 - b1);
            mc0 = b0; mc1 = b1;
            l0 *= a0; l1 *= a1;
            wg_wait<0>();
            fence_regs(o);
#pragma unroll
            for (int i = 0; i < 24; i++) { o[4 * i] *= a0; o[4 * i + 1] *= a0; o[4 * i + 2] *= a1; o[4 * i + 3] *= a1; }
#pragma unroll
            for (int i = 0; i < 32; i++) s[i] -= (i & 2) ? mc1 : mc0;
          }
          l0 += b0; l1 += b1;
          wg_wait<0>();
          fence_regs(o);
          release(sv);
        };
        auto step = [&](uint32_t (&pin)[16], uint32_t (&pout)[16]) {
          uint32_t ak, av;
          const int sk = take(rdy0, SZ_KV, ak), sv = advance(SZ_KV, av);
          wg_fence();
          qk(s, ak);
          pv(pin, av, 1);
          finish(pout, sk, sv);
        };
        auto unpark = [&]() {
          uint32_t ad, ak;
          const int bi = take(rdy0, SZ_PARK, ad);
#pragma unroll
          for (int i = 0; i < 12; i++) lds128(sbase + (ad - ring16 + img0) * 16 + (i >> 1) * 8192 + (i & 1) * 512, q[4 * i], q[4 * i + 1], q[4 * i + 2], q[4 * i + 3]);
          const int sk0 = take(false, SZ_KV, ak);
          fence_regs(q);
          release_warp(bi);
          wg_fence();
          qk(s, ak);
          probe2();
          return sk0;
        };
        auto mma4 = [&](uint32_t ad, int acc) {
#pragma unroll
          for (int kk = 0; kk < 4; kk++)
            wgmma_ss_n192<1>(o, mk_desc(ad + wg * 512, 16, 1024, 1) + (kk * 2), mk_desc(ad, 4096, 1024, 1) + (1024 + (kk >> 1) * 768 + (kk & 1) * 128), acc || kk != 0);
        };
        auto convert = [&](int i0, int i1) {
          sched_fence(keep, never);
#pragma unroll
          for (int i = i0; i < i1; i++) {
            q[i] = pack_bf16(o[2 * i] * kScaleLog2, o[2 * i + 1] * kScaleLog2);
            if ((i & 7) == 7 && i != i1 - 1) sched_fence(keep, never);
          }
          sched_fence(keep, never);
        };
        auto kend = [&](int bi, int k) {
          wg_commit();
          drain(k < 8 ? (0x54732710u >> (4 * k)) & 7 : 7);
          probe1();
          wg_wait<0>();
          release(bi);
        };
        if (type == OP_O) {
          int prev = 0;
          if (op & C_WIDE) {
            float d[64];
            auto mma3 = [&](uint32_t ad, int h, int acc) {
#pragma unroll
              for (int kk = 0; kk < 2; kk++)
                wgmma_ss_n192<1>(o, mk_desc(ad + wg * 256, 16, 512, 2) + (h * 512 + kk * 2), mk_desc(ad, 4096, 1024, 1) + (1024 + h * 768 + kk * 128), acc || kk);
            };
            auto mma2 = [&](uint32_t ad, uint32_t ob, int h, int acc) {
#pragma unroll
              for (int kk = 0; kk < 2; kk++)
                wgmma_ss_n128<1>(d, mk_desc(ad + wg * 256, 16, 512, 2) + (h * 512 + kk * 2), mk_desc(ad, 4096, 1024, 1) + (ob + h * 512 + kk * 128), acc || kk);
            };
            auto wstep = [&](uint32_t bytes, int acc, auto hook) {
              uint32_t ad;
              const int bi = take(rdy0, bytes, ad);
              wg_fence();
              if (bytes == SZ_W2) mma2(ad, 1024, 0, 1); else mma3(ad, 0, acc);
              if (bytes == SZ_W) mma3(ad, 1, 1);
              wg_commit();
              if (acc) { wg_wait<1>(); release(prev); }
              if (bytes == SZ_W) mma2(ad, 2560, 0, acc);
              if (bytes == SZ_W3) mma3(ad, 1, 1); else mma2(ad, bytes == SZ_W ? 2560 : 1024, 1, 1);
              wg_commit();
              prev = bi;
              hook();
              probe1();
              wg_wait<1>();
            };
            undefine(o);
            wstep(SZ_W, 0, [&]() { drain(0); });
#pragma unroll 1
            for (int k = 1; k < ((op >> 2) & 127) - TAIL; k++) wstep(SZ_W, 1, [&]() { drain(k); });
#pragma unroll 1
            for (int k = 0; k < TAIL; k++) wstep(SZ_W2, 1, []() {});
            pend = ptr_add(P.g->part, (((op >> 9) & 31) * 2 + rank) * 81920 + 4 * 8192 + img0 * 16);
            wstep(SZ_W3, 1, [&]() {
              fence_regs(d);
#pragma unroll
              for (int i = 0; i < 32; i++) q[16 + i] = pack_bf16(d[2 * i], d[2 * i + 1]);
              slab(2, 2);
            });
#pragma unroll 1
            for (int k = 3; k < 6; k++) wstep(SZ_W3, 1, [&]() { slab(k, 2); });
            op = prog[pc + 1];
            enter();
            pend_any = true;
            pend -= 4 * 512;
            bi0 = take(rdy0 || (op & 3) != OP_Q, SZ_Q, ad0);
            sched_fence(keep, never);
            wg_wait<0>();
            fence_regs(o);
            release(prev);
#pragma unroll
            for (int i = 0; i < 48; i++) q[i] = pack_bf16(o[2 * i], o[2 * i + 1]);
            if ((op & 3) != OP_Q) continue;
            pc++;
            goto first_step;
          }
          float c[80];
          auto mma2 = [&](uint32_t ad, uint32_t oa, uint32_t ob, int acc) {
            wgmma_ss_n160<1>(c, mk_desc(ad + wg * 256, 16, 512, 2) + (oa), mk_desc(ad, 2048, 512, 2) + (1024 + ob), acc);
            wgmma_ss_n160<1>(c, mk_desc(ad + wg * 256, 16, 512, 2) + (oa + 2), mk_desc(ad, 2048, 512, 2) + (1024 + ob + 64), 1);
          };
          auto kstep = [&](int acc, auto hook, uint32_t bytes = SZ_O) {
            uint32_t ad;
            const int bi = take(rdy0, bytes, ad);
            wg_fence();
            mma2(ad, 0, 0, acc);
            wg_commit();
            if (acc) wg_wait<1>();
            if (acc == 1) release(prev);
            if (acc > 1) release_warp(prev, acc == 2 || wg == 0);
            mma2(ad, 512, 640, 1);
            wg_commit();
            prev = bi;
            hook();
            probe1();
            wg_wait<1>();
          };
          auto unblock = [&](int k) {
            if (__all_sync(0xffffffffu, rdy0) || __all_sync(0xffffffffu, mbar_try(full0 + r.off(), r.ph(), 1500))) return;
#pragma unroll 1
            for (; k < 6; k++) drain(k);
            pend_any = false;
          };
          unblock(0);
          kstep(0, [&]() { drain(0); });
          int left = ((job >> 13) & 127) - 6;
#pragma unroll 1
          for (uint32_t k = 1, pace = left >= 29 ? 0x4511 : left <= 17 ? 0x1a : 0x155; left > 0; pace >>= 2, left--) {
            unblock(k);
            kstep(1, [&]() {
#pragma unroll 1
              for (int i = pace & 3; i > 0; i--) drain(k++);
            });
          }
          uint32_t t[8], stage[3];
          float u[80];
          auto unpack = [&](int j) {
#pragma unroll
            for (int i = 0; i < 8; i++) {
              u[16 * j + 2 * i] = __uint_as_float(t[i] << 16); u[16 * j + 2 * i + 1] = __uint_as_float(t[i] & 0xffff0000u);
              asm volatile("" : "+f"(u[16 * j + 2 * i]), "+f"(u[16 * j + 2 * i + 1]));
            }
          };
#pragma unroll
          for (int i = 0; i < 8; i++) t[i] = 0;
          const uint32_t bytes = (job & P_LD) ? SZ_OL : SZ_O;
#pragma unroll
          for (int j = 0; j < 5; j++) {
            if (j == 2 && wg == 1) {
              wg_wait<0>();
              release_warp(prev);
              bar_sync(1, 256);
            }
            kstep(j == 2 ? 3 : 2, [&]() {
              if (j == 4) asm volatile("{\n.reg .pred p;\nsetp.eq.u32 p, %0, 0;\n@p bar.arrive 1, 256;\n}\n" ::"r"(wg) : "memory");
              if (j) unpack(j - 1);
              lds2_if(job & P_LD, sbase + (cur - ring16 + img0) * 16 - 8192, t);
              if (j >= 1 && j <= 3) stage[j - 1] = sbase + (cur - ring16) * 16 - bytes + wid * 1024;
            }, bytes);
          }
          unpack(4);
          sched_fence(keep, never);
          wg_wait<0>();
          fence_regs(c);
          release_warp(prev);
          asm volatile("barrier.cluster.arrive.relaxed;" ::: "memory");
#pragma unroll
          for (int i = 0; i < 10; i++) {
            const int v = (i & 1) * 2 + (lane >> 4);
            const uint32_t sa = stage[i >> 2] + (i & 2) * 4096;
            stsm4(sa + (lane & 15) * 64 + ((v ^ ((lane >> 1) & 3)) << 4), pack_bf16(c[8 * i] + u[8 * i], c[8 * i + 1] + u[8 * i + 1]),
                  pack_bf16(c[8 * i + 2] + u[8 * i + 2], c[8 * i + 3] + u[8 * i + 3]), pack_bf16(c[8 * i + 4] + u[8 * i + 4], c[8 * i + 5] + u[8 * i + 5]),
                  pack_bf16(c[8 * i + 6] + u[8 * i + 6], c[8 * i + 7] + u[8 * i + 7]));
          }
          asm volatile("fence.proxy.async.shared::cta;" ::: "memory");
          __syncwarp();
          if (elect()) {
#pragma unroll
            for (int i = 0; i < 5; i++)
              tma3d_store(&P.out, stage[i >> 1] + (i & 1) * 8192, 0, ((job >> 7) & 7) * kSq + rank * 128 + wid * 16, ((job >> 10) & 1) * 20 + ((job >> 20) & 3) * 5 + i);
            asm volatile("cp.async.bulk.commit_group;\ncp.async.bulk.wait_group.read 0;" ::: "memory");
          }
          __syncwarp();
          break;
        }
        bi0 = take(rdy0, SZ_Q, ad0);
      first_step:
        undefine(o);
        wg_fence();
        mma4(ad0, 0);
        kend(bi0, 0);
        fence_regs(o);
      next_head:
        {
#pragma unroll 1
          for (int k = 1; k < ((op & F_PARK) ? 10 : 8); k++) {
            uint32_t ad;
            const int bi = take(rdy0, SZ_Q, ad);
            wg_fence();
            mma4(ad, 1);
            kend(bi, k);
          }
          if (op & F_PARK) {
            fence_regs(o);
            convert(0, 48);
            pend = ptr_add(P.g->tile, (((op >> 2) & 511) * 2 + rank) * SZ_PARK + img0 * 16);
            continue;
          }
          uint32_t a8, a9, ak0, ak1;
          const int b8 = take(rdy0, SZ_Q, a8), b9 = take(false, SZ_Q, a9);
          wg_fence();
          mma4(a8, 1);
          wg_commit();
          mma4(a9, 1);
          wg_commit();
          pc++;
          wg_wait<1>();
          release(b8);
          const int sk0 = take(false, SZ_KV, ak0);
          wg_wait<0>();
          fence_regs(o);
          release(b9);
          float s0[32];
          convert(0, 32);
          wg_fence();
          qk(s0, ak0, 0, 4);
          convert(32, 48);
          wg_fence();
          qk(s0, ak0, 4, 12);
          sk1 = take(false, SZ_KV, ak1);
          probe1();
          wg_wait<0>();
          first(s0, sk0, [&](int i) {
            if (i == 0) return;
            sched_fence(keep, never);
            wg_fence();
            if (i == 1) qk(s, ak1, 0, 4);
            if (i == 2) qk(s, ak1, 4, 8);
            if (i == 3) qk(s, ak1, 8, 12);
            sched_fence(keep, never);
          });
        }
        for (;;) {
          {
            uint32_t av;
            const int sv = take(rdy0, SZ_KV, av);
            undefine(o);
            wg_fence();
            pv(pa, av, 0);
            finish(pb, sk1, sv);
          }
          nop = prog[pc + 1];
#pragma unroll 1
          for (int jj = 0; jj < 7; jj++) {
            step(pb, pa);
            step(pa, pb);
          }
          float i0, i1;
          auto last = [&]() {
            uint32_t av;
            const int sv = take(rdy0, SZ_KV, av);
            wg_fence();
            pv(pb, av, 1);
            sched_fence(keep, never);
            probe1();
            l0 += __shfl_xor_sync(0xffffffffu, l0, 1); l1 += __shfl_xor_sync(0xffffffffu, l1, 1);
            l0 += __shfl_xor_sync(0xffffffffu, l0, 2); l1 += __shfl_xor_sync(0xffffffffu, l1, 2);
            i0 = rcp(l0); i1 = rcp(l1);
            pend = ptr_add(P.g->tile, (((op >> 2) & 511) * 2 + rank) * SZ_PARK + img0 * 16);
            return sv;
          };
          auto normalise = [&](uint32_t (&d)[48], auto mid) {
#pragma unroll
            for (int i = 0; i < 24; i++) {
              d[8 * (i >> 2) + (i & 3)] = pack_bf16(o[4 * i] * i0, o[4 * i + 1] * i0);
              d[8 * (i >> 2) + (i & 3) + 4] = pack_bf16(o[4 * i + 2] * i1, o[4 * i + 3] * i1);
              if ((i & 1) && i != 23) sched_fence(keep, never);
              if ((i & 3) == 3 && i != 23) mid(i >> 2);
            }
          };
          const int sv = last();
          if ((nop & 3) != OP_A) {
            op = nop;
            enter();
            pend_any = true;
            bi0 = take(rdy0 || (nop & 3) != OP_Q, SZ_Q, ad0);
            sched_fence(keep, never);
            wg_wait<0>();
            fence_regs(o);
            release(sv);
            normalise(q, [](int) {});
            undefine(o);
            if ((nop & 3) != OP_Q) break;
            sched_fence(keep, never);
            wg_fence();
            mma4(ad0, 0);
            pc++;
            kend(bi0, 0);
            fence_regs(o);
            goto next_head;
          }
          const int sk0 = unpark();
          wg_wait<1>();
          fence_regs(o);
          release(sv);
          uint32_t t[48];
          auto st = [&](int i) {
            stg2_if(true, pend + i * 512, t[8 * i], t[8 * i + 1], t[8 * i + 2], t[8 * i + 3], t[8 * i + 4], t[8 * i + 5], t[8 * i + 6], t[8 * i + 7], spol);
          };
          normalise(t, [&](int i) { if (!(i & 1)) st(i >> 1); });
          wg_wait<0>();
          first(s, sk0, [&](int i) { if (i < 3) { sched_fence(keep, never); st(3 + i); } });
          __syncwarp();
          mbar_arrive_if(lane == 0, odone0 + 8 * pc);
          pc++;
          op = nop;
          uint32_t ak1;
          sk1 = take(rdy0, SZ_KV, ak1);
          rdy0 = rdy1;
          wg_fence();
          qk(s, ak1);
        }
      }
    }
    asm volatile("barrier.cluster.wait;" ::: "memory");
  } else {
    asm volatile("setmaxnreg.dec.sync.aligned.u32 24;");
    const uint32_t* prog = P.prog[role].p;
    unsigned int* flag = P.g->flag + rank;
    if (wid == 11 && (prog[0] & 3) == OP_Q) {
      const uint32_t a = prog[1];
      const char* p = ptr_add(P.kv[rank * 2 + ((a >> 10) & 1)], ((a >> 2) & 255) * (kSk * kDh * 2) + (threadIdx.x & 31) * 128);
#pragma unroll 1
      for (uint32_t k = 0; k < 3; k++) {
        wait_word(progress, 8 * k);
        p += SZ_KV;
        asm volatile("prefetch.global.L2 [%0];\nprefetch.global.L2 [%0 + 4096];" ::"l"(p));
      }
      __syncwarp();
    }
    if (wid == 8) {
      Cursor head{0}, tail{0};
      int sh = 0, room = RING >> 12;
      uint32_t cur = 0;
      uint64_t fifo = 0;
      uint32_t dst, bar = 0, ev = ev0;
      const uint64_t pol = evict_first();
      auto retire = [&]() {
        mbar_wait(empty0 + tail.off(), tail.ph());
        tail.next();
        room += (uint32_t)fifo & 31;
        fifo >>= 5;
        sh -= 5;
        asm volatile("st.volatile.shared.u32 [%0], %1;" ::"r"(progress), "r"(tail.n) : "memory");
      };
      auto acquire = [&](uint32_t bytes) {
        uint32_t fp = bytes >> 12;
        if (cur + fp > (RING >> 12)) { fp += (RING >> 12) - cur; cur = 0; }
        room -= fp;
        while (room < 0) retire();
        fifo |= (uint64_t)fp << sh;
        sh += 5;
        dst = sbase + (cur << 12);
        bar = full0 + head.off();
        cur += bytes >> 12;
        head.next();
      };
      auto gate = [&]() {
        mbar_wait(ev, 0);
        ev += 8;
        asm volatile("fence.proxy.async.global;" ::: "memory");
      };
      for (int pc = 0;; pc++) {
        uint32_t op = prog[pc];
        const int type = op & 3;
        if (type == OP_END) break;
        if (op == OP_O) {
          gate();
          op = __shfl_sync(0xffffffffu, lds32(jobw), 0);
        }
        const int blk = (op >> 10) & 1;
        if (type == OP_Q) {
          const uint64_t px = (op & P_LASTX) ? pol : no_hint(), pw = (op & P_LASTW) ? pol : no_hint();
          int k = 0;
          if (pc == 0) {
            k = 64 * EARLY; head.n = 8 * EARLY; sh = 5 * EARLY; cur = EARLY * (SZ_Q >> 12); room -= cur;
            fifo = (SZ_Q >> 12) * (((1u << (5 * EARLY)) - 1) / 31);
          }
#pragma unroll 1
          for (int stop = (op & P_GATE) ? kD - 64 : kD;; stop = kD) {
#pragma unroll 1
            for (; k < stop; k += 64) {
              acquire(SZ_Q);
              if (elect()) {
                mbar_expect(bar, SZ_Q);
                tma3d_mc_hint(dst + 16384 + rank * 12288, &P.wq[blk], bar, k + 32 * rank, 3 * ((op >> 2) & 31), pw);
                tma2d_hint(dst, &P.x[blk], bar, k, ((op >> 7) & 7) * kSq + rank * 128, px);
              }
            }
            if (k == kD) break;
            gate();
          }
        } else if (type == OP_A) {
          const int row0 = ((op >> 2) & 255) * kSk;
          if (op & F_PARK) {
            gate();
            acquire(SZ_PARK);
            if (elect()) {
              mbar_expect(bar, SZ_PARK);
              bulk_load_hint(dst, &P.g->tile[(((op >> 20) & 511) * 2 + rank) * 3072], SZ_PARK, bar, pol);
            }
          }
          auto kv = [&](uint32_t tx, const CUtensorMap* m, int c3) {
            const uint32_t before = bar;
            acquire(SZ_KV);
            if (elect()) {
              mbar_expect(bar, tx);
              tma4d_mc_hint(dst + rank * (SZ_KV / 2), m, tx ? bar : before, c3, pol);
            }
          };
          int c3 = row0 / 8 + 4 * rank;
          const int end = c3 + 120;
          kv(SZ_KV, &P.k[blk], c3);
#pragma unroll 1
          for (uint32_t tv = SZ_KV; c3 != end; tv = 0, c3 += 8) {
            kv(2 * SZ_KV - tv, &P.k[blk], c3 + 8);
            kv(tv, &P.v[blk], c3);
          }
          if (op & P_GATE) gate();
          kv(SZ_KV, &P.v[blk], c3);
        } else {
          const uint4* part = &P.g->part[((((op >> 6) & 30) + ((op >> 21) & 1)) * 2 + rank) * 5120 + ((op >> 20) & 1) * 2560];
          auto run = [&](const uint32_t bytes, int k, int cnt, int gates) {
            const int col = bytes == SZ_O || bytes == SZ_OL ? 5 * ((op >> 20) & 3) : 5 * ((op >> 21) & 1);
            int row = 8 * k + 4 * rank, pre = bytes == SZ_O && (op & P_PRE) ? 0 : 2560;
#pragma unroll 1
            for (int h = (k * 43) >> 7, k0 = k - 3 * h; cnt > 0; h++, k0 = 0, gates = gates >> 1 | (gates & 2)) {
              const uint4* src = &P.g->tile[(P.slot[((op >> 2) & 480) + h] * 2 + rank) * 3072 + k0 * 1024];
              const uint64_t pw = h >= ((op >> 23) & 31) && h < 2 * (op >> 28) ? pol : no_hint();
              if (gates & 1) gate();
              int m = min(3 - k0, cnt);
              cnt -= m;
#pragma unroll 1
              for (; m > 0; m--, src += 1024, row += 8) {
                acquire(bytes);
                if (elect()) {
                  mbar_expect(bar, bytes);
                  if (bytes == SZ_O || bytes == SZ_OL) tma5d_mc_hint(dst + 16384 + rank * 10240, &P.wo[blk], bar, row, col, no_hint());
                  if (bytes == SZ_W || bytes == SZ_W3) tma5d_mc_hint(dst + 16384 + rank * 12288, &P.wo3[blk], bar, row, col, pw);
                  bulk_load_hint(dst, src, 16384, bar, pol);
                  if (bytes == SZ_W || bytes == SZ_W2) tma5d_mc_hint(dst + bytes - 16384 + rank * 8192, &P.wo2[blk], bar, row, col + 3, pw);
                  if (bytes == SZ_OL) bulk_load_hint(dst + SZ_O, part, 8192, bar, pol);
                }
                if (bytes == SZ_OL) part += 512;
              }
              if (pre < 2560) {
                if (elect()) asm volatile("cp.async.bulk.prefetch.L2.global [%0], 10240;" ::"l"(part + pre) : "memory");
                pre += 640;
              }
            }
          };
          const int n = (op >> 13) & 127;
          if (op & P_WIDE) {
            run(SZ_W, 0, n - TAIL, 3);
            run(SZ_W2, n - TAIL, TAIL, (n - TAIL) % 3 ? 2 : 3);
            run(SZ_W3, n - TAIL, TAIL, 0);
          } else {
            if (op & P_PRE) gate();
            run(SZ_O, kSteps - n, (op & P_LD) ? n - 5 : n, 3);
            if (op & P_LD) {
              if (!(op & P_PRE)) gate();
              run(SZ_OL, kSteps - 5, 5, 2);
            }
          }
        }
      }
#pragma unroll 1
      while (sh) retire();
    } else if (threadIdx.x == 288) {
      for (int pc = 0;; pc++) {
        const uint32_t op = prog[pc];
        const int type = op & 3;
        if (type == OP_END) break;
        if (type == OP_Q ? !(op & F_PARK) : type == OP_O && !(op & P_WIDE)) continue;
        const int id = type == OP_A ? (op >> 2) & 511 : type == OP_Q ? N_TILE + ((op >> 13) & 127) : ID_PART + ((op >> 5) & 60) + ((op >> 20) & 3);
        const uint32_t v = type == OP_O ? 1 : P.info[id] & 7;
        mbar_wait_long(odone0 + 8 * pc);
        flag_set(flag + 2 * id, v);
        if (type == OP_O && (op & P_WIDE)) flag_set(flag + 2 * id + 2, v);
      }
    } else if (wid == 10) {
      int i = threadIdx.x & 31;
      const int n_ev = P.prog[role].n_ev;
      auto event = [&]() { return i < n_ev ? P.prog[role].ev[i] : n_ev ? E_JOB | (i - n_ev) : 0; };
      uint32_t e = i < 8 ? event() : 0;
      for (uint32_t n = 0; __any_sync(0xffffffffu, e); n++) {
        uint32_t job = lds32(jobw);
        const int togo = (e & E_DRAW) ? (e & 1023) - (lds32(progress) >> 3) : 99;
        if (togo <= 0 && rank == 0) {
          job = P.job[atomicInc(&P.g->ticket, gridDim.x / 2 - 1)];
          asm volatile("{\n.reg .u32 a;\nmapa.shared::cluster.u32 a, %0, 1;\nst.volatile.shared::cluster.u32 [a], %1;\n"
                       "st.volatile.shared.u32 [%0], %1;\n}\n" ::"r"(jobw), "r"(job) : "memory");
        }
        if ((e & E_JOB) && job) {
          const uint32_t j = e & 63, heads = job == OP_O ? 0 : kH - ((job >> 2) & 31), jp = !(job & P_LD) ? 63 : (job & P_PRE) ? 0 : heads - 1, h = j - (j > jp);
          e = j == jp ? (ID_PART + ((job >> 5) & 60) + ((job >> 20) & 3)) | E_ON | E_LAST : h < heads ? (((job >> 2) & 511) + h) | E_ON | E_LAST : 0;
        }
        unsigned int* f = ptr_add(flag, 8 * (e & 1023));
        const bool ok = (e & E_ON) ? flag_get(f) - 1 < ((e & E_FREE) ? 1 : 7) : (e & E_DRAW) && job;
        if (ok) {
          mbar_arrive(ev0 + 8 * i);
          if (e & (E_FREE | E_LAST)) flag_dec(f);
          i += 8;
          e = event();
        }
        asm volatile("{\n.reg .pred p;\nsetp.ge.u32 p, %0, 0x400000;\n@p trap;\n}\n" ::"r"(n));
        if (!__any_sync(0xffffffffu, ok)) __nanosleep(__any_sync(0xffffffffu, job || togo <= 2) ? 100 : 600);
      }
    } else if (threadIdx.x == 352) {
      uint32_t items = 0;
      auto read = [&](int id) {
        if (!(P.info[id] & I_NEXT)) return;
        wait_word(progress, 8 * items);
        flag_dec(flag + 2 * id);
      };
      for (int pc = 0;; pc++) {
        const uint32_t op = prog[pc];
        const int type = op & 3;
        if (type == OP_END) break;
        if (type == OP_O) {
          const uint32_t n = (op >> 13) & 127, base = items;
#pragma unroll 1
          for (uint32_t k = 3, id = (op >> 2) & 511; k <= n; k += 3, id++) {
            items = base + k + (k + TAIL > n ? TAIL : 0);
            read(id);
          }
          items = base + n + TAIL;
        } else if (type == OP_A) {
          if (op & F_PARK) { items++; read(N_TILE + ((op >> 13) & 127)); }
          items += 32;
        } else {
          items += 10;
        }
      }
    }
    __syncwarp();
    asm volatile("barrier.cluster.arrive.relaxed;\nbarrier.cluster.wait;" ::: "memory");
  }
}

typedef CUresult (*EncodeFn)(CUtensorMap*, CUtensorMapDataType, cuuint32_t, void*, const cuuint64_t*, const cuuint64_t*,
                             const cuuint32_t*, const cuuint32_t*, CUtensorMapInterleave, CUtensorMapSwizzle,
                             CUtensorMapL2promotion, CUtensorMapFloatOOBfill);

void encode(EncodeFn fn, CUtensorMap* m, const void* ptr, int rank, const cuuint64_t* dims, const cuuint64_t* strides,
            const cuuint32_t* box, CUtensorMapSwizzle swz) {
  const cuuint32_t es[5] = {1, 1, 1, 1, 1};
  CUresult r = fn(m, CU_TENSOR_MAP_DATA_TYPE_BFLOAT16, rank, const_cast<void*>(ptr), dims, strides, box, es,
                  CU_TENSOR_MAP_INTERLEAVE_NONE, swz, CU_TENSOR_MAP_L2_PROMOTION_L2_128B, CU_TENSOR_MAP_FLOAT_OOB_FILL_NONE);
  if (r != CUDA_SUCCESS) fprintf(stderr, "cuTensorMapEncodeTiled failed: %d\n", (int)r);
}

struct Op { int type, flags, id, n, quarter, park, item0, items; double t0, t1; };
struct Use { double ready, gate, need, freed; int readers, slot, prev; bool next; };
struct PlanStats { double end, slack, park_slack; int slots, parks; uint32_t own[N_CL]; };

bool plan(const char* const* text, int n_pair, int phase, Params& P, PlanStats* stats = nullptr) {
  constexpr double T_Q = 7900, T_A = 24800, T_U = TU, T_O = 640, T_RUN = 800, T_WIDE = TW, AHEAD = 3500, PUBLISH = 1500;
  const double margin = 256.0 * ((P.dbg >> 8) & 255);
  static Op op[N_CL][MAX_OPS];
  static Use use[ID_PART];
  int n_op[N_CL], covered[2 * N_TEAM] = {};
  struct Ref { double t; Op* o; int id; };
  static Ref att[N_TILE + 1], dem[N_TILE], prk[MAX_PARK + 1], unp[MAX_PARK + 1], wr[ID_PART];
  auto sort = [](Ref* r, int n) {
    for (int i = 1; i < n; i++)
      for (int j = i; j > 0 && r[j].t < r[j - 1].t; j--) { Ref x = r[j]; r[j] = r[j - 1]; r[j - 1] = x; }
  };
  auto hex = [](char c) { return c <= '9' ? c - '0' : c - 'a' + 10; };
  for (int i = 0; i < n_pair; i++)
    for (const char* s = text[i]; *s; s++)
      for (int h = 0; *s == 'J' && h < 2; h++) {
        if (covered[2 * hex(s[1]) + h]) return false;
        covered[2 * hex(s[1]) + h] = 10 * (s[2 + 2 * h] - '0') + s[3 + 2 * h] - '0';
      }
  for (int c = 0; c < 2 * n_pair; c++) {
    int n = 0, items = 0;
    double t = 0;
    auto add = [&](int type, int flags, int id, int heads, int quarter, int its, double dt) {
      if (n < MAX_OPS) op[c][n] = {type, flags, id, heads, quarter, 0, items, its, t, t + dt};
      n++; items += its; t += dt;
    };
    for (const char* s = text[c >> 1]; *s; s++) {
      const int tm = hex(s[1]) & 15, nj = covered[2 * tm + (c & 1)];
      if (*s == 'N') { add(OP_Q, 0, 0, 0, 0, 10, T_Q); add(OP_A, 0, 0, 0, 0, 32, T_A); }
      if (*s == 'P') add(OP_Q, F_PARK, 0, 0, 0, 10, T_Q + TP);
      if (*s == '+' || *s == '-') t += *s == '+' ? 1000 : -1000;
      if (*s == 'U') { if (n == 0 || n > MAX_OPS || op[c][n - 1].type != OP_A) return false; add(OP_A, F_PARK, 0, 0, 0, 33, T_U); }
      if (*s == 'J') { if (nj < TAIL + 6 || nj > kSteps - 11) return false; add(OP_O, P_WIDE, tm * kH, nj, 2 * (c & 1), nj + TAIL, 2 * T_O * nj + T_WIDE); }
    }
    add(OP_O, 0, 0, 0, 0, 0, 0);
    add(OP_END, 0, 0, 0, 0, 0, 0);
    if (n > MAX_OPS || op[c][0].type != OP_Q) return false;
    n_op[c] = n - 1;
    att[c] = {t, &op[c][n - 2], 0};
  }
  for (int i = 0; i < 4 * N_TEAM; i++) dem[i] = {(double)covered[i / 2], nullptr, i};
  sort(att, 2 * n_pair); sort(dem, 4 * N_TEAM);
  for (int i = 0; i < 4 * N_TEAM; i++) {
    Op* f = att[i].o;
    const int nj = covered[dem[i].id / 2];
    f->flags = nj ? P_LD : 0;
    f->id = dem[i].id / 4 * kH + nj / 3; f->quarter = dem[i].id & 3; f->items = f->n = kSteps - nj;
    f[1].t0 = f[1].t1 = f->t1 = f->t0 + T_O * f->n + T_RUN; f[1].item0 += f->n;
  }
  for (int i = 0; i < ID_PART; i++) use[i] = {0, 0, 1e18, 0, 0, 0, 0, false};
  int n_att = 0, n_prk = 0, n_unp = 0;
  auto ready = [&](const Op* o) {
    const int nt = o[1].type;
    return o->t1 + (nt == OP_Q ? 6100 : o[1].n ? ((o[1].flags & P_WIDE) ? 7700 : 3900) : 1500) + PUBLISH;
  };
  for (int c = 0; c < 2 * n_pair; c++)
    for (Op* o = op[c]; o->type != OP_END; o++) {
      if (o->type == OP_A) { att[n_att] = {ready(o), o, 0}; if (++n_att > N_TILE) return false; }
      if (o->type == OP_A && o->flags) { unp[n_unp] = {o->t0 - AHEAD, o, 0}; if (++n_unp > MAX_PARK) return false; }
      if (o->type == OP_Q && o->flags) { prk[n_prk] = {ready(o), o, 0}; if (++n_prk > MAX_PARK) return false; }
      for (int i = 0; o->type == OP_O && i < o->n; i++) {
        const int nw = (o->flags & P_WIDE) ? o->n - TAIL : 0, k = nw ? i : kSteps - o->n + i;
        Use& u = use[o->id / kH * kH + k / 3];
        const double t = o->t0 + T_O * (i + (i < nw ? i : nw));
        if (t - AHEAD < u.need) u.need = t - AHEAD;
        const double f = !nw ? 1e18 : i + FLIGHT < o->items - TAIL || (nw && o[1].type != OP_O) ? t + T_O * (i < nw ? 2 : 1 + TAIL) + PUBLISH : 1e18;
        if (f > u.freed) u.freed = f;
        if (i == 0 || k % 3 == 0) u.readers++;
      }
    }
  if (n_att != N_TILE || n_prk != n_unp) return false;
  for (int i = 0; i < N_TILE; i++) { const int id = (i & 15) * kH + (i >> 4); dem[i] = {use[id].need, nullptr, id}; }
  sort(att, n_att); sort(dem, N_TILE); sort(prk, n_prk); sort(unp, n_unp);
  PlanStats st = {0, 1e18, 1e18, 0, n_prk};
  int n_wr = 0;
  for (int i = 0; i < N_TILE; i++) {
    Op* o = att[i].o;
    o->id = dem[i].id;
    if (!o->flags) o[-1].id = o->id;
    if (dem[i].t - att[i].t < st.slack) st.slack = dem[i].t - att[i].t;
    wr[n_wr++] = {o->t1 - 2 * AHEAD, o, o->id};
  }
  for (int i = 0; i < n_prk; i++) {
    prk[i].o->id = unp[i].o->id;
    prk[i].o->park = unp[i].o->park = i;
    use[N_TILE + i].freed = unp[i].o->t0 + 2 * PUBLISH;
    use[N_TILE + i].readers = 1;
    if (unp[i].t - prk[i].t < st.park_slack) st.park_slack = unp[i].t - prk[i].t;
    wr[n_wr++] = {prk[i].o->t1 - 2 * AHEAD, prk[i].o, N_TILE + i};
  }
  for (int c = 0; c < 2 * n_pair; c++)
    for (int d = 0; d < 2 * n_pair; d++)
      for (Op *f = &op[c][n_op[c] - 1], *o = op[d]; f->n && o->type != OP_END; o++)
        if (o->type == OP_O && (o->flags & P_WIDE) && o->id / kH == f->id / kH && o->quarter / 2 == f->quarter / 2) {
          if (f->t0 - o->t1 > 4096.0 * ((P.dbg >> 16) & 255)) f->flags |= P_PRE;
          const double slack = f->t0 + ((f->flags & P_PRE) ? 0 : (f->n - 5) * T_O) - AHEAD - ready(o);
          if (slack < st.park_slack) st.park_slack = slack;
        }
  constexpr double long_while = 160000;
  for (int c = 0; c < 2 * n_pair; c++)
    for (Op* o = op[c]; o->type != OP_END; o++) {
      if (o->type == OP_O && (o->flags & P_WIDE)) {
        int run = 0, best = 0, end = 0;
        for (int h = 0; 3 * h < o->n; h++) {
          bool last = true;
          for (int d = 0; d < 2 * n_pair; d++)
            for (const Op* e = op[d]; e->type != OP_END; e++) {
              if (e->type != OP_O || e == o || ((e->id ^ o->id) & 256) || e->quarter / 2 != o->quarter / 2) continue;
              const bool wide = e->flags & P_WIDE;
              if (wide ? 3 * h >= e->n : 3 * h + 3 <= kSteps - e->n) continue;
              const double dt = e->t0 + T_O * (wide ? 6 * h : 3 * h - kSteps + e->n) - o->t0 - T_O * 6 * h + (d - c) * 1e-3;
              if (dt > 0 && dt < long_while) last = false;
            }
          run = last ? run + 1 : 0;
          if (run > best) { best = run; end = h + 1; }
        }
        if (3 * end >= o->n) end++;
        o->park = (end - best) | (end / 2) << 5;
      }
      if (o->type != OP_Q) continue;
      bool lw = true, lx = true;
      for (int d = 0; d < 2 * n_pair; d++)
        for (const Op* e = op[d]; e->type != OP_END; e++) {
          const double dt = e->t0 - o->t0 + (d - c) * 1e-3;
          if (e->type != OP_Q || e == o || dt < 0 || dt > long_while) continue;
          if (((e->id ^ o->id) & (256 + 31)) == 0) lw = false;
          if (e->id / kH == o->id / kH) lx = false;
        }
      o->quarter = (lw ? P_LASTW : 0) | (lx ? P_LASTX : 0);
    }
  sort(wr, n_wr);
  int holder[N_TILE];
  for (int i = 0; i < n_wr; i++) {
    int best = -1;
    for (int sl = 0; sl < st.slots; sl++)
      if (use[holder[sl]].freed + margin <= wr[i].t && (best < 0 || use[holder[sl]].freed < use[holder[best]].freed)) best = sl;
    Use& u = use[wr[i].id];
    if (best >= 0) { u.prev = holder[best]; use[u.prev].next = true; wr[i].o->flags |= P_GATE; }
    else if (st.slots == N_TILE) return false;
    else best = st.slots++;
    u.slot = best;
    holder[best] = wr[i].id;
  }
  {
    int pos[N_CL] = {}, flag[ID_PART + 4 * N_TEAM] = {}, seen[ID_PART] = {};
    auto goal = [&](int c) { return op[c][n_op[c] - 1].item0; };
    for (bool moved = true; moved;) {
      moved = false;
      for (int c = 0; c < 2 * n_pair; c++) {
        for (; pos[c] < goal(c); pos[c]++, moved = true) {
          bool ok = true;
          for (const Op* o = op[c]; o->type != OP_END; o++) {
            const int k = pos[c] - o->item0, own = o->type == OP_A ? o->id : N_TILE + (o->park & 127);
            if (k < 0 || k >= o->items) continue;
            if (o->type == OP_O) ok = k >= o->n || flag[o->id + k / 3];
            else if (k == o->items - 1 && (o->flags & P_GATE)) ok = seen[use[own].prev] == use[use[own].prev].readers;
            else if (k == 0 && o->type == OP_A && (o->flags & F_PARK)) ok = flag[N_TILE + o->park];
          }
          if (!ok) break;
          for (const Op* o = op[c]; o->type != OP_END; o++) {
            if (pos[c] == o->item0 + o->items + (o[1].type == OP_Q ? 7 : o[1].item0 == goal(c) ? -1 : 5)) {
              if (o->type == OP_A) flag[o->id] = 1;
              if (o->type == OP_Q && (o->flags & F_PARK)) flag[N_TILE + o->park] = 1;
              if (o->type == OP_O) flag[ID_PART + o->id / kH * 4 + o->quarter] = flag[ID_PART + o->id / kH * 4 + o->quarter + 1] = 1;
            }
            const int k = pos[c] - FLIGHT - o->item0, nw = o->n - TAIL;
            if (k == 0 && o->type == OP_A && (o->flags & F_PARK)) seen[N_TILE + o->park]++;
            if (o->type == OP_O && k >= 0 && k < o->items && (k < nw || k >= o->n) && (k < nw ? k : k - TAIL) % 3 == 2) seen[o->id + (k < nw ? k : k - TAIL) / 3]++;
          }
        }
      }
    }
    for (int c = 0; c < 2 * n_pair; c++) if (pos[c] < goal(c)) return false;
  }
  int n_job = 0, longest = 0;
  for (int i = 0; i < 2 * N_TEAM; i++) if (kH + 1 - covered[i] / 3 > longest) longest = kH + 1 - covered[i] / 3;
  for (int c = 0; c < 2 * n_pair; c++) {
    uint32_t items = 0, cur = 0, pend = 0;
    int n = 0, ev = 0;
    auto item = [&](uint32_t bytes, int count) {
      for (int i = 0; i < count; i++) { if (cur + bytes > RING) cur = 0; cur += bytes; items++; }
    };
    auto event = [&](uint32_t e) { if (ev < MAX_TAB) P.prog[c].ev[ev] = e; ev++; };
    for (const Op* o = op[c];; o++) {
      if (o->type != OP_END && phase && (o->type == OP_O) != (phase == 2)) continue;
      uint32_t cw = o->type | (items % (2 * NBAR)) << 15 | (cur >> 12) << 20 | pend, pw = o->type | o->id << 2 | o->flags;
      const int ps = use[N_TILE + (o->park & 127)].slot;
      pend = 0;
      if (o->type == OP_O) {
        pw |= o->n << 13 | o->quarter << 20 | (uint32_t)o->park << 23;
        if (o->flags & P_WIDE) {
          cw |= o->n << 2 | (o->id / kH * 2 + o->quarter / 2) << 9 | C_WIDE;
          item(SZ_W, o->n - TAIL);
          item(SZ_W2, TAIL);
          item(SZ_W3, TAIL);
          pend = C_PEND;
          for (int i = 0; 3 * i < o->n; i++) event((o->id + i) | E_ON | (use[o->id + i].next ? 0 : E_LAST));
        } else {
          dem[n_job++] = {o->t0 - 1e6 * o->n, nullptr, (int)pw};
          st.own[c] = pw;
          pw = OP_O;
          event(E_DRAW | (items < 16 ? 0 : items - 16));
        }
      } else if (o->type != OP_END) {
        const bool parks = o->type == OP_Q && (o->flags & F_PARK);
        cw |= (parks ? ps : use[o->id].slot) << 2 | (o->flags & F_PARK);
        if (o->flags & F_PARK) pw |= o->park << 13 | ps << 20;
        if (o->type == OP_Q) { item(SZ_Q, 10); pw |= o->quarter; }
        else { if (o->flags & F_PARK) { item(SZ_PARK, 1); event((N_TILE + o->park) | E_ON | (use[N_TILE + o->park].next ? 0 : E_LAST)); } item(SZ_KV, 32); }
        if (parks || o->type == OP_A) pend = C_PEND;
        if (o->flags & P_GATE) event(use[parks ? N_TILE + o->park : o->id].prev | E_ON | E_FREE);
      }
      P.prog[c].c[n] = cw; P.prog[c].p[n++] = pw;
      if (o->type == OP_END) { if (o->t0 > st.end) st.end = o->t0; break; }
    }
    if (ev > MAX_TAB || ev + longest > MAX_EV) return false;
    P.prog[c].n_ev = ev;
    while (n < MAX_OPS) { P.prog[c].c[n] = OP_END; P.prog[c].p[n++] = OP_END; }
    P.first[c] = (uint16_t)(P.prog[c].p[0] & 2047);
  }
  sort(dem, n_job);
  for (int i = 0; i < n_job; i++) P.job[i] = dem[i].id;
  for (int i = 0; i < ID_PART; i++) {
    if (i < N_TILE) P.slot[i] = use[i].slot;
    P.info[i] = (use[i].readers + use[i].next) | (use[i].next ? I_NEXT : 0);
  }
  if (stats) *stats = st;
  return true;
}

const char* const kPrograms[N_CL / 2] = {
  "PNJ06565NNNNN", "PNJ15858NNNNN", "PNJ25656NNNNN", "PNJ35454+NNNNN", "PNJ47878NNNNN", "PNJ57373NNNNN",
  "NNJ68080NNNN", "NNJ76868NNNN", "NNNNNJ83535NN", "NNNNNNJf4343N", "NNNNNJa5252NN", "NNNNNJb4848NN",
  "NUNNNNNNN", "NUNNNJd5353NN", "NUNNNJe6363NN", "NNNNNJ97676N", "PNNNNNNNNN", "PNNNNNNNNN",
  "PNNNNNNNNN", "PNNNNNNNNN", "PNNNNNNNNN", "NNNNNNNNN", "NNNNNNNNN", "NNNNNNNNN",
  "NUNNNNNNN", "NNNNNNNNN", "NUNNNNNNN", "NUNNNNNNN", "NNUNNNNNN", "NUNNNNNNN",
  "NUNNNNNNN", "NNUNNJc5353NN", "NUNNNNNNN",
};

const char* const* bench_programs() {
  return kPrograms;
}

}

extern "C" void kernel_launch(void* const* d_in, const int* in_sizes, int n_in, void* d_out, int out_size) {
  (void)in_sizes; (void)n_in; (void)out_size;
  static EncodeFn fn = nullptr;
  static int n_clusters = 0;
  if (!fn) {
    cudaDriverEntryPointQueryResult qr;
    void* f = nullptr;
    cudaGetDriverEntryPoint("cuTensorMapEncodeTiled", &f, cudaEnableDefault, &qr);
    fn = (EncodeFn)f;
    cudaFuncSetAttribute(fused_kernel, cudaFuncAttributeMaxDynamicSharedMemorySize, SMEM_BYTES);
    cudaLaunchConfig_t cfg = {};
    cfg.gridDim = dim3(132); cfg.blockDim = dim3(384); cfg.dynamicSmemBytes = SMEM_BYTES;
    cudaLaunchAttribute at[1];
    at[0].id = cudaLaunchAttributeClusterDimension; at[0].val.clusterDim.x = 2; at[0].val.clusterDim.y = 1; at[0].val.clusterDim.z = 1;
    cfg.attrs = at; cfg.numAttrs = 1;
    if (cudaOccupancyMaxActiveClusters(&n_clusters, fused_kernel, &cfg) != cudaSuccess || n_clusters < 1) n_clusters = 1;
    (void)cudaGetLastError();
  }
  static Params P;
  const CUtensorMapSwizzle S128 = CU_TENSOR_MAP_SWIZZLE_128B, S64 = CU_TENSOR_MAP_SWIZZLE_64B;
  for (int blk = 0; blk < 2; blk++) {
    void* const* in = d_in + 5 * blk;
    { const cuuint64_t d[] = {kD, kB * kSq}, s[] = {kD * 2}; const cuuint32_t b[] = {64, 128};
      encode(fn, &P.x[blk], in[0], 2, d, s, b, S128); }
    { const cuuint64_t d[] = {64, 8, 3, (cuuint64_t)kB * kH * kSk / 8}, s[] = {kDh * 2, 128, 8 * kDh * 2}; const cuuint32_t b[] = {64, 8, 3, 4};
      encode(fn, &P.k[blk], in[1], 4, d, s, b, S128);
      encode(fn, &P.v[blk], in[2], 4, d, s, b, S128); }
    { const cuuint64_t d[] = {64, kD, kHD / 64}, s[] = {kHD * 2, 128}; const cuuint32_t b[] = {64, 32, 3};
      encode(fn, &P.wq[blk], in[3], 3, d, s, b, S128); }
    { const cuuint64_t d[] = {32, 2, kHD / 8, 4, kD / 32}, s[] = {kD * 2, 8 * kD * 2, 2 * kD * 2, 64}; const cuuint32_t b[] = {32, 2, 4, 4, 5};
      encode(fn, &P.wo[blk], in[4], 5, d, s, b, S64); }
    { const cuuint64_t d[] = {64, 2, kHD / 8, 4, kD / 64}, s[] = {kD * 2, 8 * kD * 2, 2 * kD * 2, 128};
      const cuuint32_t b3[] = {64, 2, 4, 4, 3}, b2[] = {64, 2, 4, 4, 2};
      encode(fn, &P.wo3[blk], in[4], 5, d, s, b3, S128);
      encode(fn, &P.wo2[blk], in[4], 5, d, s, b2, S128); }
  }
  { const cuuint64_t d[] = {32, kB * kSq, 2 * kD / 32}, s[] = {2 * kD * 2, 64}; const cuuint32_t b[] = {32, 16, 1};
    encode(fn, &P.out, d_out, 3, d, s, b, S64); }

  P.kv[0] = (const char*)d_in[1]; P.kv[1] = (const char*)d_in[6]; P.kv[2] = (const char*)d_in[2]; P.kv[3] = (const char*)d_in[7];
  P.xw[0] = (const char*)d_in[0]; P.xw[1] = (const char*)d_in[3];
  cudaGetSymbolAddress((void**)&P.g, g_scratch);
  P.dbg = DBG_DEFAULT;
  if (n_clusters >= N_CL && plan(bench_programs(), N_CL / 2, 0, P)) {
    fused_kernel<<<2 * N_CL, 384, SMEM_BYTES>>>(P);
  } else {
    const char* text[2 * N_TEAM];
    for (int i = 0; i < 2 * N_TEAM; i++) text[i] = "NNNNNNNN";
    for (int phase = 1; phase <= 2; phase++) {
      plan(text, 2 * N_TEAM, phase, P);
      fused_kernel<<<8 * N_TEAM, 384, SMEM_BYTES>>>(P);
    }
  }
}
```

```cpp
#include <cuda_runtime.h>
#include <cuda_bf16.h>
#include <cuda.h>
#include <cuda/annotated_ptr>
#include <stdint.h>
#include <stdio.h>

namespace {

constexpr int kB = 8, kSq = 256, kD = 640, kH = 32, kSk = 1024, kDh = 192;
constexpr int kHD = kH * kDh;
constexpr uint32_t RING = 224 * 1024;
constexpr uint32_t SZ_KV = 24576;
constexpr uint32_t SZ_Q = 16384 + 24576;
constexpr uint32_t SZ_O = 16384 + 20480;
constexpr uint32_t SZ_W3 = 16384 + 24576, SZ_W2 = 16384 + 16384, SZ_W = SZ_W3 + 16384;
constexpr uint32_t SZ_PARK = 49152;
constexpr uint32_t SZ_OL = SZ_O + 8192;
constexpr int NBAR = 16, FLIGHT = RING / SZ_KV + 1;
constexpr int EARLY = 3;
constexpr int kSteps = kHD / 64;
constexpr int TAIL = 4;
constexpr uint32_t KV_CH = 64, KV_SBO = 3072;
constexpr int SMEM_BYTES = RING + 1024 + 1024;
constexpr int N_TEAM = 16, N_CL = 66, MAX_OPS = 22, MAX_EV = 72, MAX_TAB = 47, N_TILE = N_TEAM * kH, MAX_PARK = 128, ID_PART = N_TILE + MAX_PARK;
enum : uint32_t { OP_END = 0, OP_Q = 1, OP_A = 2, OP_O = 3, F_PARK = 1 << 11,
                  C_WIDE = 1 << 27, C_PEND = 1 << 26, P_GATE = 1 << 12, P_WIDE = 1 << 11, P_LD = 1 << 12, P_PRE = 1 << 22, P_LASTW = 1 << 29, P_LASTX = 1 << 30,
                  I_NEXT = 8, E_ON = 1 << 15, E_FREE = 1 << 14, E_LAST = 1 << 13, E_DRAW = 1 << 12, E_JOB = 1 << 11 };

#define TU 25900
#define TW 1600
#define TP 1000
constexpr uint32_t DBG_DEFAULT = 0x040800;

struct alignas(1024) Scratch {
  unsigned int flag[2047];
  unsigned int ticket;
  uint4 part[N_TEAM * 2 * 2 * 5120];
  uint4 tile[N_TILE * 2 * 3072];
};

struct alignas(64) Params {
  const char* xw[2];
  uint16_t first[80];
  Scratch* g;
  uint32_t dbg;
  CUtensorMap x[2], wq[2], k[2], v[2], wo[2], wo3[2], wo2[2], out;
  struct {
    uint32_t c[MAX_OPS];
    uint32_t p[MAX_OPS];
    uint16_t n_ev, ev[MAX_TAB];
  } prog[N_CL];
  const char* kv[4];
  uint32_t job[N_CL];
  uint16_t slot[N_TILE];
  uint8_t info[ID_PART];
};

__device__ Scratch g_scratch;

template <int TB, int TA = 0>
__device__ __forceinline__ void wgmma_ss_n64(float (&d)[32], uint64_t da, uint64_t db, int scale_d) {
  asm volatile("{\n.reg .pred p;\nsetp.ne.b32 p, %34, 0;\n"
    "wgmma.mma_async.sync.aligned.m64n64k16.f32.bf16.bf16 {%0, %1, %2, %3, %4, %5, %6, %7, %8, %9, %10, %11, %12, %13, %14, %15, %16, %17, %18, %19, %20, %21, %22, %23, %24, %25, %26, %27, %28, %29, %30, %31}, %32, %33, p, 1, 1, %35, %36;\n}\n"
    : "+f"(d[0]), "+f"(d[1]), "+f"(d[2]), "+f"(d[3]), "+f"(d[4]), "+f"(d[5]), "+f"(d[6]), "+f"(d[7]), "+f"(d[8]), "+f"(d[9]), "+f"(d[10]), "+f"(d[11]), "+f"(d[12]), "+f"(d[13]), "+f"(d[14]), "+f"(d[15]), "+f"(d[16]), "+f"(d[17]), "+f"(d[18]), "+f"(d[19]), "+f"(d[20]), "+f"(d[21]), "+f"(d[22]), "+f"(d[23]), "+f"(d[24]), "+f"(d[25]), "+f"(d[26]), "+f"(d[27]), "+f"(d[28]), "+f"(d[29]), "+f"(d[30]), "+f"(d[31])
    : "l"(da), "l"(db), "r"(scale_d), "n"(TA), "n"(TB));
}
template <int TB>
__device__ __forceinline__ void wgmma_rs_n64(float (&d)[32], uint32_t a0, uint32_t a1, uint32_t a2, uint32_t a3, uint64_t db, int scale_d) {
  asm volatile("{\n.reg .pred p;\nsetp.ne.b32 p, %37, 0;\n"
    "wgmma.mma_async.sync.aligned.m64n64k16.f32.bf16.bf16 {%0, %1, %2, %3, %4, %5, %6, %7, %8, %9, %10, %11, %12, %13, %14, %15, %16, %17, %18, %19, %20, %21, %22, %23, %24, %25, %26, %27, %28, %29, %30, %31}, {%32, %33, %34, %35}, %36, p, 1, 1, %38;\n}\n"
    : "+f"(d[0]), "+f"(d[1]), "+f"(d[2]), "+f"(d[3]), "+f"(d[4]), "+f"(d[5]), "+f"(d[6]), "+f"(d[7]), "+f"(d[8]), "+f"(d[9]), "+f"(d[10]), "+f"(d[11]), "+f"(d[12]), "+f"(d[13]), "+f"(d[14]), "+f"(d[15]), "+f"(d[16]), "+f"(d[17]), "+f"(d[18]), "+f"(d[19]), "+f"(d[20]), "+f"(d[21]), "+f"(d[22]), "+f"(d[23]), "+f"(d[24]), "+f"(d[25]), "+f"(d[26]), "+f"(d[27]), "+f"(d[28]), "+f"(d[29]), "+f"(d[30]), "+f"(d[31])
    : "r"(a0), "r"(a1), "r"(a2), "r"(a3), "l"(db), "r"(scale_d), "n"(TB));
}
template <int TB, int TA = 0>
__device__ __forceinline__ void wgmma_ss_n128(float (&d)[64], uint64_t da, uint64_t db, int scale_d) {
  asm volatile("{\n.reg .pred p;\nsetp.ne.b32 p, %66, 0;\n"
    "wgmma.mma_async.sync.aligned.m64n128k16.f32.bf16.bf16 {%0, %1, %2, %3, %4, %5, %6, %7, %8, %9, %10, %11, %12, %13, %14, %15, %16, %17, %18, %19, %20, %21, %22, %23, %24, %25, %26, %27, %28, %29, %30, %31, %32, %33, %34, %35, %36, %37, %38, %39, %40, %41, %42, %43, %44, %45, %46, %47, %48, %49, %50, %51, %52, %53, %54, %55, %56, %57, %58, %59, %60, %61, %62, %63}, %64, %65, p, 1, 1, %67, %68;\n}\n"
    : "+f"(d[0]), "+f"(d[1]), "+f"(d[2]), "+f"(d[3]), "+f"(d[4]), "+f"(d[5]), "+f"(d[6]), "+f"(d[7]), "+f"(d[8]), "+f"(d[9]), "+f"(d[10]), "+f"(d[11]), "+f"(d[12]), "+f"(d[13]), "+f"(d[14]), "+f"(d[15]), "+f"(d[16]), "+f"(d[17]), "+f"(d[18]), "+f"(d[19]), "+f"(d[20]), "+f"(d[21]), "+f"(d[22]), "+f"(d[23]), "+f"(d[24]), "+f"(d[25]), "+f"(d[26]), "+f"(d[27]), "+f"(d[28]), "+f"(d[29]), "+f"(d[30]), "+f"(d[31]), "+f"(d[32]), "+f"(d[33]), "+f"(d[34]), "+f"(d[35]), "+f"(d[36]), "+f"(d[37]), "+f"(d[38]), "+f"(d[39]), "+f"(d[40]), "+f"(d[41]), "+f"(d[42]), "+f"(d[43]), "+f"(d[44]), "+f"(d[45]), "+f"(d[46]), "+f"(d[47]), "+f"(d[48]), "+f"(d[49]), "+f"(d[50]), "+f"(d[51]), "+f"(d[52]), "+f"(d[53]), "+f"(d[54]), "+f"(d[55]), "+f"(d[56]), "+f"(d[57]), "+f"(d[58]), "+f"(d[59]), "+f"(d[60]), "+f"(d[61]), "+f"(d[62]), "+f"(d[63])
    : "l"(da), "l"(db), "r"(scale_d), "n"(TA), "n"(TB));
}
template <int TB>
__device__ __forceinline__ void wgmma_rs_n128(float (&d)[64], uint32_t a0, uint32_t a1, uint32_t a2, uint32_t a3, uint64_t db, int scale_d) {
  asm volatile("{\n.reg .pred p;\nsetp.ne.b32 p, %69, 0;\n"
    "wgmma.mma_async.sync.aligned.m64n128k16.f32.bf16.bf16 {%0, %1, %2, %3, %4, %5, %6, %7, %8, %9, %10, %11, %12, %13, %14, %15, %16, %17, %18, %19, %20, %21, %22, %23, %24, %25, %26, %27, %28, %29, %30, %31, %32, %33, %34, %35, %36, %37, %38, %39, %40, %41, %42, %43, %44, %45, %46, %47, %48, %49, %50, %51, %52, %53, %54, %55, %56, %57, %58, %59, %60, %61, %62, %63}, {%64, %65, %66, %67}, %68, p, 1, 1, %70;\n}\n"
    : "+f"(d[0]), "+f"(d[1]), "+f"(d[2]), "+f"(d[3]), "+f"(d[4]), "+f"(d[5]), "+f"(d[6]), "+f"(d[7]), "+f"(d[8]), "+f"(d[9]), "+f"(d[10]), "+f"(d[11]), "+f"(d[12]), "+f"(d[13]), "+f"(d[14]), "+f"(d[15]), "+f"(d[16]), "+f"(d[17]), "+f"(d[18]), "+f"(d[19]), "+f"(d[20]), "+f"(d[21]), "+f"(d[22]), "+f"(d[23]), "+f"(d[24]), "+f"(d[25]), "+f"(d[26]), "+f"(d[27]), "+f"(d[28]), "+f"(d[29]), "+f"(d[30]), "+f"(d[31]), "+f"(d[32]), "+f"(d[33]), "+f"(d[34]), "+f"(d[35]), "+f"(d[36]), "+f"(d[37]), "+f"(d[38]), "+f"(d[39]), "+f"(d[40]), "+f"(d[41]), "+f"(d[42]), "+f"(d[43]), "+f"(d[44]), "+f"(d[45]), "+f"(d[46]), "+f"(d[47]), "+f"(d[48]), "+f"(d[49]), "+f"(d[50]), "+f"(d[51]), "+f"(d[52]), "+f"(d[53]), "+f"(d[54]), "+f"(d[55]), "+f"(d[56]), "+f"(d[57]), "+f"(d[58]), "+f"(d[59]), "+f"(d[60]), "+f"(d[61]), "+f"(d[62]), "+f"(d[63])
    : "r"(a0), "r"(a1), "r"(a2), "r"(a3), "l"(db), "r"(scale_d), "n"(TB));
}
template <int TB, int TA = 0>
__device__ __forceinline__ void wgmma_ss_n160(float (&d)[80], uint64_t da, uint64_t db, int scale_d) {
  asm volatile("{\n.reg .pred p;\nsetp.ne.b32 p, %82, 0;\n"
    "wgmma.mma_async.sync.aligned.m64n160k16.f32.bf16.bf16 {%0, %1, %2, %3, %4, %5, %6, %7, %8, %9, %10, %11, %12, %13, %14, %15, %16, %17, %18, %19, %20, %21, %22, %23, %24, %25, %26, %27, %28, %29, %30, %31, %32, %33, %34, %35, %36, %37, %38, %39, %40, %41, %42, %43, %44, %45, %46, %47, %48, %49, %50, %51, %52, %53, %54, %55, %56, %57, %58, %59, %60, %61, %62, %63, %64, %65, %66, %67, %68, %69, %70, %71, %72, %73, %74, %75, %76, %77, %78, %79}, %80, %81, p, 1, 1, %83, %84;\n}\n"
    : "+f"(d[0]), "+f"(d[1]), "+f"(d[2]), "+f"(d[3]), "+f"(d[4]), "+f"(d[5]), "+f"(d[6]), "+f"(d[7]), "+f"(d[8]), "+f"(d[9]), "+f"(d[10]), "+f"(d[11]), "+f"(d[12]), "+f"(d[13]), "+f"(d[14]), "+f"(d[15]), "+f"(d[16]), "+f"(d[17]), "+f"(d[18]), "+f"(d[19]), "+f"(d[20]), "+f"(d[21]), "+f"(d[22]), "+f"(d[23]), "+f"(d[24]), "+f"(d[25]), "+f"(d[26]), "+f"(d[27]), "+f"(d[28]), "+f"(d[29]), "+f"(d[30]), "+f"(d[31]), "+f"(d[32]), "+f"(d[33]), "+f"(d[34]), "+f"(d[35]), "+f"(d[36]), "+f"(d[37]), "+f"(d[38]), "+f"(d[39]), "+f"(d[40]), "+f"(d[41]), "+f"(d[42]), "+f"(d[43]), "+f"(d[44]), "+f"(d[45]), "+f"(d[46]), "+f"(d[47]), "+f"(d[48]), "+f"(d[49]), "+f"(d[50]), "+f"(d[51]), "+f"(d[52]), "+f"(d[53]), "+f"(d[54]), "+f"(d[55]), "+f"(d[56]), "+f"(d[57]), "+f"(d[58]), "+f"(d[59]), "+f"(d[60]), "+f"(d[61]), "+f"(d[62]), "+f"(d[63]), "+f"(d[64]), "+f"(d[65]), "+f"(d[66]), "+f"(d[67]), "+f"(d[68]), "+f"(d[69]), "+f"(d[70]), "+f"(d[71]), "+f"(d[72]), "+f"(d[73]), "+f"(d[74]), "+f"(d[75]), "+f"(d[76]), "+f"(d[77]), "+f"(d[78]), "+f"(d[79])
    : "l"(da), "l"(db), "r"(scale_d), "n"(TA), "n"(TB));
}
template <int TB>
__device__ __forceinline__ void wgmma_rs_n160(float (&d)[80], uint32_t a0, uint32_t a1, uint32_t a2, uint32_t a3, uint64_t db, int scale_d) {
  asm volatile("{\n.reg .pred p;\nsetp.ne.b32 p, %85, 0;\n"
    "wgmma.mma_async.sync.aligned.m64n160k16.f32.bf16.bf16 {%0, %1, %2, %3, %4, %5, %6, %7, %8, %9, %10, %11, %12, %13, %14, %15, %16, %17, %18, %19, %20, %21, %22, %23, %24, %25, %26, %27, %28, %29, %30, %31, %32, %33, %34, %35, %36, %37, %38, %39, %40, %41, %42, %43, %44, %45, %46, %47, %48, %49, %50, %51, %52, %53, %54, %55, %56, %57, %58, %59, %60, %61, %62, %63, %64, %65, %66, %67, %68, %69, %70, %71, %72, %73, %74, %75, %76, %77, %78, %79}, {%80, %81, %82, %83}, %84, p, 1, 1, %86;\n}\n"
    : "+f"(d[0]), "+f"(d[1]), "+f"(d[2]), "+f"(d[3]), "+f"(d[4]), "+f"(d[5]), "+f"(d[6]), "+f"(d[7]), "+f"(d[8]), "+f"(d[9]), "+f"(d[10]), "+f"(d[11]), "+f"(d[12]), "+f"(d[13]), "+f"(d[14]), "+f"(d[15]), "+f"(d[16]), "+f"(d[17]), "+f"(d[18]), "+f"(d[19]), "+f"(d[20]), "+f"(d[21]), "+f"(d[22]), "+f"(d[23]), "+f"(d[24]), "+f"(d[25]), "+f"(d[26]), "+f"(d[27]), "+f"(d[28]), "+f"(d[29]), "+f"(d[30]), "+f"(d[31]), "+f"(d[32]), "+f"(d[33]), "+f"(d[34]), "+f"(d[35]), "+f"(d[36]), "+f"(d[37]), "+f"(d[38]), "+f"(d[39]), "+f"(d[40]), "+f"(d[41]), "+f"(d[42]), "+f"(d[43]), "+f"(d[44]), "+f"(d[45]), "+f"(d[46]), "+f"(d[47]), "+f"(d[48]), "+f"(d[49]), "+f"(d[50]), "+f"(d[51]), "+f"(d[52]), "+f"(d[53]), "+f"(d[54]), "+f"(d[55]), "+f"(d[56]), "+f"(d[57]), "+f"(d[58]), "+f"(d[59]), "+f"(d[60]), "+f"(d[61]), "+f"(d[62]), "+f"(d[63]), "+f"(d[64]), "+f"(d[65]), "+f"(d[66]), "+f"(d[67]), "+f"(d[68]), "+f"(d[69]), "+f"(d[70]), "+f"(d[71]), "+f"(d[72]), "+f"(d[73]), "+f"(d[74]), "+f"(d[75]), "+f"(d[76]), "+f"(d[77]), "+f"(d[78]), "+f"(d[79])
    : "r"(a0), "r"(a1), "r"(a2), "r"(a3), "l"(db), "r"(scale_d), "n"(TB));
}
template <int TB, int TA = 0>
__device__ __forceinline__ void wgmma_ss_n192(float (&d)[96], uint64_t da, uint64_t db, int scale_d) {
  asm volatile("{\n.reg .pred p;\nsetp.ne.b32 p, %98, 0;\n"
    "wgmma.mma_async.sync.aligned.m64n192k16.f32.bf16.bf16 {%0, %1, %2, %3, %4, %5, %6, %7, %8, %9, %10, %11, %12, %13, %14, %15, %16, %17, %18, %19, %20, %21, %22, %23, %24, %25, %26, %27, %28, %29, %30, %31, %32, %33, %34, %35, %36, %37, %38, %39, %40, %41, %42, %43, %44, %45, %46, %47, %48, %49, %50, %51, %52, %53, %54, %55, %56, %57, %58, %59, %60, %61, %62, %63, %64, %65, %66, %67, %68, %69, %70, %71, %72, %73, %74, %75, %76, %77, %78, %79, %80, %81, %82, %83, %84, %85, %86, %87, %88, %89, %90, %91, %92, %93, %94, %95}, %96, %97, p, 1, 1, %99, %100;\n}\n"
    : "+f"(d[0]), "+f"(d[1]), "+f"(d[2]), "+f"(d[3]), "+f"(d[4]), "+f"(d[5]), "+f"(d[6]), "+f"(d[7]), "+f"(d[8]), "+f"(d[9]), "+f"(d[10]), "+f"(d[11]), "+f"(d[12]), "+f"(d[13]), "+f"(d[14]), "+f"(d[15]), "+f"(d[16]), "+f"(d[17]), "+f"(d[18]), "+f"(d[19]), "+f"(d[20]), "+f"(d[21]), "+f"(d[22]), "+f"(d[23]), "+f"(d[24]), "+f"(d[25]), "+f"(d[26]), "+f"(d[27]), "+f"(d[28]), "+f"(d[29]), "+f"(d[30]), "+f"(d[31]), "+f"(d[32]), "+f"(d[33]), "+f"(d[34]), "+f"(d[35]), "+f"(d[36]), "+f"(d[37]), "+f"(d[38]), "+f"(d[39]), "+f"(d[40]), "+f"(d[41]), "+f"(d[42]), "+f"(d[43]), "+f"(d[44]), "+f"(d[45]), "+f"(d[46]), "+f"(d[47]), "+f"(d[48]), "+f"(d[49]), "+f"(d[50]), "+f"(d[51]), "+f"(d[52]), "+f"(d[53]), "+f"(d[54]), "+f"(d[55]), "+f"(d[56]), "+f"(d[57]), "+f"(d[58]), "+f"(d[59]), "+f"(d[60]), "+f"(d[61]), "+f"(d[62]), "+f"(d[63]), "+f"(d[64]), "+f"(d[65]), "+f"(d[66]), "+f"(d[67]), "+f"(d[68]), "+f"(d[69]), "+f"(d[70]), "+f"(d[71]), "+f"(d[72]), "+f"(d[73]), "+f"(d[74]), "+f"(d[75]), "+f"(d[76]), "+f"(d[77]), "+f"(d[78]), "+f"(d[79]), "+f"(d[80]), "+f"(d[81]), "+f"(d[82]), "+f"(d[83]), "+f"(d[84]), "+f"(d[85]), "+f"(d[86]), "+f"(d[87]), "+f"(d[88]), "+f"(d[89]), "+f"(d[90]), "+f"(d[91]), "+f"(d[92]), "+f"(d[93]), "+f"(d[94]), "+f"(d[95])
    : "l"(da), "l"(db), "r"(scale_d), "n"(TA), "n"(TB));
}
template <int TB>
__device__ __forceinline__ void wgmma_rs_n192(float (&d)[96], uint32_t a0, uint32_t a1, uint32_t a2, uint32_t a3, uint64_t db, int scale_d) {
  asm volatile("{\n.reg .pred p;\nsetp.ne.b32 p, %101, 0;\n"
    "wgmma.mma_async.sync.aligned.m64n192k16.f32.bf16.bf16 {%0, %1, %2, %3, %4, %5, %6, %7, %8, %9, %10, %11, %12, %13, %14, %15, %16, %17, %18, %19, %20, %21, %22, %23, %24, %25, %26, %27, %28, %29, %30, %31, %32, %33, %34, %35, %36, %37, %38, %39, %40, %41, %42, %43, %44, %45, %46, %47, %48, %49, %50, %51, %52, %53, %54, %55, %56, %57, %58, %59, %60, %61, %62, %63, %64, %65, %66, %67, %68, %69, %70, %71, %72, %73, %74, %75, %76, %77, %78, %79, %80, %81, %82, %83, %84, %85, %86, %87, %88, %89, %90, %91, %92, %93, %94, %95}, {%96, %97, %98, %99}, %100, p, 1, 1, %102;\n}\n"
    : "+f"(d[0]), "+f"(d[1]), "+f"(d[2]), "+f"(d[3]), "+f"(d[4]), "+f"(d[5]), "+f"(d[6]), "+f"(d[7]), "+f"(d[8]), "+f"(d[9]), "+f"(d[10]), "+f"(d[11]), "+f"(d[12]), "+f"(d[13]), "+f"(d[14]), "+f"(d[15]), "+f"(d[16]), "+f"(d[17]), "+f"(d[18]), "+f"(d[19]), "+f"(d[20]), "+f"(d[21]), "+f"(d[22]), "+f"(d[23]), "+f"(d[24]), "+f"(d[25]), "+f"(d[26]), "+f"(d[27]), "+f"(d[28]), "+f"(d[29]), "+f"(d[30]), "+f"(d[31]), "+f"(d[32]), "+f"(d[33]), "+f"(d[34]), "+f"(d[35]), "+f"(d[36]), "+f"(d[37]), "+f"(d[38]), "+f"(d[39]), "+f"(d[40]), "+f"(d[41]), "+f"(d[42]), "+f"(d[43]), "+f"(d[44]), "+f"(d[45]), "+f"(d[46]), "+f"(d[47]), "+f"(d[48]), "+f"(d[49]), "+f"(d[50]), "+f"(d[51]), "+f"(d[52]), "+f"(d[53]), "+f"(d[54]), "+f"(d[55]), "+f"(d[56]), "+f"(d[57]), "+f"(d[58]), "+f"(d[59]), "+f"(d[60]), "+f"(d[61]), "+f"(d[62]), "+f"(d[63]), "+f"(d[64]), "+f"(d[65]), "+f"(d[66]), "+f"(d[67]), "+f"(d[68]), "+f"(d[69]), "+f"(d[70]), "+f"(d[71]), "+f"(d[72]), "+f"(d[73]), "+f"(d[74]), "+f"(d[75]), "+f"(d[76]), "+f"(d[77]), "+f"(d[78]), "+f"(d[79]), "+f"(d[80]), "+f"(d[81]), "+f"(d[82]), "+f"(d[83]), "+f"(d[84]), "+f"(d[85]), "+f"(d[86]), "+f"(d[87]), "+f"(d[88]), "+f"(d[89]), "+f"(d[90]), "+f"(d[91]), "+f"(d[92]), "+f"(d[93]), "+f"(d[94]), "+f"(d[95])
    : "r"(a0), "r"(a1), "r"(a2), "r"(a3), "l"(db), "r"(scale_d), "n"(TB));
}

__device__ __forceinline__ uint32_t smem_u32(const void* p) { return (uint32_t)__cvta_generic_to_shared(p); }
__device__ __forceinline__ void wg_fence() { asm volatile("wgmma.fence.sync.aligned;" ::: "memory"); }
__device__ __forceinline__ void wg_commit() { asm volatile("wgmma.commit_group.sync.aligned;" ::: "memory"); }
template <int N> __device__ __forceinline__ void wg_wait() { asm volatile("wgmma.wait_group.sync.aligned %0;" ::"n"(N) : "memory"); }
__device__ __forceinline__ void sched_fence(uint32_t& keep, bool never) {
  asm volatile("{\n.reg .pred p;\nsetp.ne.b32 p, %1, 0;\n@p mov.u32 %0, %%clock;\n}\n" : "+r"(keep) : "r"((int)never) : "memory");
}
template <int N> __device__ __forceinline__ void fence_regs(float (&r)[N]) {
#pragma unroll
  for (int i = 0; i < N; i++) asm volatile("" : "+f"(r[i])::"memory");
}
template <int N> __device__ __forceinline__ void undefine(float (&r)[N]) {
#pragma unroll
  for (int i = 0; i < N; i++) asm volatile("" : "=f"(r[i]));
}
template <int N> __device__ __forceinline__ void fence_regs(uint32_t (&r)[N]) {
#pragma unroll
  for (int i = 0; i < N; i++) asm volatile("" : "+r"(r[i])::"memory");
}
__device__ __forceinline__ uint64_t mk_desc(uint32_t a16, uint32_t lbo, uint32_t sbo, uint32_t swz) {
  uint64_t d;
  asm("mov.b64 %0, {%1, %2};" : "=l"(d) : "r"(a16 + ((lbo >> 4) << 16)), "r"((sbo >> 4) | (swz << 30)));
  return d;
}
__device__ __forceinline__ void mbar_init(uint32_t bar, uint32_t cnt) {
  asm volatile("mbarrier.init.shared::cta.b64 [%0], %1;" ::"r"(bar), "r"(cnt) : "memory");
}
__device__ __forceinline__ void mbar_expect(uint32_t bar, uint32_t tx) {
  asm volatile("mbarrier.arrive.expect_tx.shared::cta.b64 _, [%0], %1;" ::"r"(bar), "r"(tx) : "memory");
}
__device__ __forceinline__ bool mbar_test(uint32_t bar, uint32_t ph) {
  uint32_t ok;
  asm volatile("{\n.reg .pred p;\nmbarrier.test_wait.parity.shared::cta.b64 p, [%1], %2;\nselp.u32 %0, 1, 0, p;\n}\n"
               : "=r"(ok) : "r"(bar), "r"(ph) : "memory");
  return ok;
}
__device__ __forceinline__ bool mbar_try(uint32_t bar, uint32_t ph, uint32_t ns) {
  uint32_t ok;
  asm volatile("{\n.reg .pred p;\nmbarrier.try_wait.parity.shared::cta.b64 p, [%1], %2, %3;\nselp.u32 %0, 1, 0, p;\n}\n"
               : "=r"(ok) : "r"(bar), "r"(ph), "r"(ns) : "memory");
  return ok;
}
__device__ __forceinline__ void mbar_wait(uint32_t bar, uint32_t ph) {
  asm volatile("{\n.reg .pred p;\n.reg .u32 n;\nmov.u32 n, 0;\n"
               "LOOP:\nmbarrier.try_wait.parity.shared::cta.b64 p, [%0], %1;\n@p bra DONE;\n"
               "add.u32 n, n, 1;\nsetp.lt.u32 p, n, 0x1000000;\n@p bra LOOP;\ntrap;\n"
               "DONE:\n}\n" ::"r"(bar), "r"(ph) : "memory");
}
__device__ __forceinline__ void mbar_wait_long(uint32_t bar) {
  asm volatile("{\n.reg .pred p;\n.reg .u32 n;\nmov.u32 n, 0;\n"
               "LOOP:\nmbarrier.try_wait.parity.shared::cta.b64 p, [%0], 0, 20000;\n@p bra DONE;\n"
               "add.u32 n, n, 1;\nsetp.lt.u32 p, n, 0x100000;\n@p bra LOOP;\ntrap;\n"
               "DONE:\n}\n" ::"r"(bar) : "memory");
}
__device__ __forceinline__ void mbar_arrive_cluster_if(bool on, uint32_t addr) {
  asm volatile("{\n.reg .pred p;\nsetp.ne.b32 p, %1, 0;\n@p mbarrier.arrive.shared::cluster.b64 _, [%0];\n}\n" ::"r"(addr), "r"((int)on) : "memory");
}
__device__ __forceinline__ void mbar_arrive_cluster_n(uint32_t n, uint32_t addr) {
  asm volatile("{\n.reg .pred p;\nsetp.ne.b32 p, %1, 0;\n@p mbarrier.arrive.shared::cluster.b64 _, [%0], %1;\n}\n" ::"r"(addr), "r"(n) : "memory");
}
__device__ __forceinline__ void tma2d(uint32_t dst, const CUtensorMap* m, uint32_t bar, int c0, int c1) {
  asm volatile("cp.async.bulk.tensor.2d.shared::cluster.global.mbarrier::complete_tx::bytes [%0], [%1, {%3, %4}], [%2];"
               ::"r"(dst), "l"(m), "r"(bar), "r"(c0), "r"(c1) : "memory");
}
__device__ __forceinline__ void tma3d(uint32_t dst, const CUtensorMap* m, uint32_t bar, int c0, int c1, int c2) {
  asm volatile("cp.async.bulk.tensor.3d.shared::cluster.global.mbarrier::complete_tx::bytes [%0], [%1, {%3, %4, %5}], [%2];"
               ::"r"(dst), "l"(m), "r"(bar), "r"(c0), "r"(c1), "r"(c2) : "memory");
}
__device__ __forceinline__ void tma2d_hint(uint32_t dst, const CUtensorMap* m, uint32_t bar, int c0, int c1, uint64_t pol) {
  asm volatile("cp.async.bulk.tensor.2d.shared::cluster.global.mbarrier::complete_tx::bytes.L2::cache_hint [%0], [%1, {%3, %4}], [%2], %5;"
               ::"r"(dst), "l"(m), "r"(bar), "r"(c0), "r"(c1), "l"(pol) : "memory");
}
__device__ __forceinline__ void tma3d_mc_hint(uint32_t dst, const CUtensorMap* m, uint32_t bar, int c1, int c2, uint64_t pol) {
  asm volatile("cp.async.bulk.tensor.3d.shared::cluster.global.mbarrier::complete_tx::bytes.multicast::cluster.L2::cache_hint"
               " [%0], [%1, {%3, %4, %5}], [%2], %6, %7;"
               ::"r"(dst), "l"(m), "r"(bar), "r"(0), "r"(c1), "r"(c2), "h"((uint16_t)3), "l"(pol) : "memory");
}
__device__ __forceinline__ void tma5d_mc_hint(uint32_t dst, const CUtensorMap* m, uint32_t bar, int c2, int c4, uint64_t pol) {
  asm volatile("cp.async.bulk.tensor.5d.shared::cluster.global.mbarrier::complete_tx::bytes.multicast::cluster.L2::cache_hint"
               " [%0], [%1, {%3, %3, %4, %3, %5}], [%2], %6, %7;"
               ::"r"(dst), "l"(m), "r"(bar), "r"(0), "r"(c2), "r"(c4), "h"((uint16_t)3), "l"(pol) : "memory");
}
__device__ __forceinline__ void tma3d_store(const CUtensorMap* m, uint32_t src, int c0, int c1, int c2) {
  asm volatile("cp.async.bulk.tensor.3d.global.shared::cta.bulk_group [%0, {%2, %3, %4}], [%1];"
               ::"l"(m), "r"(src), "r"(c0), "r"(c1), "r"(c2) : "memory");
}
__device__ __forceinline__ void bar_sync(int id, int n) { asm volatile("bar.sync %0, %1;" ::"r"(id), "r"(n) : "memory"); }
__device__ __forceinline__ uint32_t pack_bf16(float lo, float hi) {
  uint32_t r;
  asm("cvt.rn.bf16x2.f32 %0, %1, %2;" : "=r"(r) : "f"(hi), "f"(lo));
  return r;
}
__device__ __forceinline__ float ex2(float x) {
  float y;
  asm("ex2.approx.ftz.f32 %0, %1;" : "=f"(y) : "f"(x));
  return y;
}
__device__ __forceinline__ float rcp(float x) {
  float y;
  asm("rcp.approx.ftz.f32 %0, %1;" : "=f"(y) : "f"(x));
  return y;
}
__device__ __forceinline__ void stsm4(uint32_t addr, uint32_t a, uint32_t b, uint32_t c, uint32_t d) {
  asm volatile("stmatrix.sync.aligned.m8n8.x4.shared.b16 [%0], {%1, %2, %3, %4};" ::"r"(addr), "r"(a), "r"(b), "r"(c), "r"(d) : "memory");
}

__device__ __forceinline__ void tma4d_mc_hint(uint32_t dst, const CUtensorMap* m, uint32_t bar, int c3, uint64_t pol) {
  asm volatile("cp.async.bulk.tensor.4d.shared::cluster.global.mbarrier::complete_tx::bytes.multicast::cluster.L2::cache_hint"
               " [%0], [%1, {%3, %3, %3, %4}], [%2], %5, %6;"
               ::"r"(dst), "l"(m), "r"(bar), "r"(0), "r"(c3), "h"((uint16_t)3), "l"(pol) : "memory");
}
__device__ __forceinline__ void bulk_load_hint(uint32_t dst, const void* src, uint32_t bytes, uint32_t bar, uint64_t pol) {
  asm volatile("cp.async.bulk.shared::cluster.global.mbarrier::complete_tx::bytes.L2::cache_hint [%0], [%1], %2, [%3], %4;"
               ::"r"(dst), "l"(src), "r"(bytes), "r"(bar), "l"(pol) : "memory");
}
__device__ __forceinline__ void stg2_if(bool on, void* p, uint32_t a, uint32_t b, uint32_t c, uint32_t d, uint32_t e, uint32_t f,
                                        uint32_t g, uint32_t h, uint64_t pol) {
  asm volatile("{\n.reg .pred p;\nsetp.ne.b32 p, %10, 0;\n"
               "@p st.global.L2::cache_hint.v4.b32 [%0], {%1, %2, %3, %4}, %9;\n"
               "@p st.global.L2::cache_hint.v4.b32 [%0 + 512], {%5, %6, %7, %8}, %9;\n}\n"
               ::"l"(p), "r"(a), "r"(b), "r"(c), "r"(d), "r"(e), "r"(f), "r"(g), "r"(h), "l"(pol), "r"((int)on) : "memory");
}
__device__ __forceinline__ uint64_t evict_first() {
  uint64_t p;
  asm("createpolicy.fractional.L2::evict_first.b64 %0, 1.0;" : "=l"(p));
  return p;
}
__device__ __forceinline__ uint64_t no_hint() {
  uint64_t p;
  asm("createpolicy.cvt.L2.b64 %0, %1;" : "=l"(p) : "l"(static_cast<uint64_t>(cuda::access_property{})));
  return p;
}
__device__ __forceinline__ bool elect() {
  uint32_t ok;
  asm volatile("{\n.reg .pred p;\nelect.sync _|p, 0xffffffff;\nselp.u32 %0, 1, 0, p;\n}\n" : "=r"(ok));
  return ok;
}
__device__ __forceinline__ void mbar_arrive(uint32_t bar) {
  asm volatile("mbarrier.arrive.shared::cta.b64 _, [%0];" ::"r"(bar) : "memory");
}
__device__ __forceinline__ void mbar_arrive_if(bool on, uint32_t bar) {
  asm volatile("{\n.reg .pred p;\nsetp.ne.b32 p, %1, 0;\n@p mbarrier.arrive.shared::cta.b64 _, [%0];\n}\n" ::"r"(bar), "r"((int)on) : "memory");
}
__device__ __forceinline__ void lds2_if(bool on, uint32_t p, uint32_t (&t)[8]) {
  asm volatile("{\n.reg .pred p;\nsetp.ne.b32 p, %9, 0;\n@p ld.shared.v4.b32 {%0, %1, %2, %3}, [%8];\n@p ld.shared.v4.b32 {%4, %5, %6, %7}, [%8 + 512];\n}\n"
               : "+r"(t[0]), "+r"(t[1]), "+r"(t[2]), "+r"(t[3]), "+r"(t[4]), "+r"(t[5]), "+r"(t[6]), "+r"(t[7]) : "r"(p), "r"((int)on) : "memory");
}
__device__ __forceinline__ void lds128(uint32_t p, uint32_t& a, uint32_t& b, uint32_t& c, uint32_t& d) {
  asm volatile("ld.shared.v4.b32 {%0, %1, %2, %3}, [%4];" : "=r"(a), "=r"(b), "=r"(c), "=r"(d) : "r"(p) : "memory");
}
template <class T> __device__ __forceinline__ T* ptr_add(T* base, uint32_t bytes) {
  T* r;
  asm("{\n.reg .u32 lo, hi;\nmov.b64 {lo, hi}, %1;\nadd.cc.u32 lo, lo, %2;\naddc.u32 hi, hi, 0;\nmov.b64 %0, {lo, hi};\n}\n" : "=l"(r) : "l"(base), "r"(bytes));
  return r;
}
__device__ __forceinline__ uint32_t lds32(uint32_t p) {
  uint32_t v;
  asm volatile("ld.volatile.shared.u32 %0, [%1];" : "=r"(v) : "r"(p) : "memory");
  return v;
}
__device__ __forceinline__ uint32_t flag_get(const unsigned int* p) {
  uint32_t v;
  asm volatile("ld.acquire.gpu.global.u32 %0, [%1];" : "=r"(v) : "l"(p) : "memory");
  return v;
}
__device__ __forceinline__ uint32_t wait_word(uint32_t p, uint32_t target) {
  uint32_t v;
  asm volatile("{\n.reg .pred p;\n.reg .u32 n;\nmov.u32 n, 0;\n"
               "LOOP:\nld.acquire.cta.shared.u32 %0, [%1];\nsetp.ge.u32 p, %0, %2;\n@p bra DONE;\n"
               "nanosleep.u32 %3;\nadd.u32 n, n, 1;\nsetp.lt.u32 p, n, 0x400000;\n@p bra LOOP;\ntrap;\n"
               "DONE:\n}\n" : "=r"(v) : "r"(p), "r"(target), "n"(400) : "memory");
  return v;
}
__device__ __forceinline__ void flag_set(unsigned int* p, uint32_t v) {
  asm volatile("st.release.gpu.global.u32 [%0], %1;" ::"l"(p), "r"(v) : "memory");
}
__device__ __forceinline__ void flag_dec(unsigned int* p) {
  asm volatile("red.relaxed.gpu.global.add.u32 [%0], 0xffffffff;" ::"l"(p) : "memory");
}

struct Cursor {
  uint32_t n;
  __device__ __forceinline__ uint32_t off() const { return n & (8 * NBAR - 8); }
  __device__ __forceinline__ uint32_t ph() const { return (n / (8 * NBAR)) & 1; }
  __device__ __forceinline__ void next() { n += 8; }
};

constexpr float kScaleLog2 = 0.07216878364870322f * 1.4426950408889634f;
constexpr float kSumLimit = 1048576.0f;

__global__ void __cluster_dims__(2, 1, 1) __launch_bounds__(384, 1)
fused_kernel(const __grid_constant__ Params P) {
  extern __shared__ uint8_t smem_raw[];
  const uint32_t sbase = (smem_u32(smem_raw) + 1023) & ~1023u;
  const uint32_t full0 = sbase + RING, empty0 = full0 + 8 * NBAR, odone0 = empty0 + 8 * NBAR, ev0 = odone0 + 8 * MAX_OPS;
  const uint32_t progress = ev0 + 8 * MAX_EV, jobw = progress + 4;
  const uint32_t rank = blockIdx.x & 1;
  const int role = blockIdx.x >> 1;
  const int wid = __shfl_sync(0xffffffffu, (int)(threadIdx.x >> 5), 0);
  const int wg = wid >> 2;

  if (wid < 8) {
    if (elect()) {
#pragma unroll
      for (int j = 0; j < 16; j++) {
        const int i = EARLY + 16 * wid + j;
        if (i < 2 * NBAR + MAX_OPS + MAX_EV) mbar_init(full0 + 8 * i, i < NBAR ? 1 : i < 2 * NBAR ? 16 : i < 2 * NBAR + MAX_OPS ? 8 : 1);
      }
      if (wid == 7) asm volatile("st.shared.v2.u32 [%0], {0, 0};\nfence.acq_rel.cta;" ::"r"(progress) : "memory");
      asm volatile("fence.mbarrier_init.release.cluster;" ::: "memory");
    }
  } else if (wid > 8) {
    const uint32_t g = blockIdx.x * 96 + threadIdx.x - 288, w = g - 2048;
    if (g < 4096) asm volatile("prefetch.global.L2 [%0];" ::"l"(g < 2048 ? P.xw[0] + g * (kD * 2) : P.xw[1] + (w >> 5) * (kHD * 2) + (w & 31) * 128));
  } else {
    const uint32_t op0 = P.first[role];
    if (elect()) {
#pragma unroll
      for (int k = 0; k < EARLY; k++) mbar_init(full0 + 8 * k, 1);
      asm volatile("fence.mbarrier_init.release.cluster;" ::: "memory");
      const int blk = (op0 >> 10) & 1;
      if ((op0 & 3) == OP_Q) {
#pragma unroll
        for (int k = 0; k < EARLY; k++) {
          mbar_expect(full0 + 8 * k, SZ_Q);
          tma2d(sbase + k * SZ_Q, &P.x[blk], full0 + 8 * k, 64 * k, ((op0 >> 7) & 7) * kSq + rank * 128);
          tma3d(sbase + k * SZ_Q + 16384, &P.wq[blk], full0 + 8 * k, 0, 64 * k, 3 * ((op0 >> 2) & 31));
          tma3d(sbase + k * SZ_Q + 28672, &P.wq[blk], full0 + 8 * k, 0, 64 * k + 32, 3 * ((op0 >> 2) & 31));
        }
      }
      asm volatile("prefetch.tensormap [%0];\nprefetch.tensormap [%1];" ::"l"(&P.k[blk]), "l"(&P.v[blk]) : "memory");
    }
  }
  __syncwarp();
  asm volatile("barrier.cluster.arrive.relaxed.aligned;\nbarrier.cluster.wait.aligned;" ::: "memory");

  if (wg < 2) {
    asm volatile("setmaxnreg.inc.sync.aligned.u32 240;");
    const uint32_t* prog = P.prog[role].c;
    const int wid = __shfl_sync(0xffffffffu, (int)(threadIdx.x >> 5), 1), wg = wid >> 2;
    const int lane = threadIdx.x & 31, warp = wid & 3;
    uint32_t empty_rem;
    asm volatile("mapa.shared::cluster.u32 %0, %1, %2;" : "=r"(empty_rem) : "r"(empty0), "r"(lane & 1));
    uint32_t keep = (threadIdx.x & 127) < 2 ? 4 : 0;
    auto release = [&](int slot) { mbar_arrive_cluster_n(keep, empty_rem + slot); };
    auto release_warp = [&](int slot, bool on = true) { mbar_arrive_cluster_if(lane < 2 && on, empty_rem + slot); };
    Cursor r{0};
    const uint32_t ring16 = (sbase & 0x3FFFF) >> 4;
    uint32_t cur = ring16;
    bool rdy0 = false, rdy1 = false;
    auto probe1 = [&]() { rdy0 = mbar_test(full0 + r.off(), r.ph()); };
    auto probe2 = [&]() {
      Cursor n = r;
      rdy0 = mbar_test(full0 + n.off(), n.ph());
      n.next();
      rdy1 = mbar_test(full0 + n.off(), n.ph());
    };
    auto advance = [&](uint32_t bytes, uint32_t& addr) {
      const int bi = r.off();
      r.next();
      if (cur > ring16 + ((RING - bytes) >> 4)) cur = ring16;
      addr = cur;
      cur += bytes >> 4;
      return bi;
    };
    auto take = [&](bool rdy, uint32_t bytes, uint32_t& addr) {
      if (__builtin_expect(!__all_sync(0xffffffffu, rdy), 0)) mbar_wait(full0 + r.off(), r.ph());
      return advance(bytes, addr);
    };
    const bool never = P.dbg == 0xffffffffu;
    uint32_t q[48];
#pragma unroll
    for (int i = 0; i < 48; i++) q[i] = 0;
    const int row = wg * 64 + warp * 16 + (lane >> 2);
    const int img0 = row * 4 + ((lane & 3) ^ ((row >> 1) & 3));
    uint4* pend = nullptr;
    bool pend_any = false;
    const uint64_t spol = evict_first();
    int pc = 0;
    auto slab = [&](int c, int i0) {
#pragma unroll
      for (int i = i0; i < 6; i++)
        stg2_if(c == i, pend + i * 512, q[8 * i], q[8 * i + 1], q[8 * i + 2], q[8 * i + 3],
                q[8 * i + 4], q[8 * i + 5], q[8 * i + 6], q[8 * i + 7], spol);
    };
    auto drain = [&](int c) {
      if (!pend_any || c >= 6) return;
      slab(c, 0);
      if (c == 5) {
        __syncwarp();
        mbar_arrive_if(lane == 0, odone0 - 8 + 8 * pc);
      }
    };

    for (;; pc++) {
      uint32_t op = prog[pc];
      const int type = op & 3;
      auto enter = [&]() {
        r.n = (op >> 12) & 248; cur = ring16 + (((op >> 20) & 63) << 8);
      };
      enter();
      pend_any = op & C_PEND;
      uint32_t job = 0;
      if ((op & (3 | C_WIDE)) == OP_O) job = __shfl_sync(0xffffffffu, wait_word(jobw, 1), 0);
      if (type == OP_END || job == OP_O) {
#pragma unroll 1
        for (int c = 0; c < 6; c++) drain(c);
        asm volatile("barrier.cluster.arrive.relaxed;" ::: "memory");
        break;
      }
      {
        float s[32], o[96];
        uint32_t ad0;
        int bi0, sk1;
        uint32_t pa[16], pb[16];
        float mc0, mc1, l0, l1;
        bool shifted;
        uint32_t nop;
        auto expo = [&](float (&s)[32], uint32_t (&pout)[16], float& b0, float& b1, bool shift, auto mid) {
          float c0, c1;
#pragma unroll
          for (int i = 0; i < 8; i++) {
            const float e0 = ex2(shift ? s[4 * i] - mc0 : s[4 * i]), e1 = ex2(shift ? s[4 * i + 1] - mc0 : s[4 * i + 1]);
            const float e2 = ex2(shift ? s[4 * i + 2] - mc1 : s[4 * i + 2]), e3 = ex2(shift ? s[4 * i + 3] - mc1 : s[4 * i + 3]);
            if (i) { b0 += e0; c0 += e1; b1 += e2; c1 += e3; } else { b0 = e0; c0 = e1; b1 = e2; c1 = e3; }
            pout[2 * i] = pack_bf16(e0, e1); pout[2 * i + 1] = pack_bf16(e2, e3);
            if (i & 1) mid(i >> 1);
          }
          b0 += c0; b1 += c1;
        };
        auto rowmax = [&](float (&s)[32], float& m0, float& m1) {
          m0 = fmaxf(s[0], s[1]); m1 = fmaxf(s[2], s[3]);
#pragma unroll
          for (int i = 1; i < 8; i++) { m0 = fmaxf(m0, fmaxf(s[4 * i], s[4 * i + 1])); m1 = fmaxf(m1, fmaxf(s[4 * i + 2], s[4 * i + 3])); }
          m0 = fmaxf(m0, __shfl_xor_sync(0xffffffffu, m0, 1)); m1 = fmaxf(m1, __shfl_xor_sync(0xffffffffu, m1, 1));
          m0 = fmaxf(m0, __shfl_xor_sync(0xffffffffu, m0, 2)); m1 = fmaxf(m1, __shfl_xor_sync(0xffffffffu, m1, 2));
        };
        auto first = [&](float (&s)[32], int sk0, auto mid) {
          fence_regs(s);
          release(sk0);
          mc0 = 0.f; mc1 = 0.f;
          expo(s, pa, l0, l1, false, mid);
          shifted = __any_sync(0xffffffffu, !(fmaxf(l0, l1) <= kSumLimit && fminf(l0, l1) >= 1.f / kSumLimit));
          if (shifted) {
            rowmax(s, mc0, mc1);
            expo(s, pa, l0, l1, true, [](int) {});
          }
        };
        auto qk = [&](float (&s)[32], uint32_t ak, int k0 = 0, int k1 = 12) {
#pragma unroll
          for (int kk = k0; kk < k1; kk++)
            wgmma_rs_n64<0>(s, q[4 * kk], q[4 * kk + 1], q[4 * kk + 2], q[4 * kk + 3], mk_desc(ak, 16, KV_SBO, 1) + ((kk >> 2) * KV_CH + (kk & 3) * 2), kk != 0);
          if (k1 == 12) wg_commit();
        };
        auto pv = [&](uint32_t (&pin)[16], uint32_t av, int acc) {
#pragma unroll
          for (int kk = 0; kk < 4; kk++)
            wgmma_rs_n192<1>(o, pin[4 * kk], pin[4 * kk + 1], pin[4 * kk + 2], pin[4 * kk + 3], mk_desc(av, KV_CH * 16, KV_SBO, 1) + (kk * (KV_SBO / 8)), acc || (kk != 0));
          wg_commit();
        };
        auto finish = [&](uint32_t (&pout)[16], int sk, int sv) {
          probe1();
          wg_wait<1>();
          fence_regs(s);
          release(sk);
          float b0, b1;
#pragma unroll 1
          for (bool redo = false;; redo = true) {
            expo(s, pout, b0, b1, false, [](int) {});
            if (!__any_sync(0xffffffffu, !redo && (shifted || !(fmaxf(b0, b1) <= kSumLimit)))) break;
            shifted = true;
            rowmax(s, b0, b1);
            b0 = fmaxf(mc0, b0); b1 = fmaxf(mc1, b1);
            const float a0 = ex2(mc0 - b0), a1 = ex2(mc1 - b1);
            mc0 = b0; mc1 = b1;
            l0 *= a0; l1 *= a1;
            wg_wait<0>();
            fence_regs(o);
#pragma unroll
            for (int i = 0; i < 24; i++) { o[4 * i] *= a0; o[4 * i + 1] *= a0; o[4 * i + 2] *= a1; o[4 * i + 3] *= a1; }
#pragma unroll
            for (int i = 0; i < 32; i++) s[i] -= (i & 2) ? mc1 : mc0;
          }
          l0 += b0; l1 += b1;
          wg_wait<0>();
          fence_regs(o);
          release(sv);
        };
        auto step = [&](uint32_t (&pin)[16], uint32_t (&pout)[16]) {
          uint32_t ak, av;
          const int sk = take(rdy0, SZ_KV, ak), sv = advance(SZ_KV, av);
          wg_fence();
          qk(s, ak);
          pv(pin, av, 1);
          finish(pout, sk, sv);
        };
        auto unpark = [&]() {
          uint32_t ad, ak;
          const int bi = take(rdy0, SZ_PARK, ad);
#pragma unroll
          for (int i = 0; i < 12; i++) lds128(sbase + (ad - ring16 + img0) * 16 + (i >> 1) * 8192 + (i & 1) * 512, q[4 * i], q[4 * i + 1], q[4 * i + 2], q[4 * i + 3]);
          const int sk0 = take(false, SZ_KV, ak);
          fence_regs(q);
          release_warp(bi);
          wg_fence();
          qk(s, ak);
          probe2();
          return sk0;
        };
        auto mma4 = [&](uint32_t ad, int acc) {
#pragma unroll
          for (int kk = 0; kk < 4; kk++)
            wgmma_ss_n192<1>(o, mk_desc(ad + wg * 512, 16, 1024, 1) + (kk * 2), mk_desc(ad, 4096, 1024, 1) + (1024 + (kk >> 1) * 768 + (kk & 1) * 128), acc || kk != 0);
        };
        auto convert = [&](int i0, int i1) {
          sched_fence(keep, never);
#pragma unroll
          for (int i = i0; i < i1; i++) {
            q[i] = pack_bf16(o[2 * i] * kScaleLog2, o[2 * i + 1] * kScaleLog2);
            if ((i & 7) == 7 && i != i1 - 1) sched_fence(keep, never);
          }
          sched_fence(keep, never);
        };
        auto kend = [&](int bi, int k) {
          wg_commit();
          drain(k < 8 ? (0x54732710u >> (4 * k)) & 7 : 7);
          probe1();
          wg_wait<0>();
          release(bi);
        };
        if (type == OP_O) {
          int prev = 0;
          if (op & C_WIDE) {
            float d[64];
            auto mma3 = [&](uint32_t ad, int h, int acc) {
#pragma unroll
              for (int kk = 0; kk < 2; kk++)
                wgmma_ss_n192<1>(o, mk_desc(ad + wg * 256, 16, 512, 2) + (h * 512 + kk * 2), mk_desc(ad, 4096, 1024, 1) + (1024 + h * 768 + kk * 128), acc || kk);
            };
            auto mma2 = [&](uint32_t ad, uint32_t ob, int h, int acc) {
#pragma unroll
              for (int kk = 0; kk < 2; kk++)
                wgmma_ss_n128<1>(d, mk_desc(ad + wg * 256, 16, 512, 2) + (h * 512 + kk * 2), mk_desc(ad, 4096, 1024, 1) + (ob + h * 512 + kk * 128), acc || kk);
            };
            auto wstep = [&](uint32_t bytes, int acc, auto hook) {
              uint32_t ad;
              const int bi = take(rdy0, bytes, ad);
              wg_fence();
              if (bytes == SZ_W2) mma2(ad, 1024, 0, 1); else mma3(ad, 0, acc);
              if (bytes == SZ_W) mma3(ad, 1, 1);
              wg_commit();
              if (acc) { wg_wait<1>(); release(prev); }
              if (bytes == SZ_W) mma2(ad, 2560, 0, acc);
              if (bytes == SZ_W3) mma3(ad, 1, 1); else mma2(ad, bytes == SZ_W ? 2560 : 1024, 1, 1);
              wg_commit();
              prev = bi;
              hook();
              probe1();
              wg_wait<1>();
            };
            undefine(o);
            wstep(SZ_W, 0, [&]() { drain(0); });
#pragma unroll 1
            for (int k = 1; k < ((op >> 2) & 127) - TAIL; k++) wstep(SZ_W, 1, [&]() { drain(k); });
#pragma unroll 1
            for (int k = 0; k < TAIL; k++) wstep(SZ_W2, 1, []() {});
            pend = ptr_add(P.g->part, (((op >> 9) & 31) * 2 + rank) * 81920 + 4 * 8192 + img0 * 16);
            wstep(SZ_W3, 1, [&]() {
              fence_regs(d);
#pragma unroll
              for (int i = 0; i < 32; i++) q[16 + i] = pack_bf16(d[2 * i], d[2 * i + 1]);
              slab(2, 2);
            });
#pragma unroll 1
            for (int k = 3; k < 6; k++) wstep(SZ_W3, 1, [&]() { slab(k, 2); });
            op = prog[pc + 1];
            enter();
            pend_any = true;
            pend -= 4 * 512;
            bi0 = take(rdy0 || (op & 3) != OP_Q, SZ_Q, ad0);
            sched_fence(keep, never);
            wg_wait<0>();
            fence_regs(o);
            release(prev);
#pragma unroll
            for (int i = 0; i < 48; i++) q[i] = pack_bf16(o[2 * i], o[2 * i + 1]);
            if ((op & 3) != OP_Q) continue;
            pc++;
            goto first_step;
          }
          float c[80];
          auto mma2 = [&](uint32_t ad, uint32_t oa, uint32_t ob, int acc) {
            wgmma_ss_n160<1>(c, mk_desc(ad + wg * 256, 16, 512, 2) + (oa), mk_desc(ad, 2048, 512, 2) + (1024 + ob), acc);
            wgmma_ss_n160<1>(c, mk_desc(ad + wg * 256, 16, 512, 2) + (oa + 2), mk_desc(ad, 2048, 512, 2) + (1024 + ob + 64), 1);
          };
          auto kstep = [&](int acc, auto hook, uint32_t bytes = SZ_O) {
            uint32_t ad;
            const int bi = take(rdy0, bytes, ad);
            wg_fence();
            mma2(ad, 0, 0, acc);
            wg_commit();
            if (acc) wg_wait<1>();
            if (acc == 1) release(prev);
            if (acc > 1) release_warp(prev, acc == 2 || wg == 0);
            mma2(ad, 512, 640, 1);
            wg_commit();
            prev = bi;
            hook();
            probe1();
            wg_wait<1>();
          };
          auto unblock = [&](int k) {
            if (__all_sync(0xffffffffu, rdy0) || __all_sync(0xffffffffu, mbar_try(full0 + r.off(), r.ph(), 1500))) return;
#pragma unroll 1
            for (; k < 6; k++) drain(k);
            pend_any = false;
          };
          unblock(0);
          kstep(0, [&]() { drain(0); });
          int left = ((job >> 13) & 127) - 6;
#pragma unroll 1
          for (uint32_t k = 1, pace = left >= 29 ? 0x4511 : left <= 17 ? 0x1a : 0x155; left > 0; pace >>= 2, left--) {
            unblock(k);
            kstep(1, [&]() {
#pragma unroll 1
              for (int i = pace & 3; i > 0; i--) drain(k++);
            });
          }
          uint32_t t[8], stage[3];
          float u[80];
          auto unpack = [&](int j) {
#pragma unroll
            for (int i = 0; i < 8; i++) {
              u[16 * j + 2 * i] = __uint_as_float(t[i] << 16); u[16 * j + 2 * i + 1] = __uint_as_float(t[i] & 0xffff0000u);
              asm volatile("" : "+f"(u[16 * j + 2 * i]), "+f"(u[16 * j + 2 * i + 1]));
            }
          };
#pragma unroll
          for (int i = 0; i < 8; i++) t[i] = 0;
          const uint32_t bytes = (job & P_LD) ? SZ_OL : SZ_O;
#pragma unroll
          for (int j = 0; j < 5; j++) {
            if (j == 2 && wg == 1) {
              wg_wait<0>();
              release_warp(prev);
              bar_sync(1, 256);
            }
            kstep(j == 2 ? 3 : 2, [&]() {
              if (j == 4) asm volatile("{\n.reg .pred p;\nsetp.eq.u32 p, %0, 0;\n@p bar.arrive 1, 256;\n}\n" ::"r"(wg) : "memory");
              if (j) unpack(j - 1);
              lds2_if(job & P_LD, sbase + (cur - ring16 + img0) * 16 - 8192, t);
              if (j >= 1 && j <= 3) stage[j - 1] = sbase + (cur - ring16) * 16 - bytes + wid * 1024;
            }, bytes);
          }
          unpack(4);
          sched_fence(keep, never);
          wg_wait<0>();
          fence_regs(c);
          release_warp(prev);
          asm volatile("barrier.cluster.arrive.relaxed;" ::: "memory");
#pragma unroll
          for (int i = 0; i < 10; i++) {
            const int v = (i & 1) * 2 + (lane >> 4);
            const uint32_t sa = stage[i >> 2] + (i & 2) * 4096;
            stsm4(sa + (lane & 15) * 64 + ((v ^ ((lane >> 1) & 3)) << 4), pack_bf16(c[8 * i] + u[8 * i], c[8 * i + 1] + u[8 * i + 1]),
                  pack_bf16(c[8 * i + 2] + u[8 * i + 2], c[8 * i + 3] + u[8 * i + 3]), pack_bf16(c[8 * i + 4] + u[8 * i + 4], c[8 * i + 5] + u[8 * i + 5]),
                  pack_bf16(c[8 * i + 6] + u[8 * i + 6], c[8 * i + 7] + u[8 * i + 7]));
          }
          asm volatile("fence.proxy.async.shared::cta;" ::: "memory");
          __syncwarp();
          if (elect()) {
#pragma unroll
            for (int i = 0; i < 5; i++)
              tma3d_store(&P.out, stage[i >> 1] + (i & 1) * 8192, 0, ((job >> 7) & 7) * kSq + rank * 128 + wid * 16, ((job >> 10) & 1) * 20 + ((job >> 20) & 3) * 5 + i);
            asm volatile("cp.async.bulk.commit_group;\ncp.async.bulk.wait_group.read 0;" ::: "memory");
          }
          __syncwarp();
          break;
        }
        bi0 = take(rdy0, SZ_Q, ad0);
      first_step:
        undefine(o);
        wg_fence();
        mma4(ad0, 0);
        kend(bi0, 0);
        fence_regs(o);
      next_head:
        {
#pragma unroll 1
          for (int k = 1; k < ((op & F_PARK) ? 10 : 8); k++) {
            uint32_t ad;
            const int bi = take(rdy0, SZ_Q, ad);
            wg_fence();
            mma4(ad, 1);
            kend(bi, k);
          }
          if (op & F_PARK) {
            fence_regs(o);
            convert(0, 48);
            pend = ptr_add(P.g->tile, (((op >> 2) & 511) * 2 + rank) * SZ_PARK + img0 * 16);
            continue;
          }
          uint32_t a8, a9, ak0, ak1;
          const int b8 = take(rdy0, SZ_Q, a8), b9 = take(false, SZ_Q, a9);
          wg_fence();
          mma4(a8, 1);
          wg_commit();
          mma4(a9, 1);
          wg_commit();
          pc++;
          wg_wait<1>();
          release(b8);
          const int sk0 = take(false, SZ_KV, ak0);
          wg_wait<0>();
          fence_regs(o);
          release(b9);
          float s0[32];
          convert(0, 32);
          wg_fence();
          qk(s0, ak0, 0, 4);
          convert(32, 48);
          wg_fence();
          qk(s0, ak0, 4, 12);
          sk1 = take(false, SZ_KV, ak1);
          probe1();
          wg_wait<0>();
          first(s0, sk0, [&](int i) {
            if (i == 0) return;
            sched_fence(keep, never);
            wg_fence();
            if (i == 1) qk(s, ak1, 0, 4);
            if (i == 2) qk(s, ak1, 4, 8);
            if (i == 3) qk(s, ak1, 8, 12);
            sched_fence(keep, never);
          });
        }
        for (;;) {
          {
            uint32_t av;
            const int sv = take(rdy0, SZ_KV, av);
            undefine(o);
            wg_fence();
            pv(pa, av, 0);
            finish(pb, sk1, sv);
          }
          nop = prog[pc + 1];
#pragma unroll 1
          for (int jj = 0; jj < 7; jj++) {
            step(pb, pa);
            step(pa, pb);
          }
          float i0, i1;
          auto last = [&]() {
            uint32_t av;
            const int sv = take(rdy0, SZ_KV, av);
            wg_fence();
            pv(pb, av, 1);
            sched_fence(keep, never);
            probe1();
            l0 += __shfl_xor_sync(0xffffffffu, l0, 1); l1 += __shfl_xor_sync(0xffffffffu, l1, 1);
            l0 += __shfl_xor_sync(0xffffffffu, l0, 2); l1 += __shfl_xor_sync(0xffffffffu, l1, 2);
            i0 = rcp(l0); i1 = rcp(l1);
            pend = ptr_add(P.g->tile, (((op >> 2) & 511) * 2 + rank) * SZ_PARK + img0 * 16);
            return sv;
          };
          auto normalise = [&](uint32_t (&d)[48], auto mid) {
#pragma unroll
            for (int i = 0; i < 24; i++) {
              d[8 * (i >> 2) + (i & 3)] = pack_bf16(o[4 * i] * i0, o[4 * i + 1] * i0);
              d[8 * (i >> 2) + (i & 3) + 4] = pack_bf16(o[4 * i + 2] * i1, o[4 * i + 3] * i1);
              if ((i & 1) && i != 23) sched_fence(keep, never);
              if ((i & 3) == 3 && i != 23) mid(i >> 2);
            }
          };
          const int sv = last();
          if ((nop & 3) != OP_A) {
            op = nop;
            enter();
            pend_any = true;
            bi0 = take(rdy0 || (nop & 3) != OP_Q, SZ_Q, ad0);
            sched_fence(keep, never);
            wg_wait<0>();
            fence_regs(o);
            release(sv);
            normalise(q, [](int) {});
            undefine(o);
            if ((nop & 3) != OP_Q) break;
            sched_fence(keep, never);
            wg_fence();
            mma4(ad0, 0);
            pc++;
            kend(bi0, 0);
            fence_regs(o);
            goto next_head;
          }
          const int sk0 = unpark();
          wg_wait<1>();
          fence_regs(o);
          release(sv);
          uint32_t t[48];
          auto st = [&](int i) {
            stg2_if(true, pend + i * 512, t[8 * i], t[8 * i + 1], t[8 * i + 2], t[8 * i + 3], t[8 * i + 4], t[8 * i + 5], t[8 * i + 6], t[8 * i + 7], spol);
          };
          normalise(t, [&](int i) { if (!(i & 1)) st(i >> 1); });
          wg_wait<0>();
          first(s, sk0, [&](int i) { if (i < 3) { sched_fence(keep, never); st(3 + i); } });
          __syncwarp();
          mbar_arrive_if(lane == 0, odone0 + 8 * pc);
          pc++;
          op = nop;
          uint32_t ak1;
          sk1 = take(rdy0, SZ_KV, ak1);
          rdy0 = rdy1;
          wg_fence();
          qk(s, ak1);
        }
      }
    }
    asm volatile("barrier.cluster.wait;" ::: "memory");
  } else {
    asm volatile("setmaxnreg.dec.sync.aligned.u32 24;");
    const uint32_t* prog = P.prog[role].p;
    unsigned int* flag = P.g->flag + rank;
    if (wid == 11 && (prog[0] & 3) == OP_Q) {
      const uint32_t a = prog[1];
      const char* p = ptr_add(P.kv[rank * 2 + ((a >> 10) & 1)], ((a >> 2) & 255) * (kSk * kDh * 2) + (threadIdx.x & 31) * 128);
#pragma unroll 1
      for (uint32_t k = 0; k < 3; k++) {
        wait_word(progress, 8 * k);
        p += SZ_KV;
        asm volatile("prefetch.global.L2 [%0];\nprefetch.global.L2 [%0 + 4096];" ::"l"(p));
      }
      __syncwarp();
    }
    if (wid == 8) {
      Cursor head{0}, tail{0};
      int sh = 0, room = RING >> 12;
      uint32_t cur = 0;
      uint64_t fifo = 0;
      uint32_t dst, bar = 0, ev = ev0;
      const uint64_t pol = evict_first();
      auto retire = [&]() {
        mbar_wait(empty0 + tail.off(), tail.ph());
        tail.next();
        room += (uint32_t)fifo & 31;
        fifo >>= 5;
        sh -= 5;
        asm volatile("st.volatile.shared.u32 [%0], %1;" ::"r"(progress), "r"(tail.n) : "memory");
      };
      auto acquire = [&](uint32_t bytes) {
        uint32_t fp = bytes >> 12;
        if (cur + fp > (RING >> 12)) { fp += (RING >> 12) - cur; cur = 0; }
        room -= fp;
        while (room < 0) retire();
        fifo |= (uint64_t)fp << sh;
        sh += 5;
        dst = sbase + (cur << 12);
        bar = full0 + head.off();
        cur += bytes >> 12;
        head.next();
      };
      auto gate = [&]() {
        mbar_wait(ev, 0);
        ev += 8;
        asm volatile("fence.proxy.async.global;" ::: "memory");
      };
      for (int pc = 0;; pc++) {
        uint32_t op = prog[pc];
        const int type = op & 3;
        if (type == OP_END) break;
        if (op == OP_O) {
          gate();
          op = __shfl_sync(0xffffffffu, lds32(jobw), 0);
        }
        const int blk = (op >> 10) & 1;
        if (type == OP_Q) {
          const uint64_t px = (op & P_LASTX) ? pol : no_hint(), pw = (op & P_LASTW) ? pol : no_hint();
          int k = 0;
          if (pc == 0) {
            k = 64 * EARLY; head.n = 8 * EARLY; sh = 5 * EARLY; cur = EARLY * (SZ_Q >> 12); room -= cur;
            fifo = (SZ_Q >> 12) * (((1u << (5 * EARLY)) - 1) / 31);
          }
#pragma unroll 1
          for (int stop = (op & P_GATE) ? kD - 64 : kD;; stop = kD) {
#pragma unroll 1
            for (; k < stop; k += 64) {
              acquire(SZ_Q);
              if (elect()) {
                mbar_expect(bar, SZ_Q);
                tma3d_mc_hint(dst + 16384 + rank * 12288, &P.wq[blk], bar, k + 32 * rank, 3 * ((op >> 2) & 31), pw);
                tma2d_hint(dst, &P.x[blk], bar, k, ((op >> 7) & 7) * kSq + rank * 128, px);
              }
            }
            if (k == kD) break;
            gate();
          }
        } else if (type == OP_A) {
          const int row0 = ((op >> 2) & 255) * kSk;
          if (op & F_PARK) {
            gate();
            acquire(SZ_PARK);
            if (elect()) {
              mbar_expect(bar, SZ_PARK);
              bulk_load_hint(dst, &P.g->tile[(((op >> 20) & 511) * 2 + rank) * 3072], SZ_PARK, bar, pol);
            }
          }
          auto kv = [&](uint32_t tx, const CUtensorMap* m, int c3) {
            const uint32_t before = bar;
            acquire(SZ_KV);
            if (elect()) {
              mbar_expect(bar, tx);
              tma4d_mc_hint(dst + rank * (SZ_KV / 2), m, tx ? bar : before, c3, pol);
            }
          };
          int c3 = row0 / 8 + 4 * rank;
          const int end = c3 + 120;
          kv(SZ_KV, &P.k[blk], c3);
#pragma unroll 1
          for (uint32_t tv = SZ_KV; c3 != end; tv = 0, c3 += 8) {
            kv(2 * SZ_KV - tv, &P.k[blk], c3 + 8);
            kv(tv, &P.v[blk], c3);
          }
          if (op & P_GATE) gate();
          kv(SZ_KV, &P.v[blk], c3);
        } else {
          const uint4* part = &P.g->part[((((op >> 6) & 30) + ((op >> 21) & 1)) * 2 + rank) * 5120 + ((op >> 20) & 1) * 2560];
          auto run = [&](const uint32_t bytes, int k, int cnt, int gates) {
            const int col = bytes == SZ_O || bytes == SZ_OL ? 5 * ((op >> 20) & 3) : 5 * ((op >> 21) & 1);
            int row = 8 * k + 4 * rank, pre = bytes == SZ_O && (op & P_PRE) ? 0 : 2560;
#pragma unroll 1
            for (int h = (k * 43) >> 7, k0 = k - 3 * h; cnt > 0; h++, k0 = 0, gates = gates >> 1 | (gates & 2)) {
              const uint4* src = &P.g->tile[(P.slot[((op >> 2) & 480) + h] * 2 + rank) * 3072 + k0 * 1024];
              const uint64_t pw = h >= ((op >> 23) & 31) && h < 2 * (op >> 28) ? pol : no_hint();
              if (gates & 1) gate();
              int m = min(3 - k0, cnt);
              cnt -= m;
#pragma unroll 1
              for (; m > 0; m--, src += 1024, row += 8) {
                acquire(bytes);
                if (elect()) {
                  mbar_expect(bar, bytes);
                  if (bytes == SZ_O || bytes == SZ_OL) tma5d_mc_hint(dst + 16384 + rank * 10240, &P.wo[blk], bar, row, col, no_hint());
                  if (bytes == SZ_W || bytes == SZ_W3) tma5d_mc_hint(dst + 16384 + rank * 12288, &P.wo3[blk], bar, row, col, pw);
                  bulk_load_hint(dst, src, 16384, bar, pol);
                  if (bytes == SZ_W || bytes == SZ_W2) tma5d_mc_hint(dst + bytes - 16384 + rank * 8192, &P.wo2[blk], bar, row, col + 3, pw);
                  if (bytes == SZ_OL) bulk_load_hint(dst + SZ_O, part, 8192, bar, pol);
                }
                if (bytes == SZ_OL) part += 512;
              }
              if (pre < 2560) {
                if (elect()) asm volatile("cp.async.bulk.prefetch.L2.global [%0], 10240;" ::"l"(part + pre) : "memory");
                pre += 640;
              }
            }
          };
          const int n = (op >> 13) & 127;
          if (op & P_WIDE) {
            run(SZ_W, 0, n - TAIL, 3);
            run(SZ_W2, n - TAIL, TAIL, (n - TAIL) % 3 ? 2 : 3);
            run(SZ_W3, n - TAIL, TAIL, 0);
          } else {
            if (op & P_PRE) gate();
            run(SZ_O, kSteps - n, (op & P_LD) ? n - 5 : n, 3);
            if (op & P_LD) {
              if (!(op & P_PRE)) gate();
              run(SZ_OL, kSteps - 5, 5, 2);
            }
          }
        }
      }
#pragma unroll 1
      while (sh) retire();
    } else if (threadIdx.x == 288) {
      for (int pc = 0;; pc++) {
        const uint32_t op = prog[pc];
        const int type = op & 3;
        if (type == OP_END) break;
        if (type == OP_Q ? !(op & F_PARK) : type == OP_O && !(op & P_WIDE)) continue;
        const int id = type == OP_A ? (op >> 2) & 511 : type == OP_Q ? N_TILE + ((op >> 13) & 127) : ID_PART + ((op >> 5) & 60) + ((op >> 20) & 3);
        const uint32_t v = type == OP_O ? 1 : P.info[id] & 7;
        mbar_wait_long(odone0 + 8 * pc);
        flag_set(flag + 2 * id, v);
        if (type == OP_O && (op & P_WIDE)) flag_set(flag + 2 * id + 2, v);
      }
    } else if (wid == 10) {
      int i = threadIdx.x & 31;
      const int n_ev = P.prog[role].n_ev;
      auto event = [&]() { return i < n_ev ? P.prog[role].ev[i] : n_ev ? E_JOB | (i - n_ev) : 0; };
      uint32_t e = i < 8 ? event() : 0;
      for (uint32_t n = 0; __any_sync(0xffffffffu, e); n++) {
        uint32_t job = lds32(jobw);
        const int togo = (e & E_DRAW) ? (e & 1023) - (lds32(progress) >> 3) : 99;
        if (togo <= 0 && rank == 0) {
          job = P.job[atomicInc(&P.g->ticket, gridDim.x / 2 - 1)];
          asm volatile("{\n.reg .u32 a;\nmapa.shared::cluster.u32 a, %0, 1;\nst.volatile.shared::cluster.u32 [a], %1;\n"
                       "st.volatile.shared.u32 [%0], %1;\n}\n" ::"r"(jobw), "r"(job) : "memory");
        }
        if ((e & E_JOB) && job) {
          const uint32_t j = e & 63, heads = job == OP_O ? 0 : kH - ((job >> 2) & 31), jp = !(job & P_LD) ? 63 : (job & P_PRE) ? 0 : heads - 1, h = j - (j > jp);
          e = j == jp ? (ID_PART + ((job >> 5) & 60) + ((job >> 20) & 3)) | E_ON | E_LAST : h < heads ? (((job >> 2) & 511) + h) | E_ON | E_LAST : 0;
        }
        unsigned int* f = ptr_add(flag, 8 * (e & 1023));
        const bool ok = (e & E_ON) ? flag_get(f) - 1 < ((e & E_FREE) ? 1 : 7) : (e & E_DRAW) && job;
        if (ok) {
          mbar_arrive(ev0 + 8 * i);
          if (e & (E_FREE | E_LAST)) flag_dec(f);
          i += 8;
          e = event();
        }
        asm volatile("{\n.reg .pred p;\nsetp.ge.u32 p, %0, 0x400000;\n@p trap;\n}\n" ::"r"(n));
        if (!__any_sync(0xffffffffu, ok)) __nanosleep(__any_sync(0xffffffffu, job || togo <= 2) ? 100 : 600);
      }
    } else if (threadIdx.x == 352) {
      uint32_t items = 0;
      auto read = [&](int id) {
        if (!(P.info[id] & I_NEXT)) return;
        wait_word(progress, 8 * items);
        flag_dec(flag + 2 * id);
      };
      for (int pc = 0;; pc++) {
        const uint32_t op = prog[pc];
        const int type = op & 3;
        if (type == OP_END) break;
        if (type == OP_O) {
          const uint32_t n = (op >> 13) & 127, base = items;
#pragma unroll 1
          for (uint32_t k = 3, id = (op >> 2) & 511; k <= n; k += 3, id++) {
            items = base + k + (k + TAIL > n ? TAIL : 0);
            read(id);
          }
          items = base + n + TAIL;
        } else if (type == OP_A) {
          if (op & F_PARK) { items++; read(N_TILE + ((op >> 13) & 127)); }
          items += 32;
        } else {
          items += 10;
        }
      }
    }
    __syncwarp();
    asm volatile("barrier.cluster.arrive.relaxed;\nbarrier.cluster.wait;" ::: "memory");
  }
}

typedef CUresult (*EncodeFn)(CUtensorMap*, CUtensorMapDataType, cuuint32_t, void*, const cuuint64_t*, const cuuint64_t*,
                             const cuuint32_t*, const cuuint32_t*, CUtensorMapInterleave, CUtensorMapSwizzle,
                             CUtensorMapL2promotion, CUtensorMapFloatOOBfill);

void encode(EncodeFn fn, CUtensorMap* m, const void* ptr, int rank, const cuuint64_t* dims, const cuuint64_t* strides,
            const cuuint32_t* box, CUtensorMapSwizzle swz) {
  const cuuint32_t es[5] = {1, 1, 1, 1, 1};
  CUresult r = fn(m, CU_TENSOR_MAP_DATA_TYPE_BFLOAT16, rank, const_cast<void*>(ptr), dims, strides, box, es,
                  CU_TENSOR_MAP_INTERLEAVE_NONE, swz, CU_TENSOR_MAP_L2_PROMOTION_L2_128B, CU_TENSOR_MAP_FLOAT_OOB_FILL_NONE);
  if (r != CUDA_SUCCESS) fprintf(stderr, "cuTensorMapEncodeTiled failed: %d\n", (int)r);
}

struct Op { int type, flags, id, n, quarter, park, item0, items; double t0, t1; };
struct Use { double ready, gate, need, freed; int readers, slot, prev; bool next; };
struct PlanStats { double end, slack, park_slack; int slots, parks; uint32_t own[N_CL]; };

bool plan(const char* const* text, int n_pair, int phase, Params& P, PlanStats* stats = nullptr) {
  constexpr double T_Q = 7900, T_A = 24800, T_U = TU, T_O = 640, T_RUN = 800, T_WIDE = TW, AHEAD = 3500, PUBLISH = 1500;
  const double margin = 256.0 * ((P.dbg >> 8) & 255);
  static Op op[N_CL][MAX_OPS];
  static Use use[ID_PART];
  int n_op[N_CL], covered[2 * N_TEAM] = {};
  struct Ref { double t; Op* o; int id; };
  static Ref att[N_TILE + 1], dem[N_TILE], prk[MAX_PARK + 1], unp[MAX_PARK + 1], wr[ID_PART];
  auto sort = [](Ref* r, int n) {
    for (int i = 1; i < n; i++)
      for (int j = i; j > 0 && r[j].t < r[j - 1].t; j--) { Ref x = r[j]; r[j] = r[j - 1]; r[j - 1] = x; }
  };
  auto hex = [](char c) { return c <= '9' ? c - '0' : c - 'a' + 10; };
  for (int i = 0; i < n_pair; i++)
    for (const char* s = text[i]; *s; s++)
      for (int h = 0; *s == 'J' && h < 2; h++) {
        if (covered[2 * hex(s[1]) + h]) return false;
        covered[2 * hex(s[1]) + h] = 10 * (s[2 + 2 * h] - '0') + s[3 + 2 * h] - '0';
      }
  for (int c = 0; c < 2 * n_pair; c++) {
    int n = 0, items = 0;
    double t = 0;
    auto add = [&](int type, int flags, int id, int heads, int quarter, int its, double dt) {
      if (n < MAX_OPS) op[c][n] = {type, flags, id, heads, quarter, 0, items, its, t, t + dt};
      n++; items += its; t += dt;
    };
    for (const char* s = text[c >> 1]; *s; s++) {
      const int tm = hex(s[1]) & 15, nj = covered[2 * tm + (c & 1)];
      if (*s == 'N') { add(OP_Q, 0, 0, 0, 0, 10, T_Q); add(OP_A, 0, 0, 0, 0, 32, T_A); }
      if (*s == 'P') add(OP_Q, F_PARK, 0, 0, 0, 10, T_Q + TP);
      if (*s == '+' || *s == '-') t += *s == '+' ? 1000 : -1000;
      if (*s == 'U') { if (n == 0 || n > MAX_OPS || op[c][n - 1].type != OP_A) return false; add(OP_A, F_PARK, 0, 0, 0, 33, T_U); }
      if (*s == 'J') { if (nj < TAIL + 6 || nj > kSteps - 11) return false; add(OP_O, P_WIDE, tm * kH, nj, 2 * (c & 1), nj + TAIL, 2 * T_O * nj + T_WIDE); }
    }
    add(OP_O, 0, 0, 0, 0, 0, 0);
    add(OP_END, 0, 0, 0, 0, 0, 0);
    if (n > MAX_OPS || op[c][0].type != OP_Q) return false;
    n_op[c] = n - 1;
    att[c] = {t, &op[c][n - 2], 0};
  }
  for (int i = 0; i < 4 * N_TEAM; i++) dem[i] = {(double)covered[i / 2], nullptr, i};
  sort(att, 2 * n_pair); sort(dem, 4 * N_TEAM);
  for (int i = 0; i < 4 * N_TEAM; i++) {
    Op* f = att[i].o;
    const int nj = covered[dem[i].id / 2];
    f->flags = nj ? P_LD : 0;
    f->id = dem[i].id / 4 * kH + nj / 3; f->quarter = dem[i].id & 3; f->items = f->n = kSteps - nj;
    f[1].t0 = f[1].t1 = f->t1 = f->t0 + T_O * f->n + T_RUN; f[1].item0 += f->n;
  }
  for (int i = 0; i < ID_PART; i++) use[i] = {0, 0, 1e18, 0, 0, 0, 0, false};
  int n_att = 0, n_prk = 0, n_unp = 0;
  auto ready = [&](const Op* o) {
    const int nt = o[1].type;
    return o->t1 + (nt == OP_Q ? 6100 : o[1].n ? ((o[1].flags & P_WIDE) ? 7700 : 3900) : 1500) + PUBLISH;
  };
  for (int c = 0; c < 2 * n_pair; c++)
    for (Op* o = op[c]; o->type != OP_END; o++) {
      if (o->type == OP_A) { att[n_att] = {ready(o), o, 0}; if (++n_att > N_TILE) return false; }
      if (o->type == OP_A && o->flags) { unp[n_unp] = {o->t0 - AHEAD, o, 0}; if (++n_unp > MAX_PARK) return false; }
      if (o->type == OP_Q && o->flags) { prk[n_prk] = {ready(o), o, 0}; if (++n_prk > MAX_PARK) return false; }
      for (int i = 0; o->type == OP_O && i < o->n; i++) {
        const int nw = (o->flags & P_WIDE) ? o->n - TAIL : 0, k = nw ? i : kSteps - o->n + i;
        Use& u = use[o->id / kH * kH + k / 3];
        const double t = o->t0 + T_O * (i + (i < nw ? i : nw));
        if (t - AHEAD < u.need) u.need = t - AHEAD;
        const double f = !nw ? 1e18 : i + FLIGHT < o->items - TAIL || (nw && o[1].type != OP_O) ? t + T_O * (i < nw ? 2 : 1 + TAIL) + PUBLISH : 1e18;
        if (f > u.freed) u.freed = f;
        if (i == 0 || k % 3 == 0) u.readers++;
      }
    }
  if (n_att != N_TILE || n_prk != n_unp) return false;
  for (int i = 0; i < N_TILE; i++) { const int id = (i & 15) * kH + (i >> 4); dem[i] = {use[id].need, nullptr, id}; }
  sort(att, n_att); sort(dem, N_TILE); sort(prk, n_prk); sort(unp, n_unp);
  PlanStats st = {0, 1e18, 1e18, 0, n_prk};
  int n_wr = 0;
  for (int i = 0; i < N_TILE; i++) {
    Op* o = att[i].o;
    o->id = dem[i].id;
    if (!o->flags) o[-1].id = o->id;
    if (dem[i].t - att[i].t < st.slack) st.slack = dem[i].t - att[i].t;
    wr[n_wr++] = {o->t1 - 2 * AHEAD, o, o->id};
  }
  for (int i = 0; i < n_prk; i++) {
    prk[i].o->id = unp[i].o->id;
    prk[i].o->park = unp[i].o->park = i;
    use[N_TILE + i].freed = unp[i].o->t0 + 2 * PUBLISH;
    use[N_TILE + i].readers = 1;
    if (unp[i].t - prk[i].t < st.park_slack) st.park_slack = unp[i].t - prk[i].t;
    wr[n_wr++] = {prk[i].o->t1 - 2 * AHEAD, prk[i].o, N_TILE + i};
  }
  for (int c = 0; c < 2 * n_pair; c++)
    for (int d = 0; d < 2 * n_pair; d++)
      for (Op *f = &op[c][n_op[c] - 1], *o = op[d]; f->n && o->type != OP_END; o++)
        if (o->type == OP_O && (o->flags & P_WIDE) && o->id / kH == f->id / kH && o->quarter / 2 == f->quarter / 2) {
          if (f->t0 - o->t1 > 4096.0 * ((P.dbg >> 16) & 255)) f->flags |= P_PRE;
          const double slack = f->t0 + ((f->flags & P_PRE) ? 0 : (f->n - 5) * T_O) - AHEAD - ready(o);
          if (slack < st.park_slack) st.park_slack = slack;
        }
  constexpr double long_while = 160000;
  for (int c = 0; c < 2 * n_pair; c++)
    for (Op* o = op[c]; o->type != OP_END; o++) {
      if (o->type == OP_O && (o->flags & P_WIDE)) {
        int run = 0, best = 0, end = 0;
        for (int h = 0; 3 * h < o->n; h++) {
          bool last = true;
          for (int d = 0; d < 2 * n_pair; d++)
            for (const Op* e = op[d]; e->type != OP_END; e++) {
              if (e->type != OP_O || e == o || ((e->id ^ o->id) & 256) || e->quarter / 2 != o->quarter / 2) continue;
              const bool wide = e->flags & P_WIDE;
              if (wide ? 3 * h >= e->n : 3 * h + 3 <= kSteps - e->n) continue;
              const double dt = e->t0 + T_O * (wide ? 6 * h : 3 * h - kSteps + e->n) - o->t0 - T_O * 6 * h + (d - c) * 1e-3;
              if (dt > 0 && dt < long_while) last = false;
            }
          run = last ? run + 1 : 0;
          if (run > best) { best = run; end = h + 1; }
        }
        if (3 * end >= o->n) end++;
        o->park = (end - best) | (end / 2) << 5;
      }
      if (o->type != OP_Q) continue;
      bool lw = true, lx = true;
      for (int d = 0; d < 2 * n_pair; d++)
        for (const Op* e = op[d]; e->type != OP_END; e++) {
          const double dt = e->t0 - o->t0 + (d - c) * 1e-3;
          if (e->type != OP_Q || e == o || dt < 0 || dt > long_while) continue;
          if (((e->id ^ o->id) & (256 + 31)) == 0) lw = false;
          if (e->id / kH == o->id / kH) lx = false;
        }
      o->quarter = (lw ? P_LASTW : 0) | (lx ? P_LASTX : 0);
    }
  sort(wr, n_wr);
  int holder[N_TILE];
  for (int i = 0; i < n_wr; i++) {
    int best = -1;
    for (int sl = 0; sl < st.slots; sl++)
      if (use[holder[sl]].freed + margin <= wr[i].t && (best < 0 || use[holder[sl]].freed < use[holder[best]].freed)) best = sl;
    Use& u = use[wr[i].id];
    if (best >= 0) { u.prev = holder[best]; use[u.prev].next = true; wr[i].o->flags |= P_GATE; }
    else if (st.slots == N_TILE) return false;
    else best = st.slots++;
    u.slot = best;
    holder[best] = wr[i].id;
  }
  {
    int pos[N_CL] = {}, flag[ID_PART + 4 * N_TEAM] = {}, seen[ID_PART] = {};
    auto goal = [&](int c) { return op[c][n_op[c] - 1].item0; };
    for (bool moved = true; moved;) {
      moved = false;
      for (int c = 0; c < 2 * n_pair; c++) {
        for (; pos[c] < goal(c); pos[c]++, moved = true) {
          bool ok = true;
          for (const Op* o = op[c]; o->type != OP_END; o++) {
            const int k = pos[c] - o->item0, own = o->type == OP_A ? o->id : N_TILE + (o->park & 127);
            if (k < 0 || k >= o->items) continue;
            if (o->type == OP_O) ok = k >= o->n || flag[o->id + k / 3];
            else if (k == o->items - 1 && (o->flags & P_GATE)) ok = seen[use[own].prev] == use[use[own].prev].readers;
            else if (k == 0 && o->type == OP_A && (o->flags & F_PARK)) ok = flag[N_TILE + o->park];
          }
          if (!ok) break;
          for (const Op* o = op[c]; o->type != OP_END; o++) {
            if (pos[c] == o->item0 + o->items + (o[1].type == OP_Q ? 7 : o[1].item0 == goal(c) ? -1 : 5)) {
              if (o->type == OP_A) flag[o->id] = 1;
              if (o->type == OP_Q && (o->flags & F_PARK)) flag[N_TILE + o->park] = 1;
              if (o->type == OP_O) flag[ID_PART + o->id / kH * 4 + o->quarter] = flag[ID_PART + o->id / kH * 4 + o->quarter + 1] = 1;
            }
            const int k = pos[c] - FLIGHT - o->item0, nw = o->n - TAIL;
            if (k == 0 && o->type == OP_A && (o->flags & F_PARK)) seen[N_TILE + o->park]++;
            if (o->type == OP_O && k >= 0 && k < o->items && (k < nw || k >= o->n) && (k < nw ? k : k - TAIL) % 3 == 2) seen[o->id + (k < nw ? k : k - TAIL) / 3]++;
          }
        }
      }
    }
    for (int c = 0; c < 2 * n_pair; c++) if (pos[c] < goal(c)) return false;
  }
  int n_job = 0, longest = 0;
  for (int i = 0; i < 2 * N_TEAM; i++) if (kH + 1 - covered[i] / 3 > longest) longest = kH + 1 - covered[i] / 3;
  for (int c = 0; c < 2 * n_pair; c++) {
    uint32_t items = 0, cur = 0, pend = 0;
    int n = 0, ev = 0;
    auto item = [&](uint32_t bytes, int count) {
      for (int i = 0; i < count; i++) { if (cur + bytes > RING) cur = 0; cur += bytes; items++; }
    };
    auto event = [&](uint32_t e) { if (ev < MAX_TAB) P.prog[c].ev[ev] = e; ev++; };
    for (const Op* o = op[c];; o++) {
      if (o->type != OP_END && phase && (o->type == OP_O) != (phase == 2)) continue;
      uint32_t cw = o->type | (items % (2 * NBAR)) << 15 | (cur >> 12) << 20 | pend, pw = o->type | o->id << 2 | o->flags;
      const int ps = use[N_TILE + (o->park & 127)].slot;
      pend = 0;
      if (o->type == OP_O) {
        pw |= o->n << 13 | o->quarter << 20 | (uint32_t)o->park << 23;
        if (o->flags & P_WIDE) {
          cw |= o->n << 2 | (o->id / kH * 2 + o->quarter / 2) << 9 | C_WIDE;
          item(SZ_W, o->n - TAIL);
          item(SZ_W2, TAIL);
          item(SZ_W3, TAIL);
          pend = C_PEND;
          for (int i = 0; 3 * i < o->n; i++) event((o->id + i) | E_ON | (use[o->id + i].next ? 0 : E_LAST));
        } else {
          dem[n_job++] = {o->t0 - 1e6 * o->n, nullptr, (int)pw};
          st.own[c] = pw;
          pw = OP_O;
          event(E_DRAW | (items < 16 ? 0 : items - 16));
        }
      } else if (o->type != OP_END) {
        const bool parks = o->type == OP_Q && (o->flags & F_PARK);
        cw |= (parks ? ps : use[o->id].slot) << 2 | (o->flags & F_PARK);
        if (o->flags & F_PARK) pw |= o->park << 13 | ps << 20;
        if (o->type == OP_Q) { item(SZ_Q, 10); pw |= o->quarter; }
        else { if (o->flags & F_PARK) { item(SZ_PARK, 1); event((N_TILE + o->park) | E_ON | (use[N_TILE + o->park].next ? 0 : E_LAST)); } item(SZ_KV, 32); }
        if (parks || o->type == OP_A) pend = C_PEND;
        if (o->flags & P_GATE) event(use[parks ? N_TILE + o->park : o->id].prev | E_ON | E_FREE);
      }
      P.prog[c].c[n] = cw; P.prog[c].p[n++] = pw;
      if (o->type == OP_END) { if (o->t0 > st.end) st.end = o->t0; break; }
    }
    if (ev > MAX_TAB || ev + longest > MAX_EV) return false;
    P.prog[c].n_ev = ev;
    while (n < MAX_OPS) { P.prog[c].c[n] = OP_END; P.prog[c].p[n++] = OP_END; }
    P.first[c] = (uint16_t)(P.prog[c].p[0] & 2047);
  }
  sort(dem, n_job);
  for (int i = 0; i < n_job; i++) P.job[i] = dem[i].id;
  for (int i = 0; i < ID_PART; i++) {
    if (i < N_TILE) P.slot[i] = use[i].slot;
    P.info[i] = (use[i].readers + use[i].next) | (use[i].next ? I_NEXT : 0);
  }
  if (stats) *stats = st;
  return true;
}

const char* const kPrograms[N_CL / 2] = {
  "PNJ06464NNNNN", "PNJ15559NNNNN", "PNJ26361NNNNN", "PNJ35454+NNNNN", "PNJ47878NNNNN", "PNJ57070NNNNN",
  "NNJ68080NNNN", "NNJ76969NNNN", "NNNNNJ83636NN", "NNNNNNJf4246N", "NNNNNJa5353NN", "NNNNNJb4952NN",
  "NUNNNNNNN", "NNNNNJc5555NN", "NUNNNJe6363NN", "NNNNNJ97576-N", "NNNNNNNNN", "PNNNNNNNNN",
  "PNNNNNNNNN", "PNNNNNNNNN", "PNNNNNNNNN", "NNNNNNNNN", "NNNNNNNNN", "NNNNNNNNN",
  "NUNNNNNNN", "+NNNNNNNNN", "NUNNNNNNN", "NUNNNNN+NN", "NNUNNNNNN", "NUNNNNNNN",
  "NUNNNNNNN", "-NNUNNNJd5454N", "NUNNNNNNN",
};

const char* const* bench_programs() {
  return kPrograms;
}

}

extern "C" void kernel_launch(void* const* d_in, const int* in_sizes, int n_in, void* d_out, int out_size) {
  (void)in_sizes; (void)n_in; (void)out_size;
  static EncodeFn fn = nullptr;
  static int n_clusters = 0;
  if (!fn) {
    cudaDriverEntryPointQueryResult qr;
    void* f = nullptr;
    cudaGetDriverEntryPoint("cuTensorMapEncodeTiled", &f, cudaEnableDefault, &qr);
    fn = (EncodeFn)f;
    cudaFuncSetAttribute(fused_kernel, cudaFuncAttributeMaxDynamicSharedMemorySize, SMEM_BYTES);
    cudaLaunchConfig_t cfg = {};
    cfg.gridDim = dim3(132); cfg.blockDim = dim3(384); cfg.dynamicSmemBytes = SMEM_BYTES;
    cudaLaunchAttribute at[1];
    at[0].id = cudaLaunchAttributeClusterDimension; at[0].val.clusterDim.x = 2; at[0].val.clusterDim.y = 1; at[0].val.clusterDim.z = 1;
    cfg.attrs = at; cfg.numAttrs = 1;
    if (cudaOccupancyMaxActiveClusters(&n_clusters, fused_kernel, &cfg) != cudaSuccess || n_clusters < 1) n_clusters = 1;
    (void)cudaGetLastError();
  }
  static Params P;
  const CUtensorMapSwizzle S128 = CU_TENSOR_MAP_SWIZZLE_128B, S64 = CU_TENSOR_MAP_SWIZZLE_64B;
  for (int blk = 0; blk < 2; blk++) {
    void* const* in = d_in + 5 * blk;
    { const cuuint64_t d[] = {kD, kB * kSq}, s[] = {kD * 2}; const cuuint32_t b[] = {64, 128};
      encode(fn, &P.x[blk], in[0], 2, d, s, b, S128); }
    { const cuuint64_t d[] = {64, 8, 3, (cuuint64_t)kB * kH * kSk / 8}, s[] = {kDh * 2, 128, 8 * kDh * 2}; const cuuint32_t b[] = {64, 8, 3, 4};
      encode(fn, &P.k[blk], in[1], 4, d, s, b, S128);
      encode(fn, &P.v[blk], in[2], 4, d, s, b, S128); }
    { const cuuint64_t d[] = {64, kD, kHD / 64}, s[] = {kHD * 2, 128}; const cuuint32_t b[] = {64, 32, 3};
      encode(fn, &P.wq[blk], in[3], 3, d, s, b, S128); }
    { const cuuint64_t d[] = {32, 2, kHD / 8, 4, kD / 32}, s[] = {kD * 2, 8 * kD * 2, 2 * kD * 2, 64}; const cuuint32_t b[] = {32, 2, 4, 4, 5};
      encode(fn, &P.wo[blk], in[4], 5, d, s, b, S64); }
    { const cuuint64_t d[] = {64, 2, kHD / 8, 4, kD / 64}, s[] = {kD * 2, 8 * kD * 2, 2 * kD * 2, 128};
      const cuuint32_t b3[] = {64, 2, 4, 4, 3}, b2[] = {64, 2, 4, 4, 2};
      encode(fn, &P.wo3[blk], in[4], 5, d, s, b3, S128);
      encode(fn, &P.wo2[blk], in[4], 5, d, s, b2, S128); }
  }
  { const cuuint64_t d[] = {32, kB * kSq, 2 * kD / 32}, s[] = {2 * kD * 2, 64}; const cuuint32_t b[] = {32, 16, 1};
    encode(fn, &P.out, d_out, 3, d, s, b, S64); }

  P.kv[0] = (const char*)d_in[1]; P.kv[1] = (const char*)d_in[6]; P.kv[2] = (const char*)d_in[2]; P.kv[3] = (const char*)d_in[7];
  P.xw[0] = (const char*)d_in[0]; P.xw[1] = (const char*)d_in[3];
  cudaGetSymbolAddress((void**)&P.g, g_scratch);
  P.dbg = DBG_DEFAULT;
  if (n_clusters >= N_CL && plan(bench_programs(), N_CL / 2, 0, P)) {
    fused_kernel<<<2 * N_CL, 384, SMEM_BYTES>>>(P);
  } else {
    const char* text[2 * N_TEAM];
    for (int i = 0; i < 2 * N_TEAM; i++) text[i] = "NNNNNNNN";
    for (int phase = 1; phase <= 2; phase++) {
      plan(text, 2 * N_TEAM, phase, P);
      fused_kernel<<<8 * N_TEAM, 384, SMEM_BYTES>>>(P);
    }
  }
}
```

```cpp
#include <cuda_runtime.h>
#include <cuda_bf16.h>
#include <cuda.h>
#include <cuda/annotated_ptr>
#include <stdint.h>
#include <stdio.h>

namespace {

constexpr int kB = 8, kSq = 256, kD = 640, kH = 32, kSk = 1024, kDh = 192;
constexpr int kHD = kH * kDh;
constexpr uint32_t RING = 224 * 1024;
constexpr uint32_t SZ_KV = 24576;
constexpr uint32_t SZ_Q = 16384 + 24576;
constexpr uint32_t SZ_O = 16384 + 20480;
constexpr uint32_t SZ_W3 = 16384 + 24576, SZ_W2 = 16384 + 16384, SZ_W = SZ_W3 + 16384;
constexpr uint32_t SZ_PARK = 49152;
constexpr uint32_t SZ_OL = SZ_O + 8192;
constexpr int NBAR = 16, FLIGHT = RING / SZ_KV + 1;
constexpr int EARLY = 3;
constexpr int kSteps = kHD / 64;
constexpr int TAIL = 4;
constexpr uint32_t KV_CH = 64, KV_SBO = 3072;
constexpr int SMEM_BYTES = RING + 1024 + 1024;
constexpr int N_TEAM = 16, N_CL = 66, MAX_OPS = 22, MAX_EV = 72, MAX_TAB = 47, N_TILE = N_TEAM * kH, MAX_PARK = 128, ID_PART = N_TILE + MAX_PARK;
enum : uint32_t { OP_END = 0, OP_Q = 1, OP_A = 2, OP_O = 3, F_PARK = 1 << 11,
                  C_WIDE = 1 << 27, C_PEND = 1 << 26, P_GATE = 1 << 12, P_WIDE = 1 << 11, P_LD = 1 << 12, P_PRE = 1 << 22, P_LASTW = 1 << 29, P_LASTX = 1 << 30,
                  I_NEXT = 8, E_ON = 1 << 15, E_FREE = 1 << 14, E_LAST = 1 << 13, E_DRAW = 1 << 12, E_JOB = 1 << 11 };

#define TU 25900
#define TW 1300
#define TP 500
constexpr uint32_t DBG_DEFAULT = 0x040800;

struct alignas(1024) Scratch {
  unsigned int flag[2047];
  unsigned int ticket;
  uint4 part[N_TEAM * 2 * 2 * 5120];
  uint4 tile[N_TILE * 2 * 3072];
};

struct alignas(64) Params {
  const char* xw[2];
  uint16_t first[80];
  Scratch* g;
  uint32_t dbg;
  CUtensorMap x[2], wq[2], k[2], v[2], wo[2], wo3[2], wo2[2], out;
  struct {
    uint32_t c[MAX_OPS];
    uint32_t p[MAX_OPS];
    uint16_t n_ev, ev[MAX_TAB];
  } prog[N_CL];
  const char* kv[4];
  uint32_t job[N_CL];
  uint16_t slot[N_TILE];
  uint8_t info[ID_PART];
};

__device__ Scratch g_scratch;

template <int TB, int TA = 0>
__device__ __forceinline__ void wgmma_ss_n64(float (&d)[32], uint64_t da, uint64_t db, int scale_d) {
  asm volatile("{\n.reg .pred p;\nsetp.ne.b32 p, %34, 0;\n"
    "wgmma.mma_async.sync.aligned.m64n64k16.f32.bf16.bf16 {%0, %1, %2, %3, %4, %5, %6, %7, %8, %9, %10, %11, %12, %13, %14, %15, %16, %17, %18, %19, %20, %21, %22, %23, %24, %25, %26, %27, %28, %29, %30, %31}, %32, %33, p, 1, 1, %35, %36;\n}\n"
    : "+f"(d[0]), "+f"(d[1]), "+f"(d[2]), "+f"(d[3]), "+f"(d[4]), "+f"(d[5]), "+f"(d[6]), "+f"(d[7]), "+f"(d[8]), "+f"(d[9]), "+f"(d[10]), "+f"(d[11]), "+f"(d[12]), "+f"(d[13]), "+f"(d[14]), "+f"(d[15]), "+f"(d[16]), "+f"(d[17]), "+f"(d[18]), "+f"(d[19]), "+f"(d[20]), "+f"(d[21]), "+f"(d[22]), "+f"(d[23]), "+f"(d[24]), "+f"(d[25]), "+f"(d[26]), "+f"(d[27]), "+f"(d[28]), "+f"(d[29]), "+f"(d[30]), "+f"(d[31])
    : "l"(da), "l"(db), "r"(scale_d), "n"(TA), "n"(TB));
}
template <int TB>
__device__ __forceinline__ void wgmma_rs_n64(float (&d)[32], uint32_t a0, uint32_t a1, uint32_t a2, uint32_t a3, uint64_t db, int scale_d) {
  asm volatile("{\n.reg .pred p;\nsetp.ne.b32 p, %37, 0;\n"
    "wgmma.mma_async.sync.aligned.m64n64k16.f32.bf16.bf16 {%0, %1, %2, %3, %4, %5, %6, %7, %8, %9, %10, %11, %12, %13, %14, %15, %16, %17, %18, %19, %20, %21, %22, %23, %24, %25, %26, %27, %28, %29, %30, %31}, {%32, %33, %34, %35}, %36, p, 1, 1, %38;\n}\n"
    : "+f"(d[0]), "+f"(d[1]), "+f"(d[2]), "+f"(d[3]), "+f"(d[4]), "+f"(d[5]), "+f"(d[6]), "+f"(d[7]), "+f"(d[8]), "+f"(d[9]), "+f"(d[10]), "+f"(d[11]), "+f"(d[12]), "+f"(d[13]), "+f"(d[14]), "+f"(d[15]), "+f"(d[16]), "+f"(d[17]), "+f"(d[18]), "+f"(d[19]), "+f"(d[20]), "+f"(d[21]), "+f"(d[22]), "+f"(d[23]), "+f"(d[24]), "+f"(d[25]), "+f"(d[26]), "+f"(d[27]), "+f"(d[28]), "+f"(d[29]), "+f"(d[30]), "+f"(d[31])
    : "r"(a0), "r"(a1), "r"(a2), "r"(a3), "l"(db), "r"(scale_d), "n"(TB));
}
template <int TB, int TA = 0>
__device__ __forceinline__ void wgmma_ss_n128(float (&d)[64], uint64_t da, uint64_t db, int scale_d) {
  asm volatile("{\n.reg .pred p;\nsetp.ne.b32 p, %66, 0;\n"
    "wgmma.mma_async.sync.aligned.m64n128k16.f32.bf16.bf16 {%0, %1, %2, %3, %4, %5, %6, %7, %8, %9, %10, %11, %12, %13, %14, %15, %16, %17, %18, %19, %20, %21, %22, %23, %24, %25, %26, %27, %28, %29, %30, %31, %32, %33, %34, %35, %36, %37, %38, %39, %40, %41, %42, %43, %44, %45, %46, %47, %48, %49, %50, %51, %52, %53, %54, %55, %56, %57, %58, %59, %60, %61, %62, %63}, %64, %65, p, 1, 1, %67, %68;\n}\n"
    : "+f"(d[0]), "+f"(d[1]), "+f"(d[2]), "+f"(d[3]), "+f"(d[4]), "+f"(d[5]), "+f"(d[6]), "+f"(d[7]), "+f"(d[8]), "+f"(d[9]), "+f"(d[10]), "+f"(d[11]), "+f"(d[12]), "+f"(d[13]), "+f"(d[14]), "+f"(d[15]), "+f"(d[16]), "+f"(d[17]), "+f"(d[18]), "+f"(d[19]), "+f"(d[20]), "+f"(d[21]), "+f"(d[22]), "+f"(d[23]), "+f"(d[24]), "+f"(d[25]), "+f"(d[26]), "+f"(d[27]), "+f"(d[28]), "+f"(d[29]), "+f"(d[30]), "+f"(d[31]), "+f"(d[32]), "+f"(d[33]), "+f"(d[34]), "+f"(d[35]), "+f"(d[36]), "+f"(d[37]), "+f"(d[38]), "+f"(d[39]), "+f"(d[40]), "+f"(d[41]), "+f"(d[42]), "+f"(d[43]), "+f"(d[44]), "+f"(d[45]), "+f"(d[46]), "+f"(d[47]), "+f"(d[48]), "+f"(d[49]), "+f"(d[50]), "+f"(d[51]), "+f"(d[52]), "+f"(d[53]), "+f"(d[54]), "+f"(d[55]), "+f"(d[56]), "+f"(d[57]), "+f"(d[58]), "+f"(d[59]), "+f"(d[60]), "+f"(d[61]), "+f"(d[62]), "+f"(d[63])
    : "l"(da), "l"(db), "r"(scale_d), "n"(TA), "n"(TB));
}
template <int TB>
__device__ __forceinline__ void wgmma_rs_n128(float (&d)[64], uint32_t a0, uint32_t a1, uint32_t a2, uint32_t a3, uint64_t db, int scale_d) {
  asm volatile("{\n.reg .pred p;\nsetp.ne.b32 p, %69, 0;\n"
    "wgmma.mma_async.sync.aligned.m64n128k16.f32.bf16.bf16 {%0, %1, %2, %3, %4, %5, %6, %7, %8, %9, %10, %11, %12, %13, %14, %15, %16, %17, %18, %19, %20, %21, %22, %23, %24, %25, %26, %27, %28, %29, %30, %31, %32, %33, %34, %35, %36, %37, %38, %39, %40, %41, %42, %43, %44, %45, %46, %47, %48, %49, %50, %51, %52, %53, %54, %55, %56, %57, %58, %59, %60, %61, %62, %63}, {%64, %65, %66, %67}, %68, p, 1, 1, %70;\n}\n"
    : "+f"(d[0]), "+f"(d[1]), "+f"(d[2]), "+f"(d[3]), "+f"(d[4]), "+f"(d[5]), "+f"(d[6]), "+f"(d[7]), "+f"(d[8]), "+f"(d[9]), "+f"(d[10]), "+f"(d[11]), "+f"(d[12]), "+f"(d[13]), "+f"(d[14]), "+f"(d[15]), "+f"(d[16]), "+f"(d[17]), "+f"(d[18]), "+f"(d[19]), "+f"(d[20]), "+f"(d[21]), "+f"(d[22]), "+f"(d[23]), "+f"(d[24]), "+f"(d[25]), "+f"(d[26]), "+f"(d[27]), "+f"(d[28]), "+f"(d[29]), "+f"(d[30]), "+f"(d[31]), "+f"(d[32]), "+f"(d[33]), "+f"(d[34]), "+f"(d[35]), "+f"(d[36]), "+f"(d[37]), "+f"(d[38]), "+f"(d[39]), "+f"(d[40]), "+f"(d[41]), "+f"(d[42]), "+f"(d[43]), "+f"(d[44]), "+f"(d[45]), "+f"(d[46]), "+f"(d[47]), "+f"(d[48]), "+f"(d[49]), "+f"(d[50]), "+f"(d[51]), "+f"(d[52]), "+f"(d[53]), "+f"(d[54]), "+f"(d[55]), "+f"(d[56]), "+f"(d[57]), "+f"(d[58]), "+f"(d[59]), "+f"(d[60]), "+f"(d[61]), "+f"(d[62]), "+f"(d[63])
    : "r"(a0), "r"(a1), "r"(a2), "r"(a3), "l"(db), "r"(scale_d), "n"(TB));
}
template <int TB, int TA = 0>
__device__ __forceinline__ void wgmma_ss_n160(float (&d)[80], uint64_t da, uint64_t db, int scale_d) {
  asm volatile("{\n.reg .pred p;\nsetp.ne.b32 p, %82, 0;\n"
    "wgmma.mma_async.sync.aligned.m64n160k16.f32.bf16.bf16 {%0, %1, %2, %3, %4, %5, %6, %7, %8, %9, %10, %11, %12, %13, %14, %15, %16, %17, %18, %19, %20, %21, %22, %23, %24, %25, %26, %27, %28, %29, %30, %31, %32, %33, %34, %35, %36, %37, %38, %39, %40, %41, %42, %43, %44, %45, %46, %47, %48, %49, %50, %51, %52, %53, %54, %55, %56, %57, %58, %59, %60, %61, %62, %63, %64, %65, %66, %67, %68, %69, %70, %71, %72, %73, %74, %75, %76, %77, %78, %79}, %80, %81, p, 1, 1, %83, %84;\n}\n"
    : "+f"(d[0]), "+f"(d[1]), "+f"(d[2]), "+f"(d[3]), "+f"(d[4]), "+f"(d[5]), "+f"(d[6]), "+f"(d[7]), "+f"(d[8]), "+f"(d[9]), "+f"(d[10]), "+f"(d[11]), "+f"(d[12]), "+f"(d[13]), "+f"(d[14]), "+f"(d[15]), "+f"(d[16]), "+f"(d[17]), "+f"(d[18]), "+f"(d[19]), "+f"(d[20]), "+f"(d[21]), "+f"(d[22]), "+f"(d[23]), "+f"(d[24]), "+f"(d[25]), "+f"(d[26]), "+f"(d[27]), "+f"(d[28]), "+f"(d[29]), "+f"(d[30]), "+f"(d[31]), "+f"(d[32]), "+f"(d[33]), "+f"(d[34]), "+f"(d[35]), "+f"(d[36]), "+f"(d[37]), "+f"(d[38]), "+f"(d[39]), "+f"(d[40]), "+f"(d[41]), "+f"(d[42]), "+f"(d[43]), "+f"(d[44]), "+f"(d[45]), "+f"(d[46]), "+f"(d[47]), "+f"(d[48]), "+f"(d[49]), "+f"(d[50]), "+f"(d[51]), "+f"(d[52]), "+f"(d[53]), "+f"(d[54]), "+f"(d[55]), "+f"(d[56]), "+f"(d[57]), "+f"(d[58]), "+f"(d[59]), "+f"(d[60]), "+f"(d[61]), "+f"(d[62]), "+f"(d[63]), "+f"(d[64]), "+f"(d[65]), "+f"(d[66]), "+f"(d[67]), "+f"(d[68]), "+f"(d[69]), "+f"(d[70]), "+f"(d[71]), "+f"(d[72]), "+f"(d[73]), "+f"(d[74]), "+f"(d[75]), "+f"(d[76]), "+f"(d[77]), "+f"(d[78]), "+f"(d[79])
    : "l"(da), "l"(db), "r"(scale_d), "n"(TA), "n"(TB));
}
template <int TB>
__device__ __forceinline__ void wgmma_rs_n160(float (&d)[80], uint32_t a0, uint32_t a1, uint32_t a2, uint32_t a3, uint64_t db, int scale_d) {
  asm volatile("{\n.reg .pred p;\nsetp.ne.b32 p, %85, 0;\n"
    "wgmma.mma_async.sync.aligned.m64n160k16.f32.bf16.bf16 {%0, %1, %2, %3, %4, %5, %6, %7, %8, %9, %10, %11, %12, %13, %14, %15, %16, %17, %18, %19, %20, %21, %22, %23, %24, %25, %26, %27, %28, %29, %30, %31, %32, %33, %34, %35, %36, %37, %38, %39, %40, %41, %42, %43, %44, %45, %46, %47, %48, %49, %50, %51, %52, %53, %54, %55, %56, %57, %58, %59, %60, %61, %62, %63, %64, %65, %66, %67, %68, %69, %70, %71, %72, %73, %74, %75, %76, %77, %78, %79}, {%80, %81, %82, %83}, %84, p, 1, 1, %86;\n}\n"
    : "+f"(d[0]), "+f"(d[1]), "+f"(d[2]), "+f"(d[3]), "+f"(d[4]), "+f"(d[5]), "+f"(d[6]), "+f"(d[7]), "+f"(d[8]), "+f"(d[9]), "+f"(d[10]), "+f"(d[11]), "+f"(d[12]), "+f"(d[13]), "+f"(d[14]), "+f"(d[15]), "+f"(d[16]), "+f"(d[17]), "+f"(d[18]), "+f"(d[19]), "+f"(d[20]), "+f"(d[21]), "+f"(d[22]), "+f"(d[23]), "+f"(d[24]), "+f"(d[25]), "+f"(d[26]), "+f"(d[27]), "+f"(d[28]), "+f"(d[29]), "+f"(d[30]), "+f"(d[31]), "+f"(d[32]), "+f"(d[33]), "+f"(d[34]), "+f"(d[35]), "+f"(d[36]), "+f"(d[37]), "+f"(d[38]), "+f"(d[39]), "+f"(d[40]), "+f"(d[41]), "+f"(d[42]), "+f"(d[43]), "+f"(d[44]), "+f"(d[45]), "+f"(d[46]), "+f"(d[47]), "+f"(d[48]), "+f"(d[49]), "+f"(d[50]), "+f"(d[51]), "+f"(d[52]), "+f"(d[53]), "+f"(d[54]), "+f"(d[55]), "+f"(d[56]), "+f"(d[57]), "+f"(d[58]), "+f"(d[59]), "+f"(d[60]), "+f"(d[61]), "+f"(d[62]), "+f"(d[63]), "+f"(d[64]), "+f"(d[65]), "+f"(d[66]), "+f"(d[67]), "+f"(d[68]), "+f"(d[69]), "+f"(d[70]), "+f"(d[71]), "+f"(d[72]), "+f"(d[73]), "+f"(d[74]), "+f"(d[75]), "+f"(d[76]), "+f"(d[77]), "+f"(d[78]), "+f"(d[79])
    : "r"(a0), "r"(a1), "r"(a2), "r"(a3), "l"(db), "r"(scale_d), "n"(TB));
}
template <int TB, int TA = 0>
__device__ __forceinline__ void wgmma_ss_n192(float (&d)[96], uint64_t da, uint64_t db, int scale_d) {
  asm volatile("{\n.reg .pred p;\nsetp.ne.b32 p, %98, 0;\n"
    "wgmma.mma_async.sync.aligned.m64n192k16.f32.bf16.bf16 {%0, %1, %2, %3, %4, %5, %6, %7, %8, %9, %10, %11, %12, %13, %14, %15, %16, %17, %18, %19, %20, %21, %22, %23, %24, %25, %26, %27, %28, %29, %30, %31, %32, %33, %34, %35, %36, %37, %38, %39, %40, %41, %42, %43, %44, %45, %46, %47, %48, %49, %50, %51, %52, %53, %54, %55, %56, %57, %58, %59, %60, %61, %62, %63, %64, %65, %66, %67, %68, %69, %70, %71, %72, %73, %74, %75, %76, %77, %78, %79, %80, %81, %82, %83, %84, %85, %86, %87, %88, %89, %90, %91, %92, %93, %94, %95}, %96, %97, p, 1, 1, %99, %100;\n}\n"
    : "+f"(d[0]), "+f"(d[1]), "+f"(d[2]), "+f"(d[3]), "+f"(d[4]), "+f"(d[5]), "+f"(d[6]), "+f"(d[7]), "+f"(d[8]), "+f"(d[9]), "+f"(d[10]), "+f"(d[11]), "+f"(d[12]), "+f"(d[13]), "+f"(d[14]), "+f"(d[15]), "+f"(d[16]), "+f"(d[17]), "+f"(d[18]), "+f"(d[19]), "+f"(d[20]), "+f"(d[21]), "+f"(d[22]), "+f"(d[23]), "+f"(d[24]), "+f"(d[25]), "+f"(d[26]), "+f"(d[27]), "+f"(d[28]), "+f"(d[29]), "+f"(d[30]), "+f"(d[31]), "+f"(d[32]), "+f"(d[33]), "+f"(d[34]), "+f"(d[35]), "+f"(d[36]), "+f"(d[37]), "+f"(d[38]), "+f"(d[39]), "+f"(d[40]), "+f"(d[41]), "+f"(d[42]), "+f"(d[43]), "+f"(d[44]), "+f"(d[45]), "+f"(d[46]), "+f"(d[47]), "+f"(d[48]), "+f"(d[49]), "+f"(d[50]), "+f"(d[51]), "+f"(d[52]), "+f"(d[53]), "+f"(d[54]), "+f"(d[55]), "+f"(d[56]), "+f"(d[57]), "+f"(d[58]), "+f"(d[59]), "+f"(d[60]), "+f"(d[61]), "+f"(d[62]), "+f"(d[63]), "+f"(d[64]), "+f"(d[65]), "+f"(d[66]), "+f"(d[67]), "+f"(d[68]), "+f"(d[69]), "+f"(d[70]), "+f"(d[71]), "+f"(d[72]), "+f"(d[73]), "+f"(d[74]), "+f"(d[75]), "+f"(d[76]), "+f"(d[77]), "+f"(d[78]), "+f"(d[79]), "+f"(d[80]), "+f"(d[81]), "+f"(d[82]), "+f"(d[83]), "+f"(d[84]), "+f"(d[85]), "+f"(d[86]), "+f"(d[87]), "+f"(d[88]), "+f"(d[89]), "+f"(d[90]), "+f"(d[91]), "+f"(d[92]), "+f"(d[93]), "+f"(d[94]), "+f"(d[95])
    : "l"(da), "l"(db), "r"(scale_d), "n"(TA), "n"(TB));
}
template <int TB>
__device__ __forceinline__ void wgmma_rs_n192(float (&d)[96], uint32_t a0, uint32_t a1, uint32_t a2, uint32_t a3, uint64_t db, int scale_d) {
  asm volatile("{\n.reg .pred p;\nsetp.ne.b32 p, %101, 0;\n"
    "wgmma.mma_async.sync.aligned.m64n192k16.f32.bf16.bf16 {%0, %1, %2, %3, %4, %5, %6, %7, %8, %9, %10, %11, %12, %13, %14, %15, %16, %17, %18, %19, %20, %21, %22, %23, %24, %25, %26, %27, %28, %29, %30, %31, %32, %33, %34, %35, %36, %37, %38, %39, %40, %41, %42, %43, %44, %45, %46, %47, %48, %49, %50, %51, %52, %53, %54, %55, %56, %57, %58, %59, %60, %61, %62, %63, %64, %65, %66, %67, %68, %69, %70, %71, %72, %73, %74, %75, %76, %77, %78, %79, %80, %81, %82, %83, %84, %85, %86, %87, %88, %89, %90, %91, %92, %93, %94, %95}, {%96, %97, %98, %99}, %100, p, 1, 1, %102;\n}\n"
    : "+f"(d[0]), "+f"(d[1]), "+f"(d[2]), "+f"(d[3]), "+f"(d[4]), "+f"(d[5]), "+f"(d[6]), "+f"(d[7]), "+f"(d[8]), "+f"(d[9]), "+f"(d[10]), "+f"(d[11]), "+f"(d[12]), "+f"(d[13]), "+f"(d[14]), "+f"(d[15]), "+f"(d[16]), "+f"(d[17]), "+f"(d[18]), "+f"(d[19]), "+f"(d[20]), "+f"(d[21]), "+f"(d[22]), "+f"(d[23]), "+f"(d[24]), "+f"(d[25]), "+f"(d[26]), "+f"(d[27]), "+f"(d[28]), "+f"(d[29]), "+f"(d[30]), "+f"(d[31]), "+f"(d[32]), "+f"(d[33]), "+f"(d[34]), "+f"(d[35]), "+f"(d[36]), "+f"(d[37]), "+f"(d[38]), "+f"(d[39]), "+f"(d[40]), "+f"(d[41]), "+f"(d[42]), "+f"(d[43]), "+f"(d[44]), "+f"(d[45]), "+f"(d[46]), "+f"(d[47]), "+f"(d[48]), "+f"(d[49]), "+f"(d[50]), "+f"(d[51]), "+f"(d[52]), "+f"(d[53]), "+f"(d[54]), "+f"(d[55]), "+f"(d[56]), "+f"(d[57]), "+f"(d[58]), "+f"(d[59]), "+f"(d[60]), "+f"(d[61]), "+f"(d[62]), "+f"(d[63]), "+f"(d[64]), "+f"(d[65]), "+f"(d[66]), "+f"(d[67]), "+f"(d[68]), "+f"(d[69]), "+f"(d[70]), "+f"(d[71]), "+f"(d[72]), "+f"(d[73]), "+f"(d[74]), "+f"(d[75]), "+f"(d[76]), "+f"(d[77]), "+f"(d[78]), "+f"(d[79]), "+f"(d[80]), "+f"(d[81]), "+f"(d[82]), "+f"(d[83]), "+f"(d[84]), "+f"(d[85]), "+f"(d[86]), "+f"(d[87]), "+f"(d[88]), "+f"(d[89]), "+f"(d[90]), "+f"(d[91]), "+f"(d[92]), "+f"(d[93]), "+f"(d[94]), "+f"(d[95])
    : "r"(a0), "r"(a1), "r"(a2), "r"(a3), "l"(db), "r"(scale_d), "n"(TB));
}

__device__ __forceinline__ uint32_t smem_u32(const void* p) { return (uint32_t)__cvta_generic_to_shared(p); }
__device__ __forceinline__ void wg_fence() { asm volatile("wgmma.fence.sync.aligned;" ::: "memory"); }
__device__ __forceinline__ void wg_commit() { asm volatile("wgmma.commit_group.sync.aligned;" ::: "memory"); }
template <int N> __device__ __forceinline__ void wg_wait() { asm volatile("wgmma.wait_group.sync.aligned %0;" ::"n"(N) : "memory"); }
__device__ __forceinline__ void sched_fence(uint32_t& keep, bool never) {
  asm volatile("{\n.reg .pred p;\nsetp.ne.b32 p, %1, 0;\n@p mov.u32 %0, %%clock;\n}\n" : "+r"(keep) : "r"((int)never) : "memory");
}
template <int N> __device__ __forceinline__ void fence_regs(float (&r)[N]) {
#pragma unroll
  for (int i = 0; i < N; i++) asm volatile("" : "+f"(r[i])::"memory");
}
template <int N> __device__ __forceinline__ void undefine(float (&r)[N]) {
#pragma unroll
  for (int i = 0; i < N; i++) asm volatile("" : "=f"(r[i]));
}
template <int N> __device__ __forceinline__ void fence_regs(uint32_t (&r)[N]) {
#pragma unroll
  for (int i = 0; i < N; i++) asm volatile("" : "+r"(r[i])::"memory");
}
__device__ __forceinline__ uint64_t mk_desc(uint32_t a16, uint32_t lbo, uint32_t sbo, uint32_t swz) {
  uint64_t d;
  asm("mov.b64 %0, {%1, %2};" : "=l"(d) : "r"(a16 + ((lbo >> 4) << 16)), "r"((sbo >> 4) | (swz << 30)));
  return d;
}
__device__ __forceinline__ void mbar_init(uint32_t bar, uint32_t cnt) {
  asm volatile("mbarrier.init.shared::cta.b64 [%0], %1;" ::"r"(bar), "r"(cnt) : "memory");
}
__device__ __forceinline__ void mbar_expect(uint32_t bar, uint32_t tx) {
  asm volatile("mbarrier.arrive.expect_tx.shared::cta.b64 _, [%0], %1;" ::"r"(bar), "r"(tx) : "memory");
}
__device__ __forceinline__ bool mbar_test(uint32_t bar, uint32_t ph) {
  uint32_t ok;
  asm volatile("{\n.reg .pred p;\nmbarrier.test_wait.parity.shared::cta.b64 p, [%1], %2;\nselp.u32 %0, 1, 0, p;\n}\n"
               : "=r"(ok) : "r"(bar), "r"(ph) : "memory");
  return ok;
}
__device__ __forceinline__ bool mbar_try(uint32_t bar, uint32_t ph, uint32_t ns) {
  uint32_t ok;
  asm volatile("{\n.reg .pred p;\nmbarrier.try_wait.parity.shared::cta.b64 p, [%1], %2, %3;\nselp.u32 %0, 1, 0, p;\n}\n"
               : "=r"(ok) : "r"(bar), "r"(ph), "r"(ns) : "memory");
  return ok;
}
__device__ __forceinline__ void mbar_wait(uint32_t bar, uint32_t ph) {
  asm volatile("{\n.reg .pred p;\n.reg .u32 n;\nmov.u32 n, 0;\n"
               "LOOP:\nmbarrier.try_wait.parity.shared::cta.b64 p, [%0], %1;\n@p bra DONE;\n"
               "add.u32 n, n, 1;\nsetp.lt.u32 p, n, 0x1000000;\n@p bra LOOP;\ntrap;\n"
               "DONE:\n}\n" ::"r"(bar), "r"(ph) : "memory");
}
__device__ __forceinline__ void mbar_wait_long(uint32_t bar) {
  asm volatile("{\n.reg .pred p;\n.reg .u32 n;\nmov.u32 n, 0;\n"
               "LOOP:\nmbarrier.try_wait.parity.shared::cta.b64 p, [%0], 0, 20000;\n@p bra DONE;\n"
               "add.u32 n, n, 1;\nsetp.lt.u32 p, n, 0x100000;\n@p bra LOOP;\ntrap;\n"
               "DONE:\n}\n" ::"r"(bar) : "memory");
}
__device__ __forceinline__ void mbar_arrive_cluster_if(bool on, uint32_t addr) {
  asm volatile("{\n.reg .pred p;\nsetp.ne.b32 p, %1, 0;\n@p mbarrier.arrive.shared::cluster.b64 _, [%0];\n}\n" ::"r"(addr), "r"((int)on) : "memory");
}
__device__ __forceinline__ void mbar_arrive_cluster_n(uint32_t n, uint32_t addr) {
  asm volatile("{\n.reg .pred p;\nsetp.ne.b32 p, %1, 0;\n@p mbarrier.arrive.shared::cluster.b64 _, [%0], %1;\n}\n" ::"r"(addr), "r"(n) : "memory");
}
__device__ __forceinline__ void tma2d(uint32_t dst, const CUtensorMap* m, uint32_t bar, int c0, int c1) {
  asm volatile("cp.async.bulk.tensor.2d.shared::cluster.global.mbarrier::complete_tx::bytes [%0], [%1, {%3, %4}], [%2];"
               ::"r"(dst), "l"(m), "r"(bar), "r"(c0), "r"(c1) : "memory");
}
__device__ __forceinline__ void tma3d(uint32_t dst, const CUtensorMap* m, uint32_t bar, int c0, int c1, int c2) {
  asm volatile("cp.async.bulk.tensor.3d.shared::cluster.global.mbarrier::complete_tx::bytes [%0], [%1, {%3, %4, %5}], [%2];"
               ::"r"(dst), "l"(m), "r"(bar), "r"(c0), "r"(c1), "r"(c2) : "memory");
}
__device__ __forceinline__ void tma2d_hint(uint32_t dst, const CUtensorMap* m, uint32_t bar, int c0, int c1, uint64_t pol) {
  asm volatile("cp.async.bulk.tensor.2d.shared::cluster.global.mbarrier::complete_tx::bytes.L2::cache_hint [%0], [%1, {%3, %4}], [%2], %5;"
               ::"r"(dst), "l"(m), "r"(bar), "r"(c0), "r"(c1), "l"(pol) : "memory");
}
__device__ __forceinline__ void tma3d_mc_hint(uint32_t dst, const CUtensorMap* m, uint32_t bar, int c1, int c2, uint64_t pol) {
  asm volatile("cp.async.bulk.tensor.3d.shared::cluster.global.mbarrier::complete_tx::bytes.multicast::cluster.L2::cache_hint"
               " [%0], [%1, {%3, %4, %5}], [%2], %6, %7;"
               ::"r"(dst), "l"(m), "r"(bar), "r"(0), "r"(c1), "r"(c2), "h"((uint16_t)3), "l"(pol) : "memory");
}
__device__ __forceinline__ void tma5d_mc_hint(uint32_t dst, const CUtensorMap* m, uint32_t bar, int c2, int c4, uint64_t pol) {
  asm volatile("cp.async.bulk.tensor.5d.shared::cluster.global.mbarrier::complete_tx::bytes.multicast::cluster.L2::cache_hint"
               " [%0], [%1, {%3, %3, %4, %3, %5}], [%2], %6, %7;"
               ::"r"(dst), "l"(m), "r"(bar), "r"(0), "r"(c2), "r"(c4), "h"((uint16_t)3), "l"(pol) : "memory");
}
__device__ __forceinline__ void tma3d_store(const CUtensorMap* m, uint32_t src, int c0, int c1, int c2) {
  asm volatile("cp.async.bulk.tensor.3d.global.shared::cta.bulk_group [%0, {%2, %3, %4}], [%1];"
               ::"l"(m), "r"(src), "r"(c0), "r"(c1), "r"(c2) : "memory");
}
__device__ __forceinline__ void bar_sync(int id, int n) { asm volatile("bar.sync %0, %1;" ::"r"(id), "r"(n) : "memory"); }
__device__ __forceinline__ uint32_t pack_bf16(float lo, float hi) {
  uint32_t r;
  asm("cvt.rn.bf16x2.f32 %0, %1, %2;" : "=r"(r) : "f"(hi), "f"(lo));
  return r;
}
__device__ __forceinline__ float ex2(float x) {
  float y;
  asm("ex2.approx.ftz.f32 %0, %1;" : "=f"(y) : "f"(x));
  return y;
}
__device__ __forceinline__ float rcp(float x) {
  float y;
  asm("rcp.approx.ftz.f32 %0, %1;" : "=f"(y) : "f"(x));
  return y;
}
__device__ __forceinline__ void stsm4(uint32_t addr, uint32_t a, uint32_t b, uint32_t c, uint32_t d) {
  asm volatile("stmatrix.sync.aligned.m8n8.x4.shared.b16 [%0], {%1, %2, %3, %4};" ::"r"(addr), "r"(a), "r"(b), "r"(c), "r"(d) : "memory");
}

__device__ __forceinline__ void tma4d_mc_hint(uint32_t dst, const CUtensorMap* m, uint32_t bar, int c3, uint64_t pol) {
  asm volatile("cp.async.bulk.tensor.4d.shared::cluster.global.mbarrier::complete_tx::bytes.multicast::cluster.L2::cache_hint"
               " [%0], [%1, {%3, %3, %3, %4}], [%2], %5, %6;"
               ::"r"(dst), "l"(m), "r"(bar), "r"(0), "r"(c3), "h"((uint16_t)3), "l"(pol) : "memory");
}
__device__ __forceinline__ void bulk_load_hint(uint32_t dst, const void* src, uint32_t bytes, uint32_t bar, uint64_t pol) {
  asm volatile("cp.async.bulk.shared::cluster.global.mbarrier::complete_tx::bytes.L2::cache_hint [%0], [%1], %2, [%3], %4;"
               ::"r"(dst), "l"(src), "r"(bytes), "r"(bar), "l"(pol) : "memory");
}
__device__ __forceinline__ void stg2_if(bool on, void* p, uint32_t a, uint32_t b, uint32_t c, uint32_t d, uint32_t e, uint32_t f,
                                        uint32_t g, uint32_t h, uint64_t pol) {
  asm volatile("{\n.reg .pred p;\nsetp.ne.b32 p, %10, 0;\n"
               "@p st.global.L2::cache_hint.v4.b32 [%0], {%1, %2, %3, %4}, %9;\n"
               "@p st.global.L2::cache_hint.v4.b32 [%0 + 512], {%5, %6, %7, %8}, %9;\n}\n"
               ::"l"(p), "r"(a), "r"(b), "r"(c), "r"(d), "r"(e), "r"(f), "r"(g), "r"(h), "l"(pol), "r"((int)on) : "memory");
}
__device__ __forceinline__ uint64_t evict_first() {
  uint64_t p;
  asm("createpolicy.fractional.L2::evict_first.b64 %0, 1.0;" : "=l"(p));
  return p;
}
__device__ __forceinline__ uint64_t no_hint() {
  uint64_t p;
  asm("createpolicy.cvt.L2.b64 %0, %1;" : "=l"(p) : "l"(static_cast<uint64_t>(cuda::access_property{})));
  return p;
}
__device__ __forceinline__ bool elect() {
  uint32_t ok;
  asm volatile("{\n.reg .pred p;\nelect.sync _|p, 0xffffffff;\nselp.u32 %0, 1, 0, p;\n}\n" : "=r"(ok));
  return ok;
}
__device__ __forceinline__ void mbar_arrive(uint32_t bar) {
  asm volatile("mbarrier.arrive.shared::cta.b64 _, [%0];" ::"r"(bar) : "memory");
}
__device__ __forceinline__ void mbar_arrive_if(bool on, uint32_t bar) {
  asm volatile("{\n.reg .pred p;\nsetp.ne.b32 p, %1, 0;\n@p mbarrier.arrive.shared::cta.b64 _, [%0];\n}\n" ::"r"(bar), "r"((int)on) : "memory");
}
__device__ __forceinline__ void lds2_if(bool on, uint32_t p, uint32_t (&t)[8]) {
  asm volatile("{\n.reg .pred p;\nsetp.ne.b32 p, %9, 0;\n@p ld.shared.v4.b32 {%0, %1, %2, %3}, [%8];\n@p ld.shared.v4.b32 {%4, %5, %6, %7}, [%8 + 512];\n}\n"
               : "+r"(t[0]), "+r"(t[1]), "+r"(t[2]), "+r"(t[3]), "+r"(t[4]), "+r"(t[5]), "+r"(t[6]), "+r"(t[7]) : "r"(p), "r"((int)on) : "memory");
}
__device__ __forceinline__ void lds128(uint32_t p, uint32_t& a, uint32_t& b, uint32_t& c, uint32_t& d) {
  asm volatile("ld.shared.v4.b32 {%0, %1, %2, %3}, [%4];" : "=r"(a), "=r"(b), "=r"(c), "=r"(d) : "r"(p) : "memory");
}
template <class T> __device__ __forceinline__ T* ptr_add(T* base, uint32_t bytes) {
  T* r;
  asm("{\n.reg .u32 lo, hi;\nmov.b64 {lo, hi}, %1;\nadd.cc.u32 lo, lo, %2;\naddc.u32 hi, hi, 0;\nmov.b64 %0, {lo, hi};\n}\n" : "=l"(r) : "l"(base), "r"(bytes));
  return r;
}
__device__ __forceinline__ uint32_t lds32(uint32_t p) {
  uint32_t v;
  asm volatile("ld.volatile.shared.u32 %0, [%1];" : "=r"(v) : "r"(p) : "memory");
  return v;
}
__device__ __forceinline__ uint32_t flag_get(const unsigned int* p) {
  uint32_t v;
  asm volatile("ld.acquire.gpu.global.u32 %0, [%1];" : "=r"(v) : "l"(p) : "memory");
  return v;
}
__device__ __forceinline__ uint32_t wait_word(uint32_t p, uint32_t target) {
  uint32_t v;
  asm volatile("{\n.reg .pred p;\n.reg .u32 n;\nmov.u32 n, 0;\n"
               "LOOP:\nld.acquire.cta.shared.u32 %0, [%1];\nsetp.ge.u32 p, %0, %2;\n@p bra DONE;\n"
               "nanosleep.u32 %3;\nadd.u32 n, n, 1;\nsetp.lt.u32 p, n, 0x400000;\n@p bra LOOP;\ntrap;\n"
               "DONE:\n}\n" : "=r"(v) : "r"(p), "r"(target), "n"(400) : "memory");
  return v;
}
__device__ __forceinline__ void flag_set(unsigned int* p, uint32_t v) {
  asm volatile("st.release.gpu.global.u32 [%0], %1;" ::"l"(p), "r"(v) : "memory");
}
__device__ __forceinline__ void flag_dec(unsigned int* p) {
  asm volatile("red.relaxed.gpu.global.add.u32 [%0], 0xffffffff;" ::"l"(p) : "memory");
}

struct Cursor {
  uint32_t n;
  __device__ __forceinline__ uint32_t off() const { return n & (8 * NBAR - 8); }
  __device__ __forceinline__ uint32_t ph() const { return (n / (8 * NBAR)) & 1; }
  __device__ __forceinline__ void next() { n += 8; }
};

constexpr float kScaleLog2 = 0.07216878364870322f * 1.4426950408889634f;
constexpr float kSumLimit = 1048576.0f;

__global__ void __cluster_dims__(2, 1, 1) __launch_bounds__(384, 1)
fused_kernel(const __grid_constant__ Params P) {
  extern __shared__ uint8_t smem_raw[];
  const uint32_t sbase = (smem_u32(smem_raw) + 1023) & ~1023u;
  const uint32_t full0 = sbase + RING, empty0 = full0 + 8 * NBAR, odone0 = empty0 + 8 * NBAR, ev0 = odone0 + 8 * MAX_OPS;
  const uint32_t progress = ev0 + 8 * MAX_EV, jobw = progress + 4;
  const uint32_t rank = blockIdx.x & 1;
  const int role = blockIdx.x >> 1;
  const int wid = __shfl_sync(0xffffffffu, (int)(threadIdx.x >> 5), 0);
  const int wg = wid >> 2;

  if (wid < 8) {
    if (elect()) {
#pragma unroll
      for (int j = 0; j < 16; j++) {
        const int i = EARLY + 16 * wid + j;
        if (i < 2 * NBAR + MAX_OPS + MAX_EV) mbar_init(full0 + 8 * i, i < NBAR ? 1 : i < 2 * NBAR ? 16 : i < 2 * NBAR + MAX_OPS ? 8 : 1);
      }
      if (wid == 7) asm volatile("st.shared.v2.u32 [%0], {0, 0};\nfence.acq_rel.cta;" ::"r"(progress) : "memory");
      asm volatile("fence.mbarrier_init.release.cluster;" ::: "memory");
    }
  } else if (wid > 8) {
    const uint32_t g = blockIdx.x * 96 + threadIdx.x - 288, w = g - 2048;
    if (g < 4096) asm volatile("prefetch.global.L2 [%0];" ::"l"(g < 2048 ? P.xw[0] + g * (kD * 2) : P.xw[1] + (w >> 5) * (kHD * 2) + (w & 31) * 128));
  } else {
    const uint32_t op0 = P.first[role];
    if (elect()) {
#pragma unroll
      for (int k = 0; k < EARLY; k++) mbar_init(full0 + 8 * k, 1);
      asm volatile("fence.mbarrier_init.release.cluster;" ::: "memory");
      const int blk = (op0 >> 10) & 1;
      if ((op0 & 3) == OP_Q) {
#pragma unroll
        for (int k = 0; k < EARLY; k++) {
          mbar_expect(full0 + 8 * k, SZ_Q);
          tma2d(sbase + k * SZ_Q, &P.x[blk], full0 + 8 * k, 64 * k, ((op0 >> 7) & 7) * kSq + rank * 128);
          tma3d(sbase + k * SZ_Q + 16384, &P.wq[blk], full0 + 8 * k, 0, 64 * k, 3 * ((op0 >> 2) & 31));
          tma3d(sbase + k * SZ_Q + 28672, &P.wq[blk], full0 + 8 * k, 0, 64 * k + 32, 3 * ((op0 >> 2) & 31));
        }
      }
      asm volatile("prefetch.tensormap [%0];\nprefetch.tensormap [%1];" ::"l"(&P.k[blk]), "l"(&P.v[blk]) : "memory");
    }
  }
  __syncwarp();
  asm volatile("barrier.cluster.arrive.relaxed.aligned;\nbarrier.cluster.wait.aligned;" ::: "memory");

  if (wg < 2) {
    asm volatile("setmaxnreg.inc.sync.aligned.u32 240;");
    const uint32_t* prog = P.prog[role].c;
    const int wid = __shfl_sync(0xffffffffu, (int)(threadIdx.x >> 5), 1), wg = wid >> 2;
    const int lane = threadIdx.x & 31, warp = wid & 3;
    uint32_t empty_rem;
    asm volatile("mapa.shared::cluster.u32 %0, %1, %2;" : "=r"(empty_rem) : "r"(empty0), "r"(lane & 1));
    uint32_t keep = (threadIdx.x & 127) < 2 ? 4 : 0;
    auto release = [&](int slot) { mbar_arrive_cluster_n(keep, empty_rem + slot); };
    auto release_warp = [&](int slot, bool on = true) { mbar_arrive_cluster_if(lane < 2 && on, empty_rem + slot); };
    Cursor r{0};
    const uint32_t ring16 = (sbase & 0x3FFFF) >> 4;
    uint32_t cur = ring16;
    bool rdy0 = false, rdy1 = false;
    auto probe1 = [&]() { rdy0 = mbar_test(full0 + r.off(), r.ph()); };
    auto probe2 = [&]() {
      Cursor n = r;
      rdy0 = mbar_test(full0 + n.off(), n.ph());
      n.next();
      rdy1 = mbar_test(full0 + n.off(), n.ph());
    };
    auto advance = [&](uint32_t bytes, uint32_t& addr) {
      const int bi = r.off();
      r.next();
      if (cur > ring16 + ((RING - bytes) >> 4)) cur = ring16;
      addr = cur;
      cur += bytes >> 4;
      return bi;
    };
    auto take = [&](bool rdy, uint32_t bytes, uint32_t& addr) {
      if (__builtin_expect(!__all_sync(0xffffffffu, rdy), 0)) mbar_wait(full0 + r.off(), r.ph());
      return advance(bytes, addr);
    };
    const bool never = P.dbg == 0xffffffffu;
    uint32_t q[48];
#pragma unroll
    for (int i = 0; i < 48; i++) q[i] = 0;
    const int row = wg * 64 + warp * 16 + (lane >> 2);
    const int img0 = row * 4 + ((lane & 3) ^ ((row >> 1) & 3));
    uint4* pend = nullptr;
    bool pend_any = false;
    const uint64_t spol = evict_first();
    int pc = 0;
    auto slab = [&](int c, int i0) {
#pragma unroll
      for (int i = i0; i < 6; i++)
        stg2_if(c == i, pend + i * 512, q[8 * i], q[8 * i + 1], q[8 * i + 2], q[8 * i + 3],
                q[8 * i + 4], q[8 * i + 5], q[8 * i + 6], q[8 * i + 7], spol);
    };
    auto drain = [&](int c) {
      if (!pend_any || c >= 6) return;
      slab(c, 0);
      if (c == 5) {
        __syncwarp();
        mbar_arrive_if(lane == 0, odone0 - 8 + 8 * pc);
      }
    };

    for (;; pc++) {
      uint32_t op = prog[pc];
      const int type = op & 3;
      auto enter = [&]() {
        r.n = (op >> 12) & 248; cur = ring16 + (((op >> 20) & 63) << 8);
      };
      enter();
      pend_any = op & C_PEND;
      uint32_t job = 0;
      if ((op & (3 | C_WIDE)) == OP_O) job = __shfl_sync(0xffffffffu, wait_word(jobw, 1), 0);
      if (type == OP_END || job == OP_O) {
#pragma unroll 1
        for (int c = 0; c < 6; c++) drain(c);
        asm volatile("barrier.cluster.arrive.relaxed;" ::: "memory");
        break;
      }
      {
        float s[32], o[96];
        uint32_t ad0;
        int bi0, sk1;
        uint32_t pa[16], pb[16];
        float mc0, mc1, l0, l1;
        bool shifted;
        uint32_t nop;
        auto expo = [&](float (&s)[32], uint32_t (&pout)[16], float& b0, float& b1, bool shift, auto mid) {
          float c0, c1;
#pragma unroll
          for (int i = 0; i < 8; i++) {
            const float e0 = ex2(shift ? s[4 * i] - mc0 : s[4 * i]), e1 = ex2(shift ? s[4 * i + 1] - mc0 : s[4 * i + 1]);
            const float e2 = ex2(shift ? s[4 * i + 2] - mc1 : s[4 * i + 2]), e3 = ex2(shift ? s[4 * i + 3] - mc1 : s[4 * i + 3]);
            if (i) { b0 += e0; c0 += e1; b1 += e2; c1 += e3; } else { b0 = e0; c0 = e1; b1 = e2; c1 = e3; }
            pout[2 * i] = pack_bf16(e0, e1); pout[2 * i + 1] = pack_bf16(e2, e3);
            if (i & 1) mid(i >> 1);
          }
          b0 += c0; b1 += c1;
        };
        auto rowmax = [&](float (&s)[32], float& m0, float& m1) {
          m0 = fmaxf(s[0], s[1]); m1 = fmaxf(s[2], s[3]);
#pragma unroll
          for (int i = 1; i < 8; i++) { m0 = fmaxf(m0, fmaxf(s[4 * i], s[4 * i + 1])); m1 = fmaxf(m1, fmaxf(s[4 * i + 2], s[4 * i + 3])); }
          m0 = fmaxf(m0, __shfl_xor_sync(0xffffffffu, m0, 1)); m1 = fmaxf(m1, __shfl_xor_sync(0xffffffffu, m1, 1));
          m0 = fmaxf(m0, __shfl_xor_sync(0xffffffffu, m0, 2)); m1 = fmaxf(m1, __shfl_xor_sync(0xffffffffu, m1, 2));
        };
        auto first = [&](float (&s)[32], int sk0, auto mid) {
          fence_regs(s);
          release(sk0);
          mc0 = 0.f; mc1 = 0.f;
          expo(s, pa, l0, l1, false, mid);
          shifted = __any_sync(0xffffffffu, !(fmaxf(l0, l1) <= kSumLimit && fminf(l0, l1) >= 1.f / kSumLimit));
          if (shifted) {
            rowmax(s, mc0, mc1);
            expo(s, pa, l0, l1, true, [](int) {});
          }
        };
        auto qk = [&](float (&s)[32], uint32_t ak, int k0 = 0, int k1 = 12) {
#pragma unroll
          for (int kk = k0; kk < k1; kk++)
            wgmma_rs_n64<0>(s, q[4 * kk], q[4 * kk + 1], q[4 * kk + 2], q[4 * kk + 3], mk_desc(ak, 16, KV_SBO, 1) + ((kk >> 2) * KV_CH + (kk & 3) * 2), kk != 0);
          if (k1 == 12) wg_commit();
        };
        auto pv = [&](uint32_t (&pin)[16], uint32_t av, int acc) {
#pragma unroll
          for (int kk = 0; kk < 4; kk++)
            wgmma_rs_n192<1>(o, pin[4 * kk], pin[4 * kk + 1], pin[4 * kk + 2], pin[4 * kk + 3], mk_desc(av, KV_CH * 16, KV_SBO, 1) + (kk * (KV_SBO / 8)), acc || (kk != 0));
          wg_commit();
        };
        auto finish = [&](uint32_t (&pout)[16], int sk, int sv) {
          probe1();
          wg_wait<1>();
          fence_regs(s);
          release(sk);
          float b0, b1;
#pragma unroll 1
          for (bool redo = false;; redo = true) {
            expo(s, pout, b0, b1, false, [](int) {});
            if (!__any_sync(0xffffffffu, !redo && (shifted || !(fmaxf(b0, b1) <= kSumLimit)))) break;
            shifted = true;
            rowmax(s, b0, b1);
            b0 = fmaxf(mc0, b0); b1 = fmaxf(mc1, b1);
            const float a0 = ex2(mc0 - b0), a1 = ex2(mc1 - b1);
            mc0 = b0; mc1 = b1;
            l0 *= a0; l1 *= a1;
            wg_wait<0>();
            fence_regs(o);
#pragma unroll
            for (int i = 0; i < 24; i++) { o[4 * i] *= a0; o[4 * i + 1] *= a0; o[4 * i + 2] *= a1; o[4 * i + 3] *= a1; }
#pragma unroll
            for (int i = 0; i < 32; i++) s[i] -= (i & 2) ? mc1 : mc0;
          }
          l0 += b0; l1 += b1;
          wg_wait<0>();
          fence_regs(o);
          release(sv);
        };
        auto step = [&](uint32_t (&pin)[16], uint32_t (&pout)[16]) {
          uint32_t ak, av;
          const int sk = take(rdy0, SZ_KV, ak), sv = advance(SZ_KV, av);
          wg_fence();
          qk(s, ak);
          pv(pin, av, 1);
          finish(pout, sk, sv);
        };
        auto unpark = [&]() {
          uint32_t ad, ak;
          const int bi = take(rdy0, SZ_PARK, ad);
#pragma unroll
          for (int i = 0; i < 12; i++) lds128(sbase + (ad - ring16 + img0) * 16 + (i >> 1) * 8192 + (i & 1) * 512, q[4 * i], q[4 * i + 1], q[4 * i + 2], q[4 * i + 3]);
          const int sk0 = take(false, SZ_KV, ak);
          fence_regs(q);
          release_warp(bi);
          wg_fence();
          qk(s, ak);
          probe2();
          return sk0;
        };
        auto mma4 = [&](uint32_t ad, int acc) {
#pragma unroll
          for (int kk = 0; kk < 4; kk++)
            wgmma_ss_n192<1>(o, mk_desc(ad + wg * 512, 16, 1024, 1) + (kk * 2), mk_desc(ad, 4096, 1024, 1) + (1024 + (kk >> 1) * 768 + (kk & 1) * 128), acc || kk != 0);
        };
        auto convert = [&](int i0, int i1) {
          sched_fence(keep, never);
#pragma unroll
          for (int i = i0; i < i1; i++) {
            q[i] = pack_bf16(o[2 * i] * kScaleLog2, o[2 * i + 1] * kScaleLog2);
            if ((i & 7) == 7 && i != i1 - 1) sched_fence(keep, never);
          }
          sched_fence(keep, never);
        };
        auto kend = [&](int bi, int k) {
          wg_commit();
          drain((0x54732710u >> (4 * k)) & 7);
          probe1();
          wg_wait<0>();
          release(bi);
        };
        if (type == OP_O) {
          int prev = 0;
          if (op & C_WIDE) {
            float d[64];
            auto mma3 = [&](uint32_t ad, int h, int acc) {
#pragma unroll
              for (int kk = 0; kk < 2; kk++)
                wgmma_ss_n192<1>(o, mk_desc(ad + wg * 256, 16, 512, 2) + (h * 512 + kk * 2), mk_desc(ad, 4096, 1024, 1) + (1024 + h * 768 + kk * 128), acc || kk);
            };
            auto mma2 = [&](uint32_t ad, uint32_t ob, int h, int acc) {
#pragma unroll
              for (int kk = 0; kk < 2; kk++)
                wgmma_ss_n128<1>(d, mk_desc(ad + wg * 256, 16, 512, 2) + (h * 512 + kk * 2), mk_desc(ad, 4096, 1024, 1) + (ob + h * 512 + kk * 128), acc || kk);
            };
            auto wstep = [&](uint32_t bytes, int acc, auto hook) {
              uint32_t ad;
              const int bi = take(rdy0, bytes, ad);
              wg_fence();
              if (bytes == SZ_W2) mma2(ad, 1024, 0, 1); else mma3(ad, 0, acc);
              if (bytes == SZ_W) mma3(ad, 1, 1);
              wg_commit();
              if (acc) { wg_wait<1>(); release(prev); }
              if (bytes == SZ_W) mma2(ad, 2560, 0, acc);
              if (bytes == SZ_W3) mma3(ad, 1, 1); else mma2(ad, bytes == SZ_W ? 2560 : 1024, 1, 1);
              wg_commit();
              prev = bi;
              hook();
              probe1();
              wg_wait<1>();
            };
            undefine(o);
            wstep(SZ_W, 0, [&]() { drain(0); });
#pragma unroll 1
            for (int k = 1; k < ((op >> 2) & 127) - TAIL; k++) wstep(SZ_W, 1, [&]() { drain(k); });
#pragma unroll 1
            for (int k = 0; k < TAIL; k++) wstep(SZ_W2, 1, []() {});
            pend = ptr_add(P.g->part, (((op >> 9) & 31) * 2 + rank) * 81920 + 4 * 8192 + img0 * 16);
            wstep(SZ_W3, 1, [&]() {
              fence_regs(d);
#pragma unroll
              for (int i = 0; i < 32; i++) q[16 + i] = pack_bf16(d[2 * i], d[2 * i + 1]);
              slab(2, 2);
            });
#pragma unroll 1
            for (int k = 3; k < 6; k++) wstep(SZ_W3, 1, [&]() { slab(k, 2); });
            op = prog[pc + 1];
            enter();
            pend_any = true;
            pend -= 4 * 512;
            bi0 = take(rdy0 || (op & 3) != OP_Q, SZ_Q, ad0);
            sched_fence(keep, never);
            wg_wait<0>();
            fence_regs(o);
            release(prev);
#pragma unroll
            for (int i = 0; i < 48; i++) q[i] = pack_bf16(o[2 * i], o[2 * i + 1]);
            if ((op & 3) != OP_Q) continue;
            pc++;
            goto first_step;
          }
          float c[80];
          auto mma2 = [&](uint32_t ad, uint32_t oa, uint32_t ob, int acc) {
            wgmma_ss_n160<1>(c, mk_desc(ad + wg * 256, 16, 512, 2) + (oa), mk_desc(ad, 2048, 512, 2) + (1024 + ob), acc);
            wgmma_ss_n160<1>(c, mk_desc(ad + wg * 256, 16, 512, 2) + (oa + 2), mk_desc(ad, 2048, 512, 2) + (1024 + ob + 64), 1);
          };
          auto kstep = [&](int acc, auto hook, uint32_t bytes = SZ_O) {
            uint32_t ad;
            const int bi = take(rdy0, bytes, ad);
            wg_fence();
            mma2(ad, 0, 0, acc);
            wg_commit();
            if (acc) wg_wait<1>();
            if (acc == 1) release(prev);
            if (acc > 1) release_warp(prev, acc == 2 || wg == 0);
            mma2(ad, 512, 640, 1);
            wg_commit();
            prev = bi;
            hook();
            probe1();
            wg_wait<1>();
          };
          auto unblock = [&](int k) {
            if (__all_sync(0xffffffffu, rdy0) || __all_sync(0xffffffffu, mbar_try(full0 + r.off(), r.ph(), 1500))) return;
#pragma unroll 1
            for (; k < 6; k++) drain(k);
            pend_any = false;
          };
          unblock(0);
          kstep(0, [&]() { drain(0); });
          int left = ((job >> 13) & 127) - 6;
#pragma unroll 1
          for (uint32_t k = 1, pace = left >= 22 ? 0x4511 : left <= 11 ? 0x1a : 0x155; left > 0; pace >>= 2, left--) {
            unblock(k);
            kstep(1, [&]() {
#pragma unroll 1
              for (int i = pace & 3; i > 0; i--) drain(k++);
            });
          }
          uint32_t t[8], stage[3];
          float u[80];
          auto unpack = [&](int j) {
#pragma unroll
            for (int i = 0; i < 8; i++) {
              u[16 * j + 2 * i] = __uint_as_float(t[i] << 16); u[16 * j + 2 * i + 1] = __uint_as_float(t[i] & 0xffff0000u);
              asm volatile("" : "+f"(u[16 * j + 2 * i]), "+f"(u[16 * j + 2 * i + 1]));
            }
          };
#pragma unroll
          for (int i = 0; i < 8; i++) t[i] = 0;
          const uint32_t bytes = (job & P_LD) ? SZ_OL : SZ_O;
#pragma unroll
          for (int j = 0; j < 5; j++) {
            if (j == 2 && wg == 1) {
              wg_wait<0>();
              release_warp(prev);
              bar_sync(1, 256);
            }
            kstep(j == 2 ? 3 : 2, [&]() {
              if (j == 4) asm volatile("{\n.reg .pred p;\nsetp.eq.u32 p, %0, 0;\n@p bar.arrive 1, 256;\n}\n" ::"r"(wg) : "memory");
              if (j) unpack(j - 1);
              lds2_if(job & P_LD, sbase + (cur - ring16 + img0) * 16 - 8192, t);
              if (j >= 1 && j <= 3) stage[j - 1] = sbase + (cur - ring16) * 16 - bytes + wid * 1024;
            }, bytes);
          }
          unpack(4);
          sched_fence(keep, never);
          wg_wait<0>();
          fence_regs(c);
          release_warp(prev);
          asm volatile("barrier.cluster.arrive.relaxed;" ::: "memory");
#pragma unroll
          for (int i = 0; i < 10; i++) {
            const int v = (i & 1) * 2 + (lane >> 4);
            const uint32_t sa = stage[i >> 2] + (i & 2) * 4096;
            stsm4(sa + (lane & 15) * 64 + ((v ^ ((lane >> 1) & 3)) << 4), pack_bf16(c[8 * i] + u[8 * i], c[8 * i + 1] + u[8 * i + 1]),
                  pack_bf16(c[8 * i + 2] + u[8 * i + 2], c[8 * i + 3] + u[8 * i + 3]), pack_bf16(c[8 * i + 4] + u[8 * i + 4], c[8 * i + 5] + u[8 * i + 5]),
                  pack_bf16(c[8 * i + 6] + u[8 * i + 6], c[8 * i + 7] + u[8 * i + 7]));
          }
          asm volatile("fence.proxy.async.shared::cta;" ::: "memory");
          __syncwarp();
          if (elect()) {
#pragma unroll
            for (int i = 0; i < 5; i++)
              tma3d_store(&P.out, stage[i >> 1] + (i & 1) * 8192, 0, ((job >> 7) & 7) * kSq + rank * 128 + wid * 16, ((job >> 10) & 1) * 20 + ((job >> 20) & 3) * 5 + i);
            asm volatile("cp.async.bulk.commit_group;\ncp.async.bulk.wait_group.read 0;" ::: "memory");
          }
          __syncwarp();
          break;
        }
        bi0 = take(rdy0, SZ_Q, ad0);
      first_step:
        undefine(o);
        wg_fence();
        mma4(ad0, 0);
        kend(bi0, 0);
        fence_regs(o);
      next_head:
        {
#pragma unroll 1
          for (int k = 1; k < 8; k++) {
            uint32_t ad;
            const int bi = take(rdy0, SZ_Q, ad);
            wg_fence();
            mma4(ad, 1);
            kend(bi, k);
          }
          uint32_t a8, a9, ak0, ak1;
          const int b8 = take(rdy0, SZ_Q, a8), b9 = take(false, SZ_Q, a9);
          wg_fence();
          mma4(a8, 1);
          wg_commit();
          mma4(a9, 1);
          wg_commit();
          wg_wait<1>();
          release(b8);
          probe1();
          const int sk0 = take(rdy0 || (op & F_PARK), SZ_KV, ak0);
          wg_wait<0>();
          fence_regs(o);
          release(b9);
          float s0[32];
          convert(0, 32);
          if (op & F_PARK) {
            convert(32, 48);
            pend = ptr_add(P.g->tile, (((op >> 2) & 511) * 2 + rank) * SZ_PARK + img0 * 16);
            continue;
          }
          pc++;
          wg_fence();
          qk(s0, ak0, 0, 4);
          convert(32, 48);
          wg_fence();
          qk(s0, ak0, 4, 12);
          sk1 = take(false, SZ_KV, ak1);
          probe1();
          wg_wait<0>();
          first(s0, sk0, [&](int i) {
            if (i == 0) return;
            sched_fence(keep, never);
            wg_fence();
            if (i == 1) qk(s, ak1, 0, 4);
            if (i == 2) qk(s, ak1, 4, 8);
            if (i == 3) qk(s, ak1, 8, 12);
            sched_fence(keep, never);
          });
        }
        for (;;) {
          {
            uint32_t av;
            const int sv = take(rdy0, SZ_KV, av);
            undefine(o);
            wg_fence();
            pv(pa, av, 0);
            finish(pb, sk1, sv);
          }
          nop = prog[pc + 1];
#pragma unroll 1
          for (int jj = 0; jj < 7; jj++) {
            step(pb, pa);
            step(pa, pb);
          }
          float i0, i1;
          auto last = [&]() {
            uint32_t av;
            const int sv = take(rdy0, SZ_KV, av);
            wg_fence();
            pv(pb, av, 1);
            sched_fence(keep, never);
            probe1();
            l0 += __shfl_xor_sync(0xffffffffu, l0, 1); l1 += __shfl_xor_sync(0xffffffffu, l1, 1);
            l0 += __shfl_xor_sync(0xffffffffu, l0, 2); l1 += __shfl_xor_sync(0xffffffffu, l1, 2);
            i0 = rcp(l0); i1 = rcp(l1);
            pend = ptr_add(P.g->tile, (((op >> 2) & 511) * 2 + rank) * SZ_PARK + img0 * 16);
            return sv;
          };
          auto normalise = [&](uint32_t (&d)[48], auto mid) {
#pragma unroll
            for (int i = 0; i < 24; i++) {
              d[8 * (i >> 2) + (i & 3)] = pack_bf16(o[4 * i] * i0, o[4 * i + 1] * i0);
              d[8 * (i >> 2) + (i & 3) + 4] = pack_bf16(o[4 * i + 2] * i1, o[4 * i + 3] * i1);
              if ((i & 1) && i != 23) sched_fence(keep, never);
              if ((i & 3) == 3 && i != 23) mid(i >> 2);
            }
          };
          const int sv = last();
          if ((nop & 3) != OP_A) {
            op = nop;
            enter();
            pend_any = true;
            bi0 = take(rdy0 || (nop & 3) != OP_Q, SZ_Q, ad0);
            sched_fence(keep, never);
            wg_wait<0>();
            fence_regs(o);
            release(sv);
            normalise(q, [](int) {});
            undefine(o);
            if ((nop & 3) != OP_Q) break;
            sched_fence(keep, never);
            wg_fence();
            mma4(ad0, 0);
            pc++;
            kend(bi0, 0);
            fence_regs(o);
            goto next_head;
          }
          const int sk0 = unpark();
          wg_wait<1>();
          fence_regs(o);
          release(sv);
          uint32_t t[48];
          auto st = [&](int i) {
            stg2_if(true, pend + i * 512, t[8 * i], t[8 * i + 1], t[8 * i + 2], t[8 * i + 3], t[8 * i + 4], t[8 * i + 5], t[8 * i + 6], t[8 * i + 7], spol);
          };
          normalise(t, [&](int i) { if (!(i & 1)) st(i >> 1); });
          wg_wait<0>();
          first(s, sk0, [&](int i) { if (i < 3) { sched_fence(keep, never); st(3 + i); } });
          __syncwarp();
          mbar_arrive_if(lane == 0, odone0 + 8 * pc);
          pc++;
          op = nop;
          uint32_t ak1;
          sk1 = take(rdy0, SZ_KV, ak1);
          rdy0 = rdy1;
          wg_fence();
          qk(s, ak1);
        }
      }
    }
    asm volatile("barrier.cluster.wait;" ::: "memory");
  } else {
    asm volatile("setmaxnreg.dec.sync.aligned.u32 24;");
    const uint32_t* prog = P.prog[role].p;
    unsigned int* flag = P.g->flag + rank;
    if (wid == 11 && (prog[0] & 3) == OP_Q) {
      const uint32_t a = prog[1];
      const char* p = ptr_add(P.kv[rank * 2 + ((a >> 10) & 1)], ((a >> 2) & 255) * (kSk * kDh * 2) + (threadIdx.x & 31) * 128);
#pragma unroll 1
      for (uint32_t k = 0; k < 3; k++) {
        wait_word(progress, 8 * k);
        p += SZ_KV;
        asm volatile("prefetch.global.L2 [%0];\nprefetch.global.L2 [%0 + 4096];" ::"l"(p));
      }
      __syncwarp();
    }
    if (wid == 8) {
      Cursor head{0}, tail{0};
      int sh = 0, room = RING >> 12;
      uint32_t cur = 0;
      uint64_t fifo = 0;
      uint32_t dst, bar = 0, ev = ev0;
      const uint64_t pol = evict_first();
      auto retire = [&]() {
        mbar_wait(empty0 + tail.off(), tail.ph());
        tail.next();
        room += (uint32_t)fifo & 31;
        fifo >>= 5;
        sh -= 5;
        asm volatile("st.volatile.shared.u32 [%0], %1;" ::"r"(progress), "r"(tail.n) : "memory");
      };
      auto acquire = [&](uint32_t bytes) {
        uint32_t fp = bytes >> 12;
        if (cur + fp > (RING >> 12)) { fp += (RING >> 12) - cur; cur = 0; }
        room -= fp;
        while (room < 0) retire();
        fifo |= (uint64_t)fp << sh;
        sh += 5;
        dst = sbase + (cur << 12);
        bar = full0 + head.off();
        cur += bytes >> 12;
        head.next();
      };
      auto gate = [&]() {
        mbar_wait(ev, 0);
        ev += 8;
        asm volatile("fence.proxy.async.global;" ::: "memory");
      };
      for (int pc = 0;; pc++) {
        uint32_t op = prog[pc];
        const int type = op & 3;
        if (type == OP_END) break;
        if (op == OP_O) {
          gate();
          op = __shfl_sync(0xffffffffu, lds32(jobw), 0);
        }
        const int blk = (op >> 10) & 1;
        if (type == OP_Q) {
          const uint64_t px = (op & P_LASTX) ? pol : no_hint(), pw = (op & P_LASTW) ? pol : no_hint();
          int k = 0;
          if (pc == 0) {
            k = 64 * EARLY; head.n = 8 * EARLY; sh = 5 * EARLY; cur = EARLY * (SZ_Q >> 12); room -= cur;
            fifo = (SZ_Q >> 12) * (((1u << (5 * EARLY)) - 1) / 31);
          }
#pragma unroll 1
          for (int stop = (op & P_GATE) ? kD - 64 : kD;; stop = kD) {
#pragma unroll 1
            for (; k < stop; k += 64) {
              acquire(SZ_Q);
              if (elect()) {
                mbar_expect(bar, SZ_Q);
                tma3d_mc_hint(dst + 16384 + rank * 12288, &P.wq[blk], bar, k + 32 * rank, 3 * ((op >> 2) & 31), pw);
                tma2d_hint(dst, &P.x[blk], bar, k, ((op >> 7) & 7) * kSq + rank * 128, px);
              }
            }
            if (k == kD) break;
            gate();
          }
        } else if (type == OP_A) {
          const int row0 = ((op >> 2) & 255) * kSk;
          if (op & F_PARK) {
            gate();
            acquire(SZ_PARK);
            if (elect()) {
              mbar_expect(bar, SZ_PARK);
              bulk_load_hint(dst, &P.g->tile[(((op >> 20) & 511) * 2 + rank) * 3072], SZ_PARK, bar, pol);
            }
          }
          auto kv = [&](uint32_t tx, const CUtensorMap* m, int c3) {
            const uint32_t before = bar;
            acquire(SZ_KV);
            if (elect()) {
              mbar_expect(bar, tx);
              tma4d_mc_hint(dst + rank * (SZ_KV / 2), m, tx ? bar : before, c3, pol);
            }
          };
          int c3 = row0 / 8 + 4 * rank;
#pragma unroll 1
          for (int j = 0; j <= 16; j++, c3 += 8) {
            const uint32_t tv = j < 2 || j == 16 ? SZ_KV : 0;
            if (j < 16) kv(2 * SZ_KV - tv, &P.k[blk], c3);
            else if (op & P_GATE) gate();
            if (j > 0) kv(tv, &P.v[blk], c3 - 8);
          }
        } else {
          const uint4* part = &P.g->part[((((op >> 6) & 30) + ((op >> 21) & 1)) * 2 + rank) * 5120 + ((op >> 20) & 1) * 2560];
          auto run = [&](const uint32_t bytes, int k, int cnt, int gates) {
            const int col = bytes == SZ_O || bytes == SZ_OL ? 5 * ((op >> 20) & 3) : 5 * ((op >> 21) & 1);
            int row = 8 * k + 4 * rank, pre = bytes == SZ_O && (op & P_PRE) ? 0 : 2560;
#pragma unroll 1
            for (int h = (k * 43) >> 7, k0 = k - 3 * h; cnt > 0; h++, k0 = 0, gates = gates >> 1 | (gates & 2)) {
              const uint4* src = ptr_add(P.g->tile, ((P.slot[((op >> 2) & 480) + h] * 2 + rank) * 3 + k0) * 16384);
              const uint64_t pw = h >= ((op >> 23) & 31) && h < 2 * (op >> 28) ? pol : no_hint();
              if (gates & 1) gate();
              int m = min(3 - k0, cnt);
              cnt -= m;
#pragma unroll 1
              for (; m > 0; m--, src += 1024, row += 8) {
                acquire(bytes);
                if (elect()) {
                  mbar_expect(bar, bytes);
                  if (bytes == SZ_O || bytes == SZ_OL) tma5d_mc_hint(dst + 16384 + rank * 10240, &P.wo[blk], bar, row, col, no_hint());
                  if (bytes == SZ_W || bytes == SZ_W3) tma5d_mc_hint(dst + 16384 + rank * 12288, &P.wo3[blk], bar, row, col, pw);
                  bulk_load_hint(dst, src, 16384, bar, pol);
                  if (bytes == SZ_W || bytes == SZ_W2) tma5d_mc_hint(dst + bytes - 16384 + rank * 8192, &P.wo2[blk], bar, row, col + 3, pw);
                  if (bytes == SZ_OL) bulk_load_hint(dst + SZ_O, part, 8192, bar, pol);
                }
                if (bytes == SZ_OL) part += 512;
              }
              if (pre < 2560) {
                if (elect()) asm volatile("cp.async.bulk.prefetch.L2.global [%0], 10240;" ::"l"(part + pre) : "memory");
                pre += 640;
              }
            }
          };
          const int n = (op >> 13) & 127;
          if (op & P_WIDE) {
            run(SZ_W, 0, n - TAIL, 3);
            run(SZ_W2, n - TAIL, TAIL, (n - TAIL) % 3 ? 2 : 3);
            run(SZ_W3, n - TAIL, TAIL, 0);
          } else {
            if (op & P_PRE) gate();
            run(SZ_O, kSteps - n, (op & P_LD) ? n - 5 : n, 3);
            if (op & P_LD) {
              if (!(op & P_PRE)) gate();
              run(SZ_OL, kSteps - 5, 5, 2);
            }
          }
        }
      }
#pragma unroll 1
      while (sh) retire();
    } else if (threadIdx.x == 288) {
      for (int pc = 0;; pc++) {
        const uint32_t op = prog[pc];
        const int type = op & 3;
        if (type == OP_END) break;
        if (type == OP_Q ? !(op & F_PARK) : type == OP_O && !(op & P_WIDE)) continue;
        const int id = type == OP_A ? (op >> 2) & 511 : type == OP_Q ? N_TILE + ((op >> 13) & 127) : ID_PART + ((op >> 5) & 60) + ((op >> 20) & 3);
        const uint32_t v = type == OP_O ? 1 : P.info[id] & 7;
        mbar_wait_long(odone0 + 8 * pc);
        flag_set(flag + 2 * id, v);
        if (type == OP_O && (op & P_WIDE)) flag_set(flag + 2 * id + 2, v);
      }
    } else if (wid == 10) {
      int i = threadIdx.x & 31;
      const int n_ev = P.prog[role].n_ev;
      auto event = [&]() { return i < n_ev ? P.prog[role].ev[i] : n_ev ? E_JOB | (i - n_ev) : 0; };
      uint32_t e = i < 8 ? event() : 0;
      for (uint32_t n = 0; __any_sync(0xffffffffu, e); n++) {
        uint32_t job = lds32(jobw);
        const int togo = (e & E_DRAW) ? (e & 1023) - (lds32(progress) >> 3) : 99;
        if (togo <= 0 && rank == 0) {
          job = P.job[atomicInc(&P.g->ticket, gridDim.x / 2 - 1)];
          asm volatile("{\n.reg .u32 a;\nmapa.shared::cluster.u32 a, %0, 1;\nst.volatile.shared::cluster.u32 [a], %1;\n"
                       "st.volatile.shared.u32 [%0], %1;\n}\n" ::"r"(jobw), "r"(job) : "memory");
        }
        if ((e & E_JOB) && job) {
          const uint32_t j = e & 63, heads = job == OP_O ? 0 : kH - ((job >> 2) & 31), jp = !(job & P_LD) ? 63 : (job & P_PRE) ? 0 : heads - 1, h = j - (j > jp);
          e = j == jp ? (ID_PART + ((job >> 5) & 60) + ((job >> 20) & 3)) | E_ON | E_LAST : h < heads ? (((job >> 2) & 511) + h) | E_ON | E_LAST : 0;
        }
        unsigned int* f = ptr_add(flag, 8 * (e & 1023));
        const bool ok = (e & E_ON) ? flag_get(f) - 1 < ((e & E_FREE) ? 1 : 7) : (e & E_DRAW) && job;
        if (ok) {
          mbar_arrive(ev0 + 8 * i);
          if (e & (E_FREE | E_LAST)) flag_dec(f);
          i += 8;
          e = event();
        }
        asm volatile("{\n.reg .pred p;\nsetp.ge.u32 p, %0, 0x400000;\n@p trap;\n}\n" ::"r"(n));
        if (!__any_sync(0xffffffffu, ok)) __nanosleep(__any_sync(0xffffffffu, job || togo <= 2) ? 100 : 600);
      }
    } else if (threadIdx.x == 352) {
      uint32_t items = 0;
      auto read = [&](int id) {
        if (!(P.info[id] & I_NEXT)) return;
        wait_word(progress, 8 * items);
        flag_dec(flag + 2 * id);
      };
      for (int pc = 0;; pc++) {
        const uint32_t op = prog[pc];
        const int type = op & 3;
        if (type == OP_END) break;
        if (type == OP_O) {
          const uint32_t n = (op >> 13) & 127, base = items;
#pragma unroll 1
          for (uint32_t k = 3, id = (op >> 2) & 511; k <= n; k += 3, id++) {
            items = base + k + (k + TAIL > n ? TAIL : 0);
            read(id);
          }
          items = base + n + TAIL;
        } else if (type == OP_A) {
          if (op & F_PARK) { items++; read(N_TILE + ((op >> 13) & 127)); }
          items += 32;
        } else {
          items += 10;
        }
      }
    }
    __syncwarp();
    asm volatile("barrier.cluster.arrive.relaxed;\nbarrier.cluster.wait;" ::: "memory");
  }
}

typedef CUresult (*EncodeFn)(CUtensorMap*, CUtensorMapDataType, cuuint32_t, void*, const cuuint64_t*, const cuuint64_t*,
                             const cuuint32_t*, const cuuint32_t*, CUtensorMapInterleave, CUtensorMapSwizzle,
                             CUtensorMapL2promotion, CUtensorMapFloatOOBfill);

void encode(EncodeFn fn, CUtensorMap* m, const void* ptr, int rank, const cuuint64_t* dims, const cuuint64_t* strides,
            const cuuint32_t* box, CUtensorMapSwizzle swz) {
  const cuuint32_t es[5] = {1, 1, 1, 1, 1};
  CUresult r = fn(m, CU_TENSOR_MAP_DATA_TYPE_BFLOAT16, rank, const_cast<void*>(ptr), dims, strides, box, es,
                  CU_TENSOR_MAP_INTERLEAVE_NONE, swz, CU_TENSOR_MAP_L2_PROMOTION_L2_128B, CU_TENSOR_MAP_FLOAT_OOB_FILL_NONE);
  if (r != CUDA_SUCCESS) fprintf(stderr, "cuTensorMapEncodeTiled failed: %d\n", (int)r);
}

struct Op { int type, flags, id, n, quarter, park, item0, items; double t0, t1; };
struct Use { double ready, gate, need, freed; int readers, slot, prev; bool next; };
struct PlanStats { double end, slack, park_slack; int slots, parks; uint32_t own[N_CL]; };

bool plan(const char* const* text, int n_pair, int phase, Params& P, PlanStats* stats = nullptr) {
  constexpr double T_Q = 7900, T_A = 24800, T_U = TU, T_O = 640, T_RUN = 800, T_WIDE = TW, AHEAD = 3500, PUBLISH = 1500;
  const double margin = 256.0 * ((P.dbg >> 8) & 255);
  static Op op[N_CL][MAX_OPS];
  static Use use[ID_PART];
  int n_op[N_CL], covered[2 * N_TEAM] = {};
  struct Ref { double t; Op* o; int id; };
  static Ref att[N_TILE + 1], dem[N_TILE], prk[MAX_PARK + 1], unp[MAX_PARK + 1], wr[ID_PART];
  auto sort = [](Ref* r, int n) {
    for (int i = 1; i < n; i++)
      for (int j = i; j > 0 && r[j].t < r[j - 1].t; j--) { Ref x = r[j]; r[j] = r[j - 1]; r[j - 1] = x; }
  };
  auto hex = [](char c) { return c <= '9' ? c - '0' : c - 'a' + 10; };
  for (int i = 0; i < n_pair; i++)
    for (const char* s = text[i]; *s; s++)
      for (int h = 0; *s == 'J' && h < 2; h++) {
        if (covered[2 * hex(s[1]) + h]) return false;
        covered[2 * hex(s[1]) + h] = 10 * (s[2 + 2 * h] - '0') + s[3 + 2 * h] - '0';
      }
  for (int c = 0; c < 2 * n_pair; c++) {
    int n = 0, items = 0;
    double t = 0;
    auto add = [&](int type, int flags, int id, int heads, int quarter, int its, double dt) {
      if (n < MAX_OPS) op[c][n] = {type, flags, id, heads, quarter, 0, items, its, t, t + dt};
      n++; items += its; t += dt;
    };
    for (const char* s = text[c >> 1]; *s; s++) {
      const int tm = hex(s[1]) & 15, nj = covered[2 * tm + (c & 1)];
      if (*s == 'N') { add(OP_Q, 0, 0, 0, 0, 10, T_Q); add(OP_A, 0, 0, 0, 0, 32, T_A); }
      if (*s == 'P') add(OP_Q, F_PARK, 0, 0, 0, 10, T_Q + TP);
      if (*s == '+' || *s == '-') t += *s == '+' ? 1000 : -1000;
      if (*s == 'U') { if (n == 0 || n > MAX_OPS || op[c][n - 1].type != OP_A) return false; add(OP_A, F_PARK, 0, 0, 0, 33, T_U); }
      if (*s == 'J') { if (nj < TAIL + 6 || nj > kSteps - 11) return false; add(OP_O, P_WIDE, tm * kH, nj, 2 * (c & 1), nj + TAIL, 2 * T_O * nj + T_WIDE); }
    }
    add(OP_O, 0, 0, 0, 0, 0, 0);
    add(OP_END, 0, 0, 0, 0, 0, 0);
    if (n > MAX_OPS || op[c][0].type != OP_Q) return false;
    n_op[c] = n - 1;
    att[c] = {t, &op[c][n - 2], 0};
  }
  for (int i = 0; i < 4 * N_TEAM; i++) dem[i] = {(double)covered[i / 2], nullptr, i};
  sort(att, 2 * n_pair); sort(dem, 4 * N_TEAM);
  for (int i = 0; i < 4 * N_TEAM; i++) {
    Op* f = att[i].o;
    const int nj = covered[dem[i].id / 2];
    f->flags = nj ? P_LD : 0;
    f->id = dem[i].id / 4 * kH + nj / 3; f->quarter = dem[i].id & 3; f->items = f->n = kSteps - nj;
    f[1].t0 = f[1].t1 = f->t1 = f->t0 + T_O * f->n + T_RUN; f[1].item0 += f->n;
  }
  for (int i = 0; i < ID_PART; i++) use[i] = {0, 0, 1e18, 0, 0, 0, 0, false};
  int n_att = 0, n_prk = 0, n_unp = 0;
  auto ready = [&](const Op* o) {
    const int nt = o[1].type;
    return o->t1 + (nt == OP_Q ? 6100 : o[1].n ? ((o[1].flags & P_WIDE) ? 7700 : 3900) : 1500) + PUBLISH;
  };
  for (int c = 0; c < 2 * n_pair; c++)
    for (Op* o = op[c]; o->type != OP_END; o++) {
      if (o->type == OP_A) { att[n_att] = {ready(o), o, 0}; if (++n_att > N_TILE) return false; }
      if (o->type == OP_A && o->flags) { unp[n_unp] = {o->t0 - AHEAD, o, 0}; if (++n_unp > MAX_PARK) return false; }
      if (o->type == OP_Q && o->flags) { prk[n_prk] = {ready(o), o, 0}; if (++n_prk > MAX_PARK) return false; }
      for (int i = 0; o->type == OP_O && i < o->n; i++) {
        const int nw = (o->flags & P_WIDE) ? o->n - TAIL : 0, k = nw ? i : kSteps - o->n + i;
        Use& u = use[o->id / kH * kH + k / 3];
        const double t = o->t0 + T_O * (i + (i < nw ? i : nw));
        if (t - AHEAD < u.need) u.need = t - AHEAD;
        const double f = !nw ? 1e18 : i + FLIGHT < o->items - TAIL || (nw && o[1].type != OP_O) ? t + T_O * (i < nw ? 2 : 1 + TAIL) + PUBLISH : 1e18;
        if (f > u.freed) u.freed = f;
        if (i == 0 || k % 3 == 0) u.readers++;
      }
    }
  if (n_att != N_TILE || n_prk != n_unp) return false;
  for (int i = 0; i < N_TILE; i++) { const int id = (i & 15) * kH + (i >> 4); dem[i] = {use[id].need, nullptr, id}; }
  sort(att, n_att); sort(dem, N_TILE); sort(prk, n_prk); sort(unp, n_unp);
  PlanStats st = {0, 1e18, 1e18, 0, n_prk};
  int n_wr = 0;
  for (int i = 0; i < N_TILE; i++) {
    Op* o = att[i].o;
    o->id = dem[i].id;
    if (!o->flags) o[-1].id = o->id;
    if (dem[i].t - att[i].t < st.slack) st.slack = dem[i].t - att[i].t;
    wr[n_wr++] = {o->t1 - 2 * AHEAD, o, o->id};
  }
  for (int i = 0; i < n_prk; i++) {
    prk[i].o->id = unp[i].o->id;
    prk[i].o->park = unp[i].o->park = i;
    use[N_TILE + i].freed = unp[i].o->t0 + 2 * PUBLISH;
    use[N_TILE + i].readers = 1;
    if (unp[i].t - prk[i].t < st.park_slack) st.park_slack = unp[i].t - prk[i].t;
    wr[n_wr++] = {prk[i].o->t1 - 2 * AHEAD, prk[i].o, N_TILE + i};
  }
  for (int c = 0; c < 2 * n_pair; c++)
    for (int d = 0; d < 2 * n_pair; d++)
      for (Op *f = &op[c][n_op[c] - 1], *o = op[d]; f->n && o->type != OP_END; o++)
        if (o->type == OP_O && (o->flags & P_WIDE) && o->id / kH == f->id / kH && o->quarter / 2 == f->quarter / 2) {
          if (f->t0 - o->t1 > 4096.0 * ((P.dbg >> 16) & 255)) f->flags |= P_PRE;
          const double slack = f->t0 + ((f->flags & P_PRE) ? 0 : (f->n - 5) * T_O) - AHEAD - ready(o);
          if (slack < st.park_slack) st.park_slack = slack;
        }
  constexpr double long_while = 160000;
  for (int c = 0; c < 2 * n_pair; c++)
    for (Op* o = op[c]; o->type != OP_END; o++) {
      if (o->type == OP_O && (o->flags & P_WIDE)) {
        int run = 0, best = 0, end = 0;
        for (int h = 0; 3 * h < o->n; h++) {
          bool last = true;
          for (int d = 0; d < 2 * n_pair; d++)
            for (const Op* e = op[d]; e->type != OP_END; e++) {
              if (e->type != OP_O || e == o || ((e->id ^ o->id) & 256) || e->quarter / 2 != o->quarter / 2) continue;
              const bool wide = e->flags & P_WIDE;
              if (wide ? 3 * h >= e->n : 3 * h + 3 <= kSteps - e->n) continue;
              const double dt = e->t0 + T_O * (wide ? 6 * h : 3 * h - kSteps + e->n) - o->t0 - T_O * 6 * h + (d - c) * 1e-3;
              if (dt > 0 && dt < long_while) last = false;
            }
          run = last ? run + 1 : 0;
          if (run > best) { best = run; end = h + 1; }
        }
        if (3 * end >= o->n) end++;
        o->park = (end - best) | (end / 2) << 5;
      }
      if (o->type != OP_Q) continue;
      bool lw = true, lx = true;
      for (int d = 0; d < 2 * n_pair; d++)
        for (const Op* e = op[d]; e->type != OP_END; e++) {
          const double dt = e->t0 - o->t0 + (d - c) * 1e-3;
          if (e->type != OP_Q || e == o || dt < 0 || dt > long_while) continue;
          if (((e->id ^ o->id) & (256 + 31)) == 0) lw = false;
          if (e->id / kH == o->id / kH) lx = false;
        }
      o->quarter = (lw ? P_LASTW : 0) | (lx ? P_LASTX : 0);
    }
  sort(wr, n_wr);
  int holder[N_TILE];
  for (int i = 0; i < n_wr; i++) {
    int best = -1;
    for (int sl = 0; sl < st.slots; sl++)
      if (use[holder[sl]].freed + margin <= wr[i].t && (best < 0 || use[holder[sl]].freed < use[holder[best]].freed)) best = sl;
    Use& u = use[wr[i].id];
    if (best >= 0) { u.prev = holder[best]; use[u.prev].next = true; wr[i].o->flags |= P_GATE; }
    else if (st.slots == N_TILE) return false;
    else best = st.slots++;
    u.slot = best;
    holder[best] = wr[i].id;
  }
  {
    int pos[N_CL] = {}, flag[ID_PART + 4 * N_TEAM] = {}, seen[ID_PART] = {};
    auto goal = [&](int c) { return op[c][n_op[c] - 1].item0; };
    for (bool moved = true; moved;) {
      moved = false;
      for (int c = 0; c < 2 * n_pair; c++) {
        for (; pos[c] < goal(c); pos[c]++, moved = true) {
          bool ok = true;
          for (const Op* o = op[c]; o->type != OP_END; o++) {
            const int k = pos[c] - o->item0, own = o->type == OP_A ? o->id : N_TILE + (o->park & 127);
            if (k < 0 || k >= o->items) continue;
            if (o->type == OP_O) ok = k >= o->n || flag[o->id + k / 3];
            else if (k == o->items - 1 && (o->flags & P_GATE)) ok = seen[use[own].prev] == use[use[own].prev].readers;
            else if (k == 0 && o->type == OP_A && (o->flags & F_PARK)) ok = flag[N_TILE + o->park];
          }
          if (!ok) break;
          for (const Op* o = op[c]; o->type != OP_END; o++) {
            if (pos[c] == o->item0 + o->items + (o[1].type == OP_Q ? 7 : o[1].item0 == goal(c) ? -1 : 5)) {
              if (o->type == OP_A) flag[o->id] = 1;
              if (o->type == OP_Q && (o->flags & F_PARK)) flag[N_TILE + o->park] = 1;
              if (o->type == OP_O) flag[ID_PART + o->id / kH * 4 + o->quarter] = flag[ID_PART + o->id / kH * 4 + o->quarter + 1] = 1;
            }
            const int k = pos[c] - FLIGHT - o->item0, nw = o->n - TAIL;
            if (k == 0 && o->type == OP_A && (o->flags & F_PARK)) seen[N_TILE + o->park]++;
            if (o->type == OP_O && k >= 0 && k < o->items && (k < nw || k >= o->n) && (k < nw ? k : k - TAIL) % 3 == 2) seen[o->id + (k < nw ? k : k - TAIL) / 3]++;
          }
        }
      }
    }
    for (int c = 0; c < 2 * n_pair; c++) if (pos[c] < goal(c)) return false;
  }
  int n_job = 0, longest = 0;
  for (int i = 0; i < 2 * N_TEAM; i++) if (kH + 1 - covered[i] / 3 > longest) longest = kH + 1 - covered[i] / 3;
  for (int c = 0; c < 2 * n_pair; c++) {
    uint32_t items = 0, cur = 0, pend = 0;
    int n = 0, ev = 0;
    auto item = [&](uint32_t bytes, int count) {
      for (int i = 0; i < count; i++) { if (cur + bytes > RING) cur = 0; cur += bytes; items++; }
    };
    auto event = [&](uint32_t e) { if (ev < MAX_TAB) P.prog[c].ev[ev] = e; ev++; };
    for (const Op* o = op[c];; o++) {
      if (o->type != OP_END && phase && (o->type == OP_O) != (phase == 2)) continue;
      uint32_t cw = o->type | (items % (2 * NBAR)) << 15 | (cur >> 12) << 20 | pend, pw = o->type | o->id << 2 | o->flags;
      const int ps = use[N_TILE + (o->park & 127)].slot;
      pend = 0;
      if (o->type == OP_O) {
        pw |= o->n << 13 | o->quarter << 20 | (uint32_t)o->park << 23;
        if (o->flags & P_WIDE) {
          cw |= o->n << 2 | (o->id / kH * 2 + o->quarter / 2) << 9 | C_WIDE;
          item(SZ_W, o->n - TAIL);
          item(SZ_W2, TAIL);
          item(SZ_W3, TAIL);
          pend = C_PEND;
          for (int i = 0; 3 * i < o->n; i++) event((o->id + i) | E_ON | (use[o->id + i].next ? 0 : E_LAST));
        } else {
          dem[n_job++] = {o->t0 - 1e6 * o->n, nullptr, (int)pw};
          st.own[c] = pw;
          pw = OP_O;
          event(E_DRAW | (items < 16 ? 0 : items - 16));
        }
      } else if (o->type != OP_END) {
        const bool parks = o->type == OP_Q && (o->flags & F_PARK);
        cw |= (parks ? ps : use[o->id].slot) << 2 | (o->flags & F_PARK);
        if (o->flags & F_PARK) pw |= o->park << 13 | ps << 20;
        if (o->type == OP_Q) { item(SZ_Q, 10); pw |= o->quarter; }
        else { if (o->flags & F_PARK) { item(SZ_PARK, 1); event((N_TILE + o->park) | E_ON | (use[N_TILE + o->park].next ? 0 : E_LAST)); } item(SZ_KV, 32); }
        if (parks || o->type == OP_A) pend = C_PEND;
        if (o->flags & P_GATE) event(use[parks ? N_TILE + o->park : o->id].prev | E_ON | E_FREE);
      }
      P.prog[c].c[n] = cw; P.prog[c].p[n++] = pw;
      if (o->type == OP_END) { if (o->t0 > st.end) st.end = o->t0; break; }
    }
    if (ev > MAX_TAB || ev + longest > MAX_EV) return false;
    P.prog[c].n_ev = ev;
    while (n < MAX_OPS) { P.prog[c].c[n] = OP_END; P.prog[c].p[n++] = OP_END; }
    P.first[c] = (uint16_t)(P.prog[c].p[0] & 2047);
  }
  sort(dem, n_job);
  for (int i = 0; i < n_job; i++) P.job[i] = dem[i].id;
  for (int i = 0; i < ID_PART; i++) {
    if (i < N_TILE) P.slot[i] = use[i].slot;
    P.info[i] = (use[i].readers + use[i].next) | (use[i].next ? I_NEXT : 0);
  }
  if (stats) *stats = st;
  return true;
}

const char* const kPrograms[N_CL / 2] = {
  "PNJ06565NNNNN", "PNJ15858NNNNN", "PNJ25656NNNNN", "PNJ35454+NNNNN", "PNJ47878NNNNN", "PNJ57373NNNNN",
  "NNJ68080NNNN", "NNJ76868NNNN", "NNNNNJ83535NN", "NNNNNNJf4343N", "NNNNNJa5252NN", "NNNNNJb4848NN",
  "NUNNNNNNN", "NUNNNJd5353NN", "NUNNNJe6363NN", "NNNNNJ97676N", "PNNNNNNNNN", "PNNNNNNNNN",
  "PNNNNNNNNN", "PNNNNNNNNN", "PNNNNNNNNN", "NNNNNNNNN", "NNNNNNNNN", "NNNNNNNNN",
  "NUNNNNNNN", "NNNNNNNNN", "NUNNNNNNN", "NUNNNNNNN", "NNUNNNNNN", "NUNNNNNNN",
  "NUNNNNNNN", "NNUNNJc5353NN", "NUNNNNNNN",
};

const char* const* bench_programs() {
  return kPrograms;
}

}

extern "C" void kernel_launch(void* const* d_in, const int* in_sizes, int n_in, void* d_out, int out_size) {
  (void)in_sizes; (void)n_in; (void)out_size;
  static EncodeFn fn = nullptr;
  static int n_clusters = 0;
  if (!fn) {
    cudaDriverEntryPointQueryResult qr;
    void* f = nullptr;
    cudaGetDriverEntryPoint("cuTensorMapEncodeTiled", &f, cudaEnableDefault, &qr);
    fn = (EncodeFn)f;
    cudaFuncSetAttribute(fused_kernel, cudaFuncAttributeMaxDynamicSharedMemorySize, SMEM_BYTES);
    cudaLaunchConfig_t cfg = {};
    cfg.gridDim = dim3(132); cfg.blockDim = dim3(384); cfg.dynamicSmemBytes = SMEM_BYTES;
    cudaLaunchAttribute at[1];
    at[0].id = cudaLaunchAttributeClusterDimension; at[0].val.clusterDim.x = 2; at[0].val.clusterDim.y = 1; at[0].val.clusterDim.z = 1;
    cfg.attrs = at; cfg.numAttrs = 1;
    if (cudaOccupancyMaxActiveClusters(&n_clusters, fused_kernel, &cfg) != cudaSuccess || n_clusters < 1) n_clusters = 1;
    (void)cudaGetLastError();
  }
  static Params P;
  const CUtensorMapSwizzle S128 = CU_TENSOR_MAP_SWIZZLE_128B, S64 = CU_TENSOR_MAP_SWIZZLE_64B;
  for (int blk = 0; blk < 2; blk++) {
    void* const* in = d_in + 5 * blk;
    { const cuuint64_t d[] = {kD, kB * kSq}, s[] = {kD * 2}; const cuuint32_t b[] = {64, 128};
      encode(fn, &P.x[blk], in[0], 2, d, s, b, S128); }
    { const cuuint64_t d[] = {64, 8, 3, (cuuint64_t)kB * kH * kSk / 8}, s[] = {kDh * 2, 128, 8 * kDh * 2}; const cuuint32_t b[] = {64, 8, 3, 4};
      encode(fn, &P.k[blk], in[1], 4, d, s, b, S128);
      encode(fn, &P.v[blk], in[2], 4, d, s, b, S128); }
    { const cuuint64_t d[] = {64, kD, kHD / 64}, s[] = {kHD * 2, 128}; const cuuint32_t b[] = {64, 32, 3};
      encode(fn, &P.wq[blk], in[3], 3, d, s, b, S128); }
    { const cuuint64_t d[] = {32, 2, kHD / 8, 4, kD / 32}, s[] = {kD * 2, 8 * kD * 2, 2 * kD * 2, 64}; const cuuint32_t b[] = {32, 2, 4, 4, 5};
      encode(fn, &P.wo[blk], in[4], 5, d, s, b, S64); }
    { const cuuint64_t d[] = {64, 2, kHD / 8, 4, kD / 64}, s[] = {kD * 2, 8 * kD * 2, 2 * kD * 2, 128};
      const cuuint32_t b3[] = {64, 2, 4, 4, 3}, b2[] = {64, 2, 4, 4, 2};
      encode(fn, &P.wo3[blk], in[4], 5, d, s, b3, S128);
      encode(fn, &P.wo2[blk], in[4], 5, d, s, b2, S128); }
  }
  { const cuuint64_t d[] = {32, kB * kSq, 2 * kD / 32}, s[] = {2 * kD * 2, 64}; const cuuint32_t b[] = {32, 16, 1};
    encode(fn, &P.out, d_out, 3, d, s, b, S64); }

  P.kv[0] = (const char*)d_in[1]; P.kv[1] = (const char*)d_in[6]; P.kv[2] = (const char*)d_in[2]; P.kv[3] = (const char*)d_in[7];
  P.xw[0] = (const char*)d_in[0]; P.xw[1] = (const char*)d_in[3];
  cudaGetSymbolAddress((void**)&P.g, g_scratch);
  P.dbg = DBG_DEFAULT;
  if (n_clusters >= N_CL && plan(bench_programs(), N_CL / 2, 0, P)) {
    fused_kernel<<<2 * N_CL, 384, SMEM_BYTES>>>(P);
  } else {
    const char* text[2 * N_TEAM];
    for (int i = 0; i < 2 * N_TEAM; i++) text[i] = "NNNNNNNN";
    for (int phase = 1; phase <= 2; phase++) {
      plan(text, 2 * N_TEAM, phase, P);
      fused_kernel<<<8 * N_TEAM, 384, SMEM_BYTES>>>(P);
    }
  }
}
```

```cpp
#include <cuda_runtime.h>
#include <cuda_bf16.h>
#include <cuda.h>
#include <cuda/annotated_ptr>
#include <stdint.h>
#include <stdio.h>

namespace {

constexpr int kB = 8, kSq = 256, kD = 640, kH = 32, kSk = 1024, kDh = 192;
constexpr int kHD = kH * kDh;
constexpr uint32_t RING = 224 * 1024;
constexpr uint32_t SZ_KV = 24576;
constexpr uint32_t SZ_Q = 16384 + 24576;
constexpr uint32_t SZ_O = 16384 + 20480;
constexpr uint32_t SZ_W3 = 16384 + 24576, SZ_W2 = 16384 + 16384, SZ_W = SZ_W3 + 16384;
constexpr uint32_t SZ_PARK = 49152;
constexpr uint32_t SZ_OL = SZ_O + 8192;
constexpr int NBAR = 16, FLIGHT = RING / SZ_KV + 1;
constexpr int EARLY = 3;
constexpr int kSteps = kHD / 64;
constexpr int TAIL = 4;
constexpr uint32_t KV_CH = 64, KV_SBO = 3072;
constexpr int SMEM_BYTES = RING + 1024 + 1024;
constexpr int N_TEAM = 16, N_CL = 66, MAX_OPS = 22, MAX_EV = 72, MAX_TAB = 47, N_TILE = N_TEAM * kH, MAX_PARK = 128, ID_PART = N_TILE + MAX_PARK;
enum : uint32_t { OP_END = 0, OP_Q = 1, OP_A = 2, OP_O = 3, F_PARK = 1 << 11,
                  C_WIDE = 1 << 27, C_PEND = 1 << 26, P_GATE = 1 << 12, P_WIDE = 1 << 11, P_LD = 1 << 12, P_PRE = 1 << 22, P_LASTW = 1 << 29, P_LASTX = 1 << 30,
                  I_NEXT = 8, E_ON = 1 << 15, E_FREE = 1 << 14, E_LAST = 1 << 13, E_DRAW = 1 << 12, E_JOB = 1 << 11 };

constexpr uint32_t DBG_DEFAULT = 0x040800;

struct alignas(1024) Scratch {
  unsigned int flag[2047];
  unsigned int ticket;
  uint4 part[N_TEAM * 2 * 2 * 5120];
  uint4 tile[N_TILE * 2 * 3072];
};

struct alignas(64) Params {
  const char* xw[2];
  uint16_t first[80];
  Scratch* g;
  uint32_t dbg;
  CUtensorMap x[2], wq[2], k[2], v[2], wo[2], wo3[2], wo2[2], out;
  struct {
    uint32_t c[MAX_OPS];
    uint32_t p[MAX_OPS];
    uint16_t n_ev, ev[MAX_TAB];
  } prog[N_CL];
  const char* kv[4];
  uint32_t job[N_CL];
  uint16_t slot[N_TILE];
  uint8_t info[ID_PART];
};

__device__ Scratch g_scratch;

template <int TB, int TA = 0>
__device__ __forceinline__ void wgmma_ss_n64(float (&d)[32], uint64_t da, uint64_t db, int scale_d) {
  asm volatile("{\n.reg .pred p;\nsetp.ne.b32 p, %34, 0;\n"
    "wgmma.mma_async.sync.aligned.m64n64k16.f32.bf16.bf16 {%0, %1, %2, %3, %4, %5, %6, %7, %8, %9, %10, %11, %12, %13, %14, %15, %16, %17, %18, %19, %20, %21, %22, %23, %24, %25, %26, %27, %28, %29, %30, %31}, %32, %33, p, 1, 1, %35, %36;\n}\n"
    : "+f"(d[0]), "+f"(d[1]), "+f"(d[2]), "+f"(d[3]), "+f"(d[4]), "+f"(d[5]), "+f"(d[6]), "+f"(d[7]), "+f"(d[8]), "+f"(d[9]), "+f"(d[10]), "+f"(d[11]), "+f"(d[12]), "+f"(d[13]), "+f"(d[14]), "+f"(d[15]), "+f"(d[16]), "+f"(d[17]), "+f"(d[18]), "+f"(d[19]), "+f"(d[20]), "+f"(d[21]), "+f"(d[22]), "+f"(d[23]), "+f"(d[24]), "+f"(d[25]), "+f"(d[26]), "+f"(d[27]), "+f"(d[28]), "+f"(d[29]), "+f"(d[30]), "+f"(d[31])
    : "l"(da), "l"(db), "r"(scale_d), "n"(TA), "n"(TB));
}
template <int TB>
__device__ __forceinline__ void wgmma_rs_n64(float (&d)[32], uint32_t a0, uint32_t a1, uint32_t a2, uint32_t a3, uint64_t db, int scale_d) {
  asm volatile("{\n.reg .pred p;\nsetp.ne.b32 p, %37, 0;\n"
    "wgmma.mma_async.sync.aligned.m64n64k16.f32.bf16.bf16 {%0, %1, %2, %3, %4, %5, %6, %7, %8, %9, %10, %11, %12, %13, %14, %15, %16, %17, %18, %19, %20, %21, %22, %23, %24, %25, %26, %27, %28, %29, %30, %31}, {%32, %33, %34, %35}, %36, p, 1, 1, %38;\n}\n"
    : "+f"(d[0]), "+f"(d[1]), "+f"(d[2]), "+f"(d[3]), "+f"(d[4]), "+f"(d[5]), "+f"(d[6]), "+f"(d[7]), "+f"(d[8]), "+f"(d[9]), "+f"(d[10]), "+f"(d[11]), "+f"(d[12]), "+f"(d[13]), "+f"(d[14]), "+f"(d[15]), "+f"(d[16]), "+f"(d[17]), "+f"(d[18]), "+f"(d[19]), "+f"(d[20]), "+f"(d[21]), "+f"(d[22]), "+f"(d[23]), "+f"(d[24]), "+f"(d[25]), "+f"(d[26]), "+f"(d[27]), "+f"(d[28]), "+f"(d[29]), "+f"(d[30]), "+f"(d[31])
    : "r"(a0), "r"(a1), "r"(a2), "r"(a3), "l"(db), "r"(scale_d), "n"(TB));
}
template <int TB, int TA = 0>
__device__ __forceinline__ void wgmma_ss_n128(float (&d)[64], uint64_t da, uint64_t db, int scale_d) {
  asm volatile("{\n.reg .pred p;\nsetp.ne.b32 p, %66, 0;\n"
    "wgmma.mma_async.sync.aligned.m64n128k16.f32.bf16.bf16 {%0, %1, %2, %3, %4, %5, %6, %7, %8, %9, %10, %11, %12, %13, %14, %15, %16, %17, %18, %19, %20, %21, %22, %23, %24, %25, %26, %27, %28, %29, %30, %31, %32, %33, %34, %35, %36, %37, %38, %39, %40, %41, %42, %43, %44, %45, %46, %47, %48, %49, %50, %51, %52, %53, %54, %55, %56, %57, %58, %59, %60, %61, %62, %63}, %64, %65, p, 1, 1, %67, %68;\n}\n"
    : "+f"(d[0]), "+f"(d[1]), "+f"(d[2]), "+f"(d[3]), "+f"(d[4]), "+f"(d[5]), "+f"(d[6]), "+f"(d[7]), "+f"(d[8]), "+f"(d[9]), "+f"(d[10]), "+f"(d[11]), "+f"(d[12]), "+f"(d[13]), "+f"(d[14]), "+f"(d[15]), "+f"(d[16]), "+f"(d[17]), "+f"(d[18]), "+f"(d[19]), "+f"(d[20]), "+f"(d[21]), "+f"(d[22]), "+f"(d[23]), "+f"(d[24]), "+f"(d[25]), "+f"(d[26]), "+f"(d[27]), "+f"(d[28]), "+f"(d[29]), "+f"(d[30]), "+f"(d[31]), "+f"(d[32]), "+f"(d[33]), "+f"(d[34]), "+f"(d[35]), "+f"(d[36]), "+f"(d[37]), "+f"(d[38]), "+f"(d[39]), "+f"(d[40]), "+f"(d[41]), "+f"(d[42]), "+f"(d[43]), "+f"(d[44]), "+f"(d[45]), "+f"(d[46]), "+f"(d[47]), "+f"(d[48]), "+f"(d[49]), "+f"(d[50]), "+f"(d[51]), "+f"(d[52]), "+f"(d[53]), "+f"(d[54]), "+f"(d[55]), "+f"(d[56]), "+f"(d[57]), "+f"(d[58]), "+f"(d[59]), "+f"(d[60]), "+f"(d[61]), "+f"(d[62]), "+f"(d[63])
    : "l"(da), "l"(db), "r"(scale_d), "n"(TA), "n"(TB));
}
template <int TB>
__device__ __forceinline__ void wgmma_rs_n128(float (&d)[64], uint32_t a0, uint32_t a1, uint32_t a2, uint32_t a3, uint64_t db, int scale_d) {
  asm volatile("{\n.reg .pred p;\nsetp.ne.b32 p, %69, 0;\n"
    "wgmma.mma_async.sync.aligned.m64n128k16.f32.bf16.bf16 {%0, %1, %2, %3, %4, %5, %6, %7, %8, %9, %10, %11, %12, %13, %14, %15, %16, %17, %18, %19, %20, %21, %22, %23, %24, %25, %26, %27, %28, %29, %30, %31, %32, %33, %34, %35, %36, %37, %38, %39, %40, %41, %42, %43, %44, %45, %46, %47, %48, %49, %50, %51, %52, %53, %54, %55, %56, %57, %58, %59, %60, %61, %62, %63}, {%64, %65, %66, %67}, %68, p, 1, 1, %70;\n}\n"
    : "+f"(d[0]), "+f"(d[1]), "+f"(d[2]), "+f"(d[3]), "+f"(d[4]), "+f"(d[5]), "+f"(d[6]), "+f"(d[7]), "+f"(d[8]), "+f"(d[9]), "+f"(d[10]), "+f"(d[11]), "+f"(d[12]), "+f"(d[13]), "+f"(d[14]), "+f"(d[15]), "+f"(d[16]), "+f"(d[17]), "+f"(d[18]), "+f"(d[19]), "+f"(d[20]), "+f"(d[21]), "+f"(d[22]), "+f"(d[23]), "+f"(d[24]), "+f"(d[25]), "+f"(d[26]), "+f"(d[27]), "+f"(d[28]), "+f"(d[29]), "+f"(d[30]), "+f"(d[31]), "+f"(d[32]), "+f"(d[33]), "+f"(d[34]), "+f"(d[35]), "+f"(d[36]), "+f"(d[37]), "+f"(d[38]), "+f"(d[39]), "+f"(d[40]), "+f"(d[41]), "+f"(d[42]), "+f"(d[43]), "+f"(d[44]), "+f"(d[45]), "+f"(d[46]), "+f"(d[47]), "+f"(d[48]), "+f"(d[49]), "+f"(d[50]), "+f"(d[51]), "+f"(d[52]), "+f"(d[53]), "+f"(d[54]), "+f"(d[55]), "+f"(d[56]), "+f"(d[57]), "+f"(d[58]), "+f"(d[59]), "+f"(d[60]), "+f"(d[61]), "+f"(d[62]), "+f"(d[63])
    : "r"(a0), "r"(a1), "r"(a2), "r"(a3), "l"(db), "r"(scale_d), "n"(TB));
}
template <int TB, int TA = 0>
__device__ __forceinline__ void wgmma_ss_n160(float (&d)[80], uint64_t da, uint64_t db, int scale_d) {
  asm volatile("{\n.reg .pred p;\nsetp.ne.b32 p, %82, 0;\n"
    "wgmma.mma_async.sync.aligned.m64n160k16.f32.bf16.bf16 {%0, %1, %2, %3, %4, %5, %6, %7, %8, %9, %10, %11, %12, %13, %14, %15, %16, %17, %18, %19, %20, %21, %22, %23, %24, %25, %26, %27, %28, %29, %30, %31, %32, %33, %34, %35, %36, %37, %38, %39, %40, %41, %42, %43, %44, %45, %46, %47, %48, %49, %50, %51, %52, %53, %54, %55, %56, %57, %58, %59, %60, %61, %62, %63, %64, %65, %66, %67, %68, %69, %70, %71, %72, %73, %74, %75, %76, %77, %78, %79}, %80, %81, p, 1, 1, %83, %84;\n}\n"
    : "+f"(d[0]), "+f"(d[1]), "+f"(d[2]), "+f"(d[3]), "+f"(d[4]), "+f"(d[5]), "+f"(d[6]), "+f"(d[7]), "+f"(d[8]), "+f"(d[9]), "+f"(d[10]), "+f"(d[11]), "+f"(d[12]), "+f"(d[13]), "+f"(d[14]), "+f"(d[15]), "+f"(d[16]), "+f"(d[17]), "+f"(d[18]), "+f"(d[19]), "+f"(d[20]), "+f"(d[21]), "+f"(d[22]), "+f"(d[23]), "+f"(d[24]), "+f"(d[25]), "+f"(d[26]), "+f"(d[27]), "+f"(d[28]), "+f"(d[29]), "+f"(d[30]), "+f"(d[31]), "+f"(d[32]), "+f"(d[33]), "+f"(d[34]), "+f"(d[35]), "+f"(d[36]), "+f"(d[37]), "+f"(d[38]), "+f"(d[39]), "+f"(d[40]), "+f"(d[41]), "+f"(d[42]), "+f"(d[43]), "+f"(d[44]), "+f"(d[45]), "+f"(d[46]), "+f"(d[47]), "+f"(d[48]), "+f"(d[49]), "+f"(d[50]), "+f"(d[51]), "+f"(d[52]), "+f"(d[53]), "+f"(d[54]), "+f"(d[55]), "+f"(d[56]), "+f"(d[57]), "+f"(d[58]), "+f"(d[59]), "+f"(d[60]), "+f"(d[61]), "+f"(d[62]), "+f"(d[63]), "+f"(d[64]), "+f"(d[65]), "+f"(d[66]), "+f"(d[67]), "+f"(d[68]), "+f"(d[69]), "+f"(d[70]), "+f"(d[71]), "+f"(d[72]), "+f"(d[73]), "+f"(d[74]), "+f"(d[75]), "+f"(d[76]), "+f"(d[77]), "+f"(d[78]), "+f"(d[79])
    : "l"(da), "l"(db), "r"(scale_d), "n"(TA), "n"(TB));
}
template <int TB>
__device__ __forceinline__ void wgmma_rs_n160(float (&d)[80], uint32_t a0, uint32_t a1, uint32_t a2, uint32_t a3, uint64_t db, int scale_d) {
  asm volatile("{\n.reg .pred p;\nsetp.ne.b32 p, %85, 0;\n"
    "wgmma.mma_async.sync.aligned.m64n160k16.f32.bf16.bf16 {%0, %1, %2, %3, %4, %5, %6, %7, %8, %9, %10, %11, %12, %13, %14, %15, %16, %17, %18, %19, %20, %21, %22, %23, %24, %25, %26, %27, %28, %29, %30, %31, %32, %33, %34, %35, %36, %37, %38, %39, %40, %41, %42, %43, %44, %45, %46, %47, %48, %49, %50, %51, %52, %53, %54, %55, %56, %57, %58, %59, %60, %61, %62, %63, %64, %65, %66, %67, %68, %69, %70, %71, %72, %73, %74, %75, %76, %77, %78, %79}, {%80, %81, %82, %83}, %84, p, 1, 1, %86;\n}\n"
    : "+f"(d[0]), "+f"(d[1]), "+f"(d[2]), "+f"(d[3]), "+f"(d[4]), "+f"(d[5]), "+f"(d[6]), "+f"(d[7]), "+f"(d[8]), "+f"(d[9]), "+f"(d[10]), "+f"(d[11]), "+f"(d[12]), "+f"(d[13]), "+f"(d[14]), "+f"(d[15]), "+f"(d[16]), "+f"(d[17]), "+f"(d[18]), "+f"(d[19]), "+f"(d[20]), "+f"(d[21]), "+f"(d[22]), "+f"(d[23]), "+f"(d[24]), "+f"(d[25]), "+f"(d[26]), "+f"(d[27]), "+f"(d[28]), "+f"(d[29]), "+f"(d[30]), "+f"(d[31]), "+f"(d[32]), "+f"(d[33]), "+f"(d[34]), "+f"(d[35]), "+f"(d[36]), "+f"(d[37]), "+f"(d[38]), "+f"(d[39]), "+f"(d[40]), "+f"(d[41]), "+f"(d[42]), "+f"(d[43]), "+f"(d[44]), "+f"(d[45]), "+f"(d[46]), "+f"(d[47]), "+f"(d[48]), "+f"(d[49]), "+f"(d[50]), "+f"(d[51]), "+f"(d[52]), "+f"(d[53]), "+f"(d[54]), "+f"(d[55]), "+f"(d[56]), "+f"(d[57]), "+f"(d[58]), "+f"(d[59]), "+f"(d[60]), "+f"(d[61]), "+f"(d[62]), "+f"(d[63]), "+f"(d[64]), "+f"(d[65]), "+f"(d[66]), "+f"(d[67]), "+f"(d[68]), "+f"(d[69]), "+f"(d[70]), "+f"(d[71]), "+f"(d[72]), "+f"(d[73]), "+f"(d[74]), "+f"(d[75]), "+f"(d[76]), "+f"(d[77]), "+f"(d[78]), "+f"(d[79])
    : "r"(a0), "r"(a1), "r"(a2), "r"(a3), "l"(db), "r"(scale_d), "n"(TB));
}
template <int TB, int TA = 0>
__device__ __forceinline__ void wgmma_ss_n192(float (&d)[96], uint64_t da, uint64_t db, int scale_d) {
  asm volatile("{\n.reg .pred p;\nsetp.ne.b32 p, %98, 0;\n"
    "wgmma.mma_async.sync.aligned.m64n192k16.f32.bf16.bf16 {%0, %1, %2, %3, %4, %5, %6, %7, %8, %9, %10, %11, %12, %13, %14, %15, %16, %17, %18, %19, %20, %21, %22, %23, %24, %25, %26, %27, %28, %29, %30, %31, %32, %33, %34, %35, %36, %37, %38, %39, %40, %41, %42, %43, %44, %45, %46, %47, %48, %49, %50, %51, %52, %53, %54, %55, %56, %57, %58, %59, %60, %61, %62, %63, %64, %65, %66, %67, %68, %69, %70, %71, %72, %73, %74, %75, %76, %77, %78, %79, %80, %81, %82, %83, %84, %85, %86, %87, %88, %89, %90, %91, %92, %93, %94, %95}, %96, %97, p, 1, 1, %99, %100;\n}\n"
    : "+f"(d[0]), "+f"(d[1]), "+f"(d[2]), "+f"(d[3]), "+f"(d[4]), "+f"(d[5]), "+f"(d[6]), "+f"(d[7]), "+f"(d[8]), "+f"(d[9]), "+f"(d[10]), "+f"(d[11]), "+f"(d[12]), "+f"(d[13]), "+f"(d[14]), "+f"(d[15]), "+f"(d[16]), "+f"(d[17]), "+f"(d[18]), "+f"(d[19]), "+f"(d[20]), "+f"(d[21]), "+f"(d[22]), "+f"(d[23]), "+f"(d[24]), "+f"(d[25]), "+f"(d[26]), "+f"(d[27]), "+f"(d[28]), "+f"(d[29]), "+f"(d[30]), "+f"(d[31]), "+f"(d[32]), "+f"(d[33]), "+f"(d[34]), "+f"(d[35]), "+f"(d[36]), "+f"(d[37]), "+f"(d[38]), "+f"(d[39]), "+f"(d[40]), "+f"(d[41]), "+f"(d[42]), "+f"(d[43]), "+f"(d[44]), "+f"(d[45]), "+f"(d[46]), "+f"(d[47]), "+f"(d[48]), "+f"(d[49]), "+f"(d[50]), "+f"(d[51]), "+f"(d[52]), "+f"(d[53]), "+f"(d[54]), "+f"(d[55]), "+f"(d[56]), "+f"(d[57]), "+f"(d[58]), "+f"(d[59]), "+f"(d[60]), "+f"(d[61]), "+f"(d[62]), "+f"(d[63]), "+f"(d[64]), "+f"(d[65]), "+f"(d[66]), "+f"(d[67]), "+f"(d[68]), "+f"(d[69]), "+f"(d[70]), "+f"(d[71]), "+f"(d[72]), "+f"(d[73]), "+f"(d[74]), "+f"(d[75]), "+f"(d[76]), "+f"(d[77]), "+f"(d[78]), "+f"(d[79]), "+f"(d[80]), "+f"(d[81]), "+f"(d[82]), "+f"(d[83]), "+f"(d[84]), "+f"(d[85]), "+f"(d[86]), "+f"(d[87]), "+f"(d[88]), "+f"(d[89]), "+f"(d[90]), "+f"(d[91]), "+f"(d[92]), "+f"(d[93]), "+f"(d[94]), "+f"(d[95])
    : "l"(da), "l"(db), "r"(scale_d), "n"(TA), "n"(TB));
}
template <int TB>
__device__ __forceinline__ void wgmma_rs_n192(float (&d)[96], uint32_t a0, uint32_t a1, uint32_t a2, uint32_t a3, uint64_t db, int scale_d) {
  asm volatile("{\n.reg .pred p;\nsetp.ne.b32 p, %101, 0;\n"
    "wgmma.mma_async.sync.aligned.m64n192k16.f32.bf16.bf16 {%0, %1, %2, %3, %4, %5, %6, %7, %8, %9, %10, %11, %12, %13, %14, %15, %16, %17, %18, %19, %20, %21, %22, %23, %24, %25, %26, %27, %28, %29, %30, %31, %32, %33, %34, %35, %36, %37, %38, %39, %40, %41, %42, %43, %44, %45, %46, %47, %48, %49, %50, %51, %52, %53, %54, %55, %56, %57, %58, %59, %60, %61, %62, %63, %64, %65, %66, %67, %68, %69, %70, %71, %72, %73, %74, %75, %76, %77, %78, %79, %80, %81, %82, %83, %84, %85, %86, %87, %88, %89, %90, %91, %92, %93, %94, %95}, {%96, %97, %98, %99}, %100, p, 1, 1, %102;\n}\n"
    : "+f"(d[0]), "+f"(d[1]), "+f"(d[2]), "+f"(d[3]), "+f"(d[4]), "+f"(d[5]), "+f"(d[6]), "+f"(d[7]), "+f"(d[8]), "+f"(d[9]), "+f"(d[10]), "+f"(d[11]), "+f"(d[12]), "+f"(d[13]), "+f"(d[14]), "+f"(d[15]), "+f"(d[16]), "+f"(d[17]), "+f"(d[18]), "+f"(d[19]), "+f"(d[20]), "+f"(d[21]), "+f"(d[22]), "+f"(d[23]), "+f"(d[24]), "+f"(d[25]), "+f"(d[26]), "+f"(d[27]), "+f"(d[28]), "+f"(d[29]), "+f"(d[30]), "+f"(d[31]), "+f"(d[32]), "+f"(d[33]), "+f"(d[34]), "+f"(d[35]), "+f"(d[36]), "+f"(d[37]), "+f"(d[38]), "+f"(d[39]), "+f"(d[40]), "+f"(d[41]), "+f"(d[42]), "+f"(d[43]), "+f"(d[44]), "+f"(d[45]), "+f"(d[46]), "+f"(d[47]), "+f"(d[48]), "+f"(d[49]), "+f"(d[50]), "+f"(d[51]), "+f"(d[52]), "+f"(d[53]), "+f"(d[54]), "+f"(d[55]), "+f"(d[56]), "+f"(d[57]), "+f"(d[58]), "+f"(d[59]), "+f"(d[60]), "+f"(d[61]), "+f"(d[62]), "+f"(d[63]), "+f"(d[64]), "+f"(d[65]), "+f"(d[66]), "+f"(d[67]), "+f"(d[68]), "+f"(d[69]), "+f"(d[70]), "+f"(d[71]), "+f"(d[72]), "+f"(d[73]), "+f"(d[74]), "+f"(d[75]), "+f"(d[76]), "+f"(d[77]), "+f"(d[78]), "+f"(d[79]), "+f"(d[80]), "+f"(d[81]), "+f"(d[82]), "+f"(d[83]), "+f"(d[84]), "+f"(d[85]), "+f"(d[86]), "+f"(d[87]), "+f"(d[88]), "+f"(d[89]), "+f"(d[90]), "+f"(d[91]), "+f"(d[92]), "+f"(d[93]), "+f"(d[94]), "+f"(d[95])
    : "r"(a0), "r"(a1), "r"(a2), "r"(a3), "l"(db), "r"(scale_d), "n"(TB));
}

__device__ __forceinline__ uint32_t smem_u32(const void* p) { return (uint32_t)__cvta_generic_to_shared(p); }
__device__ __forceinline__ void wg_fence() { asm volatile("wgmma.fence.sync.aligned;" ::: "memory"); }
__device__ __forceinline__ void wg_commit() { asm volatile("wgmma.commit_group.sync.aligned;" ::: "memory"); }
template <int N> __device__ __forceinline__ void wg_wait() { asm volatile("wgmma.wait_group.sync.aligned %0;" ::"n"(N) : "memory"); }
__device__ __forceinline__ void sched_fence(uint32_t& keep, bool never) {
  asm volatile("{\n.reg .pred p;\nsetp.ne.b32 p, %1, 0;\n@p mov.u32 %0, %%clock;\n}\n" : "+r"(keep) : "r"((int)never) : "memory");
}
template <int N> __device__ __forceinline__ void fence_regs(float (&r)[N]) {
#pragma unroll
  for (int i = 0; i < N; i++) asm volatile("" : "+f"(r[i])::"memory");
}
template <int N> __device__ __forceinline__ void undefine(float (&r)[N]) {
#pragma unroll
  for (int i = 0; i < N; i++) asm volatile("" : "=f"(r[i]));
}
template <int N> __device__ __forceinline__ void fence_regs(uint32_t (&r)[N]) {
#pragma unroll
  for (int i = 0; i < N; i++) asm volatile("" : "+r"(r[i])::"memory");
}
__device__ __forceinline__ uint64_t mk_desc(uint32_t a16, uint32_t lbo, uint32_t sbo, uint32_t swz) {
  uint64_t d;
  asm("mov.b64 %0, {%1, %2};" : "=l"(d) : "r"(a16 + ((lbo >> 4) << 16)), "r"((sbo >> 4) | (swz << 30)));
  return d;
}
__device__ __forceinline__ void mbar_init(uint32_t bar, uint32_t cnt) {
  asm volatile("mbarrier.init.shared::cta.b64 [%0], %1;" ::"r"(bar), "r"(cnt) : "memory");
}
__device__ __forceinline__ void mbar_expect(uint32_t bar, uint32_t tx) {
  asm volatile("mbarrier.arrive.expect_tx.shared::cta.b64 _, [%0], %1;" ::"r"(bar), "r"(tx) : "memory");
}
__device__ __forceinline__ bool mbar_test(uint32_t bar, uint32_t ph) {
  uint32_t ok;
  asm volatile("{\n.reg .pred p;\nmbarrier.test_wait.parity.shared::cta.b64 p, [%1], %2;\nselp.u32 %0, 1, 0, p;\n}\n"
               : "=r"(ok) : "r"(bar), "r"(ph) : "memory");
  return ok;
}
__device__ __forceinline__ bool mbar_try(uint32_t bar, uint32_t ph, uint32_t ns) {
  uint32_t ok;
  asm volatile("{\n.reg .pred p;\nmbarrier.try_wait.parity.shared::cta.b64 p, [%1], %2, %3;\nselp.u32 %0, 1, 0, p;\n}\n"
               : "=r"(ok) : "r"(bar), "r"(ph), "r"(ns) : "memory");
  return ok;
}
__device__ __forceinline__ void mbar_wait(uint32_t bar, uint32_t ph) {
  asm volatile("{\n.reg .pred p;\n.reg .u32 n;\nmov.u32 n, 0;\n"
               "LOOP:\nmbarrier.try_wait.parity.shared::cta.b64 p, [%0], %1;\n@p bra DONE;\n"
               "add.u32 n, n, 1;\nsetp.lt.u32 p, n, 0x1000000;\n@p bra LOOP;\ntrap;\n"
               "DONE:\n}\n" ::"r"(bar), "r"(ph) : "memory");
}
__device__ __forceinline__ void mbar_wait_long(uint32_t bar) {
  asm volatile("{\n.reg .pred p;\n.reg .u32 n;\nmov.u32 n, 0;\n"
               "LOOP:\nmbarrier.try_wait.parity.shared::cta.b64 p, [%0], 0, 20000;\n@p bra DONE;\n"
               "add.u32 n, n, 1;\nsetp.lt.u32 p, n, 0x100000;\n@p bra LOOP;\ntrap;\n"
               "DONE:\n}\n" ::"r"(bar) : "memory");
}
__device__ __forceinline__ void mbar_arrive_cluster_if(bool on, uint32_t addr) {
  asm volatile("{\n.reg .pred p;\nsetp.ne.b32 p, %1, 0;\n@p mbarrier.arrive.shared::cluster.b64 _, [%0];\n}\n" ::"r"(addr), "r"((int)on) : "memory");
}
__device__ __forceinline__ void mbar_arrive_cluster_n(uint32_t n, uint32_t addr) {
  asm volatile("{\n.reg .pred p;\nsetp.ne.b32 p, %1, 0;\n@p mbarrier.arrive.shared::cluster.b64 _, [%0], %1;\n}\n" ::"r"(addr), "r"(n) : "memory");
}
__device__ __forceinline__ void tma2d(uint32_t dst, const CUtensorMap* m, uint32_t bar, int c0, int c1) {
  asm volatile("cp.async.bulk.tensor.2d.shared::cluster.global.mbarrier::complete_tx::bytes [%0], [%1, {%3, %4}], [%2];"
               ::"r"(dst), "l"(m), "r"(bar), "r"(c0), "r"(c1) : "memory");
}
__device__ __forceinline__ void tma3d(uint32_t dst, const CUtensorMap* m, uint32_t bar, int c0, int c1, int c2) {
  asm volatile("cp.async.bulk.tensor.3d.shared::cluster.global.mbarrier::complete_tx::bytes [%0], [%1, {%3, %4, %5}], [%2];"
               ::"r"(dst), "l"(m), "r"(bar), "r"(c0), "r"(c1), "r"(c2) : "memory");
}
__device__ __forceinline__ void tma2d_hint(uint32_t dst, const CUtensorMap* m, uint32_t bar, int c0, int c1, uint64_t pol) {
  asm volatile("cp.async.bulk.tensor.2d.shared::cluster.global.mbarrier::complete_tx::bytes.L2::cache_hint [%0], [%1, {%3, %4}], [%2], %5;"
               ::"r"(dst), "l"(m), "r"(bar), "r"(c0), "r"(c1), "l"(pol) : "memory");
}
__device__ __forceinline__ void tma3d_mc_hint(uint32_t dst, const CUtensorMap* m, uint32_t bar, int c1, int c2, uint64_t pol) {
  asm volatile("cp.async.bulk.tensor.3d.shared::cluster.global.mbarrier::complete_tx::bytes.multicast::cluster.L2::cache_hint"
               " [%0], [%1, {%3, %4, %5}], [%2], %6, %7;"
               ::"r"(dst), "l"(m), "r"(bar), "r"(0), "r"(c1), "r"(c2), "h"((uint16_t)3), "l"(pol) : "memory");
}
__device__ __forceinline__ void tma5d_mc_hint(uint32_t dst, const CUtensorMap* m, uint32_t bar, int c2, int c4, uint64_t pol) {
  asm volatile("cp.async.bulk.tensor.5d.shared::cluster.global.mbarrier::complete_tx::bytes.multicast::cluster.L2::cache_hint"
               " [%0], [%1, {%3, %3, %4, %3, %5}], [%2], %6, %7;"
               ::"r"(dst), "l"(m), "r"(bar), "r"(0), "r"(c2), "r"(c4), "h"((uint16_t)3), "l"(pol) : "memory");
}
__device__ __forceinline__ void tma3d_store(const CUtensorMap* m, uint32_t src, int c0, int c1, int c2) {
  asm volatile("cp.async.bulk.tensor.3d.global.shared::cta.bulk_group [%0, {%2, %3, %4}], [%1];"
               ::"l"(m), "r"(src), "r"(c0), "r"(c1), "r"(c2) : "memory");
}
__device__ __forceinline__ void bar_sync(int id, int n) { asm volatile("bar.sync %0, %1;" ::"r"(id), "r"(n) : "memory"); }
__device__ __forceinline__ uint32_t pack_bf16(float lo, float hi) {
  uint32_t r;
  asm("cvt.rn.bf16x2.f32 %0, %1, %2;" : "=r"(r) : "f"(hi), "f"(lo));
  return r;
}
__device__ __forceinline__ float ex2(float x) {
  float y;
  asm("ex2.approx.ftz.f32 %0, %1;" : "=f"(y) : "f"(x));
  return y;
}
__device__ __forceinline__ float rcp(float x) {
  float y;
  asm("rcp.approx.ftz.f32 %0, %1;" : "=f"(y) : "f"(x));
  return y;
}
__device__ __forceinline__ void stsm4(uint32_t addr, uint32_t a, uint32_t b, uint32_t c, uint32_t d) {
  asm volatile("stmatrix.sync.aligned.m8n8.x4.shared.b16 [%0], {%1, %2, %3, %4};" ::"r"(addr), "r"(a), "r"(b), "r"(c), "r"(d) : "memory");
}

__device__ __forceinline__ void tma4d_mc_hint(uint32_t dst, const CUtensorMap* m, uint32_t bar, int c3, uint64_t pol) {
  asm volatile("cp.async.bulk.tensor.4d.shared::cluster.global.mbarrier::complete_tx::bytes.multicast::cluster.L2::cache_hint"
               " [%0], [%1, {%3, %3, %3, %4}], [%2], %5, %6;"
               ::"r"(dst), "l"(m), "r"(bar), "r"(0), "r"(c3), "h"((uint16_t)3), "l"(pol) : "memory");
}
__device__ __forceinline__ void bulk_load_hint(uint32_t dst, const void* src, uint32_t bytes, uint32_t bar, uint64_t pol) {
  asm volatile("cp.async.bulk.shared::cluster.global.mbarrier::complete_tx::bytes.L2::cache_hint [%0], [%1], %2, [%3], %4;"
               ::"r"(dst), "l"(src), "r"(bytes), "r"(bar), "l"(pol) : "memory");
}
__device__ __forceinline__ void stg2_if(bool on, void* p, uint32_t a, uint32_t b, uint32_t c, uint32_t d, uint32_t e, uint32_t f,
                                        uint32_t g, uint32_t h, uint64_t pol) {
  asm volatile("{\n.reg .pred p;\nsetp.ne.b32 p, %10, 0;\n"
               "@p st.global.L2::cache_hint.v4.b32 [%0], {%1, %2, %3, %4}, %9;\n"
               "@p st.global.L2::cache_hint.v4.b32 [%0 + 512], {%5, %6, %7, %8}, %9;\n}\n"
               ::"l"(p), "r"(a), "r"(b), "r"(c), "r"(d), "r"(e), "r"(f), "r"(g), "r"(h), "l"(pol), "r"((int)on) : "memory");
}
__device__ __forceinline__ uint64_t evict_first() {
  uint64_t p;
  asm("createpolicy.fractional.L2::evict_first.b64 %0, 1.0;" : "=l"(p));
  return p;
}
__device__ __forceinline__ uint64_t no_hint() {
  uint64_t p;
  asm("createpolicy.cvt.L2.b64 %0, %1;" : "=l"(p) : "l"(static_cast<uint64_t>(cuda::access_property{})));
  return p;
}
__device__ __forceinline__ bool elect() {
  uint32_t ok;
  asm volatile("{\n.reg .pred p;\nelect.sync _|p, 0xffffffff;\nselp.u32 %0, 1, 0, p;\n}\n" : "=r"(ok));
  return ok;
}
__device__ __forceinline__ void mbar_arrive(uint32_t bar) {
  asm volatile("mbarrier.arrive.shared::cta.b64 _, [%0];" ::"r"(bar) : "memory");
}
__device__ __forceinline__ void mbar_arrive_if(bool on, uint32_t bar) {
  asm volatile("{\n.reg .pred p;\nsetp.ne.b32 p, %1, 0;\n@p mbarrier.arrive.shared::cta.b64 _, [%0];\n}\n" ::"r"(bar), "r"((int)on) : "memory");
}
__device__ __forceinline__ void lds2_if(bool on, uint32_t p, uint32_t (&t)[8]) {
  asm volatile("{\n.reg .pred p;\nsetp.ne.b32 p, %9, 0;\n@p ld.shared.v4.b32 {%0, %1, %2, %3}, [%8];\n@p ld.shared.v4.b32 {%4, %5, %6, %7}, [%8 + 512];\n}\n"
               : "+r"(t[0]), "+r"(t[1]), "+r"(t[2]), "+r"(t[3]), "+r"(t[4]), "+r"(t[5]), "+r"(t[6]), "+r"(t[7]) : "r"(p), "r"((int)on) : "memory");
}
__device__ __forceinline__ void lds128(uint32_t p, uint32_t& a, uint32_t& b, uint32_t& c, uint32_t& d) {
  asm volatile("ld.shared.v4.b32 {%0, %1, %2, %3}, [%4];" : "=r"(a), "=r"(b), "=r"(c), "=r"(d) : "r"(p) : "memory");
}
template <class T> __device__ __forceinline__ T* ptr_add(T* base, uint32_t bytes) {
  T* r;
  asm("{\n.reg .u32 lo, hi;\nmov.b64 {lo, hi}, %1;\nadd.cc.u32 lo, lo, %2;\naddc.u32 hi, hi, 0;\nmov.b64 %0, {lo, hi};\n}\n" : "=l"(r) : "l"(base), "r"(bytes));
  return r;
}
__device__ __forceinline__ uint32_t lds32(uint32_t p) {
  uint32_t v;
  asm volatile("ld.volatile.shared.u32 %0, [%1];" : "=r"(v) : "r"(p) : "memory");
  return v;
}
__device__ __forceinline__ uint32_t flag_get(const unsigned int* p) {
  uint32_t v;
  asm volatile("ld.acquire.gpu.global.u32 %0, [%1];" : "=r"(v) : "l"(p) : "memory");
  return v;
}
__device__ __forceinline__ uint32_t wait_word(uint32_t p, uint32_t target) {
  uint32_t v;
  asm volatile("{\n.reg .pred p;\n.reg .u32 n;\nmov.u32 n, 0;\n"
               "LOOP:\nld.acquire.cta.shared.u32 %0, [%1];\nsetp.ge.u32 p, %0, %2;\n@p bra DONE;\n"
               "nanosleep.u32 %3;\nadd.u32 n, n, 1;\nsetp.lt.u32 p, n, 0x400000;\n@p bra LOOP;\ntrap;\n"
               "DONE:\n}\n" : "=r"(v) : "r"(p), "r"(target), "n"(400) : "memory");
  return v;
}
__device__ __forceinline__ void flag_set(unsigned int* p, uint32_t v) {
  asm volatile("st.release.gpu.global.u32 [%0], %1;" ::"l"(p), "r"(v) : "memory");
}
__device__ __forceinline__ void flag_dec(unsigned int* p) {
  asm volatile("red.relaxed.gpu.global.add.u32 [%0], 0xffffffff;" ::"l"(p) : "memory");
}

struct Cursor {
  uint32_t n;
  __device__ __forceinline__ uint32_t off() const { return n & (8 * NBAR - 8); }
  __device__ __forceinline__ uint32_t ph() const { return (n / (8 * NBAR)) & 1; }
  __device__ __forceinline__ void next() { n += 8; }
};

constexpr float kScaleLog2 = 0.07216878364870322f * 1.4426950408889634f;
constexpr float kSumLimit = 1048576.0f;

__global__ void __cluster_dims__(2, 1, 1) __launch_bounds__(384, 1)
fused_kernel(const __grid_constant__ Params P) {
  extern __shared__ uint8_t smem_raw[];
  const uint32_t sbase = (smem_u32(smem_raw) + 1023) & ~1023u;
  const uint32_t full0 = sbase + RING, empty0 = full0 + 8 * NBAR, odone0 = empty0 + 8 * NBAR, ev0 = odone0 + 8 * MAX_OPS;
  const uint32_t progress = ev0 + 8 * MAX_EV, jobw = progress + 4;
  const uint32_t rank = blockIdx.x & 1;
  const int role = blockIdx.x >> 1;
  const int wid = __shfl_sync(0xffffffffu, (int)(threadIdx.x >> 5), 0);
  const int wg = wid >> 2;

  if (wid < 8) {
    if (elect()) {
#pragma unroll
      for (int j = 0; j < 16; j++) {
        const int i = EARLY + 16 * wid + j;
        if (i < 2 * NBAR + MAX_OPS + MAX_EV) mbar_init(full0 + 8 * i, i < NBAR ? 1 : i < 2 * NBAR ? 16 : i < 2 * NBAR + MAX_OPS ? 8 : 1);
      }
      if (wid == 7) asm volatile("st.shared.v2.u32 [%0], {0, 0};\nfence.acq_rel.cta;" ::"r"(progress) : "memory");
      asm volatile("fence.mbarrier_init.release.cluster;" ::: "memory");
    }
  } else if (wid > 8) {
    const uint32_t g = blockIdx.x * 96 + threadIdx.x - 288, w = g - 2048;
    if (g < 4096) asm volatile("prefetch.global.L2 [%0];" ::"l"(g < 2048 ? P.xw[0] + g * (kD * 2) : P.xw[1] + (w >> 5) * (kHD * 2) + (w & 31) * 128));
  } else {
    const uint32_t op0 = P.first[role];
    if (elect()) {
#pragma unroll
      for (int k = 0; k < EARLY; k++) mbar_init(full0 + 8 * k, 1);
      asm volatile("fence.mbarrier_init.release.cluster;" ::: "memory");
      const int blk = (op0 >> 10) & 1;
      if ((op0 & 3) == OP_Q) {
#pragma unroll
        for (int k = 0; k < EARLY; k++) {
          mbar_expect(full0 + 8 * k, SZ_Q);
          tma2d(sbase + k * SZ_Q, &P.x[blk], full0 + 8 * k, 64 * k, ((op0 >> 7) & 7) * kSq + rank * 128);
          tma3d(sbase + k * SZ_Q + 16384, &P.wq[blk], full0 + 8 * k, 0, 64 * k, 3 * ((op0 >> 2) & 31));
          tma3d(sbase + k * SZ_Q + 28672, &P.wq[blk], full0 + 8 * k, 0, 64 * k + 32, 3 * ((op0 >> 2) & 31));
        }
      }
      asm volatile("prefetch.tensormap [%0];\nprefetch.tensormap [%1];" ::"l"(&P.k[blk]), "l"(&P.v[blk]) : "memory");
    }
  }
  __syncwarp();
  asm volatile("barrier.cluster.arrive.relaxed.aligned;\nbarrier.cluster.wait.aligned;" ::: "memory");

  if (wg < 2) {
    asm volatile("setmaxnreg.inc.sync.aligned.u32 240;");
    const uint32_t* prog = P.prog[role].c;
    const int wid = __shfl_sync(0xffffffffu, (int)(threadIdx.x >> 5), 1), wg = wid >> 2;
    const int lane = threadIdx.x & 31, warp = wid & 3;
    uint32_t empty_rem;
    asm volatile("mapa.shared::cluster.u32 %0, %1, %2;" : "=r"(empty_rem) : "r"(empty0), "r"(lane & 1));
    uint32_t keep = (threadIdx.x & 127) < 2 ? 4 : 0;
    auto release = [&](int slot) { mbar_arrive_cluster_n(keep, empty_rem + slot); };
    auto release_warp = [&](int slot, bool on = true) { mbar_arrive_cluster_if(lane < 2 && on, empty_rem + slot); };
    Cursor r{0};
    const uint32_t ring16 = (sbase & 0x3FFFF) >> 4;
    uint32_t cur = ring16;
    bool rdy0 = false, rdy1 = false;
    auto probe1 = [&]() { rdy0 = mbar_test(full0 + r.off(), r.ph()); };
    auto probe2 = [&]() {
      Cursor n = r;
      rdy0 = mbar_test(full0 + n.off(), n.ph());
      n.next();
      rdy1 = mbar_test(full0 + n.off(), n.ph());
    };
    auto advance = [&](uint32_t bytes, uint32_t& addr) {
      const int bi = r.off();
      r.next();
      if (cur > ring16 + ((RING - bytes) >> 4)) cur = ring16;
      addr = cur;
      cur += bytes >> 4;
      return bi;
    };
    auto take = [&](bool rdy, uint32_t bytes, uint32_t& addr) {
      if (__builtin_expect(!__all_sync(0xffffffffu, rdy), 0)) mbar_wait(full0 + r.off(), r.ph());
      return advance(bytes, addr);
    };
    const bool never = P.dbg == 0xffffffffu;
    uint32_t q[48];
#pragma unroll
    for (int i = 0; i < 48; i++) q[i] = 0;
    const int row = wg * 64 + warp * 16 + (lane >> 2);
    const int img0 = row * 4 + ((lane & 3) ^ ((row >> 1) & 3));
    uint4* pend = nullptr;
    bool pend_any = false;
    const uint64_t spol = evict_first();
    int pc = 0;
    auto slab = [&](int c, int i0) {
#pragma unroll
      for (int i = i0; i < 6; i++)
        stg2_if(c == i, pend + i * 512, q[8 * i], q[8 * i + 1], q[8 * i + 2], q[8 * i + 3],
                q[8 * i + 4], q[8 * i + 5], q[8 * i + 6], q[8 * i + 7], spol);
    };
    auto drain = [&](int c) {
      if (!pend_any || c >= 6) return;
      slab(c, 0);
      if (c == 5) {
        __syncwarp();
        mbar_arrive_if(lane == 0, odone0 - 8 + 8 * pc);
      }
    };

    for (;; pc++) {
      uint32_t op = prog[pc];
      const int type = op & 3;
      auto enter = [&]() {
        r.n = (op >> 12) & 248; cur = ring16 + (((op >> 20) & 63) << 8);
      };
      enter();
      pend_any = op & C_PEND;
      uint32_t job = 0;
      if ((op & (3 | C_WIDE)) == OP_O) job = __shfl_sync(0xffffffffu, wait_word(jobw, 1), 0);
      if (type == OP_END || job == OP_O) {
#pragma unroll 1
        for (int c = 0; c < 6; c++) drain(c);
        asm volatile("barrier.cluster.arrive.relaxed;" ::: "memory");
        break;
      }
      {
        float s[32], o[96];
        uint32_t ad0;
        int bi0, sk1;
        uint32_t pa[16], pb[16];
        float mc0, mc1, l0, l1;
        bool shifted;
        uint32_t nop;
        auto expo = [&](float (&s)[32], uint32_t (&pout)[16], float& b0, float& b1, bool shift, auto mid) {
          float c0, c1;
#pragma unroll
          for (int i = 0; i < 8; i++) {
            const float e0 = ex2(shift ? s[4 * i] - mc0 : s[4 * i]), e1 = ex2(shift ? s[4 * i + 1] - mc0 : s[4 * i + 1]);
            const float e2 = ex2(shift ? s[4 * i + 2] - mc1 : s[4 * i + 2]), e3 = ex2(shift ? s[4 * i + 3] - mc1 : s[4 * i + 3]);
            if (i) { b0 += e0; c0 += e1; b1 += e2; c1 += e3; } else { b0 = e0; c0 = e1; b1 = e2; c1 = e3; }
            pout[2 * i] = pack_bf16(e0, e1); pout[2 * i + 1] = pack_bf16(e2, e3);
            if (i & 1) mid(i >> 1);
          }
          b0 += c0; b1 += c1;
        };
        auto rowmax = [&](float (&s)[32], float& m0, float& m1) {
          m0 = fmaxf(s[0], s[1]); m1 = fmaxf(s[2], s[3]);
#pragma unroll
          for (int i = 1; i < 8; i++) { m0 = fmaxf(m0, fmaxf(s[4 * i], s[4 * i + 1])); m1 = fmaxf(m1, fmaxf(s[4 * i + 2], s[4 * i + 3])); }
          m0 = fmaxf(m0, __shfl_xor_sync(0xffffffffu, m0, 1)); m1 = fmaxf(m1, __shfl_xor_sync(0xffffffffu, m1, 1));
          m0 = fmaxf(m0, __shfl_xor_sync(0xffffffffu, m0, 2)); m1 = fmaxf(m1, __shfl_xor_sync(0xffffffffu, m1, 2));
        };
        auto first = [&](float (&s)[32], int sk0, auto mid) {
          fence_regs(s);
          release(sk0);
          mc0 = 0.f; mc1 = 0.f;
          expo(s, pa, l0, l1, false, mid);
          shifted = __any_sync(0xffffffffu, !(fmaxf(l0, l1) <= kSumLimit && fminf(l0, l1) >= 1.f / kSumLimit));
          if (shifted) {
            rowmax(s, mc0, mc1);
            expo(s, pa, l0, l1, true, [](int) {});
          }
        };
        auto qk = [&](float (&s)[32], uint32_t ak, int k0 = 0, int k1 = 12) {
#pragma unroll
          for (int kk = k0; kk < k1; kk++)
            wgmma_rs_n64<0>(s, q[4 * kk], q[4 * kk + 1], q[4 * kk + 2], q[4 * kk + 3], mk_desc(ak, 16, KV_SBO, 1) + ((kk >> 2) * KV_CH + (kk & 3) * 2), kk != 0);
          if (k1 == 12) wg_commit();
        };
        auto pv = [&](uint32_t (&pin)[16], uint32_t av, int acc) {
#pragma unroll
          for (int kk = 0; kk < 4; kk++)
            wgmma_rs_n192<1>(o, pin[4 * kk], pin[4 * kk + 1], pin[4 * kk + 2], pin[4 * kk + 3], mk_desc(av, KV_CH * 16, KV_SBO, 1) + (kk * (KV_SBO / 8)), acc || (kk != 0));
          wg_commit();
        };
        auto finish = [&](uint32_t (&pout)[16], int sk, int sv) {
          probe1();
          wg_wait<1>();
          fence_regs(s);
          release(sk);
          float b0, b1;
#pragma unroll 1
          for (bool redo = false;; redo = true) {
            expo(s, pout, b0, b1, false, [](int) {});
            if (!__any_sync(0xffffffffu, !redo && (shifted || !(fmaxf(b0, b1) <= kSumLimit)))) break;
            shifted = true;
            rowmax(s, b0, b1);
            b0 = fmaxf(mc0, b0); b1 = fmaxf(mc1, b1);
            const float a0 = ex2(mc0 - b0), a1 = ex2(mc1 - b1);
            mc0 = b0; mc1 = b1;
            l0 *= a0; l1 *= a1;
            wg_wait<0>();
            fence_regs(o);
#pragma unroll
            for (int i = 0; i < 24; i++) { o[4 * i] *= a0; o[4 * i + 1] *= a0; o[4 * i + 2] *= a1; o[4 * i + 3] *= a1; }
#pragma unroll
            for (int i = 0; i < 32; i++) s[i] -= (i & 2) ? mc1 : mc0;
          }
          l0 += b0; l1 += b1;
          wg_wait<0>();
          fence_regs(o);
          release(sv);
        };
        auto step = [&](uint32_t (&pin)[16], uint32_t (&pout)[16]) {
          uint32_t ak, av;
          const int sk = take(rdy0, SZ_KV, ak), sv = advance(SZ_KV, av);
          wg_fence();
          qk(s, ak);
          pv(pin, av, 1);
          finish(pout, sk, sv);
        };
        auto unpark = [&]() {
          uint32_t ad, ak;
          const int bi = take(rdy0, SZ_PARK, ad);
#pragma unroll
          for (int i = 0; i < 12; i++) lds128(sbase + (ad - ring16 + img0) * 16 + (i >> 1) * 8192 + (i & 1) * 512, q[4 * i], q[4 * i + 1], q[4 * i + 2], q[4 * i + 3]);
          const int sk0 = take(false, SZ_KV, ak);
          fence_regs(q);
          release_warp(bi);
          wg_fence();
          qk(s, ak);
          probe2();
          return sk0;
        };
        auto mma4 = [&](uint32_t ad, int acc) {
#pragma unroll
          for (int kk = 0; kk < 4; kk++)
            wgmma_ss_n192<1>(o, mk_desc(ad + wg * 512, 16, 1024, 1) + (kk * 2), mk_desc(ad, 4096, 1024, 1) + (1024 + (kk >> 1) * 768 + (kk & 1) * 128), acc || kk != 0);
        };
        auto convert = [&](int i0, int i1) {
          sched_fence(keep, never);
#pragma unroll
          for (int i = i0; i < i1; i++) {
            q[i] = pack_bf16(o[2 * i] * kScaleLog2, o[2 * i + 1] * kScaleLog2);
            if ((i & 7) == 7 && i != i1 - 1) sched_fence(keep, never);
          }
          sched_fence(keep, never);
        };
        auto kend = [&](int bi, int k) {
          wg_commit();
          drain((0x54732710u >> (4 * k)) & 7);
          probe1();
          wg_wait<0>();
          release(bi);
        };
        if (type == OP_O) {
          int prev = 0;
          if (op & C_WIDE) {
            float d[64];
            auto mma3 = [&](uint32_t ad, int h, int acc) {
#pragma unroll
              for (int kk = 0; kk < 2; kk++)
                wgmma_ss_n192<1>(o, mk_desc(ad + wg * 256, 16, 512, 2) + (h * 512 + kk * 2), mk_desc(ad, 4096, 1024, 1) + (1024 + h * 768 + kk * 128), acc || kk);
            };
            auto mma2 = [&](uint32_t ad, uint32_t ob, int h, int acc) {
#pragma unroll
              for (int kk = 0; kk < 2; kk++)
                wgmma_ss_n128<1>(d, mk_desc(ad + wg * 256, 16, 512, 2) + (h * 512 + kk * 2), mk_desc(ad, 4096, 1024, 1) + (ob + h * 512 + kk * 128), acc || kk);
            };
            auto wstep = [&](uint32_t bytes, int acc, auto hook) {
              uint32_t ad;
              const int bi = take(rdy0, bytes, ad);
              wg_fence();
              if (bytes == SZ_W2) mma2(ad, 1024, 0, 1); else mma3(ad, 0, acc);
              if (bytes == SZ_W) mma3(ad, 1, 1);
              wg_commit();
              if (acc) { wg_wait<1>(); release(prev); }
              if (bytes == SZ_W) mma2(ad, 2560, 0, acc);
              if (bytes == SZ_W3) mma3(ad, 1, 1); else mma2(ad, bytes == SZ_W ? 2560 : 1024, 1, 1);
              wg_commit();
              prev = bi;
              hook();
              probe1();
              wg_wait<1>();
            };
            undefine(o);
            wstep(SZ_W, 0, [&]() { drain(0); });
#pragma unroll 1
            for (int k = 1; k < ((op >> 2) & 127) - TAIL; k++) wstep(SZ_W, 1, [&]() { drain(k); });
#pragma unroll 1
            for (int k = 0; k < TAIL; k++) wstep(SZ_W2, 1, []() {});
            pend = ptr_add(P.g->part, (((op >> 9) & 31) * 2 + rank) * 81920 + 4 * 8192 + img0 * 16);
            wstep(SZ_W3, 1, [&]() {
              fence_regs(d);
#pragma unroll
              for (int i = 0; i < 32; i++) q[16 + i] = pack_bf16(d[2 * i], d[2 * i + 1]);
              slab(2, 2);
            });
#pragma unroll 1
            for (int k = 3; k < 6; k++) wstep(SZ_W3, 1, [&]() { slab(k, 2); });
            op = prog[pc + 1];
            enter();
            pend_any = true;
            pend -= 4 * 512;
            bi0 = take(rdy0 || (op & 3) != OP_Q, SZ_Q, ad0);
            sched_fence(keep, never);
            wg_wait<0>();
            fence_regs(o);
            release(prev);
#pragma unroll
            for (int i = 0; i < 48; i++) q[i] = pack_bf16(o[2 * i], o[2 * i + 1]);
            if ((op & 3) != OP_Q) continue;
            pc++;
            goto first_step;
          }
          float c[80];
          auto mma2 = [&](uint32_t ad, uint32_t oa, uint32_t ob, int acc) {
            wgmma_ss_n160<1>(c, mk_desc(ad + wg * 256, 16, 512, 2) + (oa), mk_desc(ad, 2048, 512, 2) + (1024 + ob), acc);
            wgmma_ss_n160<1>(c, mk_desc(ad + wg * 256, 16, 512, 2) + (oa + 2), mk_desc(ad, 2048, 512, 2) + (1024 + ob + 64), 1);
          };
          auto kstep = [&](int acc, auto hook, uint32_t bytes = SZ_O) {
            uint32_t ad;
            const int bi = take(rdy0, bytes, ad);
            wg_fence();
            mma2(ad, 0, 0, acc);
            wg_commit();
            if (acc) wg_wait<1>();
            if (acc == 1) release(prev);
            if (acc > 1) release_warp(prev, acc == 2 || wg == 0);
            mma2(ad, 512, 640, 1);
            wg_commit();
            prev = bi;
            hook();
            probe1();
            wg_wait<1>();
          };
          auto unblock = [&](int k) {
            if (__all_sync(0xffffffffu, rdy0) || __all_sync(0xffffffffu, mbar_try(full0 + r.off(), r.ph(), 1500))) return;
#pragma unroll 1
            for (; k < 6; k++) drain(k);
            pend_any = false;
          };
          unblock(0);
          kstep(0, [&]() { drain(0); });
          int left = ((job >> 13) & 127) - 6;
#pragma unroll 1
          for (uint32_t k = 1, pace = left >= 22 ? 0x4511 : left <= 11 ? 0x1a : 0x155; left > 0; pace >>= 2, left--) {
            unblock(k);
            kstep(1, [&]() {
#pragma unroll 1
              for (int i = pace & 3; i > 0; i--) drain(k++);
            });
          }
          uint32_t t[8], stage[3];
          float u[80];
          auto unpack = [&](int j) {
#pragma unroll
            for (int i = 0; i < 8; i++) {
              u[16 * j + 2 * i] = __uint_as_float(t[i] << 16); u[16 * j + 2 * i + 1] = __uint_as_float(t[i] & 0xffff0000u);
              asm volatile("" : "+f"(u[16 * j + 2 * i]), "+f"(u[16 * j + 2 * i + 1]));
            }
          };
#pragma unroll
          for (int i = 0; i < 8; i++) t[i] = 0;
          const uint32_t bytes = (job & P_LD) ? SZ_OL : SZ_O;
#pragma unroll
          for (int j = 0; j < 5; j++) {
            if (j == 2 && wg == 1) {
              wg_wait<0>();
              release_warp(prev);
              bar_sync(1, 256);
            }
            kstep(j == 2 ? 3 : 2, [&]() {
              if (j == 4) asm volatile("{\n.reg .pred p;\nsetp.eq.u32 p, %0, 0;\n@p bar.arrive 1, 256;\n}\n" ::"r"(wg) : "memory");
              if (j) unpack(j - 1);
              lds2_if(job & P_LD, sbase + (cur - ring16 + img0) * 16 - 8192, t);
              if (j >= 1 && j <= 3) stage[j - 1] = sbase + (cur - ring16) * 16 - bytes + wid * 1024;
            }, bytes);
          }
          unpack(4);
          sched_fence(keep, never);
          wg_wait<0>();
          fence_regs(c);
          release_warp(prev);
          asm volatile("barrier.cluster.arrive.relaxed;" ::: "memory");
#pragma unroll
          for (int i = 0; i < 10; i++) {
            const int v = (i & 1) * 2 + (lane >> 4);
            const uint32_t sa = stage[i >> 2] + (i & 2) * 4096;
            stsm4(sa + (lane & 15) * 64 + ((v ^ ((lane >> 1) & 3)) << 4), pack_bf16(c[8 * i] + u[8 * i], c[8 * i + 1] + u[8 * i + 1]),
                  pack_bf16(c[8 * i + 2] + u[8 * i + 2], c[8 * i + 3] + u[8 * i + 3]), pack_bf16(c[8 * i + 4] + u[8 * i + 4], c[8 * i + 5] + u[8 * i + 5]),
                  pack_bf16(c[8 * i + 6] + u[8 * i + 6], c[8 * i + 7] + u[8 * i + 7]));
          }
          asm volatile("fence.proxy.async.shared::cta;" ::: "memory");
          __syncwarp();
          if (elect()) {
#pragma unroll
            for (int i = 0; i < 5; i++)
              tma3d_store(&P.out, stage[i >> 1] + (i & 1) * 8192, 0, ((job >> 7) & 7) * kSq + rank * 128 + wid * 16, ((job >> 10) & 1) * 20 + ((job >> 20) & 3) * 5 + i);
            asm volatile("cp.async.bulk.commit_group;\ncp.async.bulk.wait_group.read 0;" ::: "memory");
          }
          __syncwarp();
          break;
        }
        bi0 = take(rdy0, SZ_Q, ad0);
      first_step:
        undefine(o);
        wg_fence();
        mma4(ad0, 0);
        kend(bi0, 0);
        fence_regs(o);
      next_head:
        {
#pragma unroll 1
          for (int k = 1; k < 8; k++) {
            uint32_t ad;
            const int bi = take(rdy0, SZ_Q, ad);
            wg_fence();
            mma4(ad, 1);
            kend(bi, k);
          }
          uint32_t a8, a9, ak0, ak1;
          const int b8 = take(rdy0, SZ_Q, a8), b9 = take(false, SZ_Q, a9);
          wg_fence();
          mma4(a8, 1);
          wg_commit();
          mma4(a9, 1);
          wg_commit();
          wg_wait<1>();
          release(b8);
          probe1();
          const int sk0 = take(rdy0 || (op & F_PARK), SZ_KV, ak0);
          wg_wait<0>();
          fence_regs(o);
          release(b9);
          float s0[32];
          convert(0, 32);
          if (op & F_PARK) {
            convert(32, 48);
            pend = ptr_add(P.g->tile, (((op >> 2) & 511) * 2 + rank) * SZ_PARK + img0 * 16);
            continue;
          }
          pc++;
          wg_fence();
          qk(s0, ak0, 0, 4);
          convert(32, 48);
          wg_fence();
          qk(s0, ak0, 4, 12);
          sk1 = take(false, SZ_KV, ak1);
          wg_fence();
          qk(s, ak1, 0, 4);
          wg_commit();
          probe1();
          wg_wait<1>();
          first(s0, sk0, [&](int i) {
            if (!(i & 1)) return;
            sched_fence(keep, never);
            wg_fence();
            if (i == 1) qk(s, ak1, 4, 8);
            if (i == 3) qk(s, ak1, 8, 12);
            sched_fence(keep, never);
          });
        }
        for (;;) {
          {
            uint32_t av;
            const int sv = take(rdy0, SZ_KV, av);
            undefine(o);
            wg_fence();
            pv(pa, av, 0);
            finish(pb, sk1, sv);
          }
          nop = prog[pc + 1];
#pragma unroll 1
          for (int jj = 0; jj < 7; jj++) {
            step(pb, pa);
            step(pa, pb);
          }
          float i0, i1;
          auto last = [&]() {
            uint32_t av;
            const int sv = take(rdy0, SZ_KV, av);
            wg_fence();
            pv(pb, av, 1);
            sched_fence(keep, never);
            probe1();
            l0 += __shfl_xor_sync(0xffffffffu, l0, 1); l1 += __shfl_xor_sync(0xffffffffu, l1, 1);
            l0 += __shfl_xor_sync(0xffffffffu, l0, 2); l1 += __shfl_xor_sync(0xffffffffu, l1, 2);
            i0 = rcp(l0); i1 = rcp(l1);
            pend = ptr_add(P.g->tile, (((op >> 2) & 511) * 2 + rank) * SZ_PARK + img0 * 16);
            return sv;
          };
          auto normalise = [&](uint32_t (&d)[48], auto mid) {
#pragma unroll
            for (int i = 0; i < 24; i++) {
              d[8 * (i >> 2) + (i & 3)] = pack_bf16(o[4 * i] * i0, o[4 * i + 1] * i0);
              d[8 * (i >> 2) + (i & 3) + 4] = pack_bf16(o[4 * i + 2] * i1, o[4 * i + 3] * i1);
              if ((i & 1) && i != 23) sched_fence(keep, never);
              if ((i & 3) == 3 && i != 23) mid(i >> 2);
            }
          };
          const int sv = last();
          if ((nop & 3) != OP_A) {
            op = nop;
            enter();
            pend_any = true;
            bi0 = take(rdy0 || (nop & 3) != OP_Q, SZ_Q, ad0);
            sched_fence(keep, never);
            wg_wait<0>();
            fence_regs(o);
            release(sv);
            normalise(q, [](int) {});
            undefine(o);
            if ((nop & 3) != OP_Q) break;
            sched_fence(keep, never);
            wg_fence();
            mma4(ad0, 0);
            pc++;
            kend(bi0, 0);
            fence_regs(o);
            goto next_head;
          }
          const int sk0 = unpark();
          wg_wait<1>();
          fence_regs(o);
          release(sv);
          uint32_t t[48];
          auto st = [&](int i) {
            stg2_if(true, pend + i * 512, t[8 * i], t[8 * i + 1], t[8 * i + 2], t[8 * i + 3], t[8 * i + 4], t[8 * i + 5], t[8 * i + 6], t[8 * i + 7], spol);
          };
          normalise(t, [&](int i) { if (!(i & 1)) st(i >> 1); });
          wg_wait<0>();
          first(s, sk0, [&](int i) { if (i < 3) { sched_fence(keep, never); st(3 + i); } });
          __syncwarp();
          mbar_arrive_if(lane == 0, odone0 + 8 * pc);
          pc++;
          op = nop;
          uint32_t ak1;
          sk1 = take(rdy0, SZ_KV, ak1);
          rdy0 = rdy1;
          wg_fence();
          qk(s, ak1);
        }
      }
    }
    asm volatile("barrier.cluster.wait;" ::: "memory");
  } else {
    asm volatile("setmaxnreg.dec.sync.aligned.u32 24;");
    const uint32_t* prog = P.prog[role].p;
    unsigned int* flag = P.g->flag + rank;
    if (wid == 11 && (prog[0] & 3) == OP_Q) {
      const uint32_t a = prog[1];
      const char* p = ptr_add(P.kv[rank * 2 + ((a >> 10) & 1)], ((a >> 2) & 255) * (kSk * kDh * 2) + (threadIdx.x & 31) * 128);
#pragma unroll 1
      for (uint32_t k = 0; k < 3; k++) {
        wait_word(progress, 8 * k);
        p += SZ_KV;
        asm volatile("prefetch.global.L2 [%0];\nprefetch.global.L2 [%0 + 4096];" ::"l"(p));
      }
      __syncwarp();
    }
    if (wid == 8) {
      Cursor head{0}, tail{0};
      int sh = 0, room = RING >> 12;
      uint32_t cur = 0;
      uint64_t fifo = 0;
      uint32_t dst, bar = 0, ev = ev0;
      const uint64_t pol = evict_first();
      auto retire = [&]() {
        mbar_wait(empty0 + tail.off(), tail.ph());
        tail.next();
        room += (uint32_t)fifo & 31;
        fifo >>= 5;
        sh -= 5;
        asm volatile("st.volatile.shared.u32 [%0], %1;" ::"r"(progress), "r"(tail.n) : "memory");
      };
      auto acquire = [&](uint32_t bytes) {
        uint32_t fp = bytes >> 12;
        if (cur + fp > (RING >> 12)) { fp += (RING >> 12) - cur; cur = 0; }
        room -= fp;
        while (room < 0) retire();
        fifo |= (uint64_t)fp << sh;
        sh += 5;
        dst = sbase + (cur << 12);
        bar = full0 + head.off();
        cur += bytes >> 12;
        head.next();
      };
      auto gate = [&]() {
        mbar_wait(ev, 0);
        ev += 8;
        asm volatile("fence.proxy.async.global;" ::: "memory");
      };
      for (int pc = 0;; pc++) {
        uint32_t op = prog[pc];
        const int type = op & 3;
        if (type == OP_END) break;
        if (op == OP_O) {
          gate();
          op = __shfl_sync(0xffffffffu, lds32(jobw), 0);
        }
        const int blk = (op >> 10) & 1;
        if (type == OP_Q) {
          const uint64_t px = (op & P_LASTX) ? pol : no_hint(), pw = (op & P_LASTW) ? pol : no_hint();
          int k = 0;
          if (pc == 0) {
            k = 64 * EARLY; head.n = 8 * EARLY; sh = 5 * EARLY; cur = EARLY * (SZ_Q >> 12); room -= cur;
            fifo = (SZ_Q >> 12) * (((1u << (5 * EARLY)) - 1) / 31);
          }
#pragma unroll 1
          for (int stop = (op & P_GATE) ? kD - 64 : kD;; stop = kD) {
#pragma unroll 1
            for (; k < stop; k += 64) {
              acquire(SZ_Q);
              if (elect()) {
                mbar_expect(bar, SZ_Q);
                tma3d_mc_hint(dst + 16384 + rank * 12288, &P.wq[blk], bar, k + 32 * rank, 3 * ((op >> 2) & 31), pw);
                tma2d_hint(dst, &P.x[blk], bar, k, ((op >> 7) & 7) * kSq + rank * 128, px);
              }
            }
            if (k == kD) break;
            gate();
          }
        } else if (type == OP_A) {
          const int row0 = ((op >> 2) & 255) * kSk;
          if (op & F_PARK) {
            gate();
            acquire(SZ_PARK);
            if (elect()) {
              mbar_expect(bar, SZ_PARK);
              bulk_load_hint(dst, &P.g->tile[(((op >> 20) & 511) * 2 + rank) * 3072], SZ_PARK, bar, pol);
            }
          }
          auto kv = [&](uint32_t tx, const CUtensorMap* m, int c3) {
            const uint32_t before = bar;
            acquire(SZ_KV);
            if (elect()) {
              mbar_expect(bar, tx);
              tma4d_mc_hint(dst + rank * (SZ_KV / 2), m, tx ? bar : before, c3, pol);
            }
          };
          int c3 = row0 / 8 + 4 * rank;
#pragma unroll 1
          for (int j = 0; j <= 16; j++, c3 += 8) {
            const uint32_t tv = j < 2 || j == 16 ? SZ_KV : 0;
            if (j < 16) kv(2 * SZ_KV - tv, &P.k[blk], c3);
            else if (op & P_GATE) gate();
            if (j > 0) kv(tv, &P.v[blk], c3 - 8);
          }
        } else {
          const uint4* part = &P.g->part[((((op >> 6) & 30) + ((op >> 21) & 1)) * 2 + rank) * 5120 + ((op >> 20) & 1) * 2560];
          auto run = [&](const uint32_t bytes, int k, int cnt, int gates) {
            const int col = bytes == SZ_O || bytes == SZ_OL ? 5 * ((op >> 20) & 3) : 5 * ((op >> 21) & 1);
            int row = 8 * k + 4 * rank, pre = bytes == SZ_O && (op & P_PRE) ? 0 : 2560;
#pragma unroll 1
            for (int h = (k * 43) >> 7, k0 = k - 3 * h; cnt > 0; h++, k0 = 0, gates = gates >> 1 | (gates & 2)) {
              const uint4* src = ptr_add(P.g->tile, ((P.slot[((op >> 2) & 480) + h] * 2 + rank) * 3 + k0) * 16384);
              const uint64_t pw = h >= ((op >> 23) & 31) && h < 2 * (op >> 28) ? pol : no_hint();
              if (gates & 1) gate();
              int m = min(3 - k0, cnt);
              cnt -= m;
#pragma unroll 1
              for (; m > 0; m--, src += 1024, row += 8) {
                acquire(bytes);
                if (elect()) {
                  mbar_expect(bar, bytes);
                  if (bytes == SZ_O || bytes == SZ_OL) tma5d_mc_hint(dst + 16384 + rank * 10240, &P.wo[blk], bar, row, col, no_hint());
                  if (bytes == SZ_W || bytes == SZ_W3) tma5d_mc_hint(dst + 16384 + rank * 12288, &P.wo3[blk], bar, row, col, pw);
                  bulk_load_hint(dst, src, 16384, bar, pol);
                  if (bytes == SZ_W || bytes == SZ_W2) tma5d_mc_hint(dst + bytes - 16384 + rank * 8192, &P.wo2[blk], bar, row, col + 3, pw);
                  if (bytes == SZ_OL) bulk_load_hint(dst + SZ_O, part, 8192, bar, pol);
                }
                if (bytes == SZ_OL) part += 512;
              }
              if (pre < 2560) {
                if (elect()) asm volatile("cp.async.bulk.prefetch.L2.global [%0], 10240;" ::"l"(part + pre) : "memory");
                pre += 640;
              }
            }
          };
          const int n = (op >> 13) & 127;
          if (op & P_WIDE) {
            run(SZ_W, 0, n - TAIL, 3);
            run(SZ_W2, n - TAIL, TAIL, (n - TAIL) % 3 ? 2 : 3);
            run(SZ_W3, n - TAIL, TAIL, 0);
          } else {
            if (op & P_PRE) gate();
            run(SZ_O, kSteps - n, (op & P_LD) ? n - 5 : n, 3);
            if (op & P_LD) {
              if (!(op & P_PRE)) gate();
              run(SZ_OL, kSteps - 5, 5, 2);
            }
          }
        }
      }
#pragma unroll 1
      while (sh) retire();
    } else if (threadIdx.x == 288) {
      for (int pc = 0;; pc++) {
        const uint32_t op = prog[pc];
        const int type = op & 3;
        if (type == OP_END) break;
        if (type == OP_Q ? !(op & F_PARK) : type == OP_O && !(op & P_WIDE)) continue;
        const int id = type == OP_A ? (op >> 2) & 511 : type == OP_Q ? N_TILE + ((op >> 13) & 127) : ID_PART + ((op >> 5) & 60) + ((op >> 20) & 3);
        const uint32_t v = type == OP_O ? 1 : P.info[id] & 7;
        mbar_wait_long(odone0 + 8 * pc);
        flag_set(flag + 2 * id, v);
        if (type == OP_O && (op & P_WIDE)) flag_set(flag + 2 * id + 2, v);
      }
    } else if (wid == 10) {
      int i = threadIdx.x & 31;
      const int n_ev = P.prog[role].n_ev;
      auto event = [&]() { return i < n_ev ? P.prog[role].ev[i] : n_ev ? E_JOB | (i - n_ev) : 0; };
      uint32_t e = i < 8 ? event() : 0;
      for (uint32_t n = 0; __any_sync(0xffffffffu, e); n++) {
        uint32_t job = lds32(jobw);
        const int togo = (e & E_DRAW) ? (e & 1023) - (lds32(progress) >> 3) : 99;
        if (togo <= 0 && rank == 0) {
          job = P.job[atomicInc(&P.g->ticket, gridDim.x / 2 - 1)];
          asm volatile("{\n.reg .u32 a;\nmapa.shared::cluster.u32 a, %0, 1;\nst.volatile.shared::cluster.u32 [a], %1;\n"
                       "st.volatile.shared.u32 [%0], %1;\n}\n" ::"r"(jobw), "r"(job) : "memory");
        }
        if ((e & E_JOB) && job) {
          const uint32_t j = e & 63, heads = job == OP_O ? 0 : kH - ((job >> 2) & 31), jp = !(job & P_LD) ? 63 : (job & P_PRE) ? 0 : heads - 1, h = j - (j > jp);
          e = j == jp ? (ID_PART + ((job >> 5) & 60) + ((job >> 20) & 3)) | E_ON | E_LAST : h < heads ? (((job >> 2) & 511) + h) | E_ON | E_LAST : 0;
        }
        unsigned int* f = ptr_add(flag, 8 * (e & 1023));
        const bool ok = (e & E_ON) ? flag_get(f) - 1 < ((e & E_FREE) ? 1 : 7) : (e & E_DRAW) && job;
        if (ok) {
          mbar_arrive(ev0 + 8 * i);
          if (e & (E_FREE | E_LAST)) flag_dec(f);
          i += 8;
          e = event();
        }
        asm volatile("{\n.reg .pred p;\nsetp.ge.u32 p, %0, 0x400000;\n@p trap;\n}\n" ::"r"(n));
        if (!__any_sync(0xffffffffu, ok)) __nanosleep(__any_sync(0xffffffffu, job || togo <= 2) ? 100 : 600);
      }
    } else if (threadIdx.x == 352) {
      uint32_t items = 0;
      auto read = [&](int id) {
        if (!(P.info[id] & I_NEXT)) return;
        wait_word(progress, 8 * items);
        flag_dec(flag + 2 * id);
      };
      for (int pc = 0;; pc++) {
        const uint32_t op = prog[pc];
        const int type = op & 3;
        if (type == OP_END) break;
        if (type == OP_O) {
          const uint32_t n = (op >> 13) & 127, base = items;
#pragma unroll 1
          for (uint32_t k = 3, id = (op >> 2) & 511; k <= n; k += 3, id++) {
            items = base + k + (k + TAIL > n ? TAIL : 0);
            read(id);
          }
          items = base + n + TAIL;
        } else if (type == OP_A) {
          if (op & F_PARK) { items++; read(N_TILE + ((op >> 13) & 127)); }
          items += 32;
        } else {
          items += 10;
        }
      }
    }
    __syncwarp();
    asm volatile("barrier.cluster.arrive.relaxed;\nbarrier.cluster.wait;" ::: "memory");
  }
}

typedef CUresult (*EncodeFn)(CUtensorMap*, CUtensorMapDataType, cuuint32_t, void*, const cuuint64_t*, const cuuint64_t*,
                             const cuuint32_t*, const cuuint32_t*, CUtensorMapInterleave, CUtensorMapSwizzle,
                             CUtensorMapL2promotion, CUtensorMapFloatOOBfill);

void encode(EncodeFn fn, CUtensorMap* m, const void* ptr, int rank, const cuuint64_t* dims, const cuuint64_t* strides,
            const cuuint32_t* box, CUtensorMapSwizzle swz) {
  const cuuint32_t es[5] = {1, 1, 1, 1, 1};
  CUresult r = fn(m, CU_TENSOR_MAP_DATA_TYPE_BFLOAT16, rank, const_cast<void*>(ptr), dims, strides, box, es,
                  CU_TENSOR_MAP_INTERLEAVE_NONE, swz, CU_TENSOR_MAP_L2_PROMOTION_L2_128B, CU_TENSOR_MAP_FLOAT_OOB_FILL_NONE);
  if (r != CUDA_SUCCESS) fprintf(stderr, "cuTensorMapEncodeTiled failed: %d\n", (int)r);
}

struct Op { int type, flags, id, n, quarter, park, item0, items; double t0, t1; };
struct Use { double ready, gate, need, freed; int readers, slot, prev; bool next; };
struct PlanStats { double end, slack, park_slack; int slots, parks; uint32_t own[N_CL]; };

bool plan(const char* const* text, int n_pair, int phase, Params& P, PlanStats* stats = nullptr) {
  constexpr double T_Q = 7900, T_A = 24800, T_U = 25900, T_P = 8400, T_O = 640, T_RUN = 800, T_WIDE = 1300, AHEAD = 3500, PUBLISH = 1500;
  const double margin = 256.0 * ((P.dbg >> 8) & 255);
  static Op op[N_CL][MAX_OPS];
  static Use use[ID_PART];
  int n_op[N_CL], covered[2 * N_TEAM] = {};
  struct Ref { double t; Op* o; int id; };
  static Ref att[N_TILE + 1], dem[N_TILE], prk[MAX_PARK + 1], unp[MAX_PARK + 1], wr[ID_PART];
  auto sort = [](Ref* r, int n) {
    for (int i = 1; i < n; i++)
      for (int j = i; j > 0 && r[j].t < r[j - 1].t; j--) { Ref x = r[j]; r[j] = r[j - 1]; r[j - 1] = x; }
  };
  auto hex = [](char c) { return c <= '9' ? c - '0' : c - 'a' + 10; };
  for (int i = 0; i < n_pair; i++)
    for (const char* s = text[i]; *s; s++)
      for (int h = 0; *s == 'J' && h < 2; h++) {
        if (covered[2 * hex(s[1]) + h]) return false;
        covered[2 * hex(s[1]) + h] = 10 * (s[2 + 2 * h] - '0') + s[3 + 2 * h] - '0';
      }
  for (int c = 0; c < 2 * n_pair; c++) {
    int n = 0, items = 0;
    double t = 0;
    auto add = [&](int type, int flags, int id, int heads, int quarter, int its, double dt) {
      if (n < MAX_OPS) op[c][n] = {type, flags, id, heads, quarter, 0, items, its, t, t + dt};
      n++; items += its; t += dt;
    };
    for (const char* s = text[c >> 1]; *s; s++) {
      const int tm = hex(s[1]) & 15, nj = covered[2 * tm + (c & 1)];
      if (*s == 'N') { add(OP_Q, 0, 0, 0, 0, 10, T_Q); add(OP_A, 0, 0, 0, 0, 32, T_A); }
      if (*s == 'P') add(OP_Q, F_PARK, 0, 0, 0, 10, T_P);
      if (*s == '+' || *s == '-') t += *s == '+' ? 1000 : -1000;
      if (*s == 'U') { if (n == 0 || n > MAX_OPS || op[c][n - 1].type != OP_A) return false; add(OP_A, F_PARK, 0, 0, 0, 33, T_U); }
      if (*s == 'J') { if (nj < TAIL + 6 || nj > kSteps - 11) return false; add(OP_O, P_WIDE, tm * kH, nj, 2 * (c & 1), nj + TAIL, 2 * T_O * nj + T_WIDE); }
    }
    add(OP_O, 0, 0, 0, 0, 0, 0);
    add(OP_END, 0, 0, 0, 0, 0, 0);
    if (n > MAX_OPS || op[c][0].type != OP_Q) return false;
    n_op[c] = n - 1;
    att[c] = {t, &op[c][n - 2], 0};
  }
  for (int i = 0; i < 4 * N_TEAM; i++) dem[i] = {(double)covered[i / 2], nullptr, i};
  sort(att, 2 * n_pair); sort(dem, 4 * N_TEAM);
  for (int i = 0; i < 4 * N_TEAM; i++) {
    Op* f = att[i].o;
    const int nj = covered[dem[i].id / 2];
    f->flags = nj ? P_LD : 0;
    f->id = dem[i].id / 4 * kH + nj / 3; f->quarter = dem[i].id & 3; f->items = f->n = kSteps - nj;
    f[1].t0 = f[1].t1 = f->t1 = f->t0 + T_O * f->n + T_RUN; f[1].item0 += f->n;
  }
  for (int i = 0; i < ID_PART; i++) use[i] = {0, 0, 1e18, 0, 0, 0, 0, false};
  int n_att = 0, n_prk = 0, n_unp = 0;
  auto ready = [&](const Op* o) {
    const int nt = o[1].type;
    return o->t1 + (nt == OP_Q ? 6100 : o[1].n ? ((o[1].flags & P_WIDE) ? 7700 : 3900) : 1500) + PUBLISH;
  };
  for (int c = 0; c < 2 * n_pair; c++)
    for (Op* o = op[c]; o->type != OP_END; o++) {
      if (o->type == OP_A) { att[n_att] = {ready(o), o, 0}; if (++n_att > N_TILE) return false; }
      if (o->type == OP_A && o->flags) { unp[n_unp] = {o->t0 - AHEAD, o, 0}; if (++n_unp > MAX_PARK) return false; }
      if (o->type == OP_Q && o->flags) { prk[n_prk] = {ready(o), o, 0}; if (++n_prk > MAX_PARK) return false; }
      for (int i = 0; o->type == OP_O && i < o->n; i++) {
        const int nw = (o->flags & P_WIDE) ? o->n - TAIL : 0, k = nw ? i : kSteps - o->n + i;
        Use& u = use[o->id / kH * kH + k / 3];
        const double t = o->t0 + T_O * (i + (i < nw ? i : nw));
        if (t - AHEAD < u.need) u.need = t - AHEAD;
        const double f = !nw ? 1e18 : i + FLIGHT < o->items - TAIL || (nw && o[1].type != OP_O) ? t + T_O * (i < nw ? 2 : 1 + TAIL) + PUBLISH : 1e18;
        if (f > u.freed) u.freed = f;
        if (i == 0 || k % 3 == 0) u.readers++;
      }
    }
  if (n_att != N_TILE || n_prk != n_unp) return false;
  for (int i = 0; i < N_TILE; i++) { const int id = (i & 15) * kH + (i >> 4); dem[i] = {use[id].need, nullptr, id}; }
  sort(att, n_att); sort(dem, N_TILE); sort(prk, n_prk); sort(unp, n_unp);
  PlanStats st = {0, 1e18, 1e18, 0, n_prk};
  int n_wr = 0;
  for (int i = 0; i < N_TILE; i++) {
    Op* o = att[i].o;
    o->id = dem[i].id;
    if (!o->flags) o[-1].id = o->id;
    if (dem[i].t - att[i].t < st.slack) st.slack = dem[i].t - att[i].t;
    wr[n_wr++] = {o->t1 - 2 * AHEAD, o, o->id};
  }
  for (int i = 0; i < n_prk; i++) {
    prk[i].o->id = unp[i].o->id;
    prk[i].o->park = unp[i].o->park = i;
    use[N_TILE + i].freed = unp[i].o->t0 + 2 * PUBLISH;
    use[N_TILE + i].readers = 1;
    if (unp[i].t - prk[i].t < st.park_slack) st.park_slack = unp[i].t - prk[i].t;
    wr[n_wr++] = {prk[i].o->t1 - 2 * AHEAD, prk[i].o, N_TILE + i};
  }
  for (int c = 0; c < 2 * n_pair; c++)
    for (int d = 0; d < 2 * n_pair; d++)
      for (Op *f = &op[c][n_op[c] - 1], *o = op[d]; f->n && o->type != OP_END; o++)
        if (o->type == OP_O && (o->flags & P_WIDE) && o->id / kH == f->id / kH && o->quarter / 2 == f->quarter / 2) {
          if (f->t0 - o->t1 > 4096.0 * ((P.dbg >> 16) & 255)) f->flags |= P_PRE;
          const double slack = f->t0 + ((f->flags & P_PRE) ? 0 : (f->n - 5) * T_O) - AHEAD - ready(o);
          if (slack < st.park_slack) st.park_slack = slack;
        }
  constexpr double long_while = 160000;
  for (int c = 0; c < 2 * n_pair; c++)
    for (Op* o = op[c]; o->type != OP_END; o++) {
      if (o->type == OP_O && (o->flags & P_WIDE)) {
        int run = 0, best = 0, end = 0;
        for (int h = 0; 3 * h < o->n; h++) {
          bool last = true;
          for (int d = 0; d < 2 * n_pair; d++)
            for (const Op* e = op[d]; e->type != OP_END; e++) {
              if (e->type != OP_O || e == o || ((e->id ^ o->id) & 256) || e->quarter / 2 != o->quarter / 2) continue;
              const bool wide = e->flags & P_WIDE;
              if (wide ? 3 * h >= e->n : 3 * h + 3 <= kSteps - e->n) continue;
              const double dt = e->t0 + T_O * (wide ? 6 * h : 3 * h - kSteps + e->n) - o->t0 - T_O * 6 * h + (d - c) * 1e-3;
              if (dt > 0 && dt < long_while) last = false;
            }
          run = last ? run + 1 : 0;
          if (run > best) { best = run; end = h + 1; }
        }
        if (3 * end >= o->n) end++;
        o->park = (end - best) | (end / 2) << 5;
      }
      if (o->type != OP_Q) continue;
      bool lw = true, lx = true;
      for (int d = 0; d < 2 * n_pair; d++)
        for (const Op* e = op[d]; e->type != OP_END; e++) {
          const double dt = e->t0 - o->t0 + (d - c) * 1e-3;
          if (e->type != OP_Q || e == o || dt < 0 || dt > long_while) continue;
          if (((e->id ^ o->id) & (256 + 31)) == 0) lw = false;
          if (e->id / kH == o->id / kH) lx = false;
        }
      o->quarter = (lw ? P_LASTW : 0) | (lx ? P_LASTX : 0);
    }
  sort(wr, n_wr);
  int holder[N_TILE];
  for (int i = 0; i < n_wr; i++) {
    int best = -1;
    for (int sl = 0; sl < st.slots; sl++)
      if (use[holder[sl]].freed + margin <= wr[i].t && (best < 0 || use[holder[sl]].freed < use[holder[best]].freed)) best = sl;
    Use& u = use[wr[i].id];
    if (best >= 0) { u.prev = holder[best]; use[u.prev].next = true; wr[i].o->flags |= P_GATE; }
    else if (st.slots == N_TILE) return false;
    else best = st.slots++;
    u.slot = best;
    holder[best] = wr[i].id;
  }
  {
    int pos[N_CL] = {}, flag[ID_PART + 4 * N_TEAM] = {}, seen[ID_PART] = {};
    auto goal = [&](int c) { return op[c][n_op[c] - 1].item0; };
    for (bool moved = true; moved;) {
      moved = false;
      for (int c = 0; c < 2 * n_pair; c++) {
        for (; pos[c] < goal(c); pos[c]++, moved = true) {
          bool ok = true;
          for (const Op* o = op[c]; o->type != OP_END; o++) {
            const int k = pos[c] - o->item0, own = o->type == OP_A ? o->id : N_TILE + (o->park & 127);
            if (k < 0 || k >= o->items) continue;
            if (o->type == OP_O) ok = k >= o->n || flag[o->id + k / 3];
            else if (k == o->items - 1 && (o->flags & P_GATE)) ok = seen[use[own].prev] == use[use[own].prev].readers;
            else if (k == 0 && o->type == OP_A && (o->flags & F_PARK)) ok = flag[N_TILE + o->park];
          }
          if (!ok) break;
          for (const Op* o = op[c]; o->type != OP_END; o++) {
            if (pos[c] == o->item0 + o->items + (o[1].type == OP_Q ? 7 : o[1].item0 == goal(c) ? -1 : 5)) {
              if (o->type == OP_A) flag[o->id] = 1;
              if (o->type == OP_Q && (o->flags & F_PARK)) flag[N_TILE + o->park] = 1;
              if (o->type == OP_O) flag[ID_PART + o->id / kH * 4 + o->quarter] = flag[ID_PART + o->id / kH * 4 + o->quarter + 1] = 1;
            }
            const int k = pos[c] - FLIGHT - o->item0, nw = o->n - TAIL;
            if (k == 0 && o->type == OP_A && (o->flags & F_PARK)) seen[N_TILE + o->park]++;
            if (o->type == OP_O && k >= 0 && k < o->items && (k < nw || k >= o->n) && (k < nw ? k : k - TAIL) % 3 == 2) seen[o->id + (k < nw ? k : k - TAIL) / 3]++;
          }
        }
      }
    }
    for (int c = 0; c < 2 * n_pair; c++) if (pos[c] < goal(c)) return false;
  }
  int n_job = 0, longest = 0;
  for (int i = 0; i < 2 * N_TEAM; i++) if (kH + 1 - covered[i] / 3 > longest) longest = kH + 1 - covered[i] / 3;
  for (int c = 0; c < 2 * n_pair; c++) {
    uint32_t items = 0, cur = 0, pend = 0;
    int n = 0, ev = 0;
    auto item = [&](uint32_t bytes, int count) {
      for (int i = 0; i < count; i++) { if (cur + bytes > RING) cur = 0; cur += bytes; items++; }
    };
    auto event = [&](uint32_t e) { if (ev < MAX_TAB) P.prog[c].ev[ev] = e; ev++; };
    for (const Op* o = op[c];; o++) {
      if (o->type != OP_END && phase && (o->type == OP_O) != (phase == 2)) continue;
      uint32_t cw = o->type | (items % (2 * NBAR)) << 15 | (cur >> 12) << 20 | pend, pw = o->type | o->id << 2 | o->flags;
      const int ps = use[N_TILE + (o->park & 127)].slot;
      pend = 0;
      if (o->type == OP_O) {
        pw |= o->n << 13 | o->quarter << 20 | (uint32_t)o->park << 23;
        if (o->flags & P_WIDE) {
          cw |= o->n << 2 | (o->id / kH * 2 + o->quarter / 2) << 9 | C_WIDE;
          item(SZ_W, o->n - TAIL);
          item(SZ_W2, TAIL);
          item(SZ_W3, TAIL);
          pend = C_PEND;
          for (int i = 0; 3 * i < o->n; i++) event((o->id + i) | E_ON | (use[o->id + i].next ? 0 : E_LAST));
        } else {
          dem[n_job++] = {o->t0 - 1e6 * o->n, nullptr, (int)pw};
          st.own[c] = pw;
          pw = OP_O;
          event(E_DRAW | (items < 16 ? 0 : items - 16));
        }
      } else if (o->type != OP_END) {
        const bool parks = o->type == OP_Q && (o->flags & F_PARK);
        cw |= (parks ? ps : use[o->id].slot) << 2 | (o->flags & F_PARK);
        if (o->flags & F_PARK) pw |= o->park << 13 | ps << 20;
        if (o->type == OP_Q) { item(SZ_Q, 10); pw |= o->quarter; }
        else { if (o->flags & F_PARK) { item(SZ_PARK, 1); event((N_TILE + o->park) | E_ON | (use[N_TILE + o->park].next ? 0 : E_LAST)); } item(SZ_KV, 32); }
        if (parks || o->type == OP_A) pend = C_PEND;
        if (o->flags & P_GATE) event(use[parks ? N_TILE + o->park : o->id].prev | E_ON | E_FREE);
      }
      P.prog[c].c[n] = cw; P.prog[c].p[n++] = pw;
      if (o->type == OP_END) { if (o->t0 > st.end) st.end = o->t0; break; }
    }
    if (ev > MAX_TAB || ev + longest > MAX_EV) return false;
    P.prog[c].n_ev = ev;
    while (n < MAX_OPS) { P.prog[c].c[n] = OP_END; P.prog[c].p[n++] = OP_END; }
    P.first[c] = (uint16_t)(P.prog[c].p[0] & 2047);
  }
  sort(dem, n_job);
  for (int i = 0; i < n_job; i++) P.job[i] = dem[i].id;
  for (int i = 0; i < ID_PART; i++) {
    if (i < N_TILE) P.slot[i] = use[i].slot;
    P.info[i] = (use[i].readers + use[i].next) | (use[i].next ? I_NEXT : 0);
  }
  if (stats) *stats = st;
  return true;
}

const char* const kPrograms[N_CL / 2] = {
  "PNJ06864NNNNN", "PNJ17878NNNNN", "PNJ26464NNNNN", "PNJ34148NNNNNN", "PNJ46262NNNNN", "PNJ58182NNNN",
  "NNJ67371NNNN", "PNNJ76666NNNN", "NUNNNJ84545NN", "NUNNNJ94545NN", "NUNNNNJa5551N", "NNNNNJb5959NN",
  "NNNNNJc5455NN", "PNNNNNJd5353NN", "NNNNNJe5153NN", "NNNNNJf7777N", "PNNNNNNNNN", "PNNNNNNNNN",
  "PNNNNNNNNN", "PNNNNNNNNN", "NNNNNNNNN", "NNNNNNNNN", "NNNNNNNNN", "NNNNNNNNN",
  "NNNNNNNNN", "N-NNNNNNNN", "NUNNNNNNN", "NUNNNNNNN", "NUNNNNNNN", "NUNNNUNNN",
  "NUNNNNNNN", "NUNNNNNNN", "NUUNNNNNN",
};

const char* const* bench_programs() {
  return kPrograms;
}

}

extern "C" void kernel_launch(void* const* d_in, const int* in_sizes, int n_in, void* d_out, int out_size) {
  (void)in_sizes; (void)n_in; (void)out_size;
  static EncodeFn fn = nullptr;
  static int n_clusters = 0;
  if (!fn) {
    cudaDriverEntryPointQueryResult qr;
    void* f = nullptr;
    cudaGetDriverEntryPoint("cuTensorMapEncodeTiled", &f, cudaEnableDefault, &qr);
    fn = (EncodeFn)f;
    cudaFuncSetAttribute(fused_kernel, cudaFuncAttributeMaxDynamicSharedMemorySize, SMEM_BYTES);
    cudaLaunchConfig_t cfg = {};
    cfg.gridDim = dim3(132); cfg.blockDim = dim3(384); cfg.dynamicSmemBytes = SMEM_BYTES;
    cudaLaunchAttribute at[1];
    at[0].id = cudaLaunchAttributeClusterDimension; at[0].val.clusterDim.x = 2; at[0].val.clusterDim.y = 1; at[0].val.clusterDim.z = 1;
    cfg.attrs = at; cfg.numAttrs = 1;
    if (cudaOccupancyMaxActiveClusters(&n_clusters, fused_kernel, &cfg) != cudaSuccess || n_clusters < 1) n_clusters = 1;
    (void)cudaGetLastError();
  }
  static Params P;
  const CUtensorMapSwizzle S128 = CU_TENSOR_MAP_SWIZZLE_128B, S64 = CU_TENSOR_MAP_SWIZZLE_64B;
  for (int blk = 0; blk < 2; blk++) {
    void* const* in = d_in + 5 * blk;
    { const cuuint64_t d[] = {kD, kB * kSq}, s[] = {kD * 2}; const cuuint32_t b[] = {64, 128};
      encode(fn, &P.x[blk], in[0], 2, d, s, b, S128); }
    { const cuuint64_t d[] = {64, 8, 3, (cuuint64_t)kB * kH * kSk / 8}, s[] = {kDh * 2, 128, 8 * kDh * 2}; const cuuint32_t b[] = {64, 8, 3, 4};
      encode(fn, &P.k[blk], in[1], 4, d, s, b, S128);
      encode(fn, &P.v[blk], in[2], 4, d, s, b, S128); }
    { const cuuint64_t d[] = {64, kD, kHD / 64}, s[] = {kHD * 2, 128}; const cuuint32_t b[] = {64, 32, 3};
      encode(fn, &P.wq[blk], in[3], 3, d, s, b, S128); }
    { const cuuint64_t d[] = {32, 2, kHD / 8, 4, kD / 32}, s[] = {kD * 2, 8 * kD * 2, 2 * kD * 2, 64}; const cuuint32_t b[] = {32, 2, 4, 4, 5};
      encode(fn, &P.wo[blk], in[4], 5, d, s, b, S64); }
    { const cuuint64_t d[] = {64, 2, kHD / 8, 4, kD / 64}, s[] = {kD * 2, 8 * kD * 2, 2 * kD * 2, 128};
      const cuuint32_t b3[] = {64, 2, 4, 4, 3}, b2[] = {64, 2, 4, 4, 2};
      encode(fn, &P.wo3[blk], in[4], 5, d, s, b3, S128);
      encode(fn, &P.wo2[blk], in[4], 5, d, s, b2, S128); }
  }
  { const cuuint64_t d[] = {32, kB * kSq, 2 * kD / 32}, s[] = {2 * kD * 2, 64}; const cuuint32_t b[] = {32, 16, 1};
    encode(fn, &P.out, d_out, 3, d, s, b, S64); }

  P.kv[0] = (const char*)d_in[1]; P.kv[1] = (const char*)d_in[6]; P.kv[2] = (const char*)d_in[2]; P.kv[3] = (const char*)d_in[7];
  P.xw[0] = (const char*)d_in[0]; P.xw[1] = (const char*)d_in[3];
  cudaGetSymbolAddress((void**)&P.g, g_scratch);
  P.dbg = DBG_DEFAULT;
  if (n_clusters >= N_CL && plan(bench_programs(), N_CL / 2, 0, P)) {
    fused_kernel<<<2 * N_CL, 384, SMEM_BYTES>>>(P);
  } else {
    const char* text[2 * N_TEAM];
    for (int i = 0; i < 2 * N_TEAM; i++) text[i] = "NNNNNNNN";
    for (int phase = 1; phase <= 2; phase++) {
      plan(text, 2 * N_TEAM, phase, P);
      fused_kernel<<<8 * N_TEAM, 384, SMEM_BYTES>>>(P);
    }
  }
}
```

```cpp
#include <cuda_runtime.h>
#include <cuda_bf16.h>
#include <cuda.h>
#include <cuda/annotated_ptr>
#include <stdint.h>
#include <stdio.h>

namespace {

constexpr int kB = 8, kSq = 256, kD = 640, kH = 32, kSk = 1024, kDh = 192;
constexpr int kHD = kH * kDh;
constexpr uint32_t RING = 224 * 1024;
constexpr uint32_t SZ_KV = 24576;
constexpr uint32_t SZ_Q = 16384 + 24576;
constexpr uint32_t SZ_O = 16384 + 20480;
constexpr uint32_t SZ_W3 = 16384 + 24576, SZ_W2 = 16384 + 16384, SZ_W = SZ_W3 + 16384;
constexpr uint32_t SZ_PARK = 49152;
constexpr uint32_t SZ_OL = SZ_O + 8192;
constexpr int NBAR = 16, FLIGHT = RING / SZ_KV + 1;
constexpr int EARLY = 3;
constexpr int kSteps = kHD / 64;
constexpr int TAIL = 4;
constexpr uint32_t KV_CH = 64, KV_SBO = 3072;
constexpr int SMEM_BYTES = RING + 1024 + 1024;
constexpr int N_TEAM = 16, N_CL = 66, MAX_OPS = 22, MAX_EV = 72, MAX_TAB = 47, N_TILE = N_TEAM * kH, MAX_PARK = 128, ID_PART = N_TILE + MAX_PARK;
enum : uint32_t { OP_END = 0, OP_Q = 1, OP_A = 2, OP_O = 3, F_PARK = 1 << 11,
                  C_WIDE = 1 << 27, C_PEND = 1 << 26, P_GATE = 1 << 12, P_WIDE = 1 << 11, P_LD = 1 << 12, P_PRE = 1 << 22, P_LASTW = 1 << 29, P_LASTX = 1 << 30,
                  I_NEXT = 8, E_ON = 1 << 15, E_FREE = 1 << 14, E_LAST = 1 << 13, E_DRAW = 1 << 12, E_JOB = 1 << 11 };

constexpr uint32_t DBG_DEFAULT = 0x040800;

struct alignas(1024) Scratch {
  unsigned int flag[2047];
  unsigned int ticket;
  uint4 part[N_TEAM * 2 * 2 * 5120];
  uint4 tile[N_TILE * 2 * 3072];
};

struct alignas(64) Params {
  const char* xw[2];
  uint16_t first[80];
  Scratch* g;
  uint32_t dbg;
  CUtensorMap x[2], wq[2], k[2], v[2], wo[2], wo3[2], wo2[2], out;
  struct {
    uint32_t c[MAX_OPS];
    uint32_t p[MAX_OPS];
    uint16_t n_ev, ev[MAX_TAB];
  } prog[N_CL];
  const char* kv[4];
  uint32_t job[N_CL];
  uint16_t slot[N_TILE];
  uint8_t info[ID_PART];
};

__device__ Scratch g_scratch;

template <int TB, int TA = 0>
__device__ __forceinline__ void wgmma_ss_n64(float (&d)[32], uint64_t da, uint64_t db, int scale_d) {
  asm volatile("{\n.reg .pred p;\nsetp.ne.b32 p, %34, 0;\n"
    "wgmma.mma_async.sync.aligned.m64n64k16.f32.bf16.bf16 {%0, %1, %2, %3, %4, %5, %6, %7, %8, %9, %10, %11, %12, %13, %14, %15, %16, %17, %18, %19, %20, %21, %22, %23, %24, %25, %26, %27, %28, %29, %30, %31}, %32, %33, p, 1, 1, %35, %36;\n}\n"
    : "+f"(d[0]), "+f"(d[1]), "+f"(d[2]), "+f"(d[3]), "+f"(d[4]), "+f"(d[5]), "+f"(d[6]), "+f"(d[7]), "+f"(d[8]), "+f"(d[9]), "+f"(d[10]), "+f"(d[11]), "+f"(d[12]), "+f"(d[13]), "+f"(d[14]), "+f"(d[15]), "+f"(d[16]), "+f"(d[17]), "+f"(d[18]), "+f"(d[19]), "+f"(d[20]), "+f"(d[21]), "+f"(d[22]), "+f"(d[23]), "+f"(d[24]), "+f"(d[25]), "+f"(d[26]), "+f"(d[27]), "+f"(d[28]), "+f"(d[29]), "+f"(d[30]), "+f"(d[31])
    : "l"(da), "l"(db), "r"(scale_d), "n"(TA), "n"(TB));
}
template <int TB>
__device__ __forceinline__ void wgmma_rs_n64(float (&d)[32], uint32_t a0, uint32_t a1, uint32_t a2, uint32_t a3, uint64_t db, int scale_d) {
  asm volatile("{\n.reg .pred p;\nsetp.ne.b32 p, %37, 0;\n"
    "wgmma.mma_async.sync.aligned.m64n64k16.f32.bf16.bf16 {%0, %1, %2, %3, %4, %5, %6, %7, %8, %9, %10, %11, %12, %13, %14, %15, %16, %17, %18, %19, %20, %21, %22, %23, %24, %25, %26, %27, %28, %29, %30, %31}, {%32, %33, %34, %35}, %36, p, 1, 1, %38;\n}\n"
    : "+f"(d[0]), "+f"(d[1]), "+f"(d[2]), "+f"(d[3]), "+f"(d[4]), "+f"(d[5]), "+f"(d[6]), "+f"(d[7]), "+f"(d[8]), "+f"(d[9]), "+f"(d[10]), "+f"(d[11]), "+f"(d[12]), "+f"(d[13]), "+f"(d[14]), "+f"(d[15]), "+f"(d[16]), "+f"(d[17]), "+f"(d[18]), "+f"(d[19]), "+f"(d[20]), "+f"(d[21]), "+f"(d[22]), "+f"(d[23]), "+f"(d[24]), "+f"(d[25]), "+f"(d[26]), "+f"(d[27]), "+f"(d[28]), "+f"(d[29]), "+f"(d[30]), "+f"(d[31])
    : "r"(a0), "r"(a1), "r"(a2), "r"(a3), "l"(db), "r"(scale_d), "n"(TB));
}
template <int TB, int TA = 0>
__device__ __forceinline__ void wgmma_ss_n128(float (&d)[64], uint64_t da, uint64_t db, int scale_d) {
  asm volatile("{\n.reg .pred p;\nsetp.ne.b32 p, %66, 0;\n"
    "wgmma.mma_async.sync.aligned.m64n128k16.f32.bf16.bf16 {%0, %1, %2, %3, %4, %5, %6, %7, %8, %9, %10, %11, %12, %13, %14, %15, %16, %17, %18, %19, %20, %21, %22, %23, %24, %25, %26, %27, %28, %29, %30, %31, %32, %33, %34, %35, %36, %37, %38, %39, %40, %41, %42, %43, %44, %45, %46, %47, %48, %49, %50, %51, %52, %53, %54, %55, %56, %57, %58, %59, %60, %61, %62, %63}, %64, %65, p, 1, 1, %67, %68;\n}\n"
    : "+f"(d[0]), "+f"(d[1]), "+f"(d[2]), "+f"(d[3]), "+f"(d[4]), "+f"(d[5]), "+f"(d[6]), "+f"(d[7]), "+f"(d[8]), "+f"(d[9]), "+f"(d[10]), "+f"(d[11]), "+f"(d[12]), "+f"(d[13]), "+f"(d[14]), "+f"(d[15]), "+f"(d[16]), "+f"(d[17]), "+f"(d[18]), "+f"(d[19]), "+f"(d[20]), "+f"(d[21]), "+f"(d[22]), "+f"(d[23]), "+f"(d[24]), "+f"(d[25]), "+f"(d[26]), "+f"(d[27]), "+f"(d[28]), "+f"(d[29]), "+f"(d[30]), "+f"(d[31]), "+f"(d[32]), "+f"(d[33]), "+f"(d[34]), "+f"(d[35]), "+f"(d[36]), "+f"(d[37]), "+f"(d[38]), "+f"(d[39]), "+f"(d[40]), "+f"(d[41]), "+f"(d[42]), "+f"(d[43]), "+f"(d[44]), "+f"(d[45]), "+f"(d[46]), "+f"(d[47]), "+f"(d[48]), "+f"(d[49]), "+f"(d[50]), "+f"(d[51]), "+f"(d[52]), "+f"(d[53]), "+f"(d[54]), "+f"(d[55]), "+f"(d[56]), "+f"(d[57]), "+f"(d[58]), "+f"(d[59]), "+f"(d[60]), "+f"(d[61]), "+f"(d[62]), "+f"(d[63])
    : "l"(da), "l"(db), "r"(scale_d), "n"(TA), "n"(TB));
}
template <int TB>
__device__ __forceinline__ void wgmma_rs_n128(float (&d)[64], uint32_t a0, uint32_t a1, uint32_t a2, uint32_t a3, uint64_t db, int scale_d) {
  asm volatile("{\n.reg .pred p;\nsetp.ne.b32 p, %69, 0;\n"
    "wgmma.mma_async.sync.aligned.m64n128k16.f32.bf16.bf16 {%0, %1, %2, %3, %4, %5, %6, %7, %8, %9, %10, %11, %12, %13, %14, %15, %16, %17, %18, %19, %20, %21, %22, %23, %24, %25, %26, %27, %28, %29, %30, %31, %32, %33, %34, %35, %36, %37, %38, %39, %40, %41, %42, %43, %44, %45, %46, %47, %48, %49, %50, %51, %52, %53, %54, %55, %56, %57, %58, %59, %60, %61, %62, %63}, {%64, %65, %66, %67}, %68, p, 1, 1, %70;\n}\n"
    : "+f"(d[0]), "+f"(d[1]), "+f"(d[2]), "+f"(d[3]), "+f"(d[4]), "+f"(d[5]), "+f"(d[6]), "+f"(d[7]), "+f"(d[8]), "+f"(d[9]), "+f"(d[10]), "+f"(d[11]), "+f"(d[12]), "+f"(d[13]), "+f"(d[14]), "+f"(d[15]), "+f"(d[16]), "+f"(d[17]), "+f"(d[18]), "+f"(d[19]), "+f"(d[20]), "+f"(d[21]), "+f"(d[22]), "+f"(d[23]), "+f"(d[24]), "+f"(d[25]), "+f"(d[26]), "+f"(d[27]), "+f"(d[28]), "+f"(d[29]), "+f"(d[30]), "+f"(d[31]), "+f"(d[32]), "+f"(d[33]), "+f"(d[34]), "+f"(d[35]), "+f"(d[36]), "+f"(d[37]), "+f"(d[38]), "+f"(d[39]), "+f"(d[40]), "+f"(d[41]), "+f"(d[42]), "+f"(d[43]), "+f"(d[44]), "+f"(d[45]), "+f"(d[46]), "+f"(d[47]), "+f"(d[48]), "+f"(d[49]), "+f"(d[50]), "+f"(d[51]), "+f"(d[52]), "+f"(d[53]), "+f"(d[54]), "+f"(d[55]), "+f"(d[56]), "+f"(d[57]), "+f"(d[58]), "+f"(d[59]), "+f"(d[60]), "+f"(d[61]), "+f"(d[62]), "+f"(d[63])
    : "r"(a0), "r"(a1), "r"(a2), "r"(a3), "l"(db), "r"(scale_d), "n"(TB));
}
template <int TB, int TA = 0>
__device__ __forceinline__ void wgmma_ss_n160(float (&d)[80], uint64_t da, uint64_t db, int scale_d) {
  asm volatile("{\n.reg .pred p;\nsetp.ne.b32 p, %82, 0;\n"
    "wgmma.mma_async.sync.aligned.m64n160k16.f32.bf16.bf16 {%0, %1, %2, %3, %4, %5, %6, %7, %8, %9, %10, %11, %12, %13, %14, %15, %16, %17, %18, %19, %20, %21, %22, %23, %24, %25, %26, %27, %28, %29, %30, %31, %32, %33, %34, %35, %36, %37, %38, %39, %40, %41, %42, %43, %44, %45, %46, %47, %48, %49, %50, %51, %52, %53, %54, %55, %56, %57, %58, %59, %60, %61, %62, %63, %64, %65, %66, %67, %68, %69, %70, %71, %72, %73, %74, %75, %76, %77, %78, %79}, %80, %81, p, 1, 1, %83, %84;\n}\n"
    : "+f"(d[0]), "+f"(d[1]), "+f"(d[2]), "+f"(d[3]), "+f"(d[4]), "+f"(d[5]), "+f"(d[6]), "+f"(d[7]), "+f"(d[8]), "+f"(d[9]), "+f"(d[10]), "+f"(d[11]), "+f"(d[12]), "+f"(d[13]), "+f"(d[14]), "+f"(d[15]), "+f"(d[16]), "+f"(d[17]), "+f"(d[18]), "+f"(d[19]), "+f"(d[20]), "+f"(d[21]), "+f"(d[22]), "+f"(d[23]), "+f"(d[24]), "+f"(d[25]), "+f"(d[26]), "+f"(d[27]), "+f"(d[28]), "+f"(d[29]), "+f"(d[30]), "+f"(d[31]), "+f"(d[32]), "+f"(d[33]), "+f"(d[34]), "+f"(d[35]), "+f"(d[36]), "+f"(d[37]), "+f"(d[38]), "+f"(d[39]), "+f"(d[40]), "+f"(d[41]), "+f"(d[42]), "+f"(d[43]), "+f"(d[44]), "+f"(d[45]), "+f"(d[46]), "+f"(d[47]), "+f"(d[48]), "+f"(d[49]), "+f"(d[50]), "+f"(d[51]), "+f"(d[52]), "+f"(d[53]), "+f"(d[54]), "+f"(d[55]), "+f"(d[56]), "+f"(d[57]), "+f"(d[58]), "+f"(d[59]), "+f"(d[60]), "+f"(d[61]), "+f"(d[62]), "+f"(d[63]), "+f"(d[64]), "+f"(d[65]), "+f"(d[66]), "+f"(d[67]), "+f"(d[68]), "+f"(d[69]), "+f"(d[70]), "+f"(d[71]), "+f"(d[72]), "+f"(d[73]), "+f"(d[74]), "+f"(d[75]), "+f"(d[76]), "+f"(d[77]), "+f"(d[78]), "+f"(d[79])
    : "l"(da), "l"(db), "r"(scale_d), "n"(TA), "n"(TB));
}
template <int TB>
__device__ __forceinline__ void wgmma_rs_n160(float (&d)[80], uint32_t a0, uint32_t a1, uint32_t a2, uint32_t a3, uint64_t db, int scale_d) {
  asm volatile("{\n.reg .pred p;\nsetp.ne.b32 p, %85, 0;\n"
    "wgmma.mma_async.sync.aligned.m64n160k16.f32.bf16.bf16 {%0, %1, %2, %3, %4, %5, %6, %7, %8, %9, %10, %11, %12, %13, %14, %15, %16, %17, %18, %19, %20, %21, %22, %23, %24, %25, %26, %27, %28, %29, %30, %31, %32, %33, %34, %35, %36, %37, %38, %39, %40, %41, %42, %43, %44, %45, %46, %47, %48, %49, %50, %51, %52, %53, %54, %55, %56, %57, %58, %59, %60, %61, %62, %63, %64, %65, %66, %67, %68, %69, %70, %71, %72, %73, %74, %75, %76, %77, %78, %79}, {%80, %81, %82, %83}, %84, p, 1, 1, %86;\n}\n"
    : "+f"(d[0]), "+f"(d[1]), "+f"(d[2]), "+f"(d[3]), "+f"(d[4]), "+f"(d[5]), "+f"(d[6]), "+f"(d[7]), "+f"(d[8]), "+f"(d[9]), "+f"(d[10]), "+f"(d[11]), "+f"(d[12]), "+f"(d[13]), "+f"(d[14]), "+f"(d[15]), "+f"(d[16]), "+f"(d[17]), "+f"(d[18]), "+f"(d[19]), "+f"(d[20]), "+f"(d[21]), "+f"(d[22]), "+f"(d[23]), "+f"(d[24]), "+f"(d[25]), "+f"(d[26]), "+f"(d[27]), "+f"(d[28]), "+f"(d[29]), "+f"(d[30]), "+f"(d[31]), "+f"(d[32]), "+f"(d[33]), "+f"(d[34]), "+f"(d[35]), "+f"(d[36]), "+f"(d[37]), "+f"(d[38]), "+f"(d[39]), "+f"(d[40]), "+f"(d[41]), "+f"(d[42]), "+f"(d[43]), "+f"(d[44]), "+f"(d[45]), "+f"(d[46]), "+f"(d[47]), "+f"(d[48]), "+f"(d[49]), "+f"(d[50]), "+f"(d[51]), "+f"(d[52]), "+f"(d[53]), "+f"(d[54]), "+f"(d[55]), "+f"(d[56]), "+f"(d[57]), "+f"(d[58]), "+f"(d[59]), "+f"(d[60]), "+f"(d[61]), "+f"(d[62]), "+f"(d[63]), "+f"(d[64]), "+f"(d[65]), "+f"(d[66]), "+f"(d[67]), "+f"(d[68]), "+f"(d[69]), "+f"(d[70]), "+f"(d[71]), "+f"(d[72]), "+f"(d[73]), "+f"(d[74]), "+f"(d[75]), "+f"(d[76]), "+f"(d[77]), "+f"(d[78]), "+f"(d[79])
    : "r"(a0), "r"(a1), "r"(a2), "r"(a3), "l"(db), "r"(scale_d), "n"(TB));
}
template <int TB, int TA = 0>
__device__ __forceinline__ void wgmma_ss_n192(float (&d)[96], uint64_t da, uint64_t db, int scale_d) {
  asm volatile("{\n.reg .pred p;\nsetp.ne.b32 p, %98, 0;\n"
    "wgmma.mma_async.sync.aligned.m64n192k16.f32.bf16.bf16 {%0, %1, %2, %3, %4, %5, %6, %7, %8, %9, %10, %11, %12, %13, %14, %15, %16, %17, %18, %19, %20, %21, %22, %23, %24, %25, %26, %27, %28, %29, %30, %31, %32, %33, %34, %35, %36, %37, %38, %39, %40, %41, %42, %43, %44, %45, %46, %47, %48, %49, %50, %51, %52, %53, %54, %55, %56, %57, %58, %59, %60, %61, %62, %63, %64, %65, %66, %67, %68, %69, %70, %71, %72, %73, %74, %75, %76, %77, %78, %79, %80, %81, %82, %83, %84, %85, %86, %87, %88, %89, %90, %91, %92, %93, %94, %95}, %96, %97, p, 1, 1, %99, %100;\n}\n"
    : "+f"(d[0]), "+f"(d[1]), "+f"(d[2]), "+f"(d[3]), "+f"(d[4]), "+f"(d[5]), "+f"(d[6]), "+f"(d[7]), "+f"(d[8]), "+f"(d[9]), "+f"(d[10]), "+f"(d[11]), "+f"(d[12]), "+f"(d[13]), "+f"(d[14]), "+f"(d[15]), "+f"(d[16]), "+f"(d[17]), "+f"(d[18]), "+f"(d[19]), "+f"(d[20]), "+f"(d[21]), "+f"(d[22]), "+f"(d[23]), "+f"(d[24]), "+f"(d[25]), "+f"(d[26]), "+f"(d[27]), "+f"(d[28]), "+f"(d[29]), "+f"(d[30]), "+f"(d[31]), "+f"(d[32]), "+f"(d[33]), "+f"(d[34]), "+f"(d[35]), "+f"(d[36]), "+f"(d[37]), "+f"(d[38]), "+f"(d[39]), "+f"(d[40]), "+f"(d[41]), "+f"(d[42]), "+f"(d[43]), "+f"(d[44]), "+f"(d[45]), "+f"(d[46]), "+f"(d[47]), "+f"(d[48]), "+f"(d[49]), "+f"(d[50]), "+f"(d[51]), "+f"(d[52]), "+f"(d[53]), "+f"(d[54]), "+f"(d[55]), "+f"(d[56]), "+f"(d[57]), "+f"(d[58]), "+f"(d[59]), "+f"(d[60]), "+f"(d[61]), "+f"(d[62]), "+f"(d[63]), "+f"(d[64]), "+f"(d[65]), "+f"(d[66]), "+f"(d[67]), "+f"(d[68]), "+f"(d[69]), "+f"(d[70]), "+f"(d[71]), "+f"(d[72]), "+f"(d[73]), "+f"(d[74]), "+f"(d[75]), "+f"(d[76]), "+f"(d[77]), "+f"(d[78]), "+f"(d[79]), "+f"(d[80]), "+f"(d[81]), "+f"(d[82]), "+f"(d[83]), "+f"(d[84]), "+f"(d[85]), "+f"(d[86]), "+f"(d[87]), "+f"(d[88]), "+f"(d[89]), "+f"(d[90]), "+f"(d[91]), "+f"(d[92]), "+f"(d[93]), "+f"(d[94]), "+f"(d[95])
    : "l"(da), "l"(db), "r"(scale_d), "n"(TA), "n"(TB));
}
template <int TB>
__device__ __forceinline__ void wgmma_rs_n192(float (&d)[96], uint32_t a0, uint32_t a1, uint32_t a2, uint32_t a3, uint64_t db, int scale_d) {
  asm volatile("{\n.reg .pred p;\nsetp.ne.b32 p, %101, 0;\n"
    "wgmma.mma_async.sync.aligned.m64n192k16.f32.bf16.bf16 {%0, %1, %2, %3, %4, %5, %6, %7, %8, %9, %10, %11, %12, %13, %14, %15, %16, %17, %18, %19, %20, %21, %22, %23, %24, %25, %26, %27, %28, %29, %30, %31, %32, %33, %34, %35, %36, %37, %38, %39, %40, %41, %42, %43, %44, %45, %46, %47, %48, %49, %50, %51, %52, %53, %54, %55, %56, %57, %58, %59, %60, %61, %62, %63, %64, %65, %66, %67, %68, %69, %70, %71, %72, %73, %74, %75, %76, %77, %78, %79, %80, %81, %82, %83, %84, %85, %86, %87, %88, %89, %90, %91, %92, %93, %94, %95}, {%96, %97, %98, %99}, %100, p, 1, 1, %102;\n}\n"
    : "+f"(d[0]), "+f"(d[1]), "+f"(d[2]), "+f"(d[3]), "+f"(d[4]), "+f"(d[5]), "+f"(d[6]), "+f"(d[7]), "+f"(d[8]), "+f"(d[9]), "+f"(d[10]), "+f"(d[11]), "+f"(d[12]), "+f"(d[13]), "+f"(d[14]), "+f"(d[15]), "+f"(d[16]), "+f"(d[17]), "+f"(d[18]), "+f"(d[19]), "+f"(d[20]), "+f"(d[21]), "+f"(d[22]), "+f"(d[23]), "+f"(d[24]), "+f"(d[25]), "+f"(d[26]), "+f"(d[27]), "+f"(d[28]), "+f"(d[29]), "+f"(d[30]), "+f"(d[31]), "+f"(d[32]), "+f"(d[33]), "+f"(d[34]), "+f"(d[35]), "+f"(d[36]), "+f"(d[37]), "+f"(d[38]), "+f"(d[39]), "+f"(d[40]), "+f"(d[41]), "+f"(d[42]), "+f"(d[43]), "+f"(d[44]), "+f"(d[45]), "+f"(d[46]), "+f"(d[47]), "+f"(d[48]), "+f"(d[49]), "+f"(d[50]), "+f"(d[51]), "+f"(d[52]), "+f"(d[53]), "+f"(d[54]), "+f"(d[55]), "+f"(d[56]), "+f"(d[57]), "+f"(d[58]), "+f"(d[59]), "+f"(d[60]), "+f"(d[61]), "+f"(d[62]), "+f"(d[63]), "+f"(d[64]), "+f"(d[65]), "+f"(d[66]), "+f"(d[67]), "+f"(d[68]), "+f"(d[69]), "+f"(d[70]), "+f"(d[71]), "+f"(d[72]), "+f"(d[73]), "+f"(d[74]), "+f"(d[75]), "+f"(d[76]), "+f"(d[77]), "+f"(d[78]), "+f"(d[79]), "+f"(d[80]), "+f"(d[81]), "+f"(d[82]), "+f"(d[83]), "+f"(d[84]), "+f"(d[85]), "+f"(d[86]), "+f"(d[87]), "+f"(d[88]), "+f"(d[89]), "+f"(d[90]), "+f"(d[91]), "+f"(d[92]), "+f"(d[93]), "+f"(d[94]), "+f"(d[95])
    : "r"(a0), "r"(a1), "r"(a2), "r"(a3), "l"(db), "r"(scale_d), "n"(TB));
}

__device__ __forceinline__ uint32_t smem_u32(const void* p) { return (uint32_t)__cvta_generic_to_shared(p); }
__device__ __forceinline__ void wg_fence() { asm volatile("wgmma.fence.sync.aligned;" ::: "memory"); }
__device__ __forceinline__ void wg_commit() { asm volatile("wgmma.commit_group.sync.aligned;" ::: "memory"); }
template <int N> __device__ __forceinline__ void wg_wait() { asm volatile("wgmma.wait_group.sync.aligned %0;" ::"n"(N) : "memory"); }
__device__ __forceinline__ void sched_fence(uint32_t& keep, bool never) {
  asm volatile("{\n.reg .pred p;\nsetp.ne.b32 p, %1, 0;\n@p mov.u32 %0, %%clock;\n}\n" : "+r"(keep) : "r"((int)never) : "memory");
}
template <int N> __device__ __forceinline__ void fence_regs(float (&r)[N]) {
#pragma unroll
  for (int i = 0; i < N; i++) asm volatile("" : "+f"(r[i])::"memory");
}
template <int N> __device__ __forceinline__ void undefine(float (&r)[N]) {
#pragma unroll
  for (int i = 0; i < N; i++) asm volatile("" : "=f"(r[i]));
}
template <int N> __device__ __forceinline__ void fence_regs(uint32_t (&r)[N]) {
#pragma unroll
  for (int i = 0; i < N; i++) asm volatile("" : "+r"(r[i])::"memory");
}
__device__ __forceinline__ uint64_t mk_desc(uint32_t a16, uint32_t lbo, uint32_t sbo, uint32_t swz) {
  uint64_t d;
  asm("mov.b64 %0, {%1, %2};" : "=l"(d) : "r"(a16 + ((lbo >> 4) << 16)), "r"((sbo >> 4) | (swz << 30)));
  return d;
}
__device__ __forceinline__ void mbar_init(uint32_t bar, uint32_t cnt) {
  asm volatile("mbarrier.init.shared::cta.b64 [%0], %1;" ::"r"(bar), "r"(cnt) : "memory");
}
__device__ __forceinline__ void mbar_expect(uint32_t bar, uint32_t tx) {
  asm volatile("mbarrier.arrive.expect_tx.shared::cta.b64 _, [%0], %1;" ::"r"(bar), "r"(tx) : "memory");
}
__device__ __forceinline__ bool mbar_test(uint32_t bar, uint32_t ph) {
  uint32_t ok;
  asm volatile("{\n.reg .pred p;\nmbarrier.test_wait.parity.shared::cta.b64 p, [%1], %2;\nselp.u32 %0, 1, 0, p;\n}\n"
               : "=r"(ok) : "r"(bar), "r"(ph) : "memory");
  return ok;
}
__device__ __forceinline__ bool mbar_try(uint32_t bar, uint32_t ph, uint32_t ns) {
  uint32_t ok;
  asm volatile("{\n.reg .pred p;\nmbarrier.try_wait.parity.shared::cta.b64 p, [%1], %2, %3;\nselp.u32 %0, 1, 0, p;\n}\n"
               : "=r"(ok) : "r"(bar), "r"(ph), "r"(ns) : "memory");
  return ok;
}
__device__ __forceinline__ void mbar_wait(uint32_t bar, uint32_t ph) {
  asm volatile("{\n.reg .pred p;\n.reg .u32 n;\nmov.u32 n, 0;\n"
               "LOOP:\nmbarrier.try_wait.parity.shared::cta.b64 p, [%0], %1;\n@p bra DONE;\n"
               "add.u32 n, n, 1;\nsetp.lt.u32 p, n, 0x1000000;\n@p bra LOOP;\ntrap;\n"
               "DONE:\n}\n" ::"r"(bar), "r"(ph) : "memory");
}
__device__ __forceinline__ void mbar_wait_long(uint32_t bar) {
  asm volatile("{\n.reg .pred p;\n.reg .u32 n;\nmov.u32 n, 0;\n"
               "LOOP:\nmbarrier.try_wait.parity.shared::cta.b64 p, [%0], 0, 20000;\n@p bra DONE;\n"
               "add.u32 n, n, 1;\nsetp.lt.u32 p, n, 0x100000;\n@p bra LOOP;\ntrap;\n"
               "DONE:\n}\n" ::"r"(bar) : "memory");
}
__device__ __forceinline__ void mbar_arrive_cluster_if(bool on, uint32_t addr) {
  asm volatile("{\n.reg .pred p;\nsetp.ne.b32 p, %1, 0;\n@p mbarrier.arrive.shared::cluster.b64 _, [%0];\n}\n" ::"r"(addr), "r"((int)on) : "memory");
}
__device__ __forceinline__ void mbar_arrive_cluster_n(uint32_t n, uint32_t addr) {
  asm volatile("{\n.reg .pred p;\nsetp.ne.b32 p, %1, 0;\n@p mbarrier.arrive.shared::cluster.b64 _, [%0], %1;\n}\n" ::"r"(addr), "r"(n) : "memory");
}
__device__ __forceinline__ void tma2d(uint32_t dst, const CUtensorMap* m, uint32_t bar, int c0, int c1) {
  asm volatile("cp.async.bulk.tensor.2d.shared::cluster.global.mbarrier::complete_tx::bytes [%0], [%1, {%3, %4}], [%2];"
               ::"r"(dst), "l"(m), "r"(bar), "r"(c0), "r"(c1) : "memory");
}
__device__ __forceinline__ void tma3d(uint32_t dst, const CUtensorMap* m, uint32_t bar, int c0, int c1, int c2) {
  asm volatile("cp.async.bulk.tensor.3d.shared::cluster.global.mbarrier::complete_tx::bytes [%0], [%1, {%3, %4, %5}], [%2];"
               ::"r"(dst), "l"(m), "r"(bar), "r"(c0), "r"(c1), "r"(c2) : "memory");
}
__device__ __forceinline__ void tma2d_hint(uint32_t dst, const CUtensorMap* m, uint32_t bar, int c0, int c1, uint64_t pol) {
  asm volatile("cp.async.bulk.tensor.2d.shared::cluster.global.mbarrier::complete_tx::bytes.L2::cache_hint [%0], [%1, {%3, %4}], [%2], %5;"
               ::"r"(dst), "l"(m), "r"(bar), "r"(c0), "r"(c1), "l"(pol) : "memory");
}
__device__ __forceinline__ void tma3d_mc_hint(uint32_t dst, const CUtensorMap* m, uint32_t bar, int c1, int c2, uint64_t pol) {
  asm volatile("cp.async.bulk.tensor.3d.shared::cluster.global.mbarrier::complete_tx::bytes.multicast::cluster.L2::cache_hint"
               " [%0], [%1, {%3, %4, %5}], [%2], %6, %7;"
               ::"r"(dst), "l"(m), "r"(bar), "r"(0), "r"(c1), "r"(c2), "h"((uint16_t)3), "l"(pol) : "memory");
}
__device__ __forceinline__ void tma5d_mc_hint(uint32_t dst, const CUtensorMap* m, uint32_t bar, int c2, int c4, uint64_t pol) {
  asm volatile("cp.async.bulk.tensor.5d.shared::cluster.global.mbarrier::complete_tx::bytes.multicast::cluster.L2::cache_hint"
               " [%0], [%1, {%3, %3, %4, %3, %5}], [%2], %6, %7;"
               ::"r"(dst), "l"(m), "r"(bar), "r"(0), "r"(c2), "r"(c4), "h"((uint16_t)3), "l"(pol) : "memory");
}
__device__ __forceinline__ void tma3d_store(const CUtensorMap* m, uint32_t src, int c0, int c1, int c2) {
  asm volatile("cp.async.bulk.tensor.3d.global.shared::cta.bulk_group [%0, {%2, %3, %4}], [%1];"
               ::"l"(m), "r"(src), "r"(c0), "r"(c1), "r"(c2) : "memory");
}
__device__ __forceinline__ void bar_sync(int id, int n) { asm volatile("bar.sync %0, %1;" ::"r"(id), "r"(n) : "memory"); }
__device__ __forceinline__ uint32_t pack_bf16(float lo, float hi) {
  uint32_t r;
  asm("cvt.rn.bf16x2.f32 %0, %1, %2;" : "=r"(r) : "f"(hi), "f"(lo));
  return r;
}
__device__ __forceinline__ float ex2(float x) {
  float y;
  asm("ex2.approx.ftz.f32 %0, %1;" : "=f"(y) : "f"(x));
  return y;
}
__device__ __forceinline__ float rcp(float x) {
  float y;
  asm("rcp.approx.ftz.f32 %0, %1;" : "=f"(y) : "f"(x));
  return y;
}
__device__ __forceinline__ void stsm4(uint32_t addr, uint32_t a, uint32_t b, uint32_t c, uint32_t d) {
  asm volatile("stmatrix.sync.aligned.m8n8.x4.shared.b16 [%0], {%1, %2, %3, %4};" ::"r"(addr), "r"(a), "r"(b), "r"(c), "r"(d) : "memory");
}

__device__ __forceinline__ void tma4d_mc_hint(uint32_t dst, const CUtensorMap* m, uint32_t bar, int c3, uint64_t pol) {
  asm volatile("cp.async.bulk.tensor.4d.shared::cluster.global.mbarrier::complete_tx::bytes.multicast::cluster.L2::cache_hint"
               " [%0], [%1, {%3, %3, %3, %4}], [%2], %5, %6;"
               ::"r"(dst), "l"(m), "r"(bar), "r"(0), "r"(c3), "h"((uint16_t)3), "l"(pol) : "memory");
}
__device__ __forceinline__ void bulk_load_hint(uint32_t dst, const void* src, uint32_t bytes, uint32_t bar, uint64_t pol) {
  asm volatile("cp.async.bulk.shared::cluster.global.mbarrier::complete_tx::bytes.L2::cache_hint [%0], [%1], %2, [%3], %4;"
               ::"r"(dst), "l"(src), "r"(bytes), "r"(bar), "l"(pol) : "memory");
}
__device__ __forceinline__ void stg2_if(bool on, void* p, uint32_t a, uint32_t b, uint32_t c, uint32_t d, uint32_t e, uint32_t f,
                                        uint32_t g, uint32_t h, uint64_t pol) {
  asm volatile("{\n.reg .pred p;\nsetp.ne.b32 p, %10, 0;\n"
               "@p st.global.L2::cache_hint.v4.b32 [%0], {%1, %2, %3, %4}, %9;\n"
               "@p st.global.L2::cache_hint.v4.b32 [%0 + 512], {%5, %6, %7, %8}, %9;\n}\n"
               ::"l"(p), "r"(a), "r"(b), "r"(c), "r"(d), "r"(e), "r"(f), "r"(g), "r"(h), "l"(pol), "r"((int)on) : "memory");
}
__device__ __forceinline__ uint64_t evict_first() {
  uint64_t p;
  asm("createpolicy.fractional.L2::evict_first.b64 %0, 1.0;" : "=l"(p));
  return p;
}
__device__ __forceinline__ uint64_t no_hint() {
  uint64_t p;
  asm("createpolicy.cvt.L2.b64 %0, %1;" : "=l"(p) : "l"(static_cast<uint64_t>(cuda::access_property{})));
  return p;
}
__device__ __forceinline__ bool elect() {
  uint32_t ok;
  asm volatile("{\n.reg .pred p;\nelect.sync _|p, 0xffffffff;\nselp.u32 %0, 1, 0, p;\n}\n" : "=r"(ok));
  return ok;
}
__device__ __forceinline__ void mbar_arrive(uint32_t bar) {
  asm volatile("mbarrier.arrive.shared::cta.b64 _, [%0];" ::"r"(bar) : "memory");
}
__device__ __forceinline__ void mbar_arrive_if(bool on, uint32_t bar) {
  asm volatile("{\n.reg .pred p;\nsetp.ne.b32 p, %1, 0;\n@p mbarrier.arrive.shared::cta.b64 _, [%0];\n}\n" ::"r"(bar), "r"((int)on) : "memory");
}
__device__ __forceinline__ void lds2_if(bool on, uint32_t p, uint32_t (&t)[8]) {
  asm volatile("{\n.reg .pred p;\nsetp.ne.b32 p, %9, 0;\n@p ld.shared.v4.b32 {%0, %1, %2, %3}, [%8];\n@p ld.shared.v4.b32 {%4, %5, %6, %7}, [%8 + 512];\n}\n"
               : "+r"(t[0]), "+r"(t[1]), "+r"(t[2]), "+r"(t[3]), "+r"(t[4]), "+r"(t[5]), "+r"(t[6]), "+r"(t[7]) : "r"(p), "r"((int)on) : "memory");
}
__device__ __forceinline__ void lds128(uint32_t p, uint32_t& a, uint32_t& b, uint32_t& c, uint32_t& d) {
  asm volatile("ld.shared.v4.b32 {%0, %1, %2, %3}, [%4];" : "=r"(a), "=r"(b), "=r"(c), "=r"(d) : "r"(p) : "memory");
}
template <class T> __device__ __forceinline__ T* ptr_add(T* base, uint32_t bytes) {
  T* r;
  asm("{\n.reg .u32 lo, hi;\nmov.b64 {lo, hi}, %1;\nadd.cc.u32 lo, lo, %2;\naddc.u32 hi, hi, 0;\nmov.b64 %0, {lo, hi};\n}\n" : "=l"(r) : "l"(base), "r"(bytes));
  return r;
}
__device__ __forceinline__ uint32_t lds32(uint32_t p) {
  uint32_t v;
  asm volatile("ld.volatile.shared.u32 %0, [%1];" : "=r"(v) : "r"(p) : "memory");
  return v;
}
__device__ __forceinline__ uint32_t flag_get(const unsigned int* p) {
  uint32_t v;
  asm volatile("ld.acquire.gpu.global.u32 %0, [%1];" : "=r"(v) : "l"(p) : "memory");
  return v;
}
__device__ __forceinline__ uint32_t wait_word(uint32_t p, uint32_t target) {
  uint32_t v;
  asm volatile("{\n.reg .pred p;\n.reg .u32 n;\nmov.u32 n, 0;\n"
               "LOOP:\nld.acquire.cta.shared.u32 %0, [%1];\nsetp.ge.u32 p, %0, %2;\n@p bra DONE;\n"
               "nanosleep.u32 %3;\nadd.u32 n, n, 1;\nsetp.lt.u32 p, n, 0x400000;\n@p bra LOOP;\ntrap;\n"
               "DONE:\n}\n" : "=r"(v) : "r"(p), "r"(target), "n"(400) : "memory");
  return v;
}
__device__ __forceinline__ void flag_set(unsigned int* p, uint32_t v) {
  asm volatile("st.release.gpu.global.u32 [%0], %1;" ::"l"(p), "r"(v) : "memory");
}
__device__ __forceinline__ void flag_dec(unsigned int* p) {
  asm volatile("red.relaxed.gpu.global.add.u32 [%0], 0xffffffff;" ::"l"(p) : "memory");
}

struct Cursor {
  uint32_t n;
  __device__ __forceinline__ uint32_t off() const { return n & (8 * NBAR - 8); }
  __device__ __forceinline__ uint32_t ph() const { return (n / (8 * NBAR)) & 1; }
  __device__ __forceinline__ void next() { n += 8; }
};

constexpr float kScaleLog2 = 0.07216878364870322f * 1.4426950408889634f;
constexpr float kSumLimit = 1048576.0f;

__global__ void __cluster_dims__(2, 1, 1) __launch_bounds__(384, 1)
fused_kernel(const __grid_constant__ Params P) {
  extern __shared__ uint8_t smem_raw[];
  const uint32_t sbase = (smem_u32(smem_raw) + 1023) & ~1023u;
  const uint32_t full0 = sbase + RING, empty0 = full0 + 8 * NBAR, odone0 = empty0 + 8 * NBAR, ev0 = odone0 + 8 * MAX_OPS;
  const uint32_t progress = ev0 + 8 * MAX_EV, jobw = progress + 4;
  const uint32_t rank = blockIdx.x & 1;
  const int role = blockIdx.x >> 1;
  const int wid = __shfl_sync(0xffffffffu, (int)(threadIdx.x >> 5), 0);
  const int wg = wid >> 2;

  if (wid < 8) {
    if (elect()) {
#pragma unroll
      for (int j = 0; j < 16; j++) {
        const int i = EARLY + 16 * wid + j;
        if (i < 2 * NBAR + MAX_OPS + MAX_EV) mbar_init(full0 + 8 * i, i < NBAR ? 1 : i < 2 * NBAR ? 16 : i < 2 * NBAR + MAX_OPS ? 8 : 1);
      }
      if (wid == 7) asm volatile("st.shared.v2.u32 [%0], {0, 0};\nfence.acq_rel.cta;" ::"r"(progress) : "memory");
      asm volatile("fence.mbarrier_init.release.cluster;" ::: "memory");
    }
  } else if (wid > 8) {
    const uint32_t g = blockIdx.x * 96 + threadIdx.x - 288, w = g - 2048;
    if (g < 4096) asm volatile("prefetch.global.L2 [%0];" ::"l"(g < 2048 ? P.xw[0] + g * (kD * 2) : P.xw[1] + (w >> 5) * (kHD * 2) + (w & 31) * 128));
  } else {
    const uint32_t op0 = P.first[role];
    if (elect()) {
#pragma unroll
      for (int k = 0; k < EARLY; k++) mbar_init(full0 + 8 * k, 1);
      asm volatile("fence.mbarrier_init.release.cluster;" ::: "memory");
      const int blk = (op0 >> 10) & 1;
      if ((op0 & 3) == OP_Q) {
#pragma unroll
        for (int k = 0; k < EARLY; k++) {
          mbar_expect(full0 + 8 * k, SZ_Q);
          tma2d(sbase + k * SZ_Q, &P.x[blk], full0 + 8 * k, 64 * k, ((op0 >> 7) & 7) * kSq + rank * 128);
          tma3d(sbase + k * SZ_Q + 16384, &P.wq[blk], full0 + 8 * k, 0, 64 * k, 3 * ((op0 >> 2) & 31));
          tma3d(sbase + k * SZ_Q + 28672, &P.wq[blk], full0 + 8 * k, 0, 64 * k + 32, 3 * ((op0 >> 2) & 31));
        }
      }
      asm volatile("prefetch.tensormap [%0];\nprefetch.tensormap [%1];" ::"l"(&P.k[blk]), "l"(&P.v[blk]) : "memory");
    }
  }
  __syncwarp();
  asm volatile("barrier.cluster.arrive.relaxed.aligned;\nbarrier.cluster.wait.aligned;" ::: "memory");

  if (wg < 2) {
    asm volatile("setmaxnreg.inc.sync.aligned.u32 240;");
    const uint32_t* prog = P.prog[role].c;
    const int wid = __shfl_sync(0xffffffffu, (int)(threadIdx.x >> 5), 1), wg = wid >> 2;
    const int lane = threadIdx.x & 31, warp = wid & 3;
    uint32_t empty_rem;
    asm volatile("mapa.shared::cluster.u32 %0, %1, %2;" : "=r"(empty_rem) : "r"(empty0), "r"(lane & 1));
    uint32_t keep = (threadIdx.x & 127) < 2 ? 4 : 0;
    auto release = [&](int slot) { mbar_arrive_cluster_n(keep, empty_rem + slot); };
    auto release_warp = [&](int slot, bool on = true) { mbar_arrive_cluster_if(lane < 2 && on, empty_rem + slot); };
    Cursor r{0};
    const uint32_t ring16 = (sbase & 0x3FFFF) >> 4;
    uint32_t cur = ring16;
    bool rdy0 = false, rdy1 = false;
    auto probe1 = [&]() { rdy0 = mbar_test(full0 + r.off(), r.ph()); };
    auto probe2 = [&]() {
      Cursor n = r;
      rdy0 = mbar_test(full0 + n.off(), n.ph());
      n.next();
      rdy1 = mbar_test(full0 + n.off(), n.ph());
    };
    auto advance = [&](uint32_t bytes, uint32_t& addr) {
      const int bi = r.off();
      r.next();
      if (cur > ring16 + ((RING - bytes) >> 4)) cur = ring16;
      addr = cur;
      cur += bytes >> 4;
      return bi;
    };
    auto take = [&](bool rdy, uint32_t bytes, uint32_t& addr) {
      if (__builtin_expect(!__all_sync(0xffffffffu, rdy), 0)) mbar_wait(full0 + r.off(), r.ph());
      return advance(bytes, addr);
    };
    const bool never = P.dbg == 0xffffffffu;
    uint32_t q[48];
#pragma unroll
    for (int i = 0; i < 48; i++) q[i] = 0;
    const int row = wg * 64 + warp * 16 + (lane >> 2);
    const int img0 = row * 4 + ((lane & 3) ^ ((row >> 1) & 3));
    uint4* pend = nullptr;
    bool pend_any = false;
    const uint64_t spol = evict_first();
    int pc = 0;
    auto slab = [&](int c, int i0) {
#pragma unroll
      for (int i = i0; i < 6; i++)
        stg2_if(c == i, pend + i * 512, q[8 * i], q[8 * i + 1], q[8 * i + 2], q[8 * i + 3],
                q[8 * i + 4], q[8 * i + 5], q[8 * i + 6], q[8 * i + 7], spol);
    };
    auto drain = [&](int c) {
      if (!pend_any || c >= 6) return;
      slab(c, 0);
      if (c == 5) {
        __syncwarp();
        mbar_arrive_if(lane == 0, odone0 - 8 + 8 * pc);
      }
    };

    for (;; pc++) {
      uint32_t op = prog[pc];
      const int type = op & 3;
      auto enter = [&]() {
        r.n = (op >> 12) & 248; cur = ring16 + (((op >> 20) & 63) << 8);
      };
      enter();
      pend_any = op & C_PEND;
      uint32_t job = 0;
      if ((op & (3 | C_WIDE)) == OP_O) job = __shfl_sync(0xffffffffu, wait_word(jobw, 1), 0);
      if (type == OP_END || job == OP_O) {
#pragma unroll 1
        for (int c = 0; c < 6; c++) drain(c);
        asm volatile("barrier.cluster.arrive.relaxed;" ::: "memory");
        break;
      }
      {
        float s[32], o[96];
        uint32_t ad0;
        int bi0, sk1;
        uint32_t pa[16], pb[16];
        float mc0, mc1, l0, l1;
        bool shifted;
        uint32_t nop;
        auto expo = [&](float (&s)[32], uint32_t (&pout)[16], float& b0, float& b1, bool shift, auto mid) {
          float c0, c1;
#pragma unroll
          for (int i = 0; i < 8; i++) {
            const float e0 = ex2(shift ? s[4 * i] - mc0 : s[4 * i]), e1 = ex2(shift ? s[4 * i + 1] - mc0 : s[4 * i + 1]);
            const float e2 = ex2(shift ? s[4 * i + 2] - mc1 : s[4 * i + 2]), e3 = ex2(shift ? s[4 * i + 3] - mc1 : s[4 * i + 3]);
            if (i) { b0 += e0; c0 += e1; b1 += e2; c1 += e3; } else { b0 = e0; c0 = e1; b1 = e2; c1 = e3; }
            pout[2 * i] = pack_bf16(e0, e1); pout[2 * i + 1] = pack_bf16(e2, e3);
            if (i & 1) mid(i >> 1);
          }
          b0 += c0; b1 += c1;
        };
        auto rowmax = [&](float (&s)[32], float& m0, float& m1) {
          m0 = fmaxf(s[0], s[1]); m1 = fmaxf(s[2], s[3]);
#pragma unroll
          for (int i = 1; i < 8; i++) { m0 = fmaxf(m0, fmaxf(s[4 * i], s[4 * i + 1])); m1 = fmaxf(m1, fmaxf(s[4 * i + 2], s[4 * i + 3])); }
          m0 = fmaxf(m0, __shfl_xor_sync(0xffffffffu, m0, 1)); m1 = fmaxf(m1, __shfl_xor_sync(0xffffffffu, m1, 1));
          m0 = fmaxf(m0, __shfl_xor_sync(0xffffffffu, m0, 2)); m1 = fmaxf(m1, __shfl_xor_sync(0xffffffffu, m1, 2));
        };
        auto first = [&](float (&s)[32], int sk0, auto mid) {
          fence_regs(s);
          release(sk0);
          mc0 = 0.f; mc1 = 0.f;
          expo(s, pa, l0, l1, false, mid);
          shifted = __any_sync(0xffffffffu, !(fmaxf(l0, l1) <= kSumLimit && fminf(l0, l1) >= 1.f / kSumLimit));
          if (shifted) {
            rowmax(s, mc0, mc1);
            expo(s, pa, l0, l1, true, [](int) {});
          }
        };
        auto qk = [&](float (&s)[32], uint32_t ak, int k0 = 0, int k1 = 12) {
#pragma unroll
          for (int kk = k0; kk < k1; kk++)
            wgmma_rs_n64<0>(s, q[4 * kk], q[4 * kk + 1], q[4 * kk + 2], q[4 * kk + 3], mk_desc(ak, 16, KV_SBO, 1) + ((kk >> 2) * KV_CH + (kk & 3) * 2), kk != 0);
          if (k1 == 12) wg_commit();
        };
        auto pv = [&](uint32_t (&pin)[16], uint32_t av, int acc) {
#pragma unroll
          for (int kk = 0; kk < 4; kk++)
            wgmma_rs_n192<1>(o, pin[4 * kk], pin[4 * kk + 1], pin[4 * kk + 2], pin[4 * kk + 3], mk_desc(av, KV_CH * 16, KV_SBO, 1) + (kk * (KV_SBO / 8)), acc || (kk != 0));
          wg_commit();
        };
        auto finish = [&](uint32_t (&pout)[16], int sk, int sv) {
          probe1();
          wg_wait<1>();
          fence_regs(s);
          release(sk);
          float b0, b1;
#pragma unroll 1
          for (bool redo = false;; redo = true) {
            expo(s, pout, b0, b1, false, [](int) {});
            if (!__any_sync(0xffffffffu, !redo && (shifted || !(fmaxf(b0, b1) <= kSumLimit)))) break;
            shifted = true;
            rowmax(s, b0, b1);
            b0 = fmaxf(mc0, b0); b1 = fmaxf(mc1, b1);
            const float a0 = ex2(mc0 - b0), a1 = ex2(mc1 - b1);
            mc0 = b0; mc1 = b1;
            l0 *= a0; l1 *= a1;
            wg_wait<0>();
            fence_regs(o);
#pragma unroll
            for (int i = 0; i < 24; i++) { o[4 * i] *= a0; o[4 * i + 1] *= a0; o[4 * i + 2] *= a1; o[4 * i + 3] *= a1; }
#pragma unroll
            for (int i = 0; i < 32; i++) s[i] -= (i & 2) ? mc1 : mc0;
          }
          l0 += b0; l1 += b1;
          wg_wait<0>();
          fence_regs(o);
          release(sv);
        };
        auto step = [&](uint32_t (&pin)[16], uint32_t (&pout)[16]) {
          uint32_t ak, av;
          const int sk = take(rdy0, SZ_KV, ak), sv = advance(SZ_KV, av);
          wg_fence();
          qk(s, ak);
          pv(pin, av, 1);
          finish(pout, sk, sv);
        };
        auto unpark = [&]() {
          uint32_t ad, ak;
          const Cursor k0 = r;
          const int sk0 = advance(SZ_KV, ak), bi = take(false, SZ_PARK, ad);
#pragma unroll
          for (int i = 0; i < 12; i++) lds128(sbase + (ad - ring16 + img0) * 16 + (i >> 1) * 8192 + (i & 1) * 512, q[4 * i], q[4 * i + 1], q[4 * i + 2], q[4 * i + 3]);
          if (!__all_sync(0xffffffffu, rdy0)) mbar_wait(full0 + k0.off(), k0.ph());
          fence_regs(q);
          release_warp(bi);
          wg_fence();
          qk(s, ak);
          probe2();
          return sk0;
        };
        auto mma4 = [&](uint32_t ad, int acc) {
#pragma unroll
          for (int kk = 0; kk < 4; kk++)
            wgmma_ss_n192<1>(o, mk_desc(ad + wg * 512, 16, 1024, 1) + (kk * 2), mk_desc(ad, 4096, 1024, 1) + (1024 + (kk >> 1) * 768 + (kk & 1) * 128), acc || kk != 0);
        };
        auto convert = [&](int i0, int i1) {
          sched_fence(keep, never);
#pragma unroll
          for (int i = i0; i < i1; i++) {
            q[i] = pack_bf16(o[2 * i] * kScaleLog2, o[2 * i + 1] * kScaleLog2);
            if ((i & 7) == 7 && i != i1 - 1) sched_fence(keep, never);
          }
          sched_fence(keep, never);
        };
        auto kend = [&](int bi, int k) {
          wg_commit();
          drain((0x54732710u >> (4 * k)) & 7);
          probe1();
          wg_wait<0>();
          release(bi);
        };
        if (type == OP_O) {
          int prev = 0;
          if (op & C_WIDE) {
            float d[64];
            auto mma3 = [&](uint32_t ad, int h, int acc) {
#pragma unroll
              for (int kk = 0; kk < 2; kk++)
                wgmma_ss_n192<1>(o, mk_desc(ad + wg * 256, 16, 512, 2) + (h * 512 + kk * 2), mk_desc(ad, 4096, 1024, 1) + (1024 + h * 768 + kk * 128), acc || kk);
            };
            auto mma2 = [&](uint32_t ad, uint32_t ob, int h, int acc) {
#pragma unroll
              for (int kk = 0; kk < 2; kk++)
                wgmma_ss_n128<1>(d, mk_desc(ad + wg * 256, 16, 512, 2) + (h * 512 + kk * 2), mk_desc(ad, 4096, 1024, 1) + (ob + h * 512 + kk * 128), acc || kk);
            };
            auto wstep = [&](uint32_t bytes, int acc, auto hook) {
              uint32_t ad;
              const int bi = take(rdy0, bytes, ad);
              wg_fence();
              if (bytes == SZ_W2) mma2(ad, 1024, 0, 1); else mma3(ad, 0, acc);
              if (bytes == SZ_W) mma3(ad, 1, 1);
              wg_commit();
              if (acc) { wg_wait<1>(); release(prev); }
              if (bytes == SZ_W) mma2(ad, 2560, 0, acc);
              if (bytes == SZ_W3) mma3(ad, 1, 1); else mma2(ad, bytes == SZ_W ? 2560 : 1024, 1, 1);
              wg_commit();
              prev = bi;
              hook();
              probe1();
              wg_wait<1>();
            };
            undefine(o);
            wstep(SZ_W, 0, [&]() { drain(0); });
#pragma unroll 1
            for (int k = 1; k < ((op >> 2) & 127) - TAIL; k++) wstep(SZ_W, 1, [&]() { drain(k); });
#pragma unroll 1
            for (int k = 0; k < TAIL; k++) wstep(SZ_W2, 1, []() {});
            pend = ptr_add(P.g->part, (((op >> 9) & 31) * 2 + rank) * 81920 + 4 * 8192 + img0 * 16);
            wstep(SZ_W3, 1, [&]() {
              fence_regs(d);
#pragma unroll
              for (int i = 0; i < 32; i++) q[16 + i] = pack_bf16(d[2 * i], d[2 * i + 1]);
              slab(2, 2);
            });
#pragma unroll 1
            for (int k = 3; k < 6; k++) wstep(SZ_W3, 1, [&]() { slab(k, 2); });
            op = prog[pc + 1];
            enter();
            pend_any = true;
            pend -= 4 * 512;
            bi0 = take(rdy0 || (op & 3) != OP_Q, SZ_Q, ad0);
            sched_fence(keep, never);
            wg_wait<0>();
            fence_regs(o);
            release(prev);
#pragma unroll
            for (int i = 0; i < 48; i++) q[i] = pack_bf16(o[2 * i], o[2 * i + 1]);
            if ((op & 3) != OP_Q) continue;
            pc++;
            goto first_step;
          }
          float c[80];
          auto mma2 = [&](uint32_t ad, uint32_t oa, uint32_t ob, int acc) {
            wgmma_ss_n160<1>(c, mk_desc(ad + wg * 256, 16, 512, 2) + (oa), mk_desc(ad, 2048, 512, 2) + (1024 + ob), acc);
            wgmma_ss_n160<1>(c, mk_desc(ad + wg * 256, 16, 512, 2) + (oa + 2), mk_desc(ad, 2048, 512, 2) + (1024 + ob + 64), 1);
          };
          auto kstep = [&](int acc, auto hook, uint32_t bytes = SZ_O) {
            uint32_t ad;
            const int bi = take(rdy0, bytes, ad);
            wg_fence();
            mma2(ad, 0, 0, acc);
            wg_commit();
            if (acc) wg_wait<1>();
            if (acc == 1) release(prev);
            if (acc > 1) release_warp(prev, acc == 2 || wg == 0);
            mma2(ad, 512, 640, 1);
            wg_commit();
            prev = bi;
            hook();
            probe1();
            wg_wait<1>();
          };
          auto unblock = [&](int k) {
            if (__all_sync(0xffffffffu, rdy0) || __all_sync(0xffffffffu, mbar_try(full0 + r.off(), r.ph(), 1500))) return;
#pragma unroll 1
            for (; k < 6; k++) drain(k);
            pend_any = false;
          };
          unblock(0);
          kstep(0, [&]() { drain(0); });
          int left = ((job >> 13) & 127) - 6;
#pragma unroll 1
          for (uint32_t k = 1, pace = left >= 22 ? 0x4511 : left <= 11 ? 0x1a : 0x155; left > 0; pace >>= 2, left--) {
            unblock(k);
            kstep(1, [&]() {
#pragma unroll 1
              for (int i = pace & 3; i > 0; i--) drain(k++);
            });
          }
          uint32_t t[8], stage[3];
          float u[80];
          auto unpack = [&](int j) {
#pragma unroll
            for (int i = 0; i < 8; i++) {
              u[16 * j + 2 * i] = __uint_as_float(t[i] << 16); u[16 * j + 2 * i + 1] = __uint_as_float(t[i] & 0xffff0000u);
              asm volatile("" : "+f"(u[16 * j + 2 * i]), "+f"(u[16 * j + 2 * i + 1]));
            }
          };
#pragma unroll
          for (int i = 0; i < 8; i++) t[i] = 0;
          const uint32_t bytes = (job & P_LD) ? SZ_OL : SZ_O;
#pragma unroll
          for (int j = 0; j < 5; j++) {
            if (j == 2 && wg == 1) {
              wg_wait<0>();
              release_warp(prev);
              bar_sync(1, 256);
            }
            kstep(j == 2 ? 3 : 2, [&]() {
              if (j == 4) asm volatile("{\n.reg .pred p;\nsetp.eq.u32 p, %0, 0;\n@p bar.arrive 1, 256;\n}\n" ::"r"(wg) : "memory");
              if (j) unpack(j - 1);
              lds2_if(job & P_LD, sbase + (cur - ring16 + img0) * 16 - 8192, t);
              if (j >= 1 && j <= 3) stage[j - 1] = sbase + (cur - ring16) * 16 - bytes + wid * 1024;
            }, bytes);
          }
          unpack(4);
          sched_fence(keep, never);
          wg_wait<0>();
          fence_regs(c);
          release_warp(prev);
          asm volatile("barrier.cluster.arrive.relaxed;" ::: "memory");
#pragma unroll
          for (int i = 0; i < 10; i++) {
            const int v = (i & 1) * 2 + (lane >> 4);
            const uint32_t sa = stage[i >> 2] + (i & 2) * 4096;
            stsm4(sa + (lane & 15) * 64 + ((v ^ ((lane >> 1) & 3)) << 4), pack_bf16(c[8 * i] + u[8 * i], c[8 * i + 1] + u[8 * i + 1]),
                  pack_bf16(c[8 * i + 2] + u[8 * i + 2], c[8 * i + 3] + u[8 * i + 3]), pack_bf16(c[8 * i + 4] + u[8 * i + 4], c[8 * i + 5] + u[8 * i + 5]),
                  pack_bf16(c[8 * i + 6] + u[8 * i + 6], c[8 * i + 7] + u[8 * i + 7]));
          }
          asm volatile("fence.proxy.async.shared::cta;" ::: "memory");
          __syncwarp();
          if (elect()) {
#pragma unroll
            for (int i = 0; i < 5; i++)
              tma3d_store(&P.out, stage[i >> 1] + (i & 1) * 8192, 0, ((job >> 7) & 7) * kSq + rank * 128 + wid * 16, ((job >> 10) & 1) * 20 + ((job >> 20) & 3) * 5 + i);
            asm volatile("cp.async.bulk.commit_group;\ncp.async.bulk.wait_group.read 0;" ::: "memory");
          }
          __syncwarp();
          break;
        }
        bi0 = take(rdy0, SZ_Q, ad0);
      first_step:
        undefine(o);
        wg_fence();
        mma4(ad0, 0);
        kend(bi0, 0);
        fence_regs(o);
      next_head:
        {
#pragma unroll 1
          for (int k = 1; k < 8; k++) {
            uint32_t ad;
            const int bi = take(rdy0, SZ_Q, ad);
            wg_fence();
            mma4(ad, 1);
            kend(bi, k);
          }
          uint32_t a8, a9, ak0, ak1;
          const int b8 = take(rdy0, SZ_Q, a8), b9 = take(false, SZ_Q, a9);
          wg_fence();
          mma4(a8, 1);
          wg_commit();
          mma4(a9, 1);
          wg_commit();
          wg_wait<1>();
          release(b8);
          probe1();
          const int sk0 = take(rdy0 || (op & F_PARK), SZ_KV, ak0);
          wg_wait<0>();
          fence_regs(o);
          release(b9);
          float s0[32];
          convert(0, 32);
          if (op & F_PARK) {
            convert(32, 48);
            pend = ptr_add(P.g->tile, (((op >> 2) & 511) * 2 + rank) * SZ_PARK + img0 * 16);
            continue;
          }
          pc++;
          wg_fence();
          qk(s0, ak0, 0, 4);
          convert(32, 48);
          wg_fence();
          qk(s0, ak0, 4, 12);
          sk1 = take(false, SZ_KV, ak1);
          wg_fence();
          qk(s, ak1, 0, 4);
          wg_commit();
          probe1();
          wg_wait<1>();
          first(s0, sk0, [&](int i) {
            if (!(i & 1)) return;
            sched_fence(keep, never);
            wg_fence();
            if (i == 1) qk(s, ak1, 4, 8);
            if (i == 3) qk(s, ak1, 8, 12);
            sched_fence(keep, never);
          });
        }
        for (;;) {
          {
            uint32_t av;
            const int sv = take(rdy0, SZ_KV, av);
            undefine(o);
            wg_fence();
            pv(pa, av, 0);
            finish(pb, sk1, sv);
          }
          nop = prog[pc + 1];
#pragma unroll 1
          for (int jj = 0; jj < 7; jj++) {
            step(pb, pa);
            step(pa, pb);
          }
          float i0, i1;
          auto last = [&]() {
            uint32_t av;
            const int sv = take(rdy0, SZ_KV, av);
            wg_fence();
            pv(pb, av, 1);
            sched_fence(keep, never);
            probe1();
            l0 += __shfl_xor_sync(0xffffffffu, l0, 1); l1 += __shfl_xor_sync(0xffffffffu, l1, 1);
            l0 += __shfl_xor_sync(0xffffffffu, l0, 2); l1 += __shfl_xor_sync(0xffffffffu, l1, 2);
            i0 = rcp(l0); i1 = rcp(l1);
            pend = ptr_add(P.g->tile, (((op >> 2) & 511) * 2 + rank) * SZ_PARK + img0 * 16);
            return sv;
          };
          auto normalise = [&](uint32_t (&d)[48], auto mid) {
#pragma unroll
            for (int i = 0; i < 24; i++) {
              d[8 * (i >> 2) + (i & 3)] = pack_bf16(o[4 * i] * i0, o[4 * i + 1] * i0);
              d[8 * (i >> 2) + (i & 3) + 4] = pack_bf16(o[4 * i + 2] * i1, o[4 * i + 3] * i1);
              if ((i & 1) && i != 23) sched_fence(keep, never);
              if ((i & 3) == 3 && i != 23) mid(i >> 2);
            }
          };
          const int sv = last();
          if ((nop & 3) != OP_A) {
            op = nop;
            enter();
            pend_any = true;
            bi0 = take(rdy0 || (nop & 3) != OP_Q, SZ_Q, ad0);
            sched_fence(keep, never);
            wg_wait<0>();
            fence_regs(o);
            release(sv);
            normalise(q, [](int) {});
            undefine(o);
            if ((nop & 3) != OP_Q) break;
            sched_fence(keep, never);
            wg_fence();
            mma4(ad0, 0);
            pc++;
            kend(bi0, 0);
            fence_regs(o);
            goto next_head;
          }
          const int sk0 = unpark();
          wg_wait<1>();
          fence_regs(o);
          release(sv);
          uint32_t t[48];
          auto st = [&](int i) {
            stg2_if(true, pend + i * 512, t[8 * i], t[8 * i + 1], t[8 * i + 2], t[8 * i + 3], t[8 * i + 4], t[8 * i + 5], t[8 * i + 6], t[8 * i + 7], spol);
          };
          normalise(t, [&](int i) { if (!(i & 1)) st(i >> 1); });
          wg_wait<0>();
          first(s, sk0, [&](int i) { if (i < 3) { sched_fence(keep, never); st(3 + i); } });
          __syncwarp();
          mbar_arrive_if(lane == 0, odone0 + 8 * pc);
          pc++;
          op = nop;
          uint32_t ak1;
          sk1 = take(rdy0, SZ_KV, ak1);
          rdy0 = rdy1;
          wg_fence();
          qk(s, ak1);
        }
      }
    }
    asm volatile("barrier.cluster.wait;" ::: "memory");
  } else {
    asm volatile("setmaxnreg.dec.sync.aligned.u32 24;");
    const uint32_t* prog = P.prog[role].p;
    unsigned int* flag = P.g->flag + rank;
    if (wid == 11 && (prog[0] & 3) == OP_Q) {
      const uint32_t a = prog[1];
      const char* p = ptr_add(P.kv[rank * 2 + ((a >> 10) & 1)], ((a >> 2) & 255) * (kSk * kDh * 2) + (threadIdx.x & 31) * 128);
#pragma unroll 1
      for (uint32_t k = 0; k < 3; k++) {
        wait_word(progress, 8 * k);
        p += SZ_KV;
        asm volatile("prefetch.global.L2 [%0];\nprefetch.global.L2 [%0 + 4096];" ::"l"(p));
      }
      __syncwarp();
    }
    if (wid == 8) {
      Cursor head{0}, tail{0};
      int sh = 0, room = RING >> 12;
      uint32_t cur = 0;
      uint64_t fifo = 0;
      uint32_t dst, bar = 0, ev = ev0;
      const uint64_t pol = evict_first();
      auto retire = [&]() {
        mbar_wait(empty0 + tail.off(), tail.ph());
        tail.next();
        room += (uint32_t)fifo & 31;
        fifo >>= 5;
        sh -= 5;
        asm volatile("st.volatile.shared.u32 [%0], %1;" ::"r"(progress), "r"(tail.n) : "memory");
      };
      auto acquire = [&](uint32_t bytes) {
        uint32_t fp = bytes >> 12;
        if (cur + fp > (RING >> 12)) { fp += (RING >> 12) - cur; cur = 0; }
        room -= fp;
        while (room < 0) retire();
        fifo |= (uint64_t)fp << sh;
        sh += 5;
        dst = sbase + (cur << 12);
        bar = full0 + head.off();
        cur += bytes >> 12;
        head.next();
      };
      auto gate = [&]() {
        mbar_wait(ev, 0);
        ev += 8;
        asm volatile("fence.proxy.async.global;" ::: "memory");
      };
      for (int pc = 0;; pc++) {
        uint32_t op = prog[pc];
        const int type = op & 3;
        if (type == OP_END) break;
        if (op == OP_O) {
          gate();
          op = __shfl_sync(0xffffffffu, lds32(jobw), 0);
        }
        const int blk = (op >> 10) & 1;
        if (type == OP_Q) {
          const uint64_t px = (op & P_LASTX) ? pol : no_hint(), pw = (op & P_LASTW) ? pol : no_hint();
          int k = 0;
          if (pc == 0) {
            k = 64 * EARLY; head.n = 8 * EARLY; sh = 5 * EARLY; cur = EARLY * (SZ_Q >> 12); room -= cur;
            fifo = (SZ_Q >> 12) * (((1u << (5 * EARLY)) - 1) / 31);
          }
#pragma unroll 1
          for (int stop = (op & P_GATE) ? kD - 64 : kD;; stop = kD) {
#pragma unroll 1
            for (; k < stop; k += 64) {
              acquire(SZ_Q);
              if (elect()) {
                mbar_expect(bar, SZ_Q);
                tma3d_mc_hint(dst + 16384 + rank * 12288, &P.wq[blk], bar, k + 32 * rank, 3 * ((op >> 2) & 31), pw);
                tma2d_hint(dst, &P.x[blk], bar, k, ((op >> 7) & 7) * kSq + rank * 128, px);
              }
            }
            if (k == kD) break;
            gate();
          }
        } else if (type == OP_A) {
          const int row0 = ((op >> 2) & 255) * kSk;
          auto kv = [&](uint32_t tx, const CUtensorMap* m, int c3) {
            const uint32_t before = bar;
            acquire(SZ_KV);
            if (elect()) {
              mbar_expect(bar, tx);
              tma4d_mc_hint(dst + rank * (SZ_KV / 2), m, tx ? bar : before, c3, pol);
            }
          };
          int c3 = row0 / 8 + 4 * rank;
#pragma unroll 1
          for (int j = 0; j <= 16; j++, c3 += 8) {
            const uint32_t tv = j < 2 || j == 16 ? SZ_KV : 0;
            if (j < 16) kv(2 * SZ_KV - tv, &P.k[blk], c3);
            else if (op & P_GATE) gate();
            if (j > 0) kv(tv, &P.v[blk], c3 - 8);
            else if (op & F_PARK) {
              gate();
              acquire(SZ_PARK);
              if (elect()) {
                mbar_expect(bar, SZ_PARK);
                bulk_load_hint(dst, &P.g->tile[(((op >> 20) & 511) * 2 + rank) * 3072], SZ_PARK, bar, pol);
              }
            }
          }
        } else {
          const uint4* part = &P.g->part[((((op >> 6) & 30) + ((op >> 21) & 1)) * 2 + rank) * 5120 + ((op >> 20) & 1) * 2560];
          auto run = [&](const uint32_t bytes, int k, int cnt, int gates) {
            const int col = bytes == SZ_O || bytes == SZ_OL ? 5 * ((op >> 20) & 3) : 5 * ((op >> 21) & 1);
            int row = 8 * k + 4 * rank, pre = bytes == SZ_O && (op & P_PRE) ? 0 : 2560;
#pragma unroll 1
            for (int h = (k * 43) >> 7, k0 = k - 3 * h; cnt > 0; h++, k0 = 0, gates = gates >> 1 | (gates & 2)) {
              const uint4* src = ptr_add(P.g->tile, ((P.slot[((op >> 2) & 480) + h] * 2 + rank) * 3 + k0) * 16384);
              const uint64_t pw = h >= ((op >> 23) & 31) && h < 2 * (op >> 28) ? pol : no_hint();
              if (gates & 1) gate();
              int m = min(3 - k0, cnt);
              cnt -= m;
#pragma unroll 1
              for (; m > 0; m--, src += 1024, row += 8) {
                acquire(bytes);
                if (elect()) {
                  mbar_expect(bar, bytes);
                  if (bytes == SZ_O || bytes == SZ_OL) tma5d_mc_hint(dst + 16384 + rank * 10240, &P.wo[blk], bar, row, col, no_hint());
                  if (bytes == SZ_W || bytes == SZ_W3) tma5d_mc_hint(dst + 16384 + rank * 12288, &P.wo3[blk], bar, row, col, pw);
                  bulk_load_hint(dst, src, 16384, bar, pol);
                  if (bytes == SZ_W || bytes == SZ_W2) tma5d_mc_hint(dst + bytes - 16384 + rank * 8192, &P.wo2[blk], bar, row, col + 3, pw);
                  if (bytes == SZ_OL) bulk_load_hint(dst + SZ_O, part, 8192, bar, pol);
                }
                if (bytes == SZ_OL) part += 512;
              }
              if (pre < 2560) {
                if (elect()) asm volatile("cp.async.bulk.prefetch.L2.global [%0], 10240;" ::"l"(part + pre) : "memory");
                pre += 640;
              }
            }
          };
          const int n = (op >> 13) & 127;
          if (op & P_WIDE) {
            run(SZ_W, 0, n - TAIL, 3);
            run(SZ_W2, n - TAIL, TAIL, (n - TAIL) % 3 ? 2 : 3);
            run(SZ_W3, n - TAIL, TAIL, 0);
          } else {
            if (op & P_PRE) gate();
            run(SZ_O, kSteps - n, (op & P_LD) ? n - 5 : n, 3);
            if (op & P_LD) {
              if (!(op & P_PRE)) gate();
              run(SZ_OL, kSteps - 5, 5, 2);
            }
          }
        }
      }
#pragma unroll 1
      while (sh) retire();
    } else if (threadIdx.x == 288) {
      for (int pc = 0;; pc++) {
        const uint32_t op = prog[pc];
        const int type = op & 3;
        if (type == OP_END) break;
        if (type == OP_Q ? !(op & F_PARK) : type == OP_O && !(op & P_WIDE)) continue;
        const int id = type == OP_A ? (op >> 2) & 511 : type == OP_Q ? N_TILE + ((op >> 13) & 127) : ID_PART + ((op >> 5) & 60) + ((op >> 20) & 3);
        const uint32_t v = type == OP_O ? 1 : P.info[id] & 7;
        mbar_wait_long(odone0 + 8 * pc);
        flag_set(flag + 2 * id, v);
        if (type == OP_O && (op & P_WIDE)) flag_set(flag + 2 * id + 2, v);
      }
    } else if (wid == 10) {
      int i = threadIdx.x & 31;
      const int n_ev = P.prog[role].n_ev;
      auto event = [&]() { return i < n_ev ? P.prog[role].ev[i] : n_ev ? E_JOB | (i - n_ev) : 0; };
      uint32_t e = i < 8 ? event() : 0;
      for (uint32_t n = 0; __any_sync(0xffffffffu, e); n++) {
        uint32_t job = lds32(jobw);
        const int togo = (e & E_DRAW) ? (e & 1023) - (lds32(progress) >> 3) : 99;
        if (togo <= 0 && rank == 0) {
          job = P.job[atomicInc(&P.g->ticket, gridDim.x / 2 - 1)];
          asm volatile("{\n.reg .u32 a;\nmapa.shared::cluster.u32 a, %0, 1;\nst.volatile.shared::cluster.u32 [a], %1;\n"
                       "st.volatile.shared.u32 [%0], %1;\n}\n" ::"r"(jobw), "r"(job) : "memory");
        }
        if ((e & E_JOB) && job) {
          const uint32_t j = e & 63, heads = job == OP_O ? 0 : kH - ((job >> 2) & 31), jp = !(job & P_LD) ? 63 : (job & P_PRE) ? 0 : heads - 1, h = j - (j > jp);
          e = j == jp ? (ID_PART + ((job >> 5) & 60) + ((job >> 20) & 3)) | E_ON | E_LAST : h < heads ? (((job >> 2) & 511) + h) | E_ON | E_LAST : 0;
        }
        unsigned int* f = ptr_add(flag, 8 * (e & 1023));
        const bool ok = (e & E_ON) ? flag_get(f) - 1 < ((e & E_FREE) ? 1 : 7) : (e & E_DRAW) && job;
        if (ok) {
          mbar_arrive(ev0 + 8 * i);
          if (e & (E_FREE | E_LAST)) flag_dec(f);
          i += 8;
          e = event();
        }
        asm volatile("{\n.reg .pred p;\nsetp.ge.u32 p, %0, 0x400000;\n@p trap;\n}\n" ::"r"(n));
        if (!__any_sync(0xffffffffu, ok)) __nanosleep(__any_sync(0xffffffffu, job || togo <= 2) ? 100 : 600);
      }
    } else if (threadIdx.x == 352) {
      uint32_t items = 0;
      auto read = [&](int id) {
        if (!(P.info[id] & I_NEXT)) return;
        wait_word(progress, 8 * items);
        flag_dec(flag + 2 * id);
      };
      for (int pc = 0;; pc++) {
        const uint32_t op = prog[pc];
        const int type = op & 3;
        if (type == OP_END) break;
        if (type == OP_O) {
          const uint32_t n = (op >> 13) & 127, base = items;
#pragma unroll 1
          for (uint32_t k = 3, id = (op >> 2) & 511; k <= n; k += 3, id++) {
            items = base + k + (k + TAIL > n ? TAIL : 0);
            read(id);
          }
          items = base + n + TAIL;
        } else if (type == OP_A) {
          items++;
          if (op & F_PARK) { items++; read(N_TILE + ((op >> 13) & 127)); }
          items += 31;
        } else {
          items += 10;
        }
      }
    }
    __syncwarp();
    asm volatile("barrier.cluster.arrive.relaxed;\nbarrier.cluster.wait;" ::: "memory");
  }
}

typedef CUresult (*EncodeFn)(CUtensorMap*, CUtensorMapDataType, cuuint32_t, void*, const cuuint64_t*, const cuuint64_t*,
                             const cuuint32_t*, const cuuint32_t*, CUtensorMapInterleave, CUtensorMapSwizzle,
                             CUtensorMapL2promotion, CUtensorMapFloatOOBfill);

void encode(EncodeFn fn, CUtensorMap* m, const void* ptr, int rank, const cuuint64_t* dims, const cuuint64_t* strides,
            const cuuint32_t* box, CUtensorMapSwizzle swz) {
  const cuuint32_t es[5] = {1, 1, 1, 1, 1};
  CUresult r = fn(m, CU_TENSOR_MAP_DATA_TYPE_BFLOAT16, rank, const_cast<void*>(ptr), dims, strides, box, es,
                  CU_TENSOR_MAP_INTERLEAVE_NONE, swz, CU_TENSOR_MAP_L2_PROMOTION_L2_128B, CU_TENSOR_MAP_FLOAT_OOB_FILL_NONE);
  if (r != CUDA_SUCCESS) fprintf(stderr, "cuTensorMapEncodeTiled failed: %d\n", (int)r);
}

struct Op { int type, flags, id, n, quarter, park, item0, items; double t0, t1; };
struct Use { double ready, gate, need, freed; int readers, slot, prev; bool next; };
struct PlanStats { double end, slack, park_slack; int slots, parks; uint32_t own[N_CL]; };

bool plan(const char* const* text, int n_pair, int phase, Params& P, PlanStats* stats = nullptr) {
  constexpr double T_Q = 7900, T_A = 24800, T_U = 25900, T_P = 8400, T_O = 640, T_RUN = 800, T_WIDE = 1300, AHEAD = 3500, PUBLISH = 1500;
  const double margin = 256.0 * ((P.dbg >> 8) & 255);
  static Op op[N_CL][MAX_OPS];
  static Use use[ID_PART];
  int n_op[N_CL], covered[2 * N_TEAM] = {};
  struct Ref { double t; Op* o; int id; };
  static Ref att[N_TILE + 1], dem[N_TILE], prk[MAX_PARK + 1], unp[MAX_PARK + 1], wr[ID_PART];
  auto sort = [](Ref* r, int n) {
    for (int i = 1; i < n; i++)
      for (int j = i; j > 0 && r[j].t < r[j - 1].t; j--) { Ref x = r[j]; r[j] = r[j - 1]; r[j - 1] = x; }
  };
  auto hex = [](char c) { return c <= '9' ? c - '0' : c - 'a' + 10; };
  for (int i = 0; i < n_pair; i++)
    for (const char* s = text[i]; *s; s++)
      for (int h = 0; *s == 'J' && h < 2; h++) {
        if (covered[2 * hex(s[1]) + h]) return false;
        covered[2 * hex(s[1]) + h] = 10 * (s[2 + 2 * h] - '0') + s[3 + 2 * h] - '0';
      }
  for (int c = 0; c < 2 * n_pair; c++) {
    int n = 0, items = 0;
    double t = 0;
    auto add = [&](int type, int flags, int id, int heads, int quarter, int its, double dt) {
      if (n < MAX_OPS) op[c][n] = {type, flags, id, heads, quarter, 0, items, its, t, t + dt};
      n++; items += its; t += dt;
    };
    for (const char* s = text[c >> 1]; *s; s++) {
      const int tm = hex(s[1]) & 15, nj = covered[2 * tm + (c & 1)];
      if (*s == 'N') { add(OP_Q, 0, 0, 0, 0, 10, T_Q); add(OP_A, 0, 0, 0, 0, 32, T_A); }
      if (*s == 'P') add(OP_Q, F_PARK, 0, 0, 0, 10, T_P);
      if (*s == '+' || *s == '-') t += *s == '+' ? 1000 : -1000;
      if (*s == 'U') { if (n == 0 || n > MAX_OPS || op[c][n - 1].type != OP_A) return false; add(OP_A, F_PARK, 0, 0, 0, 33, T_U); }
      if (*s == 'J') { if (nj < TAIL + 6 || nj > kSteps - 11) return false; add(OP_O, P_WIDE, tm * kH, nj, 2 * (c & 1), nj + TAIL, 2 * T_O * nj + T_WIDE); }
    }
    add(OP_O, 0, 0, 0, 0, 0, 0);
    add(OP_END, 0, 0, 0, 0, 0, 0);
    if (n > MAX_OPS || op[c][0].type != OP_Q) return false;
    n_op[c] = n - 1;
    att[c] = {t, &op[c][n - 2], 0};
  }
  for (int i = 0; i < 4 * N_TEAM; i++) dem[i] = {(double)covered[i / 2], nullptr, i};
  sort(att, 2 * n_pair); sort(dem, 4 * N_TEAM);
  for (int i = 0; i < 4 * N_TEAM; i++) {
    Op* f = att[i].o;
    const int nj = covered[dem[i].id / 2];
    f->flags = nj ? P_LD : 0;
    f->id = dem[i].id / 4 * kH + nj / 3; f->quarter = dem[i].id & 3; f->items = f->n = kSteps - nj;
    f[1].t0 = f[1].t1 = f->t1 = f->t0 + T_O * f->n + T_RUN; f[1].item0 += f->n;
  }
  for (int i = 0; i < ID_PART; i++) use[i] = {0, 0, 1e18, 0, 0, 0, 0, false};
  int n_att = 0, n_prk = 0, n_unp = 0;
  auto ready = [&](const Op* o) {
    const int nt = o[1].type;
    return o->t1 + (nt == OP_Q ? 6100 : o[1].n ? ((o[1].flags & P_WIDE) ? 7700 : 3900) : 1500) + PUBLISH;
  };
  for (int c = 0; c < 2 * n_pair; c++)
    for (Op* o = op[c]; o->type != OP_END; o++) {
      if (o->type == OP_A) { att[n_att] = {ready(o), o, 0}; if (++n_att > N_TILE) return false; }
      if (o->type == OP_A && o->flags) { unp[n_unp] = {o->t0 - AHEAD, o, 0}; if (++n_unp > MAX_PARK) return false; }
      if (o->type == OP_Q && o->flags) { prk[n_prk] = {ready(o), o, 0}; if (++n_prk > MAX_PARK) return false; }
      for (int i = 0; o->type == OP_O && i < o->n; i++) {
        const int nw = (o->flags & P_WIDE) ? o->n - TAIL : 0, k = nw ? i : kSteps - o->n + i;
        Use& u = use[o->id / kH * kH + k / 3];
        const double t = o->t0 + T_O * (i + (i < nw ? i : nw));
        if (t - AHEAD < u.need) u.need = t - AHEAD;
        const double f = !nw ? 1e18 : i + FLIGHT < o->items - TAIL || (nw && o[1].type != OP_O) ? t + T_O * (i < nw ? 2 : 1 + TAIL) + PUBLISH : 1e18;
        if (f > u.freed) u.freed = f;
        if (i == 0 || k % 3 == 0) u.readers++;
      }
    }
  if (n_att != N_TILE || n_prk != n_unp) return false;
  for (int i = 0; i < N_TILE; i++) { const int id = (i & 15) * kH + (i >> 4); dem[i] = {use[id].need, nullptr, id}; }
  sort(att, n_att); sort(dem, N_TILE); sort(prk, n_prk); sort(unp, n_unp);
  PlanStats st = {0, 1e18, 1e18, 0, n_prk};
  int n_wr = 0;
  for (int i = 0; i < N_TILE; i++) {
    Op* o = att[i].o;
    o->id = dem[i].id;
    if (!o->flags) o[-1].id = o->id;
    if (dem[i].t - att[i].t < st.slack) st.slack = dem[i].t - att[i].t;
    wr[n_wr++] = {o->t1 - 2 * AHEAD, o, o->id};
  }
  for (int i = 0; i < n_prk; i++) {
    prk[i].o->id = unp[i].o->id;
    prk[i].o->park = unp[i].o->park = i;
    use[N_TILE + i].freed = unp[i].o->t0 + 2 * PUBLISH;
    use[N_TILE + i].readers = 1;
    if (unp[i].t - prk[i].t < st.park_slack) st.park_slack = unp[i].t - prk[i].t;
    wr[n_wr++] = {prk[i].o->t1 - 2 * AHEAD, prk[i].o, N_TILE + i};
  }
  for (int c = 0; c < 2 * n_pair; c++)
    for (int d = 0; d < 2 * n_pair; d++)
      for (Op *f = &op[c][n_op[c] - 1], *o = op[d]; f->n && o->type != OP_END; o++)
        if (o->type == OP_O && (o->flags & P_WIDE) && o->id / kH == f->id / kH && o->quarter / 2 == f->quarter / 2) {
          if (f->t0 - o->t1 > 4096.0 * ((P.dbg >> 16) & 255)) f->flags |= P_PRE;
          const double slack = f->t0 + ((f->flags & P_PRE) ? 0 : (f->n - 5) * T_O) - AHEAD - ready(o);
          if (slack < st.park_slack) st.park_slack = slack;
        }
  constexpr double long_while = 160000;
  for (int c = 0; c < 2 * n_pair; c++)
    for (Op* o = op[c]; o->type != OP_END; o++) {
      if (o->type == OP_O && (o->flags & P_WIDE)) {
        int run = 0, best = 0, end = 0;
        for (int h = 0; 3 * h < o->n; h++) {
          bool last = true;
          for (int d = 0; d < 2 * n_pair; d++)
            for (const Op* e = op[d]; e->type != OP_END; e++) {
              if (e->type != OP_O || e == o || ((e->id ^ o->id) & 256) || e->quarter / 2 != o->quarter / 2) continue;
              const bool wide = e->flags & P_WIDE;
              if (wide ? 3 * h >= e->n : 3 * h + 3 <= kSteps - e->n) continue;
              const double dt = e->t0 + T_O * (wide ? 6 * h : 3 * h - kSteps + e->n) - o->t0 - T_O * 6 * h + (d - c) * 1e-3;
              if (dt > 0 && dt < long_while) last = false;
            }
          run = last ? run + 1 : 0;
          if (run > best) { best = run; end = h + 1; }
        }
        if (3 * end >= o->n) end++;
        o->park = (end - best) | (end / 2) << 5;
      }
      if (o->type != OP_Q) continue;
      bool lw = true, lx = true;
      for (int d = 0; d < 2 * n_pair; d++)
        for (const Op* e = op[d]; e->type != OP_END; e++) {
          const double dt = e->t0 - o->t0 + (d - c) * 1e-3;
          if (e->type != OP_Q || e == o || dt < 0 || dt > long_while) continue;
          if (((e->id ^ o->id) & (256 + 31)) == 0) lw = false;
          if (e->id / kH == o->id / kH) lx = false;
        }
      o->quarter = (lw ? P_LASTW : 0) | (lx ? P_LASTX : 0);
    }
  sort(wr, n_wr);
  int holder[N_TILE];
  for (int i = 0; i < n_wr; i++) {
    int best = -1;
    for (int sl = 0; sl < st.slots; sl++)
      if (use[holder[sl]].freed + margin <= wr[i].t && (best < 0 || use[holder[sl]].freed < use[holder[best]].freed)) best = sl;
    Use& u = use[wr[i].id];
    if (best >= 0) { u.prev = holder[best]; use[u.prev].next = true; wr[i].o->flags |= P_GATE; }
    else if (st.slots == N_TILE) return false;
    else best = st.slots++;
    u.slot = best;
    holder[best] = wr[i].id;
  }
  {
    int pos[N_CL] = {}, flag[ID_PART + 4 * N_TEAM] = {}, seen[ID_PART] = {};
    auto goal = [&](int c) { return op[c][n_op[c] - 1].item0; };
    for (bool moved = true; moved;) {
      moved = false;
      for (int c = 0; c < 2 * n_pair; c++) {
        for (; pos[c] < goal(c); pos[c]++, moved = true) {
          bool ok = true;
          for (const Op* o = op[c]; o->type != OP_END; o++) {
            const int k = pos[c] - o->item0, own = o->type == OP_A ? o->id : N_TILE + (o->park & 127);
            if (k < 0 || k >= o->items) continue;
            if (o->type == OP_O) ok = k >= o->n || flag[o->id + k / 3];
            else if (k == o->items - 1 && (o->flags & P_GATE)) ok = seen[use[own].prev] == use[use[own].prev].readers;
            else if (k == 1 && o->type == OP_A && (o->flags & F_PARK)) ok = flag[N_TILE + o->park];
          }
          if (!ok) break;
          for (const Op* o = op[c]; o->type != OP_END; o++) {
            if (pos[c] == o->item0 + o->items + (o[1].type == OP_Q ? 7 : o[1].item0 == goal(c) ? -1 : 5)) {
              if (o->type == OP_A) flag[o->id] = 1;
              if (o->type == OP_Q && (o->flags & F_PARK)) flag[N_TILE + o->park] = 1;
              if (o->type == OP_O) flag[ID_PART + o->id / kH * 4 + o->quarter] = flag[ID_PART + o->id / kH * 4 + o->quarter + 1] = 1;
            }
            const int k = pos[c] - FLIGHT - o->item0, nw = o->n - TAIL;
            if (k == 1 && o->type == OP_A && (o->flags & F_PARK)) seen[N_TILE + o->park]++;
            if (o->type == OP_O && k >= 0 && k < o->items && (k < nw || k >= o->n) && (k < nw ? k : k - TAIL) % 3 == 2) seen[o->id + (k < nw ? k : k - TAIL) / 3]++;
          }
        }
      }
    }
    for (int c = 0; c < 2 * n_pair; c++) if (pos[c] < goal(c)) return false;
  }
  int n_job = 0, longest = 0;
  for (int i = 0; i < 2 * N_TEAM; i++) if (kH + 1 - covered[i] / 3 > longest) longest = kH + 1 - covered[i] / 3;
  for (int c = 0; c < 2 * n_pair; c++) {
    uint32_t items = 0, cur = 0, pend = 0;
    int n = 0, ev = 0;
    auto item = [&](uint32_t bytes, int count) {
      for (int i = 0; i < count; i++) { if (cur + bytes > RING) cur = 0; cur += bytes; items++; }
    };
    auto event = [&](uint32_t e) { if (ev < MAX_TAB) P.prog[c].ev[ev] = e; ev++; };
    for (const Op* o = op[c];; o++) {
      if (o->type != OP_END && phase && (o->type == OP_O) != (phase == 2)) continue;
      uint32_t cw = o->type | (items % (2 * NBAR)) << 15 | (cur >> 12) << 20 | pend, pw = o->type | o->id << 2 | o->flags;
      const int ps = use[N_TILE + (o->park & 127)].slot;
      pend = 0;
      if (o->type == OP_O) {
        pw |= o->n << 13 | o->quarter << 20 | (uint32_t)o->park << 23;
        if (o->flags & P_WIDE) {
          cw |= o->n << 2 | (o->id / kH * 2 + o->quarter / 2) << 9 | C_WIDE;
          item(SZ_W, o->n - TAIL);
          item(SZ_W2, TAIL);
          item(SZ_W3, TAIL);
          pend = C_PEND;
          for (int i = 0; 3 * i < o->n; i++) event((o->id + i) | E_ON | (use[o->id + i].next ? 0 : E_LAST));
        } else {
          dem[n_job++] = {o->t0 - 1e6 * o->n, nullptr, (int)pw};
          st.own[c] = pw;
          pw = OP_O;
          event(E_DRAW | (items < 16 ? 0 : items - 16));
        }
      } else if (o->type != OP_END) {
        const bool parks = o->type == OP_Q && (o->flags & F_PARK);
        cw |= (parks ? ps : use[o->id].slot) << 2 | (o->flags & F_PARK);
        if (o->flags & F_PARK) pw |= o->park << 13 | ps << 20;
        if (o->type == OP_Q) { item(SZ_Q, 10); pw |= o->quarter; }
        else { item(SZ_KV, 1); if (o->flags & F_PARK) { item(SZ_PARK, 1); event((N_TILE + o->park) | E_ON | (use[N_TILE + o->park].next ? 0 : E_LAST)); } item(SZ_KV, 31); }
        if (parks || o->type == OP_A) pend = C_PEND;
        if (o->flags & P_GATE) event(use[parks ? N_TILE + o->park : o->id].prev | E_ON | E_FREE);
      }
      P.prog[c].c[n] = cw; P.prog[c].p[n++] = pw;
      if (o->type == OP_END) { if (o->t0 > st.end) st.end = o->t0; break; }
    }
    if (ev > MAX_TAB || ev + longest > MAX_EV) return false;
    P.prog[c].n_ev = ev;
    while (n < MAX_OPS) { P.prog[c].c[n] = OP_END; P.prog[c].p[n++] = OP_END; }
    P.first[c] = (uint16_t)(P.prog[c].p[0] & 2047);
  }
  sort(dem, n_job);
  for (int i = 0; i < n_job; i++) P.job[i] = dem[i].id;
  for (int i = 0; i < ID_PART; i++) {
    if (i < N_TILE) P.slot[i] = use[i].slot;
    P.info[i] = (use[i].readers + use[i].next) | (use[i].next ? I_NEXT : 0);
  }
  if (stats) *stats = st;
  return true;
}

const char* const kPrograms[N_CL / 2] = {
  "PNJ06864NNNNN", "PNJ17878NNNNN", "PNJ26464NNNNN", "PNJ34148NNNNNN", "PNJ46262NNNNN", "PNJ58182NNNN",
  "NNJ67371NNNN", "PNNJ76666NNNN", "NUNNNJ84545NN", "NUNNNJ94545NN", "NUNNNNJa5551N", "NNNNNJb5959NN",
  "NNNNNJc5455NN", "PNNNNNJd5353NN", "NNNNNJe5153NN", "NNNNNJf7777N", "PNNNNNNNNN", "PNNNNNNNNN",
  "PNNNNNNNNN", "PNNNNNNNNN", "NNNNNNNNN", "NNNNNNNNN", "NNNNNNNNN", "NNNNNNNNN",
  "NNNNNNNNN", "N-NNNNNNNN", "NUNNNNNNN", "NUNNNNNNN", "NUNNNNNNN", "NUNNNUNNN",
  "NUNNNNNNN", "NUNNNNNNN", "NUUNNNNNN",
};

const char* const* bench_programs() {
  return kPrograms;
}

}

extern "C" void kernel_launch(void* const* d_in, const int* in_sizes, int n_in, void* d_out, int out_size) {
  (void)in_sizes; (void)n_in; (void)out_size;
  static EncodeFn fn = nullptr;
  static int n_clusters = 0;
  if (!fn) {
    cudaDriverEntryPointQueryResult qr;
    void* f = nullptr;
    cudaGetDriverEntryPoint("cuTensorMapEncodeTiled", &f, cudaEnableDefault, &qr);
    fn = (EncodeFn)f;
    cudaFuncSetAttribute(fused_kernel, cudaFuncAttributeMaxDynamicSharedMemorySize, SMEM_BYTES);
    cudaLaunchConfig_t cfg = {};
    cfg.gridDim = dim3(132); cfg.blockDim = dim3(384); cfg.dynamicSmemBytes = SMEM_BYTES;
    cudaLaunchAttribute at[1];
    at[0].id = cudaLaunchAttributeClusterDimension; at[0].val.clusterDim.x = 2; at[0].val.clusterDim.y = 1; at[0].val.clusterDim.z = 1;
    cfg.attrs = at; cfg.numAttrs = 1;
    if (cudaOccupancyMaxActiveClusters(&n_clusters, fused_kernel, &cfg) != cudaSuccess || n_clusters < 1) n_clusters = 1;
    (void)cudaGetLastError();
  }
  static Params P;
  const CUtensorMapSwizzle S128 = CU_TENSOR_MAP_SWIZZLE_128B, S64 = CU_TENSOR_MAP_SWIZZLE_64B;
  for (int blk = 0; blk < 2; blk++) {
    void* const* in = d_in + 5 * blk;
    { const cuuint64_t d[] = {kD, kB * kSq}, s[] = {kD * 2}; const cuuint32_t b[] = {64, 128};
      encode(fn, &P.x[blk], in[0], 2, d, s, b, S128); }
    { const cuuint64_t d[] = {64, 8, 3, (cuuint64_t)kB * kH * kSk / 8}, s[] = {kDh * 2, 128, 8 * kDh * 2}; const cuuint32_t b[] = {64, 8, 3, 4};
      encode(fn, &P.k[blk], in[1], 4, d, s, b, S128);
      encode(fn, &P.v[blk], in[2], 4, d, s, b, S128); }
    { const cuuint64_t d[] = {64, kD, kHD / 64}, s[] = {kHD * 2, 128}; const cuuint32_t b[] = {64, 32, 3};
      encode(fn, &P.wq[blk], in[3], 3, d, s, b, S128); }
    { const cuuint64_t d[] = {32, 2, kHD / 8, 4, kD / 32}, s[] = {kD * 2, 8 * kD * 2, 2 * kD * 2, 64}; const cuuint32_t b[] = {32, 2, 4, 4, 5};
      encode(fn, &P.wo[blk], in[4], 5, d, s, b, S64); }
    { const cuuint64_t d[] = {64, 2, kHD / 8, 4, kD / 64}, s[] = {kD * 2, 8 * kD * 2, 2 * kD * 2, 128};
      const cuuint32_t b3[] = {64, 2, 4, 4, 3}, b2[] = {64, 2, 4, 4, 2};
      encode(fn, &P.wo3[blk], in[4], 5, d, s, b3, S128);
      encode(fn, &P.wo2[blk], in[4], 5, d, s, b2, S128); }
  }
  { const cuuint64_t d[] = {32, kB * kSq, 2 * kD / 32}, s[] = {2 * kD * 2, 64}; const cuuint32_t b[] = {32, 16, 1};
    encode(fn, &P.out, d_out, 3, d, s, b, S64); }

  P.kv[0] = (const char*)d_in[1]; P.kv[1] = (const char*)d_in[6]; P.kv[2] = (const char*)d_in[2]; P.kv[3] = (const char*)d_in[7];
  P.xw[0] = (const char*)d_in[0]; P.xw[1] = (const char*)d_in[3];
  cudaGetSymbolAddress((void**)&P.g, g_scratch);
  P.dbg = DBG_DEFAULT;
  if (n_clusters >= N_CL && plan(bench_programs(), N_CL / 2, 0, P)) {
    fused_kernel<<<2 * N_CL, 384, SMEM_BYTES>>>(P);
  } else {
    const char* text[2 * N_TEAM];
    for (int i = 0; i < 2 * N_TEAM; i++) text[i] = "NNNNNNNN";
    for (int phase = 1; phase <= 2; phase++) {
      plan(text, 2 * N_TEAM, phase, P);
      fused_kernel<<<8 * N_TEAM, 384, SMEM_BYTES>>>(P);
    }
  }
}
```

```cpp
#include <cuda_runtime.h>
#include <cuda_bf16.h>
#include <cuda.h>
#include <cuda/annotated_ptr>
#include <stdint.h>
#include <stdio.h>

namespace {

constexpr int kB = 8, kSq = 256, kD = 640, kH = 32, kSk = 1024, kDh = 192;
constexpr int kHD = kH * kDh;
constexpr uint32_t RING = 224 * 1024;
constexpr uint32_t SZ_KV = 24576;
constexpr uint32_t SZ_Q = 16384 + 24576;
constexpr uint32_t SZ_O = 16384 + 20480;
constexpr uint32_t SZ_W3 = 16384 + 24576, SZ_W2 = 16384 + 16384, SZ_W = SZ_W3 + 16384;
constexpr uint32_t SZ_PARK = 49152;
constexpr uint32_t SZ_OL = SZ_O + 8192;
constexpr int NBAR = 16, FLIGHT = RING / SZ_KV + 1;
constexpr int EARLY = 3;
constexpr int kSteps = kHD / 64;
constexpr int TAIL = 4;
constexpr uint32_t KV_CH = 64, KV_SBO = 3072;
constexpr int SMEM_BYTES = RING + 1024 + 1024;
constexpr int N_TEAM = 16, N_CL = 66, MAX_OPS = 22, MAX_EV = 72, MAX_TAB = 47, N_TILE = N_TEAM * kH, MAX_PARK = 128, ID_PART = N_TILE + MAX_PARK;
enum : uint32_t { OP_END = 0, OP_Q = 1, OP_A = 2, OP_O = 3, F_PARK = 1 << 11,
                  C_WIDE = 1 << 27, C_PEND = 1 << 26, P_GATE = 1 << 12, P_WIDE = 1 << 11, P_LD = 1 << 12, P_PRE = 1 << 22, P_LASTW = 1 << 29, P_LASTX = 1 << 30,
                  I_NEXT = 8, E_ON = 1 << 15, E_FREE = 1 << 14, E_LAST = 1 << 13, E_DRAW = 1 << 12, E_JOB = 1 << 11 };

#define XTA 24800
constexpr uint32_t DBG_DEFAULT = 0x040800;

struct alignas(1024) Scratch {
  unsigned int flag[2047];
  unsigned int ticket;
  uint4 part[N_TEAM * 2 * 2 * 5120];
  uint4 tile[N_TILE * 2 * 3072];
};

struct alignas(64) Params {
  const char* xw[2];
  uint16_t first[80];
  Scratch* g;
  uint32_t dbg;
  CUtensorMap x[2], wq[2], k[2], v[2], wo[2], wo3[2], wo2[2], out;
  struct {
    uint32_t c[MAX_OPS];
    uint32_t p[MAX_OPS];
    uint16_t n_ev, ev[MAX_TAB];
  } prog[N_CL];
  const char* kv[4];
  uint32_t job[N_CL];
  uint16_t slot[N_TILE];
  uint8_t info[ID_PART];
};

__device__ Scratch g_scratch;

template <int TB, int TA = 0>
__device__ __forceinline__ void wgmma_ss_n64(float (&d)[32], uint64_t da, uint64_t db, int scale_d) {
  asm volatile("{\n.reg .pred p;\nsetp.ne.b32 p, %34, 0;\n"
    "wgmma.mma_async.sync.aligned.m64n64k16.f32.bf16.bf16 {%0, %1, %2, %3, %4, %5, %6, %7, %8, %9, %10, %11, %12, %13, %14, %15, %16, %17, %18, %19, %20, %21, %22, %23, %24, %25, %26, %27, %28, %29, %30, %31}, %32, %33, p, 1, 1, %35, %36;\n}\n"
    : "+f"(d[0]), "+f"(d[1]), "+f"(d[2]), "+f"(d[3]), "+f"(d[4]), "+f"(d[5]), "+f"(d[6]), "+f"(d[7]), "+f"(d[8]), "+f"(d[9]), "+f"(d[10]), "+f"(d[11]), "+f"(d[12]), "+f"(d[13]), "+f"(d[14]), "+f"(d[15]), "+f"(d[16]), "+f"(d[17]), "+f"(d[18]), "+f"(d[19]), "+f"(d[20]), "+f"(d[21]), "+f"(d[22]), "+f"(d[23]), "+f"(d[24]), "+f"(d[25]), "+f"(d[26]), "+f"(d[27]), "+f"(d[28]), "+f"(d[29]), "+f"(d[30]), "+f"(d[31])
    : "l"(da), "l"(db), "r"(scale_d), "n"(TA), "n"(TB));
}
template <int TB>
__device__ __forceinline__ void wgmma_rs_n64(float (&d)[32], uint32_t a0, uint32_t a1, uint32_t a2, uint32_t a3, uint64_t db, int scale_d) {
  asm volatile("{\n.reg .pred p;\nsetp.ne.b32 p, %37, 0;\n"
    "wgmma.mma_async.sync.aligned.m64n64k16.f32.bf16.bf16 {%0, %1, %2, %3, %4, %5, %6, %7, %8, %9, %10, %11, %12, %13, %14, %15, %16, %17, %18, %19, %20, %21, %22, %23, %24, %25, %26, %27, %28, %29, %30, %31}, {%32, %33, %34, %35}, %36, p, 1, 1, %38;\n}\n"
    : "+f"(d[0]), "+f"(d[1]), "+f"(d[2]), "+f"(d[3]), "+f"(d[4]), "+f"(d[5]), "+f"(d[6]), "+f"(d[7]), "+f"(d[8]), "+f"(d[9]), "+f"(d[10]), "+f"(d[11]), "+f"(d[12]), "+f"(d[13]), "+f"(d[14]), "+f"(d[15]), "+f"(d[16]), "+f"(d[17]), "+f"(d[18]), "+f"(d[19]), "+f"(d[20]), "+f"(d[21]), "+f"(d[22]), "+f"(d[23]), "+f"(d[24]), "+f"(d[25]), "+f"(d[26]), "+f"(d[27]), "+f"(d[28]), "+f"(d[29]), "+f"(d[30]), "+f"(d[31])
    : "r"(a0), "r"(a1), "r"(a2), "r"(a3), "l"(db), "r"(scale_d), "n"(TB));
}
template <int TB, int TA = 0>
__device__ __forceinline__ void wgmma_ss_n128(float (&d)[64], uint64_t da, uint64_t db, int scale_d) {
  asm volatile("{\n.reg .pred p;\nsetp.ne.b32 p, %66, 0;\n"
    "wgmma.mma_async.sync.aligned.m64n128k16.f32.bf16.bf16 {%0, %1, %2, %3, %4, %5, %6, %7, %8, %9, %10, %11, %12, %13, %14, %15, %16, %17, %18, %19, %20, %21, %22, %23, %24, %25, %26, %27, %28, %29, %30, %31, %32, %33, %34, %35, %36, %37, %38, %39, %40, %41, %42, %43, %44, %45, %46, %47, %48, %49, %50, %51, %52, %53, %54, %55, %56, %57, %58, %59, %60, %61, %62, %63}, %64, %65, p, 1, 1, %67, %68;\n}\n"
    : "+f"(d[0]), "+f"(d[1]), "+f"(d[2]), "+f"(d[3]), "+f"(d[4]), "+f"(d[5]), "+f"(d[6]), "+f"(d[7]), "+f"(d[8]), "+f"(d[9]), "+f"(d[10]), "+f"(d[11]), "+f"(d[12]), "+f"(d[13]), "+f"(d[14]), "+f"(d[15]), "+f"(d[16]), "+f"(d[17]), "+f"(d[18]), "+f"(d[19]), "+f"(d[20]), "+f"(d[21]), "+f"(d[22]), "+f"(d[23]), "+f"(d[24]), "+f"(d[25]), "+f"(d[26]), "+f"(d[27]), "+f"(d[28]), "+f"(d[29]), "+f"(d[30]), "+f"(d[31]), "+f"(d[32]), "+f"(d[33]), "+f"(d[34]), "+f"(d[35]), "+f"(d[36]), "+f"(d[37]), "+f"(d[38]), "+f"(d[39]), "+f"(d[40]), "+f"(d[41]), "+f"(d[42]), "+f"(d[43]), "+f"(d[44]), "+f"(d[45]), "+f"(d[46]), "+f"(d[47]), "+f"(d[48]), "+f"(d[49]), "+f"(d[50]), "+f"(d[51]), "+f"(d[52]), "+f"(d[53]), "+f"(d[54]), "+f"(d[55]), "+f"(d[56]), "+f"(d[57]), "+f"(d[58]), "+f"(d[59]), "+f"(d[60]), "+f"(d[61]), "+f"(d[62]), "+f"(d[63])
    : "l"(da), "l"(db), "r"(scale_d), "n"(TA), "n"(TB));
}
template <int TB>
__device__ __forceinline__ void wgmma_rs_n128(float (&d)[64], uint32_t a0, uint32_t a1, uint32_t a2, uint32_t a3, uint64_t db, int scale_d) {
  asm volatile("{\n.reg .pred p;\nsetp.ne.b32 p, %69, 0;\n"
    "wgmma.mma_async.sync.aligned.m64n128k16.f32.bf16.bf16 {%0, %1, %2, %3, %4, %5, %6, %7, %8, %9, %10, %11, %12, %13, %14, %15, %16, %17, %18, %19, %20, %21, %22, %23, %24, %25, %26, %27, %28, %29, %30, %31, %32, %33, %34, %35, %36, %37, %38, %39, %40, %41, %42, %43, %44, %45, %46, %47, %48, %49, %50, %51, %52, %53, %54, %55, %56, %57, %58, %59, %60, %61, %62, %63}, {%64, %65, %66, %67}, %68, p, 1, 1, %70;\n}\n"
    : "+f"(d[0]), "+f"(d[1]), "+f"(d[2]), "+f"(d[3]), "+f"(d[4]), "+f"(d[5]), "+f"(d[6]), "+f"(d[7]), "+f"(d[8]), "+f"(d[9]), "+f"(d[10]), "+f"(d[11]), "+f"(d[12]), "+f"(d[13]), "+f"(d[14]), "+f"(d[15]), "+f"(d[16]), "+f"(d[17]), "+f"(d[18]), "+f"(d[19]), "+f"(d[20]), "+f"(d[21]), "+f"(d[22]), "+f"(d[23]), "+f"(d[24]), "+f"(d[25]), "+f"(d[26]), "+f"(d[27]), "+f"(d[28]), "+f"(d[29]), "+f"(d[30]), "+f"(d[31]), "+f"(d[32]), "+f"(d[33]), "+f"(d[34]), "+f"(d[35]), "+f"(d[36]), "+f"(d[37]), "+f"(d[38]), "+f"(d[39]), "+f"(d[40]), "+f"(d[41]), "+f"(d[42]), "+f"(d[43]), "+f"(d[44]), "+f"(d[45]), "+f"(d[46]), "+f"(d[47]), "+f"(d[48]), "+f"(d[49]), "+f"(d[50]), "+f"(d[51]), "+f"(d[52]), "+f"(d[53]), "+f"(d[54]), "+f"(d[55]), "+f"(d[56]), "+f"(d[57]), "+f"(d[58]), "+f"(d[59]), "+f"(d[60]), "+f"(d[61]), "+f"(d[62]), "+f"(d[63])
    : "r"(a0), "r"(a1), "r"(a2), "r"(a3), "l"(db), "r"(scale_d), "n"(TB));
}
template <int TB, int TA = 0>
__device__ __forceinline__ void wgmma_ss_n160(float (&d)[80], uint64_t da, uint64_t db, int scale_d) {
  asm volatile("{\n.reg .pred p;\nsetp.ne.b32 p, %82, 0;\n"
    "wgmma.mma_async.sync.aligned.m64n160k16.f32.bf16.bf16 {%0, %1, %2, %3, %4, %5, %6, %7, %8, %9, %10, %11, %12, %13, %14, %15, %16, %17, %18, %19, %20, %21, %22, %23, %24, %25, %26, %27, %28, %29, %30, %31, %32, %33, %34, %35, %36, %37, %38, %39, %40, %41, %42, %43, %44, %45, %46, %47, %48, %49, %50, %51, %52, %53, %54, %55, %56, %57, %58, %59, %60, %61, %62, %63, %64, %65, %66, %67, %68, %69, %70, %71, %72, %73, %74, %75, %76, %77, %78, %79}, %80, %81, p, 1, 1, %83, %84;\n}\n"
    : "+f"(d[0]), "+f"(d[1]), "+f"(d[2]), "+f"(d[3]), "+f"(d[4]), "+f"(d[5]), "+f"(d[6]), "+f"(d[7]), "+f"(d[8]), "+f"(d[9]), "+f"(d[10]), "+f"(d[11]), "+f"(d[12]), "+f"(d[13]), "+f"(d[14]), "+f"(d[15]), "+f"(d[16]), "+f"(d[17]), "+f"(d[18]), "+f"(d[19]), "+f"(d[20]), "+f"(d[21]), "+f"(d[22]), "+f"(d[23]), "+f"(d[24]), "+f"(d[25]), "+f"(d[26]), "+f"(d[27]), "+f"(d[28]), "+f"(d[29]), "+f"(d[30]), "+f"(d[31]), "+f"(d[32]), "+f"(d[33]), "+f"(d[34]), "+f"(d[35]), "+f"(d[36]), "+f"(d[37]), "+f"(d[38]), "+f"(d[39]), "+f"(d[40]), "+f"(d[41]), "+f"(d[42]), "+f"(d[43]), "+f"(d[44]), "+f"(d[45]), "+f"(d[46]), "+f"(d[47]), "+f"(d[48]), "+f"(d[49]), "+f"(d[50]), "+f"(d[51]), "+f"(d[52]), "+f"(d[53]), "+f"(d[54]), "+f"(d[55]), "+f"(d[56]), "+f"(d[57]), "+f"(d[58]), "+f"(d[59]), "+f"(d[60]), "+f"(d[61]), "+f"(d[62]), "+f"(d[63]), "+f"(d[64]), "+f"(d[65]), "+f"(d[66]), "+f"(d[67]), "+f"(d[68]), "+f"(d[69]), "+f"(d[70]), "+f"(d[71]), "+f"(d[72]), "+f"(d[73]), "+f"(d[74]), "+f"(d[75]), "+f"(d[76]), "+f"(d[77]), "+f"(d[78]), "+f"(d[79])
    : "l"(da), "l"(db), "r"(scale_d), "n"(TA), "n"(TB));
}
template <int TB>
__device__ __forceinline__ void wgmma_rs_n160(float (&d)[80], uint32_t a0, uint32_t a1, uint32_t a2, uint32_t a3, uint64_t db, int scale_d) {
  asm volatile("{\n.reg .pred p;\nsetp.ne.b32 p, %85, 0;\n"
    "wgmma.mma_async.sync.aligned.m64n160k16.f32.bf16.bf16 {%0, %1, %2, %3, %4, %5, %6, %7, %8, %9, %10, %11, %12, %13, %14, %15, %16, %17, %18, %19, %20, %21, %22, %23, %24, %25, %26, %27, %28, %29, %30, %31, %32, %33, %34, %35, %36, %37, %38, %39, %40, %41, %42, %43, %44, %45, %46, %47, %48, %49, %50, %51, %52, %53, %54, %55, %56, %57, %58, %59, %60, %61, %62, %63, %64, %65, %66, %67, %68, %69, %70, %71, %72, %73, %74, %75, %76, %77, %78, %79}, {%80, %81, %82, %83}, %84, p, 1, 1, %86;\n}\n"
    : "+f"(d[0]), "+f"(d[1]), "+f"(d[2]), "+f"(d[3]), "+f"(d[4]), "+f"(d[5]), "+f"(d[6]), "+f"(d[7]), "+f"(d[8]), "+f"(d[9]), "+f"(d[10]), "+f"(d[11]), "+f"(d[12]), "+f"(d[13]), "+f"(d[14]), "+f"(d[15]), "+f"(d[16]), "+f"(d[17]), "+f"(d[18]), "+f"(d[19]), "+f"(d[20]), "+f"(d[21]), "+f"(d[22]), "+f"(d[23]), "+f"(d[24]), "+f"(d[25]), "+f"(d[26]), "+f"(d[27]), "+f"(d[28]), "+f"(d[29]), "+f"(d[30]), "+f"(d[31]), "+f"(d[32]), "+f"(d[33]), "+f"(d[34]), "+f"(d[35]), "+f"(d[36]), "+f"(d[37]), "+f"(d[38]), "+f"(d[39]), "+f"(d[40]), "+f"(d[41]), "+f"(d[42]), "+f"(d[43]), "+f"(d[44]), "+f"(d[45]), "+f"(d[46]), "+f"(d[47]), "+f"(d[48]), "+f"(d[49]), "+f"(d[50]), "+f"(d[51]), "+f"(d[52]), "+f"(d[53]), "+f"(d[54]), "+f"(d[55]), "+f"(d[56]), "+f"(d[57]), "+f"(d[58]), "+f"(d[59]), "+f"(d[60]), "+f"(d[61]), "+f"(d[62]), "+f"(d[63]), "+f"(d[64]), "+f"(d[65]), "+f"(d[66]), "+f"(d[67]), "+f"(d[68]), "+f"(d[69]), "+f"(d[70]), "+f"(d[71]), "+f"(d[72]), "+f"(d[73]), "+f"(d[74]), "+f"(d[75]), "+f"(d[76]), "+f"(d[77]), "+f"(d[78]), "+f"(d[79])
    : "r"(a0), "r"(a1), "r"(a2), "r"(a3), "l"(db), "r"(scale_d), "n"(TB));
}
template <int TB, int TA = 0>
__device__ __forceinline__ void wgmma_ss_n192(float (&d)[96], uint64_t da, uint64_t db, int scale_d) {
  asm volatile("{\n.reg .pred p;\nsetp.ne.b32 p, %98, 0;\n"
    "wgmma.mma_async.sync.aligned.m64n192k16.f32.bf16.bf16 {%0, %1, %2, %3, %4, %5, %6, %7, %8, %9, %10, %11, %12, %13, %14, %15, %16, %17, %18, %19, %20, %21, %22, %23, %24, %25, %26, %27, %28, %29, %30, %31, %32, %33, %34, %35, %36, %37, %38, %39, %40, %41, %42, %43, %44, %45, %46, %47, %48, %49, %50, %51, %52, %53, %54, %55, %56, %57, %58, %59, %60, %61, %62, %63, %64, %65, %66, %67, %68, %69, %70, %71, %72, %73, %74, %75, %76, %77, %78, %79, %80, %81, %82, %83, %84, %85, %86, %87, %88, %89, %90, %91, %92, %93, %94, %95}, %96, %97, p, 1, 1, %99, %100;\n}\n"
    : "+f"(d[0]), "+f"(d[1]), "+f"(d[2]), "+f"(d[3]), "+f"(d[4]), "+f"(d[5]), "+f"(d[6]), "+f"(d[7]), "+f"(d[8]), "+f"(d[9]), "+f"(d[10]), "+f"(d[11]), "+f"(d[12]), "+f"(d[13]), "+f"(d[14]), "+f"(d[15]), "+f"(d[16]), "+f"(d[17]), "+f"(d[18]), "+f"(d[19]), "+f"(d[20]), "+f"(d[21]), "+f"(d[22]), "+f"(d[23]), "+f"(d[24]), "+f"(d[25]), "+f"(d[26]), "+f"(d[27]), "+f"(d[28]), "+f"(d[29]), "+f"(d[30]), "+f"(d[31]), "+f"(d[32]), "+f"(d[33]), "+f"(d[34]), "+f"(d[35]), "+f"(d[36]), "+f"(d[37]), "+f"(d[38]), "+f"(d[39]), "+f"(d[40]), "+f"(d[41]), "+f"(d[42]), "+f"(d[43]), "+f"(d[44]), "+f"(d[45]), "+f"(d[46]), "+f"(d[47]), "+f"(d[48]), "+f"(d[49]), "+f"(d[50]), "+f"(d[51]), "+f"(d[52]), "+f"(d[53]), "+f"(d[54]), "+f"(d[55]), "+f"(d[56]), "+f"(d[57]), "+f"(d[58]), "+f"(d[59]), "+f"(d[60]), "+f"(d[61]), "+f"(d[62]), "+f"(d[63]), "+f"(d[64]), "+f"(d[65]), "+f"(d[66]), "+f"(d[67]), "+f"(d[68]), "+f"(d[69]), "+f"(d[70]), "+f"(d[71]), "+f"(d[72]), "+f"(d[73]), "+f"(d[74]), "+f"(d[75]), "+f"(d[76]), "+f"(d[77]), "+f"(d[78]), "+f"(d[79]), "+f"(d[80]), "+f"(d[81]), "+f"(d[82]), "+f"(d[83]), "+f"(d[84]), "+f"(d[85]), "+f"(d[86]), "+f"(d[87]), "+f"(d[88]), "+f"(d[89]), "+f"(d[90]), "+f"(d[91]), "+f"(d[92]), "+f"(d[93]), "+f"(d[94]), "+f"(d[95])
    : "l"(da), "l"(db), "r"(scale_d), "n"(TA), "n"(TB));
}
template <int TB>
__device__ __forceinline__ void wgmma_rs_n192(float (&d)[96], uint32_t a0, uint32_t a1, uint32_t a2, uint32_t a3, uint64_t db, int scale_d) {
  asm volatile("{\n.reg .pred p;\nsetp.ne.b32 p, %101, 0;\n"
    "wgmma.mma_async.sync.aligned.m64n192k16.f32.bf16.bf16 {%0, %1, %2, %3, %4, %5, %6, %7, %8, %9, %10, %11, %12, %13, %14, %15, %16, %17, %18, %19, %20, %21, %22, %23, %24, %25, %26, %27, %28, %29, %30, %31, %32, %33, %34, %35, %36, %37, %38, %39, %40, %41, %42, %43, %44, %45, %46, %47, %48, %49, %50, %51, %52, %53, %54, %55, %56, %57, %58, %59, %60, %61, %62, %63, %64, %65, %66, %67, %68, %69, %70, %71, %72, %73, %74, %75, %76, %77, %78, %79, %80, %81, %82, %83, %84, %85, %86, %87, %88, %89, %90, %91, %92, %93, %94, %95}, {%96, %97, %98, %99}, %100, p, 1, 1, %102;\n}\n"
    : "+f"(d[0]), "+f"(d[1]), "+f"(d[2]), "+f"(d[3]), "+f"(d[4]), "+f"(d[5]), "+f"(d[6]), "+f"(d[7]), "+f"(d[8]), "+f"(d[9]), "+f"(d[10]), "+f"(d[11]), "+f"(d[12]), "+f"(d[13]), "+f"(d[14]), "+f"(d[15]), "+f"(d[16]), "+f"(d[17]), "+f"(d[18]), "+f"(d[19]), "+f"(d[20]), "+f"(d[21]), "+f"(d[22]), "+f"(d[23]), "+f"(d[24]), "+f"(d[25]), "+f"(d[26]), "+f"(d[27]), "+f"(d[28]), "+f"(d[29]), "+f"(d[30]), "+f"(d[31]), "+f"(d[32]), "+f"(d[33]), "+f"(d[34]), "+f"(d[35]), "+f"(d[36]), "+f"(d[37]), "+f"(d[38]), "+f"(d[39]), "+f"(d[40]), "+f"(d[41]), "+f"(d[42]), "+f"(d[43]), "+f"(d[44]), "+f"(d[45]), "+f"(d[46]), "+f"(d[47]), "+f"(d[48]), "+f"(d[49]), "+f"(d[50]), "+f"(d[51]), "+f"(d[52]), "+f"(d[53]), "+f"(d[54]), "+f"(d[55]), "+f"(d[56]), "+f"(d[57]), "+f"(d[58]), "+f"(d[59]), "+f"(d[60]), "+f"(d[61]), "+f"(d[62]), "+f"(d[63]), "+f"(d[64]), "+f"(d[65]), "+f"(d[66]), "+f"(d[67]), "+f"(d[68]), "+f"(d[69]), "+f"(d[70]), "+f"(d[71]), "+f"(d[72]), "+f"(d[73]), "+f"(d[74]), "+f"(d[75]), "+f"(d[76]), "+f"(d[77]), "+f"(d[78]), "+f"(d[79]), "+f"(d[80]), "+f"(d[81]), "+f"(d[82]), "+f"(d[83]), "+f"(d[84]), "+f"(d[85]), "+f"(d[86]), "+f"(d[87]), "+f"(d[88]), "+f"(d[89]), "+f"(d[90]), "+f"(d[91]), "+f"(d[92]), "+f"(d[93]), "+f"(d[94]), "+f"(d[95])
    : "r"(a0), "r"(a1), "r"(a2), "r"(a3), "l"(db), "r"(scale_d), "n"(TB));
}

__device__ __forceinline__ uint32_t smem_u32(const void* p) { return (uint32_t)__cvta_generic_to_shared(p); }
__device__ __forceinline__ void wg_fence() { asm volatile("wgmma.fence.sync.aligned;" ::: "memory"); }
__device__ __forceinline__ void wg_commit() { asm volatile("wgmma.commit_group.sync.aligned;" ::: "memory"); }
template <int N> __device__ __forceinline__ void wg_wait() { asm volatile("wgmma.wait_group.sync.aligned %0;" ::"n"(N) : "memory"); }
__device__ __forceinline__ void sched_fence(uint32_t& keep, bool never) {
  asm volatile("{\n.reg .pred p;\nsetp.ne.b32 p, %1, 0;\n@p mov.u32 %0, %%clock;\n}\n" : "+r"(keep) : "r"((int)never) : "memory");
}
template <int N> __device__ __forceinline__ void fence_regs(float (&r)[N]) {
#pragma unroll
  for (int i = 0; i < N; i++) asm volatile("" : "+f"(r[i])::"memory");
}
template <int N> __device__ __forceinline__ void undefine(float (&r)[N]) {
#pragma unroll
  for (int i = 0; i < N; i++) asm volatile("" : "=f"(r[i]));
}
template <int N> __device__ __forceinline__ void fence_regs(uint32_t (&r)[N]) {
#pragma unroll
  for (int i = 0; i < N; i++) asm volatile("" : "+r"(r[i])::"memory");
}
__device__ __forceinline__ uint64_t mk_desc(uint32_t a16, uint32_t lbo, uint32_t sbo, uint32_t swz) {
  uint64_t d;
  asm("mov.b64 %0, {%1, %2};" : "=l"(d) : "r"(a16 + ((lbo >> 4) << 16)), "r"((sbo >> 4) | (swz << 30)));
  return d;
}
__device__ __forceinline__ void mbar_init(uint32_t bar, uint32_t cnt) {
  asm volatile("mbarrier.init.shared::cta.b64 [%0], %1;" ::"r"(bar), "r"(cnt) : "memory");
}
__device__ __forceinline__ void mbar_expect(uint32_t bar, uint32_t tx) {
  asm volatile("mbarrier.arrive.expect_tx.shared::cta.b64 _, [%0], %1;" ::"r"(bar), "r"(tx) : "memory");
}
__device__ __forceinline__ bool mbar_test(uint32_t bar, uint32_t ph) {
  uint32_t ok;
  asm volatile("{\n.reg .pred p;\nmbarrier.test_wait.parity.shared::cta.b64 p, [%1], %2;\nselp.u32 %0, 1, 0, p;\n}\n"
               : "=r"(ok) : "r"(bar), "r"(ph) : "memory");
  return ok;
}
__device__ __forceinline__ bool mbar_try(uint32_t bar, uint32_t ph, uint32_t ns) {
  uint32_t ok;
  asm volatile("{\n.reg .pred p;\nmbarrier.try_wait.parity.shared::cta.b64 p, [%1], %2, %3;\nselp.u32 %0, 1, 0, p;\n}\n"
               : "=r"(ok) : "r"(bar), "r"(ph), "r"(ns) : "memory");
  return ok;
}
__device__ __forceinline__ void mbar_wait(uint32_t bar, uint32_t ph) {
  asm volatile("{\n.reg .pred p;\n.reg .u32 n;\nmov.u32 n, 0;\n"
               "LOOP:\nmbarrier.try_wait.parity.shared::cta.b64 p, [%0], %1;\n@p bra DONE;\n"
               "add.u32 n, n, 1;\nsetp.lt.u32 p, n, 0x1000000;\n@p bra LOOP;\ntrap;\n"
               "DONE:\n}\n" ::"r"(bar), "r"(ph) : "memory");
}
__device__ __forceinline__ void mbar_wait_long(uint32_t bar) {
  asm volatile("{\n.reg .pred p;\n.reg .u32 n;\nmov.u32 n, 0;\n"
               "LOOP:\nmbarrier.try_wait.parity.shared::cta.b64 p, [%0], 0, 20000;\n@p bra DONE;\n"
               "add.u32 n, n, 1;\nsetp.lt.u32 p, n, 0x100000;\n@p bra LOOP;\ntrap;\n"
               "DONE:\n}\n" ::"r"(bar) : "memory");
}
__device__ __forceinline__ void mbar_arrive_cluster_if(bool on, uint32_t addr) {
  asm volatile("{\n.reg .pred p;\nsetp.ne.b32 p, %1, 0;\n@p mbarrier.arrive.shared::cluster.b64 _, [%0];\n}\n" ::"r"(addr), "r"((int)on) : "memory");
}
__device__ __forceinline__ void mbar_arrive_cluster_n(uint32_t n, uint32_t addr) {
  asm volatile("{\n.reg .pred p;\nsetp.ne.b32 p, %1, 0;\n@p mbarrier.arrive.shared::cluster.b64 _, [%0], %1;\n}\n" ::"r"(addr), "r"(n) : "memory");
}
__device__ __forceinline__ void tma2d(uint32_t dst, const CUtensorMap* m, uint32_t bar, int c0, int c1) {
  asm volatile("cp.async.bulk.tensor.2d.shared::cluster.global.mbarrier::complete_tx::bytes [%0], [%1, {%3, %4}], [%2];"
               ::"r"(dst), "l"(m), "r"(bar), "r"(c0), "r"(c1) : "memory");
}
__device__ __forceinline__ void tma3d(uint32_t dst, const CUtensorMap* m, uint32_t bar, int c0, int c1, int c2) {
  asm volatile("cp.async.bulk.tensor.3d.shared::cluster.global.mbarrier::complete_tx::bytes [%0], [%1, {%3, %4, %5}], [%2];"
               ::"r"(dst), "l"(m), "r"(bar), "r"(c0), "r"(c1), "r"(c2) : "memory");
}
__device__ __forceinline__ void tma2d_hint(uint32_t dst, const CUtensorMap* m, uint32_t bar, int c0, int c1, uint64_t pol) {
  asm volatile("cp.async.bulk.tensor.2d.shared::cluster.global.mbarrier::complete_tx::bytes.L2::cache_hint [%0], [%1, {%3, %4}], [%2], %5;"
               ::"r"(dst), "l"(m), "r"(bar), "r"(c0), "r"(c1), "l"(pol) : "memory");
}
__device__ __forceinline__ void tma3d_mc_hint(uint32_t dst, const CUtensorMap* m, uint32_t bar, int c1, int c2, uint64_t pol) {
  asm volatile("cp.async.bulk.tensor.3d.shared::cluster.global.mbarrier::complete_tx::bytes.multicast::cluster.L2::cache_hint"
               " [%0], [%1, {%3, %4, %5}], [%2], %6, %7;"
               ::"r"(dst), "l"(m), "r"(bar), "r"(0), "r"(c1), "r"(c2), "h"((uint16_t)3), "l"(pol) : "memory");
}
__device__ __forceinline__ void tma5d_mc_hint(uint32_t dst, const CUtensorMap* m, uint32_t bar, int c2, int c4, uint64_t pol) {
  asm volatile("cp.async.bulk.tensor.5d.shared::cluster.global.mbarrier::complete_tx::bytes.multicast::cluster.L2::cache_hint"
               " [%0], [%1, {%3, %3, %4, %3, %5}], [%2], %6, %7;"
               ::"r"(dst), "l"(m), "r"(bar), "r"(0), "r"(c2), "r"(c4), "h"((uint16_t)3), "l"(pol) : "memory");
}
__device__ __forceinline__ void tma3d_store(const CUtensorMap* m, uint32_t src, int c0, int c1, int c2) {
  asm volatile("cp.async.bulk.tensor.3d.global.shared::cta.bulk_group [%0, {%2, %3, %4}], [%1];"
               ::"l"(m), "r"(src), "r"(c0), "r"(c1), "r"(c2) : "memory");
}
__device__ __forceinline__ void bar_sync(int id, int n) { asm volatile("bar.sync %0, %1;" ::"r"(id), "r"(n) : "memory"); }
__device__ __forceinline__ uint32_t pack_bf16(float lo, float hi) {
  uint32_t r;
  asm("cvt.rn.bf16x2.f32 %0, %1, %2;" : "=r"(r) : "f"(hi), "f"(lo));
  return r;
}
__device__ __forceinline__ float ex2(float x) {
  float y;
  asm("ex2.approx.ftz.f32 %0, %1;" : "=f"(y) : "f"(x));
  return y;
}
__device__ __forceinline__ float rcp(float x) {
  float y;
  asm("rcp.approx.ftz.f32 %0, %1;" : "=f"(y) : "f"(x));
  return y;
}
__device__ __forceinline__ void stsm4(uint32_t addr, uint32_t a, uint32_t b, uint32_t c, uint32_t d) {
  asm volatile("stmatrix.sync.aligned.m8n8.x4.shared.b16 [%0], {%1, %2, %3, %4};" ::"r"(addr), "r"(a), "r"(b), "r"(c), "r"(d) : "memory");
}

__device__ __forceinline__ void tma4d_mc_hint(uint32_t dst, const CUtensorMap* m, uint32_t bar, int c3, uint64_t pol) {
  asm volatile("cp.async.bulk.tensor.4d.shared::cluster.global.mbarrier::complete_tx::bytes.multicast::cluster.L2::cache_hint"
               " [%0], [%1, {%3, %3, %3, %4}], [%2], %5, %6;"
               ::"r"(dst), "l"(m), "r"(bar), "r"(0), "r"(c3), "h"((uint16_t)3), "l"(pol) : "memory");
}
__device__ __forceinline__ void bulk_load_hint(uint32_t dst, const void* src, uint32_t bytes, uint32_t bar, uint64_t pol) {
  asm volatile("cp.async.bulk.shared::cluster.global.mbarrier::complete_tx::bytes.L2::cache_hint [%0], [%1], %2, [%3], %4;"
               ::"r"(dst), "l"(src), "r"(bytes), "r"(bar), "l"(pol) : "memory");
}
__device__ __forceinline__ void stg2_if(bool on, void* p, uint32_t a, uint32_t b, uint32_t c, uint32_t d, uint32_t e, uint32_t f,
                                        uint32_t g, uint32_t h, uint64_t pol) {
  asm volatile("{\n.reg .pred p;\nsetp.ne.b32 p, %10, 0;\n"
               "@p st.global.L2::cache_hint.v4.b32 [%0], {%1, %2, %3, %4}, %9;\n"
               "@p st.global.L2::cache_hint.v4.b32 [%0 + 512], {%5, %6, %7, %8}, %9;\n}\n"
               ::"l"(p), "r"(a), "r"(b), "r"(c), "r"(d), "r"(e), "r"(f), "r"(g), "r"(h), "l"(pol), "r"((int)on) : "memory");
}
__device__ __forceinline__ uint64_t evict_first() {
  uint64_t p;
  asm("createpolicy.fractional.L2::evict_first.b64 %0, 1.0;" : "=l"(p));
  return p;
}
__device__ __forceinline__ uint64_t no_hint() {
  uint64_t p;
  asm("createpolicy.cvt.L2.b64 %0, %1;" : "=l"(p) : "l"(static_cast<uint64_t>(cuda::access_property{})));
  return p;
}
__device__ __forceinline__ bool elect() {
  uint32_t ok;
  asm volatile("{\n.reg .pred p;\nelect.sync _|p, 0xffffffff;\nselp.u32 %0, 1, 0, p;\n}\n" : "=r"(ok));
  return ok;
}
__device__ __forceinline__ void mbar_arrive(uint32_t bar) {
  asm volatile("mbarrier.arrive.shared::cta.b64 _, [%0];" ::"r"(bar) : "memory");
}
__device__ __forceinline__ void mbar_arrive_if(bool on, uint32_t bar) {
  asm volatile("{\n.reg .pred p;\nsetp.ne.b32 p, %1, 0;\n@p mbarrier.arrive.shared::cta.b64 _, [%0];\n}\n" ::"r"(bar), "r"((int)on) : "memory");
}
__device__ __forceinline__ void lds2_if(bool on, uint32_t p, uint32_t (&t)[8]) {
  asm volatile("{\n.reg .pred p;\nsetp.ne.b32 p, %9, 0;\n@p ld.shared.v4.b32 {%0, %1, %2, %3}, [%8];\n@p ld.shared.v4.b32 {%4, %5, %6, %7}, [%8 + 512];\n}\n"
               : "+r"(t[0]), "+r"(t[1]), "+r"(t[2]), "+r"(t[3]), "+r"(t[4]), "+r"(t[5]), "+r"(t[6]), "+r"(t[7]) : "r"(p), "r"((int)on) : "memory");
}
__device__ __forceinline__ void lds128(uint32_t p, uint32_t& a, uint32_t& b, uint32_t& c, uint32_t& d) {
  asm volatile("ld.shared.v4.b32 {%0, %1, %2, %3}, [%4];" : "=r"(a), "=r"(b), "=r"(c), "=r"(d) : "r"(p) : "memory");
}
template <class T> __device__ __forceinline__ T* ptr_add(T* base, uint32_t bytes) {
  T* r;
  asm("{\n.reg .u32 lo, hi;\nmov.b64 {lo, hi}, %1;\nadd.cc.u32 lo, lo, %2;\naddc.u32 hi, hi, 0;\nmov.b64 %0, {lo, hi};\n}\n" : "=l"(r) : "l"(base), "r"(bytes));
  return r;
}
__device__ __forceinline__ uint32_t lds32(uint32_t p) {
  uint32_t v;
  asm volatile("ld.volatile.shared.u32 %0, [%1];" : "=r"(v) : "r"(p) : "memory");
  return v;
}
__device__ __forceinline__ uint32_t flag_get(const unsigned int* p) {
  uint32_t v;
  asm volatile("ld.acquire.gpu.global.u32 %0, [%1];" : "=r"(v) : "l"(p) : "memory");
  return v;
}
__device__ __forceinline__ uint32_t wait_word(uint32_t p, uint32_t target) {
  uint32_t v;
  asm volatile("{\n.reg .pred p;\n.reg .u32 n;\nmov.u32 n, 0;\n"
               "LOOP:\nld.acquire.cta.shared.u32 %0, [%1];\nsetp.ge.u32 p, %0, %2;\n@p bra DONE;\n"
               "nanosleep.u32 %3;\nadd.u32 n, n, 1;\nsetp.lt.u32 p, n, 0x400000;\n@p bra LOOP;\ntrap;\n"
               "DONE:\n}\n" : "=r"(v) : "r"(p), "r"(target), "n"(400) : "memory");
  return v;
}
__device__ __forceinline__ void flag_set(unsigned int* p, uint32_t v) {
  asm volatile("st.release.gpu.global.u32 [%0], %1;" ::"l"(p), "r"(v) : "memory");
}
__device__ __forceinline__ void flag_dec(unsigned int* p) {
  asm volatile("red.relaxed.gpu.global.add.u32 [%0], 0xffffffff;" ::"l"(p) : "memory");
}

struct Cursor {
  uint32_t n;
  __device__ __forceinline__ uint32_t off() const { return n & (8 * NBAR - 8); }
  __device__ __forceinline__ uint32_t ph() const { return (n / (8 * NBAR)) & 1; }
  __device__ __forceinline__ void next() { n += 8; }
};

constexpr float kScaleLog2 = 0.07216878364870322f * 1.4426950408889634f;
constexpr float kSumLimit = 1048576.0f;

__global__ void __cluster_dims__(2, 1, 1) __launch_bounds__(384, 1)
fused_kernel(const __grid_constant__ Params P) {
  extern __shared__ uint8_t smem_raw[];
  const uint32_t sbase = (smem_u32(smem_raw) + 1023) & ~1023u;
  const uint32_t full0 = sbase + RING, empty0 = full0 + 8 * NBAR, odone0 = empty0 + 8 * NBAR, ev0 = odone0 + 8 * MAX_OPS;
  const uint32_t progress = ev0 + 8 * MAX_EV, jobw = progress + 4;
  const uint32_t rank = blockIdx.x & 1;
  const int role = blockIdx.x >> 1;
  const int wid = __shfl_sync(0xffffffffu, (int)(threadIdx.x >> 5), 0);
  const int wg = wid >> 2;

  if (wid < 8) {
    if (elect()) {
#pragma unroll
      for (int j = 0; j < 16; j++) {
        const int i = EARLY + 16 * wid + j;
        if (i < 2 * NBAR + MAX_OPS + MAX_EV) mbar_init(full0 + 8 * i, i < NBAR ? 1 : i < 2 * NBAR ? 16 : i < 2 * NBAR + MAX_OPS ? 8 : 1);
      }
      if (wid == 7) asm volatile("st.shared.v2.u32 [%0], {0, 0};\nfence.acq_rel.cta;" ::"r"(progress) : "memory");
      asm volatile("fence.mbarrier_init.release.cluster;" ::: "memory");
    }
  } else if (wid > 8) {
    const uint32_t g = blockIdx.x * 96 + threadIdx.x - 288, w = g - 2048;
    if (g < 4096) asm volatile("prefetch.global.L2 [%0];" ::"l"(g < 2048 ? P.xw[0] + g * (kD * 2) : P.xw[1] + (w >> 5) * (kHD * 2) + (w & 31) * 128));
  } else {
    const uint32_t op0 = P.first[role];
    if (elect()) {
#pragma unroll
      for (int k = 0; k < EARLY; k++) mbar_init(full0 + 8 * k, 1);
      asm volatile("fence.mbarrier_init.release.cluster;" ::: "memory");
      const int blk = (op0 >> 10) & 1;
      if ((op0 & 3) == OP_Q) {
#pragma unroll
        for (int k = 0; k < EARLY; k++) {
          mbar_expect(full0 + 8 * k, SZ_Q);
          tma2d(sbase + k * SZ_Q, &P.x[blk], full0 + 8 * k, 64 * k, ((op0 >> 7) & 7) * kSq + rank * 128);
          tma3d(sbase + k * SZ_Q + 16384, &P.wq[blk], full0 + 8 * k, 0, 64 * k, 3 * ((op0 >> 2) & 31));
          tma3d(sbase + k * SZ_Q + 28672, &P.wq[blk], full0 + 8 * k, 0, 64 * k + 32, 3 * ((op0 >> 2) & 31));
        }
      }
      asm volatile("prefetch.tensormap [%0];\nprefetch.tensormap [%1];" ::"l"(&P.k[blk]), "l"(&P.v[blk]) : "memory");
    }
  }
  __syncwarp();
  asm volatile("barrier.cluster.arrive.relaxed.aligned;\nbarrier.cluster.wait.aligned;" ::: "memory");

  if (wg < 2) {
    asm volatile("setmaxnreg.inc.sync.aligned.u32 240;");
    const uint32_t* prog = P.prog[role].c;
    const int wid = __shfl_sync(0xffffffffu, (int)(threadIdx.x >> 5), 1), wg = wid >> 2;
    const int lane = threadIdx.x & 31, warp = wid & 3;
    uint32_t empty_rem;
    asm volatile("mapa.shared::cluster.u32 %0, %1, %2;" : "=r"(empty_rem) : "r"(empty0), "r"(lane & 1));
    uint32_t keep = (threadIdx.x & 127) < 2 ? 4 : 0;
    auto release = [&](int slot) { mbar_arrive_cluster_n(keep, empty_rem + slot); };
    auto release_warp = [&](int slot, bool on = true) { mbar_arrive_cluster_if(lane < 2 && on, empty_rem + slot); };
    Cursor r{0};
    const uint32_t ring16 = (sbase & 0x3FFFF) >> 4;
    uint32_t cur = ring16;
    bool rdy0 = false, rdy1 = false;
    auto probe1 = [&]() { rdy0 = mbar_test(full0 + r.off(), r.ph()); };
    auto probe2 = [&]() {
      Cursor n = r;
      rdy0 = mbar_test(full0 + n.off(), n.ph());
      n.next();
      rdy1 = mbar_test(full0 + n.off(), n.ph());
    };
    auto advance = [&](uint32_t bytes, uint32_t& addr) {
      const int bi = r.off();
      r.next();
      if (cur > ring16 + ((RING - bytes) >> 4)) cur = ring16;
      addr = cur;
      cur += bytes >> 4;
      return bi;
    };
    auto take = [&](bool rdy, uint32_t bytes, uint32_t& addr) {
      if (__builtin_expect(!__all_sync(0xffffffffu, rdy), 0)) mbar_wait(full0 + r.off(), r.ph());
      return advance(bytes, addr);
    };
    const bool never = P.dbg == 0xffffffffu;
    uint32_t q[48];
#pragma unroll
    for (int i = 0; i < 48; i++) q[i] = 0;
    const int row = wg * 64 + warp * 16 + (lane >> 2);
    const int img0 = row * 4 + ((lane & 3) ^ ((row >> 1) & 3));
    uint4* pend = nullptr;
    bool pend_any = false;
    const uint64_t spol = evict_first();
    int pc = 0;
    auto slab = [&](int c, int i0) {
#pragma unroll
      for (int i = i0; i < 6; i++)
        stg2_if(c == i, pend + i * 512, q[8 * i], q[8 * i + 1], q[8 * i + 2], q[8 * i + 3],
                q[8 * i + 4], q[8 * i + 5], q[8 * i + 6], q[8 * i + 7], spol);
    };
    auto drain = [&](int c) {
      if (!pend_any || c >= 6) return;
      slab(c, 0);
      if (c == 5) {
        __syncwarp();
        mbar_arrive_if(lane == 0, odone0 - 8 + 8 * pc);
      }
    };

    for (;; pc++) {
      uint32_t op = prog[pc];
      const int type = op & 3;
      auto enter = [&]() {
        r.n = (op >> 12) & 248; cur = ring16 + (((op >> 20) & 63) << 8);
      };
      enter();
      pend_any = op & C_PEND;
      uint32_t job = 0;
      if ((op & (3 | C_WIDE)) == OP_O) job = __shfl_sync(0xffffffffu, wait_word(jobw, 1), 0);
      if (type == OP_END || job == OP_O) {
#pragma unroll 1
        for (int c = 0; c < 6; c++) drain(c);
        asm volatile("barrier.cluster.arrive.relaxed;" ::: "memory");
        break;
      }
      {
        float s[32], o[96];
        uint32_t ad0;
        int bi0, sk1, k0;
        uint32_t pa[16], pb[16];
        float mc0, mc1, l0, l1;
        bool shifted;
        uint32_t nop;
        auto expo = [&](float (&s)[32], uint32_t (&pout)[16], float& b0, float& b1, bool shift, auto mid) {
          float c0, c1;
#pragma unroll
          for (int i = 0; i < 8; i++) {
            const float e0 = ex2(shift ? s[4 * i] - mc0 : s[4 * i]), e1 = ex2(shift ? s[4 * i + 1] - mc0 : s[4 * i + 1]);
            const float e2 = ex2(shift ? s[4 * i + 2] - mc1 : s[4 * i + 2]), e3 = ex2(shift ? s[4 * i + 3] - mc1 : s[4 * i + 3]);
            if (i) { b0 += e0; c0 += e1; b1 += e2; c1 += e3; } else { b0 = e0; c0 = e1; b1 = e2; c1 = e3; }
            pout[2 * i] = pack_bf16(e0, e1); pout[2 * i + 1] = pack_bf16(e2, e3);
            if (i & 1) mid(i >> 1);
          }
          b0 += c0; b1 += c1;
        };
        auto rowmax = [&](float (&s)[32], float& m0, float& m1) {
          m0 = fmaxf(s[0], s[1]); m1 = fmaxf(s[2], s[3]);
#pragma unroll
          for (int i = 1; i < 8; i++) { m0 = fmaxf(m0, fmaxf(s[4 * i], s[4 * i + 1])); m1 = fmaxf(m1, fmaxf(s[4 * i + 2], s[4 * i + 3])); }
          m0 = fmaxf(m0, __shfl_xor_sync(0xffffffffu, m0, 1)); m1 = fmaxf(m1, __shfl_xor_sync(0xffffffffu, m1, 1));
          m0 = fmaxf(m0, __shfl_xor_sync(0xffffffffu, m0, 2)); m1 = fmaxf(m1, __shfl_xor_sync(0xffffffffu, m1, 2));
        };
        auto first = [&](float (&s)[32], int sk0, auto mid) {
          fence_regs(s);
          release(sk0);
          mc0 = 0.f; mc1 = 0.f;
          expo(s, pa, l0, l1, false, mid);
          shifted = __any_sync(0xffffffffu, !(fmaxf(l0, l1) <= kSumLimit && fminf(l0, l1) >= 1.f / kSumLimit));
          if (shifted) {
            rowmax(s, mc0, mc1);
            expo(s, pa, l0, l1, true, [](int) {});
          }
        };
        auto qk = [&](float (&s)[32], uint32_t ak, int k0 = 0, int k1 = 12) {
#pragma unroll
          for (int kk = k0; kk < k1; kk++)
            wgmma_rs_n64<0>(s, q[4 * kk], q[4 * kk + 1], q[4 * kk + 2], q[4 * kk + 3], mk_desc(ak, 16, KV_SBO, 1) + ((kk >> 2) * KV_CH + (kk & 3) * 2), kk != 0);
          if (k1 == 12) wg_commit();
        };
        auto pv = [&](uint32_t (&pin)[16], uint32_t av, int acc, int k0 = 0, int k1 = 4) {
#pragma unroll
          for (int kk = k0; kk < k1; kk++)
            wgmma_rs_n192<1>(o, pin[4 * kk], pin[4 * kk + 1], pin[4 * kk + 2], pin[4 * kk + 3], mk_desc(av, KV_CH * 16, KV_SBO, 1) + (kk * (KV_SBO / 8)), acc || (kk != 0));
          if (k0 == 0) wg_commit();
        };
        auto finish = [&](uint32_t (&pout)[16], int sk, int sv, bool part = false) {
          probe1();
          wg_wait<1>();
          fence_regs(s);
          release(sk);
          float b0, b1;
#pragma unroll 1
          for (bool redo = false;; redo = true) {
            expo(s, pout, b0, b1, false, [](int) {});
            if (!__any_sync(0xffffffffu, !redo && (shifted || !(fmaxf(b0, b1) <= kSumLimit)))) break;
            shifted = true;
            rowmax(s, b0, b1);
            b0 = fmaxf(mc0, b0); b1 = fmaxf(mc1, b1);
            const float a0 = ex2(mc0 - b0), a1 = ex2(mc1 - b1);
            mc0 = b0; mc1 = b1;
            l0 *= a0; l1 *= a1;
            wg_wait<0>();
            fence_regs(o);
#pragma unroll
            for (int i = 0; i < 24; i++) { o[4 * i] *= a0; o[4 * i + 1] *= a0; o[4 * i + 2] *= a1; o[4 * i + 3] *= a1; }
#pragma unroll
            for (int i = 0; i < 32; i++) s[i] -= (i & 2) ? mc1 : mc0;
            if (part) {
#pragma unroll
              for (int i = 8; i < 16; i++)
                pa[i] = pack_bf16(__uint_as_float(pa[i] << 16) * ((i & 1) ? a1 : a0), __uint_as_float(pa[i] & 0xffff0000u) * ((i & 1) ? a1 : a0));
            }
          }
          l0 += b0; l1 += b1;
          wg_wait<0>();
          fence_regs(o);
          mbar_arrive_cluster_n(part ? 0 : keep, empty_rem + sv);
        };
        uint32_t pav;
        int psv;
        auto step = [&](uint32_t (&pin)[16], uint32_t (&pout)[16], bool part) {
          uint32_t ak;
          const int sk = take(rdy0, SZ_KV, ak);
          psv = advance(SZ_KV, pav);
          wg_fence();
          qk(s, ak);
          if (part) pv(pin, pav, 1, 0, 2); else pv(pin, pav, 1);
          finish(pout, sk, psv, part);
        };
        auto unpark = [&](uint32_t& ak) {
          uint32_t ad;
          const Cursor k0 = r;
          const int sk0 = advance(SZ_KV, ak), bi = take(false, SZ_PARK, ad);
#pragma unroll
          for (int i = 0; i < 12; i++) lds128(sbase + (ad - ring16 + img0) * 16 + (i >> 1) * 8192 + (i & 1) * 512, q[4 * i], q[4 * i + 1], q[4 * i + 2], q[4 * i + 3]);
          if (!__all_sync(0xffffffffu, rdy0)) mbar_wait(full0 + k0.off(), k0.ph());
          fence_regs(q);
          release_warp(bi);
          wg_fence();
          qk(s, ak, 0, 4);
          wg_commit();
          return sk0;
        };
        auto mma4 = [&](uint32_t ad, int acc) {
#pragma unroll
          for (int kk = 0; kk < 4; kk++)
            wgmma_ss_n192<1>(o, mk_desc(ad + wg * 512, 16, 1024, 1) + (kk * 2), mk_desc(ad, 4096, 1024, 1) + (1024 + (kk >> 1) * 768 + (kk & 1) * 128), acc || kk != 0);
        };
        auto convert = [&](int i0, int i1) {
          sched_fence(keep, never);
#pragma unroll
          for (int i = i0; i < i1; i++) {
            q[i] = pack_bf16(o[2 * i] * kScaleLog2, o[2 * i + 1] * kScaleLog2);
            if ((i & 7) == 7 && i != i1 - 1) sched_fence(keep, never);
          }
          sched_fence(keep, never);
        };
        auto kend = [&](int bi, int k) {
          wg_commit();
          drain((0x54732710u >> (4 * k)) & 7);
          probe1();
          wg_wait<0>();
          release(bi);
        };
        if (type == OP_O) {
          int prev = 0;
          if (op & C_WIDE) {
            float d[64];
            auto mma3 = [&](uint32_t ad, int h, int acc) {
#pragma unroll
              for (int kk = 0; kk < 2; kk++)
                wgmma_ss_n192<1>(o, mk_desc(ad + wg * 256, 16, 512, 2) + (h * 512 + kk * 2), mk_desc(ad, 4096, 1024, 1) + (1024 + h * 768 + kk * 128), acc || kk);
            };
            auto mma2 = [&](uint32_t ad, uint32_t ob, int h, int acc) {
#pragma unroll
              for (int kk = 0; kk < 2; kk++)
                wgmma_ss_n128<1>(d, mk_desc(ad + wg * 256, 16, 512, 2) + (h * 512 + kk * 2), mk_desc(ad, 4096, 1024, 1) + (ob + h * 512 + kk * 128), acc || kk);
            };
            auto wstep = [&](uint32_t bytes, int acc, auto hook) {
              uint32_t ad;
              const int bi = take(rdy0, bytes, ad);
              wg_fence();
              if (bytes == SZ_W2) mma2(ad, 1024, 0, 1); else mma3(ad, 0, acc);
              if (bytes == SZ_W) mma3(ad, 1, 1);
              wg_commit();
              if (acc) { wg_wait<1>(); release(prev); }
              if (bytes == SZ_W) mma2(ad, 2560, 0, acc);
              if (bytes == SZ_W3) mma3(ad, 1, 1); else mma2(ad, bytes == SZ_W ? 2560 : 1024, 1, 1);
              wg_commit();
              prev = bi;
              hook();
              probe1();
              wg_wait<1>();
            };
            undefine(o);
            wstep(SZ_W, 0, [&]() { drain(0); });
#pragma unroll 1
            for (int k = 1; k < ((op >> 2) & 127) - TAIL; k++) wstep(SZ_W, 1, [&]() { drain(k); });
#pragma unroll 1
            for (int k = 0; k < TAIL; k++) wstep(SZ_W2, 1, []() {});
            pend = ptr_add(P.g->part, (((op >> 9) & 31) * 2 + rank) * 81920 + 4 * 8192 + img0 * 16);
            wstep(SZ_W3, 1, [&]() {
              fence_regs(d);
#pragma unroll
              for (int i = 0; i < 32; i++) q[16 + i] = pack_bf16(d[2 * i], d[2 * i + 1]);
              slab(2, 2);
            });
#pragma unroll 1
            for (int k = 3; k < 6; k++) wstep(SZ_W3, 1, [&]() { slab(k, 2); });
            op = prog[pc + 1];
            enter();
            pend_any = true;
            pend -= 4 * 512;
            bi0 = take(rdy0 || (op & 3) != OP_Q, SZ_Q, ad0);
            sched_fence(keep, never);
            wg_wait<0>();
            fence_regs(o);
            release(prev);
#pragma unroll
            for (int i = 0; i < 48; i++) q[i] = pack_bf16(o[2 * i], o[2 * i + 1]);
            if ((op & 3) != OP_Q) continue;
            pc++;
            goto first_step;
          }
          float c[80];
          auto mma2 = [&](uint32_t ad, uint32_t oa, uint32_t ob, int acc) {
            wgmma_ss_n160<1>(c, mk_desc(ad + wg * 256, 16, 512, 2) + (oa), mk_desc(ad, 2048, 512, 2) + (1024 + ob), acc);
            wgmma_ss_n160<1>(c, mk_desc(ad + wg * 256, 16, 512, 2) + (oa + 2), mk_desc(ad, 2048, 512, 2) + (1024 + ob + 64), 1);
          };
          auto kstep = [&](int acc, auto hook, uint32_t bytes = SZ_O) {
            uint32_t ad;
            const int bi = take(rdy0, bytes, ad);
            wg_fence();
            mma2(ad, 0, 0, acc);
            wg_commit();
            if (acc) wg_wait<1>();
            if (acc == 1) release(prev);
            if (acc > 1) release_warp(prev, acc == 2 || wg == 0);
            mma2(ad, 512, 640, 1);
            wg_commit();
            prev = bi;
            hook();
            probe1();
            wg_wait<1>();
          };
          auto unblock = [&](int k) {
            if (__all_sync(0xffffffffu, rdy0) || __all_sync(0xffffffffu, mbar_try(full0 + r.off(), r.ph(), 1500))) return;
#pragma unroll 1
            for (; k < 6; k++) drain(k);
            pend_any = false;
          };
          unblock(0);
          kstep(0, [&]() { drain(0); });
          int left = ((job >> 13) & 127) - 6;
#pragma unroll 1
          for (uint32_t k = 1, pace = left >= 22 ? 0x4511 : left <= 11 ? 0x1a : 0x155; left > 0; pace >>= 2, left--) {
            unblock(k);
            kstep(1, [&]() {
#pragma unroll 1
              for (int i = pace & 3; i > 0; i--) drain(k++);
            });
          }
          uint32_t t[8], stage[3];
          float u[80];
          auto unpack = [&](int j) {
#pragma unroll
            for (int i = 0; i < 8; i++) {
              u[16 * j + 2 * i] = __uint_as_float(t[i] << 16); u[16 * j + 2 * i + 1] = __uint_as_float(t[i] & 0xffff0000u);
              asm volatile("" : "+f"(u[16 * j + 2 * i]), "+f"(u[16 * j + 2 * i + 1]));
            }
          };
#pragma unroll
          for (int i = 0; i < 8; i++) t[i] = 0;
          const uint32_t bytes = (job & P_LD) ? SZ_OL : SZ_O;
#pragma unroll
          for (int j = 0; j < 5; j++) {
            if (j == 2 && wg == 1) {
              wg_wait<0>();
              release_warp(prev);
              bar_sync(1, 256);
            }
            kstep(j == 2 ? 3 : 2, [&]() {
              if (j == 4) asm volatile("{\n.reg .pred p;\nsetp.eq.u32 p, %0, 0;\n@p bar.arrive 1, 256;\n}\n" ::"r"(wg) : "memory");
              if (j) unpack(j - 1);
              lds2_if(job & P_LD, sbase + (cur - ring16 + img0) * 16 - 8192, t);
              if (j >= 1 && j <= 3) stage[j - 1] = sbase + (cur - ring16) * 16 - bytes + wid * 1024;
            }, bytes);
          }
          unpack(4);
          sched_fence(keep, never);
          wg_wait<0>();
          fence_regs(c);
          release_warp(prev);
          asm volatile("barrier.cluster.arrive.relaxed;" ::: "memory");
#pragma unroll
          for (int i = 0; i < 10; i++) {
            const int v = (i & 1) * 2 + (lane >> 4);
            const uint32_t sa = stage[i >> 2] + (i & 2) * 4096;
            stsm4(sa + (lane & 15) * 64 + ((v ^ ((lane >> 1) & 3)) << 4), pack_bf16(c[8 * i] + u[8 * i], c[8 * i + 1] + u[8 * i + 1]),
                  pack_bf16(c[8 * i + 2] + u[8 * i + 2], c[8 * i + 3] + u[8 * i + 3]), pack_bf16(c[8 * i + 4] + u[8 * i + 4], c[8 * i + 5] + u[8 * i + 5]),
                  pack_bf16(c[8 * i + 6] + u[8 * i + 6], c[8 * i + 7] + u[8 * i + 7]));
          }
          asm volatile("fence.proxy.async.shared::cta;" ::: "memory");
          __syncwarp();
          if (elect()) {
#pragma unroll
            for (int i = 0; i < 5; i++)
              tma3d_store(&P.out, stage[i >> 1] + (i & 1) * 8192, 0, ((job >> 7) & 7) * kSq + rank * 128 + wid * 16, ((job >> 10) & 1) * 20 + ((job >> 20) & 3) * 5 + i);
            asm volatile("cp.async.bulk.commit_group;\ncp.async.bulk.wait_group.read 0;" ::: "memory");
          }
          __syncwarp();
          break;
        }
        bi0 = take(rdy0, SZ_Q, ad0);
      first_step:
        undefine(o);
        wg_fence();
        mma4(ad0, 0);
        kend(bi0, 0);
        fence_regs(o);
        k0 = 1;
      next_head:
        {
#pragma unroll 1
          for (int k = k0; k < 8; k++) {
            uint32_t ad;
            const int bi = take(rdy0, SZ_Q, ad);
            wg_fence();
            mma4(ad, 1);
            kend(bi, k);
          }
          uint32_t a8, a9, ak0, ak1;
          const int b8 = take(rdy0, SZ_Q, a8), b9 = take(false, SZ_Q, a9);
          wg_fence();
          mma4(a8, 1);
          wg_commit();
          mma4(a9, 1);
          wg_commit();
          wg_wait<1>();
          release(b8);
          probe1();
          const int sk0 = take(rdy0 || (op & F_PARK), SZ_KV, ak0);
          wg_wait<0>();
          fence_regs(o);
          release(b9);
          float s0[32];
          convert(0, 32);
          if (op & F_PARK) {
            convert(32, 48);
            pend = ptr_add(P.g->tile, (((op >> 2) & 511) * 2 + rank) * SZ_PARK + img0 * 16);
            continue;
          }
          pc++;
          wg_fence();
          qk(s0, ak0, 0, 4);
          convert(32, 48);
          wg_fence();
          qk(s0, ak0, 4, 12);
          sk1 = take(false, SZ_KV, ak1);
          wg_fence();
          qk(s, ak1, 0, 4);
          wg_commit();
          probe1();
          wg_wait<1>();
          first(s0, sk0, [&](int i) {
            if (!(i & 1)) return;
            sched_fence(keep, never);
            wg_fence();
            if (i == 1) qk(s, ak1, 4, 8);
            if (i == 3) qk(s, ak1, 8, 12);
            sched_fence(keep, never);
          });
        }
        for (;;) {
          {
            uint32_t av;
            const int sv = take(rdy0, SZ_KV, av);
            undefine(o);
            wg_fence();
            pv(pa, av, 0);
            finish(pb, sk1, sv);
          }
          nop = prog[pc + 1];
#pragma unroll 1
          for (int jj = 0; jj < 7; jj++) {
            step(pb, pa, false);
            step(pa, pb, jj == 6);
          }
          float i0, i1;
          auto last = [&]() {
            uint32_t av;
            const int sv = take(rdy0, SZ_KV, av);
            wg_fence();
            pv(pa, pav, 1, 2, 4);
            pv(pb, av, 1);
            sched_fence(keep, never);
            probe1();
            l0 += __shfl_xor_sync(0xffffffffu, l0, 1); l1 += __shfl_xor_sync(0xffffffffu, l1, 1);
            l0 += __shfl_xor_sync(0xffffffffu, l0, 2); l1 += __shfl_xor_sync(0xffffffffu, l1, 2);
            i0 = rcp(l0); i1 = rcp(l1);
            pend = ptr_add(P.g->tile, (((op >> 2) & 511) * 2 + rank) * SZ_PARK + img0 * 16);
            return sv;
          };
          auto normalise = [&](uint32_t (&d)[48], auto mid) {
#pragma unroll
            for (int i = 0; i < 24; i++) {
              d[8 * (i >> 2) + (i & 3)] = pack_bf16(o[4 * i] * i0, o[4 * i + 1] * i0);
              d[8 * (i >> 2) + (i & 3) + 4] = pack_bf16(o[4 * i + 2] * i1, o[4 * i + 3] * i1);
              if ((i & 1) && i != 23) sched_fence(keep, never);
              if ((i & 3) == 3 && i != 23) mid(i >> 2);
            }
          };
          const int sv = last();
          if ((nop & 3) != OP_A) {
            op = nop;
            enter();
            pend_any = true;
            bi0 = take(rdy0 || (nop & 3) != OP_Q, SZ_Q, ad0);
            uint32_t ad1;
            const int bi1 = take((nop & 3) != OP_Q, SZ_Q, ad1);
            sched_fence(keep, never);
            wg_wait<0>();
            fence_regs(o);
            release(psv);
            release(sv);
            normalise(q, [](int) {});
            undefine(o);
            if ((nop & 3) != OP_Q) break;
            sched_fence(keep, never);
            wg_fence();
            mma4(ad0, 0);
            pc++;
            wg_commit();
            mma4(ad1, 1);
            wg_commit();
            drain(0);
            wg_wait<1>();
            release(bi0);
            drain(1);
            probe1();
            wg_wait<0>();
            release(bi1);
            fence_regs(o);
            k0 = 2;
            goto next_head;
          }
          uint32_t ak0;
          const int sk0 = unpark(ak0);
          wg_wait<1>();
          fence_regs(o);
          release(psv);
          release(sv);
          uint32_t t[48];
          auto st = [&](int i) {
            stg2_if(true, pend + i * 512, t[8 * i], t[8 * i + 1], t[8 * i + 2], t[8 * i + 3], t[8 * i + 4], t[8 * i + 5], t[8 * i + 6], t[8 * i + 7], spol);
          };
          normalise(t, [&](int i) {
            if (i & 1) {
              wg_fence();
              if (i == 1) qk(s, ak0, 4, 8);
              if (i == 3) qk(s, ak0, 8, 12);
              sched_fence(keep, never);
            }
            if (!(i & 1)) st(i >> 1);
          });
          probe2();
          wg_wait<0>();
          first(s, sk0, [&](int i) { if (i < 3) { sched_fence(keep, never); st(3 + i); } });
          __syncwarp();
          mbar_arrive_if(lane == 0, odone0 + 8 * pc);
          pc++;
          op = nop;
          uint32_t ak1;
          sk1 = take(rdy0, SZ_KV, ak1);
          rdy0 = rdy1;
          wg_fence();
          qk(s, ak1);
        }
      }
    }
    asm volatile("barrier.cluster.wait;" ::: "memory");
  } else {
    asm volatile("setmaxnreg.dec.sync.aligned.u32 24;");
    const uint32_t* prog = P.prog[role].p;
    unsigned int* flag = P.g->flag + rank;
    if (wid == 11 && (prog[0] & 3) == OP_Q) {
      const uint32_t a = prog[1];
      const char* p = ptr_add(P.kv[rank * 2 + ((a >> 10) & 1)], ((a >> 2) & 255) * (kSk * kDh * 2) + (threadIdx.x & 31) * 128);
#pragma unroll 1
      for (uint32_t k = 0; k < 3; k++) {
        wait_word(progress, 8 * k);
        p += SZ_KV;
        asm volatile("prefetch.global.L2 [%0];\nprefetch.global.L2 [%0 + 4096];" ::"l"(p));
      }
      __syncwarp();
    }
    if (wid == 8) {
      Cursor head{0}, tail{0};
      int sh = 0, room = RING >> 12;
      uint32_t cur = 0;
      uint64_t fifo = 0;
      uint32_t dst, bar = 0, ev = ev0;
      const uint64_t pol = evict_first();
      auto retire = [&]() {
        mbar_wait(empty0 + tail.off(), tail.ph());
        tail.next();
        room += (uint32_t)fifo & 31;
        fifo >>= 5;
        sh -= 5;
        asm volatile("st.volatile.shared.u32 [%0], %1;" ::"r"(progress), "r"(tail.n) : "memory");
      };
      auto acquire = [&](uint32_t bytes) {
        uint32_t fp = bytes >> 12;
        if (cur + fp > (RING >> 12)) { fp += (RING >> 12) - cur; cur = 0; }
        room -= fp;
        while (room < 0) retire();
        fifo |= (uint64_t)fp << sh;
        sh += 5;
        dst = sbase + (cur << 12);
        bar = full0 + head.off();
        cur += bytes >> 12;
        head.next();
      };
      auto gate = [&]() {
        mbar_wait(ev, 0);
        ev += 8;
        asm volatile("fence.proxy.async.global;" ::: "memory");
      };
      for (int pc = 0;; pc++) {
        uint32_t op = prog[pc];
        const int type = op & 3;
        if (type == OP_END) break;
        if (op == OP_O) {
          gate();
          op = __shfl_sync(0xffffffffu, lds32(jobw), 0);
        }
        const int blk = (op >> 10) & 1;
        if (type == OP_Q) {
          const uint64_t px = (op & P_LASTX) ? pol : no_hint(), pw = (op & P_LASTW) ? pol : no_hint();
          int k = 0;
          if (pc == 0) {
            k = 64 * EARLY; head.n = 8 * EARLY; sh = 5 * EARLY; cur = EARLY * (SZ_Q >> 12); room -= cur;
            fifo = (SZ_Q >> 12) * (((1u << (5 * EARLY)) - 1) / 31);
          }
#pragma unroll 1
          for (int stop = (op & P_GATE) ? kD - 64 : kD;; stop = kD) {
#pragma unroll 1
            for (; k < stop; k += 64) {
              acquire(SZ_Q);
              if (elect()) {
                mbar_expect(bar, SZ_Q);
                tma3d_mc_hint(dst + 16384 + rank * 12288, &P.wq[blk], bar, k + 32 * rank, 3 * ((op >> 2) & 31), pw);
                tma2d_hint(dst, &P.x[blk], bar, k, ((op >> 7) & 7) * kSq + rank * 128, px);
              }
            }
            if (k == kD) break;
            gate();
          }
        } else if (type == OP_A) {
          const int row0 = ((op >> 2) & 255) * kSk;
          auto kv = [&](uint32_t tx, const CUtensorMap* m, int c3) {
            const uint32_t before = bar;
            acquire(SZ_KV);
            if (elect()) {
              mbar_expect(bar, tx);
              tma4d_mc_hint(dst + rank * (SZ_KV / 2), m, tx ? bar : before, c3, pol);
            }
          };
          int c3 = row0 / 8 + 4 * rank;
#pragma unroll 1
          for (int j = 0; j <= 16; j++, c3 += 8) {
            const uint32_t tv = j < 2 || j == 16 ? SZ_KV : 0;
            if (j < 16) kv(2 * SZ_KV - tv, &P.k[blk], c3);
            else if (op & P_GATE) gate();
            if (j > 0) kv(tv, &P.v[blk], c3 - 8);
            else if (op & F_PARK) {
              gate();
              acquire(SZ_PARK);
              if (elect()) {
                mbar_expect(bar, SZ_PARK);
                bulk_load_hint(dst, &P.g->tile[(((op >> 20) & 511) * 2 + rank) * 3072], SZ_PARK, bar, pol);
              }
            }
          }
        } else {
          const uint4* part = &P.g->part[((((op >> 6) & 30) + ((op >> 21) & 1)) * 2 + rank) * 5120 + ((op >> 20) & 1) * 2560];
          auto run = [&](const uint32_t bytes, int k, int cnt, int gates) {
            const int col = bytes == SZ_O || bytes == SZ_OL ? 5 * ((op >> 20) & 3) : 5 * ((op >> 21) & 1);
            int row = 8 * k + 4 * rank, pre = bytes == SZ_O && (op & P_PRE) ? 0 : 2560;
#pragma unroll 1
            for (int h = (k * 43) >> 7, k0 = k - 3 * h; cnt > 0; h++, k0 = 0, gates = gates >> 1 | (gates & 2)) {
              const uint4* src = ptr_add(P.g->tile, ((P.slot[((op >> 2) & 480) + h] * 2 + rank) * 3 + k0) * 16384);
              const uint64_t pw = h >= ((op >> 23) & 31) && h < 2 * (op >> 28) ? pol : no_hint();
              if (gates & 1) gate();
              int m = min(3 - k0, cnt);
              cnt -= m;
#pragma unroll 1
              for (; m > 0; m--, src += 1024, row += 8) {
                acquire(bytes);
                if (elect()) {
                  mbar_expect(bar, bytes);
                  if (bytes == SZ_O || bytes == SZ_OL) tma5d_mc_hint(dst + 16384 + rank * 10240, &P.wo[blk], bar, row, col, no_hint());
                  if (bytes == SZ_W || bytes == SZ_W3) tma5d_mc_hint(dst + 16384 + rank * 12288, &P.wo3[blk], bar, row, col, pw);
                  bulk_load_hint(dst, src, 16384, bar, pol);
                  if (bytes == SZ_W || bytes == SZ_W2) tma5d_mc_hint(dst + bytes - 16384 + rank * 8192, &P.wo2[blk], bar, row, col + 3, pw);
                  if (bytes == SZ_OL) bulk_load_hint(dst + SZ_O, part, 8192, bar, pol);
                }
                if (bytes == SZ_OL) part += 512;
              }
              if (pre < 2560) {
                if (elect()) asm volatile("cp.async.bulk.prefetch.L2.global [%0], 10240;" ::"l"(part + pre) : "memory");
                pre += 640;
              }
            }
          };
          const int n = (op >> 13) & 127;
          if (op & P_WIDE) {
            run(SZ_W, 0, n - TAIL, 3);
            run(SZ_W2, n - TAIL, TAIL, (n - TAIL) % 3 ? 2 : 3);
            run(SZ_W3, n - TAIL, TAIL, 0);
          } else {
            if (op & P_PRE) gate();
            run(SZ_O, kSteps - n, (op & P_LD) ? n - 5 : n, 3);
            if (op & P_LD) {
              if (!(op & P_PRE)) gate();
              run(SZ_OL, kSteps - 5, 5, 2);
            }
          }
        }
      }
#pragma unroll 1
      while (sh) retire();
    } else if (threadIdx.x == 288) {
      for (int pc = 0;; pc++) {
        const uint32_t op = prog[pc];
        const int type = op & 3;
        if (type == OP_END) break;
        if (type == OP_Q ? !(op & F_PARK) : type == OP_O && !(op & P_WIDE)) continue;
        const int id = type == OP_A ? (op >> 2) & 511 : type == OP_Q ? N_TILE + ((op >> 13) & 127) : ID_PART + ((op >> 5) & 60) + ((op >> 20) & 3);
        const uint32_t v = type == OP_O ? 1 : P.info[id] & 7;
        mbar_wait_long(odone0 + 8 * pc);
        flag_set(flag + 2 * id, v);
        if (type == OP_O && (op & P_WIDE)) flag_set(flag + 2 * id + 2, v);
      }
    } else if (wid == 10) {
      int i = threadIdx.x & 31;
      const int n_ev = P.prog[role].n_ev;
      auto event = [&]() { return i < n_ev ? P.prog[role].ev[i] : n_ev ? E_JOB | (i - n_ev) : 0; };
      uint32_t e = i < 8 ? event() : 0;
      for (uint32_t n = 0; __any_sync(0xffffffffu, e); n++) {
        uint32_t job = lds32(jobw);
        const int togo = (e & E_DRAW) ? (e & 1023) - (lds32(progress) >> 3) : 99;
        if (togo <= 0 && rank == 0) {
          job = P.job[atomicInc(&P.g->ticket, gridDim.x / 2 - 1)];
          asm volatile("{\n.reg .u32 a;\nmapa.shared::cluster.u32 a, %0, 1;\nst.volatile.shared::cluster.u32 [a], %1;\n"
                       "st.volatile.shared.u32 [%0], %1;\n}\n" ::"r"(jobw), "r"(job) : "memory");
        }
        if ((e & E_JOB) && job) {
          const uint32_t j = e & 63, heads = job == OP_O ? 0 : kH - ((job >> 2) & 31), jp = !(job & P_LD) ? 63 : (job & P_PRE) ? 0 : heads - 1, h = j - (j > jp);
          e = j == jp ? (ID_PART + ((job >> 5) & 60) + ((job >> 20) & 3)) | E_ON | E_LAST : h < heads ? (((job >> 2) & 511) + h) | E_ON | E_LAST : 0;
        }
        unsigned int* f = ptr_add(flag, 8 * (e & 1023));
        const bool ok = (e & E_ON) ? flag_get(f) - 1 < ((e & E_FREE) ? 1 : 7) : (e & E_DRAW) && job;
        if (ok) {
          mbar_arrive(ev0 + 8 * i);
          if (e & (E_FREE | E_LAST)) flag_dec(f);
          i += 8;
          e = event();
        }
        asm volatile("{\n.reg .pred p;\nsetp.ge.u32 p, %0, 0x400000;\n@p trap;\n}\n" ::"r"(n));
        if (!__any_sync(0xffffffffu, ok)) __nanosleep(__any_sync(0xffffffffu, job || togo <= 2) ? 100 : 600);
      }
    } else if (threadIdx.x == 352) {
      uint32_t items = 0;
      auto read = [&](int id) {
        if (!(P.info[id] & I_NEXT)) return;
        wait_word(progress, 8 * items);
        flag_dec(flag + 2 * id);
      };
      for (int pc = 0;; pc++) {
        const uint32_t op = prog[pc];
        const int type = op & 3;
        if (type == OP_END) break;
        if (type == OP_O) {
          const uint32_t n = (op >> 13) & 127, base = items;
#pragma unroll 1
          for (uint32_t k = 3, id = (op >> 2) & 511; k <= n; k += 3, id++) {
            items = base + k + (k + TAIL > n ? TAIL : 0);
            read(id);
          }
          items = base + n + TAIL;
        } else if (type == OP_A) {
          items++;
          if (op & F_PARK) { items++; read(N_TILE + ((op >> 13) & 127)); }
          items += 31;
        } else {
          items += 10;
        }
      }
    }
    __syncwarp();
    asm volatile("barrier.cluster.arrive.relaxed;\nbarrier.cluster.wait;" ::: "memory");
  }
}

typedef CUresult (*EncodeFn)(CUtensorMap*, CUtensorMapDataType, cuuint32_t, void*, const cuuint64_t*, const cuuint64_t*,
                             const cuuint32_t*, const cuuint32_t*, CUtensorMapInterleave, CUtensorMapSwizzle,
                             CUtensorMapL2promotion, CUtensorMapFloatOOBfill);

void encode(EncodeFn fn, CUtensorMap* m, const void* ptr, int rank, const cuuint64_t* dims, const cuuint64_t* strides,
            const cuuint32_t* box, CUtensorMapSwizzle swz) {
  const cuuint32_t es[5] = {1, 1, 1, 1, 1};
  CUresult r = fn(m, CU_TENSOR_MAP_DATA_TYPE_BFLOAT16, rank, const_cast<void*>(ptr), dims, strides, box, es,
                  CU_TENSOR_MAP_INTERLEAVE_NONE, swz, CU_TENSOR_MAP_L2_PROMOTION_L2_128B, CU_TENSOR_MAP_FLOAT_OOB_FILL_NONE);
  if (r != CUDA_SUCCESS) fprintf(stderr, "cuTensorMapEncodeTiled failed: %d\n", (int)r);
}

struct Op { int type, flags, id, n, quarter, park, item0, items; double t0, t1; };
struct Use { double ready, gate, need, freed; int readers, slot, prev; bool next; };
struct PlanStats { double end, slack, park_slack; int slots, parks; uint32_t own[N_CL]; };

bool plan(const char* const* text, int n_pair, int phase, Params& P, PlanStats* stats = nullptr) {
  constexpr double T_Q = 7900, T_A = XTA, T_U = 25900, T_P = 8400, T_O = 640, T_RUN = 800, T_WIDE = 1300, AHEAD = 3500, PUBLISH = 1500;
  const double margin = 256.0 * ((P.dbg >> 8) & 255);
  static Op op[N_CL][MAX_OPS];
  static Use use[ID_PART];
  int n_op[N_CL], covered[2 * N_TEAM] = {};
  struct Ref { double t; Op* o; int id; };
  static Ref att[N_TILE + 1], dem[N_TILE], prk[MAX_PARK + 1], unp[MAX_PARK + 1], wr[ID_PART];
  auto sort = [](Ref* r, int n) {
    for (int i = 1; i < n; i++)
      for (int j = i; j > 0 && r[j].t < r[j - 1].t; j--) { Ref x = r[j]; r[j] = r[j - 1]; r[j - 1] = x; }
  };
  auto hex = [](char c) { return c <= '9' ? c - '0' : c - 'a' + 10; };
  for (int i = 0; i < n_pair; i++)
    for (const char* s = text[i]; *s; s++)
      for (int h = 0; *s == 'J' && h < 2; h++) {
        if (covered[2 * hex(s[1]) + h]) return false;
        covered[2 * hex(s[1]) + h] = 10 * (s[2 + 2 * h] - '0') + s[3 + 2 * h] - '0';
      }
  for (int c = 0; c < 2 * n_pair; c++) {
    int n = 0, items = 0;
    double t = 0;
    auto add = [&](int type, int flags, int id, int heads, int quarter, int its, double dt) {
      if (n < MAX_OPS) op[c][n] = {type, flags, id, heads, quarter, 0, items, its, t, t + dt};
      n++; items += its; t += dt;
    };
    for (const char* s = text[c >> 1]; *s; s++) {
      const int tm = hex(s[1]) & 15, nj = covered[2 * tm + (c & 1)];
      if (*s == 'N') { add(OP_Q, 0, 0, 0, 0, 10, T_Q); add(OP_A, 0, 0, 0, 0, 32, T_A); }
      if (*s == 'P') add(OP_Q, F_PARK, 0, 0, 0, 10, T_P);
      if (*s == '+' || *s == '-') t += *s == '+' ? 1000 : -1000;
      if (*s == 'U') { if (n == 0 || n > MAX_OPS || op[c][n - 1].type != OP_A) return false; add(OP_A, F_PARK, 0, 0, 0, 33, T_U); }
      if (*s == 'J') { if (nj < TAIL + 6 || nj > kSteps - 11) return false; add(OP_O, P_WIDE, tm * kH, nj, 2 * (c & 1), nj + TAIL, 2 * T_O * nj + T_WIDE); }
    }
    add(OP_O, 0, 0, 0, 0, 0, 0);
    add(OP_END, 0, 0, 0, 0, 0, 0);
    if (n > MAX_OPS || op[c][0].type != OP_Q) return false;
    n_op[c] = n - 1;
    att[c] = {t, &op[c][n - 2], 0};
  }
  for (int i = 0; i < 4 * N_TEAM; i++) dem[i] = {(double)covered[i / 2], nullptr, i};
  sort(att, 2 * n_pair); sort(dem, 4 * N_TEAM);
  for (int i = 0; i < 4 * N_TEAM; i++) {
    Op* f = att[i].o;
    const int nj = covered[dem[i].id / 2];
    f->flags = nj ? P_LD : 0;
    f->id = dem[i].id / 4 * kH + nj / 3; f->quarter = dem[i].id & 3; f->items = f->n = kSteps - nj;
    f[1].t0 = f[1].t1 = f->t1 = f->t0 + T_O * f->n + T_RUN; f[1].item0 += f->n;
  }
  for (int i = 0; i < ID_PART; i++) use[i] = {0, 0, 1e18, 0, 0, 0, 0, false};
  int n_att = 0, n_prk = 0, n_unp = 0;
  auto ready = [&](const Op* o) {
    const int nt = o[1].type;
    return o->t1 + (nt == OP_Q ? 6100 : o[1].n ? ((o[1].flags & P_WIDE) ? 7700 : 3900) : 1500) + PUBLISH;
  };
  for (int c = 0; c < 2 * n_pair; c++)
    for (Op* o = op[c]; o->type != OP_END; o++) {
      if (o->type == OP_A) { att[n_att] = {ready(o), o, 0}; if (++n_att > N_TILE) return false; }
      if (o->type == OP_A && o->flags) { unp[n_unp] = {o->t0 - AHEAD, o, 0}; if (++n_unp > MAX_PARK) return false; }
      if (o->type == OP_Q && o->flags) { prk[n_prk] = {ready(o), o, 0}; if (++n_prk > MAX_PARK) return false; }
      for (int i = 0; o->type == OP_O && i < o->n; i++) {
        const int nw = (o->flags & P_WIDE) ? o->n - TAIL : 0, k = nw ? i : kSteps - o->n + i;
        Use& u = use[o->id / kH * kH + k / 3];
        const double t = o->t0 + T_O * (i + (i < nw ? i : nw));
        if (t - AHEAD < u.need) u.need = t - AHEAD;
        const double f = !nw ? 1e18 : i + FLIGHT < o->items - TAIL || (nw && o[1].type != OP_O) ? t + T_O * (i < nw ? 2 : 1 + TAIL) + PUBLISH : 1e18;
        if (f > u.freed) u.freed = f;
        if (i == 0 || k % 3 == 0) u.readers++;
      }
    }
  if (n_att != N_TILE || n_prk != n_unp) return false;
  for (int i = 0; i < N_TILE; i++) { const int id = (i & 15) * kH + (i >> 4); dem[i] = {use[id].need, nullptr, id}; }
  sort(att, n_att); sort(dem, N_TILE); sort(prk, n_prk); sort(unp, n_unp);
  PlanStats st = {0, 1e18, 1e18, 0, n_prk};
  int n_wr = 0;
  for (int i = 0; i < N_TILE; i++) {
    Op* o = att[i].o;
    o->id = dem[i].id;
    if (!o->flags) o[-1].id = o->id;
    if (dem[i].t - att[i].t < st.slack) st.slack = dem[i].t - att[i].t;
    wr[n_wr++] = {o->t1 - 2 * AHEAD, o, o->id};
  }
  for (int i = 0; i < n_prk; i++) {
    prk[i].o->id = unp[i].o->id;
    prk[i].o->park = unp[i].o->park = i;
    use[N_TILE + i].freed = unp[i].o->t0 + 2 * PUBLISH;
    use[N_TILE + i].readers = 1;
    if (unp[i].t - prk[i].t < st.park_slack) st.park_slack = unp[i].t - prk[i].t;
    wr[n_wr++] = {prk[i].o->t1 - 2 * AHEAD, prk[i].o, N_TILE + i};
  }
  for (int c = 0; c < 2 * n_pair; c++)
    for (int d = 0; d < 2 * n_pair; d++)
      for (Op *f = &op[c][n_op[c] - 1], *o = op[d]; f->n && o->type != OP_END; o++)
        if (o->type == OP_O && (o->flags & P_WIDE) && o->id / kH == f->id / kH && o->quarter / 2 == f->quarter / 2) {
          if (f->t0 - o->t1 > 4096.0 * ((P.dbg >> 16) & 255)) f->flags |= P_PRE;
          const double slack = f->t0 + ((f->flags & P_PRE) ? 0 : (f->n - 5) * T_O) - AHEAD - ready(o);
          if (slack < st.park_slack) st.park_slack = slack;
        }
  constexpr double long_while = 160000;
  for (int c = 0; c < 2 * n_pair; c++)
    for (Op* o = op[c]; o->type != OP_END; o++) {
      if (o->type == OP_O && (o->flags & P_WIDE)) {
        int run = 0, best = 0, end = 0;
        for (int h = 0; 3 * h < o->n; h++) {
          bool last = true;
          for (int d = 0; d < 2 * n_pair; d++)
            for (const Op* e = op[d]; e->type != OP_END; e++) {
              if (e->type != OP_O || e == o || ((e->id ^ o->id) & 256) || e->quarter / 2 != o->quarter / 2) continue;
              const bool wide = e->flags & P_WIDE;
              if (wide ? 3 * h >= e->n : 3 * h + 3 <= kSteps - e->n) continue;
              const double dt = e->t0 + T_O * (wide ? 6 * h : 3 * h - kSteps + e->n) - o->t0 - T_O * 6 * h + (d - c) * 1e-3;
              if (dt > 0 && dt < long_while) last = false;
            }
          run = last ? run + 1 : 0;
          if (run > best) { best = run; end = h + 1; }
        }
        if (3 * end >= o->n) end++;
        o->park = (end - best) | (end / 2) << 5;
      }
      if (o->type != OP_Q) continue;
      bool lw = true, lx = true;
      for (int d = 0; d < 2 * n_pair; d++)
        for (const Op* e = op[d]; e->type != OP_END; e++) {
          const double dt = e->t0 - o->t0 + (d - c) * 1e-3;
          if (e->type != OP_Q || e == o || dt < 0 || dt > long_while) continue;
          if (((e->id ^ o->id) & (256 + 31)) == 0) lw = false;
          if (e->id / kH == o->id / kH) lx = false;
        }
      o->quarter = (lw ? P_LASTW : 0) | (lx ? P_LASTX : 0);
    }
  sort(wr, n_wr);
  int holder[N_TILE];
  for (int i = 0; i < n_wr; i++) {
    int best = -1;
    for (int sl = 0; sl < st.slots; sl++)
      if (use[holder[sl]].freed + margin <= wr[i].t && (best < 0 || use[holder[sl]].freed < use[holder[best]].freed)) best = sl;
    Use& u = use[wr[i].id];
    if (best >= 0) { u.prev = holder[best]; use[u.prev].next = true; wr[i].o->flags |= P_GATE; }
    else if (st.slots == N_TILE) return false;
    else best = st.slots++;
    u.slot = best;
    holder[best] = wr[i].id;
  }
  {
    int pos[N_CL] = {}, flag[ID_PART + 4 * N_TEAM] = {}, seen[ID_PART] = {};
    auto goal = [&](int c) { return op[c][n_op[c] - 1].item0; };
    for (bool moved = true; moved;) {
      moved = false;
      for (int c = 0; c < 2 * n_pair; c++) {
        for (; pos[c] < goal(c); pos[c]++, moved = true) {
          bool ok = true;
          for (const Op* o = op[c]; o->type != OP_END; o++) {
            const int k = pos[c] - o->item0, own = o->type == OP_A ? o->id : N_TILE + (o->park & 127);
            if (k < 0 || k >= o->items) continue;
            if (o->type == OP_O) ok = k >= o->n || flag[o->id + k / 3];
            else if (k == o->items - 1 && (o->flags & P_GATE)) ok = seen[use[own].prev] == use[use[own].prev].readers;
            else if (k == 1 && o->type == OP_A && (o->flags & F_PARK)) ok = flag[N_TILE + o->park];
          }
          if (!ok) break;
          for (const Op* o = op[c]; o->type != OP_END; o++) {
            if (pos[c] == o->item0 + o->items + (o[1].type == OP_Q ? 7 : o[1].item0 == goal(c) ? -1 : 5)) {
              if (o->type == OP_A) flag[o->id] = 1;
              if (o->type == OP_Q && (o->flags & F_PARK)) flag[N_TILE + o->park] = 1;
              if (o->type == OP_O) flag[ID_PART + o->id / kH * 4 + o->quarter] = flag[ID_PART + o->id / kH * 4 + o->quarter + 1] = 1;
            }
            const int k = pos[c] - FLIGHT - o->item0, nw = o->n - TAIL;
            if (k == 1 && o->type == OP_A && (o->flags & F_PARK)) seen[N_TILE + o->park]++;
            if (o->type == OP_O && k >= 0 && k < o->items && (k < nw || k >= o->n) && (k < nw ? k : k - TAIL) % 3 == 2) seen[o->id + (k < nw ? k : k - TAIL) / 3]++;
          }
        }
      }
    }
    for (int c = 0; c < 2 * n_pair; c++) if (pos[c] < goal(c)) return false;
  }
  int n_job = 0, longest = 0;
  for (int i = 0; i < 2 * N_TEAM; i++) if (kH + 1 - covered[i] / 3 > longest) longest = kH + 1 - covered[i] / 3;
  for (int c = 0; c < 2 * n_pair; c++) {
    uint32_t items = 0, cur = 0, pend = 0;
    int n = 0, ev = 0;
    auto item = [&](uint32_t bytes, int count) {
      for (int i = 0; i < count; i++) { if (cur + bytes > RING) cur = 0; cur += bytes; items++; }
    };
    auto event = [&](uint32_t e) { if (ev < MAX_TAB) P.prog[c].ev[ev] = e; ev++; };
    for (const Op* o = op[c];; o++) {
      if (o->type != OP_END && phase && (o->type == OP_O) != (phase == 2)) continue;
      uint32_t cw = o->type | (items % (2 * NBAR)) << 15 | (cur >> 12) << 20 | pend, pw = o->type | o->id << 2 | o->flags;
      const int ps = use[N_TILE + (o->park & 127)].slot;
      pend = 0;
      if (o->type == OP_O) {
        pw |= o->n << 13 | o->quarter << 20 | (uint32_t)o->park << 23;
        if (o->flags & P_WIDE) {
          cw |= o->n << 2 | (o->id / kH * 2 + o->quarter / 2) << 9 | C_WIDE;
          item(SZ_W, o->n - TAIL);
          item(SZ_W2, TAIL);
          item(SZ_W3, TAIL);
          pend = C_PEND;
          for (int i = 0; 3 * i < o->n; i++) event((o->id + i) | E_ON | (use[o->id + i].next ? 0 : E_LAST));
        } else {
          dem[n_job++] = {o->t0 - 1e6 * o->n, nullptr, (int)pw};
          st.own[c] = pw;
          pw = OP_O;
          event(E_DRAW | (items < 16 ? 0 : items - 16));
        }
      } else if (o->type != OP_END) {
        const bool parks = o->type == OP_Q && (o->flags & F_PARK);
        cw |= (parks ? ps : use[o->id].slot) << 2 | (o->flags & F_PARK);
        if (o->flags & F_PARK) pw |= o->park << 13 | ps << 20;
        if (o->type == OP_Q) { item(SZ_Q, 10); pw |= o->quarter; }
        else { item(SZ_KV, 1); if (o->flags & F_PARK) { item(SZ_PARK, 1); event((N_TILE + o->park) | E_ON | (use[N_TILE + o->park].next ? 0 : E_LAST)); } item(SZ_KV, 31); }
        if (parks || o->type == OP_A) pend = C_PEND;
        if (o->flags & P_GATE) event(use[parks ? N_TILE + o->park : o->id].prev | E_ON | E_FREE);
      }
      P.prog[c].c[n] = cw; P.prog[c].p[n++] = pw;
      if (o->type == OP_END) { if (o->t0 > st.end) st.end = o->t0; break; }
    }
    if (ev > MAX_TAB || ev + longest > MAX_EV) return false;
    P.prog[c].n_ev = ev;
    while (n < MAX_OPS) { P.prog[c].c[n] = OP_END; P.prog[c].p[n++] = OP_END; }
    P.first[c] = (uint16_t)(P.prog[c].p[0] & 2047);
  }
  sort(dem, n_job);
  for (int i = 0; i < n_job; i++) P.job[i] = dem[i].id;
  for (int i = 0; i < ID_PART; i++) {
    if (i < N_TILE) P.slot[i] = use[i].slot;
    P.info[i] = (use[i].readers + use[i].next) | (use[i].next ? I_NEXT : 0);
  }
  if (stats) *stats = st;
  return true;
}

const char* const kPrograms[N_CL / 2] = {
  "PNJ06864NNNNN", "PNJ17878NNNNN", "PNJ26464NNNNN", "PNJ34148NNNNNN", "PNJ46262NNNNN", "PNJ58182NNNN",
  "NNJ67371NNNN", "PNNJ76666NNNN", "NUNNNJ84545NN", "NUNNNJ94545NN", "NUNNNNJa5551N", "NNNNNJb5959NN",
  "NNNNNJc5455NN", "PNNNNNJd5353NN", "NNNNNJe5153NN", "NNNNNJf7777N", "PNNNNNNNNN", "PNNNNNNNNN",
  "PNNNNNNNNN", "PNNNNNNNNN", "NNNNNNNNN", "NNNNNNNNN", "NNNNNNNNN", "NNNNNNNNN",
  "NNNNNNNNN", "N-NNNNNNNN", "NUNNNNNNN", "NUNNNNNNN", "NUNNNNNNN", "NUNNNUNNN",
  "NUNNNNNNN", "NUNNNNNNN", "NUUNNNNNN",
};

const char* const* bench_programs() {
  return kPrograms;
}

}

extern "C" void kernel_launch(void* const* d_in, const int* in_sizes, int n_in, void* d_out, int out_size) {
  (void)in_sizes; (void)n_in; (void)out_size;
  static EncodeFn fn = nullptr;
  static int n_clusters = 0;
  if (!fn) {
    cudaDriverEntryPointQueryResult qr;
    void* f = nullptr;
    cudaGetDriverEntryPoint("cuTensorMapEncodeTiled", &f, cudaEnableDefault, &qr);
    fn = (EncodeFn)f;
    cudaFuncSetAttribute(fused_kernel, cudaFuncAttributeMaxDynamicSharedMemorySize, SMEM_BYTES);
    cudaLaunchConfig_t cfg = {};
    cfg.gridDim = dim3(132); cfg.blockDim = dim3(384); cfg.dynamicSmemBytes = SMEM_BYTES;
    cudaLaunchAttribute at[1];
    at[0].id = cudaLaunchAttributeClusterDimension; at[0].val.clusterDim.x = 2; at[0].val.clusterDim.y = 1; at[0].val.clusterDim.z = 1;
    cfg.attrs = at; cfg.numAttrs = 1;
    if (cudaOccupancyMaxActiveClusters(&n_clusters, fused_kernel, &cfg) != cudaSuccess || n_clusters < 1) n_clusters = 1;
    (void)cudaGetLastError();
  }
  static Params P;
  const CUtensorMapSwizzle S128 = CU_TENSOR_MAP_SWIZZLE_128B, S64 = CU_TENSOR_MAP_SWIZZLE_64B;
  for (int blk = 0; blk < 2; blk++) {
    void* const* in = d_in + 5 * blk;
    { const cuuint64_t d[] = {kD, kB * kSq}, s[] = {kD * 2}; const cuuint32_t b[] = {64, 128};
      encode(fn, &P.x[blk], in[0], 2, d, s, b, S128); }
    { const cuuint64_t d[] = {64, 8, 3, (cuuint64_t)kB * kH * kSk / 8}, s[] = {kDh * 2, 128, 8 * kDh * 2}; const cuuint32_t b[] = {64, 8, 3, 4};
      encode(fn, &P.k[blk], in[1], 4, d, s, b, S128);
      encode(fn, &P.v[blk], in[2], 4, d, s, b, S128); }
    { const cuuint64_t d[] = {64, kD, kHD / 64}, s[] = {kHD * 2, 128}; const cuuint32_t b[] = {64, 32, 3};
      encode(fn, &P.wq[blk], in[3], 3, d, s, b, S128); }
    { const cuuint64_t d[] = {32, 2, kHD / 8, 4, kD / 32}, s[] = {kD * 2, 8 * kD * 2, 2 * kD * 2, 64}; const cuuint32_t b[] = {32, 2, 4, 4, 5};
      encode(fn, &P.wo[blk], in[4], 5, d, s, b, S64); }
    { const cuuint64_t d[] = {64, 2, kHD / 8, 4, kD / 64}, s[] = {kD * 2, 8 * kD * 2, 2 * kD * 2, 128};
      const cuuint32_t b3[] = {64, 2, 4, 4, 3}, b2[] = {64, 2, 4, 4, 2};
      encode(fn, &P.wo3[blk], in[4], 5, d, s, b3, S128);
      encode(fn, &P.wo2[blk], in[4], 5, d, s, b2, S128); }
  }
  { const cuuint64_t d[] = {32, kB * kSq, 2 * kD / 32}, s[] = {2 * kD * 2, 64}; const cuuint32_t b[] = {32, 16, 1};
    encode(fn, &P.out, d_out, 3, d, s, b, S64); }

  P.kv[0] = (const char*)d_in[1]; P.kv[1] = (const char*)d_in[6]; P.kv[2] = (const char*)d_in[2]; P.kv[3] = (const char*)d_in[7];
  P.xw[0] = (const char*)d_in[0]; P.xw[1] = (const char*)d_in[3];
  cudaGetSymbolAddress((void**)&P.g, g_scratch);
  P.dbg = DBG_DEFAULT;
  if (n_clusters >= N_CL && plan(bench_programs(), N_CL / 2, 0, P)) {
    fused_kernel<<<2 * N_CL, 384, SMEM_BYTES>>>(P);
  } else {
    const char* text[2 * N_TEAM];
    for (int i = 0; i < 2 * N_TEAM; i++) text[i] = "NNNNNNNN";
    for (int phase = 1; phase <= 2; phase++) {
      plan(text, 2 * N_TEAM, phase, P);
      fused_kernel<<<8 * N_TEAM, 384, SMEM_BYTES>>>(P);
    }
  }
}
```

```cpp
#include <cuda_runtime.h>
#include <cuda_bf16.h>
#include <cuda.h>
#include <cuda/annotated_ptr>
#include <stdint.h>
#include <stdio.h>

namespace {

constexpr int kB = 8, kSq = 256, kD = 640, kH = 32, kSk = 1024, kDh = 192;
constexpr int kHD = kH * kDh;
constexpr uint32_t RING = 224 * 1024;
constexpr uint32_t SZ_KV = 24576;
constexpr uint32_t SZ_Q = 16384 + 24576;
constexpr uint32_t SZ_O = 16384 + 20480;
constexpr uint32_t SZ_W3 = 16384 + 24576, SZ_W2 = 16384 + 16384, SZ_W = SZ_W3 + 16384;
constexpr uint32_t SZ_PARK = 49152;
constexpr uint32_t SZ_OL = SZ_O + 8192;
constexpr int NBAR = 16, FLIGHT = RING / SZ_KV + 1;
constexpr int EARLY = 3;
constexpr int kSteps = kHD / 64;
constexpr int TAIL = 4;
constexpr uint32_t KV_CH = 64, KV_SBO = 3072;
constexpr int SMEM_BYTES = RING + 1024 + 1024;
constexpr int N_TEAM = 16, N_CL = 66, MAX_OPS = 22, MAX_EV = 72, MAX_TAB = 47, N_TILE = N_TEAM * kH, MAX_PARK = 128, ID_PART = N_TILE + MAX_PARK;
enum : uint32_t { OP_END = 0, OP_Q = 1, OP_A = 2, OP_O = 3, F_PARK = 1 << 11,
                  C_WIDE = 1 << 27, C_PEND = 1 << 26, P_GATE = 1 << 12, P_WIDE = 1 << 11, P_LD = 1 << 12, P_PRE = 1 << 22, P_LASTW = 1 << 29, P_LASTX = 1 << 30,
                  I_NEXT = 8, E_ON = 1 << 15, E_FREE = 1 << 14, E_LAST = 1 << 13, E_DRAW = 1 << 12, E_JOB = 1 << 11 };

constexpr uint32_t DBG_DEFAULT = 0x040800;

struct alignas(1024) Scratch {
  unsigned int flag[2047];
  unsigned int ticket;
  uint4 part[N_TEAM * 2 * 2 * 5120];
  uint4 tile[N_TILE * 2 * 3072];
};

struct alignas(64) Params {
  const char* xw[2];
  uint16_t first[80];
  Scratch* g;
  uint32_t dbg;
  CUtensorMap x[2], wq[2], k[2], v[2], wo[2], wo3[2], wo2[2], out;
  struct {
    uint32_t c[MAX_OPS];
    uint32_t p[MAX_OPS];
    uint16_t n_ev, ev[MAX_TAB];
  } prog[N_CL];
  const char* kv[4];
  uint32_t job[N_CL];
  uint16_t slot[N_TILE];
  uint8_t info[ID_PART];
};

__device__ Scratch g_scratch;

template <int TB, int TA = 0>
__device__ __forceinline__ void wgmma_ss_n64(float (&d)[32], uint64_t da, uint64_t db, int scale_d) {
  asm volatile("{\n.reg .pred p;\nsetp.ne.b32 p, %34, 0;\n"
    "wgmma.mma_async.sync.aligned.m64n64k16.f32.bf16.bf16 {%0, %1, %2, %3, %4, %5, %6, %7, %8, %9, %10, %11, %12, %13, %14, %15, %16, %17, %18, %19, %20, %21, %22, %23, %24, %25, %26, %27, %28, %29, %30, %31}, %32, %33, p, 1, 1, %35, %36;\n}\n"
    : "+f"(d[0]), "+f"(d[1]), "+f"(d[2]), "+f"(d[3]), "+f"(d[4]), "+f"(d[5]), "+f"(d[6]), "+f"(d[7]), "+f"(d[8]), "+f"(d[9]), "+f"(d[10]), "+f"(d[11]), "+f"(d[12]), "+f"(d[13]), "+f"(d[14]), "+f"(d[15]), "+f"(d[16]), "+f"(d[17]), "+f"(d[18]), "+f"(d[19]), "+f"(d[20]), "+f"(d[21]), "+f"(d[22]), "+f"(d[23]), "+f"(d[24]), "+f"(d[25]), "+f"(d[26]), "+f"(d[27]), "+f"(d[28]), "+f"(d[29]), "+f"(d[30]), "+f"(d[31])
    : "l"(da), "l"(db), "r"(scale_d), "n"(TA), "n"(TB));
}
template <int TB>
__device__ __forceinline__ void wgmma_rs_n64(float (&d)[32], uint32_t a0, uint32_t a1, uint32_t a2, uint32_t a3, uint64_t db, int scale_d) {
  asm volatile("{\n.reg .pred p;\nsetp.ne.b32 p, %37, 0;\n"
    "wgmma.mma_async.sync.aligned.m64n64k16.f32.bf16.bf16 {%0, %1, %2, %3, %4, %5, %6, %7, %8, %9, %10, %11, %12, %13, %14, %15, %16, %17, %18, %19, %20, %21, %22, %23, %24, %25, %26, %27, %28, %29, %30, %31}, {%32, %33, %34, %35}, %36, p, 1, 1, %38;\n}\n"
    : "+f"(d[0]), "+f"(d[1]), "+f"(d[2]), "+f"(d[3]), "+f"(d[4]), "+f"(d[5]), "+f"(d[6]), "+f"(d[7]), "+f"(d[8]), "+f"(d[9]), "+f"(d[10]), "+f"(d[11]), "+f"(d[12]), "+f"(d[13]), "+f"(d[14]), "+f"(d[15]), "+f"(d[16]), "+f"(d[17]), "+f"(d[18]), "+f"(d[19]), "+f"(d[20]), "+f"(d[21]), "+f"(d[22]), "+f"(d[23]), "+f"(d[24]), "+f"(d[25]), "+f"(d[26]), "+f"(d[27]), "+f"(d[28]), "+f"(d[29]), "+f"(d[30]), "+f"(d[31])
    : "r"(a0), "r"(a1), "r"(a2), "r"(a3), "l"(db), "r"(scale_d), "n"(TB));
}
template <int TB, int TA = 0>
__device__ __forceinline__ void wgmma_ss_n128(float (&d)[64], uint64_t da, uint64_t db, int scale_d) {
  asm volatile("{\n.reg .pred p;\nsetp.ne.b32 p, %66, 0;\n"
    "wgmma.mma_async.sync.aligned.m64n128k16.f32.bf16.bf16 {%0, %1, %2, %3, %4, %5, %6, %7, %8, %9, %10, %11, %12, %13, %14, %15, %16, %17, %18, %19, %20, %21, %22, %23, %24, %25, %26, %27, %28, %29, %30, %31, %32, %33, %34, %35, %36, %37, %38, %39, %40, %41, %42, %43, %44, %45, %46, %47, %48, %49, %50, %51, %52, %53, %54, %55, %56, %57, %58, %59, %60, %61, %62, %63}, %64, %65, p, 1, 1, %67, %68;\n}\n"
    : "+f"(d[0]), "+f"(d[1]), "+f"(d[2]), "+f"(d[3]), "+f"(d[4]), "+f"(d[5]), "+f"(d[6]), "+f"(d[7]), "+f"(d[8]), "+f"(d[9]), "+f"(d[10]), "+f"(d[11]), "+f"(d[12]), "+f"(d[13]), "+f"(d[14]), "+f"(d[15]), "+f"(d[16]), "+f"(d[17]), "+f"(d[18]), "+f"(d[19]), "+f"(d[20]), "+f"(d[21]), "+f"(d[22]), "+f"(d[23]), "+f"(d[24]), "+f"(d[25]), "+f"(d[26]), "+f"(d[27]), "+f"(d[28]), "+f"(d[29]), "+f"(d[30]), "+f"(d[31]), "+f"(d[32]), "+f"(d[33]), "+f"(d[34]), "+f"(d[35]), "+f"(d[36]), "+f"(d[37]), "+f"(d[38]), "+f"(d[39]), "+f"(d[40]), "+f"(d[41]), "+f"(d[42]), "+f"(d[43]), "+f"(d[44]), "+f"(d[45]), "+f"(d[46]), "+f"(d[47]), "+f"(d[48]), "+f"(d[49]), "+f"(d[50]), "+f"(d[51]), "+f"(d[52]), "+f"(d[53]), "+f"(d[54]), "+f"(d[55]), "+f"(d[56]), "+f"(d[57]), "+f"(d[58]), "+f"(d[59]), "+f"(d[60]), "+f"(d[61]), "+f"(d[62]), "+f"(d[63])
    : "l"(da), "l"(db), "r"(scale_d), "n"(TA), "n"(TB));
}
template <int TB>
__device__ __forceinline__ void wgmma_rs_n128(float (&d)[64], uint32_t a0, uint32_t a1, uint32_t a2, uint32_t a3, uint64_t db, int scale_d) {
  asm volatile("{\n.reg .pred p;\nsetp.ne.b32 p, %69, 0;\n"
    "wgmma.mma_async.sync.aligned.m64n128k16.f32.bf16.bf16 {%0, %1, %2, %3, %4, %5, %6, %7, %8, %9, %10, %11, %12, %13, %14, %15, %16, %17, %18, %19, %20, %21, %22, %23, %24, %25, %26, %27, %28, %29, %30, %31, %32, %33, %34, %35, %36, %37, %38, %39, %40, %41, %42, %43, %44, %45, %46, %47, %48, %49, %50, %51, %52, %53, %54, %55, %56, %57, %58, %59, %60, %61, %62, %63}, {%64, %65, %66, %67}, %68, p, 1, 1, %70;\n}\n"
    : "+f"(d[0]), "+f"(d[1]), "+f"(d[2]), "+f"(d[3]), "+f"(d[4]), "+f"(d[5]), "+f"(d[6]), "+f"(d[7]), "+f"(d[8]), "+f"(d[9]), "+f"(d[10]), "+f"(d[11]), "+f"(d[12]), "+f"(d[13]), "+f"(d[14]), "+f"(d[15]), "+f"(d[16]), "+f"(d[17]), "+f"(d[18]), "+f"(d[19]), "+f"(d[20]), "+f"(d[21]), "+f"(d[22]), "+f"(d[23]), "+f"(d[24]), "+f"(d[25]), "+f"(d[26]), "+f"(d[27]), "+f"(d[28]), "+f"(d[29]), "+f"(d[30]), "+f"(d[31]), "+f"(d[32]), "+f"(d[33]), "+f"(d[34]), "+f"(d[35]), "+f"(d[36]), "+f"(d[37]), "+f"(d[38]), "+f"(d[39]), "+f"(d[40]), "+f"(d[41]), "+f"(d[42]), "+f"(d[43]), "+f"(d[44]), "+f"(d[45]), "+f"(d[46]), "+f"(d[47]), "+f"(d[48]), "+f"(d[49]), "+f"(d[50]), "+f"(d[51]), "+f"(d[52]), "+f"(d[53]), "+f"(d[54]), "+f"(d[55]), "+f"(d[56]), "+f"(d[57]), "+f"(d[58]), "+f"(d[59]), "+f"(d[60]), "+f"(d[61]), "+f"(d[62]), "+f"(d[63])
    : "r"(a0), "r"(a1), "r"(a2), "r"(a3), "l"(db), "r"(scale_d), "n"(TB));
}
template <int TB, int TA = 0>
__device__ __forceinline__ void wgmma_ss_n160(float (&d)[80], uint64_t da, uint64_t db, int scale_d) {
  asm volatile("{\n.reg .pred p;\nsetp.ne.b32 p, %82, 0;\n"
    "wgmma.mma_async.sync.aligned.m64n160k16.f32.bf16.bf16 {%0, %1, %2, %3, %4, %5, %6, %7, %8, %9, %10, %11, %12, %13, %14, %15, %16, %17, %18, %19, %20, %21, %22, %23, %24, %25, %26, %27, %28, %29, %30, %31, %32, %33, %34, %35, %36, %37, %38, %39, %40, %41, %42, %43, %44, %45, %46, %47, %48, %49, %50, %51, %52, %53, %54, %55, %56, %57, %58, %59, %60, %61, %62, %63, %64, %65, %66, %67, %68, %69, %70, %71, %72, %73, %74, %75, %76, %77, %78, %79}, %80, %81, p, 1, 1, %83, %84;\n}\n"
    : "+f"(d[0]), "+f"(d[1]), "+f"(d[2]), "+f"(d[3]), "+f"(d[4]), "+f"(d[5]), "+f"(d[6]), "+f"(d[7]), "+f"(d[8]), "+f"(d[9]), "+f"(d[10]), "+f"(d[11]), "+f"(d[12]), "+f"(d[13]), "+f"(d[14]), "+f"(d[15]), "+f"(d[16]), "+f"(d[17]), "+f"(d[18]), "+f"(d[19]), "+f"(d[20]), "+f"(d[21]), "+f"(d[22]), "+f"(d[23]), "+f"(d[24]), "+f"(d[25]), "+f"(d[26]), "+f"(d[27]), "+f"(d[28]), "+f"(d[29]), "+f"(d[30]), "+f"(d[31]), "+f"(d[32]), "+f"(d[33]), "+f"(d[34]), "+f"(d[35]), "+f"(d[36]), "+f"(d[37]), "+f"(d[38]), "+f"(d[39]), "+f"(d[40]), "+f"(d[41]), "+f"(d[42]), "+f"(d[43]), "+f"(d[44]), "+f"(d[45]), "+f"(d[46]), "+f"(d[47]), "+f"(d[48]), "+f"(d[49]), "+f"(d[50]), "+f"(d[51]), "+f"(d[52]), "+f"(d[53]), "+f"(d[54]), "+f"(d[55]), "+f"(d[56]), "+f"(d[57]), "+f"(d[58]), "+f"(d[59]), "+f"(d[60]), "+f"(d[61]), "+f"(d[62]), "+f"(d[63]), "+f"(d[64]), "+f"(d[65]), "+f"(d[66]), "+f"(d[67]), "+f"(d[68]), "+f"(d[69]), "+f"(d[70]), "+f"(d[71]), "+f"(d[72]), "+f"(d[73]), "+f"(d[74]), "+f"(d[75]), "+f"(d[76]), "+f"(d[77]), "+f"(d[78]), "+f"(d[79])
    : "l"(da), "l"(db), "r"(scale_d), "n"(TA), "n"(TB));
}
template <int TB>
__device__ __forceinline__ void wgmma_rs_n160(float (&d)[80], uint32_t a0, uint32_t a1, uint32_t a2, uint32_t a3, uint64_t db, int scale_d) {
  asm volatile("{\n.reg .pred p;\nsetp.ne.b32 p, %85, 0;\n"
    "wgmma.mma_async.sync.aligned.m64n160k16.f32.bf16.bf16 {%0, %1, %2, %3, %4, %5, %6, %7, %8, %9, %10, %11, %12, %13, %14, %15, %16, %17, %18, %19, %20, %21, %22, %23, %24, %25, %26, %27, %28, %29, %30, %31, %32, %33, %34, %35, %36, %37, %38, %39, %40, %41, %42, %43, %44, %45, %46, %47, %48, %49, %50, %51, %52, %53, %54, %55, %56, %57, %58, %59, %60, %61, %62, %63, %64, %65, %66, %67, %68, %69, %70, %71, %72, %73, %74, %75, %76, %77, %78, %79}, {%80, %81, %82, %83}, %84, p, 1, 1, %86;\n}\n"
    : "+f"(d[0]), "+f"(d[1]), "+f"(d[2]), "+f"(d[3]), "+f"(d[4]), "+f"(d[5]), "+f"(d[6]), "+f"(d[7]), "+f"(d[8]), "+f"(d[9]), "+f"(d[10]), "+f"(d[11]), "+f"(d[12]), "+f"(d[13]), "+f"(d[14]), "+f"(d[15]), "+f"(d[16]), "+f"(d[17]), "+f"(d[18]), "+f"(d[19]), "+f"(d[20]), "+f"(d[21]), "+f"(d[22]), "+f"(d[23]), "+f"(d[24]), "+f"(d[25]), "+f"(d[26]), "+f"(d[27]), "+f"(d[28]), "+f"(d[29]), "+f"(d[30]), "+f"(d[31]), "+f"(d[32]), "+f"(d[33]), "+f"(d[34]), "+f"(d[35]), "+f"(d[36]), "+f"(d[37]), "+f"(d[38]), "+f"(d[39]), "+f"(d[40]), "+f"(d[41]), "+f"(d[42]), "+f"(d[43]), "+f"(d[44]), "+f"(d[45]), "+f"(d[46]), "+f"(d[47]), "+f"(d[48]), "+f"(d[49]), "+f"(d[50]), "+f"(d[51]), "+f"(d[52]), "+f"(d[53]), "+f"(d[54]), "+f"(d[55]), "+f"(d[56]), "+f"(d[57]), "+f"(d[58]), "+f"(d[59]), "+f"(d[60]), "+f"(d[61]), "+f"(d[62]), "+f"(d[63]), "+f"(d[64]), "+f"(d[65]), "+f"(d[66]), "+f"(d[67]), "+f"(d[68]), "+f"(d[69]), "+f"(d[70]), "+f"(d[71]), "+f"(d[72]), "+f"(d[73]), "+f"(d[74]), "+f"(d[75]), "+f"(d[76]), "+f"(d[77]), "+f"(d[78]), "+f"(d[79])
    : "r"(a0), "r"(a1), "r"(a2), "r"(a3), "l"(db), "r"(scale_d), "n"(TB));
}
template <int TB, int TA = 0>
__device__ __forceinline__ void wgmma_ss_n192(float (&d)[96], uint64_t da, uint64_t db, int scale_d) {
  asm volatile("{\n.reg .pred p;\nsetp.ne.b32 p, %98, 0;\n"
    "wgmma.mma_async.sync.aligned.m64n192k16.f32.bf16.bf16 {%0, %1, %2, %3, %4, %5, %6, %7, %8, %9, %10, %11, %12, %13, %14, %15, %16, %17, %18, %19, %20, %21, %22, %23, %24, %25, %26, %27, %28, %29, %30, %31, %32, %33, %34, %35, %36, %37, %38, %39, %40, %41, %42, %43, %44, %45, %46, %47, %48, %49, %50, %51, %52, %53, %54, %55, %56, %57, %58, %59, %60, %61, %62, %63, %64, %65, %66, %67, %68, %69, %70, %71, %72, %73, %74, %75, %76, %77, %78, %79, %80, %81, %82, %83, %84, %85, %86, %87, %88, %89, %90, %91, %92, %93, %94, %95}, %96, %97, p, 1, 1, %99, %100;\n}\n"
    : "+f"(d[0]), "+f"(d[1]), "+f"(d[2]), "+f"(d[3]), "+f"(d[4]), "+f"(d[5]), "+f"(d[6]), "+f"(d[7]), "+f"(d[8]), "+f"(d[9]), "+f"(d[10]), "+f"(d[11]), "+f"(d[12]), "+f"(d[13]), "+f"(d[14]), "+f"(d[15]), "+f"(d[16]), "+f"(d[17]), "+f"(d[18]), "+f"(d[19]), "+f"(d[20]), "+f"(d[21]), "+f"(d[22]), "+f"(d[23]), "+f"(d[24]), "+f"(d[25]), "+f"(d[26]), "+f"(d[27]), "+f"(d[28]), "+f"(d[29]), "+f"(d[30]), "+f"(d[31]), "+f"(d[32]), "+f"(d[33]), "+f"(d[34]), "+f"(d[35]), "+f"(d[36]), "+f"(d[37]), "+f"(d[38]), "+f"(d[39]), "+f"(d[40]), "+f"(d[41]), "+f"(d[42]), "+f"(d[43]), "+f"(d[44]), "+f"(d[45]), "+f"(d[46]), "+f"(d[47]), "+f"(d[48]), "+f"(d[49]), "+f"(d[50]), "+f"(d[51]), "+f"(d[52]), "+f"(d[53]), "+f"(d[54]), "+f"(d[55]), "+f"(d[56]), "+f"(d[57]), "+f"(d[58]), "+f"(d[59]), "+f"(d[60]), "+f"(d[61]), "+f"(d[62]), "+f"(d[63]), "+f"(d[64]), "+f"(d[65]), "+f"(d[66]), "+f"(d[67]), "+f"(d[68]), "+f"(d[69]), "+f"(d[70]), "+f"(d[71]), "+f"(d[72]), "+f"(d[73]), "+f"(d[74]), "+f"(d[75]), "+f"(d[76]), "+f"(d[77]), "+f"(d[78]), "+f"(d[79]), "+f"(d[80]), "+f"(d[81]), "+f"(d[82]), "+f"(d[83]), "+f"(d[84]), "+f"(d[85]), "+f"(d[86]), "+f"(d[87]), "+f"(d[88]), "+f"(d[89]), "+f"(d[90]), "+f"(d[91]), "+f"(d[92]), "+f"(d[93]), "+f"(d[94]), "+f"(d[95])
    : "l"(da), "l"(db), "r"(scale_d), "n"(TA), "n"(TB));
}
template <int TB>
__device__ __forceinline__ void wgmma_rs_n192(float (&d)[96], uint32_t a0, uint32_t a1, uint32_t a2, uint32_t a3, uint64_t db, int scale_d) {
  asm volatile("{\n.reg .pred p;\nsetp.ne.b32 p, %101, 0;\n"
    "wgmma.mma_async.sync.aligned.m64n192k16.f32.bf16.bf16 {%0, %1, %2, %3, %4, %5, %6, %7, %8, %9, %10, %11, %12, %13, %14, %15, %16, %17, %18, %19, %20, %21, %22, %23, %24, %25, %26, %27, %28, %29, %30, %31, %32, %33, %34, %35, %36, %37, %38, %39, %40, %41, %42, %43, %44, %45, %46, %47, %48, %49, %50, %51, %52, %53, %54, %55, %56, %57, %58, %59, %60, %61, %62, %63, %64, %65, %66, %67, %68, %69, %70, %71, %72, %73, %74, %75, %76, %77, %78, %79, %80, %81, %82, %83, %84, %85, %86, %87, %88, %89, %90, %91, %92, %93, %94, %95}, {%96, %97, %98, %99}, %100, p, 1, 1, %102;\n}\n"
    : "+f"(d[0]), "+f"(d[1]), "+f"(d[2]), "+f"(d[3]), "+f"(d[4]), "+f"(d[5]), "+f"(d[6]), "+f"(d[7]), "+f"(d[8]), "+f"(d[9]), "+f"(d[10]), "+f"(d[11]), "+f"(d[12]), "+f"(d[13]), "+f"(d[14]), "+f"(d[15]), "+f"(d[16]), "+f"(d[17]), "+f"(d[18]), "+f"(d[19]), "+f"(d[20]), "+f"(d[21]), "+f"(d[22]), "+f"(d[23]), "+f"(d[24]), "+f"(d[25]), "+f"(d[26]), "+f"(d[27]), "+f"(d[28]), "+f"(d[29]), "+f"(d[30]), "+f"(d[31]), "+f"(d[32]), "+f"(d[33]), "+f"(d[34]), "+f"(d[35]), "+f"(d[36]), "+f"(d[37]), "+f"(d[38]), "+f"(d[39]), "+f"(d[40]), "+f"(d[41]), "+f"(d[42]), "+f"(d[43]), "+f"(d[44]), "+f"(d[45]), "+f"(d[46]), "+f"(d[47]), "+f"(d[48]), "+f"(d[49]), "+f"(d[50]), "+f"(d[51]), "+f"(d[52]), "+f"(d[53]), "+f"(d[54]), "+f"(d[55]), "+f"(d[56]), "+f"(d[57]), "+f"(d[58]), "+f"(d[59]), "+f"(d[60]), "+f"(d[61]), "+f"(d[62]), "+f"(d[63]), "+f"(d[64]), "+f"(d[65]), "+f"(d[66]), "+f"(d[67]), "+f"(d[68]), "+f"(d[69]), "+f"(d[70]), "+f"(d[71]), "+f"(d[72]), "+f"(d[73]), "+f"(d[74]), "+f"(d[75]), "+f"(d[76]), "+f"(d[77]), "+f"(d[78]), "+f"(d[79]), "+f"(d[80]), "+f"(d[81]), "+f"(d[82]), "+f"(d[83]), "+f"(d[84]), "+f"(d[85]), "+f"(d[86]), "+f"(d[87]), "+f"(d[88]), "+f"(d[89]), "+f"(d[90]), "+f"(d[91]), "+f"(d[92]), "+f"(d[93]), "+f"(d[94]), "+f"(d[95])
    : "r"(a0), "r"(a1), "r"(a2), "r"(a3), "l"(db), "r"(scale_d), "n"(TB));
}

__device__ __forceinline__ uint32_t smem_u32(const void* p) { return (uint32_t)__cvta_generic_to_shared(p); }
__device__ __forceinline__ void wg_fence() { asm volatile("wgmma.fence.sync.aligned;" ::: "memory"); }
__device__ __forceinline__ void wg_commit() { asm volatile("wgmma.commit_group.sync.aligned;" ::: "memory"); }
template <int N> __device__ __forceinline__ void wg_wait() { asm volatile("wgmma.wait_group.sync.aligned %0;" ::"n"(N) : "memory"); }
__device__ __forceinline__ void sched_fence(uint32_t& keep, bool never) {
  asm volatile("{\n.reg .pred p;\nsetp.ne.b32 p, %1, 0;\n@p mov.u32 %0, %%clock;\n}\n" : "+r"(keep) : "r"((int)never) : "memory");
}
template <int N> __device__ __forceinline__ void fence_regs(float (&r)[N]) {
#pragma unroll
  for (int i = 0; i < N; i++) asm volatile("" : "+f"(r[i])::"memory");
}
template <int N> __device__ __forceinline__ void undefine(float (&r)[N]) {
#pragma unroll
  for (int i = 0; i < N; i++) asm volatile("" : "=f"(r[i]));
}
template <int N> __device__ __forceinline__ void fence_regs(uint32_t (&r)[N]) {
#pragma unroll
  for (int i = 0; i < N; i++) asm volatile("" : "+r"(r[i])::"memory");
}
__device__ __forceinline__ uint64_t mk_desc(uint32_t a16, uint32_t lbo, uint32_t sbo, uint32_t swz) {
  uint64_t d;
  asm("mov.b64 %0, {%1, %2};" : "=l"(d) : "r"(a16 + ((lbo >> 4) << 16)), "r"((sbo >> 4) | (swz << 30)));
  return d;
}
__device__ __forceinline__ void mbar_init(uint32_t bar, uint32_t cnt) {
  asm volatile("mbarrier.init.shared::cta.b64 [%0], %1;" ::"r"(bar), "r"(cnt) : "memory");
}
__device__ __forceinline__ void mbar_expect(uint32_t bar, uint32_t tx) {
  asm volatile("mbarrier.arrive.expect_tx.shared::cta.b64 _, [%0], %1;" ::"r"(bar), "r"(tx) : "memory");
}
__device__ __forceinline__ bool mbar_test(uint32_t bar, uint32_t ph) {
  uint32_t ok;
  asm volatile("{\n.reg .pred p;\nmbarrier.test_wait.parity.shared::cta.b64 p, [%1], %2;\nselp.u32 %0, 1, 0, p;\n}\n"
               : "=r"(ok) : "r"(bar), "r"(ph) : "memory");
  return ok;
}
__device__ __forceinline__ bool mbar_try(uint32_t bar, uint32_t ph, uint32_t ns) {
  uint32_t ok;
  asm volatile("{\n.reg .pred p;\nmbarrier.try_wait.parity.shared::cta.b64 p, [%1], %2, %3;\nselp.u32 %0, 1, 0, p;\n}\n"
               : "=r"(ok) : "r"(bar), "r"(ph), "r"(ns) : "memory");
  return ok;
}
__device__ __forceinline__ void mbar_wait(uint32_t bar, uint32_t ph) {
  asm volatile("{\n.reg .pred p;\n.reg .u32 n;\nmov.u32 n, 0;\n"
               "LOOP:\nmbarrier.try_wait.parity.shared::cta.b64 p, [%0], %1;\n@p bra DONE;\n"
               "add.u32 n, n, 1;\nsetp.lt.u32 p, n, 0x1000000;\n@p bra LOOP;\ntrap;\n"
               "DONE:\n}\n" ::"r"(bar), "r"(ph) : "memory");
}
__device__ __forceinline__ void mbar_wait_long(uint32_t bar) {
  asm volatile("{\n.reg .pred p;\n.reg .u32 n;\nmov.u32 n, 0;\n"
               "LOOP:\nmbarrier.try_wait.parity.shared::cta.b64 p, [%0], 0, 20000;\n@p bra DONE;\n"
               "add.u32 n, n, 1;\nsetp.lt.u32 p, n, 0x100000;\n@p bra LOOP;\ntrap;\n"
               "DONE:\n}\n" ::"r"(bar) : "memory");
}
__device__ __forceinline__ void mbar_arrive_cluster_if(bool on, uint32_t addr) {
  asm volatile("{\n.reg .pred p;\nsetp.ne.b32 p, %1, 0;\n@p mbarrier.arrive.shared::cluster.b64 _, [%0];\n}\n" ::"r"(addr), "r"((int)on) : "memory");
}
__device__ __forceinline__ void mbar_arrive_cluster_n(uint32_t n, uint32_t addr) {
  asm volatile("{\n.reg .pred p;\nsetp.ne.b32 p, %1, 0;\n@p mbarrier.arrive.shared::cluster.b64 _, [%0], %1;\n}\n" ::"r"(addr), "r"(n) : "memory");
}
__device__ __forceinline__ void tma2d(uint32_t dst, const CUtensorMap* m, uint32_t bar, int c0, int c1) {
  asm volatile("cp.async.bulk.tensor.2d.shared::cluster.global.mbarrier::complete_tx::bytes [%0], [%1, {%3, %4}], [%2];"
               ::"r"(dst), "l"(m), "r"(bar), "r"(c0), "r"(c1) : "memory");
}
__device__ __forceinline__ void tma3d(uint32_t dst, const CUtensorMap* m, uint32_t bar, int c0, int c1, int c2) {
  asm volatile("cp.async.bulk.tensor.3d.shared::cluster.global.mbarrier::complete_tx::bytes [%0], [%1, {%3, %4, %5}], [%2];"
               ::"r"(dst), "l"(m), "r"(bar), "r"(c0), "r"(c1), "r"(c2) : "memory");
}
__device__ __forceinline__ void tma2d_hint(uint32_t dst, const CUtensorMap* m, uint32_t bar, int c0, int c1, uint64_t pol) {
  asm volatile("cp.async.bulk.tensor.2d.shared::cluster.global.mbarrier::complete_tx::bytes.L2::cache_hint [%0], [%1, {%3, %4}], [%2], %5;"
               ::"r"(dst), "l"(m), "r"(bar), "r"(c0), "r"(c1), "l"(pol) : "memory");
}
__device__ __forceinline__ void tma3d_mc_hint(uint32_t dst, const CUtensorMap* m, uint32_t bar, int c1, int c2, uint64_t pol) {
  asm volatile("cp.async.bulk.tensor.3d.shared::cluster.global.mbarrier::complete_tx::bytes.multicast::cluster.L2::cache_hint"
               " [%0], [%1, {%3, %4, %5}], [%2], %6, %7;"
               ::"r"(dst), "l"(m), "r"(bar), "r"(0), "r"(c1), "r"(c2), "h"((uint16_t)3), "l"(pol) : "memory");
}
__device__ __forceinline__ void tma5d_mc_hint(uint32_t dst, const CUtensorMap* m, uint32_t bar, int c2, int c4, uint64_t pol) {
  asm volatile("cp.async.bulk.tensor.5d.shared::cluster.global.mbarrier::complete_tx::bytes.multicast::cluster.L2::cache_hint"
               " [%0], [%1, {%3, %3, %4, %3, %5}], [%2], %6, %7;"
               ::"r"(dst), "l"(m), "r"(bar), "r"(0), "r"(c2), "r"(c4), "h"((uint16_t)3), "l"(pol) : "memory");
}
__device__ __forceinline__ void tma3d_store(const CUtensorMap* m, uint32_t src, int c0, int c1, int c2) {
  asm volatile("cp.async.bulk.tensor.3d.global.shared::cta.bulk_group [%0, {%2, %3, %4}], [%1];"
               ::"l"(m), "r"(src), "r"(c0), "r"(c1), "r"(c2) : "memory");
}
__device__ __forceinline__ void bar_sync(int id, int n) { asm volatile("bar.sync %0, %1;" ::"r"(id), "r"(n) : "memory"); }
__device__ __forceinline__ uint32_t pack_bf16(float lo, float hi) {
  uint32_t r;
  asm("cvt.rn.bf16x2.f32 %0, %1, %2;" : "=r"(r) : "f"(hi), "f"(lo));
  return r;
}
__device__ __forceinline__ float ex2(float x) {
  float y;
  asm("ex2.approx.ftz.f32 %0, %1;" : "=f"(y) : "f"(x));
  return y;
}
__device__ __forceinline__ float rcp(float x) {
  float y;
  asm("rcp.approx.ftz.f32 %0, %1;" : "=f"(y) : "f"(x));
  return y;
}
__device__ __forceinline__ void stsm4(uint32_t addr, uint32_t a, uint32_t b, uint32_t c, uint32_t d) {
  asm volatile("stmatrix.sync.aligned.m8n8.x4.shared.b16 [%0], {%1, %2, %3, %4};" ::"r"(addr), "r"(a), "r"(b), "r"(c), "r"(d) : "memory");
}

__device__ __forceinline__ void tma4d_mc_hint(uint32_t dst, const CUtensorMap* m, uint32_t bar, int c3, uint64_t pol) {
  asm volatile("cp.async.bulk.tensor.4d.shared::cluster.global.mbarrier::complete_tx::bytes.multicast::cluster.L2::cache_hint"
               " [%0], [%1, {%3, %3, %3, %4}], [%2], %5, %6;"
               ::"r"(dst), "l"(m), "r"(bar), "r"(0), "r"(c3), "h"((uint16_t)3), "l"(pol) : "memory");
}
__device__ __forceinline__ void bulk_load_hint(uint32_t dst, const void* src, uint32_t bytes, uint32_t bar, uint64_t pol) {
  asm volatile("cp.async.bulk.shared::cluster.global.mbarrier::complete_tx::bytes.L2::cache_hint [%0], [%1], %2, [%3], %4;"
               ::"r"(dst), "l"(src), "r"(bytes), "r"(bar), "l"(pol) : "memory");
}
__device__ __forceinline__ void stg2_if(bool on, void* p, uint32_t a, uint32_t b, uint32_t c, uint32_t d, uint32_t e, uint32_t f,
                                        uint32_t g, uint32_t h, uint64_t pol) {
  asm volatile("{\n.reg .pred p;\nsetp.ne.b32 p, %10, 0;\n"
               "@p st.global.L2::cache_hint.v4.b32 [%0], {%1, %2, %3, %4}, %9;\n"
               "@p st.global.L2::cache_hint.v4.b32 [%0 + 512], {%5, %6, %7, %8}, %9;\n}\n"
               ::"l"(p), "r"(a), "r"(b), "r"(c), "r"(d), "r"(e), "r"(f), "r"(g), "r"(h), "l"(pol), "r"((int)on) : "memory");
}
__device__ __forceinline__ uint64_t evict_first() {
  uint64_t p;
  asm("createpolicy.fractional.L2::evict_first.b64 %0, 1.0;" : "=l"(p));
  return p;
}
__device__ __forceinline__ uint64_t no_hint() {
  uint64_t p;
  asm("createpolicy.cvt.L2.b64 %0, %1;" : "=l"(p) : "l"(static_cast<uint64_t>(cuda::access_property{})));
  return p;
}
__device__ __forceinline__ bool elect() {
  uint32_t ok;
  asm volatile("{\n.reg .pred p;\nelect.sync _|p, 0xffffffff;\nselp.u32 %0, 1, 0, p;\n}\n" : "=r"(ok));
  return ok;
}
__device__ __forceinline__ void mbar_arrive(uint32_t bar) {
  asm volatile("mbarrier.arrive.shared::cta.b64 _, [%0];" ::"r"(bar) : "memory");
}
__device__ __forceinline__ void mbar_arrive_if(bool on, uint32_t bar) {
  asm volatile("{\n.reg .pred p;\nsetp.ne.b32 p, %1, 0;\n@p mbarrier.arrive.shared::cta.b64 _, [%0];\n}\n" ::"r"(bar), "r"((int)on) : "memory");
}
__device__ __forceinline__ void lds2_if(bool on, uint32_t p, uint32_t (&t)[8]) {
  asm volatile("{\n.reg .pred p;\nsetp.ne.b32 p, %9, 0;\n@p ld.shared.v4.b32 {%0, %1, %2, %3}, [%8];\n@p ld.shared.v4.b32 {%4, %5, %6, %7}, [%8 + 512];\n}\n"
               : "+r"(t[0]), "+r"(t[1]), "+r"(t[2]), "+r"(t[3]), "+r"(t[4]), "+r"(t[5]), "+r"(t[6]), "+r"(t[7]) : "r"(p), "r"((int)on) : "memory");
}
__device__ __forceinline__ void lds128(uint32_t p, uint32_t& a, uint32_t& b, uint32_t& c, uint32_t& d) {
  asm volatile("ld.shared.v4.b32 {%0, %1, %2, %3}, [%4];" : "=r"(a), "=r"(b), "=r"(c), "=r"(d) : "r"(p) : "memory");
}
template <class T> __device__ __forceinline__ T* ptr_add(T* base, uint32_t bytes) {
  T* r;
  asm("{\n.reg .u32 lo, hi;\nmov.b64 {lo, hi}, %1;\nadd.cc.u32 lo, lo, %2;\naddc.u32 hi, hi, 0;\nmov.b64 %0, {lo, hi};\n}\n" : "=l"(r) : "l"(base), "r"(bytes));
  return r;
}
__device__ __forceinline__ uint32_t lds32(uint32_t p) {
  uint32_t v;
  asm volatile("ld.volatile.shared.u32 %0, [%1];" : "=r"(v) : "r"(p) : "memory");
  return v;
}
__device__ __forceinline__ uint32_t flag_get(const unsigned int* p) {
  uint32_t v;
  asm volatile("ld.acquire.gpu.global.u32 %0, [%1];" : "=r"(v) : "l"(p) : "memory");
  return v;
}
__device__ __forceinline__ uint32_t wait_word(uint32_t p, uint32_t target) {
  uint32_t v;
  asm volatile("{\n.reg .pred p;\n.reg .u32 n;\nmov.u32 n, 0;\n"
               "LOOP:\nld.acquire.cta.shared.u32 %0, [%1];\nsetp.ge.u32 p, %0, %2;\n@p bra DONE;\n"
               "nanosleep.u32 %3;\nadd.u32 n, n, 1;\nsetp.lt.u32 p, n, 0x400000;\n@p bra LOOP;\ntrap;\n"
               "DONE:\n}\n" : "=r"(v) : "r"(p), "r"(target), "n"(400) : "memory");
  return v;
}
__device__ __forceinline__ void flag_set(unsigned int* p, uint32_t v) {
  asm volatile("st.release.gpu.global.u32 [%0], %1;" ::"l"(p), "r"(v) : "memory");
}
__device__ __forceinline__ void flag_dec(unsigned int* p) {
  asm volatile("red.relaxed.gpu.global.add.u32 [%0], 0xffffffff;" ::"l"(p) : "memory");
}

struct Cursor {
  uint32_t n;
  __device__ __forceinline__ uint32_t off() const { return n & (8 * NBAR - 8); }
  __device__ __forceinline__ uint32_t ph() const { return (n / (8 * NBAR)) & 1; }
  __device__ __forceinline__ void next() { n += 8; }
};

constexpr float kScaleLog2 = 0.07216878364870322f * 1.4426950408889634f;
constexpr float kSumLimit = 1048576.0f;

__global__ void __cluster_dims__(2, 1, 1) __launch_bounds__(384, 1)
fused_kernel(const __grid_constant__ Params P) {
  extern __shared__ uint8_t smem_raw[];
  const uint32_t sbase = (smem_u32(smem_raw) + 1023) & ~1023u;
  const uint32_t full0 = sbase + RING, empty0 = full0 + 8 * NBAR, odone0 = empty0 + 8 * NBAR, ev0 = odone0 + 8 * MAX_OPS;
  const uint32_t progress = ev0 + 8 * MAX_EV, jobw = progress + 4;
  const uint32_t rank = blockIdx.x & 1;
  const int role = blockIdx.x >> 1;
  const int wid = __shfl_sync(0xffffffffu, (int)(threadIdx.x >> 5), 0);
  const int wg = wid >> 2;

  if (wid < 8) {
    if (elect()) {
#pragma unroll
      for (int j = 0; j < 16; j++) {
        const int i = EARLY + 16 * wid + j;
        if (i < 2 * NBAR + MAX_OPS + MAX_EV) mbar_init(full0 + 8 * i, i < NBAR ? 1 : i < 2 * NBAR ? 16 : i < 2 * NBAR + MAX_OPS ? 8 : 1);
      }
      if (wid == 7) asm volatile("st.shared.v2.u32 [%0], {0, 0};\nfence.acq_rel.cta;" ::"r"(progress) : "memory");
      asm volatile("fence.mbarrier_init.release.cluster;" ::: "memory");
    }
  } else if (wid > 8) {
    const uint32_t g = blockIdx.x * 96 + threadIdx.x - 288, w = g - 2048;
    if (g < 4096) asm volatile("prefetch.global.L2 [%0];" ::"l"(g < 2048 ? P.xw[0] + g * (kD * 2) : P.xw[1] + (w >> 5) * (kHD * 2) + (w & 31) * 128));
  } else {
    const uint32_t op0 = P.first[role];
    if (elect()) {
#pragma unroll
      for (int k = 0; k < EARLY; k++) mbar_init(full0 + 8 * k, 1);
      asm volatile("fence.mbarrier_init.release.cluster;" ::: "memory");
      const int blk = (op0 >> 10) & 1;
      if ((op0 & 3) == OP_Q) {
#pragma unroll
        for (int k = 0; k < EARLY; k++) {
          mbar_expect(full0 + 8 * k, SZ_Q);
          tma2d(sbase + k * SZ_Q, &P.x[blk], full0 + 8 * k, 64 * k, ((op0 >> 7) & 7) * kSq + rank * 128);
          tma3d(sbase + k * SZ_Q + 16384, &P.wq[blk], full0 + 8 * k, 0, 64 * k, 3 * ((op0 >> 2) & 31));
          tma3d(sbase + k * SZ_Q + 28672, &P.wq[blk], full0 + 8 * k, 0, 64 * k + 32, 3 * ((op0 >> 2) & 31));
        }
      }
      asm volatile("prefetch.tensormap [%0];\nprefetch.tensormap [%1];" ::"l"(&P.k[blk]), "l"(&P.v[blk]) : "memory");
    }
  }
  __syncwarp();
  asm volatile("barrier.cluster.arrive.relaxed.aligned;\nbarrier.cluster.wait.aligned;" ::: "memory");

  if (wg < 2) {
    asm volatile("setmaxnreg.inc.sync.aligned.u32 240;");
    const uint32_t* prog = P.prog[role].c;
    const int wid = __shfl_sync(0xffffffffu, (int)(threadIdx.x >> 5), 1), wg = wid >> 2;
    const int lane = threadIdx.x & 31, warp = wid & 3;
    uint32_t empty_rem;
    asm volatile("mapa.shared::cluster.u32 %0, %1, %2;" : "=r"(empty_rem) : "r"(empty0), "r"(lane & 1));
    uint32_t keep = (threadIdx.x & 127) < 2 ? 4 : 0;
    auto release = [&](int slot) { mbar_arrive_cluster_n(keep, empty_rem + slot); };
    auto release_warp = [&](int slot, bool on = true) { mbar_arrive_cluster_if(lane < 2 && on, empty_rem + slot); };
    Cursor r{0};
    const uint32_t ring16 = (sbase & 0x3FFFF) >> 4;
    uint32_t cur = ring16;
    bool rdy0 = false, rdy1 = false;
    auto probe1 = [&]() { rdy0 = mbar_test(full0 + r.off(), r.ph()); };
    auto probe2 = [&]() {
      Cursor n = r;
      rdy0 = mbar_test(full0 + n.off(), n.ph());
      n.next();
      rdy1 = mbar_test(full0 + n.off(), n.ph());
    };
    auto advance = [&](uint32_t bytes, uint32_t& addr) {
      const int bi = r.off();
      r.next();
      if (cur > ring16 + ((RING - bytes) >> 4)) cur = ring16;
      addr = cur;
      cur += bytes >> 4;
      return bi;
    };
    auto take = [&](bool rdy, uint32_t bytes, uint32_t& addr) {
      if (__builtin_expect(!__all_sync(0xffffffffu, rdy), 0)) mbar_wait(full0 + r.off(), r.ph());
      return advance(bytes, addr);
    };
    const bool never = P.dbg == 0xffffffffu;
    uint32_t q[48];
#pragma unroll
    for (int i = 0; i < 48; i++) q[i] = 0;
    const int row = wg * 64 + warp * 16 + (lane >> 2);
    const int img0 = row * 4 + ((lane & 3) ^ ((row >> 1) & 3));
    uint4* pend = nullptr;
    bool pend_any = false;
    const uint64_t spol = evict_first();
    int pc = 0;
    auto slab = [&](int c, int i0) {
#pragma unroll
      for (int i = i0; i < 6; i++)
        stg2_if(c == i, pend + i * 512, q[8 * i], q[8 * i + 1], q[8 * i + 2], q[8 * i + 3],
                q[8 * i + 4], q[8 * i + 5], q[8 * i + 6], q[8 * i + 7], spol);
    };
    auto drain = [&](int c) {
      if (!pend_any || c >= 6) return;
      slab(c, 0);
      if (c == 5) {
        __syncwarp();
        mbar_arrive_if(lane == 0, odone0 - 8 + 8 * pc);
      }
    };

    for (;; pc++) {
      uint32_t op = prog[pc];
      const int type = op & 3;
      auto enter = [&]() {
        r.n = (op >> 12) & 248; cur = ring16 + (((op >> 20) & 63) << 8);
      };
      enter();
      pend_any = op & C_PEND;
      uint32_t job = 0;
      if ((op & (3 | C_WIDE)) == OP_O) job = __shfl_sync(0xffffffffu, wait_word(jobw, 1), 0);
      if (type == OP_END || job == OP_O) {
#pragma unroll 1
        for (int c = 0; c < 6; c++) drain(c);
        asm volatile("barrier.cluster.arrive.relaxed;" ::: "memory");
        break;
      }
      {
        float s[32], o[96];
        uint32_t ad0;
        int bi0, sk1;
        uint32_t pa[16], pb[16];
        float mc0, mc1, l0, l1;
        bool shifted;
        uint32_t nop;
        auto expo = [&](float (&s)[32], uint32_t (&pout)[16], float& b0, float& b1, bool shift, auto mid) {
          float c0, c1;
#pragma unroll
          for (int i = 0; i < 8; i++) {
            const float e0 = ex2(shift ? s[4 * i] - mc0 : s[4 * i]), e1 = ex2(shift ? s[4 * i + 1] - mc0 : s[4 * i + 1]);
            const float e2 = ex2(shift ? s[4 * i + 2] - mc1 : s[4 * i + 2]), e3 = ex2(shift ? s[4 * i + 3] - mc1 : s[4 * i + 3]);
            if (i) { b0 += e0; c0 += e1; b1 += e2; c1 += e3; } else { b0 = e0; c0 = e1; b1 = e2; c1 = e3; }
            pout[2 * i] = pack_bf16(e0, e1); pout[2 * i + 1] = pack_bf16(e2, e3);
            if (i & 1) mid(i >> 1);
          }
          b0 += c0; b1 += c1;
        };
        auto rowmax = [&](float (&s)[32], float& m0, float& m1) {
          m0 = fmaxf(s[0], s[1]); m1 = fmaxf(s[2], s[3]);
#pragma unroll
          for (int i = 1; i < 8; i++) { m0 = fmaxf(m0, fmaxf(s[4 * i], s[4 * i + 1])); m1 = fmaxf(m1, fmaxf(s[4 * i + 2], s[4 * i + 3])); }
          m0 = fmaxf(m0, __shfl_xor_sync(0xffffffffu, m0, 1)); m1 = fmaxf(m1, __shfl_xor_sync(0xffffffffu, m1, 1));
          m0 = fmaxf(m0, __shfl_xor_sync(0xffffffffu, m0, 2)); m1 = fmaxf(m1, __shfl_xor_sync(0xffffffffu, m1, 2));
        };
        auto first = [&](float (&s)[32], int sk0, auto mid) {
          fence_regs(s);
          release(sk0);
          mc0 = 0.f; mc1 = 0.f;
          expo(s, pa, l0, l1, false, mid);
          shifted = __any_sync(0xffffffffu, !(fmaxf(l0, l1) <= kSumLimit && fminf(l0, l1) >= 1.f / kSumLimit));
          if (shifted) {
            rowmax(s, mc0, mc1);
            expo(s, pa, l0, l1, true, [](int) {});
          }
        };
        auto qk = [&](float (&s)[32], uint32_t ak, int k0 = 0, int k1 = 12) {
#pragma unroll
          for (int kk = k0; kk < k1; kk++)
            wgmma_rs_n64<0>(s, q[4 * kk], q[4 * kk + 1], q[4 * kk + 2], q[4 * kk + 3], mk_desc(ak, 16, KV_SBO, 1) + ((kk >> 2) * KV_CH + (kk & 3) * 2), kk != 0);
          if (k1 == 12) wg_commit();
        };
        auto pv = [&](uint32_t (&pin)[16], uint32_t av, int acc, int k0 = 0, int k1 = 4) {
#pragma unroll
          for (int kk = k0; kk < k1; kk++)
            wgmma_rs_n192<1>(o, pin[4 * kk], pin[4 * kk + 1], pin[4 * kk + 2], pin[4 * kk + 3], mk_desc(av, KV_CH * 16, KV_SBO, 1) + (kk * (KV_SBO / 8)), acc || (kk != 0));
          if (k0 == 0) wg_commit();
        };
        auto finish = [&](uint32_t (&pout)[16], int sk, int sv, bool part = false) {
          probe1();
          wg_wait<1>();
          fence_regs(s);
          release(sk);
          float b0, b1;
#pragma unroll 1
          for (bool redo = false;; redo = true) {
            expo(s, pout, b0, b1, false, [](int) {});
            if (!__any_sync(0xffffffffu, !redo && (shifted || !(fmaxf(b0, b1) <= kSumLimit)))) break;
            shifted = true;
            rowmax(s, b0, b1);
            b0 = fmaxf(mc0, b0); b1 = fmaxf(mc1, b1);
            const float a0 = ex2(mc0 - b0), a1 = ex2(mc1 - b1);
            mc0 = b0; mc1 = b1;
            l0 *= a0; l1 *= a1;
            wg_wait<0>();
            fence_regs(o);
#pragma unroll
            for (int i = 0; i < 24; i++) { o[4 * i] *= a0; o[4 * i + 1] *= a0; o[4 * i + 2] *= a1; o[4 * i + 3] *= a1; }
#pragma unroll
            for (int i = 0; i < 32; i++) s[i] -= (i & 2) ? mc1 : mc0;
            if (part) {
#pragma unroll
              for (int i = 8; i < 16; i++)
                pa[i] = pack_bf16(__uint_as_float(pa[i] << 16) * ((i & 1) ? a1 : a0), __uint_as_float(pa[i] & 0xffff0000u) * ((i & 1) ? a1 : a0));
            }
          }
          l0 += b0; l1 += b1;
          wg_wait<0>();
          fence_regs(o);
          mbar_arrive_cluster_n(part ? 0 : keep, empty_rem + sv);
        };
        uint32_t pav;
        int psv;
        auto step = [&](uint32_t (&pin)[16], uint32_t (&pout)[16], bool part) {
          uint32_t ak;
          const int sk = take(rdy0, SZ_KV, ak);
          psv = advance(SZ_KV, pav);
          wg_fence();
          qk(s, ak);
          if (part) { wg_fence(); pv(pin, pav, 1, 0, 2); } else { asm volatile(""); wg_fence(); pv(pin, pav, 1); }
          finish(pout, sk, psv, part);
        };
        auto unpark = [&](uint32_t& ak) {
          uint32_t ad;
          const Cursor k0 = r;
          const int sk0 = advance(SZ_KV, ak), bi = take(false, SZ_PARK, ad);
#pragma unroll
          for (int i = 0; i < 12; i++) lds128(sbase + (ad - ring16 + img0) * 16 + (i >> 1) * 8192 + (i & 1) * 512, q[4 * i], q[4 * i + 1], q[4 * i + 2], q[4 * i + 3]);
          if (!__all_sync(0xffffffffu, rdy0)) mbar_wait(full0 + k0.off(), k0.ph());
          fence_regs(q);
          release_warp(bi);
          wg_fence();
          qk(s, ak, 0, 4);
          wg_commit();
          return sk0;
        };
        auto mma4 = [&](uint32_t ad, int acc) {
#pragma unroll
          for (int kk = 0; kk < 4; kk++)
            wgmma_ss_n192<1>(o, mk_desc(ad + wg * 512, 16, 1024, 1) + (kk * 2), mk_desc(ad, 4096, 1024, 1) + (1024 + (kk >> 1) * 768 + (kk & 1) * 128), acc || kk != 0);
        };
        auto convert = [&](int i0, int i1) {
          sched_fence(keep, never);
#pragma unroll
          for (int i = i0; i < i1; i++) {
            q[i] = pack_bf16(o[2 * i] * kScaleLog2, o[2 * i + 1] * kScaleLog2);
            if ((i & 7) == 7 && i != i1 - 1) sched_fence(keep, never);
          }
          sched_fence(keep, never);
        };
        if (type == OP_O) {
          int prev = 0;
          if (op & C_WIDE) {
            float d[64];
            auto mma3 = [&](uint32_t ad, int h, int acc) {
#pragma unroll
              for (int kk = 0; kk < 2; kk++)
                wgmma_ss_n192<1>(o, mk_desc(ad + wg * 256, 16, 512, 2) + (h * 512 + kk * 2), mk_desc(ad, 4096, 1024, 1) + (1024 + h * 768 + kk * 128), acc || kk);
            };
            auto mma2 = [&](uint32_t ad, uint32_t ob, int h, int acc) {
#pragma unroll
              for (int kk = 0; kk < 2; kk++)
                wgmma_ss_n128<1>(d, mk_desc(ad + wg * 256, 16, 512, 2) + (h * 512 + kk * 2), mk_desc(ad, 4096, 1024, 1) + (ob + h * 512 + kk * 128), acc || kk);
            };
            auto wstep = [&](uint32_t bytes, int acc, auto hook) {
              uint32_t ad;
              const int bi = take(rdy0, bytes, ad);
              wg_fence();
              if (bytes == SZ_W2) mma2(ad, 1024, 0, 1); else mma3(ad, 0, acc);
              if (bytes == SZ_W) mma3(ad, 1, 1);
              wg_commit();
              if (acc) { wg_wait<1>(); release(prev); }
              if (bytes == SZ_W) mma2(ad, 2560, 0, acc);
              if (bytes == SZ_W3) mma3(ad, 1, 1); else mma2(ad, bytes == SZ_W ? 2560 : 1024, 1, 1);
              wg_commit();
              prev = bi;
              hook();
              probe1();
              wg_wait<1>();
            };
            undefine(o);
            wstep(SZ_W, 0, [&]() { drain(0); });
#pragma unroll 1
            for (int k = 1; k < ((op >> 2) & 127) - TAIL; k++) wstep(SZ_W, 1, [&]() { drain(k); });
#pragma unroll 1
            for (int k = 0; k < TAIL; k++) wstep(SZ_W2, 1, []() {});
            pend = ptr_add(P.g->part, (((op >> 9) & 31) * 2 + rank) * 81920 + 4 * 8192 + img0 * 16);
            wstep(SZ_W3, 1, [&]() {
              fence_regs(d);
#pragma unroll
              for (int i = 0; i < 32; i++) q[16 + i] = pack_bf16(d[2 * i], d[2 * i + 1]);
              slab(2, 2);
            });
#pragma unroll 1
            for (int k = 3; k < 6; k++) wstep(SZ_W3, 1, [&]() { slab(k, 2); });
            op = prog[pc + 1];
            enter();
            pend_any = true;
            pend -= 4 * 512;
            bi0 = take(rdy0 || (op & 3) != OP_Q, SZ_Q, ad0);
            sched_fence(keep, never);
            wg_wait<0>();
            fence_regs(o);
            release(prev);
#pragma unroll
            for (int i = 0; i < 48; i++) q[i] = pack_bf16(o[2 * i], o[2 * i + 1]);
            if ((op & 3) != OP_Q) continue;
            pc++;
            goto first_step;
          }
          float c[80];
          auto mma2 = [&](uint32_t ad, uint32_t oa, uint32_t ob, int acc) {
            wgmma_ss_n160<1>(c, mk_desc(ad + wg * 256, 16, 512, 2) + (oa), mk_desc(ad, 2048, 512, 2) + (1024 + ob), acc);
            wgmma_ss_n160<1>(c, mk_desc(ad + wg * 256, 16, 512, 2) + (oa + 2), mk_desc(ad, 2048, 512, 2) + (1024 + ob + 64), 1);
          };
          auto kstep = [&](int acc, auto hook, uint32_t bytes = SZ_O) {
            uint32_t ad;
            const int bi = take(rdy0, bytes, ad);
            wg_fence();
            mma2(ad, 0, 0, acc);
            wg_commit();
            if (acc) wg_wait<1>();
            if (acc == 1) release(prev);
            if (acc > 1) release_warp(prev, acc == 2 || wg == 0);
            mma2(ad, 512, 640, 1);
            wg_commit();
            prev = bi;
            hook();
            probe1();
            wg_wait<1>();
          };
          auto unblock = [&](int k) {
            if (__all_sync(0xffffffffu, rdy0) || __all_sync(0xffffffffu, mbar_try(full0 + r.off(), r.ph(), 1500))) return;
#pragma unroll 1
            for (; k < 6; k++) drain(k);
            pend_any = false;
          };
          unblock(0);
          kstep(0, [&]() { drain(0); });
          int left = ((job >> 13) & 127) - 6;
#pragma unroll 1
          for (uint32_t k = 1, pace = left >= 22 ? 0x4511 : left <= 11 ? 0x1a : 0x155; left > 0; pace >>= 2, left--) {
            unblock(k);
            kstep(1, [&]() {
#pragma unroll 1
              for (int i = pace & 3; i > 0; i--) drain(k++);
            });
          }
          uint32_t t[8], stage[3];
          float u[80];
          auto unpack = [&](int j) {
#pragma unroll
            for (int i = 0; i < 8; i++) {
              u[16 * j + 2 * i] = __uint_as_float(t[i] << 16); u[16 * j + 2 * i + 1] = __uint_as_float(t[i] & 0xffff0000u);
              asm volatile("" : "+f"(u[16 * j + 2 * i]), "+f"(u[16 * j + 2 * i + 1]));
            }
          };
#pragma unroll
          for (int i = 0; i < 8; i++) t[i] = 0;
          const uint32_t bytes = (job & P_LD) ? SZ_OL : SZ_O;
#pragma unroll
          for (int j = 0; j < 5; j++) {
            if (j == 2 && wg == 1) {
              wg_wait<0>();
              release_warp(prev);
              bar_sync(1, 256);
            }
            kstep(j == 2 ? 3 : 2, [&]() {
              if (j == 4) asm volatile("{\n.reg .pred p;\nsetp.eq.u32 p, %0, 0;\n@p bar.arrive 1, 256;\n}\n" ::"r"(wg) : "memory");
              if (j) unpack(j - 1);
              lds2_if(job & P_LD, sbase + (cur - ring16 + img0) * 16 - 8192, t);
              if (j >= 1 && j <= 3) stage[j - 1] = sbase + (cur - ring16) * 16 - bytes + wid * 1024;
            }, bytes);
          }
          unpack(4);
          sched_fence(keep, never);
          wg_wait<0>();
          fence_regs(c);
          release_warp(prev);
          asm volatile("barrier.cluster.arrive.relaxed;" ::: "memory");
#pragma unroll
          for (int i = 0; i < 10; i++) {
            const int v = (i & 1) * 2 + (lane >> 4);
            const uint32_t sa = stage[i >> 2] + (i & 2) * 4096;
            stsm4(sa + (lane & 15) * 64 + ((v ^ ((lane >> 1) & 3)) << 4), pack_bf16(c[8 * i] + u[8 * i], c[8 * i + 1] + u[8 * i + 1]),
                  pack_bf16(c[8 * i + 2] + u[8 * i + 2], c[8 * i + 3] + u[8 * i + 3]), pack_bf16(c[8 * i + 4] + u[8 * i + 4], c[8 * i + 5] + u[8 * i + 5]),
                  pack_bf16(c[8 * i + 6] + u[8 * i + 6], c[8 * i + 7] + u[8 * i + 7]));
          }
          asm volatile("fence.proxy.async.shared::cta;" ::: "memory");
          __syncwarp();
          if (elect()) {
#pragma unroll
            for (int i = 0; i < 5; i++)
              tma3d_store(&P.out, stage[i >> 1] + (i & 1) * 8192, 0, ((job >> 7) & 7) * kSq + rank * 128 + wid * 16, ((job >> 10) & 1) * 20 + ((job >> 20) & 3) * 5 + i);
            asm volatile("cp.async.bulk.commit_group;\ncp.async.bulk.wait_group.read 0;" ::: "memory");
          }
          __syncwarp();
          break;
        }
        bi0 = take(rdy0, SZ_Q, ad0);
      first_step:
        undefine(o);
        wg_fence();
        mma4(ad0, 0);
        wg_commit();
        {
          uint32_t ad1;
          const int bi1 = take(false, SZ_Q, ad1);
          wg_fence();
          mma4(ad1, 1);
          wg_commit();
          drain(0);
          wg_wait<1>();
          release(bi0);
          drain(1);
          probe1();
          wg_wait<0>();
          release(bi1);
          fence_regs(o);
#pragma unroll 1
          for (int k = 2; k < 8; k++) {
            uint32_t ad;
            const int bi = take(rdy0, SZ_Q, ad);
            wg_fence();
            mma4(ad, 1);
            wg_commit();
            drain((0x54732710u >> (4 * k)) & 7);
            probe1();
            wg_wait<0>();
            release(bi);
          }
          uint32_t a8, a9, ak0, ak1;
          const int b8 = take(rdy0, SZ_Q, a8), b9 = take(false, SZ_Q, a9);
          wg_fence();
          mma4(a8, 1);
          wg_commit();
          mma4(a9, 1);
          wg_commit();
          wg_wait<1>();
          release(b8);
          probe1();
          const int sk0 = take(rdy0 || (op & F_PARK), SZ_KV, ak0);
          wg_wait<0>();
          fence_regs(o);
          release(b9);
          float s0[32];
          convert(0, 32);
          if (op & F_PARK) {
            convert(32, 48);
            pend = ptr_add(P.g->tile, (((op >> 2) & 511) * 2 + rank) * SZ_PARK + img0 * 16);
            continue;
          }
          pc++;
          wg_fence();
          qk(s0, ak0, 0, 4);
          convert(32, 48);
          wg_fence();
          qk(s0, ak0, 4, 12);
          sk1 = take(false, SZ_KV, ak1);
          wg_fence();
          qk(s, ak1, 0, 4);
          wg_commit();
          probe1();
          wg_wait<1>();
          first(s0, sk0, [&](int i) {
            if (!(i & 1)) return;
            sched_fence(keep, never);
            wg_fence();
            if (i == 1) qk(s, ak1, 4, 8);
            if (i == 3) qk(s, ak1, 8, 12);
            sched_fence(keep, never);
          });
        }
        for (;;) {
          {
            uint32_t av;
            const int sv = take(rdy0, SZ_KV, av);
            undefine(o);
            wg_fence();
            pv(pa, av, 0);
            finish(pb, sk1, sv);
          }
          nop = prog[pc + 1];
#pragma unroll 1
          for (int jj = 0; jj < 7; jj++) {
            step(pb, pa, false);
            step(pa, pb, jj == 6);
          }
          float i0, i1;
          auto last = [&]() {
            uint32_t av;
            const int sv = take(rdy0, SZ_KV, av);
            wg_fence();
            pv(pa, pav, 1, 2, 4);
            pv(pb, av, 1);
            sched_fence(keep, never);
            probe1();
            l0 += __shfl_xor_sync(0xffffffffu, l0, 1); l1 += __shfl_xor_sync(0xffffffffu, l1, 1);
            l0 += __shfl_xor_sync(0xffffffffu, l0, 2); l1 += __shfl_xor_sync(0xffffffffu, l1, 2);
            i0 = rcp(l0); i1 = rcp(l1);
            pend = ptr_add(P.g->tile, (((op >> 2) & 511) * 2 + rank) * SZ_PARK + img0 * 16);
            return sv;
          };
          auto normalise = [&](uint32_t (&d)[48], auto mid) {
#pragma unroll
            for (int i = 0; i < 24; i++) {
              d[8 * (i >> 2) + (i & 3)] = pack_bf16(o[4 * i] * i0, o[4 * i + 1] * i0);
              d[8 * (i >> 2) + (i & 3) + 4] = pack_bf16(o[4 * i + 2] * i1, o[4 * i + 3] * i1);
              if ((i & 1) && i != 23) sched_fence(keep, never);
              if ((i & 3) == 3 && i != 23) mid(i >> 2);
            }
          };
          const int sv = last();
          if ((nop & 3) != OP_A) {
            op = nop;
            enter();
            pend_any = true;
            bi0 = take(rdy0 || (nop & 3) != OP_Q, SZ_Q, ad0);
            sched_fence(keep, never);
            wg_wait<0>();
            fence_regs(o);
            release(psv);
            release(sv);
            normalise(q, [](int) {});
            undefine(o);
            if ((nop & 3) != OP_Q) break;
            pc++;
            goto first_step;
          }
          uint32_t ak0;
          const int sk0 = unpark(ak0);
          wg_wait<1>();
          fence_regs(o);
          release(psv);
          release(sv);
          uint32_t t[48];
          auto st = [&](int i) {
            stg2_if(true, pend + i * 512, t[8 * i], t[8 * i + 1], t[8 * i + 2], t[8 * i + 3], t[8 * i + 4], t[8 * i + 5], t[8 * i + 6], t[8 * i + 7], spol);
          };
          normalise(t, [&](int i) {
            if (i & 1) {
              wg_fence();
              if (i == 1) qk(s, ak0, 4, 8);
              if (i == 3) qk(s, ak0, 8, 12);
              sched_fence(keep, never);
            }
            if (!(i & 1)) st(i >> 1);
          });
          probe2();
          wg_wait<0>();
          first(s, sk0, [&](int i) { if (i < 3) { sched_fence(keep, never); st(3 + i); } });
          __syncwarp();
          mbar_arrive_if(lane == 0, odone0 + 8 * pc);
          pc++;
          op = nop;
          uint32_t ak1;
          sk1 = take(rdy0, SZ_KV, ak1);
          rdy0 = rdy1;
          wg_fence();
          qk(s, ak1);
        }
      }
    }
    asm volatile("barrier.cluster.wait;" ::: "memory");
  } else {
    asm volatile("setmaxnreg.dec.sync.aligned.u32 24;");
    const uint32_t* prog = P.prog[role].p;
    unsigned int* flag = P.g->flag + rank;
    if (wid == 11 && (prog[0] & 3) == OP_Q) {
      const uint32_t a = prog[1];
      const char* p = ptr_add(P.kv[rank * 2 + ((a >> 10) & 1)], ((a >> 2) & 255) * (kSk * kDh * 2) + (threadIdx.x & 31) * 128);
#pragma unroll 1
      for (uint32_t k = 0; k < 3; k++) {
        wait_word(progress, 8 * k);
        p += SZ_KV;
        asm volatile("prefetch.global.L2 [%0];\nprefetch.global.L2 [%0 + 4096];" ::"l"(p));
      }
      __syncwarp();
    }
    if (wid == 8) {
      Cursor head{0}, tail{0};
      int sh = 0, room = RING >> 12;
      uint32_t cur = 0;
      uint64_t fifo = 0;
      uint32_t dst, bar = 0, ev = ev0;
      const uint64_t pol = evict_first();
      auto retire = [&]() {
        mbar_wait(empty0 + tail.off(), tail.ph());
        tail.next();
        room += (uint32_t)fifo & 31;
        fifo >>= 5;
        sh -= 5;
        asm volatile("st.volatile.shared.u32 [%0], %1;" ::"r"(progress), "r"(tail.n) : "memory");
      };
      auto acquire = [&](uint32_t bytes) {
        uint32_t fp = bytes >> 12;
        if (cur + fp > (RING >> 12)) { fp += (RING >> 12) - cur; cur = 0; }
        room -= fp;
        while (room < 0) retire();
        fifo |= (uint64_t)fp << sh;
        sh += 5;
        dst = sbase + (cur << 12);
        bar = full0 + head.off();
        cur += bytes >> 12;
        head.next();
      };
      auto gate = [&]() {
        mbar_wait(ev, 0);
        ev += 8;
        asm volatile("fence.proxy.async.global;" ::: "memory");
      };
      for (int pc = 0;; pc++) {
        uint32_t op = prog[pc];
        const int type = op & 3;
        if (type == OP_END) break;
        if (op == OP_O) {
          gate();
          op = __shfl_sync(0xffffffffu, lds32(jobw), 0);
        }
        const int blk = (op >> 10) & 1;
        if (type == OP_Q) {
          const uint64_t px = (op & P_LASTX) ? pol : no_hint(), pw = (op & P_LASTW) ? pol : no_hint();
          int k = 0;
          if (pc == 0) {
            k = 64 * EARLY; head.n = 8 * EARLY; sh = 5 * EARLY; cur = EARLY * (SZ_Q >> 12); room -= cur;
            fifo = (SZ_Q >> 12) * (((1u << (5 * EARLY)) - 1) / 31);
          }
#pragma unroll 1
          for (int stop = (op & P_GATE) ? kD - 64 : kD;; stop = kD) {
#pragma unroll 1
            for (; k < stop; k += 64) {
              acquire(SZ_Q);
              if (elect()) {
                mbar_expect(bar, SZ_Q);
                tma3d_mc_hint(dst + 16384 + rank * 12288, &P.wq[blk], bar, k + 32 * rank, 3 * ((op >> 2) & 31), pw);
                tma2d_hint(dst, &P.x[blk], bar, k, ((op >> 7) & 7) * kSq + rank * 128, px);
              }
            }
            if (k == kD) break;
            gate();
          }
        } else if (type == OP_A) {
          const int row0 = ((op >> 2) & 255) * kSk;
          auto kv = [&](uint32_t tx, const CUtensorMap* m, int c3) {
            const uint32_t before = bar;
            acquire(SZ_KV);
            if (elect()) {
              mbar_expect(bar, tx);
              tma4d_mc_hint(dst + rank * (SZ_KV / 2), m, tx ? bar : before, c3, pol);
            }
          };
          int c3 = row0 / 8 + 4 * rank;
#pragma unroll 1
          for (int j = 0; j <= 16; j++, c3 += 8) {
            const uint32_t tv = j < 2 || j == 16 ? SZ_KV : 0;
            if (j < 16) kv(2 * SZ_KV - tv, &P.k[blk], c3);
            else if (op & P_GATE) gate();
            if (j > 0) kv(tv, &P.v[blk], c3 - 8);
            else if (op & F_PARK) {
              gate();
              acquire(SZ_PARK);
              if (elect()) {
                mbar_expect(bar, SZ_PARK);
                bulk_load_hint(dst, &P.g->tile[(((op >> 20) & 511) * 2 + rank) * 3072], SZ_PARK, bar, pol);
              }
            }
          }
        } else {
          const uint4* part = &P.g->part[((((op >> 6) & 30) + ((op >> 21) & 1)) * 2 + rank) * 5120 + ((op >> 20) & 1) * 2560];
          auto run = [&](const uint32_t bytes, int k, int cnt, int gates) {
            const int col = bytes == SZ_O || bytes == SZ_OL ? 5 * ((op >> 20) & 3) : 5 * ((op >> 21) & 1);
            int row = 8 * k + 4 * rank, pre = bytes == SZ_O && (op & P_PRE) ? 0 : 2560;
#pragma unroll 1
            for (int h = (k * 43) >> 7, k0 = k - 3 * h; cnt > 0; h++, k0 = 0, gates = gates >> 1 | (gates & 2)) {
              const uint4* src = ptr_add(P.g->tile, ((P.slot[((op >> 2) & 480) + h] * 2 + rank) * 3 + k0) * 16384);
              const uint64_t pw = h >= ((op >> 23) & 31) && h < 2 * (op >> 28) ? pol : no_hint();
              if (gates & 1) gate();
              int m = min(3 - k0, cnt);
              cnt -= m;
#pragma unroll 1
              for (; m > 0; m--, src += 1024, row += 8) {
                acquire(bytes);
                if (elect()) {
                  mbar_expect(bar, bytes);
                  if (bytes == SZ_O || bytes == SZ_OL) tma5d_mc_hint(dst + 16384 + rank * 10240, &P.wo[blk], bar, row, col, no_hint());
                  if (bytes == SZ_W || bytes == SZ_W3) tma5d_mc_hint(dst + 16384 + rank * 12288, &P.wo3[blk], bar, row, col, pw);
                  bulk_load_hint(dst, src, 16384, bar, pol);
                  if (bytes == SZ_W || bytes == SZ_W2) tma5d_mc_hint(dst + bytes - 16384 + rank * 8192, &P.wo2[blk], bar, row, col + 3, pw);
                  if (bytes == SZ_OL) bulk_load_hint(dst + SZ_O, part, 8192, bar, pol);
                }
                if (bytes == SZ_OL) part += 512;
              }
              if (pre < 2560) {
                if (elect()) asm volatile("cp.async.bulk.prefetch.L2.global [%0], 10240;" ::"l"(part + pre) : "memory");
                pre += 640;
              }
            }
          };
          const int n = (op >> 13) & 127;
          if (op & P_WIDE) {
            run(SZ_W, 0, n - TAIL, 3);
            run(SZ_W2, n - TAIL, TAIL, (n - TAIL) % 3 ? 2 : 3);
            run(SZ_W3, n - TAIL, TAIL, 0);
          } else {
            if (op & P_PRE) gate();
            run(SZ_O, kSteps - n, (op & P_LD) ? n - 5 : n, 3);
            if (op & P_LD) {
              if (!(op & P_PRE)) gate();
              run(SZ_OL, kSteps - 5, 5, 2);
            }
          }
        }
      }
#pragma unroll 1
      while (sh) retire();
    } else if (threadIdx.x == 288) {
      for (int pc = 0;; pc++) {
        const uint32_t op = prog[pc];
        const int type = op & 3;
        if (type == OP_END) break;
        if (type == OP_Q ? !(op & F_PARK) : type == OP_O && !(op & P_WIDE)) continue;
        const int id = type == OP_A ? (op >> 2) & 511 : type == OP_Q ? N_TILE + ((op >> 13) & 127) : ID_PART + ((op >> 5) & 60) + ((op >> 20) & 3);
        const uint32_t v = type == OP_O ? 1 : P.info[id] & 7;
        mbar_wait_long(odone0 + 8 * pc);
        flag_set(flag + 2 * id, v);
        if (type == OP_O && (op & P_WIDE)) flag_set(flag + 2 * id + 2, v);
      }
    } else if (wid == 10) {
      int i = threadIdx.x & 31;
      const int n_ev = P.prog[role].n_ev;
      auto event = [&]() { return i < n_ev ? P.prog[role].ev[i] : n_ev ? E_JOB | (i - n_ev) : 0; };
      uint32_t e = i < 8 ? event() : 0;
      for (uint32_t n = 0; __any_sync(0xffffffffu, e); n++) {
        uint32_t job = lds32(jobw);
        const int togo = (e & E_DRAW) ? (e & 1023) - (lds32(progress) >> 3) : 99;
        if (togo <= 0 && rank == 0) {
          job = P.job[atomicInc(&P.g->ticket, gridDim.x / 2 - 1)];
          asm volatile("{\n.reg .u32 a;\nmapa.shared::cluster.u32 a, %0, 1;\nst.volatile.shared::cluster.u32 [a], %1;\n"
                       "st.volatile.shared.u32 [%0], %1;\n}\n" ::"r"(jobw), "r"(job) : "memory");
        }
        if ((e & E_JOB) && job) {
          const uint32_t j = e & 63, heads = job == OP_O ? 0 : kH - ((job >> 2) & 31), jp = !(job & P_LD) ? 63 : (job & P_PRE) ? 0 : heads - 1, h = j - (j > jp);
          e = j == jp ? (ID_PART + ((job >> 5) & 60) + ((job >> 20) & 3)) | E_ON | E_LAST : h < heads ? (((job >> 2) & 511) + h) | E_ON | E_LAST : 0;
        }
        unsigned int* f = ptr_add(flag, 8 * (e & 1023));
        const bool ok = (e & E_ON) ? flag_get(f) - 1 < ((e & E_FREE) ? 1 : 7) : (e & E_DRAW) && job;
        if (ok) {
          mbar_arrive(ev0 + 8 * i);
          if (e & (E_FREE | E_LAST)) flag_dec(f);
          i += 8;
          e = event();
        }
        asm volatile("{\n.reg .pred p;\nsetp.ge.u32 p, %0, 0x400000;\n@p trap;\n}\n" ::"r"(n));
        if (!__any_sync(0xffffffffu, ok)) __nanosleep(__any_sync(0xffffffffu, job || togo <= 2) ? 100 : 600);
      }
    } else if (threadIdx.x == 352) {
      uint32_t items = 0;
      auto read = [&](int id) {
        if (!(P.info[id] & I_NEXT)) return;
        wait_word(progress, 8 * items);
        flag_dec(flag + 2 * id);
      };
      for (int pc = 0;; pc++) {
        const uint32_t op = prog[pc];
        const int type = op & 3;
        if (type == OP_END) break;
        if (type == OP_O) {
          const uint32_t n = (op >> 13) & 127, base = items;
#pragma unroll 1
          for (uint32_t k = 3, id = (op >> 2) & 511; k <= n; k += 3, id++) {
            items = base + k + (k + TAIL > n ? TAIL : 0);
            read(id);
          }
          items = base + n + TAIL;
        } else if (type == OP_A) {
          items++;
          if (op & F_PARK) { items++; read(N_TILE + ((op >> 13) & 127)); }
          items += 31;
        } else {
          items += 10;
        }
      }
    }
    __syncwarp();
    asm volatile("barrier.cluster.arrive.relaxed;\nbarrier.cluster.wait;" ::: "memory");
  }
}

typedef CUresult (*EncodeFn)(CUtensorMap*, CUtensorMapDataType, cuuint32_t, void*, const cuuint64_t*, const cuuint64_t*,
                             const cuuint32_t*, const cuuint32_t*, CUtensorMapInterleave, CUtensorMapSwizzle,
                             CUtensorMapL2promotion, CUtensorMapFloatOOBfill);

void encode(EncodeFn fn, CUtensorMap* m, const void* ptr, int rank, const cuuint64_t* dims, const cuuint64_t* strides,
            const cuuint32_t* box, CUtensorMapSwizzle swz) {
  const cuuint32_t es[5] = {1, 1, 1, 1, 1};
  CUresult r = fn(m, CU_TENSOR_MAP_DATA_TYPE_BFLOAT16, rank, const_cast<void*>(ptr), dims, strides, box, es,
                  CU_TENSOR_MAP_INTERLEAVE_NONE, swz, CU_TENSOR_MAP_L2_PROMOTION_L2_128B, CU_TENSOR_MAP_FLOAT_OOB_FILL_NONE);
  if (r != CUDA_SUCCESS) fprintf(stderr, "cuTensorMapEncodeTiled failed: %d\n", (int)r);
}

struct Op { int type, flags, id, n, quarter, park, item0, items; double t0, t1; };
struct Use { double ready, gate, need, freed; int readers, slot, prev; bool next; };
struct PlanStats { double end, slack, park_slack; int slots, parks; uint32_t own[N_CL]; };

bool plan(const char* const* text, int n_pair, int phase, Params& P, PlanStats* stats = nullptr) {
  constexpr double T_Q = 7900, T_A = 24550, T_U = 25900, T_P = 8400, T_O = 640, T_RUN = 800, T_WIDE = 1300, AHEAD = 3500, PUBLISH = 1500;
  const double margin = 256.0 * ((P.dbg >> 8) & 255);
  static Op op[N_CL][MAX_OPS];
  static Use use[ID_PART];
  int n_op[N_CL], covered[2 * N_TEAM] = {};
  struct Ref { double t; Op* o; int id; };
  static Ref att[N_TILE + 1], dem[N_TILE], prk[MAX_PARK + 1], unp[MAX_PARK + 1], wr[ID_PART];
  auto sort = [](Ref* r, int n) {
    for (int i = 1; i < n; i++)
      for (int j = i; j > 0 && r[j].t < r[j - 1].t; j--) { Ref x = r[j]; r[j] = r[j - 1]; r[j - 1] = x; }
  };
  auto hex = [](char c) { return c <= '9' ? c - '0' : c - 'a' + 10; };
  for (int i = 0; i < n_pair; i++)
    for (const char* s = text[i]; *s; s++)
      for (int h = 0; *s == 'J' && h < 2; h++) {
        if (covered[2 * hex(s[1]) + h]) return false;
        covered[2 * hex(s[1]) + h] = 10 * (s[2 + 2 * h] - '0') + s[3 + 2 * h] - '0';
      }
  for (int c = 0; c < 2 * n_pair; c++) {
    int n = 0, items = 0;
    double t = 0;
    auto add = [&](int type, int flags, int id, int heads, int quarter, int its, double dt) {
      if (n < MAX_OPS) op[c][n] = {type, flags, id, heads, quarter, 0, items, its, t, t + dt};
      n++; items += its; t += dt;
    };
    for (const char* s = text[c >> 1]; *s; s++) {
      const int tm = hex(s[1]) & 15, nj = covered[2 * tm + (c & 1)];
      if (*s == 'N') { add(OP_Q, 0, 0, 0, 0, 10, T_Q); add(OP_A, 0, 0, 0, 0, 32, T_A); }
      if (*s == 'P') add(OP_Q, F_PARK, 0, 0, 0, 10, T_P);
      if (*s == '+' || *s == '-') t += *s == '+' ? 1000 : -1000;
      if (*s == 'U') { if (n == 0 || n > MAX_OPS || op[c][n - 1].type != OP_A) return false; add(OP_A, F_PARK, 0, 0, 0, 33, T_U); }
      if (*s == 'J') { if (nj < TAIL + 6 || nj > kSteps - 11) return false; add(OP_O, P_WIDE, tm * kH, nj, 2 * (c & 1), nj + TAIL, 2 * T_O * nj + T_WIDE); }
    }
    add(OP_O, 0, 0, 0, 0, 0, 0);
    add(OP_END, 0, 0, 0, 0, 0, 0);
    if (n > MAX_OPS || op[c][0].type != OP_Q) return false;
    n_op[c] = n - 1;
    att[c] = {t, &op[c][n - 2], 0};
  }
  for (int i = 0; i < 4 * N_TEAM; i++) dem[i] = {(double)covered[i / 2], nullptr, i};
  sort(att, 2 * n_pair); sort(dem, 4 * N_TEAM);
  for (int i = 0; i < 4 * N_TEAM; i++) {
    Op* f = att[i].o;
    const int nj = covered[dem[i].id / 2];
    f->flags = nj ? P_LD : 0;
    f->id = dem[i].id / 4 * kH + nj / 3; f->quarter = dem[i].id & 3; f->items = f->n = kSteps - nj;
    f[1].t0 = f[1].t1 = f->t1 = f->t0 + T_O * f->n + T_RUN; f[1].item0 += f->n;
  }
  for (int i = 0; i < ID_PART; i++) use[i] = {0, 0, 1e18, 0, 0, 0, 0, false};
  int n_att = 0, n_prk = 0, n_unp = 0;
  auto ready = [&](const Op* o) {
    const int nt = o[1].type;
    return o->t1 + (nt == OP_Q ? 6100 : o[1].n ? ((o[1].flags & P_WIDE) ? 7700 : 3900) : 1500) + PUBLISH;
  };
  for (int c = 0; c < 2 * n_pair; c++)
    for (Op* o = op[c]; o->type != OP_END; o++) {
      if (o->type == OP_A) { att[n_att] = {ready(o), o, 0}; if (++n_att > N_TILE) return false; }
      if (o->type == OP_A && o->flags) { unp[n_unp] = {o->t0 - AHEAD, o, 0}; if (++n_unp > MAX_PARK) return false; }
      if (o->type == OP_Q && o->flags) { prk[n_prk] = {ready(o), o, 0}; if (++n_prk > MAX_PARK) return false; }
      for (int i = 0; o->type == OP_O && i < o->n; i++) {
        const int nw = (o->flags & P_WIDE) ? o->n - TAIL : 0, k = nw ? i : kSteps - o->n + i;
        Use& u = use[o->id / kH * kH + k / 3];
        const double t = o->t0 + T_O * (i + (i < nw ? i : nw));
        if (t - AHEAD < u.need) u.need = t - AHEAD;
        const double f = !nw ? 1e18 : i + FLIGHT < o->items - TAIL || (nw && o[1].type != OP_O) ? t + T_O * (i < nw ? 2 : 1 + TAIL) + PUBLISH : 1e18;
        if (f > u.freed) u.freed = f;
        if (i == 0 || k % 3 == 0) u.readers++;
      }
    }
  if (n_att != N_TILE || n_prk != n_unp) return false;
  for (int i = 0; i < N_TILE; i++) { const int id = (i & 15) * kH + (i >> 4); dem[i] = {use[id].need, nullptr, id}; }
  sort(att, n_att); sort(dem, N_TILE); sort(prk, n_prk); sort(unp, n_unp);
  PlanStats st = {0, 1e18, 1e18, 0, n_prk};
  int n_wr = 0;
  for (int i = 0; i < N_TILE; i++) {
    Op* o = att[i].o;
    o->id = dem[i].id;
    if (!o->flags) o[-1].id = o->id;
    if (dem[i].t - att[i].t < st.slack) st.slack = dem[i].t - att[i].t;
    wr[n_wr++] = {o->t1 - 2 * AHEAD, o, o->id};
  }
  for (int i = 0; i < n_prk; i++) {
    prk[i].o->id = unp[i].o->id;
    prk[i].o->park = unp[i].o->park = i;
    use[N_TILE + i].freed = unp[i].o->t0 + 2 * PUBLISH;
    use[N_TILE + i].readers = 1;
    if (unp[i].t - prk[i].t < st.park_slack) st.park_slack = unp[i].t - prk[i].t;
    wr[n_wr++] = {prk[i].o->t1 - 2 * AHEAD, prk[i].o, N_TILE + i};
  }
  for (int c = 0; c < 2 * n_pair; c++)
    for (int d = 0; d < 2 * n_pair; d++)
      for (Op *f = &op[c][n_op[c] - 1], *o = op[d]; f->n && o->type != OP_END; o++)
        if (o->type == OP_O && (o->flags & P_WIDE) && o->id / kH == f->id / kH && o->quarter / 2 == f->quarter / 2) {
          if (f->t0 - o->t1 > 4096.0 * ((P.dbg >> 16) & 255)) f->flags |= P_PRE;
          const double slack = f->t0 + ((f->flags & P_PRE) ? 0 : (f->n - 5) * T_O) - AHEAD - ready(o);
          if (slack < st.park_slack) st.park_slack = slack;
        }
  constexpr double long_while = 160000;
  for (int c = 0; c < 2 * n_pair; c++)
    for (Op* o = op[c]; o->type != OP_END; o++) {
      if (o->type == OP_O && (o->flags & P_WIDE)) {
        int run = 0, best = 0, end = 0;
        for (int h = 0; 3 * h < o->n; h++) {
          bool last = true;
          for (int d = 0; d < 2 * n_pair; d++)
            for (const Op* e = op[d]; e->type != OP_END; e++) {
              if (e->type != OP_O || e == o || ((e->id ^ o->id) & 256) || e->quarter / 2 != o->quarter / 2) continue;
              const bool wide = e->flags & P_WIDE;
              if (wide ? 3 * h >= e->n : 3 * h + 3 <= kSteps - e->n) continue;
              const double dt = e->t0 + T_O * (wide ? 6 * h : 3 * h - kSteps + e->n) - o->t0 - T_O * 6 * h + (d - c) * 1e-3;
              if (dt > 0 && dt < long_while) last = false;
            }
          run = last ? run + 1 : 0;
          if (run > best) { best = run; end = h + 1; }
        }
        if (3 * end >= o->n) end++;
        o->park = (end - best) | (end / 2) << 5;
      }
      if (o->type != OP_Q) continue;
      bool lw = true, lx = true;
      for (int d = 0; d < 2 * n_pair; d++)
        for (const Op* e = op[d]; e->type != OP_END; e++) {
          const double dt = e->t0 - o->t0 + (d - c) * 1e-3;
          if (e->type != OP_Q || e == o || dt < 0 || dt > long_while) continue;
          if (((e->id ^ o->id) & (256 + 31)) == 0) lw = false;
          if (e->id / kH == o->id / kH) lx = false;
        }
      o->quarter = (lw ? P_LASTW : 0) | (lx ? P_LASTX : 0);
    }
  sort(wr, n_wr);
  int holder[N_TILE];
  for (int i = 0; i < n_wr; i++) {
    int best = -1;
    for (int sl = 0; sl < st.slots; sl++)
      if (use[holder[sl]].freed + margin <= wr[i].t && (best < 0 || use[holder[sl]].freed < use[holder[best]].freed)) best = sl;
    Use& u = use[wr[i].id];
    if (best >= 0) { u.prev = holder[best]; use[u.prev].next = true; wr[i].o->flags |= P_GATE; }
    else if (st.slots == N_TILE) return false;
    else best = st.slots++;
    u.slot = best;
    holder[best] = wr[i].id;
  }
  {
    int pos[N_CL] = {}, flag[ID_PART + 4 * N_TEAM] = {}, seen[ID_PART] = {};
    auto goal = [&](int c) { return op[c][n_op[c] - 1].item0; };
    for (bool moved = true; moved;) {
      moved = false;
      for (int c = 0; c < 2 * n_pair; c++) {
        for (; pos[c] < goal(c); pos[c]++, moved = true) {
          bool ok = true;
          for (const Op* o = op[c]; o->type != OP_END; o++) {
            const int k = pos[c] - o->item0, own = o->type == OP_A ? o->id : N_TILE + (o->park & 127);
            if (k < 0 || k >= o->items) continue;
            if (o->type == OP_O) ok = k >= o->n || flag[o->id + k / 3];
            else if (k == o->items - 1 && (o->flags & P_GATE)) ok = seen[use[own].prev] == use[use[own].prev].readers;
            else if (k == 1 && o->type == OP_A && (o->flags & F_PARK)) ok = flag[N_TILE + o->park];
          }
          if (!ok) break;
          for (const Op* o = op[c]; o->type != OP_END; o++) {
            if (pos[c] == o->item0 + o->items + (o[1].type == OP_Q ? 7 : o[1].item0 == goal(c) ? -1 : 5)) {
              if (o->type == OP_A) flag[o->id] = 1;
              if (o->type == OP_Q && (o->flags & F_PARK)) flag[N_TILE + o->park] = 1;
              if (o->type == OP_O) flag[ID_PART + o->id / kH * 4 + o->quarter] = flag[ID_PART + o->id / kH * 4 + o->quarter + 1] = 1;
            }
            const int k = pos[c] - FLIGHT - o->item0, nw = o->n - TAIL;
            if (k == 1 && o->type == OP_A && (o->flags & F_PARK)) seen[N_TILE + o->park]++;
            if (o->type == OP_O && k >= 0 && k < o->items && (k < nw || k >= o->n) && (k < nw ? k : k - TAIL) % 3 == 2) seen[o->id + (k < nw ? k : k - TAIL) / 3]++;
          }
        }
      }
    }
    for (int c = 0; c < 2 * n_pair; c++) if (pos[c] < goal(c)) return false;
  }
  int n_job = 0, longest = 0;
  for (int i = 0; i < 2 * N_TEAM; i++) if (kH + 1 - covered[i] / 3 > longest) longest = kH + 1 - covered[i] / 3;
  for (int c = 0; c < 2 * n_pair; c++) {
    uint32_t items = 0, cur = 0, pend = 0;
    int n = 0, ev = 0;
    auto item = [&](uint32_t bytes, int count) {
      for (int i = 0; i < count; i++) { if (cur + bytes > RING) cur = 0; cur += bytes; items++; }
    };
    auto event = [&](uint32_t e) { if (ev < MAX_TAB) P.prog[c].ev[ev] = e; ev++; };
    for (const Op* o = op[c];; o++) {
      if (o->type != OP_END && phase && (o->type == OP_O) != (phase == 2)) continue;
      uint32_t cw = o->type | (items % (2 * NBAR)) << 15 | (cur >> 12) << 20 | pend, pw = o->type | o->id << 2 | o->flags;
      const int ps = use[N_TILE + (o->park & 127)].slot;
      pend = 0;
      if (o->type == OP_O) {
        pw |= o->n << 13 | o->quarter << 20 | (uint32_t)o->park << 23;
        if (o->flags & P_WIDE) {
          cw |= o->n << 2 | (o->id / kH * 2 + o->quarter / 2) << 9 | C_WIDE;
          item(SZ_W, o->n - TAIL);
          item(SZ_W2, TAIL);
          item(SZ_W3, TAIL);
          pend = C_PEND;
          for (int i = 0; 3 * i < o->n; i++) event((o->id + i) | E_ON | (use[o->id + i].next ? 0 : E_LAST));
        } else {
          dem[n_job++] = {o->t0 - 1e6 * o->n, nullptr, (int)pw};
          st.own[c] = pw;
          pw = OP_O;
          event(E_DRAW | (items < 16 ? 0 : items - 16));
        }
      } else if (o->type != OP_END) {
        const bool parks = o->type == OP_Q && (o->flags & F_PARK);
        cw |= (parks ? ps : use[o->id].slot) << 2 | (o->flags & F_PARK);
        if (o->flags & F_PARK) pw |= o->park << 13 | ps << 20;
        if (o->type == OP_Q) { item(SZ_Q, 10); pw |= o->quarter; }
        else { item(SZ_KV, 1); if (o->flags & F_PARK) { item(SZ_PARK, 1); event((N_TILE + o->park) | E_ON | (use[N_TILE + o->park].next ? 0 : E_LAST)); } item(SZ_KV, 31); }
        if (parks || o->type == OP_A) pend = C_PEND;
        if (o->flags & P_GATE) event(use[parks ? N_TILE + o->park : o->id].prev | E_ON | E_FREE);
      }
      P.prog[c].c[n] = cw; P.prog[c].p[n++] = pw;
      if (o->type == OP_END) { if (o->t0 > st.end) st.end = o->t0; break; }
    }
    if (ev > MAX_TAB || ev + longest > MAX_EV) return false;
    P.prog[c].n_ev = ev;
    while (n < MAX_OPS) { P.prog[c].c[n] = OP_END; P.prog[c].p[n++] = OP_END; }
    P.first[c] = (uint16_t)(P.prog[c].p[0] & 2047);
  }
  sort(dem, n_job);
  for (int i = 0; i < n_job; i++) P.job[i] = dem[i].id;
  for (int i = 0; i < ID_PART; i++) {
    if (i < N_TILE) P.slot[i] = use[i].slot;
    P.info[i] = (use[i].readers + use[i].next) | (use[i].next ? I_NEXT : 0);
  }
  if (stats) *stats = st;
  return true;
}

const char* const kPrograms[N_CL / 2] = {
  "PNJ06864NNNNN", "PNJ17878NNNNN", "PNJ26464NNNNN", "PNJ34148NNNNNN", "PNJ46262NNNNN", "PNJ58182NNNN",
  "NNJ67371NNNN", "PNNJ76666NNNN", "NUNNNJ84545NN", "NUNNNJ94545NN", "NUNNNNJa5551N", "NNNNNJb5959NN",
  "NNNNNJc5455NN", "PNNNNNJd5353NN", "NNNNNJe5153NN", "NNNNNJf7777N", "PNNNNNNNNN", "PNNNNNNNNN",
  "PNNNNNNNNN", "PNNNNNNNNN", "NNNNNNNNN", "NNNNNNNNN", "NNNNNNNNN", "NNNNNNNNN",
  "NNNNNNNNN", "N-NNNNNNNN", "NUNNNNNNN", "NUNNNNNNN", "NUNNNNNNN", "NUNNNUNNN",
  "NUNNNNNNN", "NUNNNNNNN", "NUUNNNNNN",
};

const char* const* bench_programs() {
  return kPrograms;
}

}

extern "C" void kernel_launch(void* const* d_in, const int* in_sizes, int n_in, void* d_out, int out_size) {
  (void)in_sizes; (void)n_in; (void)out_size;
  static EncodeFn fn = nullptr;
  static int n_clusters = 0;
  if (!fn) {
    cudaDriverEntryPointQueryResult qr;
    void* f = nullptr;
    cudaGetDriverEntryPoint("cuTensorMapEncodeTiled", &f, cudaEnableDefault, &qr);
    fn = (EncodeFn)f;
    cudaFuncSetAttribute(fused_kernel, cudaFuncAttributeMaxDynamicSharedMemorySize, SMEM_BYTES);
    cudaLaunchConfig_t cfg = {};
    cfg.gridDim = dim3(132); cfg.blockDim = dim3(384); cfg.dynamicSmemBytes = SMEM_BYTES;
    cudaLaunchAttribute at[1];
    at[0].id = cudaLaunchAttributeClusterDimension; at[0].val.clusterDim.x = 2; at[0].val.clusterDim.y = 1; at[0].val.clusterDim.z = 1;
    cfg.attrs = at; cfg.numAttrs = 1;
    if (cudaOccupancyMaxActiveClusters(&n_clusters, fused_kernel, &cfg) != cudaSuccess || n_clusters < 1) n_clusters = 1;
    (void)cudaGetLastError();
  }
  static Params P;
  const CUtensorMapSwizzle S128 = CU_TENSOR_MAP_SWIZZLE_128B, S64 = CU_TENSOR_MAP_SWIZZLE_64B;
  for (int blk = 0; blk < 2; blk++) {
    void* const* in = d_in + 5 * blk;
    { const cuuint64_t d[] = {kD, kB * kSq}, s[] = {kD * 2}; const cuuint32_t b[] = {64, 128};
      encode(fn, &P.x[blk], in[0], 2, d, s, b, S128); }
    { const cuuint64_t d[] = {64, 8, 3, (cuuint64_t)kB * kH * kSk / 8}, s[] = {kDh * 2, 128, 8 * kDh * 2}; const cuuint32_t b[] = {64, 8, 3, 4};
      encode(fn, &P.k[blk], in[1], 4, d, s, b, S128);
      encode(fn, &P.v[blk], in[2], 4, d, s, b, S128); }
    { const cuuint64_t d[] = {64, kD, kHD / 64}, s[] = {kHD * 2, 128}; const cuuint32_t b[] = {64, 32, 3};
      encode(fn, &P.wq[blk], in[3], 3, d, s, b, S128); }
    { const cuuint64_t d[] = {32, 2, kHD / 8, 4, kD / 32}, s[] = {kD * 2, 8 * kD * 2, 2 * kD * 2, 64}; const cuuint32_t b[] = {32, 2, 4, 4, 5};
      encode(fn, &P.wo[blk], in[4], 5, d, s, b, S64); }
    { const cuuint64_t d[] = {64, 2, kHD / 8, 4, kD / 64}, s[] = {kD * 2, 8 * kD * 2, 2 * kD * 2, 128};
      const cuuint32_t b3[] = {64, 2, 4, 4, 3}, b2[] = {64, 2, 4, 4, 2};
      encode(fn, &P.wo3[blk], in[4], 5, d, s, b3, S128);
      encode(fn, &P.wo2[blk], in[4], 5, d, s, b2, S128); }
  }
  { const cuuint64_t d[] = {32, kB * kSq, 2 * kD / 32}, s[] = {2 * kD * 2, 64}; const cuuint32_t b[] = {32, 16, 1};
    encode(fn, &P.out, d_out, 3, d, s, b, S64); }

  P.kv[0] = (const char*)d_in[1]; P.kv[1] = (const char*)d_in[6]; P.kv[2] = (const char*)d_in[2]; P.kv[3] = (const char*)d_in[7];
  P.xw[0] = (const char*)d_in[0]; P.xw[1] = (const char*)d_in[3];
  cudaGetSymbolAddress((void**)&P.g, g_scratch);
  P.dbg = DBG_DEFAULT;
  if (n_clusters >= N_CL && plan(bench_programs(), N_CL / 2, 0, P)) {
    fused_kernel<<<2 * N_CL, 384, SMEM_BYTES>>>(P);
  } else {
    const char* text[2 * N_TEAM];
    for (int i = 0; i < 2 * N_TEAM; i++) text[i] = "NNNNNNNN";
    for (int phase = 1; phase <= 2; phase++) {
      plan(text, 2 * N_TEAM, phase, P);
      fused_kernel<<<8 * N_TEAM, 384, SMEM_BYTES>>>(P);
    }
  }
}
```

```cpp
#include <cuda_runtime.h>
#include <cuda_bf16.h>
#include <cuda.h>
#include <cuda/annotated_ptr>
#include <stdint.h>
#include <stdio.h>

namespace {

constexpr int kB = 8, kSq = 256, kD = 640, kH = 32, kSk = 1024, kDh = 192;
constexpr int kHD = kH * kDh;
constexpr uint32_t RING = 224 * 1024;
constexpr uint32_t SZ_KV = 24576;
constexpr uint32_t SZ_Q = 16384 + 24576;
constexpr uint32_t SZ_O = 16384 + 20480;
constexpr uint32_t SZ_W3 = 16384 + 24576, SZ_W2 = 16384 + 16384, SZ_W = SZ_W3 + 16384;
constexpr uint32_t SZ_PARK = 49152;
constexpr uint32_t SZ_OL = SZ_O + 8192;
constexpr int NBAR = 16, FLIGHT = RING / SZ_KV + 1;
constexpr int EARLY = 3;
constexpr int kSteps = kHD / 64;
constexpr int TAIL = 4;
constexpr uint32_t KV_CH = 64, KV_SBO = 3072;
constexpr int SMEM_BYTES = RING + 1024 + 1024;
constexpr int N_TEAM = 16, N_CL = 66, MAX_OPS = 22, MAX_EV = 72, MAX_TAB = 47, N_TILE = N_TEAM * kH, MAX_PARK = 128, ID_PART = N_TILE + MAX_PARK;
enum : uint32_t { OP_END = 0, OP_Q = 1, OP_A = 2, OP_O = 3, F_PARK = 1 << 11,
                  C_WIDE = 1 << 27, C_PEND = 1 << 26, P_GATE = 1 << 12, P_WIDE = 1 << 11, P_LD = 1 << 12, P_PRE = 1 << 22, P_LASTW = 1 << 29, P_LASTX = 1 << 30,
                  I_NEXT = 8, E_ON = 1 << 15, E_FREE = 1 << 14, E_LAST = 1 << 13, E_DRAW = 1 << 12, E_JOB = 1 << 11 };

constexpr uint32_t DBG_DEFAULT = 0x040800;

struct alignas(1024) Scratch {
  unsigned int flag[2047];
  unsigned int ticket;
  uint4 part[N_TEAM * 2 * 2 * 5120];
  uint4 tile[N_TILE * 2 * 3072];
};

struct alignas(64) Params {
  const char* xw[2];
  uint16_t first[80];
  Scratch* g;
  uint32_t dbg;
  CUtensorMap x[2], wq[2], k[2], v[2], wo[2], wo3[2], wo2[2], out;
  struct {
    uint32_t c[MAX_OPS];
    uint32_t p[MAX_OPS];
    uint16_t n_ev, ev[MAX_TAB];
  } prog[N_CL];
  const char* kv[4];
  uint32_t job[N_CL];
  uint16_t slot[N_TILE];
  uint8_t info[ID_PART];
};

__device__ Scratch g_scratch;

template <int TB, int TA = 0>
__device__ __forceinline__ void wgmma_ss_n64(float (&d)[32], uint64_t da, uint64_t db, int scale_d) {
  asm volatile("{\n.reg .pred p;\nsetp.ne.b32 p, %34, 0;\n"
    "wgmma.mma_async.sync.aligned.m64n64k16.f32.bf16.bf16 {%0, %1, %2, %3, %4, %5, %6, %7, %8, %9, %10, %11, %12, %13, %14, %15, %16, %17, %18, %19, %20, %21, %22, %23, %24, %25, %26, %27, %28, %29, %30, %31}, %32, %33, p, 1, 1, %35, %36;\n}\n"
    : "+f"(d[0]), "+f"(d[1]), "+f"(d[2]), "+f"(d[3]), "+f"(d[4]), "+f"(d[5]), "+f"(d[6]), "+f"(d[7]), "+f"(d[8]), "+f"(d[9]), "+f"(d[10]), "+f"(d[11]), "+f"(d[12]), "+f"(d[13]), "+f"(d[14]), "+f"(d[15]), "+f"(d[16]), "+f"(d[17]), "+f"(d[18]), "+f"(d[19]), "+f"(d[20]), "+f"(d[21]), "+f"(d[22]), "+f"(d[23]), "+f"(d[24]), "+f"(d[25]), "+f"(d[26]), "+f"(d[27]), "+f"(d[28]), "+f"(d[29]), "+f"(d[30]), "+f"(d[31])
    : "l"(da), "l"(db), "r"(scale_d), "n"(TA), "n"(TB));
}
template <int TB>
__device__ __forceinline__ void wgmma_rs_n64(float (&d)[32], uint32_t a0, uint32_t a1, uint32_t a2, uint32_t a3, uint64_t db, int scale_d) {
  asm volatile("{\n.reg .pred p;\nsetp.ne.b32 p, %37, 0;\n"
    "wgmma.mma_async.sync.aligned.m64n64k16.f32.bf16.bf16 {%0, %1, %2, %3, %4, %5, %6, %7, %8, %9, %10, %11, %12, %13, %14, %15, %16, %17, %18, %19, %20, %21, %22, %23, %24, %25, %26, %27, %28, %29, %30, %31}, {%32, %33, %34, %35}, %36, p, 1, 1, %38;\n}\n"
    : "+f"(d[0]), "+f"(d[1]), "+f"(d[2]), "+f"(d[3]), "+f"(d[4]), "+f"(d[5]), "+f"(d[6]), "+f"(d[7]), "+f"(d[8]), "+f"(d[9]), "+f"(d[10]), "+f"(d[11]), "+f"(d[12]), "+f"(d[13]), "+f"(d[14]), "+f"(d[15]), "+f"(d[16]), "+f"(d[17]), "+f"(d[18]), "+f"(d[19]), "+f"(d[20]), "+f"(d[21]), "+f"(d[22]), "+f"(d[23]), "+f"(d[24]), "+f"(d[25]), "+f"(d[26]), "+f"(d[27]), "+f"(d[28]), "+f"(d[29]), "+f"(d[30]), "+f"(d[31])
    : "r"(a0), "r"(a1), "r"(a2), "r"(a3), "l"(db), "r"(scale_d), "n"(TB));
}
template <int TB, int TA = 0>
__device__ __forceinline__ void wgmma_ss_n128(float (&d)[64], uint64_t da, uint64_t db, int scale_d) {
  asm volatile("{\n.reg .pred p;\nsetp.ne.b32 p, %66, 0;\n"
    "wgmma.mma_async.sync.aligned.m64n128k16.f32.bf16.bf16 {%0, %1, %2, %3, %4, %5, %6, %7, %8, %9, %10, %11, %12, %13, %14, %15, %16, %17, %18, %19, %20, %21, %22, %23, %24, %25, %26, %27, %28, %29, %30, %31, %32, %33, %34, %35, %36, %37, %38, %39, %40, %41, %42, %43, %44, %45, %46, %47, %48, %49, %50, %51, %52, %53, %54, %55, %56, %57, %58, %59, %60, %61, %62, %63}, %64, %65, p, 1, 1, %67, %68;\n}\n"
    : "+f"(d[0]), "+f"(d[1]), "+f"(d[2]), "+f"(d[3]), "+f"(d[4]), "+f"(d[5]), "+f"(d[6]), "+f"(d[7]), "+f"(d[8]), "+f"(d[9]), "+f"(d[10]), "+f"(d[11]), "+f"(d[12]), "+f"(d[13]), "+f"(d[14]), "+f"(d[15]), "+f"(d[16]), "+f"(d[17]), "+f"(d[18]), "+f"(d[19]), "+f"(d[20]), "+f"(d[21]), "+f"(d[22]), "+f"(d[23]), "+f"(d[24]), "+f"(d[25]), "+f"(d[26]), "+f"(d[27]), "+f"(d[28]), "+f"(d[29]), "+f"(d[30]), "+f"(d[31]), "+f"(d[32]), "+f"(d[33]), "+f"(d[34]), "+f"(d[35]), "+f"(d[36]), "+f"(d[37]), "+f"(d[38]), "+f"(d[39]), "+f"(d[40]), "+f"(d[41]), "+f"(d[42]), "+f"(d[43]), "+f"(d[44]), "+f"(d[45]), "+f"(d[46]), "+f"(d[47]), "+f"(d[48]), "+f"(d[49]), "+f"(d[50]), "+f"(d[51]), "+f"(d[52]), "+f"(d[53]), "+f"(d[54]), "+f"(d[55]), "+f"(d[56]), "+f"(d[57]), "+f"(d[58]), "+f"(d[59]), "+f"(d[60]), "+f"(d[61]), "+f"(d[62]), "+f"(d[63])
    : "l"(da), "l"(db), "r"(scale_d), "n"(TA), "n"(TB));
}
template <int TB>
__device__ __forceinline__ void wgmma_rs_n128(float (&d)[64], uint32_t a0, uint32_t a1, uint32_t a2, uint32_t a3, uint64_t db, int scale_d) {
  asm volatile("{\n.reg .pred p;\nsetp.ne.b32 p, %69, 0;\n"
    "wgmma.mma_async.sync.aligned.m64n128k16.f32.bf16.bf16 {%0, %1, %2, %3, %4, %5, %6, %7, %8, %9, %10, %11, %12, %13, %14, %15, %16, %17, %18, %19, %20, %21, %22, %23, %24, %25, %26, %27, %28, %29, %30, %31, %32, %33, %34, %35, %36, %37, %38, %39, %40, %41, %42, %43, %44, %45, %46, %47, %48, %49, %50, %51, %52, %53, %54, %55, %56, %57, %58, %59, %60, %61, %62, %63}, {%64, %65, %66, %67}, %68, p, 1, 1, %70;\n}\n"
    : "+f"(d[0]), "+f"(d[1]), "+f"(d[2]), "+f"(d[3]), "+f"(d[4]), "+f"(d[5]), "+f"(d[6]), "+f"(d[7]), "+f"(d[8]), "+f"(d[9]), "+f"(d[10]), "+f"(d[11]), "+f"(d[12]), "+f"(d[13]), "+f"(d[14]), "+f"(d[15]), "+f"(d[16]), "+f"(d[17]), "+f"(d[18]), "+f"(d[19]), "+f"(d[20]), "+f"(d[21]), "+f"(d[22]), "+f"(d[23]), "+f"(d[24]), "+f"(d[25]), "+f"(d[26]), "+f"(d[27]), "+f"(d[28]), "+f"(d[29]), "+f"(d[30]), "+f"(d[31]), "+f"(d[32]), "+f"(d[33]), "+f"(d[34]), "+f"(d[35]), "+f"(d[36]), "+f"(d[37]), "+f"(d[38]), "+f"(d[39]), "+f"(d[40]), "+f"(d[41]), "+f"(d[42]), "+f"(d[43]), "+f"(d[44]), "+f"(d[45]), "+f"(d[46]), "+f"(d[47]), "+f"(d[48]), "+f"(d[49]), "+f"(d[50]), "+f"(d[51]), "+f"(d[52]), "+f"(d[53]), "+f"(d[54]), "+f"(d[55]), "+f"(d[56]), "+f"(d[57]), "+f"(d[58]), "+f"(d[59]), "+f"(d[60]), "+f"(d[61]), "+f"(d[62]), "+f"(d[63])
    : "r"(a0), "r"(a1), "r"(a2), "r"(a3), "l"(db), "r"(scale_d), "n"(TB));
}
template <int TB, int TA = 0>
__device__ __forceinline__ void wgmma_ss_n160(float (&d)[80], uint64_t da, uint64_t db, int scale_d) {
  asm volatile("{\n.reg .pred p;\nsetp.ne.b32 p, %82, 0;\n"
    "wgmma.mma_async.sync.aligned.m64n160k16.f32.bf16.bf16 {%0, %1, %2, %3, %4, %5, %6, %7, %8, %9, %10, %11, %12, %13, %14, %15, %16, %17, %18, %19, %20, %21, %22, %23, %24, %25, %26, %27, %28, %29, %30, %31, %32, %33, %34, %35, %36, %37, %38, %39, %40, %41, %42, %43, %44, %45, %46, %47, %48, %49, %50, %51, %52, %53, %54, %55, %56, %57, %58, %59, %60, %61, %62, %63, %64, %65, %66, %67, %68, %69, %70, %71, %72, %73, %74, %75, %76, %77, %78, %79}, %80, %81, p, 1, 1, %83, %84;\n}\n"
    : "+f"(d[0]), "+f"(d[1]), "+f"(d[2]), "+f"(d[3]), "+f"(d[4]), "+f"(d[5]), "+f"(d[6]), "+f"(d[7]), "+f"(d[8]), "+f"(d[9]), "+f"(d[10]), "+f"(d[11]), "+f"(d[12]), "+f"(d[13]), "+f"(d[14]), "+f"(d[15]), "+f"(d[16]), "+f"(d[17]), "+f"(d[18]), "+f"(d[19]), "+f"(d[20]), "+f"(d[21]), "+f"(d[22]), "+f"(d[23]), "+f"(d[24]), "+f"(d[25]), "+f"(d[26]), "+f"(d[27]), "+f"(d[28]), "+f"(d[29]), "+f"(d[30]), "+f"(d[31]), "+f"(d[32]), "+f"(d[33]), "+f"(d[34]), "+f"(d[35]), "+f"(d[36]), "+f"(d[37]), "+f"(d[38]), "+f"(d[39]), "+f"(d[40]), "+f"(d[41]), "+f"(d[42]), "+f"(d[43]), "+f"(d[44]), "+f"(d[45]), "+f"(d[46]), "+f"(d[47]), "+f"(d[48]), "+f"(d[49]), "+f"(d[50]), "+f"(d[51]), "+f"(d[52]), "+f"(d[53]), "+f"(d[54]), "+f"(d[55]), "+f"(d[56]), "+f"(d[57]), "+f"(d[58]), "+f"(d[59]), "+f"(d[60]), "+f"(d[61]), "+f"(d[62]), "+f"(d[63]), "+f"(d[64]), "+f"(d[65]), "+f"(d[66]), "+f"(d[67]), "+f"(d[68]), "+f"(d[69]), "+f"(d[70]), "+f"(d[71]), "+f"(d[72]), "+f"(d[73]), "+f"(d[74]), "+f"(d[75]), "+f"(d[76]), "+f"(d[77]), "+f"(d[78]), "+f"(d[79])
    : "l"(da), "l"(db), "r"(scale_d), "n"(TA), "n"(TB));
}
template <int TB>
__device__ __forceinline__ void wgmma_rs_n160(float (&d)[80], uint32_t a0, uint32_t a1, uint32_t a2, uint32_t a3, uint64_t db, int scale_d) {
  asm volatile("{\n.reg .pred p;\nsetp.ne.b32 p, %85, 0;\n"
    "wgmma.mma_async.sync.aligned.m64n160k16.f32.bf16.bf16 {%0, %1, %2, %3, %4, %5, %6, %7, %8, %9, %10, %11, %12, %13, %14, %15, %16, %17, %18, %19, %20, %21, %22, %23, %24, %25, %26, %27, %28, %29, %30, %31, %32, %33, %34, %35, %36, %37, %38, %39, %40, %41, %42, %43, %44, %45, %46, %47, %48, %49, %50, %51, %52, %53, %54, %55, %56, %57, %58, %59, %60, %61, %62, %63, %64, %65, %66, %67, %68, %69, %70, %71, %72, %73, %74, %75, %76, %77, %78, %79}, {%80, %81, %82, %83}, %84, p, 1, 1, %86;\n}\n"
    : "+f"(d[0]), "+f"(d[1]), "+f"(d[2]), "+f"(d[3]), "+f"(d[4]), "+f"(d[5]), "+f"(d[6]), "+f"(d[7]), "+f"(d[8]), "+f"(d[9]), "+f"(d[10]), "+f"(d[11]), "+f"(d[12]), "+f"(d[13]), "+f"(d[14]), "+f"(d[15]), "+f"(d[16]), "+f"(d[17]), "+f"(d[18]), "+f"(d[19]), "+f"(d[20]), "+f"(d[21]), "+f"(d[22]), "+f"(d[23]), "+f"(d[24]), "+f"(d[25]), "+f"(d[26]), "+f"(d[27]), "+f"(d[28]), "+f"(d[29]), "+f"(d[30]), "+f"(d[31]), "+f"(d[32]), "+f"(d[33]), "+f"(d[34]), "+f"(d[35]), "+f"(d[36]), "+f"(d[37]), "+f"(d[38]), "+f"(d[39]), "+f"(d[40]), "+f"(d[41]), "+f"(d[42]), "+f"(d[43]), "+f"(d[44]), "+f"(d[45]), "+f"(d[46]), "+f"(d[47]), "+f"(d[48]), "+f"(d[49]), "+f"(d[50]), "+f"(d[51]), "+f"(d[52]), "+f"(d[53]), "+f"(d[54]), "+f"(d[55]), "+f"(d[56]), "+f"(d[57]), "+f"(d[58]), "+f"(d[59]), "+f"(d[60]), "+f"(d[61]), "+f"(d[62]), "+f"(d[63]), "+f"(d[64]), "+f"(d[65]), "+f"(d[66]), "+f"(d[67]), "+f"(d[68]), "+f"(d[69]), "+f"(d[70]), "+f"(d[71]), "+f"(d[72]), "+f"(d[73]), "+f"(d[74]), "+f"(d[75]), "+f"(d[76]), "+f"(d[77]), "+f"(d[78]), "+f"(d[79])
    : "r"(a0), "r"(a1), "r"(a2), "r"(a3), "l"(db), "r"(scale_d), "n"(TB));
}
template <int TB, int TA = 0>
__device__ __forceinline__ void wgmma_ss_n192(float (&d)[96], uint64_t da, uint64_t db, int scale_d) {
  asm volatile("{\n.reg .pred p;\nsetp.ne.b32 p, %98, 0;\n"
    "wgmma.mma_async.sync.aligned.m64n192k16.f32.bf16.bf16 {%0, %1, %2, %3, %4, %5, %6, %7, %8, %9, %10, %11, %12, %13, %14, %15, %16, %17, %18, %19, %20, %21, %22, %23, %24, %25, %26, %27, %28, %29, %30, %31, %32, %33, %34, %35, %36, %37, %38, %39, %40, %41, %42, %43, %44, %45, %46, %47, %48, %49, %50, %51, %52, %53, %54, %55, %56, %57, %58, %59, %60, %61, %62, %63, %64, %65, %66, %67, %68, %69, %70, %71, %72, %73, %74, %75, %76, %77, %78, %79, %80, %81, %82, %83, %84, %85, %86, %87, %88, %89, %90, %91, %92, %93, %94, %95}, %96, %97, p, 1, 1, %99, %100;\n}\n"
    : "+f"(d[0]), "+f"(d[1]), "+f"(d[2]), "+f"(d[3]), "+f"(d[4]), "+f"(d[5]), "+f"(d[6]), "+f"(d[7]), "+f"(d[8]), "+f"(d[9]), "+f"(d[10]), "+f"(d[11]), "+f"(d[12]), "+f"(d[13]), "+f"(d[14]), "+f"(d[15]), "+f"(d[16]), "+f"(d[17]), "+f"(d[18]), "+f"(d[19]), "+f"(d[20]), "+f"(d[21]), "+f"(d[22]), "+f"(d[23]), "+f"(d[24]), "+f"(d[25]), "+f"(d[26]), "+f"(d[27]), "+f"(d[28]), "+f"(d[29]), "+f"(d[30]), "+f"(d[31]), "+f"(d[32]), "+f"(d[33]), "+f"(d[34]), "+f"(d[35]), "+f"(d[36]), "+f"(d[37]), "+f"(d[38]), "+f"(d[39]), "+f"(d[40]), "+f"(d[41]), "+f"(d[42]), "+f"(d[43]), "+f"(d[44]), "+f"(d[45]), "+f"(d[46]), "+f"(d[47]), "+f"(d[48]), "+f"(d[49]), "+f"(d[50]), "+f"(d[51]), "+f"(d[52]), "+f"(d[53]), "+f"(d[54]), "+f"(d[55]), "+f"(d[56]), "+f"(d[57]), "+f"(d[58]), "+f"(d[59]), "+f"(d[60]), "+f"(d[61]), "+f"(d[62]), "+f"(d[63]), "+f"(d[64]), "+f"(d[65]), "+f"(d[66]), "+f"(d[67]), "+f"(d[68]), "+f"(d[69]), "+f"(d[70]), "+f"(d[71]), "+f"(d[72]), "+f"(d[73]), "+f"(d[74]), "+f"(d[75]), "+f"(d[76]), "+f"(d[77]), "+f"(d[78]), "+f"(d[79]), "+f"(d[80]), "+f"(d[81]), "+f"(d[82]), "+f"(d[83]), "+f"(d[84]), "+f"(d[85]), "+f"(d[86]), "+f"(d[87]), "+f"(d[88]), "+f"(d[89]), "+f"(d[90]), "+f"(d[91]), "+f"(d[92]), "+f"(d[93]), "+f"(d[94]), "+f"(d[95])
    : "l"(da), "l"(db), "r"(scale_d), "n"(TA), "n"(TB));
}
template <int TB>
__device__ __forceinline__ void wgmma_rs_n192(float (&d)[96], uint32_t a0, uint32_t a1, uint32_t a2, uint32_t a3, uint64_t db, int scale_d) {
  asm volatile("{\n.reg .pred p;\nsetp.ne.b32 p, %101, 0;\n"
    "wgmma.mma_async.sync.aligned.m64n192k16.f32.bf16.bf16 {%0, %1, %2, %3, %4, %5, %6, %7, %8, %9, %10, %11, %12, %13, %14, %15, %16, %17, %18, %19, %20, %21, %22, %23, %24, %25, %26, %27, %28, %29, %30, %31, %32, %33, %34, %35, %36, %37, %38, %39, %40, %41, %42, %43, %44, %45, %46, %47, %48, %49, %50, %51, %52, %53, %54, %55, %56, %57, %58, %59, %60, %61, %62, %63, %64, %65, %66, %67, %68, %69, %70, %71, %72, %73, %74, %75, %76, %77, %78, %79, %80, %81, %82, %83, %84, %85, %86, %87, %88, %89, %90, %91, %92, %93, %94, %95}, {%96, %97, %98, %99}, %100, p, 1, 1, %102;\n}\n"
    : "+f"(d[0]), "+f"(d[1]), "+f"(d[2]), "+f"(d[3]), "+f"(d[4]), "+f"(d[5]), "+f"(d[6]), "+f"(d[7]), "+f"(d[8]), "+f"(d[9]), "+f"(d[10]), "+f"(d[11]), "+f"(d[12]), "+f"(d[13]), "+f"(d[14]), "+f"(d[15]), "+f"(d[16]), "+f"(d[17]), "+f"(d[18]), "+f"(d[19]), "+f"(d[20]), "+f"(d[21]), "+f"(d[22]), "+f"(d[23]), "+f"(d[24]), "+f"(d[25]), "+f"(d[26]), "+f"(d[27]), "+f"(d[28]), "+f"(d[29]), "+f"(d[30]), "+f"(d[31]), "+f"(d[32]), "+f"(d[33]), "+f"(d[34]), "+f"(d[35]), "+f"(d[36]), "+f"(d[37]), "+f"(d[38]), "+f"(d[39]), "+f"(d[40]), "+f"(d[41]), "+f"(d[42]), "+f"(d[43]), "+f"(d[44]), "+f"(d[45]), "+f"(d[46]), "+f"(d[47]), "+f"(d[48]), "+f"(d[49]), "+f"(d[50]), "+f"(d[51]), "+f"(d[52]), "+f"(d[53]), "+f"(d[54]), "+f"(d[55]), "+f"(d[56]), "+f"(d[57]), "+f"(d[58]), "+f"(d[59]), "+f"(d[60]), "+f"(d[61]), "+f"(d[62]), "+f"(d[63]), "+f"(d[64]), "+f"(d[65]), "+f"(d[66]), "+f"(d[67]), "+f"(d[68]), "+f"(d[69]), "+f"(d[70]), "+f"(d[71]), "+f"(d[72]), "+f"(d[73]), "+f"(d[74]), "+f"(d[75]), "+f"(d[76]), "+f"(d[77]), "+f"(d[78]), "+f"(d[79]), "+f"(d[80]), "+f"(d[81]), "+f"(d[82]), "+f"(d[83]), "+f"(d[84]), "+f"(d[85]), "+f"(d[86]), "+f"(d[87]), "+f"(d[88]), "+f"(d[89]), "+f"(d[90]), "+f"(d[91]), "+f"(d[92]), "+f"(d[93]), "+f"(d[94]), "+f"(d[95])
    : "r"(a0), "r"(a1), "r"(a2), "r"(a3), "l"(db), "r"(scale_d), "n"(TB));
}

__device__ __forceinline__ uint32_t smem_u32(const void* p) { return (uint32_t)__cvta_generic_to_shared(p); }
__device__ __forceinline__ void wg_fence() { asm volatile("wgmma.fence.sync.aligned;" ::: "memory"); }
__device__ __forceinline__ void wg_commit() { asm volatile("wgmma.commit_group.sync.aligned;" ::: "memory"); }
template <int N> __device__ __forceinline__ void wg_wait() { asm volatile("wgmma.wait_group.sync.aligned %0;" ::"n"(N) : "memory"); }
__device__ __forceinline__ void sched_fence(uint32_t& keep, bool never) {
  asm volatile("{\n.reg .pred p;\nsetp.ne.b32 p, %1, 0;\n@p mov.u32 %0, %%clock;\n}\n" : "+r"(keep) : "r"((int)never) : "memory");
}
template <int N> __device__ __forceinline__ void fence_regs(float (&r)[N]) {
#pragma unroll
  for (int i = 0; i < N; i++) asm volatile("" : "+f"(r[i])::"memory");
}
template <int N> __device__ __forceinline__ void undefine(float (&r)[N]) {
#pragma unroll
  for (int i = 0; i < N; i++) asm volatile("" : "=f"(r[i]));
}
template <int N> __device__ __forceinline__ void fence_regs(uint32_t (&r)[N]) {
#pragma unroll
  for (int i = 0; i < N; i++) asm volatile("" : "+r"(r[i])::"memory");
}
__device__ __forceinline__ uint64_t mk_desc(uint32_t a16, uint32_t lbo, uint32_t sbo, uint32_t swz) {
  uint64_t d;
  asm("mov.b64 %0, {%1, %2};" : "=l"(d) : "r"(a16 + ((lbo >> 4) << 16)), "r"((sbo >> 4) | (swz << 30)));
  return d;
}
__device__ __forceinline__ void mbar_init(uint32_t bar, uint32_t cnt) {
  asm volatile("mbarrier.init.shared::cta.b64 [%0], %1;" ::"r"(bar), "r"(cnt) : "memory");
}
__device__ __forceinline__ void mbar_expect(uint32_t bar, uint32_t tx) {
  asm volatile("mbarrier.arrive.expect_tx.shared::cta.b64 _, [%0], %1;" ::"r"(bar), "r"(tx) : "memory");
}
__device__ __forceinline__ bool mbar_test(uint32_t bar, uint32_t ph) {
  uint32_t ok;
  asm volatile("{\n.reg .pred p;\nmbarrier.test_wait.parity.shared::cta.b64 p, [%1], %2;\nselp.u32 %0, 1, 0, p;\n}\n"
               : "=r"(ok) : "r"(bar), "r"(ph) : "memory");
  return ok;
}
__device__ __forceinline__ bool mbar_try(uint32_t bar, uint32_t ph, uint32_t ns) {
  uint32_t ok;
  asm volatile("{\n.reg .pred p;\nmbarrier.try_wait.parity.shared::cta.b64 p, [%1], %2, %3;\nselp.u32 %0, 1, 0, p;\n}\n"
               : "=r"(ok) : "r"(bar), "r"(ph), "r"(ns) : "memory");
  return ok;
}
__device__ __forceinline__ void mbar_wait(uint32_t bar, uint32_t ph) {
  asm volatile("{\n.reg .pred p;\n.reg .u32 n;\nmov.u32 n, 0;\n"
               "LOOP:\nmbarrier.try_wait.parity.shared::cta.b64 p, [%0], %1;\n@p bra DONE;\n"
               "add.u32 n, n, 1;\nsetp.lt.u32 p, n, 0x1000000;\n@p bra LOOP;\ntrap;\n"
               "DONE:\n}\n" ::"r"(bar), "r"(ph) : "memory");
}
__device__ __forceinline__ void mbar_wait_long(uint32_t bar) {
  asm volatile("{\n.reg .pred p;\n.reg .u32 n;\nmov.u32 n, 0;\n"
               "LOOP:\nmbarrier.try_wait.parity.shared::cta.b64 p, [%0], 0, 20000;\n@p bra DONE;\n"
               "add.u32 n, n, 1;\nsetp.lt.u32 p, n, 0x100000;\n@p bra LOOP;\ntrap;\n"
               "DONE:\n}\n" ::"r"(bar) : "memory");
}
__device__ __forceinline__ void mbar_arrive_cluster_if(bool on, uint32_t addr) {
  asm volatile("{\n.reg .pred p;\nsetp.ne.b32 p, %1, 0;\n@p mbarrier.arrive.shared::cluster.b64 _, [%0];\n}\n" ::"r"(addr), "r"((int)on) : "memory");
}
__device__ __forceinline__ void mbar_arrive_cluster_n(uint32_t n, uint32_t addr) {
  asm volatile("{\n.reg .pred p;\nsetp.ne.b32 p, %1, 0;\n@p mbarrier.arrive.shared::cluster.b64 _, [%0], %1;\n}\n" ::"r"(addr), "r"(n) : "memory");
}
__device__ __forceinline__ void tma2d(uint32_t dst, const CUtensorMap* m, uint32_t bar, int c0, int c1) {
  asm volatile("cp.async.bulk.tensor.2d.shared::cluster.global.mbarrier::complete_tx::bytes [%0], [%1, {%3, %4}], [%2];"
               ::"r"(dst), "l"(m), "r"(bar), "r"(c0), "r"(c1) : "memory");
}
__device__ __forceinline__ void tma3d(uint32_t dst, const CUtensorMap* m, uint32_t bar, int c0, int c1, int c2) {
  asm volatile("cp.async.bulk.tensor.3d.shared::cluster.global.mbarrier::complete_tx::bytes [%0], [%1, {%3, %4, %5}], [%2];"
               ::"r"(dst), "l"(m), "r"(bar), "r"(c0), "r"(c1), "r"(c2) : "memory");
}
__device__ __forceinline__ void tma2d_hint(uint32_t dst, const CUtensorMap* m, uint32_t bar, int c0, int c1, uint64_t pol) {
  asm volatile("cp.async.bulk.tensor.2d.shared::cluster.global.mbarrier::complete_tx::bytes.L2::cache_hint [%0], [%1, {%3, %4}], [%2], %5;"
               ::"r"(dst), "l"(m), "r"(bar), "r"(c0), "r"(c1), "l"(pol) : "memory");
}
__device__ __forceinline__ void tma3d_mc_hint(uint32_t dst, const CUtensorMap* m, uint32_t bar, int c1, int c2, uint64_t pol) {
  asm volatile("cp.async.bulk.tensor.3d.shared::cluster.global.mbarrier::complete_tx::bytes.multicast::cluster.L2::cache_hint"
               " [%0], [%1, {%3, %4, %5}], [%2], %6, %7;"
               ::"r"(dst), "l"(m), "r"(bar), "r"(0), "r"(c1), "r"(c2), "h"((uint16_t)3), "l"(pol) : "memory");
}
__device__ __forceinline__ void tma5d_mc_hint(uint32_t dst, const CUtensorMap* m, uint32_t bar, int c2, int c4, uint64_t pol) {
  asm volatile("cp.async.bulk.tensor.5d.shared::cluster.global.mbarrier::complete_tx::bytes.multicast::cluster.L2::cache_hint"
               " [%0], [%1, {%3, %3, %4, %3, %5}], [%2], %6, %7;"
               ::"r"(dst), "l"(m), "r"(bar), "r"(0), "r"(c2), "r"(c4), "h"((uint16_t)3), "l"(pol) : "memory");
}
__device__ __forceinline__ void tma3d_store(const CUtensorMap* m, uint32_t src, int c0, int c1, int c2) {
  asm volatile("cp.async.bulk.tensor.3d.global.shared::cta.bulk_group [%0, {%2, %3, %4}], [%1];"
               ::"l"(m), "r"(src), "r"(c0), "r"(c1), "r"(c2) : "memory");
}
__device__ __forceinline__ void bar_sync(int id, int n) { asm volatile("bar.sync %0, %1;" ::"r"(id), "r"(n) : "memory"); }
__device__ __forceinline__ uint32_t pack_bf16(float lo, float hi) {
  uint32_t r;
  asm("cvt.rn.bf16x2.f32 %0, %1, %2;" : "=r"(r) : "f"(hi), "f"(lo));
  return r;
}
__device__ __forceinline__ float ex2(float x) {
  float y;
  asm("ex2.approx.ftz.f32 %0, %1;" : "=f"(y) : "f"(x));
  return y;
}
__device__ __forceinline__ float rcp(float x) {
  float y;
  asm("rcp.approx.ftz.f32 %0, %1;" : "=f"(y) : "f"(x));
  return y;
}
__device__ __forceinline__ void stsm4(uint32_t addr, uint32_t a, uint32_t b, uint32_t c, uint32_t d) {
  asm volatile("stmatrix.sync.aligned.m8n8.x4.shared.b16 [%0], {%1, %2, %3, %4};" ::"r"(addr), "r"(a), "r"(b), "r"(c), "r"(d) : "memory");
}

__device__ __forceinline__ void tma4d_mc_hint(uint32_t dst, const CUtensorMap* m, uint32_t bar, int c3, uint64_t pol) {
  asm volatile("cp.async.bulk.tensor.4d.shared::cluster.global.mbarrier::complete_tx::bytes.multicast::cluster.L2::cache_hint"
               " [%0], [%1, {%3, %3, %3, %4}], [%2], %5, %6;"
               ::"r"(dst), "l"(m), "r"(bar), "r"(0), "r"(c3), "h"((uint16_t)3), "l"(pol) : "memory");
}
__device__ __forceinline__ void bulk_load_hint(uint32_t dst, const void* src, uint32_t bytes, uint32_t bar, uint64_t pol) {
  asm volatile("cp.async.bulk.shared::cluster.global.mbarrier::complete_tx::bytes.L2::cache_hint [%0], [%1], %2, [%3], %4;"
               ::"r"(dst), "l"(src), "r"(bytes), "r"(bar), "l"(pol) : "memory");
}
__device__ __forceinline__ void stg2_if(bool on, void* p, uint32_t a, uint32_t b, uint32_t c, uint32_t d, uint32_t e, uint32_t f,
                                        uint32_t g, uint32_t h, uint64_t pol) {
  asm volatile("{\n.reg .pred p;\nsetp.ne.b32 p, %10, 0;\n"
               "@p st.global.L2::cache_hint.v4.b32 [%0], {%1, %2, %3, %4}, %9;\n"
               "@p st.global.L2::cache_hint.v4.b32 [%0 + 512], {%5, %6, %7, %8}, %9;\n}\n"
               ::"l"(p), "r"(a), "r"(b), "r"(c), "r"(d), "r"(e), "r"(f), "r"(g), "r"(h), "l"(pol), "r"((int)on) : "memory");
}
__device__ __forceinline__ uint64_t evict_first() {
  uint64_t p;
  asm("createpolicy.fractional.L2::evict_first.b64 %0, 1.0;" : "=l"(p));
  return p;
}
__device__ __forceinline__ uint64_t no_hint() {
  uint64_t p;
  asm("createpolicy.cvt.L2.b64 %0, %1;" : "=l"(p) : "l"(static_cast<uint64_t>(cuda::access_property{})));
  return p;
}
__device__ __forceinline__ bool elect() {
  uint32_t ok;
  asm volatile("{\n.reg .pred p;\nelect.sync _|p, 0xffffffff;\nselp.u32 %0, 1, 0, p;\n}\n" : "=r"(ok));
  return ok;
}
__device__ __forceinline__ void mbar_arrive(uint32_t bar) {
  asm volatile("mbarrier.arrive.shared::cta.b64 _, [%0];" ::"r"(bar) : "memory");
}
__device__ __forceinline__ void mbar_arrive_if(bool on, uint32_t bar) {
  asm volatile("{\n.reg .pred p;\nsetp.ne.b32 p, %1, 0;\n@p mbarrier.arrive.shared::cta.b64 _, [%0];\n}\n" ::"r"(bar), "r"((int)on) : "memory");
}
__device__ __forceinline__ void lds2_if(bool on, uint32_t p, uint32_t (&t)[8]) {
  asm volatile("{\n.reg .pred p;\nsetp.ne.b32 p, %9, 0;\n@p ld.shared.v4.b32 {%0, %1, %2, %3}, [%8];\n@p ld.shared.v4.b32 {%4, %5, %6, %7}, [%8 + 512];\n}\n"
               : "+r"(t[0]), "+r"(t[1]), "+r"(t[2]), "+r"(t[3]), "+r"(t[4]), "+r"(t[5]), "+r"(t[6]), "+r"(t[7]) : "r"(p), "r"((int)on) : "memory");
}
__device__ __forceinline__ void lds128(uint32_t p, uint32_t& a, uint32_t& b, uint32_t& c, uint32_t& d) {
  asm volatile("ld.shared.v4.b32 {%0, %1, %2, %3}, [%4];" : "=r"(a), "=r"(b), "=r"(c), "=r"(d) : "r"(p) : "memory");
}
template <class T> __device__ __forceinline__ T* ptr_add(T* base, uint32_t bytes) {
  T* r;
  asm("{\n.reg .u32 lo, hi;\nmov.b64 {lo, hi}, %1;\nadd.cc.u32 lo, lo, %2;\naddc.u32 hi, hi, 0;\nmov.b64 %0, {lo, hi};\n}\n" : "=l"(r) : "l"(base), "r"(bytes));
  return r;
}
__device__ __forceinline__ uint32_t lds32(uint32_t p) {
  uint32_t v;
  asm volatile("ld.volatile.shared.u32 %0, [%1];" : "=r"(v) : "r"(p) : "memory");
  return v;
}
__device__ __forceinline__ uint32_t flag_get(const unsigned int* p) {
  uint32_t v;
  asm volatile("ld.acquire.gpu.global.u32 %0, [%1];" : "=r"(v) : "l"(p) : "memory");
  return v;
}
__device__ __forceinline__ uint32_t wait_word(uint32_t p, uint32_t target) {
  uint32_t v;
  asm volatile("{\n.reg .pred p;\n.reg .u32 n;\nmov.u32 n, 0;\n"
               "LOOP:\nld.acquire.cta.shared.u32 %0, [%1];\nsetp.ge.u32 p, %0, %2;\n@p bra DONE;\n"
               "nanosleep.u32 %3;\nadd.u32 n, n, 1;\nsetp.lt.u32 p, n, 0x400000;\n@p bra LOOP;\ntrap;\n"
               "DONE:\n}\n" : "=r"(v) : "r"(p), "r"(target), "n"(400) : "memory");
  return v;
}
__device__ __forceinline__ void flag_set(unsigned int* p, uint32_t v) {
  asm volatile("st.release.gpu.global.u32 [%0], %1;" ::"l"(p), "r"(v) : "memory");
}
__device__ __forceinline__ void flag_dec(unsigned int* p) {
  asm volatile("red.relaxed.gpu.global.add.u32 [%0], 0xffffffff;" ::"l"(p) : "memory");
}

struct Cursor {
  uint32_t n;
  __device__ __forceinline__ uint32_t off() const { return n & (8 * NBAR - 8); }
  __device__ __forceinline__ uint32_t ph() const { return (n / (8 * NBAR)) & 1; }
  __device__ __forceinline__ void next() { n += 8; }
};

constexpr float kScaleLog2 = 0.07216878364870322f * 1.4426950408889634f;
constexpr float kSumLimit = 1048576.0f;

__global__ void __cluster_dims__(2, 1, 1) __launch_bounds__(384, 1)
fused_kernel(const __grid_constant__ Params P) {
  extern __shared__ uint8_t smem_raw[];
  const uint32_t sbase = (smem_u32(smem_raw) + 1023) & ~1023u;
  const uint32_t full0 = sbase + RING, empty0 = full0 + 8 * NBAR, odone0 = empty0 + 8 * NBAR, ev0 = odone0 + 8 * MAX_OPS;
  const uint32_t progress = ev0 + 8 * MAX_EV, jobw = progress + 4;
  const uint32_t rank = blockIdx.x & 1;
  const int role = blockIdx.x >> 1;
  const int wid = __shfl_sync(0xffffffffu, (int)(threadIdx.x >> 5), 0);
  const int wg = wid >> 2;

  if (wid < 8) {
    if (elect()) {
#pragma unroll
      for (int j = 0; j < 16; j++) {
        const int i = EARLY + 16 * wid + j;
        if (i < 2 * NBAR + MAX_OPS + MAX_EV) mbar_init(full0 + 8 * i, i < NBAR ? 1 : i < 2 * NBAR ? 16 : i < 2 * NBAR + MAX_OPS ? 8 : 1);
      }
      if (wid == 7) asm volatile("st.shared.v2.u32 [%0], {0, 0};\nfence.acq_rel.cta;" ::"r"(progress) : "memory");
      asm volatile("fence.mbarrier_init.release.cluster;" ::: "memory");
    }
  } else if (wid > 8) {
    const uint32_t g = blockIdx.x * 96 + threadIdx.x - 288, w = g - 2048;
    if (g < 4096) asm volatile("prefetch.global.L2 [%0];" ::"l"(g < 2048 ? P.xw[0] + g * (kD * 2) : P.xw[1] + (w >> 5) * (kHD * 2) + (w & 31) * 128));
  } else {
    const uint32_t op0 = P.first[role];
    if (elect()) {
#pragma unroll
      for (int k = 0; k < EARLY; k++) mbar_init(full0 + 8 * k, 1);
      asm volatile("fence.mbarrier_init.release.cluster;" ::: "memory");
      const int blk = (op0 >> 10) & 1;
      if ((op0 & 3) == OP_Q) {
#pragma unroll
        for (int k = 0; k < EARLY; k++) {
          mbar_expect(full0 + 8 * k, SZ_Q);
          tma2d(sbase + k * SZ_Q, &P.x[blk], full0 + 8 * k, 64 * k, ((op0 >> 7) & 7) * kSq + rank * 128);
          tma3d(sbase + k * SZ_Q + 16384, &P.wq[blk], full0 + 8 * k, 0, 64 * k, 3 * ((op0 >> 2) & 31));
          tma3d(sbase + k * SZ_Q + 28672, &P.wq[blk], full0 + 8 * k, 0, 64 * k + 32, 3 * ((op0 >> 2) & 31));
        }
      }
      asm volatile("prefetch.tensormap [%0];\nprefetch.tensormap [%1];" ::"l"(&P.k[blk]), "l"(&P.v[blk]) : "memory");
    }
  }
  __syncwarp();
  asm volatile("barrier.cluster.arrive.relaxed.aligned;\nbarrier.cluster.wait.aligned;" ::: "memory");

  if (wg < 2) {
    asm volatile("setmaxnreg.inc.sync.aligned.u32 240;");
    const uint32_t* prog = P.prog[role].c;
    const int wid = __shfl_sync(0xffffffffu, (int)(threadIdx.x >> 5), 1), wg = wid >> 2;
    const int lane = threadIdx.x & 31, warp = wid & 3;
    uint32_t empty_rem;
    asm volatile("mapa.shared::cluster.u32 %0, %1, %2;" : "=r"(empty_rem) : "r"(empty0), "r"(lane & 1));
    uint32_t keep = (threadIdx.x & 127) < 2 ? 4 : 0;
    auto release = [&](int slot) { mbar_arrive_cluster_n(keep, empty_rem + slot); };
    auto release_warp = [&](int slot, bool on = true) { mbar_arrive_cluster_if(lane < 2 && on, empty_rem + slot); };
    Cursor r{0};
    const uint32_t ring16 = (sbase & 0x3FFFF) >> 4;
    uint32_t cur = ring16;
    bool rdy0 = false, rdy1 = false;
    auto probe1 = [&]() { rdy0 = mbar_test(full0 + r.off(), r.ph()); };
    auto probe2 = [&]() {
      Cursor n = r;
      rdy0 = mbar_test(full0 + n.off(), n.ph());
      n.next();
      rdy1 = mbar_test(full0 + n.off(), n.ph());
    };
    auto advance = [&](uint32_t bytes, uint32_t& addr) {
      const int bi = r.off();
      r.next();
      if (cur > ring16 + ((RING - bytes) >> 4)) cur = ring16;
      addr = cur;
      cur += bytes >> 4;
      return bi;
    };
    auto take = [&](bool rdy, uint32_t bytes, uint32_t& addr) {
      if (__builtin_expect(!__all_sync(0xffffffffu, rdy), 0)) mbar_wait(full0 + r.off(), r.ph());
      return advance(bytes, addr);
    };
    const bool never = P.dbg == 0xffffffffu;
    uint32_t q[48];
#pragma unroll
    for (int i = 0; i < 48; i++) q[i] = 0;
    const int row = wg * 64 + warp * 16 + (lane >> 2);
    const int img0 = row * 4 + ((lane & 3) ^ ((row >> 1) & 3));
    uint4* pend = nullptr;
    bool pend_any = false;
    const uint64_t spol = evict_first();
    int pc = 0;
    auto slab = [&](int c, int i0) {
#pragma unroll
      for (int i = i0; i < 6; i++)
        stg2_if(c == i, pend + i * 512, q[8 * i], q[8 * i + 1], q[8 * i + 2], q[8 * i + 3],
                q[8 * i + 4], q[8 * i + 5], q[8 * i + 6], q[8 * i + 7], spol);
    };
    auto drain = [&](int c) {
      if (!pend_any || c >= 6) return;
      slab(c, 0);
      if (c == 5) {
        __syncwarp();
        mbar_arrive_if(lane == 0, odone0 - 8 + 8 * pc);
      }
    };

    for (;; pc++) {
      uint32_t op = prog[pc];
      const int type = op & 3;
      auto enter = [&]() {
        r.n = (op >> 12) & 248; cur = ring16 + (((op >> 20) & 63) << 8);
      };
      enter();
      pend_any = op & C_PEND;
      uint32_t job = 0;
      if ((op & (3 | C_WIDE)) == OP_O) job = __shfl_sync(0xffffffffu, wait_word(jobw, 1), 0);
      if (type == OP_END || job == OP_O) {
#pragma unroll 1
        for (int c = 0; c < 6; c++) drain(c);
        asm volatile("barrier.cluster.arrive.relaxed;" ::: "memory");
        break;
      }
      {
        float s[32], o[96];
        uint32_t ad0;
        int bi0, sk1;
        uint32_t pa[16], pb[16];
        float mc0, mc1, l0, l1;
        bool shifted;
        uint32_t nop;
        auto expo = [&](float (&s)[32], uint32_t (&pout)[16], float& b0, float& b1, bool shift, auto mid) {
          float c0, c1;
#pragma unroll
          for (int i = 0; i < 8; i++) {
            const float e0 = ex2(shift ? s[4 * i] - mc0 : s[4 * i]), e1 = ex2(shift ? s[4 * i + 1] - mc0 : s[4 * i + 1]);
            const float e2 = ex2(shift ? s[4 * i + 2] - mc1 : s[4 * i + 2]), e3 = ex2(shift ? s[4 * i + 3] - mc1 : s[4 * i + 3]);
            if (i) { b0 += e0; c0 += e1; b1 += e2; c1 += e3; } else { b0 = e0; c0 = e1; b1 = e2; c1 = e3; }
            pout[2 * i] = pack_bf16(e0, e1); pout[2 * i + 1] = pack_bf16(e2, e3);
            if (i & 1) mid(i >> 1);
          }
          b0 += c0; b1 += c1;
        };
        auto rowmax = [&](float (&s)[32], float& m0, float& m1) {
          m0 = fmaxf(s[0], s[1]); m1 = fmaxf(s[2], s[3]);
#pragma unroll
          for (int i = 1; i < 8; i++) { m0 = fmaxf(m0, fmaxf(s[4 * i], s[4 * i + 1])); m1 = fmaxf(m1, fmaxf(s[4 * i + 2], s[4 * i + 3])); }
          m0 = fmaxf(m0, __shfl_xor_sync(0xffffffffu, m0, 1)); m1 = fmaxf(m1, __shfl_xor_sync(0xffffffffu, m1, 1));
          m0 = fmaxf(m0, __shfl_xor_sync(0xffffffffu, m0, 2)); m1 = fmaxf(m1, __shfl_xor_sync(0xffffffffu, m1, 2));
        };
        auto first = [&](float (&s)[32], int sk0, auto mid) {
          fence_regs(s);
          release(sk0);
          mc0 = 0.f; mc1 = 0.f;
          expo(s, pa, l0, l1, false, mid);
          shifted = __any_sync(0xffffffffu, !(fmaxf(l0, l1) <= kSumLimit && fminf(l0, l1) >= 1.f / kSumLimit));
          if (shifted) {
            rowmax(s, mc0, mc1);
            expo(s, pa, l0, l1, true, [](int) {});
          }
        };
        auto qk = [&](float (&s)[32], uint32_t ak, int k0 = 0, int k1 = 12) {
#pragma unroll
          for (int kk = k0; kk < k1; kk++)
            wgmma_rs_n64<0>(s, q[4 * kk], q[4 * kk + 1], q[4 * kk + 2], q[4 * kk + 3], mk_desc(ak, 16, KV_SBO, 1) + ((kk >> 2) * KV_CH + (kk & 3) * 2), kk != 0);
          if (k1 == 12) wg_commit();
        };
        auto pv = [&](uint32_t (&pin)[16], uint32_t av, int acc, int k0 = 0, int k1 = 4) {
#pragma unroll
          for (int kk = k0; kk < k1; kk++)
            wgmma_rs_n192<1>(o, pin[4 * kk], pin[4 * kk + 1], pin[4 * kk + 2], pin[4 * kk + 3], mk_desc(av, KV_CH * 16, KV_SBO, 1) + (kk * (KV_SBO / 8)), acc || (kk != 0));
          if (k0 == 0) wg_commit();
        };
        auto finish = [&](uint32_t (&pout)[16], int sk, int sv, bool part = false) {
          probe1();
          wg_wait<1>();
          fence_regs(s);
          release(sk);
          float b0, b1;
#pragma unroll 1
          for (bool redo = false;; redo = true) {
            expo(s, pout, b0, b1, false, [](int) {});
            if (!__any_sync(0xffffffffu, !redo && (shifted || !(fmaxf(b0, b1) <= kSumLimit)))) break;
            shifted = true;
            rowmax(s, b0, b1);
            b0 = fmaxf(mc0, b0); b1 = fmaxf(mc1, b1);
            const float a0 = ex2(mc0 - b0), a1 = ex2(mc1 - b1);
            mc0 = b0; mc1 = b1;
            l0 *= a0; l1 *= a1;
            wg_wait<0>();
            fence_regs(o);
#pragma unroll
            for (int i = 0; i < 24; i++) { o[4 * i] *= a0; o[4 * i + 1] *= a0; o[4 * i + 2] *= a1; o[4 * i + 3] *= a1; }
#pragma unroll
            for (int i = 0; i < 32; i++) s[i] -= (i & 2) ? mc1 : mc0;
            if (part) {
#pragma unroll
              for (int i = 8; i < 16; i++)
                pa[i] = pack_bf16(__uint_as_float(pa[i] << 16) * ((i & 1) ? a1 : a0), __uint_as_float(pa[i] & 0xffff0000u) * ((i & 1) ? a1 : a0));
            }
          }
          l0 += b0; l1 += b1;
          wg_wait<0>();
          fence_regs(o);
          mbar_arrive_cluster_n(part ? 0 : keep, empty_rem + sv);
        };
        uint32_t pav;
        int psv;
        auto step = [&](uint32_t (&pin)[16], uint32_t (&pout)[16], bool part) {
          uint32_t ak;
          const int sk = take(rdy0, SZ_KV, ak);
          psv = advance(SZ_KV, pav);
          wg_fence();
          qk(s, ak);
          if (part) { wg_fence(); pv(pin, pav, 1, 0, 2); } else { asm volatile(""); wg_fence(); pv(pin, pav, 1); }
          finish(pout, sk, psv, part);
        };
        auto unpark = [&](uint32_t& ak) {
          uint32_t ad;
          const Cursor k0 = r;
          const int sk0 = advance(SZ_KV, ak), bi = take(false, SZ_PARK, ad);
#pragma unroll
          for (int i = 0; i < 12; i++) lds128(sbase + (ad - ring16 + img0) * 16 + (i >> 1) * 8192 + (i & 1) * 512, q[4 * i], q[4 * i + 1], q[4 * i + 2], q[4 * i + 3]);
          if (!__all_sync(0xffffffffu, rdy0)) mbar_wait(full0 + k0.off(), k0.ph());
          fence_regs(q);
          release_warp(bi);
          wg_fence();
          qk(s, ak, 0, 4);
          wg_commit();
          return sk0;
        };
        auto mma4 = [&](uint32_t ad, int acc) {
#pragma unroll
          for (int kk = 0; kk < 4; kk++)
            wgmma_ss_n192<1>(o, mk_desc(ad + wg * 512, 16, 1024, 1) + (kk * 2), mk_desc(ad, 4096, 1024, 1) + (1024 + (kk >> 1) * 768 + (kk & 1) * 128), acc || kk != 0);
        };
        auto convert = [&](int i0, int i1) {
          sched_fence(keep, never);
#pragma unroll
          for (int i = i0; i < i1; i++) {
            q[i] = pack_bf16(o[2 * i] * kScaleLog2, o[2 * i + 1] * kScaleLog2);
            if ((i & 7) == 7 && i != i1 - 1) sched_fence(keep, never);
          }
          sched_fence(keep, never);
        };
        if (type == OP_O) {
          int prev = 0;
          if (op & C_WIDE) {
            float d[64];
            auto mma3 = [&](uint32_t ad, int h, int acc) {
#pragma unroll
              for (int kk = 0; kk < 2; kk++)
                wgmma_ss_n192<1>(o, mk_desc(ad + wg * 256, 16, 512, 2) + (h * 512 + kk * 2), mk_desc(ad, 4096, 1024, 1) + (1024 + h * 768 + kk * 128), acc || kk);
            };
            auto mma2 = [&](uint32_t ad, uint32_t ob, int h, int acc) {
#pragma unroll
              for (int kk = 0; kk < 2; kk++)
                wgmma_ss_n128<1>(d, mk_desc(ad + wg * 256, 16, 512, 2) + (h * 512 + kk * 2), mk_desc(ad, 4096, 1024, 1) + (ob + h * 512 + kk * 128), acc || kk);
            };
            auto wstep = [&](uint32_t bytes, int acc, auto hook) {
              uint32_t ad;
              const int bi = take(rdy0, bytes, ad);
              wg_fence();
              if (bytes == SZ_W2) mma2(ad, 1024, 0, 1); else mma3(ad, 0, acc);
              if (bytes == SZ_W) mma3(ad, 1, 1);
              wg_commit();
              if (acc) { wg_wait<1>(); release(prev); }
              if (bytes == SZ_W) mma2(ad, 2560, 0, acc);
              if (bytes == SZ_W3) mma3(ad, 1, 1); else mma2(ad, bytes == SZ_W ? 2560 : 1024, 1, 1);
              wg_commit();
              prev = bi;
              hook();
              probe1();
              wg_wait<1>();
            };
            undefine(o);
            wstep(SZ_W, 0, [&]() { drain(0); });
#pragma unroll 1
            for (int k = 1; k < ((op >> 2) & 127) - TAIL; k++) wstep(SZ_W, 1, [&]() { drain(k); });
#pragma unroll 1
            for (int k = 0; k < TAIL; k++) wstep(SZ_W2, 1, []() {});
            pend = ptr_add(P.g->part, (((op >> 9) & 31) * 2 + rank) * 81920 + 4 * 8192 + img0 * 16);
            wstep(SZ_W3, 1, [&]() {
              fence_regs(d);
#pragma unroll
              for (int i = 0; i < 32; i++) q[16 + i] = pack_bf16(d[2 * i], d[2 * i + 1]);
              slab(2, 2);
            });
#pragma unroll 1
            for (int k = 3; k < 6; k++) wstep(SZ_W3, 1, [&]() { slab(k, 2); });
            op = prog[pc + 1];
            enter();
            pend_any = true;
            pend -= 4 * 512;
            bi0 = take(rdy0 || (op & 3) != OP_Q, SZ_Q, ad0);
            sched_fence(keep, never);
            wg_wait<0>();
            fence_regs(o);
            release(prev);
#pragma unroll
            for (int i = 0; i < 48; i++) q[i] = pack_bf16(o[2 * i], o[2 * i + 1]);
            if ((op & 3) != OP_Q) continue;
            pc++;
            goto first_step;
          }
          float c[80];
          auto mma2 = [&](uint32_t ad, uint32_t oa, uint32_t ob, int acc) {
            wgmma_ss_n160<1>(c, mk_desc(ad + wg * 256, 16, 512, 2) + (oa), mk_desc(ad, 2048, 512, 2) + (1024 + ob), acc);
            wgmma_ss_n160<1>(c, mk_desc(ad + wg * 256, 16, 512, 2) + (oa + 2), mk_desc(ad, 2048, 512, 2) + (1024 + ob + 64), 1);
          };
          auto kstep = [&](int acc, auto hook, uint32_t bytes = SZ_O) {
            uint32_t ad;
            const int bi = take(rdy0, bytes, ad);
            wg_fence();
            mma2(ad, 0, 0, acc);
            wg_commit();
            if (acc) wg_wait<1>();
            if (acc == 1) release(prev);
            if (acc > 1) release_warp(prev, acc == 2 || wg == 0);
            mma2(ad, 512, 640, 1);
            wg_commit();
            prev = bi;
            hook();
            probe1();
            wg_wait<1>();
          };
          auto unblock = [&](int k) {
            if (__all_sync(0xffffffffu, rdy0) || __all_sync(0xffffffffu, mbar_try(full0 + r.off(), r.ph(), 1500))) return;
#pragma unroll 1
            for (; k < 6; k++) drain(k);
            pend_any = false;
          };
          unblock(0);
          kstep(0, [&]() { drain(0); });
          int left = ((job >> 13) & 127) - 6;
#pragma unroll 1
          for (uint32_t k = 1, pace = left >= 22 ? 0x4511 : left <= 11 ? 0x1a : 0x155; left > 0; pace >>= 2, left--) {
            unblock(k);
            kstep(1, [&]() {
#pragma unroll 1
              for (int i = pace & 3; i > 0; i--) drain(k++);
            });
          }
          uint32_t t[8], stage[3];
          float u[80];
          auto unpack = [&](int j) {
#pragma unroll
            for (int i = 0; i < 8; i++) {
              u[16 * j + 2 * i] = __uint_as_float(t[i] << 16); u[16 * j + 2 * i + 1] = __uint_as_float(t[i] & 0xffff0000u);
              asm volatile("" : "+f"(u[16 * j + 2 * i]), "+f"(u[16 * j + 2 * i + 1]));
            }
          };
#pragma unroll
          for (int i = 0; i < 8; i++) t[i] = 0;
          const uint32_t bytes = (job & P_LD) ? SZ_OL : SZ_O;
#pragma unroll
          for (int j = 0; j < 5; j++) {
            if (j == 2 && wg == 1) {
              wg_wait<0>();
              release_warp(prev);
              bar_sync(1, 256);
            }
            kstep(j == 2 ? 3 : 2, [&]() {
              if (j == 4) asm volatile("{\n.reg .pred p;\nsetp.eq.u32 p, %0, 0;\n@p bar.arrive 1, 256;\n}\n" ::"r"(wg) : "memory");
              if (j) unpack(j - 1);
              lds2_if(job & P_LD, sbase + (cur - ring16 + img0) * 16 - 8192, t);
              if (j >= 1 && j <= 3) stage[j - 1] = sbase + (cur - ring16) * 16 - bytes + wid * 1024;
            }, bytes);
          }
          unpack(4);
          sched_fence(keep, never);
          wg_wait<0>();
          fence_regs(c);
          release_warp(prev);
          asm volatile("barrier.cluster.arrive.relaxed;" ::: "memory");
#pragma unroll
          for (int i = 0; i < 10; i++) {
            const int v = (i & 1) * 2 + (lane >> 4);
            const uint32_t sa = stage[i >> 2] + (i & 2) * 4096;
            stsm4(sa + (lane & 15) * 64 + ((v ^ ((lane >> 1) & 3)) << 4), pack_bf16(c[8 * i] + u[8 * i], c[8 * i + 1] + u[8 * i + 1]),
                  pack_bf16(c[8 * i + 2] + u[8 * i + 2], c[8 * i + 3] + u[8 * i + 3]), pack_bf16(c[8 * i + 4] + u[8 * i + 4], c[8 * i + 5] + u[8 * i + 5]),
                  pack_bf16(c[8 * i + 6] + u[8 * i + 6], c[8 * i + 7] + u[8 * i + 7]));
          }
          asm volatile("fence.proxy.async.shared::cta;" ::: "memory");
          __syncwarp();
          if (elect()) {
#pragma unroll
            for (int i = 0; i < 5; i++)
              tma3d_store(&P.out, stage[i >> 1] + (i & 1) * 8192, 0, ((job >> 7) & 7) * kSq + rank * 128 + wid * 16, ((job >> 10) & 1) * 20 + ((job >> 20) & 3) * 5 + i);
            asm volatile("cp.async.bulk.commit_group;\ncp.async.bulk.wait_group.read 0;" ::: "memory");
          }
          __syncwarp();
          break;
        }
        bi0 = take(rdy0, SZ_Q, ad0);
      first_step:
        undefine(o);
        wg_fence();
        mma4(ad0, 0);
        wg_commit();
        {
          uint32_t ad1;
          const int bi1 = take(false, SZ_Q, ad1);
          wg_fence();
          mma4(ad1, 1);
          wg_commit();
          drain(0);
          wg_wait<1>();
          release(bi0);
          drain(1);
          probe1();
          wg_wait<0>();
          release(bi1);
          fence_regs(o);
#pragma unroll 1
          for (int k = 2; k < 8; k++) {
            uint32_t ad;
            const int bi = take(rdy0, SZ_Q, ad);
            wg_fence();
            mma4(ad, 1);
            wg_commit();
            drain((0x54732710u >> (4 * k)) & 7);
            probe1();
            wg_wait<0>();
            release(bi);
          }
          uint32_t a8, a9, ak0, ak1;
          const int b8 = take(rdy0, SZ_Q, a8), b9 = take(false, SZ_Q, a9);
          wg_fence();
          mma4(a8, 1);
          wg_commit();
          mma4(a9, 1);
          wg_commit();
          wg_wait<1>();
          release(b8);
          probe1();
          const int sk0 = take(rdy0 || (op & F_PARK), SZ_KV, ak0);
          wg_wait<0>();
          fence_regs(o);
          release(b9);
          float s0[32];
          convert(0, 32);
          if (op & F_PARK) {
            convert(32, 48);
            pend = ptr_add(P.g->tile, (((op >> 2) & 511) * 2 + rank) * SZ_PARK + img0 * 16);
            continue;
          }
          pc++;
          wg_fence();
          qk(s0, ak0, 0, 4);
          convert(32, 48);
          wg_fence();
          qk(s0, ak0, 4, 12);
          sk1 = take(false, SZ_KV, ak1);
          wg_fence();
          qk(s, ak1, 0, 4);
          wg_commit();
          probe1();
          wg_wait<1>();
          first(s0, sk0, [&](int i) {
            if (!(i & 1)) return;
            sched_fence(keep, never);
            wg_fence();
            if (i == 1) qk(s, ak1, 4, 8);
            if (i == 3) qk(s, ak1, 8, 12);
            sched_fence(keep, never);
          });
        }
        for (;;) {
          {
            uint32_t av;
            const int sv = take(rdy0, SZ_KV, av);
            undefine(o);
            wg_fence();
            pv(pa, av, 0);
            finish(pb, sk1, sv);
          }
          nop = prog[pc + 1];
#pragma unroll 1
          for (int jj = 0; jj < 7; jj++) {
            step(pb, pa, false);
            step(pa, pb, jj == 6);
          }
          float i0, i1;
          auto last = [&]() {
            uint32_t av;
            const int sv = take(rdy0, SZ_KV, av);
            wg_fence();
            pv(pa, pav, 1, 2, 4);
            pv(pb, av, 1);
            sched_fence(keep, never);
            probe1();
            l0 += __shfl_xor_sync(0xffffffffu, l0, 1); l1 += __shfl_xor_sync(0xffffffffu, l1, 1);
            l0 += __shfl_xor_sync(0xffffffffu, l0, 2); l1 += __shfl_xor_sync(0xffffffffu, l1, 2);
            i0 = rcp(l0); i1 = rcp(l1);
            pend = ptr_add(P.g->tile, (((op >> 2) & 511) * 2 + rank) * SZ_PARK + img0 * 16);
            return sv;
          };
          auto normalise = [&](uint32_t (&d)[48], auto mid) {
#pragma unroll
            for (int i = 0; i < 24; i++) {
              d[8 * (i >> 2) + (i & 3)] = pack_bf16(o[4 * i] * i0, o[4 * i + 1] * i0);
              d[8 * (i >> 2) + (i & 3) + 4] = pack_bf16(o[4 * i + 2] * i1, o[4 * i + 3] * i1);
              if ((i & 1) && i != 23) sched_fence(keep, never);
              if ((i & 3) == 3 && i != 23) mid(i >> 2);
            }
          };
          const int sv = last();
          if ((nop & 3) != OP_A) {
            op = nop;
            enter();
            pend_any = true;
            bi0 = take(rdy0 || (nop & 3) != OP_Q, SZ_Q, ad0);
            sched_fence(keep, never);
            wg_wait<0>();
            fence_regs(o);
            release(psv);
            release(sv);
            normalise(q, [](int) {});
            undefine(o);
            if ((nop & 3) != OP_Q) break;
            pc++;
            goto first_step;
          }
          uint32_t ak0;
          const int sk0 = unpark(ak0);
          wg_wait<1>();
          fence_regs(o);
          release(psv);
          release(sv);
          uint32_t t[48];
          auto st = [&](int i) {
            stg2_if(true, pend + i * 512, t[8 * i], t[8 * i + 1], t[8 * i + 2], t[8 * i + 3], t[8 * i + 4], t[8 * i + 5], t[8 * i + 6], t[8 * i + 7], spol);
          };
          normalise(t, [&](int i) {
            if (i & 1) {
              wg_fence();
              if (i == 1) qk(s, ak0, 4, 8);
              if (i == 3) qk(s, ak0, 8, 12);
              sched_fence(keep, never);
            }
            if (!(i & 1)) st(i >> 1);
          });
          probe2();
          wg_wait<0>();
          first(s, sk0, [&](int i) { if (i < 3) { sched_fence(keep, never); st(3 + i); } });
          __syncwarp();
          mbar_arrive_if(lane == 0, odone0 + 8 * pc);
          pc++;
          op = nop;
          uint32_t ak1;
          sk1 = take(rdy0, SZ_KV, ak1);
          rdy0 = rdy1;
          wg_fence();
          qk(s, ak1);
        }
      }
    }
    asm volatile("barrier.cluster.wait;" ::: "memory");
  } else {
    asm volatile("setmaxnreg.dec.sync.aligned.u32 24;");
    const uint32_t* prog = P.prog[role].p;
    unsigned int* flag = P.g->flag + rank;
    if (wid == 11 && (prog[0] & 3) == OP_Q) {
      const uint32_t a = prog[1];
      const char* p = ptr_add(P.kv[rank * 2 + ((a >> 10) & 1)], ((a >> 2) & 255) * (kSk * kDh * 2) + (threadIdx.x & 31) * 128);
#pragma unroll 1
      for (uint32_t k = 0; k < 3; k++) {
        wait_word(progress, 8 * k);
        p += SZ_KV;
        asm volatile("prefetch.global.L2 [%0];\nprefetch.global.L2 [%0 + 4096];" ::"l"(p));
      }
      __syncwarp();
    }
    if (wid == 8) {
      Cursor head{0}, tail{0};
      int sh = 0, room = RING >> 12;
      uint32_t cur = 0;
      uint64_t fifo = 0;
      uint32_t dst, bar = 0, ev = ev0;
      const uint64_t pol = evict_first();
      auto retire = [&]() {
        mbar_wait(empty0 + tail.off(), tail.ph());
        tail.next();
        room += (uint32_t)fifo & 31;
        fifo >>= 5;
        sh -= 5;
        asm volatile("st.volatile.shared.u32 [%0], %1;" ::"r"(progress), "r"(tail.n) : "memory");
      };
      auto acquire = [&](uint32_t bytes) {
        uint32_t fp = bytes >> 12;
        if (cur + fp > (RING >> 12)) { fp += (RING >> 12) - cur; cur = 0; }
        room -= fp;
        while (room < 0) retire();
        fifo |= (uint64_t)fp << sh;
        sh += 5;
        dst = sbase + (cur << 12);
        bar = full0 + head.off();
        cur += bytes >> 12;
        head.next();
      };
      auto gate = [&]() {
        mbar_wait(ev, 0);
        ev += 8;
        asm volatile("fence.proxy.async.global;" ::: "memory");
      };
      for (int pc = 0;; pc++) {
        uint32_t op = prog[pc];
        const int type = op & 3;
        if (type == OP_END) break;
        if (op == OP_O) {
          gate();
          op = __shfl_sync(0xffffffffu, lds32(jobw), 0);
        }
        const int blk = (op >> 10) & 1;
        if (type == OP_Q) {
          const uint64_t px = (op & P_LASTX) ? pol : no_hint(), pw = (op & P_LASTW) ? pol : no_hint();
          int k = 0;
          if (pc == 0) {
            k = 64 * EARLY; head.n = 8 * EARLY; sh = 5 * EARLY; cur = EARLY * (SZ_Q >> 12); room -= cur;
            fifo = (SZ_Q >> 12) * (((1u << (5 * EARLY)) - 1) / 31);
          }
#pragma unroll 1
          for (int stop = (op & P_GATE) ? kD - 64 : kD;; stop = kD) {
#pragma unroll 1
            for (; k < stop; k += 64) {
              acquire(SZ_Q);
              if (elect()) {
                mbar_expect(bar, SZ_Q);
                tma3d_mc_hint(dst + 16384 + rank * 12288, &P.wq[blk], bar, k + 32 * rank, 3 * ((op >> 2) & 31), pw);
                tma2d_hint(dst, &P.x[blk], bar, k, ((op >> 7) & 7) * kSq + rank * 128, px);
              }
            }
            if (k == kD) break;
            gate();
          }
        } else if (type == OP_A) {
          const int row0 = ((op >> 2) & 255) * kSk;
          auto kv = [&](uint32_t tx, const CUtensorMap* m, int c3) {
            const uint32_t before = bar;
            acquire(SZ_KV);
            if (elect()) {
              mbar_expect(bar, tx);
              tma4d_mc_hint(dst + rank * (SZ_KV / 2), m, tx ? bar : before, c3, pol);
            }
          };
          int c3 = row0 / 8 + 4 * rank;
#pragma unroll 1
          for (int j = 0; j <= 16; j++, c3 += 8) {
            const uint32_t tv = j < 2 || j == 16 ? SZ_KV : 0;
            if (j < 16) kv(2 * SZ_KV - tv, &P.k[blk], c3);
            else if (op & P_GATE) gate();
            if (j > 0) kv(tv, &P.v[blk], c3 - 8);
            else if (op & F_PARK) {
              gate();
              acquire(SZ_PARK);
              if (elect()) {
                mbar_expect(bar, SZ_PARK);
                bulk_load_hint(dst, &P.g->tile[(((op >> 20) & 511) * 2 + rank) * 3072], SZ_PARK, bar, pol);
              }
            }
          }
        } else {
          const uint4* part = &P.g->part[((((op >> 6) & 30) + ((op >> 21) & 1)) * 2 + rank) * 5120 + ((op >> 20) & 1) * 2560];
          auto run = [&](const uint32_t bytes, int k, int cnt, int gates) {
            const int col = bytes == SZ_O || bytes == SZ_OL ? 5 * ((op >> 20) & 3) : 5 * ((op >> 21) & 1);
            int row = 8 * k + 4 * rank, pre = bytes == SZ_O && (op & P_PRE) ? 0 : 2560;
#pragma unroll 1
            for (int h = (k * 43) >> 7, k0 = k - 3 * h; cnt > 0; h++, k0 = 0, gates = gates >> 1 | (gates & 2)) {
              const uint4* src = ptr_add(P.g->tile, ((P.slot[((op >> 2) & 480) + h] * 2 + rank) * 3 + k0) * 16384);
              const uint64_t pw = h >= ((op >> 23) & 31) && h < 2 * (op >> 28) ? pol : no_hint();
              if (gates & 1) gate();
              int m = min(3 - k0, cnt);
              cnt -= m;
#pragma unroll 1
              for (; m > 0; m--, src += 1024, row += 8) {
                acquire(bytes);
                if (elect()) {
                  mbar_expect(bar, bytes);
                  if (bytes == SZ_O || bytes == SZ_OL) tma5d_mc_hint(dst + 16384 + rank * 10240, &P.wo[blk], bar, row, col, no_hint());
                  if (bytes == SZ_W || bytes == SZ_W3) tma5d_mc_hint(dst + 16384 + rank * 12288, &P.wo3[blk], bar, row, col, pw);
                  bulk_load_hint(dst, src, 16384, bar, pol);
                  if (bytes == SZ_W || bytes == SZ_W2) tma5d_mc_hint(dst + bytes - 16384 + rank * 8192, &P.wo2[blk], bar, row, col + 3, pw);
                  if (bytes == SZ_OL) bulk_load_hint(dst + SZ_O, part, 8192, bar, pol);
                }
                if (bytes == SZ_OL) part += 512;
              }
              if (pre < 2560) {
                if (elect()) asm volatile("cp.async.bulk.prefetch.L2.global [%0], 10240;" ::"l"(part + pre) : "memory");
                pre += 640;
              }
            }
          };
          const int n = (op >> 13) & 127;
          if (op & P_WIDE) {
            run(SZ_W, 0, n - TAIL, 3);
            run(SZ_W2, n - TAIL, TAIL, (n - TAIL) % 3 ? 2 : 3);
            run(SZ_W3, n - TAIL, TAIL, 0);
          } else {
            if (op & P_PRE) gate();
            run(SZ_O, kSteps - n, (op & P_LD) ? n - 5 : n, 3);
            if (op & P_LD) {
              if (!(op & P_PRE)) gate();
              run(SZ_OL, kSteps - 5, 5, 2);
            }
          }
        }
      }
#pragma unroll 1
      while (sh) retire();
    } else if (threadIdx.x == 288) {
      for (int pc = 0;; pc++) {
        const uint32_t op = prog[pc];
        const int type = op & 3;
        if (type == OP_END) break;
        if (type == OP_Q ? !(op & F_PARK) : type == OP_O && !(op & P_WIDE)) continue;
        const int id = type == OP_A ? (op >> 2) & 511 : type == OP_Q ? N_TILE + ((op >> 13) & 127) : ID_PART + ((op >> 5) & 60) + ((op >> 20) & 3);
        const uint32_t v = type == OP_O ? 1 : P.info[id] & 7;
        mbar_wait_long(odone0 + 8 * pc);
        flag_set(flag + 2 * id, v);
        if (type == OP_O && (op & P_WIDE)) flag_set(flag + 2 * id + 2, v);
      }
    } else if (wid == 10) {
      int i = threadIdx.x & 31;
      const int n_ev = P.prog[role].n_ev;
      auto event = [&]() { return i < n_ev ? P.prog[role].ev[i] : n_ev ? E_JOB | (i - n_ev) : 0; };
      uint32_t e = i < 8 ? event() : 0;
      for (uint32_t n = 0; __any_sync(0xffffffffu, e); n++) {
        uint32_t job = lds32(jobw);
        const int togo = (e & E_DRAW) ? (e & 1023) - (lds32(progress) >> 3) : 99;
        if (togo <= 0 && rank == 0) {
          job = P.job[atomicInc(&P.g->ticket, gridDim.x / 2 - 1)];
          asm volatile("{\n.reg .u32 a;\nmapa.shared::cluster.u32 a, %0, 1;\nst.volatile.shared::cluster.u32 [a], %1;\n"
                       "st.volatile.shared.u32 [%0], %1;\n}\n" ::"r"(jobw), "r"(job) : "memory");
        }
        if ((e & E_JOB) && job) {
          const uint32_t j = e & 63, heads = job == OP_O ? 0 : kH - ((job >> 2) & 31), jp = !(job & P_LD) ? 63 : (job & P_PRE) ? 0 : heads - 1, h = j - (j > jp);
          e = j == jp ? (ID_PART + ((job >> 5) & 60) + ((job >> 20) & 3)) | E_ON | E_LAST : h < heads ? (((job >> 2) & 511) + h) | E_ON | E_LAST : 0;
        }
        unsigned int* f = ptr_add(flag, 8 * (e & 1023));
        const bool ok = (e & E_ON) ? flag_get(f) - 1 < ((e & E_FREE) ? 1 : 7) : (e & E_DRAW) && job;
        if (ok) {
          mbar_arrive(ev0 + 8 * i);
          if (e & (E_FREE | E_LAST)) flag_dec(f);
          i += 8;
          e = event();
        }
        asm volatile("{\n.reg .pred p;\nsetp.ge.u32 p, %0, 0x400000;\n@p trap;\n}\n" ::"r"(n));
        if (!__any_sync(0xffffffffu, ok)) __nanosleep(__any_sync(0xffffffffu, job || togo <= 2) ? 100 : 600);
      }
    } else if (threadIdx.x == 352) {
      uint32_t items = 0;
      auto read = [&](int id) {
        if (!(P.info[id] & I_NEXT)) return;
        wait_word(progress, 8 * items);
        flag_dec(flag + 2 * id);
      };
      for (int pc = 0;; pc++) {
        const uint32_t op = prog[pc];
        const int type = op & 3;
        if (type == OP_END) break;
        if (type == OP_O) {
          const uint32_t n = (op >> 13) & 127, base = items;
#pragma unroll 1
          for (uint32_t k = 3, id = (op >> 2) & 511; k <= n; k += 3, id++) {
            items = base + k + (k + TAIL > n ? TAIL : 0);
            read(id);
          }
          items = base + n + TAIL;
        } else if (type == OP_A) {
          items++;
          if (op & F_PARK) { items++; read(N_TILE + ((op >> 13) & 127)); }
          items += 31;
        } else {
          items += 10;
        }
      }
    }
    __syncwarp();
    asm volatile("barrier.cluster.arrive.relaxed;\nbarrier.cluster.wait;" ::: "memory");
  }
}

typedef CUresult (*EncodeFn)(CUtensorMap*, CUtensorMapDataType, cuuint32_t, void*, const cuuint64_t*, const cuuint64_t*,
                             const cuuint32_t*, const cuuint32_t*, CUtensorMapInterleave, CUtensorMapSwizzle,
                             CUtensorMapL2promotion, CUtensorMapFloatOOBfill);

void encode(EncodeFn fn, CUtensorMap* m, const void* ptr, int rank, const cuuint64_t* dims, const cuuint64_t* strides,
            const cuuint32_t* box, CUtensorMapSwizzle swz) {
  const cuuint32_t es[5] = {1, 1, 1, 1, 1};
  CUresult r = fn(m, CU_TENSOR_MAP_DATA_TYPE_BFLOAT16, rank, const_cast<void*>(ptr), dims, strides, box, es,
                  CU_TENSOR_MAP_INTERLEAVE_NONE, swz, CU_TENSOR_MAP_L2_PROMOTION_L2_128B, CU_TENSOR_MAP_FLOAT_OOB_FILL_NONE);
  if (r != CUDA_SUCCESS) fprintf(stderr, "cuTensorMapEncodeTiled failed: %d\n", (int)r);
}

struct Op { int type, flags, id, n, quarter, park, item0, items; double t0, t1; };
struct Use { double need, freed; int readers, slot, prev; bool next; };
struct PlanStats { double end, slack, park_slack; int slots, parks; uint32_t own[N_CL]; };

bool plan(const char* const* text, int n_pair, int phase, Params& P, PlanStats* stats = nullptr) {
  constexpr double T_Q = 7900, T_A = 24550, T_U = 25900, T_P = 8400, T_O = 640, T_RUN = 800, T_WIDE = 1300, AHEAD = 3500, PUBLISH = 1500;
  const double margin = 256.0 * ((P.dbg >> 8) & 255);
  static Op op[N_CL][MAX_OPS];
  static Use use[ID_PART];
  int n_op[N_CL], covered[2 * N_TEAM] = {};
  struct Ref { double t; Op* o; int id; };
  static Ref att[N_TILE + 1], dem[N_TILE], prk[MAX_PARK + 1], unp[MAX_PARK + 1], wr[ID_PART];
  auto sort = [](Ref* r, int n) {
    for (int i = 1; i < n; i++)
      for (int j = i; j > 0 && r[j].t < r[j - 1].t; j--) { Ref x = r[j]; r[j] = r[j - 1]; r[j - 1] = x; }
  };
  auto hex = [](char c) { return c <= '9' ? c - '0' : c - 'a' + 10; };
  for (int i = 0; i < n_pair; i++)
    for (const char* s = text[i]; *s; s++)
      for (int h = 0; *s == 'J' && h < 2; h++) {
        if (covered[2 * hex(s[1]) + h]) return false;
        covered[2 * hex(s[1]) + h] = 10 * (s[2 + 2 * h] - '0') + s[3 + 2 * h] - '0';
      }
  for (int c = 0; c < 2 * n_pair; c++) {
    int n = 0, items = 0;
    double t = 0;
    auto add = [&](int type, int flags, int id, int heads, int quarter, int its, double dt) {
      if (n < MAX_OPS) op[c][n] = {type, flags, id, heads, quarter, 0, items, its, t, t + dt};
      n++; items += its; t += dt;
    };
    for (const char* s = text[c >> 1]; *s; s++) {
      const int tm = hex(s[1]) & 15, nj = covered[2 * tm + (c & 1)];
      if (*s == 'N') { add(OP_Q, 0, 0, 0, 0, 10, T_Q); add(OP_A, 0, 0, 0, 0, 32, T_A); }
      if (*s == 'P') add(OP_Q, F_PARK, 0, 0, 0, 10, T_P);
      if (*s == '+' || *s == '-') t += *s == '+' ? 1000 : -1000;
      if (*s == 'U') { if (n == 0 || n > MAX_OPS || op[c][n - 1].type != OP_A) return false; add(OP_A, F_PARK, 0, 0, 0, 33, T_U); }
      if (*s == 'J') { if (nj < TAIL + 6 || nj > kSteps - 11) return false; add(OP_O, P_WIDE, tm * kH, nj, 2 * (c & 1), nj + TAIL, 2 * T_O * nj + T_WIDE); }
    }
    add(OP_O, 0, 0, 0, 0, 0, 0);
    add(OP_END, 0, 0, 0, 0, 0, 0);
    if (n > MAX_OPS || op[c][0].type != OP_Q) return false;
    n_op[c] = n - 1;
    att[c] = {t, &op[c][n - 2], 0};
  }
  for (int i = 0; i < 4 * N_TEAM; i++) dem[i] = {(double)covered[i / 2], nullptr, i};
  sort(att, 2 * n_pair); sort(dem, 4 * N_TEAM);
  for (int i = 0; i < 4 * N_TEAM; i++) {
    Op* f = att[i].o;
    const int nj = covered[dem[i].id / 2];
    f->flags = nj ? P_LD : 0;
    f->id = dem[i].id / 4 * kH + nj / 3; f->quarter = dem[i].id & 3; f->items = f->n = kSteps - nj;
    f[1].t0 = f[1].t1 = f->t1 = f->t0 + T_O * f->n + T_RUN; f[1].item0 += f->n;
  }
  for (int i = 0; i < ID_PART; i++) use[i] = {1e18, 0, 0, 0, 0, false};
  int n_att = 0, n_prk = 0, n_unp = 0;
  auto ready = [&](const Op* o) {
    const int nt = o[1].type;
    return o->t1 + (nt == OP_Q ? 6100 : o[1].n ? ((o[1].flags & P_WIDE) ? 7700 : 3900) : 1500) + PUBLISH;
  };
  for (int c = 0; c < 2 * n_pair; c++)
    for (Op* o = op[c]; o->type != OP_END; o++) {
      if (o->type == OP_A) { att[n_att] = {ready(o), o, 0}; if (++n_att > N_TILE) return false; }
      if (o->type == OP_A && o->flags) { unp[n_unp] = {o->t0 - AHEAD, o, 0}; if (++n_unp > MAX_PARK) return false; }
      if (o->type == OP_Q && o->flags) { prk[n_prk] = {ready(o), o, 0}; if (++n_prk > MAX_PARK) return false; }
      for (int i = 0; o->type == OP_O && i < o->n; i++) {
        const int nw = (o->flags & P_WIDE) ? o->n - TAIL : 0, k = nw ? i : kSteps - o->n + i;
        Use& u = use[o->id / kH * kH + k / 3];
        const double t = o->t0 + T_O * (i + (i < nw ? i : nw));
        if (t - AHEAD < u.need) u.need = t - AHEAD;
        const double f = !nw ? 1e18 : i + FLIGHT < o->items - TAIL || (nw && o[1].type != OP_O) ? t + T_O * (i < nw ? 2 : 1 + TAIL) + PUBLISH : 1e18;
        if (f > u.freed) u.freed = f;
        if (i == 0 || k % 3 == 0) u.readers++;
      }
    }
  if (n_att != N_TILE || n_prk != n_unp) return false;
  for (int i = 0; i < N_TILE; i++) { const int id = (i & 15) * kH + (i >> 4); dem[i] = {use[id].need, nullptr, id}; }
  sort(att, n_att); sort(dem, N_TILE); sort(prk, n_prk); sort(unp, n_unp);
  PlanStats st = {0, 1e18, 1e18, 0, n_prk};
  int n_wr = 0;
  for (int i = 0; i < N_TILE; i++) {
    Op* o = att[i].o;
    o->id = dem[i].id;
    if (!o->flags) o[-1].id = o->id;
    if (dem[i].t - att[i].t < st.slack) st.slack = dem[i].t - att[i].t;
    wr[n_wr++] = {o->t1 - 2 * AHEAD, o, o->id};
  }
  for (int i = 0; i < n_prk; i++) {
    prk[i].o->id = unp[i].o->id;
    prk[i].o->park = unp[i].o->park = i;
    use[N_TILE + i].freed = unp[i].o->t0 + 2 * PUBLISH;
    use[N_TILE + i].readers = 1;
    if (unp[i].t - prk[i].t < st.park_slack) st.park_slack = unp[i].t - prk[i].t;
    wr[n_wr++] = {prk[i].o->t1 - 2 * AHEAD, prk[i].o, N_TILE + i};
  }
  for (int c = 0; c < 2 * n_pair; c++)
    for (int d = 0; d < 2 * n_pair; d++)
      for (Op *f = &op[c][n_op[c] - 1], *o = op[d]; f->n && o->type != OP_END; o++)
        if (o->type == OP_O && (o->flags & P_WIDE) && o->id / kH == f->id / kH && o->quarter / 2 == f->quarter / 2) {
          if (f->t0 - o->t1 > 4096.0 * ((P.dbg >> 16) & 255)) f->flags |= P_PRE;
          const double slack = f->t0 + ((f->flags & P_PRE) ? 0 : (f->n - 5) * T_O) - AHEAD - ready(o);
          if (slack < st.park_slack) st.park_slack = slack;
        }
  constexpr double long_while = 160000;
  for (int c = 0; c < 2 * n_pair; c++)
    for (Op* o = op[c]; o->type != OP_END; o++) {
      if (o->type == OP_O && (o->flags & P_WIDE)) {
        int run = 0, best = 0, end = 0;
        for (int h = 0; 3 * h < o->n; h++) {
          bool last = true;
          for (int d = 0; d < 2 * n_pair; d++)
            for (const Op* e = op[d]; e->type != OP_END; e++) {
              if (e->type != OP_O || e == o || ((e->id ^ o->id) & 256) || e->quarter / 2 != o->quarter / 2) continue;
              const bool wide = e->flags & P_WIDE;
              if (wide ? 3 * h >= e->n : 3 * h + 3 <= kSteps - e->n) continue;
              const double dt = e->t0 + T_O * (wide ? 6 * h : 3 * h - kSteps + e->n) - o->t0 - T_O * 6 * h + (d - c) * 1e-3;
              if (dt > 0 && dt < long_while) last = false;
            }
          run = last ? run + 1 : 0;
          if (run > best) { best = run; end = h + 1; }
        }
        const int from = end - best;
        if (3 * end >= o->n) end++;
        o->park = from | (end / 2) << 5;
      }
      if (o->type != OP_Q) continue;
      bool lw = true, lx = true;
      for (int d = 0; d < 2 * n_pair; d++)
        for (const Op* e = op[d]; e->type != OP_END; e++) {
          const double dt = e->t0 - o->t0 + (d - c) * 1e-3;
          if (e->type != OP_Q || e == o || dt < 0 || dt > long_while) continue;
          if (((e->id ^ o->id) & (256 + 31)) == 0) lw = false;
          if (e->id / kH == o->id / kH) lx = false;
        }
      o->quarter = (lw ? P_LASTW : 0) | (lx ? P_LASTX : 0);
    }
  sort(wr, n_wr);
  int holder[N_TILE];
  for (int i = 0; i < n_wr; i++) {
    int best = -1;
    for (int sl = 0; sl < st.slots; sl++)
      if (use[holder[sl]].freed + margin <= wr[i].t && (best < 0 || use[holder[sl]].freed < use[holder[best]].freed)) best = sl;
    Use& u = use[wr[i].id];
    if (best >= 0) { u.prev = holder[best]; use[u.prev].next = true; wr[i].o->flags |= P_GATE; }
    else if (st.slots == N_TILE) return false;
    else best = st.slots++;
    u.slot = best;
    holder[best] = wr[i].id;
  }
  {
    int pos[N_CL] = {}, flag[ID_PART + 4 * N_TEAM] = {}, seen[ID_PART] = {};
    auto goal = [&](int c) { return op[c][n_op[c] - 1].item0; };
    for (bool moved = true; moved;) {
      moved = false;
      for (int c = 0; c < 2 * n_pair; c++) {
        for (; pos[c] < goal(c); pos[c]++, moved = true) {
          bool ok = true;
          for (const Op* o = op[c]; o->type != OP_END; o++) {
            const int k = pos[c] - o->item0, own = o->type == OP_A ? o->id : N_TILE + (o->park & 127);
            if (k < 0 || k >= o->items) continue;
            if (o->type == OP_O) ok = k >= o->n || flag[o->id + k / 3];
            else if (k == o->items - 1 && (o->flags & P_GATE)) ok = seen[use[own].prev] == use[use[own].prev].readers;
            else if (k == 1 && o->type == OP_A && (o->flags & F_PARK)) ok = flag[N_TILE + o->park];
          }
          if (!ok) break;
          for (const Op* o = op[c]; o->type != OP_END; o++) {
            if (pos[c] == o->item0 + o->items + (o[1].type == OP_Q ? 7 : o[1].item0 == goal(c) ? -1 : 5)) {
              if (o->type == OP_A) flag[o->id] = 1;
              if (o->type == OP_Q && (o->flags & F_PARK)) flag[N_TILE + o->park] = 1;
              if (o->type == OP_O) flag[ID_PART + o->id / kH * 4 + o->quarter] = flag[ID_PART + o->id / kH * 4 + o->quarter + 1] = 1;
            }
            const int k = pos[c] - FLIGHT - o->item0, nw = o->n - TAIL;
            if (k == 1 && o->type == OP_A && (o->flags & F_PARK)) seen[N_TILE + o->park]++;
            if (o->type == OP_O && k >= 0 && k < o->items && (k < nw || k >= o->n) && (k < nw ? k : k - TAIL) % 3 == 2) seen[o->id + (k < nw ? k : k - TAIL) / 3]++;
          }
        }
      }
    }
    for (int c = 0; c < 2 * n_pair; c++) if (pos[c] < goal(c)) return false;
  }
  int n_job = 0, longest = 0;
  for (int i = 0; i < 2 * N_TEAM; i++) if (kH + 1 - covered[i] / 3 > longest) longest = kH + 1 - covered[i] / 3;
  for (int c = 0; c < 2 * n_pair; c++) {
    uint32_t items = 0, cur = 0, pend = 0;
    int n = 0, ev = 0;
    auto item = [&](uint32_t bytes, int count) {
      for (int i = 0; i < count; i++) { if (cur + bytes > RING) cur = 0; cur += bytes; items++; }
    };
    auto event = [&](uint32_t e) { if (ev < MAX_TAB) P.prog[c].ev[ev] = e; ev++; };
    for (const Op* o = op[c];; o++) {
      if (o->type != OP_END && phase && (o->type == OP_O) != (phase == 2)) continue;
      uint32_t cw = o->type | (items % (2 * NBAR)) << 15 | (cur >> 12) << 20 | pend, pw = o->type | o->id << 2 | o->flags;
      const int ps = use[N_TILE + (o->park & 127)].slot;
      pend = 0;
      if (o->type == OP_O) {
        pw |= o->n << 13 | o->quarter << 20 | (uint32_t)o->park << 23;
        if (o->flags & P_WIDE) {
          cw |= o->n << 2 | (o->id / kH * 2 + o->quarter / 2) << 9 | C_WIDE;
          item(SZ_W, o->n - TAIL);
          item(SZ_W2, TAIL);
          item(SZ_W3, TAIL);
          pend = C_PEND;
          for (int i = 0; 3 * i < o->n; i++) event((o->id + i) | E_ON | (use[o->id + i].next ? 0 : E_LAST));
        } else {
          dem[n_job++] = {o->t0 - 1e6 * o->n, nullptr, (int)pw};
          st.own[c] = pw;
          pw = OP_O;
          event(E_DRAW | (items < 16 ? 0 : items - 16));
        }
      } else if (o->type != OP_END) {
        const bool parks = o->type == OP_Q && (o->flags & F_PARK);
        cw |= (parks ? ps : use[o->id].slot) << 2 | (o->flags & F_PARK);
        if (o->flags & F_PARK) pw |= o->park << 13 | ps << 20;
        if (o->type == OP_Q) { item(SZ_Q, 10); pw |= o->quarter; }
        else { item(SZ_KV, 1); if (o->flags & F_PARK) { item(SZ_PARK, 1); event((N_TILE + o->park) | E_ON | (use[N_TILE + o->park].next ? 0 : E_LAST)); } item(SZ_KV, 31); }
        if (parks || o->type == OP_A) pend = C_PEND;
        if (o->flags & P_GATE) event(use[parks ? N_TILE + o->park : o->id].prev | E_ON | E_FREE);
      }
      P.prog[c].c[n] = cw; P.prog[c].p[n++] = pw;
      if (o->type == OP_END) { if (o->t0 > st.end) st.end = o->t0; break; }
    }
    if (ev > MAX_TAB || ev + longest > MAX_EV) return false;
    P.prog[c].n_ev = ev;
    while (n < MAX_OPS) { P.prog[c].c[n] = OP_END; P.prog[c].p[n++] = OP_END; }
    P.first[c] = (uint16_t)(P.prog[c].p[0] & 2047);
  }
  sort(dem, n_job);
  for (int i = 0; i < n_job; i++) P.job[i] = dem[i].id;
  for (int i = 0; i < ID_PART; i++) {
    if (i < N_TILE) P.slot[i] = use[i].slot;
    P.info[i] = (use[i].readers + use[i].next) | (use[i].next ? I_NEXT : 0);
  }
  if (stats) *stats = st;
  return true;
}

const char* const kPrograms[N_CL / 2] = {
  "PNJ06864NNNNN", "PNJ17878NNNNN", "PNJ26464NNNNN", "PNJ34148NNNNNN", "PNJ46262NNNNN", "PNJ58182NNNN",
  "NNJ67371NNNN", "PNNJ76666NNNN", "NUNNNJ84545NN", "NUNNNJ94545NN", "NUNNNNJa5551N", "NNNNNJb5959NN",
  "NNNNNJc5455NN", "PNNNNNJd5353NN", "NNNNNJe5153NN", "NNNNNJf7777N", "PNNNNNNNNN", "PNNNNNNNNN",
  "PNNNNNNNNN", "PNNNNNNNNN", "NNNNNNNNN", "NNNNNNNNN", "NNNNNNNNN", "NNNNNNNNN",
  "NNNNNNNNN", "N-NNNNNNNN", "NUNNNNNNN", "NUNNNNNNN", "NUNNNNNNN", "NUNNNUNNN",
  "NUNNNNNNN", "NUNNNNNNN", "NUUNNNNNN",
};

const char* const* bench_programs() {
  return kPrograms;
}

}

extern "C" void kernel_launch(void* const* d_in, const int* in_sizes, int n_in, void* d_out, int out_size) {
  (void)in_sizes; (void)n_in; (void)out_size;
  static EncodeFn fn = nullptr;
  static int n_clusters = 0;
  if (!fn) {
    cudaDriverEntryPointQueryResult qr;
    void* f = nullptr;
    cudaGetDriverEntryPoint("cuTensorMapEncodeTiled", &f, cudaEnableDefault, &qr);
    fn = (EncodeFn)f;
    cudaFuncSetAttribute(fused_kernel, cudaFuncAttributeMaxDynamicSharedMemorySize, SMEM_BYTES);
    cudaLaunchConfig_t cfg = {};
    cfg.gridDim = dim3(132); cfg.blockDim = dim3(384); cfg.dynamicSmemBytes = SMEM_BYTES;
    cudaLaunchAttribute at[1];
    at[0].id = cudaLaunchAttributeClusterDimension; at[0].val.clusterDim.x = 2; at[0].val.clusterDim.y = 1; at[0].val.clusterDim.z = 1;
    cfg.attrs = at; cfg.numAttrs = 1;
    if (cudaOccupancyMaxActiveClusters(&n_clusters, fused_kernel, &cfg) != cudaSuccess || n_clusters < 1) n_clusters = 1;
    (void)cudaGetLastError();
  }
  static Params P;
  const CUtensorMapSwizzle S128 = CU_TENSOR_MAP_SWIZZLE_128B, S64 = CU_TENSOR_MAP_SWIZZLE_64B;
  for (int blk = 0; blk < 2; blk++) {
    void* const* in = d_in + 5 * blk;
    { const cuuint64_t d[] = {kD, kB * kSq}, s[] = {kD * 2}; const cuuint32_t b[] = {64, 128};
      encode(fn, &P.x[blk], in[0], 2, d, s, b, S128); }
    { const cuuint64_t d[] = {64, 8, 3, (cuuint64_t)kB * kH * kSk / 8}, s[] = {kDh * 2, 128, 8 * kDh * 2}; const cuuint32_t b[] = {64, 8, 3, 4};
      encode(fn, &P.k[blk], in[1], 4, d, s, b, S128);
      encode(fn, &P.v[blk], in[2], 4, d, s, b, S128); }
    { const cuuint64_t d[] = {64, kD, kHD / 64}, s[] = {kHD * 2, 128}; const cuuint32_t b[] = {64, 32, 3};
      encode(fn, &P.wq[blk], in[3], 3, d, s, b, S128); }
    { const cuuint64_t d[] = {32, 2, kHD / 8, 4, kD / 32}, s[] = {kD * 2, 8 * kD * 2, 2 * kD * 2, 64}; const cuuint32_t b[] = {32, 2, 4, 4, 5};
      encode(fn, &P.wo[blk], in[4], 5, d, s, b, S64); }
    { const cuuint64_t d[] = {64, 2, kHD / 8, 4, kD / 64}, s[] = {kD * 2, 8 * kD * 2, 2 * kD * 2, 128};
      const cuuint32_t b3[] = {64, 2, 4, 4, 3}, b2[] = {64, 2, 4, 4, 2};
      encode(fn, &P.wo3[blk], in[4], 5, d, s, b3, S128);
      encode(fn, &P.wo2[blk], in[4], 5, d, s, b2, S128); }
  }
  { const cuuint64_t d[] = {32, kB * kSq, 2 * kD / 32}, s[] = {2 * kD * 2, 64}; const cuuint32_t b[] = {32, 16, 1};
    encode(fn, &P.out, d_out, 3, d, s, b, S64); }

  P.kv[0] = (const char*)d_in[1]; P.kv[1] = (const char*)d_in[6]; P.kv[2] = (const char*)d_in[2]; P.kv[3] = (const char*)d_in[7];
  P.xw[0] = (const char*)d_in[0]; P.xw[1] = (const char*)d_in[3];
  cudaGetSymbolAddress((void**)&P.g, g_scratch);
  P.dbg = DBG_DEFAULT;
  if (n_clusters >= N_CL && plan(bench_programs(), N_CL / 2, 0, P)) {
    fused_kernel<<<2 * N_CL, 384, SMEM_BYTES>>>(P);
  } else {
    const char* text[2 * N_TEAM];
    for (int i = 0; i < 2 * N_TEAM; i++) text[i] = "NNNNNNNN";
    for (int phase = 1; phase <= 2; phase++) {
      plan(text, 2 * N_TEAM, phase, P);
      fused_kernel<<<8 * N_TEAM, 384, SMEM_BYTES>>>(P);
    }
  }
}
```

```cpp
#include <cuda_runtime.h>
#include <cuda_bf16.h>
#include <cuda.h>
#include <cuda/annotated_ptr>
#include <stdint.h>
#include <stdio.h>

namespace {

constexpr int kB = 8, kSq = 256, kD = 640, kH = 32, kSk = 1024, kDh = 192;
constexpr int kHD = kH * kDh;
constexpr uint32_t RING = 224 * 1024;
constexpr uint32_t SZ_KV = 24576;
constexpr uint32_t SZ_Q = 16384 + 24576;
constexpr uint32_t SZ_O = 16384 + 20480;
constexpr uint32_t SZ_W3 = 16384 + 24576, SZ_W2 = 16384 + 16384, SZ_W = SZ_W3 + 16384;
constexpr uint32_t SZ_PARK = 49152;
constexpr uint32_t SZ_OL = SZ_O + 8192;
constexpr int NBAR = 16, FLIGHT = RING / SZ_KV + 1;
constexpr int EARLY = 3;
constexpr int kSteps = kHD / 64;
constexpr int TAIL = 4;
constexpr uint32_t KV_CH = 64, KV_SBO = 3072;
constexpr int SMEM_BYTES = RING + 1024 + 1024;
constexpr int N_TEAM = 16, N_CL = 66, MAX_OPS = 22, MAX_EV = 72, MAX_TAB = 47, N_TILE = N_TEAM * kH, MAX_PARK = 128, ID_PART = N_TILE + MAX_PARK;
enum : uint32_t { OP_END = 0, OP_Q = 1, OP_A = 2, OP_O = 3, F_PARK = 1 << 11,
                  C_WIDE = 1 << 27, C_PEND = 1 << 26, P_GATE = 1 << 12, P_WIDE = 1 << 11, P_LD = 1 << 12, P_PRE = 1 << 22, P_LASTW = 1 << 29, P_LASTX = 1 << 30,
                  I_NEXT = 8, E_ON = 1 << 15, E_FREE = 1 << 14, E_LAST = 1 << 13, E_DRAW = 1 << 12, E_JOB = 1 << 11 };

constexpr uint32_t DBG_DEFAULT = 0x040800;

struct alignas(1024) Scratch {
  unsigned int flag[2047];
  unsigned int ticket;
  uint4 part[N_TEAM * 2 * 2 * 5120];
  uint4 tile[N_TILE * 2 * 3072];
};

struct alignas(64) Params {
  const char* xw[2];
  uint16_t first[80];
  Scratch* g;
  uint32_t dbg;
  CUtensorMap x[2], wq[2], k[2], v[2], wo[2], wo3[2], wo2[2], out;
  struct {
    uint32_t c[MAX_OPS];
    uint32_t p[MAX_OPS];
    uint16_t n_ev, ev[MAX_TAB];
  } prog[N_CL];
  const char* kv[4];
  uint32_t job[N_CL];
  uint16_t slot[N_TILE];
  uint8_t info[ID_PART];
};

__device__ Scratch g_scratch;

template <int TB, int TA = 0>
__device__ __forceinline__ void wgmma_ss_n64(float (&d)[32], uint64_t da, uint64_t db, int scale_d) {
  asm volatile("{\n.reg .pred p;\nsetp.ne.b32 p, %34, 0;\n"
    "wgmma.mma_async.sync.aligned.m64n64k16.f32.bf16.bf16 {%0, %1, %2, %3, %4, %5, %6, %7, %8, %9, %10, %11, %12, %13, %14, %15, %16, %17, %18, %19, %20, %21, %22, %23, %24, %25, %26, %27, %28, %29, %30, %31}, %32, %33, p, 1, 1, %35, %36;\n}\n"
    : "+f"(d[0]), "+f"(d[1]), "+f"(d[2]), "+f"(d[3]), "+f"(d[4]), "+f"(d[5]), "+f"(d[6]), "+f"(d[7]), "+f"(d[8]), "+f"(d[9]), "+f"(d[10]), "+f"(d[11]), "+f"(d[12]), "+f"(d[13]), "+f"(d[14]), "+f"(d[15]), "+f"(d[16]), "+f"(d[17]), "+f"(d[18]), "+f"(d[19]), "+f"(d[20]), "+f"(d[21]), "+f"(d[22]), "+f"(d[23]), "+f"(d[24]), "+f"(d[25]), "+f"(d[26]), "+f"(d[27]), "+f"(d[28]), "+f"(d[29]), "+f"(d[30]), "+f"(d[31])
    : "l"(da), "l"(db), "r"(scale_d), "n"(TA), "n"(TB));
}
template <int TB>
__device__ __forceinline__ void wgmma_rs_n64(float (&d)[32], uint32_t a0, uint32_t a1, uint32_t a2, uint32_t a3, uint64_t db, int scale_d) {
  asm volatile("{\n.reg .pred p;\nsetp.ne.b32 p, %37, 0;\n"
    "wgmma.mma_async.sync.aligned.m64n64k16.f32.bf16.bf16 {%0, %1, %2, %3, %4, %5, %6, %7, %8, %9, %10, %11, %12, %13, %14, %15, %16, %17, %18, %19, %20, %21, %22, %23, %24, %25, %26, %27, %28, %29, %30, %31}, {%32, %33, %34, %35}, %36, p, 1, 1, %38;\n}\n"
    : "+f"(d[0]), "+f"(d[1]), "+f"(d[2]), "+f"(d[3]), "+f"(d[4]), "+f"(d[5]), "+f"(d[6]), "+f"(d[7]), "+f"(d[8]), "+f"(d[9]), "+f"(d[10]), "+f"(d[11]), "+f"(d[12]), "+f"(d[13]), "+f"(d[14]), "+f"(d[15]), "+f"(d[16]), "+f"(d[17]), "+f"(d[18]), "+f"(d[19]), "+f"(d[20]), "+f"(d[21]), "+f"(d[22]), "+f"(d[23]), "+f"(d[24]), "+f"(d[25]), "+f"(d[26]), "+f"(d[27]), "+f"(d[28]), "+f"(d[29]), "+f"(d[30]), "+f"(d[31])
    : "r"(a0), "r"(a1), "r"(a2), "r"(a3), "l"(db), "r"(scale_d), "n"(TB));
}
template <int TB, int TA = 0>
__device__ __forceinline__ void wgmma_ss_n128(float (&d)[64], uint64_t da, uint64_t db, int scale_d) {
  asm volatile("{\n.reg .pred p;\nsetp.ne.b32 p, %66, 0;\n"
    "wgmma.mma_async.sync.aligned.m64n128k16.f32.bf16.bf16 {%0, %1, %2, %3, %4, %5, %6, %7, %8, %9, %10, %11, %12, %13, %14, %15, %16, %17, %18, %19, %20, %21, %22, %23, %24, %25, %26, %27, %28, %29, %30, %31, %32, %33, %34, %35, %36, %37, %38, %39, %40, %41, %42, %43, %44, %45, %46, %47, %48, %49, %50, %51, %52, %53, %54, %55, %56, %57, %58, %59, %60, %61, %62, %63}, %64, %65, p, 1, 1, %67, %68;\n}\n"
    : "+f"(d[0]), "+f"(d[1]), "+f"(d[2]), "+f"(d[3]), "+f"(d[4]), "+f"(d[5]), "+f"(d[6]), "+f"(d[7]), "+f"(d[8]), "+f"(d[9]), "+f"(d[10]), "+f"(d[11]), "+f"(d[12]), "+f"(d[13]), "+f"(d[14]), "+f"(d[15]), "+f"(d[16]), "+f"(d[17]), "+f"(d[18]), "+f"(d[19]), "+f"(d[20]), "+f"(d[21]), "+f"(d[22]), "+f"(d[23]), "+f"(d[24]), "+f"(d[25]), "+f"(d[26]), "+f"(d[27]), "+f"(d[28]), "+f"(d[29]), "+f"(d[30]), "+f"(d[31]), "+f"(d[32]), "+f"(d[33]), "+f"(d[34]), "+f"(d[35]), "+f"(d[36]), "+f"(d[37]), "+f"(d[38]), "+f"(d[39]), "+f"(d[40]), "+f"(d[41]), "+f"(d[42]), "+f"(d[43]), "+f"(d[44]), "+f"(d[45]), "+f"(d[46]), "+f"(d[47]), "+f"(d[48]), "+f"(d[49]), "+f"(d[50]), "+f"(d[51]), "+f"(d[52]), "+f"(d[53]), "+f"(d[54]), "+f"(d[55]), "+f"(d[56]), "+f"(d[57]), "+f"(d[58]), "+f"(d[59]), "+f"(d[60]), "+f"(d[61]), "+f"(d[62]), "+f"(d[63])
    : "l"(da), "l"(db), "r"(scale_d), "n"(TA), "n"(TB));
}
template <int TB>
__device__ __forceinline__ void wgmma_rs_n128(float (&d)[64], uint32_t a0, uint32_t a1, uint32_t a2, uint32_t a3, uint64_t db, int scale_d) {
  asm volatile("{\n.reg .pred p;\nsetp.ne.b32 p, %69, 0;\n"
    "wgmma.mma_async.sync.aligned.m64n128k16.f32.bf16.bf16 {%0, %1, %2, %3, %4, %5, %6, %7, %8, %9, %10, %11, %12, %13, %14, %15, %16, %17, %18, %19, %20, %21, %22, %23, %24, %25, %26, %27, %28, %29, %30, %31, %32, %33, %34, %35, %36, %37, %38, %39, %40, %41, %42, %43, %44, %45, %46, %47, %48, %49, %50, %51, %52, %53, %54, %55, %56, %57, %58, %59, %60, %61, %62, %63}, {%64, %65, %66, %67}, %68, p, 1, 1, %70;\n}\n"
    : "+f"(d[0]), "+f"(d[1]), "+f"(d[2]), "+f"(d[3]), "+f"(d[4]), "+f"(d[5]), "+f"(d[6]), "+f"(d[7]), "+f"(d[8]), "+f"(d[9]), "+f"(d[10]), "+f"(d[11]), "+f"(d[12]), "+f"(d[13]), "+f"(d[14]), "+f"(d[15]), "+f"(d[16]), "+f"(d[17]), "+f"(d[18]), "+f"(d[19]), "+f"(d[20]), "+f"(d[21]), "+f"(d[22]), "+f"(d[23]), "+f"(d[24]), "+f"(d[25]), "+f"(d[26]), "+f"(d[27]), "+f"(d[28]), "+f"(d[29]), "+f"(d[30]), "+f"(d[31]), "+f"(d[32]), "+f"(d[33]), "+f"(d[34]), "+f"(d[35]), "+f"(d[36]), "+f"(d[37]), "+f"(d[38]), "+f"(d[39]), "+f"(d[40]), "+f"(d[41]), "+f"(d[42]), "+f"(d[43]), "+f"(d[44]), "+f"(d[45]), "+f"(d[46]), "+f"(d[47]), "+f"(d[48]), "+f"(d[49]), "+f"(d[50]), "+f"(d[51]), "+f"(d[52]), "+f"(d[53]), "+f"(d[54]), "+f"(d[55]), "+f"(d[56]), "+f"(d[57]), "+f"(d[58]), "+f"(d[59]), "+f"(d[60]), "+f"(d[61]), "+f"(d[62]), "+f"(d[63])
    : "r"(a0), "r"(a1), "r"(a2), "r"(a3), "l"(db), "r"(scale_d), "n"(TB));
}
template <int TB, int TA = 0>
__device__ __forceinline__ void wgmma_ss_n160(float (&d)[80], uint64_t da, uint64_t db, int scale_d) {
  asm volatile("{\n.reg .pred p;\nsetp.ne.b32 p, %82, 0;\n"
    "wgmma.mma_async.sync.aligned.m64n160k16.f32.bf16.bf16 {%0, %1, %2, %3, %4, %5, %6, %7, %8, %9, %10, %11, %12, %13, %14, %15, %16, %17, %18, %19, %20, %21, %22, %23, %24, %25, %26, %27, %28, %29, %30, %31, %32, %33, %34, %35, %36, %37, %38, %39, %40, %41, %42, %43, %44, %45, %46, %47, %48, %49, %50, %51, %52, %53, %54, %55, %56, %57, %58, %59, %60, %61, %62, %63, %64, %65, %66, %67, %68, %69, %70, %71, %72, %73, %74, %75, %76, %77, %78, %79}, %80, %81, p, 1, 1, %83, %84;\n}\n"
    : "+f"(d[0]), "+f"(d[1]), "+f"(d[2]), "+f"(d[3]), "+f"(d[4]), "+f"(d[5]), "+f"(d[6]), "+f"(d[7]), "+f"(d[8]), "+f"(d[9]), "+f"(d[10]), "+f"(d[11]), "+f"(d[12]), "+f"(d[13]), "+f"(d[14]), "+f"(d[15]), "+f"(d[16]), "+f"(d[17]), "+f"(d[18]), "+f"(d[19]), "+f"(d[20]), "+f"(d[21]), "+f"(d[22]), "+f"(d[23]), "+f"(d[24]), "+f"(d[25]), "+f"(d[26]), "+f"(d[27]), "+f"(d[28]), "+f"(d[29]), "+f"(d[30]), "+f"(d[31]), "+f"(d[32]), "+f"(d[33]), "+f"(d[34]), "+f"(d[35]), "+f"(d[36]), "+f"(d[37]), "+f"(d[38]), "+f"(d[39]), "+f"(d[40]), "+f"(d[41]), "+f"(d[42]), "+f"(d[43]), "+f"(d[44]), "+f"(d[45]), "+f"(d[46]), "+f"(d[47]), "+f"(d[48]), "+f"(d[49]), "+f"(d[50]), "+f"(d[51]), "+f"(d[52]), "+f"(d[53]), "+f"(d[54]), "+f"(d[55]), "+f"(d[56]), "+f"(d[57]), "+f"(d[58]), "+f"(d[59]), "+f"(d[60]), "+f"(d[61]), "+f"(d[62]), "+f"(d[63]), "+f"(d[64]), "+f"(d[65]), "+f"(d[66]), "+f"(d[67]), "+f"(d[68]), "+f"(d[69]), "+f"(d[70]), "+f"(d[71]), "+f"(d[72]), "+f"(d[73]), "+f"(d[74]), "+f"(d[75]), "+f"(d[76]), "+f"(d[77]), "+f"(d[78]), "+f"(d[79])
    : "l"(da), "l"(db), "r"(scale_d), "n"(TA), "n"(TB));
}
template <int TB>
__device__ __forceinline__ void wgmma_rs_n160(float (&d)[80], uint32_t a0, uint32_t a1, uint32_t a2, uint32_t a3, uint64_t db, int scale_d) {
  asm volatile("{\n.reg .pred p;\nsetp.ne.b32 p, %85, 0;\n"
    "wgmma.mma_async.sync.aligned.m64n160k16.f32.bf16.bf16 {%0, %1, %2, %3, %4, %5, %6, %7, %8, %9, %10, %11, %12, %13, %14, %15, %16, %17, %18, %19, %20, %21, %22, %23, %24, %25, %26, %27, %28, %29, %30, %31, %32, %33, %34, %35, %36, %37, %38, %39, %40, %41, %42, %43, %44, %45, %46, %47, %48, %49, %50, %51, %52, %53, %54, %55, %56, %57, %58, %59, %60, %61, %62, %63, %64, %65, %66, %67, %68, %69, %70, %71, %72, %73, %74, %75, %76, %77, %78, %79}, {%80, %81, %82, %83}, %84, p, 1, 1, %86;\n}\n"
    : "+f"(d[0]), "+f"(d[1]), "+f"(d[2]), "+f"(d[3]), "+f"(d[4]), "+f"(d[5]), "+f"(d[6]), "+f"(d[7]), "+f"(d[8]), "+f"(d[9]), "+f"(d[10]), "+f"(d[11]), "+f"(d[12]), "+f"(d[13]), "+f"(d[14]), "+f"(d[15]), "+f"(d[16]), "+f"(d[17]), "+f"(d[18]), "+f"(d[19]), "+f"(d[20]), "+f"(d[21]), "+f"(d[22]), "+f"(d[23]), "+f"(d[24]), "+f"(d[25]), "+f"(d[26]), "+f"(d[27]), "+f"(d[28]), "+f"(d[29]), "+f"(d[30]), "+f"(d[31]), "+f"(d[32]), "+f"(d[33]), "+f"(d[34]), "+f"(d[35]), "+f"(d[36]), "+f"(d[37]), "+f"(d[38]), "+f"(d[39]), "+f"(d[40]), "+f"(d[41]), "+f"(d[42]), "+f"(d[43]), "+f"(d[44]), "+f"(d[45]), "+f"(d[46]), "+f"(d[47]), "+f"(d[48]), "+f"(d[49]), "+f"(d[50]), "+f"(d[51]), "+f"(d[52]), "+f"(d[53]), "+f"(d[54]), "+f"(d[55]), "+f"(d[56]), "+f"(d[57]), "+f"(d[58]), "+f"(d[59]), "+f"(d[60]), "+f"(d[61]), "+f"(d[62]), "+f"(d[63]), "+f"(d[64]), "+f"(d[65]), "+f"(d[66]), "+f"(d[67]), "+f"(d[68]), "+f"(d[69]), "+f"(d[70]), "+f"(d[71]), "+f"(d[72]), "+f"(d[73]), "+f"(d[74]), "+f"(d[75]), "+f"(d[76]), "+f"(d[77]), "+f"(d[78]), "+f"(d[79])
    : "r"(a0), "r"(a1), "r"(a2), "r"(a3), "l"(db), "r"(scale_d), "n"(TB));
}
template <int TB, int TA = 0>
__device__ __forceinline__ void wgmma_ss_n192(float (&d)[96], uint64_t da, uint64_t db, int scale_d) {
  asm volatile("{\n.reg .pred p;\nsetp.ne.b32 p, %98, 0;\n"
    "wgmma.mma_async.sync.aligned.m64n192k16.f32.bf16.bf16 {%0, %1, %2, %3, %4, %5, %6, %7, %8, %9, %10, %11, %12, %13, %14, %15, %16, %17, %18, %19, %20, %21, %22, %23, %24, %25, %26, %27, %28, %29, %30, %31, %32, %33, %34, %35, %36, %37, %38, %39, %40, %41, %42, %43, %44, %45, %46, %47, %48, %49, %50, %51, %52, %53, %54, %55, %56, %57, %58, %59, %60, %61, %62, %63, %64, %65, %66, %67, %68, %69, %70, %71, %72, %73, %74, %75, %76, %77, %78, %79, %80, %81, %82, %83, %84, %85, %86, %87, %88, %89, %90, %91, %92, %93, %94, %95}, %96, %97, p, 1, 1, %99, %100;\n}\n"
    : "+f"(d[0]), "+f"(d[1]), "+f"(d[2]), "+f"(d[3]), "+f"(d[4]), "+f"(d[5]), "+f"(d[6]), "+f"(d[7]), "+f"(d[8]), "+f"(d[9]), "+f"(d[10]), "+f"(d[11]), "+f"(d[12]), "+f"(d[13]), "+f"(d[14]), "+f"(d[15]), "+f"(d[16]), "+f"(d[17]), "+f"(d[18]), "+f"(d[19]), "+f"(d[20]), "+f"(d[21]), "+f"(d[22]), "+f"(d[23]), "+f"(d[24]), "+f"(d[25]), "+f"(d[26]), "+f"(d[27]), "+f"(d[28]), "+f"(d[29]), "+f"(d[30]), "+f"(d[31]), "+f"(d[32]), "+f"(d[33]), "+f"(d[34]), "+f"(d[35]), "+f"(d[36]), "+f"(d[37]), "+f"(d[38]), "+f"(d[39]), "+f"(d[40]), "+f"(d[41]), "+f"(d[42]), "+f"(d[43]), "+f"(d[44]), "+f"(d[45]), "+f"(d[46]), "+f"(d[47]), "+f"(d[48]), "+f"(d[49]), "+f"(d[50]), "+f"(d[51]), "+f"(d[52]), "+f"(d[53]), "+f"(d[54]), "+f"(d[55]), "+f"(d[56]), "+f"(d[57]), "+f"(d[58]), "+f"(d[59]), "+f"(d[60]), "+f"(d[61]), "+f"(d[62]), "+f"(d[63]), "+f"(d[64]), "+f"(d[65]), "+f"(d[66]), "+f"(d[67]), "+f"(d[68]), "+f"(d[69]), "+f"(d[70]), "+f"(d[71]), "+f"(d[72]), "+f"(d[73]), "+f"(d[74]), "+f"(d[75]), "+f"(d[76]), "+f"(d[77]), "+f"(d[78]), "+f"(d[79]), "+f"(d[80]), "+f"(d[81]), "+f"(d[82]), "+f"(d[83]), "+f"(d[84]), "+f"(d[85]), "+f"(d[86]), "+f"(d[87]), "+f"(d[88]), "+f"(d[89]), "+f"(d[90]), "+f"(d[91]), "+f"(d[92]), "+f"(d[93]), "+f"(d[94]), "+f"(d[95])
    : "l"(da), "l"(db), "r"(scale_d), "n"(TA), "n"(TB));
}
template <int TB>
__device__ __forceinline__ void wgmma_rs_n192(float (&d)[96], uint32_t a0, uint32_t a1, uint32_t a2, uint32_t a3, uint64_t db, int scale_d) {
  asm volatile("{\n.reg .pred p;\nsetp.ne.b32 p, %101, 0;\n"
    "wgmma.mma_async.sync.aligned.m64n192k16.f32.bf16.bf16 {%0, %1, %2, %3, %4, %5, %6, %7, %8, %9, %10, %11, %12, %13, %14, %15, %16, %17, %18, %19, %20, %21, %22, %23, %24, %25, %26, %27, %28, %29, %30, %31, %32, %33, %34, %35, %36, %37, %38, %39, %40, %41, %42, %43, %44, %45, %46, %47, %48, %49, %50, %51, %52, %53, %54, %55, %56, %57, %58, %59, %60, %61, %62, %63, %64, %65, %66, %67, %68, %69, %70, %71, %72, %73, %74, %75, %76, %77, %78, %79, %80, %81, %82, %83, %84, %85, %86, %87, %88, %89, %90, %91, %92, %93, %94, %95}, {%96, %97, %98, %99}, %100, p, 1, 1, %102;\n}\n"
    : "+f"(d[0]), "+f"(d[1]), "+f"(d[2]), "+f"(d[3]), "+f"(d[4]), "+f"(d[5]), "+f"(d[6]), "+f"(d[7]), "+f"(d[8]), "+f"(d[9]), "+f"(d[10]), "+f"(d[11]), "+f"(d[12]), "+f"(d[13]), "+f"(d[14]), "+f"(d[15]), "+f"(d[16]), "+f"(d[17]), "+f"(d[18]), "+f"(d[19]), "+f"(d[20]), "+f"(d[21]), "+f"(d[22]), "+f"(d[23]), "+f"(d[24]), "+f"(d[25]), "+f"(d[26]), "+f"(d[27]), "+f"(d[28]), "+f"(d[29]), "+f"(d[30]), "+f"(d[31]), "+f"(d[32]), "+f"(d[33]), "+f"(d[34]), "+f"(d[35]), "+f"(d[36]), "+f"(d[37]), "+f"(d[38]), "+f"(d[39]), "+f"(d[40]), "+f"(d[41]), "+f"(d[42]), "+f"(d[43]), "+f"(d[44]), "+f"(d[45]), "+f"(d[46]), "+f"(d[47]), "+f"(d[48]), "+f"(d[49]), "+f"(d[50]), "+f"(d[51]), "+f"(d[52]), "+f"(d[53]), "+f"(d[54]), "+f"(d[55]), "+f"(d[56]), "+f"(d[57]), "+f"(d[58]), "+f"(d[59]), "+f"(d[60]), "+f"(d[61]), "+f"(d[62]), "+f"(d[63]), "+f"(d[64]), "+f"(d[65]), "+f"(d[66]), "+f"(d[67]), "+f"(d[68]), "+f"(d[69]), "+f"(d[70]), "+f"(d[71]), "+f"(d[72]), "+f"(d[73]), "+f"(d[74]), "+f"(d[75]), "+f"(d[76]), "+f"(d[77]), "+f"(d[78]), "+f"(d[79]), "+f"(d[80]), "+f"(d[81]), "+f"(d[82]), "+f"(d[83]), "+f"(d[84]), "+f"(d[85]), "+f"(d[86]), "+f"(d[87]), "+f"(d[88]), "+f"(d[89]), "+f"(d[90]), "+f"(d[91]), "+f"(d[92]), "+f"(d[93]), "+f"(d[94]), "+f"(d[95])
    : "r"(a0), "r"(a1), "r"(a2), "r"(a3), "l"(db), "r"(scale_d), "n"(TB));
}

__device__ __forceinline__ uint32_t smem_u32(const void* p) { return (uint32_t)__cvta_generic_to_shared(p); }
__device__ __forceinline__ void wg_fence() { asm volatile("wgmma.fence.sync.aligned;" ::: "memory"); }
__device__ __forceinline__ void wg_commit() { asm volatile("wgmma.commit_group.sync.aligned;" ::: "memory"); }
template <int N> __device__ __forceinline__ void wg_wait() { asm volatile("wgmma.wait_group.sync.aligned %0;" ::"n"(N) : "memory"); }
__device__ __forceinline__ void sched_fence(uint32_t& keep, bool never) {
  asm volatile("{\n.reg .pred p;\nsetp.ne.b32 p, %1, 0;\n@p mov.u32 %0, %%clock;\n}\n" : "+r"(keep) : "r"((int)never) : "memory");
}
template <int N> __device__ __forceinline__ void fence_regs(float (&r)[N]) {
#pragma unroll
  for (int i = 0; i < N; i++) asm volatile("" : "+f"(r[i])::"memory");
}
template <int N> __device__ __forceinline__ void undefine(float (&r)[N]) {
#pragma unroll
  for (int i = 0; i < N; i++) asm volatile("" : "=f"(r[i]));
}
template <int N> __device__ __forceinline__ void fence_regs(uint32_t (&r)[N]) {
#pragma unroll
  for (int i = 0; i < N; i++) asm volatile("" : "+r"(r[i])::"memory");
}
__device__ __forceinline__ uint64_t mk_desc(uint32_t a16, uint32_t lbo, uint32_t sbo, uint32_t swz) {
  uint64_t d;
  asm("mov.b64 %0, {%1, %2};" : "=l"(d) : "r"(a16 + ((lbo >> 4) << 16)), "r"((sbo >> 4) | (swz << 30)));
  return d;
}
__device__ __forceinline__ void mbar_init(uint32_t bar, uint32_t cnt) {
  asm volatile("mbarrier.init.shared::cta.b64 [%0], %1;" ::"r"(bar), "r"(cnt) : "memory");
}
__device__ __forceinline__ void mbar_expect(uint32_t bar, uint32_t tx) {
  asm volatile("mbarrier.arrive.expect_tx.shared::cta.b64 _, [%0], %1;" ::"r"(bar), "r"(tx) : "memory");
}
__device__ __forceinline__ bool mbar_test(uint32_t bar, uint32_t ph) {
  uint32_t ok;
  asm volatile("{\n.reg .pred p;\nmbarrier.test_wait.parity.shared::cta.b64 p, [%1], %2;\nselp.u32 %0, 1, 0, p;\n}\n"
               : "=r"(ok) : "r"(bar), "r"(ph) : "memory");
  return ok;
}
__device__ __forceinline__ bool mbar_try(uint32_t bar, uint32_t ph, uint32_t ns) {
  uint32_t ok;
  asm volatile("{\n.reg .pred p;\nmbarrier.try_wait.parity.shared::cta.b64 p, [%1], %2, %3;\nselp.u32 %0, 1, 0, p;\n}\n"
               : "=r"(ok) : "r"(bar), "r"(ph), "r"(ns) : "memory");
  return ok;
}
__device__ __forceinline__ void mbar_wait(uint32_t bar, uint32_t ph) {
  asm volatile("{\n.reg .pred p;\n.reg .u32 n;\nmov.u32 n, 0;\n"
               "LOOP:\nmbarrier.try_wait.parity.shared::cta.b64 p, [%0], %1;\n@p bra DONE;\n"
               "add.u32 n, n, 1;\nsetp.lt.u32 p, n, 0x1000000;\n@p bra LOOP;\ntrap;\n"
               "DONE:\n}\n" ::"r"(bar), "r"(ph) : "memory");
}
__device__ __forceinline__ void mbar_wait_long(uint32_t bar) {
  asm volatile("{\n.reg .pred p;\n.reg .u32 n;\nmov.u32 n, 0;\n"
               "LOOP:\nmbarrier.try_wait.parity.shared::cta.b64 p, [%0], 0, 20000;\n@p bra DONE;\n"
               "add.u32 n, n, 1;\nsetp.lt.u32 p, n, 0x100000;\n@p bra LOOP;\ntrap;\n"
               "DONE:\n}\n" ::"r"(bar) : "memory");
}
__device__ __forceinline__ void mbar_arrive_cluster_if(bool on, uint32_t addr) {
  asm volatile("{\n.reg .pred p;\nsetp.ne.b32 p, %1, 0;\n@p mbarrier.arrive.shared::cluster.b64 _, [%0];\n}\n" ::"r"(addr), "r"((int)on) : "memory");
}
__device__ __forceinline__ void mbar_arrive_cluster_n(uint32_t n, uint32_t addr) {
  asm volatile("{\n.reg .pred p;\nsetp.ne.b32 p, %1, 0;\n@p mbarrier.arrive.shared::cluster.b64 _, [%0], %1;\n}\n" ::"r"(addr), "r"(n) : "memory");
}
__device__ __forceinline__ void tma2d(uint32_t dst, const CUtensorMap* m, uint32_t bar, int c0, int c1) {
  asm volatile("cp.async.bulk.tensor.2d.shared::cluster.global.mbarrier::complete_tx::bytes [%0], [%1, {%3, %4}], [%2];"
               ::"r"(dst), "l"(m), "r"(bar), "r"(c0), "r"(c1) : "memory");
}
__device__ __forceinline__ void tma3d(uint32_t dst, const CUtensorMap* m, uint32_t bar, int c0, int c1, int c2) {
  asm volatile("cp.async.bulk.tensor.3d.shared::cluster.global.mbarrier::complete_tx::bytes [%0], [%1, {%3, %4, %5}], [%2];"
               ::"r"(dst), "l"(m), "r"(bar), "r"(c0), "r"(c1), "r"(c2) : "memory");
}
__device__ __forceinline__ void tma2d_hint(uint32_t dst, const CUtensorMap* m, uint32_t bar, int c0, int c1, uint64_t pol) {
  asm volatile("cp.async.bulk.tensor.2d.shared::cluster.global.mbarrier::complete_tx::bytes.L2::cache_hint [%0], [%1, {%3, %4}], [%2], %5;"
               ::"r"(dst), "l"(m), "r"(bar), "r"(c0), "r"(c1), "l"(pol) : "memory");
}
__device__ __forceinline__ void tma3d_mc_hint(uint32_t dst, const CUtensorMap* m, uint32_t bar, int c1, int c2, uint64_t pol) {
  asm volatile("cp.async.bulk.tensor.3d.shared::cluster.global.mbarrier::complete_tx::bytes.multicast::cluster.L2::cache_hint"
               " [%0], [%1, {%3, %4, %5}], [%2], %6, %7;"
               ::"r"(dst), "l"(m), "r"(bar), "r"(0), "r"(c1), "r"(c2), "h"((uint16_t)3), "l"(pol) : "memory");
}
__device__ __forceinline__ void tma5d_mc_hint(uint32_t dst, const CUtensorMap* m, uint32_t bar, int c2, int c4, uint64_t pol) {
  asm volatile("cp.async.bulk.tensor.5d.shared::cluster.global.mbarrier::complete_tx::bytes.multicast::cluster.L2::cache_hint"
               " [%0], [%1, {%3, %3, %4, %3, %5}], [%2], %6, %7;"
               ::"r"(dst), "l"(m), "r"(bar), "r"(0), "r"(c2), "r"(c4), "h"((uint16_t)3), "l"(pol) : "memory");
}
__device__ __forceinline__ void tma3d_store(const CUtensorMap* m, uint32_t src, int c0, int c1, int c2) {
  asm volatile("cp.async.bulk.tensor.3d.global.shared::cta.bulk_group [%0, {%2, %3, %4}], [%1];"
               ::"l"(m), "r"(src), "r"(c0), "r"(c1), "r"(c2) : "memory");
}
__device__ __forceinline__ void bar_sync(int id, int n) { asm volatile("bar.sync %0, %1;" ::"r"(id), "r"(n) : "memory"); }
__device__ __forceinline__ uint32_t pack_bf16(float lo, float hi) {
  uint32_t r;
  asm("cvt.rn.bf16x2.f32 %0, %1, %2;" : "=r"(r) : "f"(hi), "f"(lo));
  return r;
}
__device__ __forceinline__ float ex2(float x) {
  float y;
  asm("ex2.approx.ftz.f32 %0, %1;" : "=f"(y) : "f"(x));
  return y;
}
__device__ __forceinline__ float rcp(float x) {
  float y;
  asm("rcp.approx.ftz.f32 %0, %1;" : "=f"(y) : "f"(x));
  return y;
}
__device__ __forceinline__ void stsm4(uint32_t addr, uint32_t a, uint32_t b, uint32_t c, uint32_t d) {
  asm volatile("stmatrix.sync.aligned.m8n8.x4.shared.b16 [%0], {%1, %2, %3, %4};" ::"r"(addr), "r"(a), "r"(b), "r"(c), "r"(d) : "memory");
}

__device__ __forceinline__ void tma4d_mc_hint(uint32_t dst, const CUtensorMap* m, uint32_t bar, int c3, uint64_t pol) {
  asm volatile("cp.async.bulk.tensor.4d.shared::cluster.global.mbarrier::complete_tx::bytes.multicast::cluster.L2::cache_hint"
               " [%0], [%1, {%3, %3, %3, %4}], [%2], %5, %6;"
               ::"r"(dst), "l"(m), "r"(bar), "r"(0), "r"(c3), "h"((uint16_t)3), "l"(pol) : "memory");
}
__device__ __forceinline__ void bulk_load_hint(uint32_t dst, const void* src, uint32_t bytes, uint32_t bar, uint64_t pol) {
  asm volatile("cp.async.bulk.shared::cluster.global.mbarrier::complete_tx::bytes.L2::cache_hint [%0], [%1], %2, [%3], %4;"
               ::"r"(dst), "l"(src), "r"(bytes), "r"(bar), "l"(pol) : "memory");
}
__device__ __forceinline__ void stg2_if(bool on, void* p, uint32_t a, uint32_t b, uint32_t c, uint32_t d, uint32_t e, uint32_t f,
                                        uint32_t g, uint32_t h, uint64_t pol) {
  asm volatile("{\n.reg .pred p;\nsetp.ne.b32 p, %10, 0;\n"
               "@p st.global.L2::cache_hint.v4.b32 [%0], {%1, %2, %3, %4}, %9;\n"
               "@p st.global.L2::cache_hint.v4.b32 [%0 + 512], {%5, %6, %7, %8}, %9;\n}\n"
               ::"l"(p), "r"(a), "r"(b), "r"(c), "r"(d), "r"(e), "r"(f), "r"(g), "r"(h), "l"(pol), "r"((int)on) : "memory");
}
__device__ __forceinline__ uint64_t evict_first() {
  uint64_t p;
  asm("createpolicy.fractional.L2::evict_first.b64 %0, 1.0;" : "=l"(p));
  return p;
}
__device__ __forceinline__ uint64_t no_hint() {
  uint64_t p;
  asm("createpolicy.cvt.L2.b64 %0, %1;" : "=l"(p) : "l"(static_cast<uint64_t>(cuda::access_property{})));
  return p;
}
__device__ __forceinline__ bool elect() {
  uint32_t ok;
  asm volatile("{\n.reg .pred p;\nelect.sync _|p, 0xffffffff;\nselp.u32 %0, 1, 0, p;\n}\n" : "=r"(ok));
  return ok;
}
__device__ __forceinline__ void mbar_arrive(uint32_t bar) {
  asm volatile("mbarrier.arrive.shared::cta.b64 _, [%0];" ::"r"(bar) : "memory");
}
__device__ __forceinline__ void mbar_arrive_if(bool on, uint32_t bar) {
  asm volatile("{\n.reg .pred p;\nsetp.ne.b32 p, %1, 0;\n@p mbarrier.arrive.shared::cta.b64 _, [%0];\n}\n" ::"r"(bar), "r"((int)on) : "memory");
}
__device__ __forceinline__ void lds2_if(bool on, uint32_t p, uint32_t (&t)[8]) {
  asm volatile("{\n.reg .pred p;\nsetp.ne.b32 p, %9, 0;\n@p ld.shared.v4.b32 {%0, %1, %2, %3}, [%8];\n@p ld.shared.v4.b32 {%4, %5, %6, %7}, [%8 + 512];\n}\n"
               : "+r"(t[0]), "+r"(t[1]), "+r"(t[2]), "+r"(t[3]), "+r"(t[4]), "+r"(t[5]), "+r"(t[6]), "+r"(t[7]) : "r"(p), "r"((int)on) : "memory");
}
__device__ __forceinline__ void lds128(uint32_t p, uint32_t& a, uint32_t& b, uint32_t& c, uint32_t& d) {
  asm volatile("ld.shared.v4.b32 {%0, %1, %2, %3}, [%4];" : "=r"(a), "=r"(b), "=r"(c), "=r"(d) : "r"(p) : "memory");
}
template <class T> __device__ __forceinline__ T* ptr_add(T* base, uint32_t bytes) {
  T* r;
  asm("{\n.reg .u32 lo, hi;\nmov.b64 {lo, hi}, %1;\nadd.cc.u32 lo, lo, %2;\naddc.u32 hi, hi, 0;\nmov.b64 %0, {lo, hi};\n}\n" : "=l"(r) : "l"(base), "r"(bytes));
  return r;
}
__device__ __forceinline__ uint32_t lds32(uint32_t p) {
  uint32_t v;
  asm volatile("ld.volatile.shared.u32 %0, [%1];" : "=r"(v) : "r"(p) : "memory");
  return v;
}
__device__ __forceinline__ uint32_t flag_get(const unsigned int* p) {
  uint32_t v;
  asm volatile("ld.acquire.gpu.global.u32 %0, [%1];" : "=r"(v) : "l"(p) : "memory");
  return v;
}
__device__ __forceinline__ uint32_t wait_word(uint32_t p, uint32_t target) {
  uint32_t v;
  asm volatile("{\n.reg .pred p;\n.reg .u32 n;\nmov.u32 n, 0;\n"
               "LOOP:\nld.acquire.cta.shared.u32 %0, [%1];\nsetp.ge.u32 p, %0, %2;\n@p bra DONE;\n"
               "nanosleep.u32 %3;\nadd.u32 n, n, 1;\nsetp.lt.u32 p, n, 0x400000;\n@p bra LOOP;\ntrap;\n"
               "DONE:\n}\n" : "=r"(v) : "r"(p), "r"(target), "n"(400) : "memory");
  return v;
}
__device__ __forceinline__ void flag_set(unsigned int* p, uint32_t v) {
  asm volatile("st.release.gpu.global.u32 [%0], %1;" ::"l"(p), "r"(v) : "memory");
}
__device__ __forceinline__ void flag_dec(unsigned int* p) {
  asm volatile("red.relaxed.gpu.global.add.u32 [%0], 0xffffffff;" ::"l"(p) : "memory");
}

struct Cursor {
  uint32_t n;
  __device__ __forceinline__ uint32_t off() const { return n & (8 * NBAR - 8); }
  __device__ __forceinline__ uint32_t ph() const { return (n / (8 * NBAR)) & 1; }
  __device__ __forceinline__ void next() { n += 8; }
};

constexpr float kScaleLog2 = 0.07216878364870322f * 1.4426950408889634f;
constexpr float kSumLimit = 1048576.0f;

__global__ void __cluster_dims__(2, 1, 1) __launch_bounds__(384, 1)
fused_kernel(const __grid_constant__ Params P) {
  extern __shared__ uint8_t smem_raw[];
  const uint32_t sbase = (smem_u32(smem_raw) + 1023) & ~1023u;
  const uint32_t full0 = sbase + RING, empty0 = full0 + 8 * NBAR, odone0 = empty0 + 8 * NBAR, ev0 = odone0 + 8 * MAX_OPS;
  const uint32_t progress = ev0 + 8 * MAX_EV, jobw = progress + 4;
  const uint32_t rank = blockIdx.x & 1;
  const int role = blockIdx.x >> 1;
  const int wid = __shfl_sync(0xffffffffu, (int)(threadIdx.x >> 5), 0);
  const int wg = wid >> 2;

  if (wid < 8) {
    if (elect()) {
#pragma unroll
      for (int j = 0; j < 16; j++) {
        const int i = EARLY + 16 * wid + j;
        if (i < 2 * NBAR + MAX_OPS + MAX_EV) mbar_init(full0 + 8 * i, i < NBAR ? 1 : i < 2 * NBAR ? 16 : i < 2 * NBAR + MAX_OPS ? 8 : 1);
      }
      if (wid == 7) asm volatile("st.shared.v2.u32 [%0], {0, 0};\nfence.acq_rel.cta;" ::"r"(progress) : "memory");
      asm volatile("fence.mbarrier_init.release.cluster;" ::: "memory");
    }
  } else if (wid > 8) {
    const uint32_t g = blockIdx.x * 96 + threadIdx.x - 288, w = g - 2048;
    if (g < 4096) asm volatile("prefetch.global.L2 [%0];" ::"l"(g < 2048 ? P.xw[0] + g * (kD * 2) : P.xw[1] + (w >> 5) * (kHD * 2) + (w & 31) * 128));
  } else {
    const uint32_t op0 = P.first[role];
    if (elect()) {
#pragma unroll
      for (int k = 0; k < EARLY; k++) mbar_init(full0 + 8 * k, 1);
      asm volatile("fence.mbarrier_init.release.cluster;" ::: "memory");
      const int blk = (op0 >> 10) & 1;
      if ((op0 & 3) == OP_Q) {
#pragma unroll
        for (int k = 0; k < EARLY; k++) {
          mbar_expect(full0 + 8 * k, SZ_Q);
          tma2d(sbase + k * SZ_Q, &P.x[blk], full0 + 8 * k, 64 * k, ((op0 >> 7) & 7) * kSq + rank * 128);
          tma3d(sbase + k * SZ_Q + 16384, &P.wq[blk], full0 + 8 * k, 0, 64 * k, 3 * ((op0 >> 2) & 31));
          tma3d(sbase + k * SZ_Q + 28672, &P.wq[blk], full0 + 8 * k, 0, 64 * k + 32, 3 * ((op0 >> 2) & 31));
        }
      }
      asm volatile("prefetch.tensormap [%0];\nprefetch.tensormap [%1];" ::"l"(&P.k[blk]), "l"(&P.v[blk]) : "memory");
    }
  }
  __syncwarp();
  asm volatile("barrier.cluster.arrive.relaxed.aligned;\nbarrier.cluster.wait.aligned;" ::: "memory");

  if (wg < 2) {
    asm volatile("setmaxnreg.inc.sync.aligned.u32 240;");
    const uint32_t* prog = P.prog[role].c;
    const int wid = __shfl_sync(0xffffffffu, (int)(threadIdx.x >> 5), 1), wg = wid >> 2;
    const int lane = threadIdx.x & 31, warp = wid & 3;
    uint32_t empty_rem;
    asm volatile("mapa.shared::cluster.u32 %0, %1, %2;" : "=r"(empty_rem) : "r"(empty0), "r"(lane & 1));
    uint32_t keep = (threadIdx.x & 127) < 2 ? 4 : 0;
    auto release = [&](int slot) { mbar_arrive_cluster_n(keep, empty_rem + slot); };
    auto release_warp = [&](int slot, bool on = true) { mbar_arrive_cluster_if(lane < 2 && on, empty_rem + slot); };
    Cursor r{0};
    const uint32_t ring16 = (sbase & 0x3FFFF) >> 4;
    uint32_t cur = ring16;
    bool rdy0 = false, rdy1 = false;
    auto probe1 = [&]() { rdy0 = mbar_test(full0 + r.off(), r.ph()); };
    auto probe2 = [&]() {
      Cursor n = r;
      rdy0 = mbar_test(full0 + n.off(), n.ph());
      n.next();
      rdy1 = mbar_test(full0 + n.off(), n.ph());
    };
    auto advance = [&](uint32_t bytes, uint32_t& addr) {
      const int bi = r.off();
      r.next();
      if (cur > ring16 + ((RING - bytes) >> 4)) cur = ring16;
      addr = cur;
      cur += bytes >> 4;
      return bi;
    };
    auto take = [&](bool rdy, uint32_t bytes, uint32_t& addr) {
      if (__builtin_expect(!__all_sync(0xffffffffu, rdy), 0)) mbar_wait(full0 + r.off(), r.ph());
      return advance(bytes, addr);
    };
    const bool never = P.dbg == 0xffffffffu;
    uint32_t q[48];
#pragma unroll
    for (int i = 0; i < 48; i++) q[i] = 0;
    const int row = wg * 64 + warp * 16 + (lane >> 2);
    const int img0 = row * 4 + ((lane & 3) ^ ((row >> 1) & 3));
    uint4* pend = nullptr;
    bool pend_any = false;
    const uint64_t spol = evict_first();
    int pc = 0;
    uint32_t seen = 0;
    int sent = 0;
    auto slab = [&](int c, int i0) {
#pragma unroll
      for (int i = i0; i < 6; i++)
        stg2_if(c == i, pend + i * 512, q[8 * i], q[8 * i + 1], q[8 * i + 2], q[8 * i + 3],
                q[8 * i + 4], q[8 * i + 5], q[8 * i + 6], q[8 * i + 7], spol);
    };
    auto drain = [&](int c) {
      if (!pend_any || c >= 6) return;
      slab(c, 0);
      if (c == 5) {
        __syncwarp();
        mbar_arrive_if(lane == 0, odone0 - 8 + 8 * pc);
      }
    };

    for (;; pc++) {
      uint32_t op = prog[pc];
      const int type = op & 3;
      auto enter = [&]() {
        r.n = (op >> 12) & 248; cur = ring16 + (((op >> 20) & 63) << 8);
      };
      enter();
      pend_any = op & C_PEND;
      uint32_t job = 0;
      if ((op & (3 | C_WIDE)) == OP_O) job = seen ? seen : __shfl_sync(0xffffffffu, wait_word(jobw, 1), 0);
      if (type == OP_END || job == OP_O) {
#pragma unroll 1
        for (int c = sent; c < 6; c++) drain(c);
        asm volatile("barrier.cluster.arrive.relaxed;" ::: "memory");
        break;
      }
      {
        float s[32], o[96];
        uint32_t ad0;
        int bi0, sk1;
        uint32_t pa[16], pb[16];
        float mc0, mc1, l0, l1;
        bool shifted;
        uint32_t nop;
        auto expo = [&](float (&s)[32], uint32_t (&pout)[16], float& b0, float& b1, bool shift, auto mid) {
          float c0, c1;
#pragma unroll
          for (int i = 0; i < 8; i++) {
            const float e0 = ex2(shift ? s[4 * i] - mc0 : s[4 * i]), e1 = ex2(shift ? s[4 * i + 1] - mc0 : s[4 * i + 1]);
            const float e2 = ex2(shift ? s[4 * i + 2] - mc1 : s[4 * i + 2]), e3 = ex2(shift ? s[4 * i + 3] - mc1 : s[4 * i + 3]);
            if (i) { b0 += e0; c0 += e1; b1 += e2; c1 += e3; } else { b0 = e0; c0 = e1; b1 = e2; c1 = e3; }
            pout[2 * i] = pack_bf16(e0, e1); pout[2 * i + 1] = pack_bf16(e2, e3);
            if (i & 1) mid(i >> 1);
          }
          b0 += c0; b1 += c1;
        };
        auto rowmax = [&](float (&s)[32], float& m0, float& m1) {
          m0 = fmaxf(s[0], s[1]); m1 = fmaxf(s[2], s[3]);
#pragma unroll
          for (int i = 1; i < 8; i++) { m0 = fmaxf(m0, fmaxf(s[4 * i], s[4 * i + 1])); m1 = fmaxf(m1, fmaxf(s[4 * i + 2], s[4 * i + 3])); }
          m0 = fmaxf(m0, __shfl_xor_sync(0xffffffffu, m0, 1)); m1 = fmaxf(m1, __shfl_xor_sync(0xffffffffu, m1, 1));
          m0 = fmaxf(m0, __shfl_xor_sync(0xffffffffu, m0, 2)); m1 = fmaxf(m1, __shfl_xor_sync(0xffffffffu, m1, 2));
        };
        auto first = [&](float (&s)[32], int sk0, auto mid) {
          fence_regs(s);
          release(sk0);
          mc0 = 0.f; mc1 = 0.f;
          expo(s, pa, l0, l1, false, mid);
          shifted = __any_sync(0xffffffffu, !(fmaxf(l0, l1) <= kSumLimit && fminf(l0, l1) >= 1.f / kSumLimit));
          if (shifted) {
            rowmax(s, mc0, mc1);
            expo(s, pa, l0, l1, true, [](int) {});
          }
        };
        auto qk = [&](float (&s)[32], uint32_t ak, int k0 = 0, int k1 = 12) {
#pragma unroll
          for (int kk = k0; kk < k1; kk++)
            wgmma_rs_n64<0>(s, q[4 * kk], q[4 * kk + 1], q[4 * kk + 2], q[4 * kk + 3], mk_desc(ak, 16, KV_SBO, 1) + ((kk >> 2) * KV_CH + (kk & 3) * 2), kk != 0);
          if (k1 == 12) wg_commit();
        };
        auto pv = [&](uint32_t (&pin)[16], uint32_t av, int acc, int k0 = 0, int k1 = 4) {
#pragma unroll
          for (int kk = k0; kk < k1; kk++)
            wgmma_rs_n192<1>(o, pin[4 * kk], pin[4 * kk + 1], pin[4 * kk + 2], pin[4 * kk + 3], mk_desc(av, KV_CH * 16, KV_SBO, 1) + (kk * (KV_SBO / 8)), acc || (kk != 0));
          if (k0 == 0) wg_commit();
        };
        auto finish = [&](uint32_t (&pout)[16], int sk, int sv, bool part = false) {
          probe1();
          wg_wait<1>();
          fence_regs(s);
          release(sk);
          float b0, b1;
#pragma unroll 1
          for (bool redo = false;; redo = true) {
            expo(s, pout, b0, b1, false, [](int) {});
            if (!__any_sync(0xffffffffu, !redo && (shifted || !(fmaxf(b0, b1) <= kSumLimit)))) break;
            shifted = true;
            rowmax(s, b0, b1);
            b0 = fmaxf(mc0, b0); b1 = fmaxf(mc1, b1);
            const float a0 = ex2(mc0 - b0), a1 = ex2(mc1 - b1);
            mc0 = b0; mc1 = b1;
            l0 *= a0; l1 *= a1;
            wg_wait<0>();
            fence_regs(o);
#pragma unroll
            for (int i = 0; i < 24; i++) { o[4 * i] *= a0; o[4 * i + 1] *= a0; o[4 * i + 2] *= a1; o[4 * i + 3] *= a1; }
#pragma unroll
            for (int i = 0; i < 32; i++) s[i] -= (i & 2) ? mc1 : mc0;
            if (part) {
#pragma unroll
              for (int i = 8; i < 16; i++)
                pa[i] = pack_bf16(__uint_as_float(pa[i] << 16) * ((i & 1) ? a1 : a0), __uint_as_float(pa[i] & 0xffff0000u) * ((i & 1) ? a1 : a0));
            }
          }
          l0 += b0; l1 += b1;
          wg_wait<0>();
          fence_regs(o);
          mbar_arrive_cluster_n(part ? 0 : keep, empty_rem + sv);
        };
        uint32_t pav;
        int psv;
        auto step = [&](uint32_t (&pin)[16], uint32_t (&pout)[16], bool part) {
          uint32_t ak;
          const int sk = take(rdy0, SZ_KV, ak);
          psv = advance(SZ_KV, pav);
          wg_fence();
          qk(s, ak);
          if (part) { wg_fence(); pv(pin, pav, 1, 0, 2); } else { asm volatile(""); wg_fence(); pv(pin, pav, 1); }
          finish(pout, sk, psv, part);
        };
        auto unpark = [&](uint32_t& ak) {
          uint32_t ad;
          const Cursor k0 = r;
          const int sk0 = advance(SZ_KV, ak), bi = take(false, SZ_PARK, ad);
#pragma unroll
          for (int i = 0; i < 12; i++) lds128(sbase + (ad - ring16 + img0) * 16 + (i >> 1) * 8192 + (i & 1) * 512, q[4 * i], q[4 * i + 1], q[4 * i + 2], q[4 * i + 3]);
          if (!__all_sync(0xffffffffu, rdy0)) mbar_wait(full0 + k0.off(), k0.ph());
          fence_regs(q);
          release_warp(bi);
          wg_fence();
          qk(s, ak, 0, 4);
          wg_commit();
          return sk0;
        };
        auto mma4 = [&](uint32_t ad, int acc) {
#pragma unroll
          for (int kk = 0; kk < 4; kk++)
            wgmma_ss_n192<1>(o, mk_desc(ad + wg * 512, 16, 1024, 1) + (kk * 2), mk_desc(ad, 4096, 1024, 1) + (1024 + (kk >> 1) * 768 + (kk & 1) * 128), acc || kk != 0);
        };
        auto convert = [&](int i0, int i1) {
          sched_fence(keep, never);
#pragma unroll
          for (int i = i0; i < i1; i++) {
            q[i] = pack_bf16(o[2 * i] * kScaleLog2, o[2 * i + 1] * kScaleLog2);
            if ((i & 7) == 7 && i != i1 - 1) sched_fence(keep, never);
          }
          sched_fence(keep, never);
        };
        if (type == OP_O) {
          int prev = 0;
          if (op & C_WIDE) {
            float d[64];
            auto mma3 = [&](uint32_t ad, int h, int acc) {
#pragma unroll
              for (int kk = 0; kk < 2; kk++)
                wgmma_ss_n192<1>(o, mk_desc(ad + wg * 256, 16, 512, 2) + (h * 512 + kk * 2), mk_desc(ad, 4096, 1024, 1) + (1024 + h * 768 + kk * 128), acc || kk);
            };
            auto mma2 = [&](uint32_t ad, uint32_t ob, int h, int acc) {
#pragma unroll
              for (int kk = 0; kk < 2; kk++)
                wgmma_ss_n128<1>(d, mk_desc(ad + wg * 256, 16, 512, 2) + (h * 512 + kk * 2), mk_desc(ad, 4096, 1024, 1) + (ob + h * 512 + kk * 128), acc || kk);
            };
            auto wstep = [&](uint32_t bytes, int acc, auto hook) {
              uint32_t ad;
              const int bi = take(rdy0, bytes, ad);
              wg_fence();
              if (bytes == SZ_W2) mma2(ad, 1024, 0, 1); else mma3(ad, 0, acc);
              if (bytes == SZ_W) mma3(ad, 1, 1);
              wg_commit();
              if (acc) { wg_wait<1>(); release(prev); }
              if (bytes == SZ_W) mma2(ad, 2560, 0, acc);
              if (bytes == SZ_W3) mma3(ad, 1, 1); else mma2(ad, bytes == SZ_W ? 2560 : 1024, 1, 1);
              wg_commit();
              prev = bi;
              hook();
              probe1();
              wg_wait<1>();
            };
            undefine(o);
            wstep(SZ_W, 0, [&]() { drain(0); });
#pragma unroll 1
            for (int k = 1; k < ((op >> 2) & 127) - TAIL; k++) wstep(SZ_W, 1, [&]() { drain(k); });
#pragma unroll 1
            for (int k = 0; k < TAIL; k++) wstep(SZ_W2, 1, []() {});
            pend = ptr_add(P.g->part, (((op >> 9) & 31) * 2 + rank) * 81920 + 4 * 8192 + img0 * 16);
            wstep(SZ_W3, 1, [&]() {
              fence_regs(d);
#pragma unroll
              for (int i = 0; i < 32; i++) q[16 + i] = pack_bf16(d[2 * i], d[2 * i + 1]);
              slab(2, 2);
            });
#pragma unroll 1
            for (int k = 3; k < 6; k++) wstep(SZ_W3, 1, [&]() { slab(k, 2); });
            op = prog[pc + 1];
            enter();
            pend_any = true;
            pend -= 4 * 512;
            bi0 = take(rdy0 || (op & 3) != OP_Q, SZ_Q, ad0);
            sched_fence(keep, never);
            wg_wait<0>();
            fence_regs(o);
            release(prev);
#pragma unroll
            for (int i = 0; i < 48; i++) q[i] = pack_bf16(o[2 * i], o[2 * i + 1]);
            if ((op & 3) != OP_Q) continue;
            pc++;
            goto first_step;
          }
          float c[80];
          auto mma2 = [&](uint32_t ad, uint32_t oa, uint32_t ob, int acc) {
            wgmma_ss_n160<1>(c, mk_desc(ad + wg * 256, 16, 512, 2) + (oa), mk_desc(ad, 2048, 512, 2) + (1024 + ob), acc);
            wgmma_ss_n160<1>(c, mk_desc(ad + wg * 256, 16, 512, 2) + (oa + 2), mk_desc(ad, 2048, 512, 2) + (1024 + ob + 64), 1);
          };
          auto kstep = [&](int acc, auto hook, uint32_t bytes = SZ_O) {
            uint32_t ad;
            const int bi = take(rdy0, bytes, ad);
            wg_fence();
            mma2(ad, 0, 0, acc);
            wg_commit();
            if (acc) wg_wait<1>();
            if (acc == 1) release(prev);
            if (acc > 1) release_warp(prev, acc == 2 || wg == 0);
            mma2(ad, 512, 640, 1);
            wg_commit();
            prev = bi;
            hook();
            probe1();
            wg_wait<1>();
          };
          auto unblock = [&](int k) {
            if (__all_sync(0xffffffffu, rdy0) || __all_sync(0xffffffffu, mbar_try(full0 + r.off(), r.ph(), 1500))) return;
#pragma unroll 1
            for (; k < 6; k++) drain(k);
            pend_any = false;
          };
          unblock(sent);
          kstep(0, [&]() { drain(sent); });
          int left = ((job >> 13) & 127) - 6;
#pragma unroll 1
          for (uint32_t k = sent + 1, pace = left >= 22 ? 0x4511 : left <= 11 ? 0x1a : 0x155; left > 0; pace >>= 2, left--) {
            unblock(k);
            kstep(1, [&]() {
#pragma unroll 1
              for (int i = pace & 3; i > 0; i--) drain(k++);
            });
          }
          uint32_t t[8], stage[3];
          float u[80];
          auto unpack = [&](int j) {
#pragma unroll
            for (int i = 0; i < 8; i++) {
              u[16 * j + 2 * i] = __uint_as_float(t[i] << 16); u[16 * j + 2 * i + 1] = __uint_as_float(t[i] & 0xffff0000u);
              asm volatile("" : "+f"(u[16 * j + 2 * i]), "+f"(u[16 * j + 2 * i + 1]));
            }
          };
#pragma unroll
          for (int i = 0; i < 8; i++) t[i] = 0;
          const uint32_t bytes = (job & P_LD) ? SZ_OL : SZ_O;
#pragma unroll
          for (int j = 0; j < 5; j++) {
            if (j == 2 && wg == 1) {
              wg_wait<0>();
              release_warp(prev);
              bar_sync(1, 256);
            }
            kstep(j == 2 ? 3 : 2, [&]() {
              if (j == 4) asm volatile("{\n.reg .pred p;\nsetp.eq.u32 p, %0, 0;\n@p bar.arrive 1, 256;\n}\n" ::"r"(wg) : "memory");
              if (j) unpack(j - 1);
              lds2_if(job & P_LD, sbase + (cur - ring16 + img0) * 16 - 8192, t);
              if (j >= 1 && j <= 3) stage[j - 1] = sbase + (cur - ring16) * 16 - bytes + wid * 1024;
            }, bytes);
          }
          unpack(4);
          uint32_t lane16 = (lane & 15) * 64;
          const int orow = ((job >> 7) & 7) * kSq + rank * 128 + wid * 16, ocol = ((job >> 10) & 1) * 20 + ((job >> 20) & 3) * 5;
          sched_fence(lane16, never);
          wg_wait<0>();
          fence_regs(c);
          release_warp(prev);
          asm volatile("barrier.cluster.arrive.relaxed;" ::: "memory");
#pragma unroll
          for (int i = 0; i < 10; i++) {
            const int v = (i & 1) * 2 + (lane >> 4);
            const uint32_t sa = stage[i >> 2] + (i & 2) * 4096;
            stsm4(sa + lane16 + ((v ^ ((lane >> 1) & 3)) << 4), pack_bf16(c[8 * i] + u[8 * i], c[8 * i + 1] + u[8 * i + 1]),
                  pack_bf16(c[8 * i + 2] + u[8 * i + 2], c[8 * i + 3] + u[8 * i + 3]), pack_bf16(c[8 * i + 4] + u[8 * i + 4], c[8 * i + 5] + u[8 * i + 5]),
                  pack_bf16(c[8 * i + 6] + u[8 * i + 6], c[8 * i + 7] + u[8 * i + 7]));
            if (i != 3 && i != 9) continue;
            asm volatile("fence.proxy.async.shared::cta;" ::: "memory");
            __syncwarp();
            if (elect()) {
#pragma unroll
              for (int j = i == 3 ? 0 : 2; 2 * j < i; j++) tma3d_store(&P.out, stage[j >> 1] + (j & 1) * 8192, 0, orow, ocol + j);
            }
            if (i == 3) sched_fence(lane16, never);
          }
          if (elect()) asm volatile("cp.async.bulk.commit_group;\ncp.async.bulk.wait_group.read 0;" ::: "memory");
          __syncwarp();
          break;
        }
        bi0 = take(rdy0, SZ_Q, ad0);
      first_step:
        undefine(o);
        wg_fence();
        mma4(ad0, 0);
        wg_commit();
        {
          uint32_t ad1;
          const int bi1 = take(false, SZ_Q, ad1);
          wg_fence();
          mma4(ad1, 1);
          wg_commit();
          drain(0);
          wg_wait<1>();
          release(bi0);
          drain(1);
          probe1();
          wg_wait<0>();
          release(bi1);
          fence_regs(o);
#pragma unroll 1
          for (int k = 2; k < 8; k++) {
            uint32_t ad;
            const int bi = take(rdy0, SZ_Q, ad);
            wg_fence();
            mma4(ad, 1);
            wg_commit();
            drain((0x54732710u >> (4 * k)) & 7);
            probe1();
            wg_wait<0>();
            release(bi);
          }
          uint32_t a8, a9, ak0, ak1;
          const int b8 = take(rdy0, SZ_Q, a8), b9 = take(false, SZ_Q, a9);
          wg_fence();
          mma4(a8, 1);
          wg_commit();
          mma4(a9, 1);
          wg_commit();
          wg_wait<1>();
          release(b8);
          probe1();
          const int sk0 = take(rdy0 || (op & F_PARK), SZ_KV, ak0);
          wg_wait<0>();
          fence_regs(o);
          release(b9);
          float s0[32];
          convert(0, 32);
          if (op & F_PARK) {
            convert(32, 48);
            pend = ptr_add(P.g->tile, (((op >> 2) & 511) * 2 + rank) * SZ_PARK + img0 * 16);
            continue;
          }
          pc++;
          wg_fence();
          qk(s0, ak0, 0, 4);
          convert(32, 48);
          wg_fence();
          qk(s0, ak0, 4, 12);
          sk1 = take(false, SZ_KV, ak1);
          wg_fence();
          qk(s, ak1, 0, 4);
          wg_commit();
          probe1();
          wg_wait<1>();
          first(s0, sk0, [&](int i) {
            if (!(i & 1)) return;
            sched_fence(keep, never);
            wg_fence();
            if (i == 1) qk(s, ak1, 4, 8);
            if (i == 3) qk(s, ak1, 8, 12);
            sched_fence(keep, never);
          });
        }
        for (;;) {
          {
            uint32_t av;
            const int sv = take(rdy0, SZ_KV, av);
            undefine(o);
            wg_fence();
            pv(pa, av, 0);
            finish(pb, sk1, sv);
          }
          nop = prog[pc + 1];
#pragma unroll 1
          for (int jj = 0; jj < 7; jj++) {
            step(pb, pa, false);
            step(pa, pb, jj == 6);
          }
          float i0, i1;
          auto last = [&]() {
            uint32_t av;
            const int sv = take(rdy0, SZ_KV, av);
            wg_fence();
            pv(pa, pav, 1, 2, 4);
            pv(pb, av, 1);
            sched_fence(keep, never);
            probe1();
            l0 += __shfl_xor_sync(0xffffffffu, l0, 1); l1 += __shfl_xor_sync(0xffffffffu, l1, 1);
            l0 += __shfl_xor_sync(0xffffffffu, l0, 2); l1 += __shfl_xor_sync(0xffffffffu, l1, 2);
            i0 = rcp(l0); i1 = rcp(l1);
            pend = ptr_add(P.g->tile, (((op >> 2) & 511) * 2 + rank) * SZ_PARK + img0 * 16);
            return sv;
          };
          auto normalise = [&](uint32_t (&d)[48], auto mid) {
#pragma unroll
            for (int i = 0; i < 24; i++) {
              d[8 * (i >> 2) + (i & 3)] = pack_bf16(o[4 * i] * i0, o[4 * i + 1] * i0);
              d[8 * (i >> 2) + (i & 3) + 4] = pack_bf16(o[4 * i + 2] * i1, o[4 * i + 3] * i1);
              if ((i & 1) && i != 23) sched_fence(keep, never);
              if ((i & 3) == 3 && i != 23) mid(i >> 2);
            }
          };
          const int sv = last();
          if ((nop & 3) != OP_A) {
            op = nop;
            enter();
            pend_any = true;
            bi0 = take(rdy0 || (nop & 3) != OP_Q, SZ_Q, ad0);
            seen = __shfl_sync(0xffffffffu, lds32(jobw), 0);
            sched_fence(keep, never);
            wg_wait<0>();
            fence_regs(o);
            release(psv);
            release(sv);
            const bool rush = (nop & (3 | C_WIDE)) == OP_O && seen && ((seen >> 13) & 127) <= 20;
            sent = rush ? 3 : 0;
            normalise(q, [&](int i) {
              if (i < 3) stg2_if(rush, pend + i * 512, q[8 * i], q[8 * i + 1], q[8 * i + 2], q[8 * i + 3], q[8 * i + 4], q[8 * i + 5], q[8 * i + 6], q[8 * i + 7], spol);
            });
            undefine(o);
            if ((nop & 3) != OP_Q) break;
            pc++;
            goto first_step;
          }
          uint32_t ak0;
          const int sk0 = unpark(ak0);
          wg_wait<1>();
          fence_regs(o);
          release(psv);
          release(sv);
          uint32_t t[48];
          auto st = [&](int i) {
            stg2_if(true, pend + i * 512, t[8 * i], t[8 * i + 1], t[8 * i + 2], t[8 * i + 3], t[8 * i + 4], t[8 * i + 5], t[8 * i + 6], t[8 * i + 7], spol);
          };
          normalise(t, [&](int i) {
            if (i & 1) {
              wg_fence();
              if (i == 1) qk(s, ak0, 4, 8);
              if (i == 3) qk(s, ak0, 8, 12);
              sched_fence(keep, never);
            }
            if (!(i & 1)) st(i >> 1);
          });
          probe2();
          wg_wait<0>();
          first(s, sk0, [&](int i) { if (i < 3) { sched_fence(keep, never); st(3 + i); } });
          __syncwarp();
          mbar_arrive_if(lane == 0, odone0 + 8 * pc);
          pc++;
          op = nop;
          uint32_t ak1;
          sk1 = take(rdy0, SZ_KV, ak1);
          rdy0 = rdy1;
          wg_fence();
          qk(s, ak1);
        }
      }
    }
    asm volatile("barrier.cluster.wait;" ::: "memory");
  } else {
    asm volatile("setmaxnreg.dec.sync.aligned.u32 24;");
    const uint32_t* prog = P.prog[role].p;
    unsigned int* flag = P.g->flag + rank;
    if (wid == 11 && (prog[0] & 3) == OP_Q) {
      const uint32_t a = prog[1];
      const char* p = ptr_add(P.kv[rank * 2 + ((a >> 10) & 1)], ((a >> 2) & 255) * (kSk * kDh * 2) + (threadIdx.x & 31) * 128);
#pragma unroll 1
      for (uint32_t k = 0; k < 3; k++) {
        wait_word(progress, 8 * k);
        p += SZ_KV;
        asm volatile("prefetch.global.L2 [%0];\nprefetch.global.L2 [%0 + 4096];" ::"l"(p));
      }
      __syncwarp();
    }
    if (wid == 8) {
      Cursor head{0}, tail{0};
      int sh = 0, room = RING >> 12;
      uint32_t cur = 0;
      uint64_t fifo = 0;
      uint32_t dst, bar = 0, ev = ev0;
      const uint64_t pol = evict_first();
      auto retire = [&]() {
        mbar_wait(empty0 + tail.off(), tail.ph());
        tail.next();
        room += (uint32_t)fifo & 31;
        fifo >>= 5;
        sh -= 5;
        asm volatile("st.volatile.shared.u32 [%0], %1;" ::"r"(progress), "r"(tail.n) : "memory");
      };
      auto acquire = [&](uint32_t bytes) {
        uint32_t fp = bytes >> 12;
        if (cur + fp > (RING >> 12)) { fp += (RING >> 12) - cur; cur = 0; }
        room -= fp;
        while (room < 0) retire();
        fifo |= (uint64_t)fp << sh;
        sh += 5;
        dst = sbase + (cur << 12);
        bar = full0 + head.off();
        cur += bytes >> 12;
        head.next();
      };
      auto gate = [&]() {
        mbar_wait(ev, 0);
        ev += 8;
        asm volatile("fence.proxy.async.global;" ::: "memory");
      };
      for (int pc = 0;; pc++) {
        uint32_t op = prog[pc];
        const int type = op & 3;
        if (type == OP_END) break;
        if (op == OP_O) {
          gate();
          op = __shfl_sync(0xffffffffu, lds32(jobw), 0);
        }
        const int blk = (op >> 10) & 1;
        if (type == OP_Q) {
          const uint64_t px = (op & P_LASTX) ? pol : no_hint(), pw = (op & P_LASTW) ? pol : no_hint();
          int k = 0;
          if (pc == 0) {
            k = 64 * EARLY; head.n = 8 * EARLY; sh = 5 * EARLY; cur = EARLY * (SZ_Q >> 12); room -= cur;
            fifo = (SZ_Q >> 12) * (((1u << (5 * EARLY)) - 1) / 31);
          }
#pragma unroll 1
          for (int stop = (op & P_GATE) ? kD - 64 : kD;; stop = kD) {
#pragma unroll 1
            for (; k < stop; k += 64) {
              acquire(SZ_Q);
              if (elect()) {
                mbar_expect(bar, SZ_Q);
                tma3d_mc_hint(dst + 16384 + rank * 12288, &P.wq[blk], bar, k + 32 * rank, 3 * ((op >> 2) & 31), pw);
                tma2d_hint(dst, &P.x[blk], bar, k, ((op >> 7) & 7) * kSq + rank * 128, px);
              }
            }
            if (k == kD) break;
            gate();
          }
        } else if (type == OP_A) {
          const int row0 = ((op >> 2) & 255) * kSk;
          auto kv = [&](uint32_t tx, const CUtensorMap* m, int c3) {
            const uint32_t before = bar;
            acquire(SZ_KV);
            if (elect()) {
              mbar_expect(bar, tx);
              tma4d_mc_hint(dst + rank * (SZ_KV / 2), m, tx ? bar : before, c3, pol);
            }
          };
          int c3 = row0 / 8 + 4 * rank;
#pragma unroll 1
          for (int j = 0; j <= 16; j++, c3 += 8) {
            const uint32_t tv = j < 2 || j == 16 ? SZ_KV : 0;
            if (j < 16) kv(2 * SZ_KV - tv, &P.k[blk], c3);
            else if (op & P_GATE) gate();
            if (j > 0) kv(tv, &P.v[blk], c3 - 8);
            else if (op & F_PARK) {
              gate();
              acquire(SZ_PARK);
              if (elect()) {
                mbar_expect(bar, SZ_PARK);
                bulk_load_hint(dst, &P.g->tile[(((op >> 20) & 511) * 2 + rank) * 3072], SZ_PARK, bar, pol);
              }
            }
          }
        } else {
          const uint4* part = &P.g->part[((((op >> 6) & 30) + ((op >> 21) & 1)) * 2 + rank) * 5120 + ((op >> 20) & 1) * 2560];
          auto run = [&](const uint32_t bytes, int k, int cnt, int gates) {
            const int col = bytes == SZ_O || bytes == SZ_OL ? 5 * ((op >> 20) & 3) : 5 * ((op >> 21) & 1);
            int row = 8 * k + 4 * rank, pre = bytes == SZ_O && (op & P_PRE) ? 0 : 2560;
#pragma unroll 1
            for (int h = (k * 43) >> 7, k0 = k - 3 * h; cnt > 0; h++, k0 = 0, gates = gates >> 1 | (gates & 2)) {
              const uint4* src = ptr_add(P.g->tile, ((P.slot[((op >> 2) & 480) + h] * 2 + rank) * 3 + k0) * 16384);
              const uint64_t pw = h >= ((op >> 23) & 31) && h < 2 * (op >> 28) ? pol : no_hint();
              if (gates & 1) gate();
              int m = min(3 - k0, cnt);
              cnt -= m;
#pragma unroll 1
              for (; m > 0; m--, src += 1024, row += 8) {
                acquire(bytes);
                if (elect()) {
                  mbar_expect(bar, bytes);
                  if (bytes == SZ_O || bytes == SZ_OL) tma5d_mc_hint(dst + 16384 + rank * 10240, &P.wo[blk], bar, row, col, no_hint());
                  if (bytes == SZ_W || bytes == SZ_W3) tma5d_mc_hint(dst + 16384 + rank * 12288, &P.wo3[blk], bar, row, col, pw);
                  bulk_load_hint(dst, src, 16384, bar, pol);
                  if (bytes == SZ_W || bytes == SZ_W2) tma5d_mc_hint(dst + bytes - 16384 + rank * 8192, &P.wo2[blk], bar, row, col + 3, pw);
                  if (bytes == SZ_OL) bulk_load_hint(dst + SZ_O, part, 8192, bar, pol);
                }
                if (bytes == SZ_OL) part += 512;
              }
              if (pre < 2560) {
                if (elect()) asm volatile("cp.async.bulk.prefetch.L2.global [%0], 10240;" ::"l"(part + pre) : "memory");
                pre += 640;
              }
            }
          };
          const int n = (op >> 13) & 127;
          if (op & P_WIDE) {
            run(SZ_W, 0, n - TAIL, 3);
            run(SZ_W2, n - TAIL, TAIL, (n - TAIL) % 3 ? 2 : 3);
            run(SZ_W3, n - TAIL, TAIL, 0);
          } else {
            if (op & P_PRE) gate();
            run(SZ_O, kSteps - n, (op & P_LD) ? n - 5 : n, 3);
            if (op & P_LD) {
              if (!(op & P_PRE)) gate();
              run(SZ_OL, kSteps - 5, 5, 2);
            }
          }
        }
      }
#pragma unroll 1
      while (sh) retire();
    } else if (threadIdx.x == 288) {
      for (int pc = 0;; pc++) {
        const uint32_t op = prog[pc];
        const int type = op & 3;
        if (type == OP_END) break;
        if (type == OP_Q ? !(op & F_PARK) : type == OP_O && !(op & P_WIDE)) continue;
        const int id = type == OP_A ? (op >> 2) & 511 : type == OP_Q ? N_TILE + ((op >> 13) & 127) : ID_PART + ((op >> 5) & 60) + ((op >> 20) & 3);
        const uint32_t v = type == OP_O ? 1 : P.info[id] & 7;
        mbar_wait_long(odone0 + 8 * pc);
        flag_set(flag + 2 * id, v);
        if (type == OP_O && (op & P_WIDE)) flag_set(flag + 2 * id + 2, v);
      }
    } else if (wid == 10) {
      int i = threadIdx.x & 31;
      const int n_ev = P.prog[role].n_ev;
      auto event = [&]() { return i < n_ev ? P.prog[role].ev[i] : n_ev ? E_JOB | (i - n_ev) : 0; };
      uint32_t e = i < 8 ? event() : 0;
      for (uint32_t n = 0; __any_sync(0xffffffffu, e); n++) {
        uint32_t job = lds32(jobw);
        const int togo = (e & E_DRAW) ? (e & 1023) - (lds32(progress) >> 3) : 99;
        if (togo <= 0 && rank == 0) {
          job = P.job[atomicInc(&P.g->ticket, gridDim.x / 2 - 1)];
          asm volatile("{\n.reg .u32 a;\nmapa.shared::cluster.u32 a, %0, 1;\nst.volatile.shared::cluster.u32 [a], %1;\n"
                       "st.volatile.shared.u32 [%0], %1;\n}\n" ::"r"(jobw), "r"(job) : "memory");
        }
        if ((e & E_JOB) && job) {
          const uint32_t j = e & 63, heads = job == OP_O ? 0 : kH - ((job >> 2) & 31), jp = !(job & P_LD) ? 63 : (job & P_PRE) ? 0 : heads - 1, h = j - (j > jp);
          e = j == jp ? (ID_PART + ((job >> 5) & 60) + ((job >> 20) & 3)) | E_ON | E_LAST : h < heads ? (((job >> 2) & 511) + h) | E_ON | E_LAST : 0;
        }
        unsigned int* f = ptr_add(flag, 8 * (e & 1023));
        const bool ok = (e & E_ON) ? flag_get(f) - 1 < ((e & E_FREE) ? 1 : 7) : (e & E_DRAW) && job;
        if (ok) {
          mbar_arrive(ev0 + 8 * i);
          if (e & (E_FREE | E_LAST)) flag_dec(f);
          i += 8;
          e = event();
        }
        asm volatile("{\n.reg .pred p;\nsetp.ge.u32 p, %0, 0x400000;\n@p trap;\n}\n" ::"r"(n));
        if (!__any_sync(0xffffffffu, ok)) __nanosleep(__any_sync(0xffffffffu, job || togo <= 2) ? 100 : 600);
      }
    } else if (threadIdx.x == 352) {
      uint32_t items = 0;
      auto read = [&](int id) {
        if (!(P.info[id] & I_NEXT)) return;
        wait_word(progress, 8 * items);
        flag_dec(flag + 2 * id);
      };
      for (int pc = 0;; pc++) {
        const uint32_t op = prog[pc];
        const int type = op & 3;
        if (type == OP_END) break;
        if (type == OP_O) {
          const uint32_t n = (op >> 13) & 127, base = items;
#pragma unroll 1
          for (uint32_t k = 3, id = (op >> 2) & 511; k <= n; k += 3, id++) {
            items = base + k + (k + TAIL > n ? TAIL : 0);
            read(id);
          }
          items = base + n + TAIL;
        } else if (type == OP_A) {
          items++;
          if (op & F_PARK) { items++; read(N_TILE + ((op >> 13) & 127)); }
          items += 31;
        } else {
          items += 10;
        }
      }
    }
    __syncwarp();
    asm volatile("barrier.cluster.arrive.relaxed;\nbarrier.cluster.wait;" ::: "memory");
  }
}

typedef CUresult (*EncodeFn)(CUtensorMap*, CUtensorMapDataType, cuuint32_t, void*, const cuuint64_t*, const cuuint64_t*,
                             const cuuint32_t*, const cuuint32_t*, CUtensorMapInterleave, CUtensorMapSwizzle,
                             CUtensorMapL2promotion, CUtensorMapFloatOOBfill);

void encode(EncodeFn fn, CUtensorMap* m, const void* ptr, int rank, const cuuint64_t* dims, const cuuint64_t* strides,
            const cuuint32_t* box, CUtensorMapSwizzle swz) {
  const cuuint32_t es[5] = {1, 1, 1, 1, 1};
  CUresult r = fn(m, CU_TENSOR_MAP_DATA_TYPE_BFLOAT16, rank, const_cast<void*>(ptr), dims, strides, box, es,
                  CU_TENSOR_MAP_INTERLEAVE_NONE, swz, CU_TENSOR_MAP_L2_PROMOTION_L2_128B, CU_TENSOR_MAP_FLOAT_OOB_FILL_NONE);
  if (r != CUDA_SUCCESS) fprintf(stderr, "cuTensorMapEncodeTiled failed: %d\n", (int)r);
}

struct Op { int type, flags, id, n, quarter, park, item0, items; double t0, t1; };
struct Use { double need, freed; int readers, slot, prev; bool next; };
struct PlanStats { double end, slack, park_slack; int slots, parks; uint32_t own[N_CL]; };

bool plan(const char* const* text, int n_pair, int phase, Params& P, PlanStats* stats = nullptr) {
  constexpr double T_Q = 7900, T_A = 24550, T_U = 25900, T_P = 8400, T_O = 640, T_RUN = 800, T_WIDE = 1300, AHEAD = 3500, PUBLISH = 1500;
  const double margin = 256.0 * ((P.dbg >> 8) & 255);
  static Op op[N_CL][MAX_OPS];
  static Use use[ID_PART];
  int n_op[N_CL], covered[2 * N_TEAM] = {};
  struct Ref { double t; Op* o; int id; };
  static Ref att[N_TILE + 1], dem[N_TILE], prk[MAX_PARK + 1], unp[MAX_PARK + 1], wr[ID_PART];
  auto sort = [](Ref* r, int n) {
    for (int i = 1; i < n; i++)
      for (int j = i; j > 0 && r[j].t < r[j - 1].t; j--) { Ref x = r[j]; r[j] = r[j - 1]; r[j - 1] = x; }
  };
  auto hex = [](char c) { return c <= '9' ? c - '0' : c - 'a' + 10; };
  for (int i = 0; i < n_pair; i++)
    for (const char* s = text[i]; *s; s++)
      for (int h = 0; *s == 'J' && h < 2; h++) {
        if (covered[2 * hex(s[1]) + h]) return false;
        covered[2 * hex(s[1]) + h] = 10 * (s[2 + 2 * h] - '0') + s[3 + 2 * h] - '0';
      }
  for (int c = 0; c < 2 * n_pair; c++) {
    int n = 0, items = 0;
    double t = 0;
    auto add = [&](int type, int flags, int id, int heads, int quarter, int its, double dt) {
      if (n < MAX_OPS) op[c][n] = {type, flags, id, heads, quarter, 0, items, its, t, t + dt};
      n++; items += its; t += dt;
    };
    for (const char* s = text[c >> 1]; *s; s++) {
      const int tm = hex(s[1]) & 15, nj = covered[2 * tm + (c & 1)];
      if (*s == 'N') { add(OP_Q, 0, 0, 0, 0, 10, T_Q); add(OP_A, 0, 0, 0, 0, 32, T_A); }
      if (*s == 'P') add(OP_Q, F_PARK, 0, 0, 0, 10, T_P);
      if (*s == '+' || *s == '-') t += *s == '+' ? 1000 : -1000;
      if (*s == 'U') { if (n == 0 || n > MAX_OPS || op[c][n - 1].type != OP_A) return false; add(OP_A, F_PARK, 0, 0, 0, 33, T_U); }
      if (*s == 'J') { if (nj < TAIL + 6 || nj > kSteps - 11) return false; add(OP_O, P_WIDE, tm * kH, nj, 2 * (c & 1), nj + TAIL, 2 * T_O * nj + T_WIDE); }
    }
    add(OP_O, 0, 0, 0, 0, 0, 0);
    add(OP_END, 0, 0, 0, 0, 0, 0);
    if (n > MAX_OPS || op[c][0].type != OP_Q) return false;
    n_op[c] = n - 1;
    att[c] = {t, &op[c][n - 2], 0};
  }
  for (int i = 0; i < 4 * N_TEAM; i++) dem[i] = {(double)covered[i / 2], nullptr, i};
  sort(att, 2 * n_pair); sort(dem, 4 * N_TEAM);
  for (int i = 0; i < 4 * N_TEAM; i++) {
    Op* f = att[i].o;
    const int nj = covered[dem[i].id / 2];
    f->flags = nj ? P_LD : 0;
    f->id = dem[i].id / 4 * kH + nj / 3; f->quarter = dem[i].id & 3; f->items = f->n = kSteps - nj;
    f[1].t0 = f[1].t1 = f->t1 = f->t0 + T_O * f->n + T_RUN; f[1].item0 += f->n;
  }
  for (int i = 0; i < ID_PART; i++) use[i] = {1e18, 0, 0, 0, 0, false};
  int n_att = 0, n_prk = 0, n_unp = 0;
  auto ready = [&](const Op* o) {
    const int nt = o[1].type;
    return o->t1 + (nt == OP_Q ? 6100 : !o[1].n ? 1500 : (o[1].flags & P_WIDE) ? 7700 : (P.dbg & 1) ? (o[1].n <= 20 ? 1700 : o[1].n < 28 ? 3900 : 5800) : 3900) + PUBLISH;
  };
  for (int c = 0; c < 2 * n_pair; c++)
    for (Op* o = op[c]; o->type != OP_END; o++) {
      if (o->type == OP_A) { att[n_att] = {ready(o), o, 0}; if (++n_att > N_TILE) return false; }
      if (o->type == OP_A && o->flags) { unp[n_unp] = {o->t0 - AHEAD, o, 0}; if (++n_unp > MAX_PARK) return false; }
      if (o->type == OP_Q && o->flags) { prk[n_prk] = {ready(o), o, 0}; if (++n_prk > MAX_PARK) return false; }
      for (int i = 0; o->type == OP_O && i < o->n; i++) {
        const int nw = (o->flags & P_WIDE) ? o->n - TAIL : 0, k = nw ? i : kSteps - o->n + i;
        Use& u = use[o->id / kH * kH + k / 3];
        const double t = o->t0 + T_O * (i + (i < nw ? i : nw));
        if (t - AHEAD < u.need) u.need = t - AHEAD;
        const double f = !nw ? 1e18 : i + FLIGHT < o->items - TAIL || (nw && o[1].type != OP_O) ? t + T_O * (i < nw ? 2 : 1 + TAIL) + PUBLISH : 1e18;
        if (f > u.freed) u.freed = f;
        if (i == 0 || k % 3 == 0) u.readers++;
      }
    }
  if (n_att != N_TILE || n_prk != n_unp) return false;
  for (int i = 0; i < N_TILE; i++) { const int id = (i & 15) * kH + (i >> 4); dem[i] = {use[id].need, nullptr, id}; }
  sort(att, n_att); sort(dem, N_TILE); sort(prk, n_prk); sort(unp, n_unp);
  PlanStats st = {0, 1e18, 1e18, 0, n_prk};
  int n_wr = 0;
  for (int i = 0; i < N_TILE; i++) {
    Op* o = att[i].o;
    o->id = dem[i].id;
    if (!o->flags) o[-1].id = o->id;
    if (dem[i].t - att[i].t < st.slack) st.slack = dem[i].t - att[i].t;
    wr[n_wr++] = {o->t1 - 2 * AHEAD, o, o->id};
  }
  for (int i = 0; i < n_prk; i++) {
    prk[i].o->id = unp[i].o->id;
    prk[i].o->park = unp[i].o->park = i;
    use[N_TILE + i].freed = unp[i].o->t0 + 2 * PUBLISH;
    use[N_TILE + i].readers = 1;
    if (unp[i].t - prk[i].t < st.park_slack) st.park_slack = unp[i].t - prk[i].t;
    wr[n_wr++] = {prk[i].o->t1 - 2 * AHEAD, prk[i].o, N_TILE + i};
  }
  for (int c = 0; c < 2 * n_pair; c++)
    for (int d = 0; d < 2 * n_pair; d++)
      for (Op *f = &op[c][n_op[c] - 1], *o = op[d]; f->n && o->type != OP_END; o++)
        if (o->type == OP_O && (o->flags & P_WIDE) && o->id / kH == f->id / kH && o->quarter / 2 == f->quarter / 2) {
          if (f->t0 - o->t1 > 4096.0 * ((P.dbg >> 16) & 255)) f->flags |= P_PRE;
          const double slack = f->t0 + ((f->flags & P_PRE) ? 0 : (f->n - 5) * T_O) - AHEAD - ready(o);
          if (slack < st.park_slack) st.park_slack = slack;
        }
  constexpr double long_while = 160000;
  for (int c = 0; c < 2 * n_pair; c++)
    for (Op* o = op[c]; o->type != OP_END; o++) {
      if (o->type == OP_O && (o->flags & P_WIDE)) {
        int run = 0, best = 0, end = 0;
        for (int h = 0; 3 * h < o->n; h++) {
          bool last = true;
          for (int d = 0; d < 2 * n_pair; d++)
            for (const Op* e = op[d]; e->type != OP_END; e++) {
              if (e->type != OP_O || e == o || ((e->id ^ o->id) & 256) || e->quarter / 2 != o->quarter / 2) continue;
              const bool wide = e->flags & P_WIDE;
              if (wide ? 3 * h >= e->n : 3 * h + 3 <= kSteps - e->n) continue;
              const double dt = e->t0 + T_O * (wide ? 6 * h : 3 * h - kSteps + e->n) - o->t0 - T_O * 6 * h + (d - c) * 1e-3;
              if (dt > 0 && dt < long_while) last = false;
            }
          run = last ? run + 1 : 0;
          if (run > best) { best = run; end = h + 1; }
        }
        const int from = end - best;
        if (3 * end >= o->n) end++;
        o->park = from | (end / 2) << 5;
      }
      if (o->type != OP_Q) continue;
      bool lw = true, lx = true;
      for (int d = 0; d < 2 * n_pair; d++)
        for (const Op* e = op[d]; e->type != OP_END; e++) {
          const double dt = e->t0 - o->t0 + (d - c) * 1e-3;
          if (e->type != OP_Q || e == o || dt < 0 || dt > long_while) continue;
          if (((e->id ^ o->id) & (256 + 31)) == 0) lw = false;
          if (e->id / kH == o->id / kH) lx = false;
        }
      o->quarter = (lw ? P_LASTW : 0) | (lx ? P_LASTX : 0);
    }
  sort(wr, n_wr);
  int holder[N_TILE];
  for (int i = 0; i < n_wr; i++) {
    int best = -1;
    for (int sl = 0; sl < st.slots; sl++)
      if (use[holder[sl]].freed + margin <= wr[i].t && (best < 0 || use[holder[sl]].freed < use[holder[best]].freed)) best = sl;
    Use& u = use[wr[i].id];
    if (best >= 0) { u.prev = holder[best]; use[u.prev].next = true; wr[i].o->flags |= P_GATE; }
    else if (st.slots == N_TILE) return false;
    else best = st.slots++;
    u.slot = best;
    holder[best] = wr[i].id;
  }
  {
    int pos[N_CL] = {}, flag[ID_PART + 4 * N_TEAM] = {}, seen[ID_PART] = {};
    auto goal = [&](int c) { return op[c][n_op[c] - 1].item0; };
    for (bool moved = true; moved;) {
      moved = false;
      for (int c = 0; c < 2 * n_pair; c++) {
        for (; pos[c] < goal(c); pos[c]++, moved = true) {
          bool ok = true;
          for (const Op* o = op[c]; o->type != OP_END; o++) {
            const int k = pos[c] - o->item0, own = o->type == OP_A ? o->id : N_TILE + (o->park & 127);
            if (k < 0 || k >= o->items) continue;
            if (o->type == OP_O) ok = k >= o->n || flag[o->id + k / 3];
            else if (k == o->items - 1 && (o->flags & P_GATE)) ok = seen[use[own].prev] == use[use[own].prev].readers;
            else if (k == 1 && o->type == OP_A && (o->flags & F_PARK)) ok = flag[N_TILE + o->park];
          }
          if (!ok) break;
          for (const Op* o = op[c]; o->type != OP_END; o++) {
            if (pos[c] == o->item0 + o->items + (o[1].type == OP_Q ? 7 : o[1].item0 == goal(c) ? -1 : 5)) {
              if (o->type == OP_A) flag[o->id] = 1;
              if (o->type == OP_Q && (o->flags & F_PARK)) flag[N_TILE + o->park] = 1;
              if (o->type == OP_O) flag[ID_PART + o->id / kH * 4 + o->quarter] = flag[ID_PART + o->id / kH * 4 + o->quarter + 1] = 1;
            }
            const int k = pos[c] - FLIGHT - o->item0, nw = o->n - TAIL;
            if (k == 1 && o->type == OP_A && (o->flags & F_PARK)) seen[N_TILE + o->park]++;
            if (o->type == OP_O && k >= 0 && k < o->items && (k < nw || k >= o->n) && (k < nw ? k : k - TAIL) % 3 == 2) seen[o->id + (k < nw ? k : k - TAIL) / 3]++;
          }
        }
      }
    }
    for (int c = 0; c < 2 * n_pair; c++) if (pos[c] < goal(c)) return false;
  }
  int n_job = 0, longest = 0;
  for (int i = 0; i < 2 * N_TEAM; i++) if (kH + 1 - covered[i] / 3 > longest) longest = kH + 1 - covered[i] / 3;
  for (int c = 0; c < 2 * n_pair; c++) {
    uint32_t items = 0, cur = 0, pend = 0;
    int n = 0, ev = 0;
    auto item = [&](uint32_t bytes, int count) {
      for (int i = 0; i < count; i++) { if (cur + bytes > RING) cur = 0; cur += bytes; items++; }
    };
    auto event = [&](uint32_t e) { if (ev < MAX_TAB) P.prog[c].ev[ev] = e; ev++; };
    for (const Op* o = op[c];; o++) {
      if (o->type != OP_END && phase && (o->type == OP_O) != (phase == 2)) continue;
      uint32_t cw = o->type | (items % (2 * NBAR)) << 15 | (cur >> 12) << 20 | pend, pw = o->type | o->id << 2 | o->flags;
      const int ps = use[N_TILE + (o->park & 127)].slot;
      pend = 0;
      if (o->type == OP_O) {
        pw |= o->n << 13 | o->quarter << 20 | (uint32_t)o->park << 23;
        if (o->flags & P_WIDE) {
          cw |= o->n << 2 | (o->id / kH * 2 + o->quarter / 2) << 9 | C_WIDE;
          item(SZ_W, o->n - TAIL);
          item(SZ_W2, TAIL);
          item(SZ_W3, TAIL);
          pend = C_PEND;
          for (int i = 0; 3 * i < o->n; i++) event((o->id + i) | E_ON | (use[o->id + i].next ? 0 : E_LAST));
        } else {
          dem[n_job++] = {o->t0 - 1e6 * o->n, nullptr, (int)pw};
          st.own[c] = pw;
          pw = OP_O;
          event(E_DRAW | (items < 16 ? 0 : items - 16));
        }
      } else if (o->type != OP_END) {
        const bool parks = o->type == OP_Q && (o->flags & F_PARK);
        cw |= (parks ? ps : use[o->id].slot) << 2 | (o->flags & F_PARK);
        if (o->flags & F_PARK) pw |= o->park << 13 | ps << 20;
        if (o->type == OP_Q) { item(SZ_Q, 10); pw |= o->quarter; }
        else { item(SZ_KV, 1); if (o->flags & F_PARK) { item(SZ_PARK, 1); event((N_TILE + o->park) | E_ON | (use[N_TILE + o->park].next ? 0 : E_LAST)); } item(SZ_KV, 31); }
        if (parks || o->type == OP_A) pend = C_PEND;
        if (o->flags & P_GATE) event(use[parks ? N_TILE + o->park : o->id].prev | E_ON | E_FREE);
      }
      P.prog[c].c[n] = cw; P.prog[c].p[n++] = pw;
      if (o->type == OP_END) { if (o->t0 > st.end) st.end = o->t0; break; }
    }
    if (ev > MAX_TAB || ev + longest > MAX_EV) return false;
    P.prog[c].n_ev = ev;
    while (n < MAX_OPS) { P.prog[c].c[n] = OP_END; P.prog[c].p[n++] = OP_END; }
    P.first[c] = (uint16_t)(P.prog[c].p[0] & 2047);
  }
  sort(dem, n_job);
  for (int i = 0; i < n_job; i++) P.job[i] = dem[i].id;
  for (int i = 0; i < ID_PART; i++) {
    if (i < N_TILE) P.slot[i] = use[i].slot;
    P.info[i] = (use[i].readers + use[i].next) | (use[i].next ? I_NEXT : 0);
  }
  if (stats) *stats = st;
  return true;
}

const char* const kPrograms[N_CL / 2] = {
  "PNJ06864NNNNN", "PNJ17878NNNNN", "PNJ26464NNNNN", "PNJ34148NNNNNN", "PNJ46262NNNNN", "PNJ58182NNNN",
  "NNJ67371NNNN", "PNNJ76666NNNN", "NUNNNJ84545NN", "NUNNNJ94545NN", "NUNNNNJa5551N", "NNNNNJb5959NN",
  "NNNNNJc5455NN", "PNNNNNJd5353NN", "NNNNNJe5153NN", "NNNNNJf7777N", "PNNNNNNNNN", "PNNNNNNNNN",
  "PNNNNNNNNN", "PNNNNNNNNN", "NNNNNNNNN", "NNNNNNNNN", "NNNNNNNNN", "NNNNNNNNN",
  "NNNNNNNNN", "N-NNNNNNNN", "NUNNNNNNN", "NUNNNNNNN", "NUNNNNNNN", "NUNNNUNNN",
  "NUNNNNNNN", "NUNNNNNNN", "NUUNNNNNN",
};

const char* const* bench_programs() {
  return kPrograms;
}

}

extern "C" void kernel_launch(void* const* d_in, const int* in_sizes, int n_in, void* d_out, int out_size) {
  (void)in_sizes; (void)n_in; (void)out_size;
  static EncodeFn fn = nullptr;
  static int n_clusters = 0;
  if (!fn) {
    cudaDriverEntryPointQueryResult qr;
    void* f = nullptr;
    cudaGetDriverEntryPoint("cuTensorMapEncodeTiled", &f, cudaEnableDefault, &qr);
    fn = (EncodeFn)f;
    cudaFuncSetAttribute(fused_kernel, cudaFuncAttributeMaxDynamicSharedMemorySize, SMEM_BYTES);
    cudaLaunchConfig_t cfg = {};
    cfg.gridDim = dim3(132); cfg.blockDim = dim3(384); cfg.dynamicSmemBytes = SMEM_BYTES;
    cudaLaunchAttribute at[1];
    at[0].id = cudaLaunchAttributeClusterDimension; at[0].val.clusterDim.x = 2; at[0].val.clusterDim.y = 1; at[0].val.clusterDim.z = 1;
    cfg.attrs = at; cfg.numAttrs = 1;
    if (cudaOccupancyMaxActiveClusters(&n_clusters, fused_kernel, &cfg) != cudaSuccess || n_clusters < 1) n_clusters = 1;
    (void)cudaGetLastError();
  }
  static Params P;
  const CUtensorMapSwizzle S128 = CU_TENSOR_MAP_SWIZZLE_128B, S64 = CU_TENSOR_MAP_SWIZZLE_64B;
  for (int blk = 0; blk < 2; blk++) {
    void* const* in = d_in + 5 * blk;
    { const cuuint64_t d[] = {kD, kB * kSq}, s[] = {kD * 2}; const cuuint32_t b[] = {64, 128};
      encode(fn, &P.x[blk], in[0], 2, d, s, b, S128); }
    { const cuuint64_t d[] = {64, 8, 3, (cuuint64_t)kB * kH * kSk / 8}, s[] = {kDh * 2, 128, 8 * kDh * 2}; const cuuint32_t b[] = {64, 8, 3, 4};
      encode(fn, &P.k[blk], in[1], 4, d, s, b, S128);
      encode(fn, &P.v[blk], in[2], 4, d, s, b, S128); }
    { const cuuint64_t d[] = {64, kD, kHD / 64}, s[] = {kHD * 2, 128}; const cuuint32_t b[] = {64, 32, 3};
      encode(fn, &P.wq[blk], in[3], 3, d, s, b, S128); }
    { const cuuint64_t d[] = {32, 2, kHD / 8, 4, kD / 32}, s[] = {kD * 2, 8 * kD * 2, 2 * kD * 2, 64}; const cuuint32_t b[] = {32, 2, 4, 4, 5};
      encode(fn, &P.wo[blk], in[4], 5, d, s, b, S64); }
    { const cuuint64_t d[] = {64, 2, kHD / 8, 4, kD / 64}, s[] = {kD * 2, 8 * kD * 2, 2 * kD * 2, 128};
      const cuuint32_t b3[] = {64, 2, 4, 4, 3}, b2[] = {64, 2, 4, 4, 2};
      encode(fn, &P.wo3[blk], in[4], 5, d, s, b3, S128);
      encode(fn, &P.wo2[blk], in[4], 5, d, s, b2, S128); }
  }
  { const cuuint64_t d[] = {32, kB * kSq, 2 * kD / 32}, s[] = {2 * kD * 2, 64}; const cuuint32_t b[] = {32, 16, 1};
    encode(fn, &P.out, d_out, 3, d, s, b, S64); }

  P.kv[0] = (const char*)d_in[1]; P.kv[1] = (const char*)d_in[6]; P.kv[2] = (const char*)d_in[2]; P.kv[3] = (const char*)d_in[7];
  P.xw[0] = (const char*)d_in[0]; P.xw[1] = (const char*)d_in[3];
  cudaGetSymbolAddress((void**)&P.g, g_scratch);
  P.dbg = DBG_DEFAULT;
  if (n_clusters >= N_CL && plan(bench_programs(), N_CL / 2, 0, P)) {
    fused_kernel<<<2 * N_CL, 384, SMEM_BYTES>>>(P);
  } else {
    const char* text[2 * N_TEAM];
    for (int i = 0; i < 2 * N_TEAM; i++) text[i] = "NNNNNNNN";
    for (int phase = 1; phase <= 2; phase++) {
      plan(text, 2 * N_TEAM, phase, P);
      fused_kernel<<<8 * N_TEAM, 384, SMEM_BYTES>>>(P);
    }
  }
}
```

```cpp
#include <cuda_runtime.h>
#include <cuda_bf16.h>
#include <cuda.h>
#include <cuda/annotated_ptr>
#include <stdint.h>
#include <stdio.h>

namespace {

constexpr int kB = 8, kSq = 256, kD = 640, kH = 32, kSk = 1024, kDh = 192;
constexpr int kHD = kH * kDh;
constexpr uint32_t RING = 224 * 1024;
constexpr uint32_t SZ_KV = 24576;
constexpr uint32_t SZ_Q = 16384 + 24576;
constexpr uint32_t SZ_O = 16384 + 20480;
constexpr uint32_t SZ_W3 = 16384 + 24576, SZ_W2 = 16384 + 16384, SZ_W = SZ_W3 + 16384;
constexpr uint32_t SZ_PARK = 49152;
constexpr uint32_t SZ_OL = SZ_O + 8192;
constexpr int NBAR = 16, FLIGHT = RING / SZ_KV + 1;
constexpr int EARLY = 3;
constexpr int kSteps = kHD / 64;
constexpr int TAIL = 4;
constexpr uint32_t KV_CH = 64, KV_SBO = 3072;
constexpr int SMEM_BYTES = RING + 1024 + 1024;
constexpr int N_TEAM = 16, N_CL = 66, MAX_OPS = 22, MAX_EV = 72, MAX_TAB = 47, N_TILE = N_TEAM * kH, MAX_PARK = 128, ID_PART = N_TILE + MAX_PARK;
enum : uint32_t { OP_END = 0, OP_Q = 1, OP_A = 2, OP_O = 3, F_PARK = 1 << 11,
                  C_WIDE = 1 << 27, C_PEND = 1 << 26, P_GATE = 1 << 12, P_WIDE = 1 << 11, P_LD = 1 << 12, P_PRE = 1 << 22, P_LASTW = 1 << 29, P_LASTX = 1 << 30,
                  I_NEXT = 8, E_ON = 1 << 15, E_FREE = 1 << 14, E_LAST = 1 << 13, E_DRAW = 1 << 12, E_JOB = 1 << 11 };

constexpr uint32_t DBG_DEFAULT = 0x040800;

struct alignas(1024) Scratch {
  unsigned int flag[2047];
  unsigned int ticket;
  uint4 part[N_TEAM * 2 * 2 * 5120];
  uint4 tile[N_TILE * 2 * 3072];
};

struct alignas(64) Params {
  const char* xw[2];
  uint16_t first[80];
  Scratch* g;
  uint32_t dbg;
  CUtensorMap x[2], wq[2], k[2], v[2], wo[2], wo3[2], wo2[2], out;
  struct {
    uint32_t c[MAX_OPS];
    uint32_t p[MAX_OPS];
    uint16_t n_ev, ev[MAX_TAB];
  } prog[N_CL];
  const char* kv[4];
  uint32_t job[N_CL];
  uint16_t slot[N_TILE];
  uint8_t info[ID_PART];
};

__device__ Scratch g_scratch;

template <int TB, int TA = 0>
__device__ __forceinline__ void wgmma_ss_n64(float (&d)[32], uint64_t da, uint64_t db, int scale_d) {
  asm volatile("{\n.reg .pred p;\nsetp.ne.b32 p, %34, 0;\n"
    "wgmma.mma_async.sync.aligned.m64n64k16.f32.bf16.bf16 {%0, %1, %2, %3, %4, %5, %6, %7, %8, %9, %10, %11, %12, %13, %14, %15, %16, %17, %18, %19, %20, %21, %22, %23, %24, %25, %26, %27, %28, %29, %30, %31}, %32, %33, p, 1, 1, %35, %36;\n}\n"
    : "+f"(d[0]), "+f"(d[1]), "+f"(d[2]), "+f"(d[3]), "+f"(d[4]), "+f"(d[5]), "+f"(d[6]), "+f"(d[7]), "+f"(d[8]), "+f"(d[9]), "+f"(d[10]), "+f"(d[11]), "+f"(d[12]), "+f"(d[13]), "+f"(d[14]), "+f"(d[15]), "+f"(d[16]), "+f"(d[17]), "+f"(d[18]), "+f"(d[19]), "+f"(d[20]), "+f"(d[21]), "+f"(d[22]), "+f"(d[23]), "+f"(d[24]), "+f"(d[25]), "+f"(d[26]), "+f"(d[27]), "+f"(d[28]), "+f"(d[29]), "+f"(d[30]), "+f"(d[31])
    : "l"(da), "l"(db), "r"(scale_d), "n"(TA), "n"(TB));
}
template <int TB>
__device__ __forceinline__ void wgmma_rs_n64(float (&d)[32], uint32_t a0, uint32_t a1, uint32_t a2, uint32_t a3, uint64_t db, int scale_d) {
  asm volatile("{\n.reg .pred p;\nsetp.ne.b32 p, %37, 0;\n"
    "wgmma.mma_async.sync.aligned.m64n64k16.f32.bf16.bf16 {%0, %1, %2, %3, %4, %5, %6, %7, %8, %9, %10, %11, %12, %13, %14, %15, %16, %17, %18, %19, %20, %21, %22, %23, %24, %25, %26, %27, %28, %29, %30, %31}, {%32, %33, %34, %35}, %36, p, 1, 1, %38;\n}\n"
    : "+f"(d[0]), "+f"(d[1]), "+f"(d[2]), "+f"(d[3]), "+f"(d[4]), "+f"(d[5]), "+f"(d[6]), "+f"(d[7]), "+f"(d[8]), "+f"(d[9]), "+f"(d[10]), "+f"(d[11]), "+f"(d[12]), "+f"(d[13]), "+f"(d[14]), "+f"(d[15]), "+f"(d[16]), "+f"(d[17]), "+f"(d[18]), "+f"(d[19]), "+f"(d[20]), "+f"(d[21]), "+f"(d[22]), "+f"(d[23]), "+f"(d[24]), "+f"(d[25]), "+f"(d[26]), "+f"(d[27]), "+f"(d[28]), "+f"(d[29]), "+f"(d[30]), "+f"(d[31])
    : "r"(a0), "r"(a1), "r"(a2), "r"(a3), "l"(db), "r"(scale_d), "n"(TB));
}
template <int TB, int TA = 0>
__device__ __forceinline__ void wgmma_ss_n128(float (&d)[64], uint64_t da, uint64_t db, int scale_d) {
  asm volatile("{\n.reg .pred p;\nsetp.ne.b32 p, %66, 0;\n"
    "wgmma.mma_async.sync.aligned.m64n128k16.f32.bf16.bf16 {%0, %1, %2, %3, %4, %5, %6, %7, %8, %9, %10, %11, %12, %13, %14, %15, %16, %17, %18, %19, %20, %21, %22, %23, %24, %25, %26, %27, %28, %29, %30, %31, %32, %33, %34, %35, %36, %37, %38, %39, %40, %41, %42, %43, %44, %45, %46, %47, %48, %49, %50, %51, %52, %53, %54, %55, %56, %57, %58, %59, %60, %61, %62, %63}, %64, %65, p, 1, 1, %67, %68;\n}\n"
    : "+f"(d[0]), "+f"(d[1]), "+f"(d[2]), "+f"(d[3]), "+f"(d[4]), "+f"(d[5]), "+f"(d[6]), "+f"(d[7]), "+f"(d[8]), "+f"(d[9]), "+f"(d[10]), "+f"(d[11]), "+f"(d[12]), "+f"(d[13]), "+f"(d[14]), "+f"(d[15]), "+f"(d[16]), "+f"(d[17]), "+f"(d[18]), "+f"(d[19]), "+f"(d[20]), "+f"(d[21]), "+f"(d[22]), "+f"(d[23]), "+f"(d[24]), "+f"(d[25]), "+f"(d[26]), "+f"(d[27]), "+f"(d[28]), "+f"(d[29]), "+f"(d[30]), "+f"(d[31]), "+f"(d[32]), "+f"(d[33]), "+f"(d[34]), "+f"(d[35]), "+f"(d[36]), "+f"(d[37]), "+f"(d[38]), "+f"(d[39]), "+f"(d[40]), "+f"(d[41]), "+f"(d[42]), "+f"(d[43]), "+f"(d[44]), "+f"(d[45]), "+f"(d[46]), "+f"(d[47]), "+f"(d[48]), "+f"(d[49]), "+f"(d[50]), "+f"(d[51]), "+f"(d[52]), "+f"(d[53]), "+f"(d[54]), "+f"(d[55]), "+f"(d[56]), "+f"(d[57]), "+f"(d[58]), "+f"(d[59]), "+f"(d[60]), "+f"(d[61]), "+f"(d[62]), "+f"(d[63])
    : "l"(da), "l"(db), "r"(scale_d), "n"(TA), "n"(TB));
}
template <int TB>
__device__ __forceinline__ void wgmma_rs_n128(float (&d)[64], uint32_t a0, uint32_t a1, uint32_t a2, uint32_t a3, uint64_t db, int scale_d) {
  asm volatile("{\n.reg .pred p;\nsetp.ne.b32 p, %69, 0;\n"
    "wgmma.mma_async.sync.aligned.m64n128k16.f32.bf16.bf16 {%0, %1, %2, %3, %4, %5, %6, %7, %8, %9, %10, %11, %12, %13, %14, %15, %16, %17, %18, %19, %20, %21, %22, %23, %24, %25, %26, %27, %28, %29, %30, %31, %32, %33, %34, %35, %36, %37, %38, %39, %40, %41, %42, %43, %44, %45, %46, %47, %48, %49, %50, %51, %52, %53, %54, %55, %56, %57, %58, %59, %60, %61, %62, %63}, {%64, %65, %66, %67}, %68, p, 1, 1, %70;\n}\n"
    : "+f"(d[0]), "+f"(d[1]), "+f"(d[2]), "+f"(d[3]), "+f"(d[4]), "+f"(d[5]), "+f"(d[6]), "+f"(d[7]), "+f"(d[8]), "+f"(d[9]), "+f"(d[10]), "+f"(d[11]), "+f"(d[12]), "+f"(d[13]), "+f"(d[14]), "+f"(d[15]), "+f"(d[16]), "+f"(d[17]), "+f"(d[18]), "+f"(d[19]), "+f"(d[20]), "+f"(d[21]), "+f"(d[22]), "+f"(d[23]), "+f"(d[24]), "+f"(d[25]), "+f"(d[26]), "+f"(d[27]), "+f"(d[28]), "+f"(d[29]), "+f"(d[30]), "+f"(d[31]), "+f"(d[32]), "+f"(d[33]), "+f"(d[34]), "+f"(d[35]), "+f"(d[36]), "+f"(d[37]), "+f"(d[38]), "+f"(d[39]), "+f"(d[40]), "+f"(d[41]), "+f"(d[42]), "+f"(d[43]), "+f"(d[44]), "+f"(d[45]), "+f"(d[46]), "+f"(d[47]), "+f"(d[48]), "+f"(d[49]), "+f"(d[50]), "+f"(d[51]), "+f"(d[52]), "+f"(d[53]), "+f"(d[54]), "+f"(d[55]), "+f"(d[56]), "+f"(d[57]), "+f"(d[58]), "+f"(d[59]), "+f"(d[60]), "+f"(d[61]), "+f"(d[62]), "+f"(d[63])
    : "r"(a0), "r"(a1), "r"(a2), "r"(a3), "l"(db), "r"(scale_d), "n"(TB));
}
template <int TB, int TA = 0>
__device__ __forceinline__ void wgmma_ss_n160(float (&d)[80], uint64_t da, uint64_t db, int scale_d) {
  asm volatile("{\n.reg .pred p;\nsetp.ne.b32 p, %82, 0;\n"
    "wgmma.mma_async.sync.aligned.m64n160k16.f32.bf16.bf16 {%0, %1, %2, %3, %4, %5, %6, %7, %8, %9, %10, %11, %12, %13, %14, %15, %16, %17, %18, %19, %20, %21, %22, %23, %24, %25, %26, %27, %28, %29, %30, %31, %32, %33, %34, %35, %36, %37, %38, %39, %40, %41, %42, %43, %44, %45, %46, %47, %48, %49, %50, %51, %52, %53, %54, %55, %56, %57, %58, %59, %60, %61, %62, %63, %64, %65, %66, %67, %68, %69, %70, %71, %72, %73, %74, %75, %76, %77, %78, %79}, %80, %81, p, 1, 1, %83, %84;\n}\n"
    : "+f"(d[0]), "+f"(d[1]), "+f"(d[2]), "+f"(d[3]), "+f"(d[4]), "+f"(d[5]), "+f"(d[6]), "+f"(d[7]), "+f"(d[8]), "+f"(d[9]), "+f"(d[10]), "+f"(d[11]), "+f"(d[12]), "+f"(d[13]), "+f"(d[14]), "+f"(d[15]), "+f"(d[16]), "+f"(d[17]), "+f"(d[18]), "+f"(d[19]), "+f"(d[20]), "+f"(d[21]), "+f"(d[22]), "+f"(d[23]), "+f"(d[24]), "+f"(d[25]), "+f"(d[26]), "+f"(d[27]), "+f"(d[28]), "+f"(d[29]), "+f"(d[30]), "+f"(d[31]), "+f"(d[32]), "+f"(d[33]), "+f"(d[34]), "+f"(d[35]), "+f"(d[36]), "+f"(d[37]), "+f"(d[38]), "+f"(d[39]), "+f"(d[40]), "+f"(d[41]), "+f"(d[42]), "+f"(d[43]), "+f"(d[44]), "+f"(d[45]), "+f"(d[46]), "+f"(d[47]), "+f"(d[48]), "+f"(d[49]), "+f"(d[50]), "+f"(d[51]), "+f"(d[52]), "+f"(d[53]), "+f"(d[54]), "+f"(d[55]), "+f"(d[56]), "+f"(d[57]), "+f"(d[58]), "+f"(d[59]), "+f"(d[60]), "+f"(d[61]), "+f"(d[62]), "+f"(d[63]), "+f"(d[64]), "+f"(d[65]), "+f"(d[66]), "+f"(d[67]), "+f"(d[68]), "+f"(d[69]), "+f"(d[70]), "+f"(d[71]), "+f"(d[72]), "+f"(d[73]), "+f"(d[74]), "+f"(d[75]), "+f"(d[76]), "+f"(d[77]), "+f"(d[78]), "+f"(d[79])
    : "l"(da), "l"(db), "r"(scale_d), "n"(TA), "n"(TB));
}
template <int TB>
__device__ __forceinline__ void wgmma_rs_n160(float (&d)[80], uint32_t a0, uint32_t a1, uint32_t a2, uint32_t a3, uint64_t db, int scale_d) {
  asm volatile("{\n.reg .pred p;\nsetp.ne.b32 p, %85, 0;\n"
    "wgmma.mma_async.sync.aligned.m64n160k16.f32.bf16.bf16 {%0, %1, %2, %3, %4, %5, %6, %7, %8, %9, %10, %11, %12, %13, %14, %15, %16, %17, %18, %19, %20, %21, %22, %23, %24, %25, %26, %27, %28, %29, %30, %31, %32, %33, %34, %35, %36, %37, %38, %39, %40, %41, %42, %43, %44, %45, %46, %47, %48, %49, %50, %51, %52, %53, %54, %55, %56, %57, %58, %59, %60, %61, %62, %63, %64, %65, %66, %67, %68, %69, %70, %71, %72, %73, %74, %75, %76, %77, %78, %79}, {%80, %81, %82, %83}, %84, p, 1, 1, %86;\n}\n"
    : "+f"(d[0]), "+f"(d[1]), "+f"(d[2]), "+f"(d[3]), "+f"(d[4]), "+f"(d[5]), "+f"(d[6]), "+f"(d[7]), "+f"(d[8]), "+f"(d[9]), "+f"(d[10]), "+f"(d[11]), "+f"(d[12]), "+f"(d[13]), "+f"(d[14]), "+f"(d[15]), "+f"(d[16]), "+f"(d[17]), "+f"(d[18]), "+f"(d[19]), "+f"(d[20]), "+f"(d[21]), "+f"(d[22]), "+f"(d[23]), "+f"(d[24]), "+f"(d[25]), "+f"(d[26]), "+f"(d[27]), "+f"(d[28]), "+f"(d[29]), "+f"(d[30]), "+f"(d[31]), "+f"(d[32]), "+f"(d[33]), "+f"(d[34]), "+f"(d[35]), "+f"(d[36]), "+f"(d[37]), "+f"(d[38]), "+f"(d[39]), "+f"(d[40]), "+f"(d[41]), "+f"(d[42]), "+f"(d[43]), "+f"(d[44]), "+f"(d[45]), "+f"(d[46]), "+f"(d[47]), "+f"(d[48]), "+f"(d[49]), "+f"(d[50]), "+f"(d[51]), "+f"(d[52]), "+f"(d[53]), "+f"(d[54]), "+f"(d[55]), "+f"(d[56]), "+f"(d[57]), "+f"(d[58]), "+f"(d[59]), "+f"(d[60]), "+f"(d[61]), "+f"(d[62]), "+f"(d[63]), "+f"(d[64]), "+f"(d[65]), "+f"(d[66]), "+f"(d[67]), "+f"(d[68]), "+f"(d[69]), "+f"(d[70]), "+f"(d[71]), "+f"(d[72]), "+f"(d[73]), "+f"(d[74]), "+f"(d[75]), "+f"(d[76]), "+f"(d[77]), "+f"(d[78]), "+f"(d[79])
    : "r"(a0), "r"(a1), "r"(a2), "r"(a3), "l"(db), "r"(scale_d), "n"(TB));
}
template <int TB, int TA = 0>
__device__ __forceinline__ void wgmma_ss_n192(float (&d)[96], uint64_t da, uint64_t db, int scale_d) {
  asm volatile("{\n.reg .pred p;\nsetp.ne.b32 p, %98, 0;\n"
    "wgmma.mma_async.sync.aligned.m64n192k16.f32.bf16.bf16 {%0, %1, %2, %3, %4, %5, %6, %7, %8, %9, %10, %11, %12, %13, %14, %15, %16, %17, %18, %19, %20, %21, %22, %23, %24, %25, %26, %27, %28, %29, %30, %31, %32, %33, %34, %35, %36, %37, %38, %39, %40, %41, %42, %43, %44, %45, %46, %47, %48, %49, %50, %51, %52, %53, %54, %55, %56, %57, %58, %59, %60, %61, %62, %63, %64, %65, %66, %67, %68, %69, %70, %71, %72, %73, %74, %75, %76, %77, %78, %79, %80, %81, %82, %83, %84, %85, %86, %87, %88, %89, %90, %91, %92, %93, %94, %95}, %96, %97, p, 1, 1, %99, %100;\n}\n"
    : "+f"(d[0]), "+f"(d[1]), "+f"(d[2]), "+f"(d[3]), "+f"(d[4]), "+f"(d[5]), "+f"(d[6]), "+f"(d[7]), "+f"(d[8]), "+f"(d[9]), "+f"(d[10]), "+f"(d[11]), "+f"(d[12]), "+f"(d[13]), "+f"(d[14]), "+f"(d[15]), "+f"(d[16]), "+f"(d[17]), "+f"(d[18]), "+f"(d[19]), "+f"(d[20]), "+f"(d[21]), "+f"(d[22]), "+f"(d[23]), "+f"(d[24]), "+f"(d[25]), "+f"(d[26]), "+f"(d[27]), "+f"(d[28]), "+f"(d[29]), "+f"(d[30]), "+f"(d[31]), "+f"(d[32]), "+f"(d[33]), "+f"(d[34]), "+f"(d[35]), "+f"(d[36]), "+f"(d[37]), "+f"(d[38]), "+f"(d[39]), "+f"(d[40]), "+f"(d[41]), "+f"(d[42]), "+f"(d[43]), "+f"(d[44]), "+f"(d[45]), "+f"(d[46]), "+f"(d[47]), "+f"(d[48]), "+f"(d[49]), "+f"(d[50]), "+f"(d[51]), "+f"(d[52]), "+f"(d[53]), "+f"(d[54]), "+f"(d[55]), "+f"(d[56]), "+f"(d[57]), "+f"(d[58]), "+f"(d[59]), "+f"(d[60]), "+f"(d[61]), "+f"(d[62]), "+f"(d[63]), "+f"(d[64]), "+f"(d[65]), "+f"(d[66]), "+f"(d[67]), "+f"(d[68]), "+f"(d[69]), "+f"(d[70]), "+f"(d[71]), "+f"(d[72]), "+f"(d[73]), "+f"(d[74]), "+f"(d[75]), "+f"(d[76]), "+f"(d[77]), "+f"(d[78]), "+f"(d[79]), "+f"(d[80]), "+f"(d[81]), "+f"(d[82]), "+f"(d[83]), "+f"(d[84]), "+f"(d[85]), "+f"(d[86]), "+f"(d[87]), "+f"(d[88]), "+f"(d[89]), "+f"(d[90]), "+f"(d[91]), "+f"(d[92]), "+f"(d[93]), "+f"(d[94]), "+f"(d[95])
    : "l"(da), "l"(db), "r"(scale_d), "n"(TA), "n"(TB));
}
template <int TB>
__device__ __forceinline__ void wgmma_rs_n192(float (&d)[96], uint32_t a0, uint32_t a1, uint32_t a2, uint32_t a3, uint64_t db, int scale_d) {
  asm volatile("{\n.reg .pred p;\nsetp.ne.b32 p, %101, 0;\n"
    "wgmma.mma_async.sync.aligned.m64n192k16.f32.bf16.bf16 {%0, %1, %2, %3, %4, %5, %6, %7, %8, %9, %10, %11, %12, %13, %14, %15, %16, %17, %18, %19, %20, %21, %22, %23, %24, %25, %26, %27, %28, %29, %30, %31, %32, %33, %34, %35, %36, %37, %38, %39, %40, %41, %42, %43, %44, %45, %46, %47, %48, %49, %50, %51, %52, %53, %54, %55, %56, %57, %58, %59, %60, %61, %62, %63, %64, %65, %66, %67, %68, %69, %70, %71, %72, %73, %74, %75, %76, %77, %78, %79, %80, %81, %82, %83, %84, %85, %86, %87, %88, %89, %90, %91, %92, %93, %94, %95}, {%96, %97, %98, %99}, %100, p, 1, 1, %102;\n}\n"
    : "+f"(d[0]), "+f"(d[1]), "+f"(d[2]), "+f"(d[3]), "+f"(d[4]), "+f"(d[5]), "+f"(d[6]), "+f"(d[7]), "+f"(d[8]), "+f"(d[9]), "+f"(d[10]), "+f"(d[11]), "+f"(d[12]), "+f"(d[13]), "+f"(d[14]), "+f"(d[15]), "+f"(d[16]), "+f"(d[17]), "+f"(d[18]), "+f"(d[19]), "+f"(d[20]), "+f"(d[21]), "+f"(d[22]), "+f"(d[23]), "+f"(d[24]), "+f"(d[25]), "+f"(d[26]), "+f"(d[27]), "+f"(d[28]), "+f"(d[29]), "+f"(d[30]), "+f"(d[31]), "+f"(d[32]), "+f"(d[33]), "+f"(d[34]), "+f"(d[35]), "+f"(d[36]), "+f"(d[37]), "+f"(d[38]), "+f"(d[39]), "+f"(d[40]), "+f"(d[41]), "+f"(d[42]), "+f"(d[43]), "+f"(d[44]), "+f"(d[45]), "+f"(d[46]), "+f"(d[47]), "+f"(d[48]), "+f"(d[49]), "+f"(d[50]), "+f"(d[51]), "+f"(d[52]), "+f"(d[53]), "+f"(d[54]), "+f"(d[55]), "+f"(d[56]), "+f"(d[57]), "+f"(d[58]), "+f"(d[59]), "+f"(d[60]), "+f"(d[61]), "+f"(d[62]), "+f"(d[63]), "+f"(d[64]), "+f"(d[65]), "+f"(d[66]), "+f"(d[67]), "+f"(d[68]), "+f"(d[69]), "+f"(d[70]), "+f"(d[71]), "+f"(d[72]), "+f"(d[73]), "+f"(d[74]), "+f"(d[75]), "+f"(d[76]), "+f"(d[77]), "+f"(d[78]), "+f"(d[79]), "+f"(d[80]), "+f"(d[81]), "+f"(d[82]), "+f"(d[83]), "+f"(d[84]), "+f"(d[85]), "+f"(d[86]), "+f"(d[87]), "+f"(d[88]), "+f"(d[89]), "+f"(d[90]), "+f"(d[91]), "+f"(d[92]), "+f"(d[93]), "+f"(d[94]), "+f"(d[95])
    : "r"(a0), "r"(a1), "r"(a2), "r"(a3), "l"(db), "r"(scale_d), "n"(TB));
}

__device__ __forceinline__ uint32_t smem_u32(const void* p) { return (uint32_t)__cvta_generic_to_shared(p); }
__device__ __forceinline__ void wg_fence() { asm volatile("wgmma.fence.sync.aligned;" ::: "memory"); }
__device__ __forceinline__ void wg_commit() { asm volatile("wgmma.commit_group.sync.aligned;" ::: "memory"); }
template <int N> __device__ __forceinline__ void wg_wait() { asm volatile("wgmma.wait_group.sync.aligned %0;" ::"n"(N) : "memory"); }
__device__ __forceinline__ void sched_fence(uint32_t& keep, bool never) {
  asm volatile("{\n.reg .pred p;\nsetp.ne.b32 p, %1, 0;\n@p mov.u32 %0, %%clock;\n}\n" : "+r"(keep) : "r"((int)never) : "memory");
}
template <int N> __device__ __forceinline__ void fence_regs(float (&r)[N]) {
#pragma unroll
  for (int i = 0; i < N; i++) asm volatile("" : "+f"(r[i])::"memory");
}
template <int N> __device__ __forceinline__ void undefine(float (&r)[N]) {
#pragma unroll
  for (int i = 0; i < N; i++) asm volatile("" : "=f"(r[i]));
}
template <int N> __device__ __forceinline__ void fence_regs(uint32_t (&r)[N]) {
#pragma unroll
  for (int i = 0; i < N; i++) asm volatile("" : "+r"(r[i])::"memory");
}
__device__ __forceinline__ uint64_t mk_desc(uint32_t a16, uint32_t lbo, uint32_t sbo, uint32_t swz) {
  uint64_t d;
  asm("mov.b64 %0, {%1, %2};" : "=l"(d) : "r"(a16 + ((lbo >> 4) << 16)), "r"((sbo >> 4) | (swz << 30)));
  return d;
}
__device__ __forceinline__ void mbar_init(uint32_t bar, uint32_t cnt) {
  asm volatile("mbarrier.init.shared::cta.b64 [%0], %1;" ::"r"(bar), "r"(cnt) : "memory");
}
__device__ __forceinline__ void mbar_expect(uint32_t bar, uint32_t tx) {
  asm volatile("mbarrier.arrive.expect_tx.shared::cta.b64 _, [%0], %1;" ::"r"(bar), "r"(tx) : "memory");
}
__device__ __forceinline__ bool mbar_test(uint32_t bar, uint32_t ph) {
  uint32_t ok;
  asm volatile("{\n.reg .pred p;\nmbarrier.test_wait.parity.shared::cta.b64 p, [%1], %2;\nselp.u32 %0, 1, 0, p;\n}\n"
               : "=r"(ok) : "r"(bar), "r"(ph) : "memory");
  return ok;
}
__device__ __forceinline__ bool mbar_try(uint32_t bar, uint32_t ph, uint32_t ns) {
  uint32_t ok;
  asm volatile("{\n.reg .pred p;\nmbarrier.try_wait.parity.shared::cta.b64 p, [%1], %2, %3;\nselp.u32 %0, 1, 0, p;\n}\n"
               : "=r"(ok) : "r"(bar), "r"(ph), "r"(ns) : "memory");
  return ok;
}
__device__ __forceinline__ void mbar_wait(uint32_t bar, uint32_t ph) {
  asm volatile("{\n.reg .pred p;\n.reg .u32 n;\nmov.u32 n, 0;\n"
               "LOOP:\nmbarrier.try_wait.parity.shared::cta.b64 p, [%0], %1;\n@p bra DONE;\n"
               "add.u32 n, n, 1;\nsetp.lt.u32 p, n, 0x1000000;\n@p bra LOOP;\ntrap;\n"
               "DONE:\n}\n" ::"r"(bar), "r"(ph) : "memory");
}
__device__ __forceinline__ void mbar_wait_long(uint32_t bar) {
  asm volatile("{\n.reg .pred p;\n.reg .u32 n;\nmov.u32 n, 0;\n"
               "LOOP:\nmbarrier.try_wait.parity.shared::cta.b64 p, [%0], 0, 20000;\n@p bra DONE;\n"
               "add.u32 n, n, 1;\nsetp.lt.u32 p, n, 0x100000;\n@p bra LOOP;\ntrap;\n"
               "DONE:\n}\n" ::"r"(bar) : "memory");
}
__device__ __forceinline__ void mbar_arrive_cluster_if(bool on, uint32_t addr) {
  asm volatile("{\n.reg .pred p;\nsetp.ne.b32 p, %1, 0;\n@p mbarrier.arrive.shared::cluster.b64 _, [%0];\n}\n" ::"r"(addr), "r"((int)on) : "memory");
}
__device__ __forceinline__ void mbar_arrive_cluster_n(uint32_t n, uint32_t addr) {
  asm volatile("{\n.reg .pred p;\nsetp.ne.b32 p, %1, 0;\n@p mbarrier.arrive.shared::cluster.b64 _, [%0], %1;\n}\n" ::"r"(addr), "r"(n) : "memory");
}
__device__ __forceinline__ void tma2d(uint32_t dst, const CUtensorMap* m, uint32_t bar, int c0, int c1) {
  asm volatile("cp.async.bulk.tensor.2d.shared::cluster.global.mbarrier::complete_tx::bytes [%0], [%1, {%3, %4}], [%2];"
               ::"r"(dst), "l"(m), "r"(bar), "r"(c0), "r"(c1) : "memory");
}
__device__ __forceinline__ void tma3d(uint32_t dst, const CUtensorMap* m, uint32_t bar, int c0, int c1, int c2) {
  asm volatile("cp.async.bulk.tensor.3d.shared::cluster.global.mbarrier::complete_tx::bytes [%0], [%1, {%3, %4, %5}], [%2];"
               ::"r"(dst), "l"(m), "r"(bar), "r"(c0), "r"(c1), "r"(c2) : "memory");
}
__device__ __forceinline__ void tma2d_hint(uint32_t dst, const CUtensorMap* m, uint32_t bar, int c0, int c1, uint64_t pol) {
  asm volatile("cp.async.bulk.tensor.2d.shared::cluster.global.mbarrier::complete_tx::bytes.L2::cache_hint [%0], [%1, {%3, %4}], [%2], %5;"
               ::"r"(dst), "l"(m), "r"(bar), "r"(c0), "r"(c1), "l"(pol) : "memory");
}
__device__ __forceinline__ void tma3d_mc_hint(uint32_t dst, const CUtensorMap* m, uint32_t bar, int c1, int c2, uint64_t pol) {
  asm volatile("cp.async.bulk.tensor.3d.shared::cluster.global.mbarrier::complete_tx::bytes.multicast::cluster.L2::cache_hint"
               " [%0], [%1, {%3, %4, %5}], [%2], %6, %7;"
               ::"r"(dst), "l"(m), "r"(bar), "r"(0), "r"(c1), "r"(c2), "h"((uint16_t)3), "l"(pol) : "memory");
}
__device__ __forceinline__ void tma5d_mc_hint(uint32_t dst, const CUtensorMap* m, uint32_t bar, int c2, int c4, uint64_t pol) {
  asm volatile("cp.async.bulk.tensor.5d.shared::cluster.global.mbarrier::complete_tx::bytes.multicast::cluster.L2::cache_hint"
               " [%0], [%1, {%3, %3, %4, %3, %5}], [%2], %6, %7;"
               ::"r"(dst), "l"(m), "r"(bar), "r"(0), "r"(c2), "r"(c4), "h"((uint16_t)3), "l"(pol) : "memory");
}
__device__ __forceinline__ void tma3d_store(const CUtensorMap* m, uint32_t src, int c0, int c1, int c2) {
  asm volatile("cp.async.bulk.tensor.3d.global.shared::cta.bulk_group [%0, {%2, %3, %4}], [%1];"
               ::"l"(m), "r"(src), "r"(c0), "r"(c1), "r"(c2) : "memory");
}
__device__ __forceinline__ void bar_sync(int id, int n) { asm volatile("bar.sync %0, %1;" ::"r"(id), "r"(n) : "memory"); }
__device__ __forceinline__ uint32_t pack_bf16(float lo, float hi) {
  uint32_t r;
  asm("cvt.rn.bf16x2.f32 %0, %1, %2;" : "=r"(r) : "f"(hi), "f"(lo));
  return r;
}
__device__ __forceinline__ float ex2(float x) {
  float y;
  asm("ex2.approx.ftz.f32 %0, %1;" : "=f"(y) : "f"(x));
  return y;
}
__device__ __forceinline__ float rcp(float x) {
  float y;
  asm("rcp.approx.ftz.f32 %0, %1;" : "=f"(y) : "f"(x));
  return y;
}
__device__ __forceinline__ void stsm4(uint32_t addr, uint32_t a, uint32_t b, uint32_t c, uint32_t d) {
  asm volatile("stmatrix.sync.aligned.m8n8.x4.shared.b16 [%0], {%1, %2, %3, %4};" ::"r"(addr), "r"(a), "r"(b), "r"(c), "r"(d) : "memory");
}

__device__ __forceinline__ void tma4d_mc_hint(uint32_t dst, const CUtensorMap* m, uint32_t bar, int c3, uint64_t pol) {
  asm volatile("cp.async.bulk.tensor.4d.shared::cluster.global.mbarrier::complete_tx::bytes.multicast::cluster.L2::cache_hint"
               " [%0], [%1, {%3, %3, %3, %4}], [%2], %5, %6;"
               ::"r"(dst), "l"(m), "r"(bar), "r"(0), "r"(c3), "h"((uint16_t)3), "l"(pol) : "memory");
}
__device__ __forceinline__ void bulk_load_hint(uint32_t dst, const void* src, uint32_t bytes, uint32_t bar, uint64_t pol) {
  asm volatile("cp.async.bulk.shared::cluster.global.mbarrier::complete_tx::bytes.L2::cache_hint [%0], [%1], %2, [%3], %4;"
               ::"r"(dst), "l"(src), "r"(bytes), "r"(bar), "l"(pol) : "memory");
}
__device__ __forceinline__ void stg2_if(bool on, void* p, uint32_t a, uint32_t b, uint32_t c, uint32_t d, uint32_t e, uint32_t f,
                                        uint32_t g, uint32_t h, uint64_t pol) {
  asm volatile("{\n.reg .pred p;\nsetp.ne.b32 p, %10, 0;\n"
               "@p st.global.L2::cache_hint.v4.b32 [%0], {%1, %2, %3, %4}, %9;\n"
               "@p st.global.L2::cache_hint.v4.b32 [%0 + 512], {%5, %6, %7, %8}, %9;\n}\n"
               ::"l"(p), "r"(a), "r"(b), "r"(c), "r"(d), "r"(e), "r"(f), "r"(g), "r"(h), "l"(pol), "r"((int)on) : "memory");
}
__device__ __forceinline__ uint64_t evict_first() {
  uint64_t p;
  asm("createpolicy.fractional.L2::evict_first.b64 %0, 1.0;" : "=l"(p));
  return p;
}
__device__ __forceinline__ uint64_t no_hint() {
  uint64_t p;
  asm("createpolicy.cvt.L2.b64 %0, %1;" : "=l"(p) : "l"(static_cast<uint64_t>(cuda::access_property{})));
  return p;
}
__device__ __forceinline__ bool elect() {
  uint32_t ok;
  asm volatile("{\n.reg .pred p;\nelect.sync _|p, 0xffffffff;\nselp.u32 %0, 1, 0, p;\n}\n" : "=r"(ok));
  return ok;
}
__device__ __forceinline__ void mbar_arrive(uint32_t bar) {
  asm volatile("mbarrier.arrive.shared::cta.b64 _, [%0];" ::"r"(bar) : "memory");
}
__device__ __forceinline__ void mbar_arrive_if(bool on, uint32_t bar) {
  asm volatile("{\n.reg .pred p;\nsetp.ne.b32 p, %1, 0;\n@p mbarrier.arrive.shared::cta.b64 _, [%0];\n}\n" ::"r"(bar), "r"((int)on) : "memory");
}
__device__ __forceinline__ void lds2_if(bool on, uint32_t p, uint32_t (&t)[8]) {
  asm volatile("{\n.reg .pred p;\nsetp.ne.b32 p, %9, 0;\n@p ld.shared.v4.b32 {%0, %1, %2, %3}, [%8];\n@p ld.shared.v4.b32 {%4, %5, %6, %7}, [%8 + 512];\n}\n"
               : "+r"(t[0]), "+r"(t[1]), "+r"(t[2]), "+r"(t[3]), "+r"(t[4]), "+r"(t[5]), "+r"(t[6]), "+r"(t[7]) : "r"(p), "r"((int)on) : "memory");
}
__device__ __forceinline__ void lds128(uint32_t p, uint32_t& a, uint32_t& b, uint32_t& c, uint32_t& d) {
  asm volatile("ld.shared.v4.b32 {%0, %1, %2, %3}, [%4];" : "=r"(a), "=r"(b), "=r"(c), "=r"(d) : "r"(p) : "memory");
}
template <class T> __device__ __forceinline__ T* ptr_add(T* base, uint32_t bytes) {
  T* r;
  asm("{\n.reg .u32 lo, hi;\nmov.b64 {lo, hi}, %1;\nadd.cc.u32 lo, lo, %2;\naddc.u32 hi, hi, 0;\nmov.b64 %0, {lo, hi};\n}\n" : "=l"(r) : "l"(base), "r"(bytes));
  return r;
}
__device__ __forceinline__ uint32_t lds32(uint32_t p) {
  uint32_t v;
  asm volatile("ld.volatile.shared.u32 %0, [%1];" : "=r"(v) : "r"(p) : "memory");
  return v;
}
__device__ __forceinline__ uint32_t flag_get(const unsigned int* p) {
  uint32_t v;
  asm volatile("ld.acquire.gpu.global.u32 %0, [%1];" : "=r"(v) : "l"(p) : "memory");
  return v;
}
__device__ __forceinline__ uint32_t wait_word(uint32_t p, uint32_t target) {
  uint32_t v;
  asm volatile("{\n.reg .pred p;\n.reg .u32 n;\nmov.u32 n, 0;\n"
               "LOOP:\nld.acquire.cta.shared.u32 %0, [%1];\nsetp.ge.u32 p, %0, %2;\n@p bra DONE;\n"
               "nanosleep.u32 %3;\nadd.u32 n, n, 1;\nsetp.lt.u32 p, n, 0x400000;\n@p bra LOOP;\ntrap;\n"
               "DONE:\n}\n" : "=r"(v) : "r"(p), "r"(target), "n"(400) : "memory");
  return v;
}
__device__ __forceinline__ void flag_set(unsigned int* p, uint32_t v) {
  asm volatile("st.release.gpu.global.u32 [%0], %1;" ::"l"(p), "r"(v) : "memory");
}
__device__ __forceinline__ void flag_dec(unsigned int* p) {
  asm volatile("red.relaxed.gpu.global.add.u32 [%0], 0xffffffff;" ::"l"(p) : "memory");
}

struct Cursor {
  uint32_t n;
  __device__ __forceinline__ uint32_t off() const { return n & (8 * NBAR - 8); }
  __device__ __forceinline__ uint32_t ph() const { return (n / (8 * NBAR)) & 1; }
  __device__ __forceinline__ void next() { n += 8; }
};

constexpr float kScaleLog2 = 0.07216878364870322f * 1.4426950408889634f;
constexpr float kSumLimit = 1048576.0f;

__global__ void __cluster_dims__(2, 1, 1) __launch_bounds__(384, 1)
fused_kernel(const __grid_constant__ Params P) {
  extern __shared__ uint8_t smem_raw[];
  const uint32_t sbase = (smem_u32(smem_raw) + 1023) & ~1023u;
  const uint32_t full0 = sbase + RING, empty0 = full0 + 8 * NBAR, odone0 = empty0 + 8 * NBAR, ev0 = odone0 + 8 * MAX_OPS;
  const uint32_t progress = ev0 + 8 * MAX_EV, jobw = progress + 4;
  const uint32_t rank = blockIdx.x & 1;
  const int role = blockIdx.x >> 1;
  const int wid = __shfl_sync(0xffffffffu, (int)(threadIdx.x >> 5), 0);
  const int wg = wid >> 2;

  if (wid < 8) {
    if (elect()) {
#pragma unroll
      for (int j = 0; j < 16; j++) {
        const int i = EARLY + 16 * wid + j;
        if (i < 2 * NBAR + MAX_OPS + MAX_EV) mbar_init(full0 + 8 * i, i < NBAR ? 1 : i < 2 * NBAR ? 16 : i < 2 * NBAR + MAX_OPS ? 8 : 1);
      }
      if (wid == 7) asm volatile("st.shared.v2.u32 [%0], {0, 0};\nfence.acq_rel.cta;" ::"r"(progress) : "memory");
      asm volatile("fence.mbarrier_init.release.cluster;" ::: "memory");
    }
  } else if (wid > 8) {
    const uint32_t g = blockIdx.x * 96 + threadIdx.x - 288, w = g - 2048;
    if (g < 4096) asm volatile("prefetch.global.L2 [%0];" ::"l"(g < 2048 ? P.xw[0] + g * (kD * 2) : P.xw[1] + (w >> 5) * (kHD * 2) + (w & 31) * 128));
  } else {
    const uint32_t op0 = P.first[role];
    if (elect()) {
#pragma unroll
      for (int k = 0; k < EARLY; k++) mbar_init(full0 + 8 * k, 1);
      asm volatile("fence.mbarrier_init.release.cluster;" ::: "memory");
      const int blk = (op0 >> 10) & 1;
      if ((op0 & 3) == OP_Q) {
#pragma unroll
        for (int k = 0; k < EARLY; k++) {
          mbar_expect(full0 + 8 * k, SZ_Q);
          tma2d(sbase + k * SZ_Q, &P.x[blk], full0 + 8 * k, 64 * k, ((op0 >> 7) & 7) * kSq + rank * 128);
          tma3d(sbase + k * SZ_Q + 16384, &P.wq[blk], full0 + 8 * k, 0, 64 * k, 3 * ((op0 >> 2) & 31));
          tma3d(sbase + k * SZ_Q + 28672, &P.wq[blk], full0 + 8 * k, 0, 64 * k + 32, 3 * ((op0 >> 2) & 31));
        }
      }
      asm volatile("prefetch.tensormap [%0];\nprefetch.tensormap [%1];" ::"l"(&P.k[blk]), "l"(&P.v[blk]) : "memory");
    }
  }
  __syncwarp();
  asm volatile("barrier.cluster.arrive.relaxed.aligned;\nbarrier.cluster.wait.aligned;" ::: "memory");

  if (wg < 2) {
    asm volatile("setmaxnreg.inc.sync.aligned.u32 240;");
    const uint32_t* prog = P.prog[role].c;
    const int wid = __shfl_sync(0xffffffffu, (int)(threadIdx.x >> 5), 1), wg = wid >> 2;
    const int lane = threadIdx.x & 31, warp = wid & 3;
    uint32_t empty_rem;
    asm volatile("mapa.shared::cluster.u32 %0, %1, %2;" : "=r"(empty_rem) : "r"(empty0), "r"(lane & 1));
    uint32_t keep = (threadIdx.x & 127) < 2 ? 4 : 0;
    auto release = [&](int slot) { mbar_arrive_cluster_n(keep, empty_rem + slot); };
    auto release_warp = [&](int slot, bool on = true) { mbar_arrive_cluster_if(lane < 2 && on, empty_rem + slot); };
    Cursor r{0};
    const uint32_t ring16 = (sbase & 0x3FFFF) >> 4;
    uint32_t cur = ring16;
    bool rdy0 = false, rdy1 = false;
    auto probe1 = [&]() { rdy0 = mbar_test(full0 + r.off(), r.ph()); };
    auto probe2 = [&]() {
      Cursor n = r;
      rdy0 = mbar_test(full0 + n.off(), n.ph());
      n.next();
      rdy1 = mbar_test(full0 + n.off(), n.ph());
    };
    auto advance = [&](uint32_t bytes, uint32_t& addr) {
      const int bi = r.off();
      r.next();
      if (cur > ring16 + ((RING - bytes) >> 4)) cur = ring16;
      addr = cur;
      cur += bytes >> 4;
      return bi;
    };
    auto take = [&](bool rdy, uint32_t bytes, uint32_t& addr) {
      if (__builtin_expect(!__all_sync(0xffffffffu, rdy), 0)) mbar_wait(full0 + r.off(), r.ph());
      return advance(bytes, addr);
    };
    const bool never = P.dbg == 0xffffffffu;
    uint32_t q[48];
#pragma unroll
    for (int i = 0; i < 48; i++) q[i] = 0;
    const int row = wg * 64 + warp * 16 + (lane >> 2);
    const int img0 = row * 4 + ((lane & 3) ^ ((row >> 1) & 3));
    uint4* pend = nullptr;
    bool pend_any = false;
    const uint64_t spol = evict_first();
    int pc = 0;
    auto slab = [&](int c, int i0) {
#pragma unroll
      for (int i = i0; i < 6; i++)
        stg2_if(c == i, pend + i * 512, q[8 * i], q[8 * i + 1], q[8 * i + 2], q[8 * i + 3],
                q[8 * i + 4], q[8 * i + 5], q[8 * i + 6], q[8 * i + 7], spol);
    };
    auto drain = [&](int c) {
      if (!pend_any || c >= 6) return;
      slab(c, 0);
      if (c == 5) {
        __syncwarp();
        mbar_arrive_if(lane == 0, odone0 - 8 + 8 * pc);
      }
    };

    for (;; pc++) {
      uint32_t op = prog[pc];
      const int type = op & 3;
      auto enter = [&]() {
        r.n = (op >> 12) & 248; cur = ring16 + (((op >> 20) & 63) << 8);
      };
      enter();
      pend_any = op & C_PEND;
      uint32_t job = 0;
      if ((op & (3 | C_WIDE)) == OP_O) job = __shfl_sync(0xffffffffu, wait_word(jobw, 1), 0);
      if (type == OP_END || job == OP_O) {
#pragma unroll 1
        for (int c = 0; c < 6; c++) drain(c);
        asm volatile("barrier.cluster.arrive.relaxed;" ::: "memory");
        break;
      }
      {
        float s[32], o[96];
        uint32_t ad0;
        int bi0, sk1;
        uint32_t pa[16], pb[16];
        float mc0, mc1, l0, l1;
        bool shifted;
        uint32_t nop;
        auto expo = [&](float (&s)[32], uint32_t (&pout)[16], float& b0, float& b1, bool shift, auto mid) {
          float c0, c1;
#pragma unroll
          for (int i = 0; i < 8; i++) {
            const float e0 = ex2(shift ? s[4 * i] - mc0 : s[4 * i]), e1 = ex2(shift ? s[4 * i + 1] - mc0 : s[4 * i + 1]);
            const float e2 = ex2(shift ? s[4 * i + 2] - mc1 : s[4 * i + 2]), e3 = ex2(shift ? s[4 * i + 3] - mc1 : s[4 * i + 3]);
            if (i) { b0 += e0; c0 += e1; b1 += e2; c1 += e3; } else { b0 = e0; c0 = e1; b1 = e2; c1 = e3; }
            pout[2 * i] = pack_bf16(e0, e1); pout[2 * i + 1] = pack_bf16(e2, e3);
            if (i & 1) mid(i >> 1);
          }
          b0 += c0; b1 += c1;
        };
        auto rowmax = [&](float (&s)[32], float& m0, float& m1) {
          m0 = fmaxf(s[0], s[1]); m1 = fmaxf(s[2], s[3]);
#pragma unroll
          for (int i = 1; i < 8; i++) { m0 = fmaxf(m0, fmaxf(s[4 * i], s[4 * i + 1])); m1 = fmaxf(m1, fmaxf(s[4 * i + 2], s[4 * i + 3])); }
          m0 = fmaxf(m0, __shfl_xor_sync(0xffffffffu, m0, 1)); m1 = fmaxf(m1, __shfl_xor_sync(0xffffffffu, m1, 1));
          m0 = fmaxf(m0, __shfl_xor_sync(0xffffffffu, m0, 2)); m1 = fmaxf(m1, __shfl_xor_sync(0xffffffffu, m1, 2));
        };
        auto first = [&](float (&s)[32], int sk0, auto mid) {
          fence_regs(s);
          release(sk0);
          mc0 = 0.f; mc1 = 0.f;
          expo(s, pa, l0, l1, false, mid);
          shifted = __any_sync(0xffffffffu, !(fmaxf(l0, l1) <= kSumLimit && fminf(l0, l1) >= 1.f / kSumLimit));
          if (shifted) {
            rowmax(s, mc0, mc1);
            expo(s, pa, l0, l1, true, [](int) {});
          }
        };
        auto qk = [&](float (&s)[32], uint32_t ak, int k0 = 0, int k1 = 12) {
#pragma unroll
          for (int kk = k0; kk < k1; kk++)
            wgmma_rs_n64<0>(s, q[4 * kk], q[4 * kk + 1], q[4 * kk + 2], q[4 * kk + 3], mk_desc(ak, 16, KV_SBO, 1) + ((kk >> 2) * KV_CH + (kk & 3) * 2), kk != 0);
          if (k1 == 12) wg_commit();
        };
        auto pv = [&](uint32_t (&pin)[16], uint32_t av, int acc, int k0 = 0, int k1 = 4) {
#pragma unroll
          for (int kk = k0; kk < k1; kk++)
            wgmma_rs_n192<1>(o, pin[4 * kk], pin[4 * kk + 1], pin[4 * kk + 2], pin[4 * kk + 3], mk_desc(av, KV_CH * 16, KV_SBO, 1) + (kk * (KV_SBO / 8)), acc || (kk != 0));
          if (k0 == 0) wg_commit();
        };
        auto finish = [&](uint32_t (&pout)[16], int sk, int sv, bool part = false) {
          probe1();
          wg_wait<1>();
          fence_regs(s);
          release(sk);
          float b0, b1;
#pragma unroll 1
          for (bool redo = false;; redo = true) {
            expo(s, pout, b0, b1, false, [](int) {});
            if (!__any_sync(0xffffffffu, !redo && (shifted || !(fmaxf(b0, b1) <= kSumLimit)))) break;
            shifted = true;
            rowmax(s, b0, b1);
            b0 = fmaxf(mc0, b0); b1 = fmaxf(mc1, b1);
            const float a0 = ex2(mc0 - b0), a1 = ex2(mc1 - b1);
            mc0 = b0; mc1 = b1;
            l0 *= a0; l1 *= a1;
            wg_wait<0>();
            fence_regs(o);
#pragma unroll
            for (int i = 0; i < 24; i++) { o[4 * i] *= a0; o[4 * i + 1] *= a0; o[4 * i + 2] *= a1; o[4 * i + 3] *= a1; }
#pragma unroll
            for (int i = 0; i < 32; i++) s[i] -= (i & 2) ? mc1 : mc0;
            if (part) {
#pragma unroll
              for (int i = 8; i < 16; i++)
                pa[i] = pack_bf16(__uint_as_float(pa[i] << 16) * ((i & 1) ? a1 : a0), __uint_as_float(pa[i] & 0xffff0000u) * ((i & 1) ? a1 : a0));
            }
          }
          l0 += b0; l1 += b1;
          wg_wait<0>();
          fence_regs(o);
          mbar_arrive_cluster_n(part ? 0 : keep, empty_rem + sv);
        };
        uint32_t pav;
        int psv;
        auto step = [&](uint32_t (&pin)[16], uint32_t (&pout)[16], bool part) {
          uint32_t ak;
          const int sk = take(rdy0, SZ_KV, ak);
          psv = advance(SZ_KV, pav);
          wg_fence();
          qk(s, ak);
          if (part) { wg_fence(); pv(pin, pav, 1, 0, 2); } else { asm volatile(""); wg_fence(); pv(pin, pav, 1); }
          finish(pout, sk, psv, part);
        };
        auto unpark = [&](uint32_t& ak) {
          uint32_t ad;
          const Cursor k0 = r;
          const int sk0 = advance(SZ_KV, ak), bi = take(false, SZ_PARK, ad);
#pragma unroll
          for (int i = 0; i < 12; i++) lds128(sbase + (ad - ring16 + img0) * 16 + (i >> 1) * 8192 + (i & 1) * 512, q[4 * i], q[4 * i + 1], q[4 * i + 2], q[4 * i + 3]);
          if (!__all_sync(0xffffffffu, rdy0)) mbar_wait(full0 + k0.off(), k0.ph());
          fence_regs(q);
          release_warp(bi);
          wg_fence();
          qk(s, ak, 0, 4);
          wg_commit();
          return sk0;
        };
        auto mma4 = [&](uint32_t ad, int acc) {
#pragma unroll
          for (int kk = 0; kk < 4; kk++)
            wgmma_ss_n192<1>(o, mk_desc(ad + wg * 512, 16, 1024, 1) + (kk * 2), mk_desc(ad, 4096, 1024, 1) + (1024 + (kk >> 1) * 768 + (kk & 1) * 128), acc || kk != 0);
        };
        auto convert = [&](int i0, int i1) {
          sched_fence(keep, never);
#pragma unroll
          for (int i = i0; i < i1; i++) {
            q[i] = pack_bf16(o[2 * i] * kScaleLog2, o[2 * i + 1] * kScaleLog2);
            if ((i & 7) == 7 && i != i1 - 1) sched_fence(keep, never);
          }
          sched_fence(keep, never);
        };
        if (type == OP_O) {
          int prev = 0;
          if (op & C_WIDE) {
            float d[64];
            auto mma3 = [&](uint32_t ad, int h, int acc) {
#pragma unroll
              for (int kk = 0; kk < 2; kk++)
                wgmma_ss_n192<1>(o, mk_desc(ad + wg * 256, 16, 512, 2) + (h * 512 + kk * 2), mk_desc(ad, 4096, 1024, 1) + (1024 + h * 768 + kk * 128), acc || kk);
            };
            auto mma2 = [&](uint32_t ad, uint32_t ob, int h, int acc) {
#pragma unroll
              for (int kk = 0; kk < 2; kk++)
                wgmma_ss_n128<1>(d, mk_desc(ad + wg * 256, 16, 512, 2) + (h * 512 + kk * 2), mk_desc(ad, 4096, 1024, 1) + (ob + h * 512 + kk * 128), acc || kk);
            };
            auto wstep = [&](uint32_t bytes, int acc, auto hook) {
              uint32_t ad;
              const int bi = take(rdy0, bytes, ad);
              wg_fence();
              if (bytes == SZ_W2) mma2(ad, 1024, 0, 1); else mma3(ad, 0, acc);
              if (bytes == SZ_W) mma3(ad, 1, 1);
              wg_commit();
              if (acc) { wg_wait<1>(); release(prev); }
              if (bytes == SZ_W) mma2(ad, 2560, 0, acc);
              if (bytes == SZ_W3) mma3(ad, 1, 1); else mma2(ad, bytes == SZ_W ? 2560 : 1024, 1, 1);
              wg_commit();
              prev = bi;
              hook();
              probe1();
              wg_wait<1>();
            };
            undefine(o);
            wstep(SZ_W, 0, [&]() { drain(0); });
#pragma unroll 1
            for (int k = 1; k < ((op >> 2) & 127) - TAIL; k++) wstep(SZ_W, 1, [&]() { drain(k); });
#pragma unroll 1
            for (int k = 0; k < TAIL; k++) wstep(SZ_W2, 1, []() {});
            pend = ptr_add(P.g->part, (((op >> 9) & 31) * 2 + rank) * 81920 + 4 * 8192 + img0 * 16);
            wstep(SZ_W3, 1, [&]() {
              fence_regs(d);
#pragma unroll
              for (int i = 0; i < 32; i++) q[16 + i] = pack_bf16(d[2 * i], d[2 * i + 1]);
              slab(2, 2);
            });
#pragma unroll 1
            for (int k = 3; k < 6; k++) wstep(SZ_W3, 1, [&]() { slab(k, 2); });
            op = prog[pc + 1];
            enter();
            pend_any = true;
            pend -= 4 * 512;
            bi0 = take(rdy0 || (op & 3) != OP_Q, SZ_Q, ad0);
            sched_fence(keep, never);
            wg_wait<0>();
            fence_regs(o);
            release(prev);
#pragma unroll
            for (int i = 0; i < 48; i++) q[i] = pack_bf16(o[2 * i], o[2 * i + 1]);
            if ((op & 3) != OP_Q) continue;
            pc++;
            goto first_step;
          }
          float c[80];
          auto mma2 = [&](uint32_t ad, uint32_t oa, uint32_t ob, int acc) {
            wgmma_ss_n160<1>(c, mk_desc(ad + wg * 256, 16, 512, 2) + (oa), mk_desc(ad, 2048, 512, 2) + (1024 + ob), acc);
            wgmma_ss_n160<1>(c, mk_desc(ad + wg * 256, 16, 512, 2) + (oa + 2), mk_desc(ad, 2048, 512, 2) + (1024 + ob + 64), 1);
          };
          auto kstep = [&](int acc, auto hook, uint32_t bytes = SZ_O) {
            uint32_t ad;
            const int bi = take(rdy0, bytes, ad);
            wg_fence();
            mma2(ad, 0, 0, acc);
            wg_commit();
            if (acc) wg_wait<1>();
            if (acc == 1) release(prev);
            if (acc > 1) release_warp(prev, acc == 2 || wg == 0);
            mma2(ad, 512, 640, 1);
            wg_commit();
            prev = bi;
            hook();
            probe1();
            wg_wait<1>();
          };
          auto unblock = [&](int k) {
            if (__all_sync(0xffffffffu, rdy0) || __all_sync(0xffffffffu, mbar_try(full0 + r.off(), r.ph(), 1500))) return;
#pragma unroll 1
            for (; k < 6; k++) drain(k);
            pend_any = false;
          };
          unblock(0);
          kstep(0, [&]() { drain(0); });
          int left = ((job >> 13) & 127) - 6;
#pragma unroll 1
          for (uint32_t k = 1, pace = left >= 22 ? 0x4511 : left <= 11 ? 0x1a : 0x155; left > 0; pace >>= 2, left--) {
            unblock(k);
            kstep(1, [&]() {
#pragma unroll 1
              for (int i = pace & 3; i > 0; i--) drain(k++);
            });
          }
          uint32_t t[8], stage[3];
          float u[80];
          auto unpack = [&](int j) {
#pragma unroll
            for (int i = 0; i < 8; i++) {
              u[16 * j + 2 * i] = __uint_as_float(t[i] << 16); u[16 * j + 2 * i + 1] = __uint_as_float(t[i] & 0xffff0000u);
              asm volatile("" : "+f"(u[16 * j + 2 * i]), "+f"(u[16 * j + 2 * i + 1]));
            }
          };
#pragma unroll
          for (int i = 0; i < 8; i++) t[i] = 0;
          const uint32_t bytes = (job & P_LD) ? SZ_OL : SZ_O;
#pragma unroll
          for (int j = 0; j < 5; j++) {
            if (j == 2 && wg == 1) {
              wg_wait<0>();
              release_warp(prev);
              bar_sync(1, 256);
            }
            kstep(j == 2 ? 3 : 2, [&]() {
              if (j == 4) asm volatile("{\n.reg .pred p;\nsetp.eq.u32 p, %0, 0;\n@p bar.arrive 1, 256;\n}\n" ::"r"(wg) : "memory");
              if (j) unpack(j - 1);
              lds2_if(job & P_LD, sbase + (cur - ring16 + img0) * 16 - 8192, t);
              if (j >= 1 && j <= 3) stage[j - 1] = sbase + (cur - ring16) * 16 - bytes + wid * 1024;
            }, bytes);
          }
          unpack(4);
          uint32_t lane16 = (lane & 15) * 64;
          const int orow = ((job >> 7) & 7) * kSq + rank * 128 + wid * 16, ocol = ((job >> 10) & 1) * 20 + ((job >> 20) & 3) * 5;
          sched_fence(lane16, never);
          wg_wait<0>();
          fence_regs(c);
          release_warp(prev);
          asm volatile("barrier.cluster.arrive.relaxed;" ::: "memory");
#pragma unroll
          for (int i = 0; i < 10; i++) {
            const int v = (i & 1) * 2 + (lane >> 4);
            const uint32_t sa = stage[i >> 2] + (i & 2) * 4096;
            stsm4(sa + lane16 + ((v ^ ((lane >> 1) & 3)) << 4), pack_bf16(c[8 * i] + u[8 * i], c[8 * i + 1] + u[8 * i + 1]),
                  pack_bf16(c[8 * i + 2] + u[8 * i + 2], c[8 * i + 3] + u[8 * i + 3]), pack_bf16(c[8 * i + 4] + u[8 * i + 4], c[8 * i + 5] + u[8 * i + 5]),
                  pack_bf16(c[8 * i + 6] + u[8 * i + 6], c[8 * i + 7] + u[8 * i + 7]));
            if (i != 3 && i != 9) continue;
            asm volatile("fence.proxy.async.shared::cta;" ::: "memory");
            __syncwarp();
            if (elect()) {
#pragma unroll
              for (int j = i == 3 ? 0 : 2; 2 * j < i; j++) tma3d_store(&P.out, stage[j >> 1] + (j & 1) * 8192, 0, orow, ocol + j);
            }
            if (i == 3) sched_fence(lane16, never);
          }
          if (elect()) asm volatile("cp.async.bulk.commit_group;\ncp.async.bulk.wait_group.read 0;" ::: "memory");
          __syncwarp();
          break;
        }
        bi0 = take(rdy0, SZ_Q, ad0);
      first_step:
        undefine(o);
        wg_fence();
        mma4(ad0, 0);
        wg_commit();
        {
          uint32_t ad1;
          const int bi1 = take(false, SZ_Q, ad1);
          wg_fence();
          mma4(ad1, 1);
          wg_commit();
          drain(0);
          wg_wait<1>();
          release(bi0);
          drain(1);
          probe1();
          wg_wait<0>();
          release(bi1);
          fence_regs(o);
#pragma unroll 1
          for (int k = 2; k < 8; k++) {
            uint32_t ad;
            const int bi = take(rdy0, SZ_Q, ad);
            wg_fence();
            mma4(ad, 1);
            wg_commit();
            drain((0x54732710u >> (4 * k)) & 7);
            probe1();
            wg_wait<0>();
            release(bi);
          }
          uint32_t a8, a9, ak0, ak1;
          const int b8 = take(rdy0, SZ_Q, a8), b9 = take(false, SZ_Q, a9);
          wg_fence();
          mma4(a8, 1);
          wg_commit();
          mma4(a9, 1);
          wg_commit();
          wg_wait<1>();
          release(b8);
          probe1();
          const int sk0 = take(rdy0 || (op & F_PARK), SZ_KV, ak0);
          wg_wait<0>();
          fence_regs(o);
          release(b9);
          float s0[32];
          convert(0, 32);
          if (op & F_PARK) {
            convert(32, 48);
            pend = ptr_add(P.g->tile, (((op >> 2) & 511) * 2 + rank) * SZ_PARK + img0 * 16);
            continue;
          }
          pc++;
          wg_fence();
          qk(s0, ak0, 0, 4);
          convert(32, 48);
          wg_fence();
          qk(s0, ak0, 4, 12);
          sk1 = take(false, SZ_KV, ak1);
          wg_fence();
          qk(s, ak1, 0, 4);
          wg_commit();
          probe1();
          wg_wait<1>();
          first(s0, sk0, [&](int i) {
            if (!(i & 1)) return;
            sched_fence(keep, never);
            wg_fence();
            if (i == 1) qk(s, ak1, 4, 8);
            if (i == 3) qk(s, ak1, 8, 12);
            sched_fence(keep, never);
          });
        }
        for (;;) {
          {
            uint32_t av;
            const int sv = take(rdy0, SZ_KV, av);
            undefine(o);
            wg_fence();
            pv(pa, av, 0);
            finish(pb, sk1, sv);
          }
          nop = prog[pc + 1];
#pragma unroll 1
          for (int jj = 0; jj < 7; jj++) {
            step(pb, pa, false);
            step(pa, pb, jj == 6);
          }
          float i0, i1;
          auto last = [&]() {
            uint32_t av;
            const int sv = take(rdy0, SZ_KV, av);
            wg_fence();
            pv(pa, pav, 1, 2, 4);
            pv(pb, av, 1);
            sched_fence(keep, never);
            probe1();
            l0 += __shfl_xor_sync(0xffffffffu, l0, 1); l1 += __shfl_xor_sync(0xffffffffu, l1, 1);
            l0 += __shfl_xor_sync(0xffffffffu, l0, 2); l1 += __shfl_xor_sync(0xffffffffu, l1, 2);
            i0 = rcp(l0); i1 = rcp(l1);
            pend = ptr_add(P.g->tile, (((op >> 2) & 511) * 2 + rank) * SZ_PARK + img0 * 16);
            return sv;
          };
          auto normalise = [&](uint32_t (&d)[48], auto mid) {
#pragma unroll
            for (int i = 0; i < 24; i++) {
              d[8 * (i >> 2) + (i & 3)] = pack_bf16(o[4 * i] * i0, o[4 * i + 1] * i0);
              d[8 * (i >> 2) + (i & 3) + 4] = pack_bf16(o[4 * i + 2] * i1, o[4 * i + 3] * i1);
              if ((i & 1) && i != 23) sched_fence(keep, never);
              if ((i & 3) == 3 && i != 23) mid(i >> 2);
            }
          };
          const int sv = last();
          if ((nop & 3) != OP_A) {
            op = nop;
            enter();
            pend_any = true;
            bi0 = take(rdy0 || (nop & 3) != OP_Q, SZ_Q, ad0);
            sched_fence(keep, never);
            wg_wait<0>();
            fence_regs(o);
            release(psv);
            release(sv);
            normalise(q, [](int) {});
            undefine(o);
            if ((nop & 3) != OP_Q) break;
            pc++;
            goto first_step;
          }
          uint32_t ak0;
          const int sk0 = unpark(ak0);
          wg_wait<1>();
          fence_regs(o);
          release(psv);
          release(sv);
          uint32_t t[48];
          auto st = [&](int i) {
            stg2_if(true, pend + i * 512, t[8 * i], t[8 * i + 1], t[8 * i + 2], t[8 * i + 3], t[8 * i + 4], t[8 * i + 5], t[8 * i + 6], t[8 * i + 7], spol);
          };
          normalise(t, [&](int i) {
            if (i & 1) {
              wg_fence();
              if (i == 1) qk(s, ak0, 4, 8);
              if (i == 3) qk(s, ak0, 8, 12);
              sched_fence(keep, never);
            }
            if (!(i & 1)) st(i >> 1);
          });
          probe2();
          wg_wait<0>();
          first(s, sk0, [&](int i) { if (i < 3) { sched_fence(keep, never); st(3 + i); } });
          __syncwarp();
          mbar_arrive_if(lane == 0, odone0 + 8 * pc);
          pc++;
          op = nop;
          uint32_t ak1;
          sk1 = take(rdy0, SZ_KV, ak1);
          rdy0 = rdy1;
          wg_fence();
          qk(s, ak1);
        }
      }
    }
    asm volatile("barrier.cluster.wait;" ::: "memory");
  } else {
    asm volatile("setmaxnreg.dec.sync.aligned.u32 24;");
    const uint32_t* prog = P.prog[role].p;
    unsigned int* flag = P.g->flag + rank;
    if (wid == 11 && (prog[0] & 3) == OP_Q) {
      const uint32_t a = prog[1];
      const char* p = ptr_add(P.kv[rank * 2 + ((a >> 10) & 1)], ((a >> 2) & 255) * (kSk * kDh * 2) + (threadIdx.x & 31) * 128);
#pragma unroll 1
      for (uint32_t k = 0; k < 3; k++) {
        wait_word(progress, 8 * k);
        p += SZ_KV;
        asm volatile("prefetch.global.L2 [%0];\nprefetch.global.L2 [%0 + 4096];" ::"l"(p));
      }
      __syncwarp();
    }
    if (wid == 8) {
      Cursor head{0}, tail{0};
      int sh = 0, room = RING >> 12;
      uint32_t cur = 0;
      uint64_t fifo = 0;
      uint32_t dst, bar = 0, ev = ev0;
      const uint64_t pol = evict_first();
      auto retire = [&]() {
        mbar_wait(empty0 + tail.off(), tail.ph());
        tail.next();
        room += (uint32_t)fifo & 31;
        fifo >>= 5;
        sh -= 5;
        asm volatile("st.volatile.shared.u32 [%0], %1;" ::"r"(progress), "r"(tail.n) : "memory");
      };
      auto acquire = [&](uint32_t bytes) {
        uint32_t fp = bytes >> 12;
        if (cur + fp > (RING >> 12)) { fp += (RING >> 12) - cur; cur = 0; }
        room -= fp;
        while (room < 0) retire();
        fifo |= (uint64_t)fp << sh;
        sh += 5;
        dst = sbase + (cur << 12);
        bar = full0 + head.off();
        cur += bytes >> 12;
        head.next();
      };
      auto gate = [&]() {
        mbar_wait(ev, 0);
        ev += 8;
        asm volatile("fence.proxy.async.global;" ::: "memory");
      };
      for (int pc = 0;; pc++) {
        uint32_t op = prog[pc];
        const int type = op & 3;
        if (type == OP_END) break;
        if (op == OP_O) {
          gate();
          op = __shfl_sync(0xffffffffu, lds32(jobw), 0);
        }
        const int blk = (op >> 10) & 1;
        if (type == OP_Q) {
          const uint64_t px = (op & P_LASTX) ? pol : no_hint(), pw = (op & P_LASTW) ? pol : no_hint();
          int k = 0;
          if (pc == 0) {
            k = 64 * EARLY; head.n = 8 * EARLY; sh = 5 * EARLY; cur = EARLY * (SZ_Q >> 12); room -= cur;
            fifo = (SZ_Q >> 12) * (((1u << (5 * EARLY)) - 1) / 31);
          }
#pragma unroll 1
          for (int stop = (op & P_GATE) ? kD - 64 : kD;; stop = kD) {
#pragma unroll 1
            for (; k < stop; k += 64) {
              acquire(SZ_Q);
              if (elect()) {
                mbar_expect(bar, SZ_Q);
                tma3d_mc_hint(dst + 16384 + rank * 12288, &P.wq[blk], bar, k + 32 * rank, 3 * ((op >> 2) & 31), pw);
                tma2d_hint(dst, &P.x[blk], bar, k, ((op >> 7) & 7) * kSq + rank * 128, px);
              }
            }
            if (k == kD) break;
            gate();
          }
        } else if (type == OP_A) {
          const int row0 = ((op >> 2) & 255) * kSk;
          auto kv = [&](uint32_t tx, const CUtensorMap* m, int c3) {
            const uint32_t before = bar;
            acquire(SZ_KV);
            if (elect()) {
              mbar_expect(bar, tx);
              tma4d_mc_hint(dst + rank * (SZ_KV / 2), m, tx ? bar : before, c3, pol);
            }
          };
          int c3 = row0 / 8 + 4 * rank;
#pragma unroll 1
          for (int j = 0; j <= 16; j++, c3 += 8) {
            const uint32_t tv = j < 2 || j == 16 ? SZ_KV : 0;
            if (j < 16) kv(2 * SZ_KV - tv, &P.k[blk], c3);
            else if (op & P_GATE) gate();
            if (j > 0) kv(tv, &P.v[blk], c3 - 8);
            else if (op & F_PARK) {
              gate();
              acquire(SZ_PARK);
              if (elect()) {
                mbar_expect(bar, SZ_PARK);
                bulk_load_hint(dst, &P.g->tile[(((op >> 20) & 511) * 2 + rank) * 3072], SZ_PARK, bar, pol);
              }
            }
          }
        } else {
          const uint4* part = &P.g->part[((((op >> 6) & 30) + ((op >> 21) & 1)) * 2 + rank) * 5120 + ((op >> 20) & 1) * 2560];
          auto run = [&](const uint32_t bytes, int k, int cnt, int gates) {
            const int col = bytes == SZ_O || bytes == SZ_OL ? 5 * ((op >> 20) & 3) : 5 * ((op >> 21) & 1);
            int row = 8 * k + 4 * rank, pre = bytes == SZ_O && (op & P_PRE) ? 0 : 2560;
#pragma unroll 1
            for (int h = (k * 43) >> 7, k0 = k - 3 * h; cnt > 0; h++, k0 = 0, gates = gates >> 1 | (gates & 2)) {
              const uint4* src = ptr_add(P.g->tile, ((P.slot[((op >> 2) & 480) + h] * 2 + rank) * 3 + k0) * 16384);
              const uint64_t pw = h >= ((op >> 23) & 31) && h < 2 * (op >> 28) ? pol : no_hint();
              if (gates & 1) gate();
              int m = min(3 - k0, cnt);
              cnt -= m;
#pragma unroll 1
              for (; m > 0; m--, src += 1024, row += 8) {
                acquire(bytes);
                if (elect()) {
                  mbar_expect(bar, bytes);
                  if (bytes == SZ_O || bytes == SZ_OL) tma5d_mc_hint(dst + 16384 + rank * 10240, &P.wo[blk], bar, row, col, no_hint());
                  if (bytes == SZ_W || bytes == SZ_W3) tma5d_mc_hint(dst + 16384 + rank * 12288, &P.wo3[blk], bar, row, col, pw);
                  bulk_load_hint(dst, src, 16384, bar, pol);
                  if (bytes == SZ_W || bytes == SZ_W2) tma5d_mc_hint(dst + bytes - 16384 + rank * 8192, &P.wo2[blk], bar, row, col + 3, pw);
                  if (bytes == SZ_OL) bulk_load_hint(dst + SZ_O, part, 8192, bar, pol);
                }
                if (bytes == SZ_OL) part += 512;
              }
              if (pre < 2560) {
                if (elect()) asm volatile("cp.async.bulk.prefetch.L2.global [%0], 10240;" ::"l"(part + pre) : "memory");
                pre += 640;
              }
            }
          };
          const int n = (op >> 13) & 127;
          if (op & P_WIDE) {
            run(SZ_W, 0, n - TAIL, 3);
            run(SZ_W2, n - TAIL, TAIL, (n - TAIL) % 3 ? 2 : 3);
            run(SZ_W3, n - TAIL, TAIL, 0);
          } else {
            if (op & P_PRE) gate();
            run(SZ_O, kSteps - n, (op & P_LD) ? n - 5 : n, 3);
            if (op & P_LD) {
              if (!(op & P_PRE)) gate();
              run(SZ_OL, kSteps - 5, 5, 2);
            }
          }
        }
      }
#pragma unroll 1
      while (sh) retire();
    } else if (threadIdx.x == 288) {
      for (int pc = 0;; pc++) {
        const uint32_t op = prog[pc];
        const int type = op & 3;
        if (type == OP_END) break;
        if (type == OP_Q ? !(op & F_PARK) : type == OP_O && !(op & P_WIDE)) continue;
        const int id = type == OP_A ? (op >> 2) & 511 : type == OP_Q ? N_TILE + ((op >> 13) & 127) : ID_PART + ((op >> 5) & 60) + ((op >> 20) & 3);
        const uint32_t v = type == OP_O ? 1 : P.info[id] & 7;
        mbar_wait_long(odone0 + 8 * pc);
        flag_set(flag + 2 * id, v);
        if (type == OP_O && (op & P_WIDE)) flag_set(flag + 2 * id + 2, v);
      }
    } else if (wid == 10) {
      int i = threadIdx.x & 31;
      const int n_ev = P.prog[role].n_ev;
      auto event = [&]() { return i < n_ev ? P.prog[role].ev[i] : n_ev ? E_JOB | (i - n_ev) : 0; };
      uint32_t e = i < 8 ? event() : 0;
      for (uint32_t n = 0; __any_sync(0xffffffffu, e); n++) {
        uint32_t job = lds32(jobw);
        const int togo = (e & E_DRAW) ? (e & 1023) - (lds32(progress) >> 3) : 99;
        if (togo <= 0 && rank == 0) {
          job = P.job[atomicInc(&P.g->ticket, gridDim.x / 2 - 1)];
          asm volatile("{\n.reg .u32 a;\nmapa.shared::cluster.u32 a, %0, 1;\nst.volatile.shared::cluster.u32 [a], %1;\n"
                       "st.volatile.shared.u32 [%0], %1;\n}\n" ::"r"(jobw), "r"(job) : "memory");
        }
        if ((e & E_JOB) && job) {
          const uint32_t j = e & 63, heads = job == OP_O ? 0 : kH - ((job >> 2) & 31), jp = !(job & P_LD) ? 63 : (job & P_PRE) ? 0 : heads - 1, h = j - (j > jp);
          e = j == jp ? (ID_PART + ((job >> 5) & 60) + ((job >> 20) & 3)) | E_ON | E_LAST : h < heads ? (((job >> 2) & 511) + h) | E_ON | E_LAST : 0;
        }
        unsigned int* f = ptr_add(flag, 8 * (e & 1023));
        const bool ok = (e & E_ON) ? flag_get(f) - 1 < ((e & E_FREE) ? 1 : 7) : (e & E_DRAW) && job;
        if (ok) {
          mbar_arrive(ev0 + 8 * i);
          if (e & (E_FREE | E_LAST)) flag_dec(f);
          i += 8;
          e = event();
        }
        asm volatile("{\n.reg .pred p;\nsetp.ge.u32 p, %0, 0x400000;\n@p trap;\n}\n" ::"r"(n));
        if (!__any_sync(0xffffffffu, ok)) __nanosleep(__any_sync(0xffffffffu, job || togo <= 2) ? 100 : 600);
      }
    } else if (threadIdx.x == 352) {
      uint32_t items = 0;
      auto read = [&](int id) {
        if (!(P.info[id] & I_NEXT)) return;
        wait_word(progress, 8 * items);
        flag_dec(flag + 2 * id);
      };
      for (int pc = 0;; pc++) {
        const uint32_t op = prog[pc];
        const int type = op & 3;
        if (type == OP_END) break;
        if (type == OP_O) {
          const uint32_t n = (op >> 13) & 127, base = items;
#pragma unroll 1
          for (uint32_t k = 3, id = (op >> 2) & 511; k <= n; k += 3, id++) {
            items = base + k + (k + TAIL > n ? TAIL : 0);
            read(id);
          }
          items = base + n + TAIL;
        } else if (type == OP_A) {
          items++;
          if (op & F_PARK) { items++; read(N_TILE + ((op >> 13) & 127)); }
          items += 31;
        } else {
          items += 10;
        }
      }
    }
    __syncwarp();
    asm volatile("barrier.cluster.arrive.relaxed;\nbarrier.cluster.wait;" ::: "memory");
  }
}

typedef CUresult (*EncodeFn)(CUtensorMap*, CUtensorMapDataType, cuuint32_t, void*, const cuuint64_t*, const cuuint64_t*,
                             const cuuint32_t*, const cuuint32_t*, CUtensorMapInterleave, CUtensorMapSwizzle,
                             CUtensorMapL2promotion, CUtensorMapFloatOOBfill);

void encode(EncodeFn fn, CUtensorMap* m, const void* ptr, int rank, const cuuint64_t* dims, const cuuint64_t* strides,
            const cuuint32_t* box, CUtensorMapSwizzle swz) {
  const cuuint32_t es[5] = {1, 1, 1, 1, 1};
  CUresult r = fn(m, CU_TENSOR_MAP_DATA_TYPE_BFLOAT16, rank, const_cast<void*>(ptr), dims, strides, box, es,
                  CU_TENSOR_MAP_INTERLEAVE_NONE, swz, CU_TENSOR_MAP_L2_PROMOTION_L2_128B, CU_TENSOR_MAP_FLOAT_OOB_FILL_NONE);
  if (r != CUDA_SUCCESS) fprintf(stderr, "cuTensorMapEncodeTiled failed: %d\n", (int)r);
}

struct Op { int type, flags, id, n, quarter, park, item0, items; double t0, t1; };
struct Use { double need, freed; int readers, slot, prev; bool next; };
struct PlanStats { double end, slack, park_slack; int slots, parks; uint32_t own[N_CL]; };

bool plan(const char* const* text, int n_pair, int phase, Params& P, PlanStats* stats = nullptr) {
  constexpr double T_Q = 7900, T_A = 24550, T_U = 25900, T_P = 8400, T_O = 640, T_RUN = 800, T_WIDE = 1300, AHEAD = 3500, PUBLISH = 1500;
  const double margin = 256.0 * ((P.dbg >> 8) & 255);
  static Op op[N_CL][MAX_OPS];
  static Use use[ID_PART];
  int n_op[N_CL], covered[2 * N_TEAM] = {};
  struct Ref { double t; Op* o; int id; };
  static Ref att[N_TILE + 1], dem[N_TILE], prk[MAX_PARK + 1], unp[MAX_PARK + 1], wr[ID_PART];
  auto sort = [](Ref* r, int n) {
    for (int i = 1; i < n; i++)
      for (int j = i; j > 0 && r[j].t < r[j - 1].t; j--) { Ref x = r[j]; r[j] = r[j - 1]; r[j - 1] = x; }
  };
  auto hex = [](char c) { return c <= '9' ? c - '0' : c - 'a' + 10; };
  for (int i = 0; i < n_pair; i++)
    for (const char* s = text[i]; *s; s++)
      for (int h = 0; *s == 'J' && h < 2; h++) {
        if (covered[2 * hex(s[1]) + h]) return false;
        covered[2 * hex(s[1]) + h] = 10 * (s[2 + 2 * h] - '0') + s[3 + 2 * h] - '0';
      }
  for (int c = 0; c < 2 * n_pair; c++) {
    int n = 0, items = 0;
    double t = 0;
    auto add = [&](int type, int flags, int id, int heads, int quarter, int its, double dt) {
      if (n < MAX_OPS) op[c][n] = {type, flags, id, heads, quarter, 0, items, its, t, t + dt};
      n++; items += its; t += dt;
    };
    for (const char* s = text[c >> 1]; *s; s++) {
      const int tm = hex(s[1]) & 15, nj = covered[2 * tm + (c & 1)];
      if (*s == 'N') { add(OP_Q, 0, 0, 0, 0, 10, T_Q); add(OP_A, 0, 0, 0, 0, 32, T_A); }
      if (*s == 'P') add(OP_Q, F_PARK, 0, 0, 0, 10, T_P);
      if (*s == '+' || *s == '-') t += *s == '+' ? 1000 : -1000;
      if (*s == 'U') { if (n == 0 || n > MAX_OPS || op[c][n - 1].type != OP_A) return false; add(OP_A, F_PARK, 0, 0, 0, 33, T_U); }
      if (*s == 'J') { if (nj < TAIL + 6 || nj > kSteps - 11) return false; add(OP_O, P_WIDE, tm * kH, nj, 2 * (c & 1), nj + TAIL, 2 * T_O * nj + T_WIDE); }
    }
    add(OP_O, 0, 0, 0, 0, 0, 0);
    add(OP_END, 0, 0, 0, 0, 0, 0);
    if (n > MAX_OPS || op[c][0].type != OP_Q) return false;
    n_op[c] = n - 1;
    att[c] = {t, &op[c][n - 2], 0};
  }
  for (int i = 0; i < 4 * N_TEAM; i++) dem[i] = {(double)covered[i / 2], nullptr, i};
  sort(att, 2 * n_pair); sort(dem, 4 * N_TEAM);
  for (int i = 0; i < 4 * N_TEAM; i++) {
    Op* f = att[i].o;
    const int nj = covered[dem[i].id / 2];
    f->flags = nj ? P_LD : 0;
    f->id = dem[i].id / 4 * kH + nj / 3; f->quarter = dem[i].id & 3; f->items = f->n = kSteps - nj;
    f[1].t0 = f[1].t1 = f->t1 = f->t0 + T_O * f->n + T_RUN; f[1].item0 += f->n;
  }
  for (int i = 0; i < ID_PART; i++) use[i] = {1e18, 0, 0, 0, 0, false};
  int n_att = 0, n_prk = 0, n_unp = 0;
  auto ready = [&](const Op* o) {
    const int nt = o[1].type;
    return o->t1 + (nt == OP_Q ? 6100 : !o[1].n ? 1500 : (o[1].flags & P_WIDE) ? 7700 : 3900) + PUBLISH;
  };
  for (int c = 0; c < 2 * n_pair; c++)
    for (Op* o = op[c]; o->type != OP_END; o++) {
      if (o->type == OP_A) { att[n_att] = {ready(o), o, 0}; if (++n_att > N_TILE) return false; }
      if (o->type == OP_A && o->flags) { unp[n_unp] = {o->t0 - AHEAD, o, 0}; if (++n_unp > MAX_PARK) return false; }
      if (o->type == OP_Q && o->flags) { prk[n_prk] = {ready(o), o, 0}; if (++n_prk > MAX_PARK) return false; }
      for (int i = 0; o->type == OP_O && i < o->n; i++) {
        const int nw = (o->flags & P_WIDE) ? o->n - TAIL : 0, k = nw ? i : kSteps - o->n + i;
        Use& u = use[o->id / kH * kH + k / 3];
        const double t = o->t0 + T_O * (i + (i < nw ? i : nw));
        if (t - AHEAD < u.need) u.need = t - AHEAD;
        const double f = !nw ? 1e18 : i + FLIGHT < o->items - TAIL || (nw && o[1].type != OP_O) ? t + T_O * (i < nw ? 2 : 1 + TAIL) + PUBLISH : 1e18;
        if (f > u.freed) u.freed = f;
        if (i == 0 || k % 3 == 0) u.readers++;
      }
    }
  if (n_att != N_TILE || n_prk != n_unp) return false;
  for (int i = 0; i < N_TILE; i++) { const int id = (i & 15) * kH + (i >> 4); dem[i] = {use[id].need, nullptr, id}; }
  sort(att, n_att); sort(dem, N_TILE); sort(prk, n_prk); sort(unp, n_unp);
  PlanStats st = {0, 1e18, 1e18, 0, n_prk};
  int n_wr = 0;
  for (int i = 0; i < N_TILE; i++) {
    Op* o = att[i].o;
    o->id = dem[i].id;
    if (!o->flags) o[-1].id = o->id;
    if (dem[i].t - att[i].t < st.slack) st.slack = dem[i].t - att[i].t;
    wr[n_wr++] = {o->t1 - 2 * AHEAD, o, o->id};
  }
  for (int i = 0; i < n_prk; i++) {
    prk[i].o->id = unp[i].o->id;
    prk[i].o->park = unp[i].o->park = i;
    use[N_TILE + i].freed = unp[i].o->t0 + 2 * PUBLISH;
    use[N_TILE + i].readers = 1;
    if (unp[i].t - prk[i].t < st.park_slack) st.park_slack = unp[i].t - prk[i].t;
    wr[n_wr++] = {prk[i].o->t1 - 2 * AHEAD, prk[i].o, N_TILE + i};
  }
  for (int c = 0; c < 2 * n_pair; c++)
    for (int d = 0; d < 2 * n_pair; d++)
      for (Op *f = &op[c][n_op[c] - 1], *o = op[d]; f->n && o->type != OP_END; o++)
        if (o->type == OP_O && (o->flags & P_WIDE) && o->id / kH == f->id / kH && o->quarter / 2 == f->quarter / 2) {
          if (f->t0 - o->t1 > 4096.0 * ((P.dbg >> 16) & 255)) f->flags |= P_PRE;
          const double slack = f->t0 + ((f->flags & P_PRE) ? 0 : (f->n - 5) * T_O) - AHEAD - ready(o);
          if (slack < st.park_slack) st.park_slack = slack;
        }
  constexpr double long_while = 160000;
  for (int c = 0; c < 2 * n_pair; c++)
    for (Op* o = op[c]; o->type != OP_END; o++) {
      if (o->type == OP_O && (o->flags & P_WIDE)) {
        int run = 0, best = 0, end = 0;
        for (int h = 0; 3 * h < o->n; h++) {
          bool last = true;
          for (int d = 0; d < 2 * n_pair; d++)
            for (const Op* e = op[d]; e->type != OP_END; e++) {
              if (e->type != OP_O || e == o || ((e->id ^ o->id) & 256) || e->quarter / 2 != o->quarter / 2) continue;
              const bool wide = e->flags & P_WIDE;
              if (wide ? 3 * h >= e->n : 3 * h + 3 <= kSteps - e->n) continue;
              const double dt = e->t0 + T_O * (wide ? 6 * h : 3 * h - kSteps + e->n) - o->t0 - T_O * 6 * h + (d - c) * 1e-3;
              if (dt > 0 && dt < long_while) last = false;
            }
          run = last ? run + 1 : 0;
          if (run > best) { best = run; end = h + 1; }
        }
        const int from = end - best;
        if (3 * end >= o->n) end++;
        o->park = from | (end / 2) << 5;
      }
      if (o->type != OP_Q) continue;
      bool lw = true, lx = true;
      for (int d = 0; d < 2 * n_pair; d++)
        for (const Op* e = op[d]; e->type != OP_END; e++) {
          const double dt = e->t0 - o->t0 + (d - c) * 1e-3;
          if (e->type != OP_Q || e == o || dt < 0 || dt > long_while) continue;
          if (((e->id ^ o->id) & (256 + 31)) == 0) lw = false;
          if (e->id / kH == o->id / kH) lx = false;
        }
      o->quarter = (lw ? P_LASTW : 0) | (lx ? P_LASTX : 0);
    }
  sort(wr, n_wr);
  int holder[N_TILE];
  for (int i = 0; i < n_wr; i++) {
    int best = -1;
    for (int sl = 0; sl < st.slots; sl++)
      if (use[holder[sl]].freed + margin <= wr[i].t && (best < 0 || use[holder[sl]].freed < use[holder[best]].freed)) best = sl;
    Use& u = use[wr[i].id];
    if (best >= 0) { u.prev = holder[best]; use[u.prev].next = true; wr[i].o->flags |= P_GATE; }
    else if (st.slots == N_TILE) return false;
    else best = st.slots++;
    u.slot = best;
    holder[best] = wr[i].id;
  }
  {
    int pos[N_CL] = {}, flag[ID_PART + 4 * N_TEAM] = {}, seen[ID_PART] = {};
    auto goal = [&](int c) { return op[c][n_op[c] - 1].item0; };
    for (bool moved = true; moved;) {
      moved = false;
      for (int c = 0; c < 2 * n_pair; c++) {
        for (; pos[c] < goal(c); pos[c]++, moved = true) {
          bool ok = true;
          for (const Op* o = op[c]; o->type != OP_END; o++) {
            const int k = pos[c] - o->item0, own = o->type == OP_A ? o->id : N_TILE + (o->park & 127);
            if (k < 0 || k >= o->items) continue;
            if (o->type == OP_O) ok = k >= o->n || flag[o->id + k / 3];
            else if (k == o->items - 1 && (o->flags & P_GATE)) ok = seen[use[own].prev] == use[use[own].prev].readers;
            else if (k == 1 && o->type == OP_A && (o->flags & F_PARK)) ok = flag[N_TILE + o->park];
          }
          if (!ok) break;
          for (const Op* o = op[c]; o->type != OP_END; o++) {
            if (pos[c] == o->item0 + o->items + (o[1].type == OP_Q ? 7 : o[1].item0 == goal(c) ? -1 : 5)) {
              if (o->type == OP_A) flag[o->id] = 1;
              if (o->type == OP_Q && (o->flags & F_PARK)) flag[N_TILE + o->park] = 1;
              if (o->type == OP_O) flag[ID_PART + o->id / kH * 4 + o->quarter] = flag[ID_PART + o->id / kH * 4 + o->quarter + 1] = 1;
            }
            const int k = pos[c] - FLIGHT - o->item0, nw = o->n - TAIL;
            if (k == 1 && o->type == OP_A && (o->flags & F_PARK)) seen[N_TILE + o->park]++;
            if (o->type == OP_O && k >= 0 && k < o->items && (k < nw || k >= o->n) && (k < nw ? k : k - TAIL) % 3 == 2) seen[o->id + (k < nw ? k : k - TAIL) / 3]++;
          }
        }
      }
    }
    for (int c = 0; c < 2 * n_pair; c++) if (pos[c] < goal(c)) return false;
  }
  int n_job = 0, longest = 0;
  for (int i = 0; i < 2 * N_TEAM; i++) if (kH + 1 - covered[i] / 3 > longest) longest = kH + 1 - covered[i] / 3;
  for (int c = 0; c < 2 * n_pair; c++) {
    uint32_t items = 0, cur = 0, pend = 0;
    int n = 0, ev = 0;
    auto item = [&](uint32_t bytes, int count) {
      for (int i = 0; i < count; i++) { if (cur + bytes > RING) cur = 0; cur += bytes; items++; }
    };
    auto event = [&](uint32_t e) { if (ev < MAX_TAB) P.prog[c].ev[ev] = e; ev++; };
    for (const Op* o = op[c];; o++) {
      if (o->type != OP_END && phase && (o->type == OP_O) != (phase == 2)) continue;
      uint32_t cw = o->type | (items % (2 * NBAR)) << 15 | (cur >> 12) << 20 | pend, pw = o->type | o->id << 2 | o->flags;
      const int ps = use[N_TILE + (o->park & 127)].slot;
      pend = 0;
      if (o->type == OP_O) {
        pw |= o->n << 13 | o->quarter << 20 | (uint32_t)o->park << 23;
        if (o->flags & P_WIDE) {
          cw |= o->n << 2 | (o->id / kH * 2 + o->quarter / 2) << 9 | C_WIDE;
          item(SZ_W, o->n - TAIL);
          item(SZ_W2, TAIL);
          item(SZ_W3, TAIL);
          pend = C_PEND;
          for (int i = 0; 3 * i < o->n; i++) event((o->id + i) | E_ON | (use[o->id + i].next ? 0 : E_LAST));
        } else {
          dem[n_job++] = {o->t0 - 1e6 * o->n, nullptr, (int)pw};
          st.own[c] = pw;
          pw = OP_O;
          event(E_DRAW | (items < 16 ? 0 : items - 16));
        }
      } else if (o->type != OP_END) {
        const bool parks = o->type == OP_Q && (o->flags & F_PARK);
        cw |= (parks ? ps : use[o->id].slot) << 2 | (o->flags & F_PARK);
        if (o->flags & F_PARK) pw |= o->park << 13 | ps << 20;
        if (o->type == OP_Q) { item(SZ_Q, 10); pw |= o->quarter; }
        else { item(SZ_KV, 1); if (o->flags & F_PARK) { item(SZ_PARK, 1); event((N_TILE + o->park) | E_ON | (use[N_TILE + o->park].next ? 0 : E_LAST)); } item(SZ_KV, 31); }
        if (parks || o->type == OP_A) pend = C_PEND;
        if (o->flags & P_GATE) event(use[parks ? N_TILE + o->park : o->id].prev | E_ON | E_FREE);
      }
      P.prog[c].c[n] = cw; P.prog[c].p[n++] = pw;
      if (o->type == OP_END) { if (o->t0 > st.end) st.end = o->t0; break; }
    }
    if (ev > MAX_TAB || ev + longest > MAX_EV) return false;
    P.prog[c].n_ev = ev;
    while (n < MAX_OPS) { P.prog[c].c[n] = OP_END; P.prog[c].p[n++] = OP_END; }
    P.first[c] = (uint16_t)(P.prog[c].p[0] & 2047);
  }
  sort(dem, n_job);
  for (int i = 0; i < n_job; i++) P.job[i] = dem[i].id;
  for (int i = 0; i < ID_PART; i++) {
    if (i < N_TILE) P.slot[i] = use[i].slot;
    P.info[i] = (use[i].readers + use[i].next) | (use[i].next ? I_NEXT : 0);
  }
  if (stats) *stats = st;
  return true;
}

const char* const kPrograms[N_CL / 2] = {
  "PNJ06864NNNNN", "PNJ17878NNNNN", "PNJ26464NNNNN", "PNJ34148NNNNNN", "PNJ46262NNNNN", "PNJ58182NNNN",
  "NNJ67371NNNN", "PNNJ76666NNNN", "NUNNNJ84545NN", "NUNNNJ94545NN", "NUNNNNJa5551N", "NNNNNJb5959NN",
  "NNNNNJc5455NN", "PNNNNNJd5353NN", "NNNNNJe5153NN", "NNNNNJf7777N", "PNNNNNNNNN", "PNNNNNNNNN",
  "PNNNNNNNNN", "PNNNNNNNNN", "NNNNNNNNN", "NNNNNNNNN", "NNNNNNNNN", "NNNNNNNNN",
  "NNNNNNNNN", "N-NNNNNNNN", "NUNNNNNNN", "NUNNNNNNN", "NUNNNNNNN", "NUNNNUNNN",
  "NUNNNNNNN", "NUNNNNNNN", "NUUNNNNNN",
};

const char* const* bench_programs() {
  return kPrograms;
}

}

extern "C" void kernel_launch(void* const* d_in, const int* in_sizes, int n_in, void* d_out, int out_size) {
  (void)in_sizes; (void)n_in; (void)out_size;
  static EncodeFn fn = nullptr;
  static int n_clusters = 0;
  if (!fn) {
    cudaDriverEntryPointQueryResult qr;
    void* f = nullptr;
    cudaGetDriverEntryPoint("cuTensorMapEncodeTiled", &f, cudaEnableDefault, &qr);
    fn = (EncodeFn)f;
    cudaFuncSetAttribute(fused_kernel, cudaFuncAttributeMaxDynamicSharedMemorySize, SMEM_BYTES);
    cudaLaunchConfig_t cfg = {};
    cfg.gridDim = dim3(132); cfg.blockDim = dim3(384); cfg.dynamicSmemBytes = SMEM_BYTES;
    cudaLaunchAttribute at[1];
    at[0].id = cudaLaunchAttributeClusterDimension; at[0].val.clusterDim.x = 2; at[0].val.clusterDim.y = 1; at[0].val.clusterDim.z = 1;
    cfg.attrs = at; cfg.numAttrs = 1;
    if (cudaOccupancyMaxActiveClusters(&n_clusters, fused_kernel, &cfg) != cudaSuccess || n_clusters < 1) n_clusters = 1;
    (void)cudaGetLastError();
  }
  static Params P;
  const CUtensorMapSwizzle S128 = CU_TENSOR_MAP_SWIZZLE_128B, S64 = CU_TENSOR_MAP_SWIZZLE_64B;
  for (int blk = 0; blk < 2; blk++) {
    void* const* in = d_in + 5 * blk;
    { const cuuint64_t d[] = {kD, kB * kSq}, s[] = {kD * 2}; const cuuint32_t b[] = {64, 128};
      encode(fn, &P.x[blk], in[0], 2, d, s, b, S128); }
    { const cuuint64_t d[] = {64, 8, 3, (cuuint64_t)kB * kH * kSk / 8}, s[] = {kDh * 2, 128, 8 * kDh * 2}; const cuuint32_t b[] = {64, 8, 3, 4};
      encode(fn, &P.k[blk], in[1], 4, d, s, b, S128);
      encode(fn, &P.v[blk], in[2], 4, d, s, b, S128); }
    { const cuuint64_t d[] = {64, kD, kHD / 64}, s[] = {kHD * 2, 128}; const cuuint32_t b[] = {64, 32, 3};
      encode(fn, &P.wq[blk], in[3], 3, d, s, b, S128); }
    { const cuuint64_t d[] = {32, 2, kHD / 8, 4, kD / 32}, s[] = {kD * 2, 8 * kD * 2, 2 * kD * 2, 64}; const cuuint32_t b[] = {32, 2, 4, 4, 5};
      encode(fn, &P.wo[blk], in[4], 5, d, s, b, S64); }
    { const cuuint64_t d[] = {64, 2, kHD / 8, 4, kD / 64}, s[] = {kD * 2, 8 * kD * 2, 2 * kD * 2, 128};
      const cuuint32_t b3[] = {64, 2, 4, 4, 3}, b2[] = {64, 2, 4, 4, 2};
      encode(fn, &P.wo3[blk], in[4], 5, d, s, b3, S128);
      encode(fn, &P.wo2[blk], in[4], 5, d, s, b2, S128); }
  }
  { const cuuint64_t d[] = {32, kB * kSq, 2 * kD / 32}, s[] = {2 * kD * 2, 64}; const cuuint32_t b[] = {32, 16, 1};
    encode(fn, &P.out, d_out, 3, d, s, b, S64); }

  P.kv[0] = (const char*)d_in[1]; P.kv[1] = (const char*)d_in[6]; P.kv[2] = (const char*)d_in[2]; P.kv[3] = (const char*)d_in[7];
  P.xw[0] = (const char*)d_in[0]; P.xw[1] = (const char*)d_in[3];
  cudaGetSymbolAddress((void**)&P.g, g_scratch);
  P.dbg = DBG_DEFAULT;
  if (n_clusters >= N_CL && plan(bench_programs(), N_CL / 2, 0, P)) {
    fused_kernel<<<2 * N_CL, 384, SMEM_BYTES>>>(P);
  } else {
    const char* text[2 * N_TEAM];
    for (int i = 0; i < 2 * N_TEAM; i++) text[i] = "NNNNNNNN";
    for (int phase = 1; phase <= 2; phase++) {
      plan(text, 2 * N_TEAM, phase, P);
      fused_kernel<<<8 * N_TEAM, 384, SMEM_BYTES>>>(P);
    }
  }
}
```

```cpp
#include <cuda_runtime.h>
#include <cuda_bf16.h>
#include <cuda.h>
#include <cuda/annotated_ptr>
#include <stdint.h>
#include <stdio.h>

namespace {

constexpr int kB = 8, kSq = 256, kD = 640, kH = 32, kSk = 1024, kDh = 192;
constexpr int kHD = kH * kDh;
constexpr uint32_t RING = 224 * 1024;
constexpr uint32_t SZ_KV = 24576;
constexpr uint32_t SZ_Q = 16384 + 24576;
constexpr uint32_t SZ_O = 16384 + 20480;
constexpr uint32_t SZ_W3 = 16384 + 24576, SZ_W2 = 16384 + 16384, SZ_W = SZ_W3 + 16384;
constexpr uint32_t SZ_PARK = 49152;
constexpr uint32_t SZ_OL = SZ_O + 8192;
constexpr int NBAR = 16, FLIGHT = RING / SZ_KV + 1;
constexpr int EARLY = 3;
constexpr int kSteps = kHD / 64;
constexpr int TAIL = 4;
constexpr uint32_t KV_CH = 64, KV_SBO = 3072;
constexpr int SMEM_BYTES = RING + 1024 + 1024;
constexpr int N_TEAM = 16, N_CL = 66, MAX_OPS = 22, MAX_EV = 72, MAX_TAB = 47, N_TILE = N_TEAM * kH, MAX_PARK = 128, ID_PART = N_TILE + MAX_PARK;
enum : uint32_t { OP_END = 0, OP_Q = 1, OP_A = 2, OP_O = 3, F_PARK = 1 << 11,
                  C_WIDE = 1 << 27, C_PEND = 1 << 26, P_GATE = 1 << 12, P_WIDE = 1 << 11, P_LD = 1 << 12, P_PRE = 1 << 22, P_LASTW = 1 << 29, P_LASTX = 1 << 30,
                  I_NEXT = 8, E_ON = 1 << 15, E_FREE = 1 << 14, E_LAST = 1 << 13, E_DRAW = 1 << 12, E_JOB = 1 << 11 };

constexpr uint32_t DBG_DEFAULT = 0x040800;

struct alignas(1024) Scratch {
  unsigned int flag[2047];
  unsigned int ticket;
  uint4 part[N_TEAM * 2 * 2 * 5120];
  uint4 tile[N_TILE * 2 * 3072];
};

struct alignas(64) Params {
  const char* xw[2];
  uint16_t first[80];
  Scratch* g;
  uint32_t dbg;
  CUtensorMap x[2], wq[2], k[2], v[2], wo[2], wo3[2], wo2[2], out;
  struct {
    uint32_t c[MAX_OPS];
    uint32_t p[MAX_OPS];
    uint16_t n_ev, ev[MAX_TAB];
  } prog[N_CL];
  const char* kv[4];
  uint32_t job[N_CL];
  uint16_t slot[N_TILE];
  uint8_t info[ID_PART];
};

__device__ Scratch g_scratch;

template <int TB, int TA = 0>
__device__ __forceinline__ void wgmma_ss_n64(float (&d)[32], uint64_t da, uint64_t db, int scale_d) {
  asm volatile("{\n.reg .pred p;\nsetp.ne.b32 p, %34, 0;\n"
    "wgmma.mma_async.sync.aligned.m64n64k16.f32.bf16.bf16 {%0, %1, %2, %3, %4, %5, %6, %7, %8, %9, %10, %11, %12, %13, %14, %15, %16, %17, %18, %19, %20, %21, %22, %23, %24, %25, %26, %27, %28, %29, %30, %31}, %32, %33, p, 1, 1, %35, %36;\n}\n"
    : "+f"(d[0]), "+f"(d[1]), "+f"(d[2]), "+f"(d[3]), "+f"(d[4]), "+f"(d[5]), "+f"(d[6]), "+f"(d[7]), "+f"(d[8]), "+f"(d[9]), "+f"(d[10]), "+f"(d[11]), "+f"(d[12]), "+f"(d[13]), "+f"(d[14]), "+f"(d[15]), "+f"(d[16]), "+f"(d[17]), "+f"(d[18]), "+f"(d[19]), "+f"(d[20]), "+f"(d[21]), "+f"(d[22]), "+f"(d[23]), "+f"(d[24]), "+f"(d[25]), "+f"(d[26]), "+f"(d[27]), "+f"(d[28]), "+f"(d[29]), "+f"(d[30]), "+f"(d[31])
    : "l"(da), "l"(db), "r"(scale_d), "n"(TA), "n"(TB));
}
template <int TB>
__device__ __forceinline__ void wgmma_rs_n64(float (&d)[32], uint32_t a0, uint32_t a1, uint32_t a2, uint32_t a3, uint64_t db, int scale_d) {
  asm volatile("{\n.reg .pred p;\nsetp.ne.b32 p, %37, 0;\n"
    "wgmma.mma_async.sync.aligned.m64n64k16.f32.bf16.bf16 {%0, %1, %2, %3, %4, %5, %6, %7, %8, %9, %10, %11, %12, %13, %14, %15, %16, %17, %18, %19, %20, %21, %22, %23, %24, %25, %26, %27, %28, %29, %30, %31}, {%32, %33, %34, %35}, %36, p, 1, 1, %38;\n}\n"
    : "+f"(d[0]), "+f"(d[1]), "+f"(d[2]), "+f"(d[3]), "+f"(d[4]), "+f"(d[5]), "+f"(d[6]), "+f"(d[7]), "+f"(d[8]), "+f"(d[9]), "+f"(d[10]), "+f"(d[11]), "+f"(d[12]), "+f"(d[13]), "+f"(d[14]), "+f"(d[15]), "+f"(d[16]), "+f"(d[17]), "+f"(d[18]), "+f"(d[19]), "+f"(d[20]), "+f"(d[21]), "+f"(d[22]), "+f"(d[23]), "+f"(d[24]), "+f"(d[25]), "+f"(d[26]), "+f"(d[27]), "+f"(d[28]), "+f"(d[29]), "+f"(d[30]), "+f"(d[31])
    : "r"(a0), "r"(a1), "r"(a2), "r"(a3), "l"(db), "r"(scale_d), "n"(TB));
}
template <int TB, int TA = 0>
__device__ __forceinline__ void wgmma_ss_n128(float (&d)[64], uint64_t da, uint64_t db, int scale_d) {
  asm volatile("{\n.reg .pred p;\nsetp.ne.b32 p, %66, 0;\n"
    "wgmma.mma_async.sync.aligned.m64n128k16.f32.bf16.bf16 {%0, %1, %2, %3, %4, %5, %6, %7, %8, %9, %10, %11, %12, %13, %14, %15, %16, %17, %18, %19, %20, %21, %22, %23, %24, %25, %26, %27, %28, %29, %30, %31, %32, %33, %34, %35, %36, %37, %38, %39, %40, %41, %42, %43, %44, %45, %46, %47, %48, %49, %50, %51, %52, %53, %54, %55, %56, %57, %58, %59, %60, %61, %62, %63}, %64, %65, p, 1, 1, %67, %68;\n}\n"
    : "+f"(d[0]), "+f"(d[1]), "+f"(d[2]), "+f"(d[3]), "+f"(d[4]), "+f"(d[5]), "+f"(d[6]), "+f"(d[7]), "+f"(d[8]), "+f"(d[9]), "+f"(d[10]), "+f"(d[11]), "+f"(d[12]), "+f"(d[13]), "+f"(d[14]), "+f"(d[15]), "+f"(d[16]), "+f"(d[17]), "+f"(d[18]), "+f"(d[19]), "+f"(d[20]), "+f"(d[21]), "+f"(d[22]), "+f"(d[23]), "+f"(d[24]), "+f"(d[25]), "+f"(d[26]), "+f"(d[27]), "+f"(d[28]), "+f"(d[29]), "+f"(d[30]), "+f"(d[31]), "+f"(d[32]), "+f"(d[33]), "+f"(d[34]), "+f"(d[35]), "+f"(d[36]), "+f"(d[37]), "+f"(d[38]), "+f"(d[39]), "+f"(d[40]), "+f"(d[41]), "+f"(d[42]), "+f"(d[43]), "+f"(d[44]), "+f"(d[45]), "+f"(d[46]), "+f"(d[47]), "+f"(d[48]), "+f"(d[49]), "+f"(d[50]), "+f"(d[51]), "+f"(d[52]), "+f"(d[53]), "+f"(d[54]), "+f"(d[55]), "+f"(d[56]), "+f"(d[57]), "+f"(d[58]), "+f"(d[59]), "+f"(d[60]), "+f"(d[61]), "+f"(d[62]), "+f"(d[63])
    : "l"(da), "l"(db), "r"(scale_d), "n"(TA), "n"(TB));
}
template <int TB>
__device__ __forceinline__ void wgmma_rs_n128(float (&d)[64], uint32_t a0, uint32_t a1, uint32_t a2, uint32_t a3, uint64_t db, int scale_d) {
  asm volatile("{\n.reg .pred p;\nsetp.ne.b32 p, %69, 0;\n"
    "wgmma.mma_async.sync.aligned.m64n128k16.f32.bf16.bf16 {%0, %1, %2, %3, %4, %5, %6, %7, %8, %9, %10, %11, %12, %13, %14, %15, %16, %17, %18, %19, %20, %21, %22, %23, %24, %25, %26, %27, %28, %29, %30, %31, %32, %33, %34, %35, %36, %37, %38, %39, %40, %41, %42, %43, %44, %45, %46, %47, %48, %49, %50, %51, %52, %53, %54, %55, %56, %57, %58, %59, %60, %61, %62, %63}, {%64, %65, %66, %67}, %68, p, 1, 1, %70;\n}\n"
    : "+f"(d[0]), "+f"(d[1]), "+f"(d[2]), "+f"(d[3]), "+f"(d[4]), "+f"(d[5]), "+f"(d[6]), "+f"(d[7]), "+f"(d[8]), "+f"(d[9]), "+f"(d[10]), "+f"(d[11]), "+f"(d[12]), "+f"(d[13]), "+f"(d[14]), "+f"(d[15]), "+f"(d[16]), "+f"(d[17]), "+f"(d[18]), "+f"(d[19]), "+f"(d[20]), "+f"(d[21]), "+f"(d[22]), "+f"(d[23]), "+f"(d[24]), "+f"(d[25]), "+f"(d[26]), "+f"(d[27]), "+f"(d[28]), "+f"(d[29]), "+f"(d[30]), "+f"(d[31]), "+f"(d[32]), "+f"(d[33]), "+f"(d[34]), "+f"(d[35]), "+f"(d[36]), "+f"(d[37]), "+f"(d[38]), "+f"(d[39]), "+f"(d[40]), "+f"(d[41]), "+f"(d[42]), "+f"(d[43]), "+f"(d[44]), "+f"(d[45]), "+f"(d[46]), "+f"(d[47]), "+f"(d[48]), "+f"(d[49]), "+f"(d[50]), "+f"(d[51]), "+f"(d[52]), "+f"(d[53]), "+f"(d[54]), "+f"(d[55]), "+f"(d[56]), "+f"(d[57]), "+f"(d[58]), "+f"(d[59]), "+f"(d[60]), "+f"(d[61]), "+f"(d[62]), "+f"(d[63])
    : "r"(a0), "r"(a1), "r"(a2), "r"(a3), "l"(db), "r"(scale_d), "n"(TB));
}
template <int TB, int TA = 0>
__device__ __forceinline__ void wgmma_ss_n160(float (&d)[80], uint64_t da, uint64_t db, int scale_d) {
  asm volatile("{\n.reg .pred p;\nsetp.ne.b32 p, %82, 0;\n"
    "wgmma.mma_async.sync.aligned.m64n160k16.f32.bf16.bf16 {%0, %1, %2, %3, %4, %5, %6, %7, %8, %9, %10, %11, %12, %13, %14, %15, %16, %17, %18, %19, %20, %21, %22, %23, %24, %25, %26, %27, %28, %29, %30, %31, %32, %33, %34, %35, %36, %37, %38, %39, %40, %41, %42, %43, %44, %45, %46, %47, %48, %49, %50, %51, %52, %53, %54, %55, %56, %57, %58, %59, %60, %61, %62, %63, %64, %65, %66, %67, %68, %69, %70, %71, %72, %73, %74, %75, %76, %77, %78, %79}, %80, %81, p, 1, 1, %83, %84;\n}\n"
    : "+f"(d[0]), "+f"(d[1]), "+f"(d[2]), "+f"(d[3]), "+f"(d[4]), "+f"(d[5]), "+f"(d[6]), "+f"(d[7]), "+f"(d[8]), "+f"(d[9]), "+f"(d[10]), "+f"(d[11]), "+f"(d[12]), "+f"(d[13]), "+f"(d[14]), "+f"(d[15]), "+f"(d[16]), "+f"(d[17]), "+f"(d[18]), "+f"(d[19]), "+f"(d[20]), "+f"(d[21]), "+f"(d[22]), "+f"(d[23]), "+f"(d[24]), "+f"(d[25]), "+f"(d[26]), "+f"(d[27]), "+f"(d[28]), "+f"(d[29]), "+f"(d[30]), "+f"(d[31]), "+f"(d[32]), "+f"(d[33]), "+f"(d[34]), "+f"(d[35]), "+f"(d[36]), "+f"(d[37]), "+f"(d[38]), "+f"(d[39]), "+f"(d[40]), "+f"(d[41]), "+f"(d[42]), "+f"(d[43]), "+f"(d[44]), "+f"(d[45]), "+f"(d[46]), "+f"(d[47]), "+f"(d[48]), "+f"(d[49]), "+f"(d[50]), "+f"(d[51]), "+f"(d[52]), "+f"(d[53]), "+f"(d[54]), "+f"(d[55]), "+f"(d[56]), "+f"(d[57]), "+f"(d[58]), "+f"(d[59]), "+f"(d[60]), "+f"(d[61]), "+f"(d[62]), "+f"(d[63]), "+f"(d[64]), "+f"(d[65]), "+f"(d[66]), "+f"(d[67]), "+f"(d[68]), "+f"(d[69]), "+f"(d[70]), "+f"(d[71]), "+f"(d[72]), "+f"(d[73]), "+f"(d[74]), "+f"(d[75]), "+f"(d[76]), "+f"(d[77]), "+f"(d[78]), "+f"(d[79])
    : "l"(da), "l"(db), "r"(scale_d), "n"(TA), "n"(TB));
}
template <int TB>
__device__ __forceinline__ void wgmma_rs_n160(float (&d)[80], uint32_t a0, uint32_t a1, uint32_t a2, uint32_t a3, uint64_t db, int scale_d) {
  asm volatile("{\n.reg .pred p;\nsetp.ne.b32 p, %85, 0;\n"
    "wgmma.mma_async.sync.aligned.m64n160k16.f32.bf16.bf16 {%0, %1, %2, %3, %4, %5, %6, %7, %8, %9, %10, %11, %12, %13, %14, %15, %16, %17, %18, %19, %20, %21, %22, %23, %24, %25, %26, %27, %28, %29, %30, %31, %32, %33, %34, %35, %36, %37, %38, %39, %40, %41, %42, %43, %44, %45, %46, %47, %48, %49, %50, %51, %52, %53, %54, %55, %56, %57, %58, %59, %60, %61, %62, %63, %64, %65, %66, %67, %68, %69, %70, %71, %72, %73, %74, %75, %76, %77, %78, %79}, {%80, %81, %82, %83}, %84, p, 1, 1, %86;\n}\n"
    : "+f"(d[0]), "+f"(d[1]), "+f"(d[2]), "+f"(d[3]), "+f"(d[4]), "+f"(d[5]), "+f"(d[6]), "+f"(d[7]), "+f"(d[8]), "+f"(d[9]), "+f"(d[10]), "+f"(d[11]), "+f"(d[12]), "+f"(d[13]), "+f"(d[14]), "+f"(d[15]), "+f"(d[16]), "+f"(d[17]), "+f"(d[18]), "+f"(d[19]), "+f"(d[20]), "+f"(d[21]), "+f"(d[22]), "+f"(d[23]), "+f"(d[24]), "+f"(d[25]), "+f"(d[26]), "+f"(d[27]), "+f"(d[28]), "+f"(d[29]), "+f"(d[30]), "+f"(d[31]), "+f"(d[32]), "+f"(d[33]), "+f"(d[34]), "+f"(d[35]), "+f"(d[36]), "+f"(d[37]), "+f"(d[38]), "+f"(d[39]), "+f"(d[40]), "+f"(d[41]), "+f"(d[42]), "+f"(d[43]), "+f"(d[44]), "+f"(d[45]), "+f"(d[46]), "+f"(d[47]), "+f"(d[48]), "+f"(d[49]), "+f"(d[50]), "+f"(d[51]), "+f"(d[52]), "+f"(d[53]), "+f"(d[54]), "+f"(d[55]), "+f"(d[56]), "+f"(d[57]), "+f"(d[58]), "+f"(d[59]), "+f"(d[60]), "+f"(d[61]), "+f"(d[62]), "+f"(d[63]), "+f"(d[64]), "+f"(d[65]), "+f"(d[66]), "+f"(d[67]), "+f"(d[68]), "+f"(d[69]), "+f"(d[70]), "+f"(d[71]), "+f"(d[72]), "+f"(d[73]), "+f"(d[74]), "+f"(d[75]), "+f"(d[76]), "+f"(d[77]), "+f"(d[78]), "+f"(d[79])
    : "r"(a0), "r"(a1), "r"(a2), "r"(a3), "l"(db), "r"(scale_d), "n"(TB));
}
template <int TB, int TA = 0>
__device__ __forceinline__ void wgmma_ss_n192(float (&d)[96], uint64_t da, uint64_t db, int scale_d) {
  asm volatile("{\n.reg .pred p;\nsetp.ne.b32 p, %98, 0;\n"
    "wgmma.mma_async.sync.aligned.m64n192k16.f32.bf16.bf16 {%0, %1, %2, %3, %4, %5, %6, %7, %8, %9, %10, %11, %12, %13, %14, %15, %16, %17, %18, %19, %20, %21, %22, %23, %24, %25, %26, %27, %28, %29, %30, %31, %32, %33, %34, %35, %36, %37, %38, %39, %40, %41, %42, %43, %44, %45, %46, %47, %48, %49, %50, %51, %52, %53, %54, %55, %56, %57, %58, %59, %60, %61, %62, %63, %64, %65, %66, %67, %68, %69, %70, %71, %72, %73, %74, %75, %76, %77, %78, %79, %80, %81, %82, %83, %84, %85, %86, %87, %88, %89, %90, %91, %92, %93, %94, %95}, %96, %97, p, 1, 1, %99, %100;\n}\n"
    : "+f"(d[0]), "+f"(d[1]), "+f"(d[2]), "+f"(d[3]), "+f"(d[4]), "+f"(d[5]), "+f"(d[6]), "+f"(d[7]), "+f"(d[8]), "+f"(d[9]), "+f"(d[10]), "+f"(d[11]), "+f"(d[12]), "+f"(d[13]), "+f"(d[14]), "+f"(d[15]), "+f"(d[16]), "+f"(d[17]), "+f"(d[18]), "+f"(d[19]), "+f"(d[20]), "+f"(d[21]), "+f"(d[22]), "+f"(d[23]), "+f"(d[24]), "+f"(d[25]), "+f"(d[26]), "+f"(d[27]), "+f"(d[28]), "+f"(d[29]), "+f"(d[30]), "+f"(d[31]), "+f"(d[32]), "+f"(d[33]), "+f"(d[34]), "+f"(d[35]), "+f"(d[36]), "+f"(d[37]), "+f"(d[38]), "+f"(d[39]), "+f"(d[40]), "+f"(d[41]), "+f"(d[42]), "+f"(d[43]), "+f"(d[44]), "+f"(d[45]), "+f"(d[46]), "+f"(d[47]), "+f"(d[48]), "+f"(d[49]), "+f"(d[50]), "+f"(d[51]), "+f"(d[52]), "+f"(d[53]), "+f"(d[54]), "+f"(d[55]), "+f"(d[56]), "+f"(d[57]), "+f"(d[58]), "+f"(d[59]), "+f"(d[60]), "+f"(d[61]), "+f"(d[62]), "+f"(d[63]), "+f"(d[64]), "+f"(d[65]), "+f"(d[66]), "+f"(d[67]), "+f"(d[68]), "+f"(d[69]), "+f"(d[70]), "+f"(d[71]), "+f"(d[72]), "+f"(d[73]), "+f"(d[74]), "+f"(d[75]), "+f"(d[76]), "+f"(d[77]), "+f"(d[78]), "+f"(d[79]), "+f"(d[80]), "+f"(d[81]), "+f"(d[82]), "+f"(d[83]), "+f"(d[84]), "+f"(d[85]), "+f"(d[86]), "+f"(d[87]), "+f"(d[88]), "+f"(d[89]), "+f"(d[90]), "+f"(d[91]), "+f"(d[92]), "+f"(d[93]), "+f"(d[94]), "+f"(d[95])
    : "l"(da), "l"(db), "r"(scale_d), "n"(TA), "n"(TB));
}
template <int TB>
__device__ __forceinline__ void wgmma_rs_n192(float (&d)[96], uint32_t a0, uint32_t a1, uint32_t a2, uint32_t a3, uint64_t db, int scale_d) {
  asm volatile("{\n.reg .pred p;\nsetp.ne.b32 p, %101, 0;\n"
    "wgmma.mma_async.sync.aligned.m64n192k16.f32.bf16.bf16 {%0, %1, %2, %3, %4, %5, %6, %7, %8, %9, %10, %11, %12, %13, %14, %15, %16, %17, %18, %19, %20, %21, %22, %23, %24, %25, %26, %27, %28, %29, %30, %31, %32, %33, %34, %35, %36, %37, %38, %39, %40, %41, %42, %43, %44, %45, %46, %47, %48, %49, %50, %51, %52, %53, %54, %55, %56, %57, %58, %59, %60, %61, %62, %63, %64, %65, %66, %67, %68, %69, %70, %71, %72, %73, %74, %75, %76, %77, %78, %79, %80, %81, %82, %83, %84, %85, %86, %87, %88, %89, %90, %91, %92, %93, %94, %95}, {%96, %97, %98, %99}, %100, p, 1, 1, %102;\n}\n"
    : "+f"(d[0]), "+f"(d[1]), "+f"(d[2]), "+f"(d[3]), "+f"(d[4]), "+f"(d[5]), "+f"(d[6]), "+f"(d[7]), "+f"(d[8]), "+f"(d[9]), "+f"(d[10]), "+f"(d[11]), "+f"(d[12]), "+f"(d[13]), "+f"(d[14]), "+f"(d[15]), "+f"(d[16]), "+f"(d[17]), "+f"(d[18]), "+f"(d[19]), "+f"(d[20]), "+f"(d[21]), "+f"(d[22]), "+f"(d[23]), "+f"(d[24]), "+f"(d[25]), "+f"(d[26]), "+f"(d[27]), "+f"(d[28]), "+f"(d[29]), "+f"(d[30]), "+f"(d[31]), "+f"(d[32]), "+f"(d[33]), "+f"(d[34]), "+f"(d[35]), "+f"(d[36]), "+f"(d[37]), "+f"(d[38]), "+f"(d[39]), "+f"(d[40]), "+f"(d[41]), "+f"(d[42]), "+f"(d[43]), "+f"(d[44]), "+f"(d[45]), "+f"(d[46]), "+f"(d[47]), "+f"(d[48]), "+f"(d[49]), "+f"(d[50]), "+f"(d[51]), "+f"(d[52]), "+f"(d[53]), "+f"(d[54]), "+f"(d[55]), "+f"(d[56]), "+f"(d[57]), "+f"(d[58]), "+f"(d[59]), "+f"(d[60]), "+f"(d[61]), "+f"(d[62]), "+f"(d[63]), "+f"(d[64]), "+f"(d[65]), "+f"(d[66]), "+f"(d[67]), "+f"(d[68]), "+f"(d[69]), "+f"(d[70]), "+f"(d[71]), "+f"(d[72]), "+f"(d[73]), "+f"(d[74]), "+f"(d[75]), "+f"(d[76]), "+f"(d[77]), "+f"(d[78]), "+f"(d[79]), "+f"(d[80]), "+f"(d[81]), "+f"(d[82]), "+f"(d[83]), "+f"(d[84]), "+f"(d[85]), "+f"(d[86]), "+f"(d[87]), "+f"(d[88]), "+f"(d[89]), "+f"(d[90]), "+f"(d[91]), "+f"(d[92]), "+f"(d[93]), "+f"(d[94]), "+f"(d[95])
    : "r"(a0), "r"(a1), "r"(a2), "r"(a3), "l"(db), "r"(scale_d), "n"(TB));
}

__device__ __forceinline__ uint32_t smem_u32(const void* p) { return (uint32_t)__cvta_generic_to_shared(p); }
__device__ __forceinline__ void wg_fence() { asm volatile("wgmma.fence.sync.aligned;" ::: "memory"); }
__device__ __forceinline__ void wg_commit() { asm volatile("wgmma.commit_group.sync.aligned;" ::: "memory"); }
template <int N> __device__ __forceinline__ void wg_wait() { asm volatile("wgmma.wait_group.sync.aligned %0;" ::"n"(N) : "memory"); }
__device__ __forceinline__ void sched_fence(uint32_t& keep, bool never) {
  asm volatile("{\n.reg .pred p;\nsetp.ne.b32 p, %1, 0;\n@p mov.u32 %0, %%clock;\n}\n" : "+r"(keep) : "r"((int)never) : "memory");
}
template <int N> __device__ __forceinline__ void fence_regs(float (&r)[N]) {
#pragma unroll
  for (int i = 0; i < N; i++) asm volatile("" : "+f"(r[i])::"memory");
}
template <int N> __device__ __forceinline__ void undefine(float (&r)[N]) {
#pragma unroll
  for (int i = 0; i < N; i++) asm volatile("" : "=f"(r[i]));
}
template <int N> __device__ __forceinline__ void fence_regs(uint32_t (&r)[N]) {
#pragma unroll
  for (int i = 0; i < N; i++) asm volatile("" : "+r"(r[i])::"memory");
}
__device__ __forceinline__ uint64_t mk_desc(uint32_t a16, uint32_t lbo, uint32_t sbo, uint32_t swz) {
  uint64_t d;
  asm("mov.b64 %0, {%1, %2};" : "=l"(d) : "r"(a16 + ((lbo >> 4) << 16)), "r"((sbo >> 4) | (swz << 30)));
  return d;
}
__device__ __forceinline__ void mbar_init(uint32_t bar, uint32_t cnt) {
  asm volatile("mbarrier.init.shared::cta.b64 [%0], %1;" ::"r"(bar), "r"(cnt) : "memory");
}
__device__ __forceinline__ void mbar_expect(uint32_t bar, uint32_t tx) {
  asm volatile("mbarrier.arrive.expect_tx.shared::cta.b64 _, [%0], %1;" ::"r"(bar), "r"(tx) : "memory");
}
__device__ __forceinline__ bool mbar_test(uint32_t bar, uint32_t ph) {
  uint32_t ok;
  asm volatile("{\n.reg .pred p;\nmbarrier.test_wait.parity.shared::cta.b64 p, [%1], %2;\nselp.u32 %0, 1, 0, p;\n}\n"
               : "=r"(ok) : "r"(bar), "r"(ph) : "memory");
  return ok;
}
__device__ __forceinline__ bool mbar_try(uint32_t bar, uint32_t ph, uint32_t ns) {
  uint32_t ok;
  asm volatile("{\n.reg .pred p;\nmbarrier.try_wait.parity.shared::cta.b64 p, [%1], %2, %3;\nselp.u32 %0, 1, 0, p;\n}\n"
               : "=r"(ok) : "r"(bar), "r"(ph), "r"(ns) : "memory");
  return ok;
}
__device__ __forceinline__ void mbar_wait(uint32_t bar, uint32_t ph) {
  asm volatile("{\n.reg .pred p;\n.reg .u32 n;\nmov.u32 n, 0;\n"
               "LOOP:\nmbarrier.try_wait.parity.shared::cta.b64 p, [%0], %1;\n@p bra DONE;\n"
               "add.u32 n, n, 1;\nsetp.lt.u32 p, n, 0x1000000;\n@p bra LOOP;\ntrap;\n"
               "DONE:\n}\n" ::"r"(bar), "r"(ph) : "memory");
}
__device__ __forceinline__ void mbar_wait_long(uint32_t bar) {
  asm volatile("{\n.reg .pred p;\n.reg .u32 n;\nmov.u32 n, 0;\n"
               "LOOP:\nmbarrier.try_wait.parity.shared::cta.b64 p, [%0], 0, 20000;\n@p bra DONE;\n"
               "add.u32 n, n, 1;\nsetp.lt.u32 p, n, 0x100000;\n@p bra LOOP;\ntrap;\n"
               "DONE:\n}\n" ::"r"(bar) : "memory");
}
__device__ __forceinline__ void mbar_arrive_cluster_if(bool on, uint32_t addr) {
  asm volatile("{\n.reg .pred p;\nsetp.ne.b32 p, %1, 0;\n@p mbarrier.arrive.shared::cluster.b64 _, [%0];\n}\n" ::"r"(addr), "r"((int)on) : "memory");
}
__device__ __forceinline__ void mbar_arrive_cluster_n(uint32_t n, uint32_t addr) {
  asm volatile("{\n.reg .pred p;\nsetp.ne.b32 p, %1, 0;\n@p mbarrier.arrive.shared::cluster.b64 _, [%0], %1;\n}\n" ::"r"(addr), "r"(n) : "memory");
}
__device__ __forceinline__ void tma2d(uint32_t dst, const CUtensorMap* m, uint32_t bar, int c0, int c1) {
  asm volatile("cp.async.bulk.tensor.2d.shared::cluster.global.mbarrier::complete_tx::bytes [%0], [%1, {%3, %4}], [%2];"
               ::"r"(dst), "l"(m), "r"(bar), "r"(c0), "r"(c1) : "memory");
}
__device__ __forceinline__ void tma3d(uint32_t dst, const CUtensorMap* m, uint32_t bar, int c0, int c1, int c2) {
  asm volatile("cp.async.bulk.tensor.3d.shared::cluster.global.mbarrier::complete_tx::bytes [%0], [%1, {%3, %4, %5}], [%2];"
               ::"r"(dst), "l"(m), "r"(bar), "r"(c0), "r"(c1), "r"(c2) : "memory");
}
__device__ __forceinline__ void tma2d_hint(uint32_t dst, const CUtensorMap* m, uint32_t bar, int c0, int c1, uint64_t pol) {
  asm volatile("cp.async.bulk.tensor.2d.shared::cluster.global.mbarrier::complete_tx::bytes.L2::cache_hint [%0], [%1, {%3, %4}], [%2], %5;"
               ::"r"(dst), "l"(m), "r"(bar), "r"(c0), "r"(c1), "l"(pol) : "memory");
}
__device__ __forceinline__ void tma3d_mc_hint(uint32_t dst, const CUtensorMap* m, uint32_t bar, int c1, int c2, uint64_t pol) {
  asm volatile("cp.async.bulk.tensor.3d.shared::cluster.global.mbarrier::complete_tx::bytes.multicast::cluster.L2::cache_hint"
               " [%0], [%1, {%3, %4, %5}], [%2], %6, %7;"
               ::"r"(dst), "l"(m), "r"(bar), "r"(0), "r"(c1), "r"(c2), "h"((uint16_t)3), "l"(pol) : "memory");
}
__device__ __forceinline__ void tma5d_mc_hint(uint32_t dst, const CUtensorMap* m, uint32_t bar, int c2, int c4, uint64_t pol) {
  asm volatile("cp.async.bulk.tensor.5d.shared::cluster.global.mbarrier::complete_tx::bytes.multicast::cluster.L2::cache_hint"
               " [%0], [%1, {%3, %3, %4, %3, %5}], [%2], %6, %7;"
               ::"r"(dst), "l"(m), "r"(bar), "r"(0), "r"(c2), "r"(c4), "h"((uint16_t)3), "l"(pol) : "memory");
}
__device__ __forceinline__ void tma3d_store(const CUtensorMap* m, uint32_t src, int c0, int c1, int c2) {
  asm volatile("cp.async.bulk.tensor.3d.global.shared::cta.bulk_group [%0, {%2, %3, %4}], [%1];"
               ::"l"(m), "r"(src), "r"(c0), "r"(c1), "r"(c2) : "memory");
}
__device__ __forceinline__ void bar_sync(int id, int n) { asm volatile("bar.sync %0, %1;" ::"r"(id), "r"(n) : "memory"); }
__device__ __forceinline__ uint32_t pack_bf16(float lo, float hi) {
  uint32_t r;
  asm("cvt.rn.bf16x2.f32 %0, %1, %2;" : "=r"(r) : "f"(hi), "f"(lo));
  return r;
}
__device__ __forceinline__ float ex2(float x) {
  float y;
  asm("ex2.approx.ftz.f32 %0, %1;" : "=f"(y) : "f"(x));
  return y;
}
__device__ __forceinline__ float rcp(float x) {
  float y;
  asm("rcp.approx.ftz.f32 %0, %1;" : "=f"(y) : "f"(x));
  return y;
}
__device__ __forceinline__ void stsm4(uint32_t addr, uint32_t a, uint32_t b, uint32_t c, uint32_t d) {
  asm volatile("stmatrix.sync.aligned.m8n8.x4.shared.b16 [%0], {%1, %2, %3, %4};" ::"r"(addr), "r"(a), "r"(b), "r"(c), "r"(d) : "memory");
}

__device__ __forceinline__ void tma4d_mc_hint(uint32_t dst, const CUtensorMap* m, uint32_t bar, int c3, uint64_t pol) {
  asm volatile("cp.async.bulk.tensor.4d.shared::cluster.global.mbarrier::complete_tx::bytes.multicast::cluster.L2::cache_hint"
               " [%0], [%1, {%3, %3, %3, %4}], [%2], %5, %6;"
               ::"r"(dst), "l"(m), "r"(bar), "r"(0), "r"(c3), "h"((uint16_t)3), "l"(pol) : "memory");
}
__device__ __forceinline__ void bulk_load_hint(uint32_t dst, const void* src, uint32_t bytes, uint32_t bar, uint64_t pol) {
  asm volatile("cp.async.bulk.shared::cluster.global.mbarrier::complete_tx::bytes.L2::cache_hint [%0], [%1], %2, [%3], %4;"
               ::"r"(dst), "l"(src), "r"(bytes), "r"(bar), "l"(pol) : "memory");
}
__device__ __forceinline__ void stg2_if(bool on, void* p, uint32_t a, uint32_t b, uint32_t c, uint32_t d, uint32_t e, uint32_t f,
                                        uint32_t g, uint32_t h, uint64_t pol) {
  asm volatile("{\n.reg .pred p;\nsetp.ne.b32 p, %10, 0;\n"
               "@p st.global.L2::cache_hint.v4.b32 [%0], {%1, %2, %3, %4}, %9;\n"
               "@p st.global.L2::cache_hint.v4.b32 [%0 + 512], {%5, %6, %7, %8}, %9;\n}\n"
               ::"l"(p), "r"(a), "r"(b), "r"(c), "r"(d), "r"(e), "r"(f), "r"(g), "r"(h), "l"(pol), "r"((int)on) : "memory");
}
__device__ __forceinline__ uint64_t evict_first() {
  uint64_t p;
  asm("createpolicy.fractional.L2::evict_first.b64 %0, 1.0;" : "=l"(p));
  return p;
}
__device__ __forceinline__ uint64_t no_hint() {
  uint64_t p;
  asm("createpolicy.cvt.L2.b64 %0, %1;" : "=l"(p) : "l"(static_cast<uint64_t>(cuda::access_property{})));
  return p;
}
__device__ __forceinline__ bool elect() {
  uint32_t ok;
  asm volatile("{\n.reg .pred p;\nelect.sync _|p, 0xffffffff;\nselp.u32 %0, 1, 0, p;\n}\n" : "=r"(ok));
  return ok;
}
__device__ __forceinline__ void mbar_arrive(uint32_t bar) {
  asm volatile("mbarrier.arrive.shared::cta.b64 _, [%0];" ::"r"(bar) : "memory");
}
__device__ __forceinline__ void mbar_arrive_if(bool on, uint32_t bar) {
  asm volatile("{\n.reg .pred p;\nsetp.ne.b32 p, %1, 0;\n@p mbarrier.arrive.shared::cta.b64 _, [%0];\n}\n" ::"r"(bar), "r"((int)on) : "memory");
}
__device__ __forceinline__ void lds2_if(bool on, uint32_t p, uint32_t (&t)[8]) {
  asm volatile("{\n.reg .pred p;\nsetp.ne.b32 p, %9, 0;\n@p ld.shared.v4.b32 {%0, %1, %2, %3}, [%8];\n@p ld.shared.v4.b32 {%4, %5, %6, %7}, [%8 + 512];\n}\n"
               : "+r"(t[0]), "+r"(t[1]), "+r"(t[2]), "+r"(t[3]), "+r"(t[4]), "+r"(t[5]), "+r"(t[6]), "+r"(t[7]) : "r"(p), "r"((int)on) : "memory");
}
__device__ __forceinline__ void lds128(uint32_t p, uint32_t& a, uint32_t& b, uint32_t& c, uint32_t& d) {
  asm volatile("ld.shared.v4.b32 {%0, %1, %2, %3}, [%4];" : "=r"(a), "=r"(b), "=r"(c), "=r"(d) : "r"(p) : "memory");
}
template <class T> __device__ __forceinline__ T* ptr_add(T* base, uint32_t bytes) {
  T* r;
  asm("{\n.reg .u32 lo, hi;\nmov.b64 {lo, hi}, %1;\nadd.cc.u32 lo, lo, %2;\naddc.u32 hi, hi, 0;\nmov.b64 %0, {lo, hi};\n}\n" : "=l"(r) : "l"(base), "r"(bytes));
  return r;
}
__device__ __forceinline__ uint32_t lds32(uint32_t p) {
  uint32_t v;
  asm volatile("ld.volatile.shared.u32 %0, [%1];" : "=r"(v) : "r"(p) : "memory");
  return v;
}
__device__ __forceinline__ uint32_t flag_get(const unsigned int* p) {
  uint32_t v;
  asm volatile("ld.acquire.gpu.global.u32 %0, [%1];" : "=r"(v) : "l"(p) : "memory");
  return v;
}
__device__ __forceinline__ uint32_t wait_word(uint32_t p, uint32_t target) {
  uint32_t v;
  asm volatile("{\n.reg .pred p;\n.reg .u32 n;\nmov.u32 n, 0;\n"
               "LOOP:\nld.acquire.cta.shared.u32 %0, [%1];\nsetp.ge.u32 p, %0, %2;\n@p bra DONE;\n"
               "nanosleep.u32 %3;\nadd.u32 n, n, 1;\nsetp.lt.u32 p, n, 0x400000;\n@p bra LOOP;\ntrap;\n"
               "DONE:\n}\n" : "=r"(v) : "r"(p), "r"(target), "n"(400) : "memory");
  return v;
}
__device__ __forceinline__ void flag_set(unsigned int* p, uint32_t v) {
  asm volatile("st.release.gpu.global.u32 [%0], %1;" ::"l"(p), "r"(v) : "memory");
}
__device__ __forceinline__ void flag_dec(unsigned int* p) {
  asm volatile("red.relaxed.gpu.global.add.u32 [%0], 0xffffffff;" ::"l"(p) : "memory");
}

struct Cursor {
  uint32_t n;
  __device__ __forceinline__ uint32_t off() const { return n & (8 * NBAR - 8); }
  __device__ __forceinline__ uint32_t ph() const { return (n / (8 * NBAR)) & 1; }
  __device__ __forceinline__ void next() { n += 8; }
};

constexpr float kScaleLog2 = 0.07216878364870322f * 1.4426950408889634f;
constexpr float kSumLimit = 1048576.0f;

__global__ void __cluster_dims__(2, 1, 1) __launch_bounds__(384, 1)
fused_kernel(const __grid_constant__ Params P) {
  extern __shared__ uint8_t smem_raw[];
  const uint32_t sbase = (smem_u32(smem_raw) + 1023) & ~1023u;
  const uint32_t full0 = sbase + RING, empty0 = full0 + 8 * NBAR, odone0 = empty0 + 8 * NBAR, ev0 = odone0 + 8 * MAX_OPS;
  const uint32_t progress = ev0 + 8 * MAX_EV, jobw = progress + 4;
  const uint32_t rank = blockIdx.x & 1;
  const int role = blockIdx.x >> 1;
  const int wid = __shfl_sync(0xffffffffu, (int)(threadIdx.x >> 5), 0);
  const int wg = wid >> 2;

  if (wid < 8) {
    if (elect()) {
#pragma unroll
      for (int j = 0; j < 16; j++) {
        const int i = EARLY + 16 * wid + j;
        if (i < 2 * NBAR + MAX_OPS + MAX_EV) mbar_init(full0 + 8 * i, i < NBAR ? 1 : i < 2 * NBAR ? 16 : i < 2 * NBAR + MAX_OPS ? 8 : 1);
      }
      if (wid == 7) asm volatile("st.shared.v2.u32 [%0], {0, 0};\nfence.acq_rel.cta;" ::"r"(progress) : "memory");
      asm volatile("fence.mbarrier_init.release.cluster;" ::: "memory");
    }
  } else if (wid > 8) {
    const uint32_t g = blockIdx.x * 96 + threadIdx.x - 288, w = g - 2048;
    if (g < 4096) asm volatile("prefetch.global.L2 [%0];" ::"l"(g < 2048 ? P.xw[0] + g * (kD * 2) : P.xw[1] + (w >> 5) * (kHD * 2) + (w & 31) * 128));
  } else {
    const uint32_t op0 = P.first[role];
    if (elect()) {
#pragma unroll
      for (int k = 0; k < EARLY; k++) mbar_init(full0 + 8 * k, 1);
      asm volatile("fence.mbarrier_init.release.cluster;" ::: "memory");
      const int blk = (op0 >> 10) & 1;
      if ((op0 & 3) == OP_Q) {
#pragma unroll
        for (int k = 0; k < EARLY; k++) {
          mbar_expect(full0 + 8 * k, SZ_Q);
          tma2d(sbase + k * SZ_Q, &P.x[blk], full0 + 8 * k, 64 * k, ((op0 >> 7) & 7) * kSq + rank * 128);
          tma3d(sbase + k * SZ_Q + 16384, &P.wq[blk], full0 + 8 * k, 0, 64 * k, 3 * ((op0 >> 2) & 31));
          tma3d(sbase + k * SZ_Q + 28672, &P.wq[blk], full0 + 8 * k, 0, 64 * k + 32, 3 * ((op0 >> 2) & 31));
        }
      }
      asm volatile("prefetch.tensormap [%0];\nprefetch.tensormap [%1];" ::"l"(&P.k[blk]), "l"(&P.v[blk]) : "memory");
    }
  }
  __syncwarp();
  asm volatile("barrier.cluster.arrive.relaxed.aligned;\nbarrier.cluster.wait.aligned;" ::: "memory");

  if (wg < 2) {
    asm volatile("setmaxnreg.inc.sync.aligned.u32 240;");
    const uint32_t* prog = P.prog[role].c;
    const int wid = __shfl_sync(0xffffffffu, (int)(threadIdx.x >> 5), 1), wg = wid >> 2;
    const int lane = threadIdx.x & 31, warp = wid & 3;
    uint32_t empty_rem;
    asm volatile("mapa.shared::cluster.u32 %0, %1, %2;" : "=r"(empty_rem) : "r"(empty0), "r"(lane & 1));
    uint32_t keep = (threadIdx.x & 127) < 2 ? 4 : 0;
    auto release = [&](int slot) { mbar_arrive_cluster_n(keep, empty_rem + slot); };
    auto release_warp = [&](int slot, bool on = true) { mbar_arrive_cluster_if(lane < 2 && on, empty_rem + slot); };
    Cursor r{0};
    const uint32_t ring16 = (sbase & 0x3FFFF) >> 4;
    uint32_t cur = ring16;
    bool rdy0 = false, rdy1 = false;
    auto probe1 = [&]() { rdy0 = mbar_test(full0 + r.off(), r.ph()); };
    auto probe2 = [&]() {
      Cursor n = r;
      rdy0 = mbar_test(full0 + n.off(), n.ph());
      n.next();
      rdy1 = mbar_test(full0 + n.off(), n.ph());
    };
    auto advance = [&](uint32_t bytes, uint32_t& addr) {
      const int bi = r.off();
      r.next();
      if (cur > ring16 + ((RING - bytes) >> 4)) cur = ring16;
      addr = cur;
      cur += bytes >> 4;
      return bi;
    };
    auto take = [&](bool rdy, uint32_t bytes, uint32_t& addr) {
      if (__builtin_expect(!__all_sync(0xffffffffu, rdy), 0)) mbar_wait(full0 + r.off(), r.ph());
      return advance(bytes, addr);
    };
    const bool never = P.dbg == 0xffffffffu;
    uint32_t q[48];
#pragma unroll
    for (int i = 0; i < 48; i++) q[i] = 0;
    const int row = wg * 64 + warp * 16 + (lane >> 2);
    const int img0 = row * 4 + ((lane & 3) ^ ((row >> 1) & 3));
    uint4* pend = nullptr;
    bool pend_any = false;
    const uint64_t spol = evict_first();
    int pc = 0;
    auto slab = [&](int c, int i0) {
#pragma unroll
      for (int i = i0; i < 6; i++)
        stg2_if(c == i, pend + i * 512, q[8 * i], q[8 * i + 1], q[8 * i + 2], q[8 * i + 3],
                q[8 * i + 4], q[8 * i + 5], q[8 * i + 6], q[8 * i + 7], spol);
    };
    auto drain = [&](int c) {
      if (!pend_any || c >= 6) return;
      slab(c, 0);
      if (c == 5) {
        __syncwarp();
        mbar_arrive_if(lane == 0, odone0 - 8 + 8 * pc);
      }
    };

    for (;; pc++) {
      uint32_t op = prog[pc];
      const int type = op & 3;
      auto enter = [&]() {
        r.n = (op >> 12) & 248; cur = ring16 + (((op >> 20) & 63) << 8);
      };
      enter();
      pend_any = op & C_PEND;
      uint32_t job = 0;
      if ((op & (3 | C_WIDE)) == OP_O) job = __shfl_sync(0xffffffffu, wait_word(jobw, 1), 0);
      if (type == OP_END || job == OP_O) {
#pragma unroll 1
        for (int c = 0; c < 6; c++) drain(c);
        asm volatile("barrier.cluster.arrive.relaxed;" ::: "memory");
        break;
      }
      {
        float s[32], o[96];
        uint32_t ad0;
        int bi0, sk1;
        uint32_t pa[16], pb[16];
        float mc0, mc1, l0, l1;
        bool shifted;
        uint32_t nop;
        auto expo = [&](float (&s)[32], uint32_t (&pout)[16], float& b0, float& b1, bool shift, auto mid) {
          float c0, c1;
#pragma unroll
          for (int i = 0; i < 8; i++) {
            const float e0 = ex2(shift ? s[4 * i] - mc0 : s[4 * i]), e1 = ex2(shift ? s[4 * i + 1] - mc0 : s[4 * i + 1]);
            const float e2 = ex2(shift ? s[4 * i + 2] - mc1 : s[4 * i + 2]), e3 = ex2(shift ? s[4 * i + 3] - mc1 : s[4 * i + 3]);
            if (i) { b0 += e0; c0 += e1; b1 += e2; c1 += e3; } else { b0 = e0; c0 = e1; b1 = e2; c1 = e3; }
            pout[2 * i] = pack_bf16(e0, e1); pout[2 * i + 1] = pack_bf16(e2, e3);
            if (i & 1) mid(i >> 1);
          }
          b0 += c0; b1 += c1;
        };
        auto rowmax = [&](float (&s)[32], float& m0, float& m1) {
          m0 = fmaxf(s[0], s[1]); m1 = fmaxf(s[2], s[3]);
#pragma unroll
          for (int i = 1; i < 8; i++) { m0 = fmaxf(m0, fmaxf(s[4 * i], s[4 * i + 1])); m1 = fmaxf(m1, fmaxf(s[4 * i + 2], s[4 * i + 3])); }
          m0 = fmaxf(m0, __shfl_xor_sync(0xffffffffu, m0, 1)); m1 = fmaxf(m1, __shfl_xor_sync(0xffffffffu, m1, 1));
          m0 = fmaxf(m0, __shfl_xor_sync(0xffffffffu, m0, 2)); m1 = fmaxf(m1, __shfl_xor_sync(0xffffffffu, m1, 2));
        };
        auto first = [&](float (&s)[32], int sk0, auto mid) {
          fence_regs(s);
          release(sk0);
          mc0 = 0.f; mc1 = 0.f;
          expo(s, pa, l0, l1, false, mid);
          shifted = __any_sync(0xffffffffu, !(fmaxf(l0, l1) <= kSumLimit && fminf(l0, l1) >= 1.f / kSumLimit));
          if (shifted) {
            rowmax(s, mc0, mc1);
            expo(s, pa, l0, l1, true, [](int) {});
          }
        };
        auto qk = [&](float (&s)[32], uint32_t ak, int k0 = 0, int k1 = 12) {
#pragma unroll
          for (int kk = k0; kk < k1; kk++)
            wgmma_rs_n64<0>(s, q[4 * kk], q[4 * kk + 1], q[4 * kk + 2], q[4 * kk + 3], mk_desc(ak, 16, KV_SBO, 1) + ((kk >> 2) * KV_CH + (kk & 3) * 2), kk != 0);
          if (k1 == 12) wg_commit();
        };
        auto pv = [&](uint32_t (&pin)[16], uint32_t av, int acc, int k0 = 0, int k1 = 4) {
#pragma unroll
          for (int kk = k0; kk < k1; kk++)
            wgmma_rs_n192<1>(o, pin[4 * kk], pin[4 * kk + 1], pin[4 * kk + 2], pin[4 * kk + 3], mk_desc(av, KV_CH * 16, KV_SBO, 1) + (kk * (KV_SBO / 8)), acc || (kk != 0));
          if (k0 == 0) wg_commit();
        };
        auto finish = [&](uint32_t (&pout)[16], int sk, int sv, bool part = false) {
          probe1();
          wg_wait<1>();
          fence_regs(s);
          release(sk);
          float b0, b1;
#pragma unroll 1
          for (bool redo = false;; redo = true) {
            expo(s, pout, b0, b1, false, [](int) {});
            if (!__any_sync(0xffffffffu, !redo && (shifted || !(fmaxf(b0, b1) <= kSumLimit)))) break;
            shifted = true;
            rowmax(s, b0, b1);
            b0 = fmaxf(mc0, b0); b1 = fmaxf(mc1, b1);
            const float a0 = ex2(mc0 - b0), a1 = ex2(mc1 - b1);
            mc0 = b0; mc1 = b1;
            l0 *= a0; l1 *= a1;
            wg_wait<0>();
            fence_regs(o);
#pragma unroll
            for (int i = 0; i < 24; i++) { o[4 * i] *= a0; o[4 * i + 1] *= a0; o[4 * i + 2] *= a1; o[4 * i + 3] *= a1; }
#pragma unroll
            for (int i = 0; i < 32; i++) s[i] -= (i & 2) ? mc1 : mc0;
            if (part) {
#pragma unroll
              for (int i = 8; i < 16; i++)
                pa[i] = pack_bf16(__uint_as_float(pa[i] << 16) * ((i & 1) ? a1 : a0), __uint_as_float(pa[i] & 0xffff0000u) * ((i & 1) ? a1 : a0));
            }
          }
          l0 += b0; l1 += b1;
          wg_wait<0>();
          fence_regs(o);
          mbar_arrive_cluster_n(part ? 0 : keep, empty_rem + sv);
        };
        uint32_t pav;
        int psv;
        auto step = [&](uint32_t (&pin)[16], uint32_t (&pout)[16], bool part) {
          uint32_t ak;
          const int sk = take(rdy0, SZ_KV, ak);
          psv = advance(SZ_KV, pav);
          wg_fence();
          qk(s, ak);
          if (part) { wg_fence(); pv(pin, pav, 1, 0, 2); } else { asm volatile(""); wg_fence(); pv(pin, pav, 1); }
          finish(pout, sk, psv, part);
        };
        auto unpark = [&](uint32_t& ak) {
          uint32_t ad;
          const Cursor k0 = r;
          const int sk0 = advance(SZ_KV, ak), bi = take(false, SZ_PARK, ad);
#pragma unroll
          for (int i = 0; i < 12; i++) lds128(sbase + (ad - ring16 + img0) * 16 + (i >> 1) * 8192 + (i & 1) * 512, q[4 * i], q[4 * i + 1], q[4 * i + 2], q[4 * i + 3]);
          if (!__all_sync(0xffffffffu, rdy0)) mbar_wait(full0 + k0.off(), k0.ph());
          fence_regs(q);
          release_warp(bi);
          wg_fence();
          qk(s, ak, 0, 4);
          wg_commit();
          return sk0;
        };
        auto mma4 = [&](uint32_t ad, int acc) {
#pragma unroll
          for (int kk = 0; kk < 4; kk++)
            wgmma_ss_n192<1>(o, mk_desc(ad + wg * 512, 16, 1024, 1) + (kk * 2), mk_desc(ad, 4096, 1024, 1) + (1024 + (kk >> 1) * 768 + (kk & 1) * 128), acc || kk != 0);
        };
        auto convert = [&](int i0, int i1) {
          sched_fence(keep, never);
#pragma unroll
          for (int i = i0; i < i1; i++) {
            q[i] = pack_bf16(o[2 * i] * kScaleLog2, o[2 * i + 1] * kScaleLog2);
            if ((i & 7) == 7 && i != i1 - 1) sched_fence(keep, never);
          }
          sched_fence(keep, never);
        };
        if (type == OP_O) {
          int prev = 0;
          if (op & C_WIDE) {
            float d[64];
            auto mma3 = [&](uint32_t ad, int h, int acc) {
#pragma unroll
              for (int kk = 0; kk < 2; kk++)
                wgmma_ss_n192<1>(o, mk_desc(ad + wg * 256, 16, 512, 2) + (h * 512 + kk * 2), mk_desc(ad, 4096, 1024, 1) + (1024 + h * 768 + kk * 128), acc || kk);
            };
            auto mma2 = [&](uint32_t ad, uint32_t ob, int h, int acc) {
#pragma unroll
              for (int kk = 0; kk < 2; kk++)
                wgmma_ss_n128<1>(d, mk_desc(ad + wg * 256, 16, 512, 2) + (h * 512 + kk * 2), mk_desc(ad, 4096, 1024, 1) + (ob + h * 512 + kk * 128), acc || kk);
            };
            auto wstep = [&](uint32_t bytes, int acc, auto hook) {
              uint32_t ad;
              const int bi = take(rdy0, bytes, ad);
              wg_fence();
              if (bytes == SZ_W2) mma2(ad, 1024, 0, 1); else mma3(ad, 0, acc);
              if (bytes == SZ_W) mma3(ad, 1, 1);
              wg_commit();
              if (acc) { wg_wait<1>(); release(prev); }
              if (bytes == SZ_W) mma2(ad, 2560, 0, acc);
              if (bytes == SZ_W3) mma3(ad, 1, 1); else mma2(ad, bytes == SZ_W ? 2560 : 1024, 1, 1);
              wg_commit();
              prev = bi;
              hook();
              probe1();
              wg_wait<1>();
            };
            undefine(o);
            wstep(SZ_W, 0, [&]() { drain(0); });
#pragma unroll 1
            for (int k = 1; k < ((op >> 2) & 127) - TAIL; k++) wstep(SZ_W, 1, [&]() { drain(k); });
#pragma unroll 1
            for (int k = 0; k < TAIL; k++) wstep(SZ_W2, 1, []() {});
            pend = ptr_add(P.g->part, (((op >> 9) & 31) * 2 + rank) * 81920 + 4 * 8192 + img0 * 16);
            wstep(SZ_W3, 1, [&]() {
              fence_regs(d);
#pragma unroll
              for (int i = 0; i < 32; i++) q[16 + i] = pack_bf16(d[2 * i], d[2 * i + 1]);
              slab(2, 2);
            });
#pragma unroll 1
            for (int k = 3; k < 6; k++) wstep(SZ_W3, 1, [&]() { slab(k, 2); });
            op = prog[pc + 1];
            enter();
            pend_any = true;
            pend -= 4 * 512;
            bi0 = take(rdy0 || (op & 3) != OP_Q, SZ_Q, ad0);
            sched_fence(keep, never);
            wg_wait<0>();
            fence_regs(o);
            release(prev);
#pragma unroll
            for (int i = 0; i < 48; i++) q[i] = pack_bf16(o[2 * i], o[2 * i + 1]);
            if ((op & 3) != OP_Q) continue;
            pc++;
            goto first_step;
          }
          float c[80];
          auto mma2 = [&](uint32_t ad, uint32_t oa, uint32_t ob, int acc) {
            wgmma_ss_n160<1>(c, mk_desc(ad + wg * 256, 16, 512, 2) + (oa), mk_desc(ad, 2048, 512, 2) + (1024 + ob), acc);
            wgmma_ss_n160<1>(c, mk_desc(ad + wg * 256, 16, 512, 2) + (oa + 2), mk_desc(ad, 2048, 512, 2) + (1024 + ob + 64), 1);
          };
          auto kstep = [&](int acc, auto hook, uint32_t bytes = SZ_O) {
            uint32_t ad;
            const int bi = take(rdy0, bytes, ad);
            wg_fence();
            mma2(ad, 0, 0, acc);
            wg_commit();
            if (acc) wg_wait<1>();
            if (acc == 1) release(prev);
            if (acc > 1) release_warp(prev, acc == 2 || wg == 0);
            mma2(ad, 512, 640, 1);
            wg_commit();
            prev = bi;
            hook();
            probe1();
            wg_wait<1>();
          };
          auto unblock = [&](int k) {
            if (__all_sync(0xffffffffu, rdy0) || __all_sync(0xffffffffu, mbar_try(full0 + r.off(), r.ph(), 1500))) return;
#pragma unroll 1
            for (; k < 6; k++) drain(k);
            pend_any = false;
          };
          unblock(0);
          kstep(0, [&]() { drain(0); });
          int left = ((job >> 13) & 127) - 6;
#pragma unroll 1
          for (uint32_t k = 1, pace = left >= 22 ? 0x4511 : left <= 11 ? 0x1a : 0x155; left > 0; pace >>= 2, left--) {
            unblock(k);
            kstep(1, [&]() {
#pragma unroll 1
              for (int i = pace & 3; i > 0; i--) drain(k++);
            });
          }
          uint32_t t[8], stage[3];
          float u[80];
          auto unpack = [&](int j) {
#pragma unroll
            for (int i = 0; i < 8; i++) {
              u[16 * j + 2 * i] = __uint_as_float(t[i] << 16); u[16 * j + 2 * i + 1] = __uint_as_float(t[i] & 0xffff0000u);
              asm volatile("" : "+f"(u[16 * j + 2 * i]), "+f"(u[16 * j + 2 * i + 1]));
            }
          };
#pragma unroll
          for (int i = 0; i < 8; i++) t[i] = 0;
          const uint32_t bytes = (job & P_LD) ? SZ_OL : SZ_O;
#pragma unroll
          for (int j = 0; j < 5; j++) {
            if (j == 2 && wg == 1) {
              wg_wait<0>();
              release_warp(prev);
              bar_sync(1, 256);
            }
            kstep(j == 2 ? 3 : 2, [&]() {
              if (j == 4) asm volatile("{\n.reg .pred p;\nsetp.eq.u32 p, %0, 0;\n@p bar.arrive 1, 256;\n}\n" ::"r"(wg) : "memory");
              if (j) unpack(j - 1);
              lds2_if(job & P_LD, sbase + (cur - ring16 + img0) * 16 - 8192, t);
              if (j >= 1 && j <= 3) stage[j - 1] = sbase + (cur - ring16) * 16 - bytes + wid * 1024;
            }, bytes);
          }
          unpack(4);
          uint32_t lane16 = (lane & 15) * 64;
          const int orow = ((job >> 7) & 7) * kSq + rank * 128 + wid * 16, ocol = ((job >> 10) & 1) * 20 + ((job >> 20) & 3) * 5;
          sched_fence(lane16, never);
          wg_wait<0>();
          fence_regs(c);
          release_warp(prev);
          asm volatile("barrier.cluster.arrive.relaxed;" ::: "memory");
#pragma unroll
          for (int i = 0; i < 10; i++) {
            const int v = (i & 1) * 2 + (lane >> 4);
            const uint32_t sa = stage[i >> 2] + (i & 2) * 4096;
            stsm4(sa + lane16 + ((v ^ ((lane >> 1) & 3)) << 4), pack_bf16(c[8 * i] + u[8 * i], c[8 * i + 1] + u[8 * i + 1]),
                  pack_bf16(c[8 * i + 2] + u[8 * i + 2], c[8 * i + 3] + u[8 * i + 3]), pack_bf16(c[8 * i + 4] + u[8 * i + 4], c[8 * i + 5] + u[8 * i + 5]),
                  pack_bf16(c[8 * i + 6] + u[8 * i + 6], c[8 * i + 7] + u[8 * i + 7]));
            if (i != 3 && i != 9) continue;
            asm volatile("fence.proxy.async.shared::cta;" ::: "memory");
            __syncwarp();
            if (elect()) {
#pragma unroll
              for (int j = i == 3 ? 0 : 2; 2 * j < i; j++) tma3d_store(&P.out, stage[j >> 1] + (j & 1) * 8192, 0, orow, ocol + j);
            }
            if (i == 3) sched_fence(lane16, never);
          }
          if (elect()) asm volatile("cp.async.bulk.commit_group;\ncp.async.bulk.wait_group.read 0;" ::: "memory");
          __syncwarp();
          break;
        }
        bi0 = take(rdy0, SZ_Q, ad0);
      first_step:
        undefine(o);
        wg_fence();
        mma4(ad0, 0);
        wg_commit();
        {
          uint32_t ad1;
          const int bi1 = take(false, SZ_Q, ad1);
          wg_fence();
          mma4(ad1, 1);
          wg_commit();
          drain(0);
          wg_wait<1>();
          release(bi0);
          drain(1);
          probe1();
          wg_wait<0>();
          release(bi1);
          fence_regs(o);
#pragma unroll 1
          for (int k = 2; k < 8; k++) {
            uint32_t ad;
            const int bi = take(rdy0, SZ_Q, ad);
            wg_fence();
            mma4(ad, 1);
            wg_commit();
            drain((0x54732710u >> (4 * k)) & 7);
            probe1();
            wg_wait<0>();
            release(bi);
          }
          uint32_t a8, a9, ak0, ak1;
          const int b8 = take(rdy0, SZ_Q, a8), b9 = take(false, SZ_Q, a9);
          wg_fence();
          mma4(a8, 1);
          wg_commit();
          mma4(a9, 1);
          wg_commit();
          wg_wait<1>();
          release(b8);
          probe1();
          const int sk0 = take(rdy0 || (op & F_PARK), SZ_KV, ak0);
          wg_wait<0>();
          fence_regs(o);
          release(b9);
          float s0[32];
          convert(0, 32);
          if (op & F_PARK) {
            convert(32, 48);
            pend = ptr_add(P.g->tile, (((op >> 2) & 511) * 2 + rank) * SZ_PARK + img0 * 16);
            continue;
          }
          pc++;
          wg_fence();
          qk(s0, ak0, 0, 4);
          convert(32, 48);
          wg_fence();
          qk(s0, ak0, 4, 12);
          sk1 = take(false, SZ_KV, ak1);
          wg_fence();
          qk(s, ak1, 0, 4);
          wg_commit();
          probe1();
          wg_wait<1>();
          first(s0, sk0, [&](int i) {
            if (!(i & 1)) return;
            sched_fence(keep, never);
            wg_fence();
            if (i == 1) qk(s, ak1, 4, 8);
            if (i == 3) qk(s, ak1, 8, 12);
            sched_fence(keep, never);
          });
        }
        for (;;) {
          {
            uint32_t av;
            const int sv = take(rdy0, SZ_KV, av);
            undefine(o);
            wg_fence();
            pv(pa, av, 0);
            finish(pb, sk1, sv);
          }
          nop = prog[pc + 1];
#pragma unroll 1
          for (int jj = 0; jj < 7; jj++) {
            step(pb, pa, false);
            step(pa, pb, jj == 6);
          }
          float i0, i1;
          auto last = [&]() {
            uint32_t av;
            const int sv = take(rdy0, SZ_KV, av);
            wg_fence();
            pv(pa, pav, 1, 2, 4);
            pv(pb, av, 1);
            sched_fence(keep, never);
            probe1();
            l0 += __shfl_xor_sync(0xffffffffu, l0, 1); l1 += __shfl_xor_sync(0xffffffffu, l1, 1);
            l0 += __shfl_xor_sync(0xffffffffu, l0, 2); l1 += __shfl_xor_sync(0xffffffffu, l1, 2);
            i0 = rcp(l0); i1 = rcp(l1);
            pend = ptr_add(P.g->tile, (((op >> 2) & 511) * 2 + rank) * SZ_PARK + img0 * 16);
            return sv;
          };
          auto normalise = [&](uint32_t (&d)[48], auto mid) {
#pragma unroll
            for (int i = 0; i < 24; i++) {
              d[8 * (i >> 2) + (i & 3)] = pack_bf16(o[4 * i] * i0, o[4 * i + 1] * i0);
              d[8 * (i >> 2) + (i & 3) + 4] = pack_bf16(o[4 * i + 2] * i1, o[4 * i + 3] * i1);
              if ((i & 1) && i != 23) sched_fence(keep, never);
              if ((i & 3) == 3 && i != 23) mid(i >> 2);
            }
          };
          const int sv = last();
          if ((nop & 3) != OP_A) {
            op = nop;
            enter();
            pend_any = true;
            bi0 = take(rdy0 || (nop & 3) != OP_Q, SZ_Q, ad0);
            sched_fence(keep, never);
            wg_wait<0>();
            fence_regs(o);
            release(psv);
            release(sv);
            normalise(q, [](int) {});
            undefine(o);
            if ((nop & 3) != OP_Q) break;
            pc++;
            goto first_step;
          }
          uint32_t ak0;
          const int sk0 = unpark(ak0);
          wg_wait<1>();
          fence_regs(o);
          release(psv);
          release(sv);
          uint32_t t[48];
          auto st = [&](int i) {
            stg2_if(true, pend + i * 512, t[8 * i], t[8 * i + 1], t[8 * i + 2], t[8 * i + 3], t[8 * i + 4], t[8 * i + 5], t[8 * i + 6], t[8 * i + 7], spol);
          };
          normalise(t, [&](int i) {
            if (i & 1) {
              wg_fence();
              if (i == 1) qk(s, ak0, 4, 8);
              if (i == 3) qk(s, ak0, 8, 12);
              sched_fence(keep, never);
            }
            if (!(i & 1)) st(i >> 1);
          });
          probe2();
          wg_wait<0>();
          first(s, sk0, [&](int i) { if (i < 3) { sched_fence(keep, never); st(3 + i); } });
          __syncwarp();
          mbar_arrive_if(lane == 0, odone0 + 8 * pc);
          pc++;
          op = nop;
          uint32_t ak1;
          sk1 = take(rdy0, SZ_KV, ak1);
          rdy0 = rdy1;
          wg_fence();
          qk(s, ak1);
        }
      }
    }
    asm volatile("barrier.cluster.wait;" ::: "memory");
  } else {
    asm volatile("setmaxnreg.dec.sync.aligned.u32 24;");
    const uint32_t* prog = P.prog[role].p;
    unsigned int* flag = P.g->flag + rank;
    if (wid == 11 && (prog[0] & 3) == OP_Q) {
      const uint32_t a = prog[1];
      const char* p = ptr_add(P.kv[rank * 2 + ((a >> 10) & 1)], ((a >> 2) & 255) * (kSk * kDh * 2) + (threadIdx.x & 31) * 128);
#pragma unroll 1
      for (uint32_t k = 0; k < 3; k++) {
        wait_word(progress, 8 * k);
        p += SZ_KV;
        asm volatile("prefetch.global.L2 [%0];\nprefetch.global.L2 [%0 + 4096];" ::"l"(p));
      }
      __syncwarp();
    }
    if (wid == 8) {
      Cursor head{0}, tail{0};
      int sh = 0, room = RING >> 12;
      uint32_t cur = 0;
      uint64_t fifo = 0;
      uint32_t dst, bar = 0, ev = ev0;
      const uint64_t pol = evict_first();
      auto retire = [&]() {
        mbar_wait(empty0 + tail.off(), tail.ph());
        tail.next();
        room += (uint32_t)fifo & 31;
        fifo >>= 5;
        sh -= 5;
        asm volatile("st.volatile.shared.u32 [%0], %1;" ::"r"(progress), "r"(tail.n) : "memory");
      };
      auto acquire = [&](uint32_t bytes) {
        uint32_t fp = bytes >> 12;
        if (cur + fp > (RING >> 12)) { fp += (RING >> 12) - cur; cur = 0; }
        room -= fp;
        while (room < 0) retire();
        fifo |= (uint64_t)fp << sh;
        sh += 5;
        dst = sbase + (cur << 12);
        bar = full0 + head.off();
        cur += bytes >> 12;
        head.next();
      };
      auto gate = [&]() {
        mbar_wait(ev, 0);
        ev += 8;
        asm volatile("fence.proxy.async.global;" ::: "memory");
      };
      for (int pc = 0;; pc++) {
        uint32_t op = prog[pc];
        const int type = op & 3;
        if (type == OP_END) break;
        if (op == OP_O) {
          gate();
          op = __shfl_sync(0xffffffffu, lds32(jobw), 0);
        }
        const int blk = (op >> 10) & 1;
        if (type == OP_Q) {
          const uint64_t px = (op & P_LASTX) ? pol : no_hint(), pw = (op & P_LASTW) ? pol : no_hint();
          int k = 0;
          if (pc == 0) {
            k = 64 * EARLY; head.n = 8 * EARLY; sh = 5 * EARLY; cur = EARLY * (SZ_Q >> 12); room -= cur;
            fifo = (SZ_Q >> 12) * (((1u << (5 * EARLY)) - 1) / 31);
          }
#pragma unroll 1
          for (int stop = (op & P_GATE) ? kD - 64 : kD;; stop = kD) {
#pragma unroll 1
            for (; k < stop; k += 64) {
              acquire(SZ_Q);
              if (elect()) {
                mbar_expect(bar, SZ_Q);
                tma3d_mc_hint(dst + 16384 + rank * 12288, &P.wq[blk], bar, k + 32 * rank, 3 * ((op >> 2) & 31), pw);
                tma2d_hint(dst, &P.x[blk], bar, k, ((op >> 7) & 7) * kSq + rank * 128, px);
              }
            }
            if (k == kD) break;
            gate();
          }
        } else if (type == OP_A) {
          const int row0 = ((op >> 2) & 255) * kSk;
          auto kv = [&](uint32_t tx, const CUtensorMap* m, int c3) {
            const uint32_t before = bar;
            acquire(SZ_KV);
            if (elect()) {
              mbar_expect(bar, tx);
              tma4d_mc_hint(dst + rank * (SZ_KV / 2), m, tx ? bar : before, c3, pol);
            }
          };
          int c3 = row0 / 8 + 4 * rank;
#pragma unroll 1
          for (int j = 0; j <= 16; j++, c3 += 8) {
            const uint32_t tv = j < 2 || j == 16 ? SZ_KV : 0;
            if (j < 16) kv(2 * SZ_KV - tv, &P.k[blk], c3);
            else if (op & P_GATE) gate();
            if (j > 0) kv(tv, &P.v[blk], c3 - 8);
            else if (op & F_PARK) {
              gate();
              acquire(SZ_PARK);
              if (elect()) {
                mbar_expect(bar, SZ_PARK);
                bulk_load_hint(dst, &P.g->tile[(((op >> 20) & 511) * 2 + rank) * 3072], SZ_PARK, bar, pol);
              }
            }
          }
        } else {
          const uint4* part = &P.g->part[((((op >> 6) & 30) + ((op >> 21) & 1)) * 2 + rank) * 5120 + ((op >> 20) & 1) * 2560];
          auto run = [&](const uint32_t bytes, int k, int cnt, int gates) {
            const int col = bytes == SZ_O || bytes == SZ_OL ? 5 * ((op >> 20) & 3) : 5 * ((op >> 21) & 1);
            int row = 8 * k + 4 * rank, pre = bytes == SZ_O && (op & P_PRE) ? 0 : 2560;
#pragma unroll 1
            for (int h = (k * 43) >> 7, k0 = k - 3 * h; cnt > 0; h++, k0 = 0, gates = gates >> 1 | (gates & 2)) {
              const uint4* src = ptr_add(P.g->tile, ((P.slot[((op >> 2) & 480) + h] * 2 + rank) * 3 + k0) * 16384);
              const uint64_t pw = h >= ((op >> 23) & 31) && h < 2 * (op >> 28) ? pol : no_hint();
              bool shut = bytes == SZ_OL && (gates & 1);
              uint32_t held = 0;
              int owed = 0;
              if ((gates & 1) && !shut) gate();
              int m = min(3 - k0, cnt);
              cnt -= m;
#pragma unroll 1
              for (; m > 0; m--, src += 1024, row += 8) {
                acquire(bytes);
                if (elect()) {
                  mbar_expect(bar, bytes);
                  if (bytes == SZ_O || bytes == SZ_OL) tma5d_mc_hint(dst + 16384 + rank * 10240, &P.wo[blk], bar, row, col, no_hint());
                  if (bytes == SZ_W || bytes == SZ_W3) tma5d_mc_hint(dst + 16384 + rank * 12288, &P.wo3[blk], bar, row, col, pw);
                  if (bytes != SZ_OL) bulk_load_hint(dst, src, 16384, bar, pol);
                  if (bytes == SZ_W || bytes == SZ_W2) tma5d_mc_hint(dst + bytes - 16384 + rank * 8192, &P.wo2[blk], bar, row, col + 3, pw);
                  if (bytes == SZ_OL) bulk_load_hint(dst + SZ_O, part, 8192, bar, pol);
                }
                if (bytes == SZ_OL) {
                  part += 512;
                  held = held << 8 | cur;
                  owed++;
                  if (shut && (m == 1 || __all_sync(0xffffffffu, mbar_test(ev, 0)))) { gate(); shut = false; }
#pragma unroll 1
                  for (; !shut && owed > 0; owed--)
                    if (elect()) bulk_load_hint(sbase + (((held >> (8 * owed - 8)) & 255) << 12) - bytes, src - (owed - 1) * 1024, 16384,
                                                full0 + ((head.n - 8 * owed) & (8 * NBAR - 8)), pol);
                }
              }
              if (pre < 2560) {
                if (elect()) asm volatile("cp.async.bulk.prefetch.L2.global [%0], 10240;" ::"l"(part + pre) : "memory");
                pre += 640;
              }
            }
          };
          const int n = (op >> 13) & 127;
          if (op & P_WIDE) {
            run(SZ_W, 0, n - TAIL, 3);
            run(SZ_W2, n - TAIL, TAIL, (n - TAIL) % 3 ? 2 : 3);
            run(SZ_W3, n - TAIL, TAIL, 0);
          } else {
            if (op & P_PRE) gate();
            run(SZ_O, kSteps - n, (op & P_LD) ? n - 5 : n, 3);
            if (op & P_LD) {
              if (!(op & P_PRE)) gate();
              run(SZ_OL, kSteps - 5, 5, 2);
            }
          }
        }
      }
#pragma unroll 1
      while (sh) retire();
    } else if (threadIdx.x == 288) {
      for (int pc = 0;; pc++) {
        const uint32_t op = prog[pc];
        const int type = op & 3;
        if (type == OP_END) break;
        if (type == OP_Q ? !(op & F_PARK) : type == OP_O && !(op & P_WIDE)) continue;
        const int id = type == OP_A ? (op >> 2) & 511 : type == OP_Q ? N_TILE + ((op >> 13) & 127) : ID_PART + ((op >> 5) & 60) + ((op >> 20) & 3);
        const uint32_t v = type == OP_O ? 1 : P.info[id] & 7;
        mbar_wait_long(odone0 + 8 * pc);
        flag_set(flag + 2 * id, v);
        if (type == OP_O && (op & P_WIDE)) flag_set(flag + 2 * id + 2, v);
      }
    } else if (wid == 10) {
      int i = threadIdx.x & 31;
      const int n_ev = P.prog[role].n_ev;
      auto event = [&]() { return i < n_ev ? P.prog[role].ev[i] : n_ev ? E_JOB | (i - n_ev) : 0; };
      uint32_t e = i < 8 ? event() : 0;
      for (uint32_t n = 0; __any_sync(0xffffffffu, e); n++) {
        uint32_t job = lds32(jobw);
        const int togo = (e & E_DRAW) ? (e & 1023) - (lds32(progress) >> 3) : 99;
        if (togo <= 0 && rank == 0) {
          job = P.job[atomicInc(&P.g->ticket, gridDim.x / 2 - 1)];
          asm volatile("{\n.reg .u32 a;\nmapa.shared::cluster.u32 a, %0, 1;\nst.volatile.shared::cluster.u32 [a], %1;\n"
                       "st.volatile.shared.u32 [%0], %1;\n}\n" ::"r"(jobw), "r"(job) : "memory");
        }
        if ((e & E_JOB) && job) {
          const uint32_t j = e & 63, heads = job == OP_O ? 0 : kH - ((job >> 2) & 31), jp = !(job & P_LD) ? 63 : (job & P_PRE) ? 0 : heads - 1, h = j - (j > jp);
          e = j == jp ? (ID_PART + ((job >> 5) & 60) + ((job >> 20) & 3)) | E_ON | E_LAST : h < heads ? (((job >> 2) & 511) + h) | E_ON | E_LAST : 0;
        }
        unsigned int* f = ptr_add(flag, 8 * (e & 1023));
        const bool ok = (e & E_ON) ? flag_get(f) - 1 < ((e & E_FREE) ? 1 : 7) : (e & E_DRAW) && job;
        if (ok) {
          mbar_arrive(ev0 + 8 * i);
          if (e & (E_FREE | E_LAST)) flag_dec(f);
          i += 8;
          e = event();
        }
        asm volatile("{\n.reg .pred p;\nsetp.ge.u32 p, %0, 0x400000;\n@p trap;\n}\n" ::"r"(n));
        if (!__any_sync(0xffffffffu, ok)) __nanosleep(__any_sync(0xffffffffu, job || togo <= 2) ? 100 : 600);
      }
    } else if (threadIdx.x == 352) {
      uint32_t items = 0;
      auto read = [&](int id) {
        if (!(P.info[id] & I_NEXT)) return;
        wait_word(progress, 8 * items);
        flag_dec(flag + 2 * id);
      };
      for (int pc = 0;; pc++) {
        const uint32_t op = prog[pc];
        const int type = op & 3;
        if (type == OP_END) break;
        if (type == OP_O) {
          const uint32_t n = (op >> 13) & 127, base = items;
#pragma unroll 1
          for (uint32_t k = 3, id = (op >> 2) & 511; k <= n; k += 3, id++) {
            items = base + k + (k + TAIL > n ? TAIL : 0);
            read(id);
          }
          items = base + n + TAIL;
        } else if (type == OP_A) {
          items++;
          if (op & F_PARK) { items++; read(N_TILE + ((op >> 13) & 127)); }
          items += 31;
        } else {
          items += 10;
        }
      }
    }
    __syncwarp();
    asm volatile("barrier.cluster.arrive.relaxed;\nbarrier.cluster.wait;" ::: "memory");
  }
}

typedef CUresult (*EncodeFn)(CUtensorMap*, CUtensorMapDataType, cuuint32_t, void*, const cuuint64_t*, const cuuint64_t*,
                             const cuuint32_t*, const cuuint32_t*, CUtensorMapInterleave, CUtensorMapSwizzle,
                             CUtensorMapL2promotion, CUtensorMapFloatOOBfill);

void encode(EncodeFn fn, CUtensorMap* m, const void* ptr, int rank, const cuuint64_t* dims, const cuuint64_t* strides,
            const cuuint32_t* box, CUtensorMapSwizzle swz) {
  const cuuint32_t es[5] = {1, 1, 1, 1, 1};
  CUresult r = fn(m, CU_TENSOR_MAP_DATA_TYPE_BFLOAT16, rank, const_cast<void*>(ptr), dims, strides, box, es,
                  CU_TENSOR_MAP_INTERLEAVE_NONE, swz, CU_TENSOR_MAP_L2_PROMOTION_L2_128B, CU_TENSOR_MAP_FLOAT_OOB_FILL_NONE);
  if (r != CUDA_SUCCESS) fprintf(stderr, "cuTensorMapEncodeTiled failed: %d\n", (int)r);
}

struct Op { int type, flags, id, n, quarter, park, item0, items; double t0, t1; };
struct Use { double need, freed; int readers, slot, prev; bool next; };
struct PlanStats { double end, slack, park_slack; int slots, parks; uint32_t own[N_CL]; };

bool plan(const char* const* text, int n_pair, int phase, Params& P, PlanStats* stats = nullptr) {
  constexpr double T_Q = 7900, T_A = 24550, T_U = 25900, T_P = 8400, T_O = 640, T_RUN = 800, T_WIDE = 1300, AHEAD = 3500, PUBLISH = 1500;
  const double margin = 256.0 * ((P.dbg >> 8) & 255);
  static Op op[N_CL][MAX_OPS];
  static Use use[ID_PART];
  int n_op[N_CL], covered[2 * N_TEAM] = {};
  struct Ref { double t; Op* o; int id; };
  static Ref att[N_TILE + 1], dem[N_TILE], prk[MAX_PARK + 1], unp[MAX_PARK + 1], wr[ID_PART];
  auto sort = [](Ref* r, int n) {
    for (int i = 1; i < n; i++)
      for (int j = i; j > 0 && r[j].t < r[j - 1].t; j--) { Ref x = r[j]; r[j] = r[j - 1]; r[j - 1] = x; }
  };
  auto hex = [](char c) { return c <= '9' ? c - '0' : c - 'a' + 10; };
  for (int i = 0; i < n_pair; i++)
    for (const char* s = text[i]; *s; s++)
      for (int h = 0; *s == 'J' && h < 2; h++) {
        if (covered[2 * hex(s[1]) + h]) return false;
        covered[2 * hex(s[1]) + h] = 10 * (s[2 + 2 * h] - '0') + s[3 + 2 * h] - '0';
      }
  for (int c = 0; c < 2 * n_pair; c++) {
    int n = 0, items = 0;
    double t = 0;
    auto add = [&](int type, int flags, int id, int heads, int quarter, int its, double dt) {
      if (n < MAX_OPS) op[c][n] = {type, flags, id, heads, quarter, 0, items, its, t, t + dt};
      n++; items += its; t += dt;
    };
    for (const char* s = text[c >> 1]; *s; s++) {
      const int tm = hex(s[1]) & 15, nj = covered[2 * tm + (c & 1)];
      if (*s == 'N') { add(OP_Q, 0, 0, 0, 0, 10, T_Q); add(OP_A, 0, 0, 0, 0, 32, T_A); }
      if (*s == 'P') add(OP_Q, F_PARK, 0, 0, 0, 10, T_P);
      if (*s == '+' || *s == '-') t += *s == '+' ? 1000 : -1000;
      if (*s == 'U') { if (n == 0 || n > MAX_OPS || op[c][n - 1].type != OP_A) return false; add(OP_A, F_PARK, 0, 0, 0, 33, T_U); }
      if (*s == 'J') { if (nj < TAIL + 6 || nj > kSteps - 11) return false; add(OP_O, P_WIDE, tm * kH, nj, 2 * (c & 1), nj + TAIL, 2 * T_O * nj + T_WIDE); }
    }
    add(OP_O, 0, 0, 0, 0, 0, 0);
    add(OP_END, 0, 0, 0, 0, 0, 0);
    if (n > MAX_OPS || op[c][0].type != OP_Q) return false;
    n_op[c] = n - 1;
    att[c] = {t, &op[c][n - 2], 0};
  }
  for (int i = 0; i < 4 * N_TEAM; i++) dem[i] = {(double)covered[i / 2], nullptr, i};
  sort(att, 2 * n_pair); sort(dem, 4 * N_TEAM);
  for (int i = 0; i < 4 * N_TEAM; i++) {
    Op* f = att[i].o;
    const int nj = covered[dem[i].id / 2];
    f->flags = nj ? P_LD : 0;
    f->id = dem[i].id / 4 * kH + nj / 3; f->quarter = dem[i].id & 3; f->items = f->n = kSteps - nj;
    f[1].t0 = f[1].t1 = f->t1 = f->t0 + T_O * f->n + T_RUN; f[1].item0 += f->n;
  }
  for (int i = 0; i < ID_PART; i++) use[i] = {1e18, 0, 0, 0, 0, false};
  int n_att = 0, n_prk = 0, n_unp = 0;
  auto ready = [&](const Op* o) {
    const int nt = o[1].type;
    return o->t1 + (nt == OP_Q ? 6100 : !o[1].n ? 1500 : (o[1].flags & P_WIDE) ? 7700 : 3900) + PUBLISH;
  };
  for (int c = 0; c < 2 * n_pair; c++)
    for (Op* o = op[c]; o->type != OP_END; o++) {
      if (o->type == OP_A) { att[n_att] = {ready(o), o, 0}; if (++n_att > N_TILE) return false; }
      if (o->type == OP_A && o->flags) { unp[n_unp] = {o->t0 - AHEAD, o, 0}; if (++n_unp > MAX_PARK) return false; }
      if (o->type == OP_Q && o->flags) { prk[n_prk] = {ready(o), o, 0}; if (++n_prk > MAX_PARK) return false; }
      for (int i = 0; o->type == OP_O && i < o->n; i++) {
        const int nw = (o->flags & P_WIDE) ? o->n - TAIL : 0, k = nw ? i : kSteps - o->n + i;
        Use& u = use[o->id / kH * kH + k / 3];
        const double t = o->t0 + T_O * (i + (i < nw ? i : nw));
        if (t - AHEAD < u.need) u.need = t - AHEAD;
        const double f = !nw ? 1e18 : i + FLIGHT < o->items - TAIL || (nw && o[1].type != OP_O) ? t + T_O * (i < nw ? 2 : 1 + TAIL) + PUBLISH : 1e18;
        if (f > u.freed) u.freed = f;
        if (i == 0 || k % 3 == 0) u.readers++;
      }
    }
  if (n_att != N_TILE || n_prk != n_unp) return false;
  for (int i = 0; i < N_TILE; i++) { const int id = (i & 15) * kH + (i >> 4); dem[i] = {use[id].need, nullptr, id}; }
  sort(att, n_att); sort(dem, N_TILE); sort(prk, n_prk); sort(unp, n_unp);
  PlanStats st = {0, 1e18, 1e18, 0, n_prk};
  int n_wr = 0;
  for (int i = 0; i < N_TILE; i++) {
    Op* o = att[i].o;
    o->id = dem[i].id;
    if (!o->flags) o[-1].id = o->id;
    if (dem[i].t - att[i].t < st.slack) st.slack = dem[i].t - att[i].t;
    wr[n_wr++] = {o->t1 - 2 * AHEAD, o, o->id};
  }
  for (int i = 0; i < n_prk; i++) {
    prk[i].o->id = unp[i].o->id;
    prk[i].o->park = unp[i].o->park = i;
    use[N_TILE + i].freed = unp[i].o->t0 + 2 * PUBLISH;
    use[N_TILE + i].readers = 1;
    if (unp[i].t - prk[i].t < st.park_slack) st.park_slack = unp[i].t - prk[i].t;
    wr[n_wr++] = {prk[i].o->t1 - 2 * AHEAD, prk[i].o, N_TILE + i};
  }
  for (int c = 0; c < 2 * n_pair; c++)
    for (int d = 0; d < 2 * n_pair; d++)
      for (Op *f = &op[c][n_op[c] - 1], *o = op[d]; f->n && o->type != OP_END; o++)
        if (o->type == OP_O && (o->flags & P_WIDE) && o->id / kH == f->id / kH && o->quarter / 2 == f->quarter / 2) {
          if (f->t0 - o->t1 > 4096.0 * ((P.dbg >> 16) & 255)) f->flags |= P_PRE;
          const double slack = f->t0 + ((f->flags & P_PRE) ? 0 : (f->n - 5) * T_O) - AHEAD - ready(o);
          if (slack < st.park_slack) st.park_slack = slack;
        }
  constexpr double long_while = 160000;
  for (int c = 0; c < 2 * n_pair; c++)
    for (Op* o = op[c]; o->type != OP_END; o++) {
      if (o->type == OP_O && (o->flags & P_WIDE)) {
        int run = 0, best = 0, end = 0;
        for (int h = 0; 3 * h < o->n; h++) {
          bool last = true;
          for (int d = 0; d < 2 * n_pair; d++)
            for (const Op* e = op[d]; e->type != OP_END; e++) {
              if (e->type != OP_O || e == o || ((e->id ^ o->id) & 256) || e->quarter / 2 != o->quarter / 2) continue;
              const bool wide = e->flags & P_WIDE;
              if (wide ? 3 * h >= e->n : 3 * h + 3 <= kSteps - e->n) continue;
              const double dt = e->t0 + T_O * (wide ? 6 * h : 3 * h - kSteps + e->n) - o->t0 - T_O * 6 * h + (d - c) * 1e-3;
              if (dt > 0 && dt < long_while) last = false;
            }
          run = last ? run + 1 : 0;
          if (run > best) { best = run; end = h + 1; }
        }
        const int from = end - best;
        if (3 * end >= o->n) end++;
        o->park = from | (end / 2) << 5;
      }
      if (o->type != OP_Q) continue;
      bool lw = true, lx = true;
      for (int d = 0; d < 2 * n_pair; d++)
        for (const Op* e = op[d]; e->type != OP_END; e++) {
          const double dt = e->t0 - o->t0 + (d - c) * 1e-3;
          if (e->type != OP_Q || e == o || dt < 0 || dt > long_while) continue;
          if (((e->id ^ o->id) & (256 + 31)) == 0) lw = false;
          if (e->id / kH == o->id / kH) lx = false;
        }
      o->quarter = (lw ? P_LASTW : 0) | (lx ? P_LASTX : 0);
    }
  sort(wr, n_wr);
  int holder[N_TILE];
  for (int i = 0; i < n_wr; i++) {
    int best = -1;
    for (int sl = 0; sl < st.slots; sl++)
      if (use[holder[sl]].freed + margin <= wr[i].t && (best < 0 || use[holder[sl]].freed < use[holder[best]].freed)) best = sl;
    Use& u = use[wr[i].id];
    if (best >= 0) { u.prev = holder[best]; use[u.prev].next = true; wr[i].o->flags |= P_GATE; }
    else if (st.slots == N_TILE) return false;
    else best = st.slots++;
    u.slot = best;
    holder[best] = wr[i].id;
  }
  {
    int pos[N_CL] = {}, flag[ID_PART + 4 * N_TEAM] = {}, seen[ID_PART] = {};
    auto goal = [&](int c) { return op[c][n_op[c] - 1].item0; };
    for (bool moved = true; moved;) {
      moved = false;
      for (int c = 0; c < 2 * n_pair; c++) {
        for (; pos[c] < goal(c); pos[c]++, moved = true) {
          bool ok = true;
          for (const Op* o = op[c]; o->type != OP_END; o++) {
            const int k = pos[c] - o->item0, own = o->type == OP_A ? o->id : N_TILE + (o->park & 127);
            if (k < 0 || k >= o->items) continue;
            if (o->type == OP_O) ok = k >= o->n || flag[o->id + k / 3];
            else if (k == o->items - 1 && (o->flags & P_GATE)) ok = seen[use[own].prev] == use[use[own].prev].readers;
            else if (k == 1 && o->type == OP_A && (o->flags & F_PARK)) ok = flag[N_TILE + o->park];
          }
          if (!ok) break;
          for (const Op* o = op[c]; o->type != OP_END; o++) {
            if (pos[c] == o->item0 + o->items + (o[1].type == OP_Q ? 7 : o[1].item0 == goal(c) ? -1 : 5)) {
              if (o->type == OP_A) flag[o->id] = 1;
              if (o->type == OP_Q && (o->flags & F_PARK)) flag[N_TILE + o->park] = 1;
              if (o->type == OP_O) flag[ID_PART + o->id / kH * 4 + o->quarter] = flag[ID_PART + o->id / kH * 4 + o->quarter + 1] = 1;
            }
            const int k = pos[c] - FLIGHT - o->item0, nw = o->n - TAIL;
            if (k == 1 && o->type == OP_A && (o->flags & F_PARK)) seen[N_TILE + o->park]++;
            if (o->type == OP_O && k >= 0 && k < o->items && (k < nw || k >= o->n) && (k < nw ? k : k - TAIL) % 3 == 2) seen[o->id + (k < nw ? k : k - TAIL) / 3]++;
          }
        }
      }
    }
    for (int c = 0; c < 2 * n_pair; c++) if (pos[c] < goal(c)) return false;
  }
  int n_job = 0, longest = 0;
  for (int i = 0; i < 2 * N_TEAM; i++) if (kH + 1 - covered[i] / 3 > longest) longest = kH + 1 - covered[i] / 3;
  for (int c = 0; c < 2 * n_pair; c++) {
    uint32_t items = 0, cur = 0, pend = 0;
    int n = 0, ev = 0;
    auto item = [&](uint32_t bytes, int count) {
      for (int i = 0; i < count; i++) { if (cur + bytes > RING) cur = 0; cur += bytes; items++; }
    };
    auto event = [&](uint32_t e) { if (ev < MAX_TAB) P.prog[c].ev[ev] = e; ev++; };
    for (const Op* o = op[c];; o++) {
      if (o->type != OP_END && phase && (o->type == OP_O) != (phase == 2)) continue;
      uint32_t cw = o->type | (items % (2 * NBAR)) << 15 | (cur >> 12) << 20 | pend, pw = o->type | o->id << 2 | o->flags;
      const int ps = use[N_TILE + (o->park & 127)].slot;
      pend = 0;
      if (o->type == OP_O) {
        pw |= o->n << 13 | o->quarter << 20 | (uint32_t)o->park << 23;
        if (o->flags & P_WIDE) {
          cw |= o->n << 2 | (o->id / kH * 2 + o->quarter / 2) << 9 | C_WIDE;
          item(SZ_W, o->n - TAIL);
          item(SZ_W2, TAIL);
          item(SZ_W3, TAIL);
          pend = C_PEND;
          for (int i = 0; 3 * i < o->n; i++) event((o->id + i) | E_ON | (use[o->id + i].next ? 0 : E_LAST));
        } else {
          dem[n_job++] = {o->t0 - 1e6 * o->n, nullptr, (int)pw};
          st.own[c] = pw;
          pw = OP_O;
          event(E_DRAW | (items < 16 ? 0 : items - 16));
        }
      } else if (o->type != OP_END) {
        const bool parks = o->type == OP_Q && (o->flags & F_PARK);
        cw |= (parks ? ps : use[o->id].slot) << 2 | (o->flags & F_PARK);
        if (o->flags & F_PARK) pw |= o->park << 13 | ps << 20;
        if (o->type == OP_Q) { item(SZ_Q, 10); pw |= o->quarter; }
        else { item(SZ_KV, 1); if (o->flags & F_PARK) { item(SZ_PARK, 1); event((N_TILE + o->park) | E_ON | (use[N_TILE + o->park].next ? 0 : E_LAST)); } item(SZ_KV, 31); }
        if (parks || o->type == OP_A) pend = C_PEND;
        if (o->flags & P_GATE) event(use[parks ? N_TILE + o->park : o->id].prev | E_ON | E_FREE);
      }
      P.prog[c].c[n] = cw; P.prog[c].p[n++] = pw;
      if (o->type == OP_END) { if (o->t0 > st.end) st.end = o->t0; break; }
    }
    if (ev > MAX_TAB || ev + longest > MAX_EV) return false;
    P.prog[c].n_ev = ev;
    while (n < MAX_OPS) { P.prog[c].c[n] = OP_END; P.prog[c].p[n++] = OP_END; }
    P.first[c] = (uint16_t)(P.prog[c].p[0] & 2047);
  }
  sort(dem, n_job);
  for (int i = 0; i < n_job; i++) P.job[i] = dem[i].id;
  for (int i = 0; i < ID_PART; i++) {
    if (i < N_TILE) P.slot[i] = use[i].slot;
    P.info[i] = (use[i].readers + use[i].next) | (use[i].next ? I_NEXT : 0);
  }
  if (stats) *stats = st;
  return true;
}

const char* const kPrograms[N_CL / 2] = {
  "PNJ06864NNNNN", "PNJ17778NNNNN", "PNJ26464NNNNN", "PNJ34148NNNNNN", "PNJ46262NNNNN", "PNJ58482NNNN",
  "NNJ67371NNNN", "PNNJ76666NNNN", "NUNNNJ84545NN", "NUNNNJ94444NN", "NNNUNNJa5551N", "NNNNNJb5959NN",
  "NNNNNJc5456NN", "PNNNNNJd5351NN", "NNNNNJe5253NN", "NNNNNJf7777N", "PNNNNNNNNN", "PNNNNNNNNN",
  "PNNNNNNNNN", "PNNNNNNNNN", "NNNNNNNNN", "NNNNNNNNN", "NNNNNNNNN", "NNNNNNNNN",
  "NNNNNNNNN", "N-NNNNNNNN", "NUNNNNNNN", "NUNNNNNNN", "NUNNNNNNN", "NUNNNUNNN",
  "NUNNNNNNN", "NUNNNNNNN", "NUUNNNNNN",
};

const char* const* bench_programs() {
  return kPrograms;
}

}

extern "C" void kernel_launch(void* const* d_in, const int* in_sizes, int n_in, void* d_out, int out_size) {
  (void)in_sizes; (void)n_in; (void)out_size;
  static EncodeFn fn = nullptr;
  static int n_clusters = 0;
  if (!fn) {
    cudaDriverEntryPointQueryResult qr;
    void* f = nullptr;
    cudaGetDriverEntryPoint("cuTensorMapEncodeTiled", &f, cudaEnableDefault, &qr);
    fn = (EncodeFn)f;
    cudaFuncSetAttribute(fused_kernel, cudaFuncAttributeMaxDynamicSharedMemorySize, SMEM_BYTES);
    cudaLaunchConfig_t cfg = {};
    cfg.gridDim = dim3(132); cfg.blockDim = dim3(384); cfg.dynamicSmemBytes = SMEM_BYTES;
    cudaLaunchAttribute at[1];
    at[0].id = cudaLaunchAttributeClusterDimension; at[0].val.clusterDim.x = 2; at[0].val.clusterDim.y = 1; at[0].val.clusterDim.z = 1;
    cfg.attrs = at; cfg.numAttrs = 1;
    if (cudaOccupancyMaxActiveClusters(&n_clusters, fused_kernel, &cfg) != cudaSuccess || n_clusters < 1) n_clusters = 1;
    (void)cudaGetLastError();
  }
  static Params P;
  const CUtensorMapSwizzle S128 = CU_TENSOR_MAP_SWIZZLE_128B, S64 = CU_TENSOR_MAP_SWIZZLE_64B;
  for (int blk = 0; blk < 2; blk++) {
    void* const* in = d_in + 5 * blk;
    { const cuuint64_t d[] = {kD, kB * kSq}, s[] = {kD * 2}; const cuuint32_t b[] = {64, 128};
      encode(fn, &P.x[blk], in[0], 2, d, s, b, S128); }
    { const cuuint64_t d[] = {64, 8, 3, (cuuint64_t)kB * kH * kSk / 8}, s[] = {kDh * 2, 128, 8 * kDh * 2}; const cuuint32_t b[] = {64, 8, 3, 4};
      encode(fn, &P.k[blk], in[1], 4, d, s, b, S128);
      encode(fn, &P.v[blk], in[2], 4, d, s, b, S128); }
    { const cuuint64_t d[] = {64, kD, kHD / 64}, s[] = {kHD * 2, 128}; const cuuint32_t b[] = {64, 32, 3};
      encode(fn, &P.wq[blk], in[3], 3, d, s, b, S128); }
    { const cuuint64_t d[] = {32, 2, kHD / 8, 4, kD / 32}, s[] = {kD * 2, 8 * kD * 2, 2 * kD * 2, 64}; const cuuint32_t b[] = {32, 2, 4, 4, 5};
      encode(fn, &P.wo[blk], in[4], 5, d, s, b, S64); }
    { const cuuint64_t d[] = {64, 2, kHD / 8, 4, kD / 64}, s[] = {kD * 2, 8 * kD * 2, 2 * kD * 2, 128};
      const cuuint32_t b3[] = {64, 2, 4, 4, 3}, b2[] = {64, 2, 4, 4, 2};
      encode(fn, &P.wo3[blk], in[4], 5, d, s, b3, S128);
      encode(fn, &P.wo2[blk], in[4], 5, d, s, b2, S128); }
  }
  { const cuuint64_t d[] = {32, kB * kSq, 2 * kD / 32}, s[] = {2 * kD * 2, 64}; const cuuint32_t b[] = {32, 16, 1};
    encode(fn, &P.out, d_out, 3, d, s, b, S64); }

  P.kv[0] = (const char*)d_in[1]; P.kv[1] = (const char*)d_in[6]; P.kv[2] = (const char*)d_in[2]; P.kv[3] = (const char*)d_in[7];
  P.xw[0] = (const char*)d_in[0]; P.xw[1] = (const char*)d_in[3];
  cudaGetSymbolAddress((void**)&P.g, g_scratch);
  P.dbg = DBG_DEFAULT;
  if (n_clusters >= N_CL && plan(bench_programs(), N_CL / 2, 0, P)) {
    fused_kernel<<<2 * N_CL, 384, SMEM_BYTES>>>(P);
  } else {
    const char* text[2 * N_TEAM];
    for (int i = 0; i < 2 * N_TEAM; i++) text[i] = "NNNNNNNN";
    for (int phase = 1; phase <= 2; phase++) {
      plan(text, 2 * N_TEAM, phase, P);
      fused_kernel<<<8 * N_TEAM, 384, SMEM_BYTES>>>(P);
    }
  }
}
```
